```python
import torch

def _softmax(x, axis=-1):
    return torch.softmax(x, dim=axis)
def _gelu(x):
    return torch.nn.functional.gelu(x, approximate="tanh")
def _silu(x):
    return torch.nn.functional.silu(x)
def _sigmoid(x):
    return torch.sigmoid(x)
def _layernorm(x, axis=-1, eps=1e-5):
    m = x.mean(dim=axis, keepdim=True)
    v = x.var(dim=axis, keepdim=True, unbiased=False)
    return (x - m) / torch.sqrt(v + eps)
def _scatter_add(tgt, idx, src, axis=0):
    return tgt.clone().index_add_(axis, idx, src)
def _segment_sum(src, seg, n):
    out = torch.zeros((n,) + src.shape[1:], dtype=src.dtype)
    return out.index_add_(0, seg, src)
def _pad(x, pw):
    flat = tuple(v for pair in reversed(pw) for v in pair)
    return torch.nn.functional.pad(x, flat)

kernel_name = 'recurrent_scan__sliding_local_dilated__glu_gated_geglu__prompt'

def setup_inputs():

    _w = (lambda a: (lambda t: t.to(torch.bfloat16) if t.is_floating_point() else t)(torch.as_tensor(a)))
    def _A_setup():
        B, S, D = 1, 2048, 1024
        return {
            "x": _w((lambda *s: torch.randn(*s, dtype=torch.bfloat16) * 0.05)(B, S, D)),
            "wqkv": _w((lambda *s: torch.randn(*s, dtype=torch.bfloat16) * 0.2)(D, 3 * D)),
            "wo": _w((lambda *s: torch.randn(*s, dtype=torch.bfloat16) * 0.2)(D, D)),
        }
    _A_in = _A_setup()

    def _B_setup():
        B, S, Dm, Df = 1, 2048, 1024, 3584
        return {
            "x": _w((lambda *s: torch.randn(*s, dtype=torch.bfloat16) * 0.05)(B, S, Dm)),
            "w_gate": _w((lambda *s: torch.randn(*s, dtype=torch.bfloat16) * 0.1)(Dm, Df) * (Dm ** -0.5)),
            "w_up": _w((lambda *s: torch.randn(*s, dtype=torch.bfloat16) * 0.1)(Dm, Df) * (Dm ** -0.5)),
            "w_down": _w((lambda *s: torch.randn(*s, dtype=torch.bfloat16) * 0.1)(Df, Dm) * (Df ** -0.5)),
        }
    _B_in = _B_setup()

    return {
        "A_x": _A_in["x"],
        "A_wqkv": _A_in["wqkv"],
        "A_wo": _A_in["wo"],
        "B_x": _B_in["x"],
        "B_w_gate": _B_in["w_gate"],
        "B_w_up": _B_in["w_up"],
        "B_w_down": _B_in["w_down"],
    }

def reference(A_x, A_wqkv, A_wo, B_x, B_w_gate, B_w_up, B_w_down):
    def _A_ref(x, wqkv, wo):
        B, S, D = x.shape
        H = 32; Dh = D // H
        W, dil = 8, 2
        qkv = (lambda x, *d: x.permute(*d))((x @ wqkv).reshape(B, S, 3, H, Dh), 2, 0, 3, 1, 4)
        q, k, v = qkv[0], qkv[1], qkv[2]
        scale = Dh ** -0.5
        pos = torch.arange(S)
        off = torch.arange(W) * dil
        idx = pos[:, None] - off[None, :]
        mask = idx >= 0
        idx_c = torch.where(mask, idx, 0).reshape(-1)
        kg = k[:, :, idx_c, :].reshape(B, H, S, W, Dh)
        vg = v[:, :, idx_c, :].reshape(B, H, S, W, Dh)
        logits = torch.einsum("bhsd,bhswd->bhsw", q, kg) * scale
        logits = torch.where(mask[None, None, :, :], logits, -1e9)
        attn = _softmax(logits, axis=-1)
        o = torch.einsum("bhsw,bhswd->bhsd", attn, vg)
        return (lambda x, *d: x.permute(*d))(o, 0, 2, 1, 3).reshape(B, S, D) @ wo

    def _B_ref(x, w_gate, w_up, w_down):
        g = torch.einsum("bsd,df->bsf", x, w_gate)
        u = torch.einsum("bsd,df->bsf", x, w_up)
        h = _gelu(g) * u
        return torch.einsum("bsf,fd->bsd", h, w_down)

    x = A_x
    xn = _layernorm(x, axis=-1)
    s = _A_ref(xn, A_wqkv, A_wo)
    g = _silu(_B_ref(xn, B_w_gate, B_w_up, B_w_down))
    return x + s * g
```

```cpp
#include <cuda_runtime.h>
#include <cuda_bf16.h>
#include <cuda.h>
#include <stdint.h>

namespace {

constexpr int SEQ = 2048, DM = 1024, DF = 3584, K2 = DM + DF, NQKV = 3 * DM;
constexpr int NCTA = 128;
constexpr int G1_STAGES = 4, G1_STAGE_BYTES = 49152, G1_KSTEPS = 16, G1_TILES = 5;
constexpr int G2_STAGES = 7, G2_STAGE_BYTES = 32768, G2_KSTEPS = 72;
constexpr int A_BYTES = 16384;
constexpr int BAR_OFF = G2_STAGES * G2_STAGE_BYTES;
constexpr int SMEM_BYTES = BAR_OFF + 1024 + 256;
constexpr int G1_SKEW = 2, G2_SKEW = 4;
constexpr int CONSUMER_REGS = 216, AUX_REGS = 72;

enum { F_LN = 0, F_QKV = 1, F_EARLY = 2, F_LATE = 3 };
constexpr unsigned CNT_LN = 64, CNT_QKV = 12, CNT_EARLY = 20 + 16, CNT_LATE = 8;

__device__ __align__(1024) __nv_bfloat16 g_xn[SEQ * DM];
__device__ __align__(1024) __nv_bfloat16 g_qkv[SEQ * NQKV];
__device__ __align__(1024) __nv_bfloat16 g_a2[SEQ * K2];
__device__ __align__(128) unsigned g_flags[4 * 16 * 32];
__device__ __align__(128) unsigned g_epoch[NCTA * 8];

#define TRACE(slot) do {} while (0)
#define TRACE_GT(slot) do {} while (0)

__device__ __forceinline__ uint32_t smem_u32(const void* p) { return (uint32_t)__cvta_generic_to_shared(p); }
__device__ __forceinline__ void mbar_init(uint32_t bar, uint32_t cnt) {
    asm volatile("mbarrier.init.shared::cta.b64 [%0], %1;" :: "r"(bar), "r"(cnt) : "memory");
}
__device__ __forceinline__ void mbar_expect_tx(uint32_t bar, uint32_t bytes) {
    asm volatile("mbarrier.arrive.expect_tx.shared::cta.b64 _, [%0], %1;" :: "r"(bar), "r"(bytes) : "memory");
}
__device__ __forceinline__ void mbar_arrive(uint32_t bar) {
    asm volatile("mbarrier.arrive.shared::cta.b64 _, [%0];" :: "r"(bar) : "memory");
}
__device__ __forceinline__ void mbar_arrive_cluster(uint32_t bar, uint32_t cta) {
    asm volatile("{\n.reg .b32 ra;\nmapa.shared::cluster.u32 ra, %0, %1;\nmbarrier.arrive.shared::cluster.b64 _, [ra];\n}"
                 :: "r"(bar), "r"(cta) : "memory");
}
__device__ __forceinline__ bool mbar_try_wait(uint32_t bar, uint32_t parity) {
    uint32_t ok;
    asm volatile("{\n.reg .pred p;\nmbarrier.try_wait.parity.shared::cta.b64 p, [%1], %2;\nselp.u32 %0, 1, 0, p;\n}"
                 : "=r"(ok) : "r"(bar), "r"(parity) : "memory");
    return ok;
}
__device__ __forceinline__ void mbar_wait(uint32_t bar, uint32_t parity) {
    int spins = 0;
    while (!mbar_try_wait(bar, parity)) { if (++spins > (1 << 17)) break; }
}
__device__ __forceinline__ void flag_wait(const unsigned* p, unsigned target) {
    for (int spins = 0; spins < (1 << 19); spins++) {
        unsigned v;
        asm volatile("ld.acquire.gpu.global.u32 %0, [%1];" : "=r"(v) : "l"(p) : "memory");
        if ((int)(v - target) >= 0) break;
    }
}
__device__ __forceinline__ void flag_add(unsigned* p) {
    asm volatile("red.release.gpu.global.add.u32 [%0], 1;" :: "l"(p) : "memory");
}
__device__ __forceinline__ void fence_proxy_async_global() { asm volatile("fence.proxy.async.global;" ::: "memory"); }

__device__ __forceinline__ void tma_2d(uint32_t dst, const CUtensorMap* m, uint32_t bar, int c0, int c1) {
    asm volatile("cp.async.bulk.tensor.2d.shared::cluster.global.mbarrier::complete_tx::bytes [%0], [%1, {%3, %4}], [%2];"
                 :: "r"(dst), "l"(m), "r"(bar), "r"(c0), "r"(c1) : "memory");
}
__device__ __forceinline__ void tma_3d_mc(uint32_t dst, const CUtensorMap* m, uint32_t bar, int c1, int c2) {
    asm volatile("cp.async.bulk.tensor.3d.shared::cluster.global.mbarrier::complete_tx::bytes.multicast::cluster"
                 " [%0], [%1, {%3, %4, %5}], [%2], %6;"
                 :: "r"(dst), "l"(m), "r"(bar), "r"(0), "r"(c1), "r"(c2), "h"((uint16_t)3) : "memory");
}
__device__ __forceinline__ void tma_5d_mc(uint32_t dst, const CUtensorMap* m, uint32_t bar, int c0, int c4) {
    asm volatile("cp.async.bulk.tensor.5d.shared::cluster.global.mbarrier::complete_tx::bytes.multicast::cluster"
                 " [%0], [%1, {%3, %4, %4, %4, %5}], [%2], %6;"
                 :: "r"(dst), "l"(m), "r"(bar), "r"(c0), "r"(0), "r"(c4), "h"((uint16_t)3) : "memory");
}
__device__ __forceinline__ void tma_store_2d(const CUtensorMap* m, uint32_t src, int c0, int c1) {
    asm volatile("cp.async.bulk.tensor.2d.global.shared::cta.bulk_group [%0, {%2, %3}], [%1];"
                 :: "l"(m), "r"(src), "r"(c0), "r"(c1) : "memory");
}
__device__ __forceinline__ void prefetch_map(const CUtensorMap* m) {
    asm volatile("prefetch.tensormap [%0];" :: "l"(m) : "memory");
}
__device__ __forceinline__ void wg_fence() { asm volatile("wgmma.fence.sync.aligned;" ::: "memory"); }
__device__ __forceinline__ void wg_commit() { asm volatile("wgmma.commit_group.sync.aligned;" ::: "memory"); }
template <int N> __device__ __forceinline__ void wg_wait() { asm volatile("wgmma.wait_group.sync.aligned %0;" :: "n"(N) : "memory"); }

__device__ __forceinline__ uint64_t desc_a(uint32_t addr) {
    return (uint64_t)((addr & 0x3FFFF) >> 4) | (1ull << 16) | (64ull << 32) | (1ull << 62);
}
__device__ __forceinline__ uint64_t desc_b(uint32_t addr) {
    return (uint64_t)((addr & 0x3FFFF) >> 4) | (512ull << 16) | (64ull << 32) | (1ull << 62);
}

#define R8(d, o) "+f"(d[o]), "+f"(d[o+1]), "+f"(d[o+2]), "+f"(d[o+3]), "+f"(d[o+4]), "+f"(d[o+5]), "+f"(d[o+6]), "+f"(d[o+7])
#define R32(d, o) R8(d, o), R8(d, o+8), R8(d, o+16), R8(d, o+24)
#define R64(d, o) R32(d, o), R32(d, o+32)

__device__ __forceinline__ void wgmma_n256(float (&d)[128], uint64_t da, uint64_t db, int scale_d) {
    asm volatile("{\n.reg .pred p;\nsetp.ne.b32 p, %130, 0;\n"
        "wgmma.mma_async.sync.aligned.m64n256k16.f32.bf16.bf16 "
        "{%0,%1,%2,%3,%4,%5,%6,%7,%8,%9,%10,%11,%12,%13,%14,%15,%16,%17,%18,%19,%20,%21,%22,%23,%24,%25,%26,%27,%28,%29,%30,%31,"
        "%32,%33,%34,%35,%36,%37,%38,%39,%40,%41,%42,%43,%44,%45,%46,%47,%48,%49,%50,%51,%52,%53,%54,%55,%56,%57,%58,%59,%60,%61,%62,%63,"
        "%64,%65,%66,%67,%68,%69,%70,%71,%72,%73,%74,%75,%76,%77,%78,%79,%80,%81,%82,%83,%84,%85,%86,%87,%88,%89,%90,%91,%92,%93,%94,%95,"
        "%96,%97,%98,%99,%100,%101,%102,%103,%104,%105,%106,%107,%108,%109,%110,%111,%112,%113,%114,%115,%116,%117,%118,%119,%120,%121,%122,%123,%124,%125,%126,%127},"
        " %128, %129, p, 1, 1, 0, 1;\n}"
        : R64(d, 0), R64(d, 64) : "l"(da), "l"(db), "r"(scale_d));
}
__device__ __forceinline__ void wgmma_n128(float (&d)[64], uint64_t da, uint64_t db, int scale_d) {
    asm volatile("{\n.reg .pred p;\nsetp.ne.b32 p, %66, 0;\n"
        "wgmma.mma_async.sync.aligned.m64n128k16.f32.bf16.bf16 "
        "{%0,%1,%2,%3,%4,%5,%6,%7,%8,%9,%10,%11,%12,%13,%14,%15,%16,%17,%18,%19,%20,%21,%22,%23,%24,%25,%26,%27,%28,%29,%30,%31,"
        "%32,%33,%34,%35,%36,%37,%38,%39,%40,%41,%42,%43,%44,%45,%46,%47,%48,%49,%50,%51,%52,%53,%54,%55,%56,%57,%58,%59,%60,%61,%62,%63},"
        " %64, %65, p, 1, 1, 0, 1;\n}"
        : R64(d, 0) : "l"(da), "l"(db), "r"(scale_d));
}

__device__ __forceinline__ uint32_t pack_bf16(float lo, float hi) {
    uint32_t r; asm("cvt.rn.bf16x2.f32 %0, %1, %2;" : "=r"(r) : "f"(hi), "f"(lo)); return r;
}
__device__ __forceinline__ float bf_lo(uint32_t v) { return __uint_as_float(v << 16); }
__device__ __forceinline__ float bf_hi(uint32_t v) { return __uint_as_float(v & 0xffff0000u); }
__device__ __forceinline__ float round_bf16(float v) { return bf_lo(pack_bf16(v, 0.f)); }
__device__ __forceinline__ uint32_t mul_bf16x2(uint32_t a, uint32_t b) {
    uint32_t r; asm("mul.rn.bf16x2 %0, %1, %2;" : "=r"(r) : "r"(a), "r"(b)); return r;
}
__device__ __forceinline__ uint32_t add_bf16x2(uint32_t a, uint32_t b) {
    uint32_t r; asm("add.rn.bf16x2 %0, %1, %2;" : "=r"(r) : "r"(a), "r"(b)); return r;
}
__device__ __forceinline__ uint32_t sub_bf16x2(uint32_t a, uint32_t b) {
    uint32_t r; asm("sub.rn.bf16x2 %0, %1, %2;" : "=r"(r) : "r"(a), "r"(b)); return r;
}
__device__ __forceinline__ float tanh_fast(float x) { float r; asm("tanh.approx.f32 %0, %1;" : "=f"(r) : "f"(x)); return r; }
__device__ __forceinline__ float gelu_tanh(float g) {
    float t = fmaf(g * g, 0.044715f * 0.7978845608f, 0.7978845608f) * g;
    float hg = 0.5f * g;
    return fmaf(hg, tanh_fast(t), hg);
}
__device__ __forceinline__ uint32_t geglu2(uint32_t g2, uint32_t u2) {
    return mul_bf16x2(pack_bf16(gelu_tanh(bf_lo(g2)), gelu_tanh(bf_hi(g2))), u2);
}
__device__ __forceinline__ float silu(float d) {
    float hd = 0.5f * d;
    return fmaf(hd, tanh_fast(hd), hd);
}
__device__ __forceinline__ void mma_16816(float (&c)[4], uint32_t a0, uint32_t a1, uint32_t a2, uint32_t a3, uint32_t b0, uint32_t b1) {
    asm volatile("mma.sync.aligned.m16n8k16.row.col.f32.bf16.bf16.f32 {%0,%1,%2,%3}, {%4,%5,%6,%7}, {%8,%9}, {%0,%1,%2,%3};"
                 : "+f"(c[0]), "+f"(c[1]), "+f"(c[2]), "+f"(c[3]) : "r"(a0), "r"(a1), "r"(a2), "r"(a3), "r"(b0), "r"(b1));
}
__device__ __forceinline__ void mma_1688(float (&c)[4], uint32_t a0, uint32_t a1, uint32_t b0) {
    asm volatile("mma.sync.aligned.m16n8k8.row.col.f32.bf16.bf16.f32 {%0,%1,%2,%3}, {%4,%5}, {%6}, {%0,%1,%2,%3};"
                 : "+f"(c[0]), "+f"(c[1]), "+f"(c[2]), "+f"(c[3]) : "r"(a0), "r"(a1), "r"(b0));
}
__device__ __forceinline__ uint32_t movm(uint32_t a) {
    uint32_t d; asm volatile("movmatrix.sync.aligned.m8n8.trans.b16 %0, %1;" : "=r"(d) : "r"(a)); return d;
}
__device__ __forceinline__ uint4 movm4(uint4 v) { return make_uint4(movm(v.x), movm(v.y), movm(v.z), movm(v.w)); }

__device__ __forceinline__ uint32_t window_softmax(float l0, float l1) {
    float m = fmaxf(l0, l1);
    m = fmaxf(m, __shfl_xor_sync(0xffffffffu, m, 1));
    m = fmaxf(m, __shfl_xor_sync(0xffffffffu, m, 2));
    float e0 = exp2f((l0 - m) * 1.4426950408889634f), e1 = exp2f((l1 - m) * 1.4426950408889634f);
    float s = e0 + e1;
    s += __shfl_xor_sync(0xffffffffu, s, 1);
    s += __shfl_xor_sync(0xffffffffu, s, 2);
    float r = __frcp_rn(s);
    return pack_bf16(e0 * r, e1 * r);
}
__device__ __forceinline__ float logit(float dot) { return round_bf16(round_bf16(dot) * 0.17677669529663687f); }

__device__ __forceinline__ void attention_head(int mblk, int head, int par, int lane) {
    const int g = lane >> 2, t = lane & 3;
    const __nv_bfloat16* base = g_qkv + head * 32 + t * 8;
    const int row0 = mblk * 128 + par + 2 * g;
    const int hrow = row0 >= 16 ? row0 - 16 : 0;
    auto ld = [&](int row, int part) { return __ldcg(reinterpret_cast<const uint4*>(base + (size_t)row * NQKV + part * DM)); };
    uint4 k0 = ld(hrow, 1), v0 = ld(hrow, 2);
    uint4 qa = ld(row0, 0), qb = ld(row0 + 16, 0), k1 = ld(row0, 1), k2 = ld(row0 + 16, 1);
    v0 = movm4(v0);
    const bool up0 = 2 * t > g, up1 = 2 * t + 1 > g;
    const uint32_t keep = (up0 ? 0x0000ffffu : 0u) | (up1 ? 0xffff0000u : 0u);
#pragma unroll 1
    for (int sp = 0; sp < 4; sp++) {
        const int row = row0 + sp * 32;
        uint4 v1 = ld(row, 2), v2 = ld(row + 16, 2);
        float s0[4] = {0.f, 0.f, 0.f, 0.f}, s1[4] = {0.f, 0.f, 0.f, 0.f}, s2[4] = {0.f, 0.f, 0.f, 0.f};
        mma_16816(s0, qa.x, qb.x, qa.y, qb.y, k0.x, k0.y); mma_16816(s0, qa.z, qb.z, qa.w, qb.w, k0.z, k0.w);
        mma_16816(s1, qa.x, qb.x, qa.y, qb.y, k1.x, k1.y); mma_16816(s1, qa.z, qb.z, qa.w, qb.w, k1.z, k1.w);
        mma_16816(s2, qa.x, qb.x, qa.y, qb.y, k2.x, k2.y); mma_16816(s2, qa.z, qb.z, qa.w, qb.w, k2.z, k2.w);
        k0 = k2;
        if (sp < 3) { qa = ld(row + 32, 0); qb = ld(row + 48, 0); k1 = ld(row + 32, 1); k2 = ld(row + 48, 1); }
        const bool masked = (mblk | sp) == 0;
        float la0 = up0 ? (masked ? -1e9f : logit(s0[0])) : logit(s1[0]);
        float la1 = up1 ? (masked ? -1e9f : logit(s0[1])) : logit(s1[1]);
        float lb0 = logit(up0 ? s1[2] : s2[2]);
        float lb1 = logit(up1 ? s1[3] : s2[3]);
        const uint32_t pa = window_softmax(la0, la1), pb = window_softmax(lb0, lb1);
        v1 = movm4(v1); v2 = movm4(v2);
        const uint32_t a0 = pa & keep, a2 = pa & ~keep, a3 = pb & keep, a5 = pb & ~keep;
        float o0[4] = {0.f, 0.f, 0.f, 0.f}, o1[4] = {0.f, 0.f, 0.f, 0.f}, o2[4] = {0.f, 0.f, 0.f, 0.f}, o3[4] = {0.f, 0.f, 0.f, 0.f};
        mma_16816(o0, a0, 0u, a2, a3, v0.x, v1.x); mma_1688(o0, 0u, a5, v2.x);
        mma_16816(o1, a0, 0u, a2, a3, v0.y, v1.y); mma_1688(o1, 0u, a5, v2.y);
        mma_16816(o2, a0, 0u, a2, a3, v0.z, v1.z); mma_1688(o2, 0u, a5, v2.z);
        mma_16816(o3, a0, 0u, a2, a3, v0.w, v1.w); mma_1688(o3, 0u, a5, v2.w);
        v0 = v2;
        __nv_bfloat16* op = g_a2 + (size_t)row * K2 + head * 32 + t * 8;
        *reinterpret_cast<uint4*>(op) = make_uint4(pack_bf16(o0[0], o0[1]), pack_bf16(o1[0], o1[1]), pack_bf16(o2[0], o2[1]), pack_bf16(o3[0], o3[1]));
        *reinterpret_cast<uint4*>(op + (size_t)16 * K2) = make_uint4(pack_bf16(o0[2], o0[3]), pack_bf16(o1[2], o1[3]), pack_bf16(o2[2], o2[3]), pack_bf16(o3[2], o3[3]));
    }
}

__device__ __forceinline__ void layernorm_row(const uint4 (&v)[4], __nv_bfloat16* dst) {
    const uint32_t* w = reinterpret_cast<const uint32_t*>(v);
    float sum = 0.f;
#pragma unroll
    for (int i = 0; i < 16; i++) sum += bf_lo(w[i]) + bf_hi(w[i]);
#pragma unroll
    for (int o = 16; o > 0; o >>= 1) sum += __shfl_xor_sync(0xffffffffu, sum, o);
    const float mean = sum * (1.f / DM);
    float sq = 0.f;
#pragma unroll
    for (int i = 0; i < 16; i++) {
        float a = bf_lo(w[i]) - mean, b = bf_hi(w[i]) - mean;
        sq = fmaf(a, a, sq); sq = fmaf(b, b, sq);
    }
#pragma unroll
    for (int o = 16; o > 0; o >>= 1) sq += __shfl_xor_sync(0xffffffffu, sq, o);
    const float var = round_bf16(sq * (1.f / DM));
    const float inv = 1.f / round_bf16(sqrtf(round_bf16(var + 1e-5f)));
    const uint32_t m2 = pack_bf16(mean, mean);
#pragma unroll
    for (int i = 0; i < 4; i++) {
        uint32_t o[4];
#pragma unroll
        for (int j = 0; j < 4; j++) {
            uint32_t c = sub_bf16x2(w[i * 4 + j], m2);
            o[j] = pack_bf16(bf_lo(c) * inv, bf_hi(c) * inv);
        }
        *reinterpret_cast<uint4*>(dst + i * 256) = make_uint4(o[0], o[1], o[2], o[3]);
    }
}

struct Maps { CUtensorMap xn, wqkv, wg, wu, a2, wo, wd, x, out; };

__global__ void __cluster_dims__(2, 1, 1) __launch_bounds__(384, 1)
fused_kernel(const __grid_constant__ Maps maps, const __nv_bfloat16* __restrict__ x) {
    extern __shared__ __align__(1024) uint8_t smem_raw[];
    const uint32_t base = (smem_u32(smem_raw) + 1023) & ~1023u;
    const uint32_t bars = base + BAR_OFF;
    auto full1 = [&](int s) { return bars + s * 8; };
    auto empty1 = [&](int s) { return bars + 32 + s * 8; };
    auto full2 = [&](int s) { return bars + 64 + s * 8; };
    auto empty2 = [&](int s) { return bars + 128 + s * 8; };
    const uint32_t sig_bar = bars + 192;
    auto stage2 = [&](int q) { return base + (q == 0 ? 6 : q - 1) * G2_STAGE_BYTES; };

    const int warp = __shfl_sync(0xffffffffu, threadIdx.x >> 5, 0);
    const int lane = threadIdx.x & 31;
    const int rank = blockIdx.x & 1;
    const int mblk = ((blockIdx.x >> 1) & 7) * 2 + rank;
    const int nslot = blockIdx.x >> 4;
    unsigned* const flags = g_flags + mblk * 32;

    if (warp >= 8) {
        if (warp == 8) {
            if (lane == 0) {
                TRACE_GT(0); TRACE(1);
                prefetch_map(&maps.wqkv); prefetch_map(&maps.xn);
                for (int s = 0; s < G1_STAGES; s++) { mbar_init(full1(s), 1); mbar_init(empty1(s), 4); }
                for (int s = 0; s < G2_STAGES; s++) { mbar_init(full2(s), 1); mbar_init(empty2(s), 4); }
                mbar_init(sig_bar, 8);
                asm volatile("fence.mbarrier_init.release.cluster;" ::: "memory");
            }
            __syncwarp();
        }
        asm volatile("barrier.cluster.arrive.relaxed.aligned;" ::: "memory");
        const unsigned epoch = __ldcg(g_epoch + blockIdx.x * 8) + 1;
        asm volatile("setmaxnreg.dec.sync.aligned.u32 %0;" :: "n"(AUX_REGS));
        asm volatile("barrier.cluster.wait.acquire.aligned;" ::: "memory");

        if (warp == 8) {
            if (lane == 0) {
                TRACE(2);
                auto load_b1 = [&](int s, int ntile, int k) {
                    const uint32_t dst = base + s * G1_STAGE_BYTES + A_BYTES + rank * 16384;
                    if (ntile < 12) tma_3d_mc(dst, &maps.wqkv, full1(s), k * 64, ntile * 4 + rank * 2);
                    else tma_3d_mc(dst, rank ? &maps.wu : &maps.wg, full1(s), k * 64, (ntile - 12) * 2);
                };
                for (int s = 0; s < G1_STAGES; s++) { mbar_expect_tx(full1(s), G1_STAGE_BYTES); load_b1(s, nslot, s); }
                prefetch_map(rank ? &maps.wu : &maps.wg); prefetch_map(&maps.a2); prefetch_map(&maps.wo);
                prefetch_map(&maps.wd); prefetch_map(&maps.x); prefetch_map(&maps.out);
                flag_wait(flags + F_LN * 512, epoch * CNT_LN);
                fence_proxy_async_global();
                TRACE(3);
                for (int s = 0; s < G1_STAGES; s++) tma_2d(base + s * G1_STAGE_BYTES, &maps.xn, full1(s), s * 64, mblk * 128);
                uint32_t ph = 0;
                for (int it = G1_STAGES; it < G1_TILES * G1_KSTEPS; it++) {
                    const int s = it & 3, k = it & 15, ntile = (it >> 4) * 8 + nslot;
                    mbar_wait(empty1(s), ph);
                    mbar_expect_tx(full1(s), G1_STAGE_BYTES);
                    tma_2d(base + s * G1_STAGE_BYTES, &maps.xn, full1(s), k * 64, mblk * 128);
                    load_b1(s, ntile, k);
                    if (s == 3) ph ^= 1;
                }
                TRACE(4);
                flag_wait(flags + F_EARLY * 512, epoch * CNT_EARLY);
                fence_proxy_async_global();
                TRACE(5);
                int q = 0; uint32_t ph2 = 1;
                for (int u = 0; u < G2_KSTEPS; u++) {
                    if (u < G2_STAGES) {
                        if (u == 1) mbar_wait(empty1(0), ph);
                        if (u == 2) mbar_wait(empty1(1), ph);
                        if (u == 4) mbar_wait(empty1(2), ph);
                        if (u == 5) mbar_wait(empty1(3), ph);
                    } else {
                        mbar_wait(empty2(q), ph2);
                    }
                    if (u == 56) { TRACE(6); flag_wait(flags + F_LATE * 512, epoch * CNT_LATE); fence_proxy_async_global(); TRACE(7); }
                    const uint32_t sa = stage2(q);
                    mbar_expect_tx(full2(q), G2_STAGE_BYTES);
                    tma_2d(sa, &maps.a2, full2(q), u * 64, mblk * 128);
                    tma_5d_mc(sa + A_BYTES + rank * 8192, u < 16 ? &maps.wo : &maps.wd, full2(q),
                              nslot * 128 + rank * 64, (u < 16 ? u : u - 16) * 2);
                    if (++q == G2_STAGES) { q = 0; ph2 ^= 1; }
                }
                mbar_wait(empty2(q), ph2);
                mbar_expect_tx(full2(q), G2_STAGE_BYTES);
                tma_2d(stage2(q), &maps.x, full2(q), nslot * 128, mblk * 128);
                tma_2d(stage2(q) + 16384, &maps.x, full2(q), nslot * 128 + 64, mblk * 128);
                g_epoch[blockIdx.x * 8] = epoch;
                TRACE(8);
            }
        } else if (warp == 9) {
            if (lane == 0) {
                for (int t = 0; t < G1_TILES; t++) {
                    mbar_wait(sig_bar, t & 1);
                    const int ntile = t * 8 + nslot;
                    flag_add(flags + (ntile < 12 ? F_QKV : (t < 4 ? F_EARLY : F_LATE)) * 512);
                }
            }
        } else {
            if (lane == 0) {
                flag_wait(flags + F_QKV * 512, epoch * CNT_QKV);
                if (mblk > 0) flag_wait(flags - 32 + F_QKV * 512, epoch * CNT_QKV);
                if (warp == 10) TRACE(9);
            }
            __syncwarp();
#pragma unroll 1
            for (int i = 0; i < 4; i++) attention_head(mblk, nslot * 4 + (warp - 10) * 2 + (i >> 1), i & 1, lane);
            __syncwarp();
            if (lane == 0) { flag_add(flags + F_EARLY * 512); if (warp == 10) TRACE(10); }
        }
    } else {
        {
            const int r = mblk * 128 + nslot * 16 + warp * 2;
            const uint4* xp = reinterpret_cast<const uint4*>(x + (size_t)r * DM) + lane;
            uint4 va[4], vb[4];
#pragma unroll
            for (int i = 0; i < 4; i++) { va[i] = __ldg(xp + i * 32); vb[i] = __ldg(xp + 128 + i * 32); }
            asm volatile("barrier.cluster.arrive.relaxed.aligned;" ::: "memory");
            layernorm_row(va, g_xn + (size_t)r * DM + lane * 8);
            if (threadIdx.x == 0) TRACE(34);
            layernorm_row(vb, g_xn + (size_t)(r + 1) * DM + lane * 8);
            if (threadIdx.x == 0) TRACE(35);
            __syncwarp();
            if (lane == 0) flag_add(flags + F_LN * 512);
        }
        if (threadIdx.x == 0) TRACE(11);
        asm volatile("setmaxnreg.inc.sync.aligned.u32 %0;" :: "n"(CONSUMER_REGS));
        asm volatile("barrier.cluster.wait.acquire.aligned;" ::: "memory");

        const int wg = warp >> 2;
        const int tid = threadIdx.x & 127;
        float acc[128];
        uint32_t pk[64];
#pragma unroll
        for (int i = 0; i < 64; i++) asm volatile("mov.b32 %0, 0;" : "=r"(pk[i]));
#pragma unroll
        for (int i = 0; i < 128; i++) asm volatile("mov.b32 %0, 0;" : "=f"(acc[i]));

        const int orow = mblk * 128 + warp * 16 + (lane >> 2);
        __nv_bfloat16* optr = nullptr;
        auto release = [&](uint32_t bar) { if (tid < 2) mbar_arrive_cluster(bar, tid); };
        auto chunk_geglu = [&](int j) {
            const int c = j >> 1, h = j & 1;
            uint4 v;
            v.x = geglu2(pk[8 * c + h], pk[32 + 8 * c + h]);
            v.y = geglu2(pk[8 * c + 2 + h], pk[32 + 8 * c + 2 + h]);
            v.z = geglu2(pk[8 * c + 4 + h], pk[32 + 8 * c + 4 + h]);
            v.w = geglu2(pk[8 * c + 6 + h], pk[32 + 8 * c + 6 + h]);
            *reinterpret_cast<uint4*>(optr + h * 8 * K2 + c * 32) = v;
        };
        auto chunk_qkv = [&](int c) {
            *reinterpret_cast<uint4*>(optr + c * 32) = make_uint4(pk[8 * c], pk[8 * c + 2], pk[8 * c + 4], pk[8 * c + 6]);
            *reinterpret_cast<uint4*>(optr + 8 * NQKV + c * 32) = make_uint4(pk[8 * c + 1], pk[8 * c + 3], pk[8 * c + 5], pk[8 * c + 7]);
        };
        auto signal_stores = [&]() { __syncwarp(); if (lane == 0) mbar_arrive(sig_bar); };

        int pending = 0;
#pragma unroll 1
        for (int t = 0; t < G1_TILES; t++) {
#pragma unroll
            for (int k = 0; k < G1_KSTEPS; k++) {
                const int s = k & 3;
                mbar_wait(full1(s), (k >> 2) & 1);
                if (t == 0 && k == 0 && threadIdx.x == 0) TRACE(12);
                if (wg == 1 && k == G1_KSTEPS - G1_SKEW) asm volatile("bar.sync 1, 256;" ::: "memory");
                const uint64_t da = desc_a(base + s * G1_STAGE_BYTES + wg * 8192);
                const uint64_t db = desc_b(base + s * G1_STAGE_BYTES + A_BYTES);
                wg_fence();
#pragma unroll
                for (int kk = 0; kk < 4; kk++) wgmma_n256(acc, da + kk * 2, db + kk * 128, (k | kk) != 0);
                wg_commit();
                if (wg == 0 && k == G1_KSTEPS - 1) asm volatile("bar.arrive 1, 256;" ::: "memory");
                if (k >= 1 && k <= 8) {
                    if (pending == 2) chunk_geglu(k - 1);
                    else if (pending == 1) chunk_qkv(k - 1);
                    if (k == 8 && pending) signal_stores();
                }
                wg_wait<1>();
                if (k > 0) release(empty1((k - 1) & 3));
            }
            wg_wait<0>();
            release(empty1(3));
#pragma unroll
            for (int i = 0; i < 64; i++) pk[i] = pack_bf16(acc[2 * i], acc[2 * i + 1]);
            const int ntile = t * 8 + nslot;
            pending = ntile < 12 ? 1 : 2;
            optr = ntile < 12 ? g_qkv + (size_t)orow * NQKV + ntile * 256 + (lane & 3) * 8
                              : g_a2 + (size_t)orow * K2 + DM + (ntile - 12) * 128 + (lane & 3) * 8;
            if (tid == 0) TRACE(16 + wg * 8 + t);
        }

        float accs[64], accd[64];
#pragma unroll
        for (int i = 0; i < 64; i++) { accs[i] = 0.f; accd[i] = 0.f; }
#pragma unroll
        for (int u = 0; u < 17; u++) {
            const int q = u % G2_STAGES;
            mbar_wait(full2(q), (u / G2_STAGES) & 1);
            const uint64_t da = desc_a(stage2(q) + wg * 8192), db = desc_b(stage2(q) + A_BYTES);
            wg_fence();
#pragma unroll
            for (int kk = 0; kk < 4; kk++) {
                if (u < 16) wgmma_n128(accs, da + kk * 2, db + kk * 128, (u | kk) != 0);
                else wgmma_n128(accd, da + kk * 2, db + kk * 128, kk != 0);
            }
            wg_commit();
            if (u >= 1 && u <= 8) { chunk_geglu(u - 1); if (u == 8) signal_stores(); }
            wg_wait<1>();
            if (u > 0) release(empty2((u - 1) % G2_STAGES));
        }
        if (tid == 0) TRACE(16 + wg * 8 + 5);
        {
            int q = 17 % G2_STAGES, qp = 16 % G2_STAGES; uint32_t ph = (17 / G2_STAGES) & 1;
#pragma unroll 1
            for (int u = 17; u < G2_KSTEPS; u++) {
                mbar_wait(full2(q), ph);
                if (wg == 1 && u == G2_KSTEPS - G2_SKEW) asm volatile("bar.sync 1, 256;" ::: "memory");
                const uint64_t da = desc_a(stage2(q) + wg * 8192), db = desc_b(stage2(q) + A_BYTES);
                wg_fence();
#pragma unroll
                for (int kk = 0; kk < 4; kk++) wgmma_n128(accd, da + kk * 2, db + kk * 128, 1);
                wg_commit();
                if (wg == 0 && u == G2_KSTEPS - 1) asm volatile("bar.arrive 1, 256;" ::: "memory");
                wg_wait<1>();
                if (u - 1 + G2_STAGES <= G2_KSTEPS) release(empty2(qp));
                qp = q;
                if (++q == G2_STAGES) { q = 0; ph ^= 1; }
            }
        }
        wg_wait<0>();
        if (tid == 0) TRACE(16 + wg * 8 + 6);

        constexpr int QX = G2_KSTEPS % G2_STAGES;
        mbar_wait(full2(QX), (G2_KSTEPS / G2_STAGES) & 1);
        const uint32_t xs = stage2(QX) + warp * 2048;
        const uint32_t xrow = xs + ((lane & 7) + ((lane >> 3) & 1) * 8) * 128;
#pragma unroll
        for (int j = 0; j < 8; j++) {
            const uint32_t addr = xrow + (j >> 2) * 16384 + (((((j & 3) * 2) + (lane >> 4)) ^ (lane & 7)) << 4);
            uint32_t r[4];
            asm volatile("ldmatrix.sync.aligned.m8n8.x4.shared.b16 {%0,%1,%2,%3}, [%4];"
                         : "=r"(r[0]), "=r"(r[1]), "=r"(r[2]), "=r"(r[3]) : "r"(addr) : "memory");
#pragma unroll
            for (int i = 0; i < 4; i++) {
                const int e = (j * 4 + i) * 2;
                const uint32_t s2 = pack_bf16(accs[e], accs[e + 1]);
                const uint32_t d2 = pack_bf16(accd[e], accd[e + 1]);
                const uint32_t g2 = pack_bf16(silu(bf_lo(d2)), silu(bf_hi(d2)));
                r[i] = add_bf16x2(r[i], mul_bf16x2(s2, g2));
            }
            asm volatile("stmatrix.sync.aligned.m8n8.x4.shared.b16 [%0], {%1,%2,%3,%4};"
                         :: "r"(addr), "r"(r[0]), "r"(r[1]), "r"(r[2]), "r"(r[3]) : "memory");
            if (j == 3 || j == 7) {
                asm volatile("fence.proxy.async.shared::cta;" ::: "memory");
                __syncwarp();
                if (lane == 0) {
                    tma_store_2d(&maps.out, xs + (j >> 2) * 16384, nslot * 128 + (j >> 2) * 64, mblk * 128 + warp * 16);
                    asm volatile("cp.async.bulk.commit_group;" ::: "memory");
                }
            }
        }
        if (lane == 0) asm volatile("cp.async.bulk.wait_group.read 0;" ::: "memory");
        if (tid == 0) { TRACE(16 + wg * 8 + 7); if (wg == 1) TRACE_GT(13); }
    }
}

typedef CUresult (*EncodeFn)(CUtensorMap*, CUtensorMapDataType, cuuint32_t, void*, const cuuint64_t*, const cuuint64_t*,
                             const cuuint32_t*, const cuuint32_t*, CUtensorMapInterleave, CUtensorMapSwizzle,
                             CUtensorMapL2promotion, CUtensorMapFloatOOBfill);

void encode(EncodeFn fn, CUtensorMap* m, const void* ptr, int rank, const cuuint64_t* dims, const cuuint64_t* strides,
            const cuuint32_t* box) {
    const cuuint32_t es[5] = {1, 1, 1, 1, 1};
    fn(m, CU_TENSOR_MAP_DATA_TYPE_BFLOAT16, rank, const_cast<void*>(ptr), dims, strides, box, es,
       CU_TENSOR_MAP_INTERLEAVE_NONE, CU_TENSOR_MAP_SWIZZLE_128B, CU_TENSOR_MAP_L2_PROMOTION_L2_128B,
       CU_TENSOR_MAP_FLOAT_OOB_FILL_NONE);
}
void encode_2d(EncodeFn fn, CUtensorMap* m, const void* ptr, int cols, int box_rows) {
    const cuuint64_t dims[2] = {(cuuint64_t)cols, SEQ}, strides[1] = {(cuuint64_t)cols * 2};
    const cuuint32_t box[2] = {64, (cuuint32_t)box_rows};
    encode(fn, m, ptr, 2, dims, strides, box);
}
void encode_w1(EncodeFn fn, CUtensorMap* m, const void* ptr, int cols) {
    const cuuint64_t dims[3] = {64, DM, (cuuint64_t)cols / 64}, strides[2] = {(cuuint64_t)cols * 2, 128};
    const cuuint32_t box[3] = {64, 64, 2};
    encode(fn, m, ptr, 3, dims, strides, box);
}
void encode_w2(EncodeFn fn, CUtensorMap* m, const void* ptr, int rows) {
    const cuuint64_t rb = DM * 2;
    const cuuint64_t dims[5] = {DM, 2, 4, 4, (cuuint64_t)rows / 32}, strides[4] = {rb, 8 * rb, 2 * rb, 32 * rb};
    const cuuint32_t box[5] = {64, 2, 4, 4, 2};
    encode(fn, m, ptr, 5, dims, strides, box);
}

}

extern "C" void kernel_launch(void* const* d_in, const int* in_sizes, int n_in, void* d_out, int out_size) {
    (void)in_sizes; (void)n_in; (void)out_size;
    static EncodeFn fn = nullptr;
    static void *p_xn = nullptr, *p_a2 = nullptr;
    if (!fn) {
        cudaDriverEntryPointQueryResult st;
        cudaGetDriverEntryPoint("cuTensorMapEncodeTiled", (void**)&fn, cudaEnableDefault, &st);
        cudaGetSymbolAddress(&p_xn, g_xn);
        cudaGetSymbolAddress(&p_a2, g_a2);
        cudaFuncSetAttribute(fused_kernel, cudaFuncAttributeMaxDynamicSharedMemorySize, SMEM_BYTES);
    }
    Maps maps;
    encode_2d(fn, &maps.xn, p_xn, DM, 128);
    encode_w1(fn, &maps.wqkv, d_in[1], NQKV);
    encode_w1(fn, &maps.wg, d_in[4], DF);
    encode_w1(fn, &maps.wu, d_in[5], DF);
    encode_2d(fn, &maps.a2, p_a2, K2, 128);
    encode_w2(fn, &maps.wo, d_in[2], DM);
    encode_w2(fn, &maps.wd, d_in[6], DF);
    encode_2d(fn, &maps.x, d_in[0], DM, 128);
    encode_2d(fn, &maps.out, d_out, DM, 16);
    fused_kernel<<<NCTA, 384, SMEM_BYTES>>>(maps, (const __nv_bfloat16*)d_in[0]);
}
```

```cpp
#include <cuda_runtime.h>
#include <cuda_bf16.h>
#include <cuda.h>
#include <stdint.h>

namespace {

constexpr int SEQ = 2048, DM = 1024, DF = 3584, K2 = DM + DF, NQKV = 3 * DM;
constexpr int NCTA = 128;
constexpr int G1_STAGES = 4, G1_STAGE_BYTES = 49152, G1_KSTEPS = 16, G1_TILES = 5;
constexpr int G2_STAGES = 6, G2_STAGE_BYTES = 32768, G2_KSTEPS = 72, G2_DSTEPS = 56, G2_LATE = 40;
constexpr int A_BYTES = 16384;
constexpr int AUX_OFF = G1_STAGES * G1_STAGE_BYTES;
constexpr int BAR_OFF = AUX_OFF + 32768;
constexpr int SMEM_BYTES = BAR_OFF + 1024 + 256;
constexpr int G1_SKEW = 2, G2_SKEW = 2;
constexpr int CONSUMER_REGS = 216, AUX_REGS = 72;

enum { F_LN = 0, F_QKV = 1, F_EARLY = 2, F_LATE = 3, F_O = 4, F_CS = 5 };
constexpr unsigned CNT_LN = 16, CNT_QKV = 12, CNT_EARLY = 20, CNT_LATE = 8, CNT_O = 16, CNT_CS = 16;

__device__ __align__(1024) __nv_bfloat16 g_xn[SEQ * DM];
__device__ __align__(1024) __nv_bfloat16 g_qkv[SEQ * NQKV];
__device__ __align__(1024) __nv_bfloat16 g_a2[SEQ * K2];
__device__ __align__(128) float2 g_stats[SEQ];
__device__ __align__(128) float g_colsum[16 * 2048];
__device__ __align__(128) unsigned g_flags[6 * 16 * 32];
__device__ __align__(128) unsigned g_epoch[NCTA * 8];

#define TRACE(slot) do {} while (0)
#define TRACE_GT(slot) do {} while (0)

__device__ __forceinline__ uint32_t smem_u32(const void* p) { return (uint32_t)__cvta_generic_to_shared(p); }
__device__ __forceinline__ void mbar_init(uint32_t bar, uint32_t cnt) {
    asm volatile("mbarrier.init.shared::cta.b64 [%0], %1;" :: "r"(bar), "r"(cnt) : "memory");
}
__device__ __forceinline__ void mbar_expect_tx(uint32_t bar, uint32_t bytes) {
    asm volatile("mbarrier.arrive.expect_tx.shared::cta.b64 _, [%0], %1;" :: "r"(bar), "r"(bytes) : "memory");
}
__device__ __forceinline__ void mbar_arrive(uint32_t bar) {
    asm volatile("mbarrier.arrive.shared::cta.b64 _, [%0];" :: "r"(bar) : "memory");
}
__device__ __forceinline__ void mbar_arrive_cluster(uint32_t bar, uint32_t cta) {
    asm volatile("{\n.reg .b32 ra;\nmapa.shared::cluster.u32 ra, %0, %1;\nmbarrier.arrive.shared::cluster.b64 _, [ra];\n}"
                 :: "r"(bar), "r"(cta) : "memory");
}
__device__ __forceinline__ bool mbar_try_wait(uint32_t bar, uint32_t parity) {
    uint32_t ok;
    asm volatile("{\n.reg .pred p;\nmbarrier.try_wait.parity.shared::cta.b64 p, [%1], %2;\nselp.u32 %0, 1, 0, p;\n}"
                 : "=r"(ok) : "r"(bar), "r"(parity) : "memory");
    return ok;
}
__device__ __forceinline__ void mbar_wait(uint32_t bar, uint32_t parity) {
    int spins = 0;
    while (!mbar_try_wait(bar, parity)) { if (++spins > (1 << 17)) break; }
}
__device__ __forceinline__ void flag_wait(const unsigned* p, unsigned target) {
    for (int spins = 0; spins < (1 << 19); spins++) {
        unsigned v;
        asm volatile("ld.acquire.gpu.global.u32 %0, [%1];" : "=r"(v) : "l"(p) : "memory");
        if ((int)(v - target) >= 0) break;
        __nanosleep(64);
    }
}
__device__ __forceinline__ void flag_add(unsigned* p) {
    asm volatile("red.release.gpu.global.add.u32 [%0], 1;" :: "l"(p) : "memory");
}
__device__ __forceinline__ void fence_proxy_async() { asm volatile("fence.proxy.async;" ::: "memory"); }
__device__ __forceinline__ uint4 lds128(uint32_t addr) {
    uint4 v;
    asm volatile("ld.shared.v4.u32 {%0,%1,%2,%3}, [%4];" : "=r"(v.x), "=r"(v.y), "=r"(v.z), "=r"(v.w) : "r"(addr) : "memory");
    return v;
}
__device__ __forceinline__ float2 lds64f(uint32_t addr) {
    float2 v;
    asm volatile("ld.shared.v2.f32 {%0,%1}, [%2];" : "=f"(v.x), "=f"(v.y) : "r"(addr) : "memory");
    return v;
}
__device__ __forceinline__ void sts128(uint32_t addr, uint4 v) {
    asm volatile("st.shared.v4.u32 [%0], {%1,%2,%3,%4};" :: "r"(addr), "r"(v.x), "r"(v.y), "r"(v.z), "r"(v.w) : "memory");
}
__device__ __forceinline__ void sts64f(uint32_t addr, float a, float b) {
    asm volatile("st.shared.v2.f32 [%0], {%1,%2};" :: "r"(addr), "f"(a), "f"(b) : "memory");
}

__device__ __forceinline__ void tma_2d(uint32_t dst, const CUtensorMap* m, uint32_t bar, int c0, int c1) {
    asm volatile("cp.async.bulk.tensor.2d.shared::cluster.global.mbarrier::complete_tx::bytes [%0], [%1, {%3, %4}], [%2];"
                 :: "r"(dst), "l"(m), "r"(bar), "r"(c0), "r"(c1) : "memory");
}
__device__ __forceinline__ void tma_3d_mc(uint32_t dst, const CUtensorMap* m, uint32_t bar, int c1, int c2) {
    asm volatile("cp.async.bulk.tensor.3d.shared::cluster.global.mbarrier::complete_tx::bytes.multicast::cluster"
                 " [%0], [%1, {%3, %4, %5}], [%2], %6;"
                 :: "r"(dst), "l"(m), "r"(bar), "r"(0), "r"(c1), "r"(c2), "h"((uint16_t)3) : "memory");
}
__device__ __forceinline__ void tma_5d_mc(uint32_t dst, const CUtensorMap* m, uint32_t bar, int c0, int c4) {
    asm volatile("cp.async.bulk.tensor.5d.shared::cluster.global.mbarrier::complete_tx::bytes.multicast::cluster"
                 " [%0], [%1, {%3, %4, %4, %4, %5}], [%2], %6;"
                 :: "r"(dst), "l"(m), "r"(bar), "r"(c0), "r"(0), "r"(c4), "h"((uint16_t)3) : "memory");
}
__device__ __forceinline__ void tma_store_2d(const CUtensorMap* m, uint32_t src, int c0, int c1) {
    asm volatile("cp.async.bulk.tensor.2d.global.shared::cta.bulk_group [%0, {%2, %3}], [%1];"
                 :: "l"(m), "r"(src), "r"(c0), "r"(c1) : "memory");
}
__device__ __forceinline__ void prefetch_map(const CUtensorMap* m) {
    asm volatile("prefetch.tensormap [%0];" :: "l"(m) : "memory");
}
__device__ __forceinline__ void wg_fence() { asm volatile("wgmma.fence.sync.aligned;" ::: "memory"); }
__device__ __forceinline__ void wg_commit() { asm volatile("wgmma.commit_group.sync.aligned;" ::: "memory"); }
template <int N> __device__ __forceinline__ void wg_wait() { asm volatile("wgmma.wait_group.sync.aligned %0;" :: "n"(N) : "memory"); }

__device__ __forceinline__ uint64_t desc_a(uint32_t addr) {
    return (uint64_t)((addr & 0x3FFFF) >> 4) | (1ull << 16) | (64ull << 32) | (1ull << 62);
}
__device__ __forceinline__ uint64_t desc_b(uint32_t addr) {
    return (uint64_t)((addr & 0x3FFFF) >> 4) | (512ull << 16) | (64ull << 32) | (1ull << 62);
}

#define R8(d, o) "+f"(d[o]), "+f"(d[o+1]), "+f"(d[o+2]), "+f"(d[o+3]), "+f"(d[o+4]), "+f"(d[o+5]), "+f"(d[o+6]), "+f"(d[o+7])
#define R32(d, o) R8(d, o), R8(d, o+8), R8(d, o+16), R8(d, o+24)
#define R64(d, o) R32(d, o), R32(d, o+32)

__device__ __forceinline__ void wgmma_n256(float (&d)[128], uint64_t da, uint64_t db, int scale_d) {
    asm volatile("{\n.reg .pred p;\nsetp.ne.b32 p, %130, 0;\n"
        "wgmma.mma_async.sync.aligned.m64n256k16.f32.bf16.bf16 "
        "{%0,%1,%2,%3,%4,%5,%6,%7,%8,%9,%10,%11,%12,%13,%14,%15,%16,%17,%18,%19,%20,%21,%22,%23,%24,%25,%26,%27,%28,%29,%30,%31,"
        "%32,%33,%34,%35,%36,%37,%38,%39,%40,%41,%42,%43,%44,%45,%46,%47,%48,%49,%50,%51,%52,%53,%54,%55,%56,%57,%58,%59,%60,%61,%62,%63,"
        "%64,%65,%66,%67,%68,%69,%70,%71,%72,%73,%74,%75,%76,%77,%78,%79,%80,%81,%82,%83,%84,%85,%86,%87,%88,%89,%90,%91,%92,%93,%94,%95,"
        "%96,%97,%98,%99,%100,%101,%102,%103,%104,%105,%106,%107,%108,%109,%110,%111,%112,%113,%114,%115,%116,%117,%118,%119,%120,%121,%122,%123,%124,%125,%126,%127},"
        " %128, %129, p, 1, 1, 0, 1;\n}"
        : R64(d, 0), R64(d, 64) : "l"(da), "l"(db), "r"(scale_d));
}
__device__ __forceinline__ void wgmma_n128(float (&d)[64], uint64_t da, uint64_t db, int scale_d) {
    asm volatile("{\n.reg .pred p;\nsetp.ne.b32 p, %66, 0;\n"
        "wgmma.mma_async.sync.aligned.m64n128k16.f32.bf16.bf16 "
        "{%0,%1,%2,%3,%4,%5,%6,%7,%8,%9,%10,%11,%12,%13,%14,%15,%16,%17,%18,%19,%20,%21,%22,%23,%24,%25,%26,%27,%28,%29,%30,%31,"
        "%32,%33,%34,%35,%36,%37,%38,%39,%40,%41,%42,%43,%44,%45,%46,%47,%48,%49,%50,%51,%52,%53,%54,%55,%56,%57,%58,%59,%60,%61,%62,%63},"
        " %64, %65, p, 1, 1, 0, 1;\n}"
        : R64(d, 0) : "l"(da), "l"(db), "r"(scale_d));
}

__device__ __forceinline__ uint32_t pack_bf16(float lo, float hi) {
    uint32_t r; asm("cvt.rn.bf16x2.f32 %0, %1, %2;" : "=r"(r) : "f"(hi), "f"(lo)); return r;
}
__device__ __forceinline__ float bf_lo(uint32_t v) { return __uint_as_float(v << 16); }
__device__ __forceinline__ float bf_hi(uint32_t v) { return __uint_as_float(v & 0xffff0000u); }
__device__ __forceinline__ float round_bf16(float v) { return bf_lo(pack_bf16(v, 0.f)); }
__device__ __forceinline__ uint32_t mul_bf16x2(uint32_t a, uint32_t b) {
    uint32_t r; asm("mul.rn.bf16x2 %0, %1, %2;" : "=r"(r) : "r"(a), "r"(b)); return r;
}
__device__ __forceinline__ uint32_t add_bf16x2(uint32_t a, uint32_t b) {
    uint32_t r; asm("add.rn.bf16x2 %0, %1, %2;" : "=r"(r) : "r"(a), "r"(b)); return r;
}
__device__ __forceinline__ uint32_t sub_bf16x2(uint32_t a, uint32_t b) {
    uint32_t r; asm("sub.rn.bf16x2 %0, %1, %2;" : "=r"(r) : "r"(a), "r"(b)); return r;
}
__device__ __forceinline__ float tanh_fast(float x) { float r; asm("tanh.approx.f32 %0, %1;" : "=f"(r) : "f"(x)); return r; }
__device__ __forceinline__ float gelu_tanh(float g) {
    float t = fmaf(g * g, 0.044715f * 0.7978845608f, 0.7978845608f) * g;
    float hg = 0.5f * g;
    return fmaf(hg, tanh_fast(t), hg);
}
__device__ __forceinline__ uint32_t geglu2(uint32_t g2, uint32_t u2) {
    return mul_bf16x2(pack_bf16(gelu_tanh(bf_lo(g2)), gelu_tanh(bf_hi(g2))), u2);
}
__device__ __forceinline__ float silu(float d) {
    float hd = 0.5f * d;
    return fmaf(hd, tanh_fast(hd), hd);
}
__device__ __forceinline__ float ex2_fast(float x) { float r; asm("ex2.approx.ftz.f32 %0, %1;" : "=f"(r) : "f"(x)); return r; }
__device__ __forceinline__ void unpack8(uint4 v, float (&f)[8]) {
    f[0] = bf_lo(v.x); f[1] = bf_hi(v.x); f[2] = bf_lo(v.y); f[3] = bf_hi(v.y);
    f[4] = bf_lo(v.z); f[5] = bf_hi(v.z); f[6] = bf_lo(v.w); f[7] = bf_hi(v.w);
}
__device__ __forceinline__ uint4 pack8(const float (&f)[8]) {
    return make_uint4(pack_bf16(f[0], f[1]), pack_bf16(f[2], f[3]), pack_bf16(f[4], f[5]), pack_bf16(f[6], f[7]));
}
template <int N> __device__ __forceinline__ void fence_regs(float (&d)[N]) {
#pragma unroll
    for (int i = 0; i < N; i++) asm volatile("" : "+f"(d[i]) :: "memory");
}

__device__ __forceinline__ void window_softmax(float (&l)[8], int lim) {
    constexpr float SCALE = 0.17677669529663687f, LOG2E = 1.4426950408889634f;
#pragma unroll
    for (int j = 0; j < 8; j += 2) {
        uint32_t p = pack_bf16(l[j], l[j + 1]);
        p = pack_bf16(bf_lo(p) * SCALE, bf_hi(p) * SCALE);
        l[j] = 2 * j < lim ? -1e9f : bf_lo(p);
        l[j + 1] = 2 * j + 2 < lim ? -1e9f : bf_hi(p);
    }
    const float m = fmaxf(fmaxf(fmaxf(l[0], l[1]), fmaxf(l[2], l[3])), fmaxf(fmaxf(l[4], l[5]), fmaxf(l[6], l[7])));
#pragma unroll
    for (int j = 0; j < 8; j++) l[j] = ex2_fast((l[j] - m) * LOG2E);
    const float r = __frcp_rn(((l[0] + l[1]) + (l[2] + l[3])) + ((l[4] + l[5]) + (l[6] + l[7])));
#pragma unroll
    for (int j = 0; j < 8; j += 2) {
        const uint32_t p = pack_bf16(l[j] * r, l[j + 1] * r);
        l[j] = bf_lo(p); l[j + 1] = bf_hi(p);
    }
}

__device__ __forceinline__ void attention(const CUtensorMap* map, uint32_t buf, uint32_t bar_qk, uint32_t bar_v,
                                          int row0, int col0, int lane) {
    auto load_rows = [&](uint32_t dst, uint32_t bar, int col, int r) {
        tma_2d(dst, map, bar, col, max(r - 16, 0));
        tma_2d(dst + 2048, map, bar, col, r);
        tma_2d(dst + 4096, map, bar, col, r + 16);
    };
    auto load_qk = [&](int r) {
        mbar_expect_tx(bar_qk, 10240);
        tma_2d(buf, map, bar_qk, col0, r);
        tma_2d(buf + 2048, map, bar_qk, col0, r + 16);
        load_rows(buf + 4096, bar_qk, DM + col0, r);
    };
    auto load_v = [&](int r) {
        mbar_expect_tx(bar_v, 6144);
        load_rows(buf + 10240, bar_v, 2 * DM + col0, r);
    };
    if (lane == 0) { load_qk(row0); load_v(row0); }
    const int b = (lane & 1) + (lane & 2) * 2 + (lane >> 3) * 8, hx = (lane & 4) ? 6 : 0;
    const uint32_t rowaddr = buf + b * 128, sw = hx ^ (b & 7);
#pragma unroll 1
    for (int un = 0; un < 4; un++) {
        const int r = row0 + un * 32;
        float la[8], lb[8];
#pragma unroll
        for (int j = 0; j < 8; j++) { la[j] = 0.f; lb[j] = 0.f; }
        mbar_wait(bar_qk, un & 1);
#pragma unroll 1
        for (int c = 0; c < 4; c++) {
            uint32_t a[4];
#pragma unroll
            for (int i = 0; i < 4; i++) a[i] = rowaddr + ((sw ^ c ^ (2 * i)) << 4);
            float qa[8], qb[8];
            unpack8(lds128(a[0]), qa);
            unpack8(lds128(a[1] + 256), qb);
#pragma unroll
            for (int j = 0; j < 9; j++) {
                float k[8];
                unpack8(lds128(a[(j + 1) & 3] + 4096 + (j + 1) * 256), k);
#pragma unroll
                for (int d = 0; d < 8; d++) {
                    if (j < 8) la[j] = fmaf(qa[d], k[d], la[j]);
                    if (j > 0) lb[j - 1] = fmaf(qb[d], k[d], lb[j - 1]);
                }
            }
        }
        __syncwarp();
        if (un < 3 && lane == 0) load_qk(r + 32);
        window_softmax(la, r == 0 ? 14 - b : 0);
        window_softmax(lb, r == 0 ? 12 - b : 0);
        mbar_wait(bar_v, un & 1);
        __nv_bfloat16* op = g_a2 + (size_t)(r + b) * K2 + col0;
#pragma unroll 1
        for (int c = 0; c < 4; c++) {
            uint32_t a[4];
#pragma unroll
            for (int i = 0; i < 4; i++) a[i] = rowaddr + ((sw ^ c ^ (2 * i)) << 4);
            float oa[8], ob[8];
#pragma unroll
            for (int d = 0; d < 8; d++) { oa[d] = 0.f; ob[d] = 0.f; }
#pragma unroll
            for (int j = 0; j < 9; j++) {
                float v[8];
                unpack8(lds128(a[(j + 1) & 3] + 10240 + (j + 1) * 256), v);
#pragma unroll
                for (int d = 0; d < 8; d++) {
                    if (j < 8) oa[d] = fmaf(la[j], v[d], oa[d]);
                    if (j > 0) ob[d] = fmaf(lb[j - 1], v[d], ob[d]);
                }
            }
            *reinterpret_cast<uint4*>(op + (hx ^ c) * 8) = pack8(oa);
            *reinterpret_cast<uint4*>(op + 2 * K2 + (hx ^ c) * 8) = pack8(ob);
        }
        __syncwarp();
        if (un < 3 && lane == 0) load_v(r + 32);
    }
}

__device__ __forceinline__ void layernorm_row(const uint4 (&v)[4], int row, int lane) {
    const uint32_t* w = reinterpret_cast<const uint32_t*>(v);
    float sum = 0.f;
#pragma unroll
    for (int i = 0; i < 16; i++) sum += bf_lo(w[i]) + bf_hi(w[i]);
#pragma unroll
    for (int o = 16; o > 0; o >>= 1) sum += __shfl_xor_sync(0xffffffffu, sum, o);
    const float mean = sum * (1.f / DM);
    float sq = 0.f;
#pragma unroll
    for (int i = 0; i < 16; i++) {
        float a = bf_lo(w[i]) - mean, b = bf_hi(w[i]) - mean;
        sq = fmaf(a, a, sq); sq = fmaf(b, b, sq);
    }
#pragma unroll
    for (int o = 16; o > 0; o >>= 1) sq += __shfl_xor_sync(0xffffffffu, sq, o);
    const float var = round_bf16(sq * (1.f / DM));
    const float inv = 1.f / round_bf16(sqrtf(round_bf16(var + 1e-5f)));
    const uint32_t m2 = pack_bf16(mean, mean);
    __nv_bfloat16* dst = g_xn + (size_t)row * DM + lane * 8;
#pragma unroll
    for (int i = 0; i < 4; i++) {
        uint32_t o[4];
#pragma unroll
        for (int j = 0; j < 4; j++) {
            uint32_t c = sub_bf16x2(w[i * 4 + j], m2);
            o[j] = pack_bf16(bf_lo(c) * inv, bf_hi(c) * inv);
        }
        *reinterpret_cast<uint4*>(dst + i * 256) = make_uint4(o[0], o[1], o[2], o[3]);
    }
    if (lane == 0) g_stats[row] = make_float2(-bf_lo(m2), inv);
}

struct Params {
    CUtensorMap x, xn, wqkv, wg, wu, qkv, a2, wo, wd, out;
    const __nv_bfloat16 *px, *pwqkv, *pwg, *pwu;
};

__device__ __forceinline__ bool tile_is_qkv(int nt) { return nt < 4 || (nt >= 8 && nt < 16); }
__device__ __forceinline__ int tile_index(int nt) { return nt < 4 ? nt + 8 : (nt < 8 ? nt - 4 : (nt < 16 ? nt - 8 : nt - 12)); }

__global__ void __cluster_dims__(2, 1, 1) __launch_bounds__(384, 1)
fused_kernel(const __grid_constant__ Params prm) {
    extern __shared__ __align__(1024) uint8_t smem_raw[];
    const uint32_t base = (smem_u32(smem_raw) + 1023) & ~1023u;
    const uint32_t bars = base + BAR_OFF;
    auto full1 = [&](int s) { return bars + s * 8; };
    auto empty1 = [&](int s) { return bars + 32 + s * 8; };
    auto full2 = [&](int s) { return bars + 64 + s * 8; };
    auto empty2 = [&](int s) { return bars + 128 + s * 8; };
    const uint32_t sig_bar = bars + 192, fold_bar = bars + 200, x_bar = bars + 208, att_bars = bars + 216;
    auto stage2 = [&](int q) { return base + q * G2_STAGE_BYTES; };
    const uint32_t aux = base + AUX_OFF;

    const int warp = __shfl_sync(0xffffffffu, threadIdx.x >> 5, 0);
    const int lane = threadIdx.x & 31;
    const int rank = blockIdx.x & 1;
    const int mblk = ((blockIdx.x >> 1) & 7) * 2 + rank;
    const int nslot = blockIdx.x >> 4;

    if (warp >= 8) {
        unsigned* const flags = g_flags + mblk * 32;
        if (warp == 8) {
            if (lane == 0) {
                TRACE_GT(0); TRACE(1);
                prefetch_map(&prm.x); prefetch_map(nslot < 4 ? &prm.wqkv : (rank ? &prm.wu : &prm.wg));
                for (int s = 0; s < G1_STAGES; s++) { mbar_init(full1(s), 1); mbar_init(empty1(s), 4); }
                for (int s = 0; s < G2_STAGES; s++) { mbar_init(full2(s), 1); mbar_init(empty2(s), 4); }
                mbar_init(sig_bar, 8); mbar_init(fold_bar, 1); mbar_init(x_bar, 2);
                for (int s = 0; s < 4; s++) mbar_init(att_bars + s * 8, 1);
                asm volatile("fence.mbarrier_init.release.cluster;" ::: "memory");
            }
            __syncwarp();
        }
        asm volatile("barrier.cluster.arrive.relaxed.aligned;" ::: "memory");
        if (warp == 8 && lane == 0) {
            fence_proxy_async();
            for (int s = 0; s < G1_STAGES; s++) {
                mbar_expect_tx(full1(s), G1_STAGE_BYTES);
                tma_2d(base + s * G1_STAGE_BYTES, &prm.x, full1(s), s * 64, mblk * 128);
            }
        }
        const unsigned epoch = __ldcg(g_epoch + blockIdx.x * 8) + 1;
        asm volatile("setmaxnreg.dec.sync.aligned.u32 %0;" :: "n"(AUX_REGS));
        asm volatile("barrier.cluster.wait.acquire.aligned;" ::: "memory");

        if (warp == 8) {
            if (lane == 0) {
                TRACE(2);
                auto load_b1 = [&](int s, int nt, int k) {
                    const uint32_t dst = base + s * G1_STAGE_BYTES + A_BYTES + rank * 16384;
                    if (tile_is_qkv(nt)) tma_3d_mc(dst, &prm.wqkv, full1(s), k * 64, tile_index(nt) * 4 + rank * 2);
                    else tma_3d_mc(dst, rank ? &prm.wu : &prm.wg, full1(s), k * 64, tile_index(nt) * 2);
                };
                for (int s = 0; s < G1_STAGES; s++) load_b1(s, nslot, s);
                prefetch_map(&prm.xn); prefetch_map(&prm.wqkv); prefetch_map(rank ? &prm.wu : &prm.wg);
                prefetch_map(&prm.qkv); prefetch_map(&prm.a2); prefetch_map(&prm.wo); prefetch_map(&prm.wd);
                prefetch_map(&prm.out);
                uint32_t ph = 0;
                for (int it = G1_STAGES; it < G1_TILES * G1_KSTEPS; it++) {
                    const int s = it & 3, k = it & 15;
                    if (it == G1_KSTEPS) {
                        TRACE(14);
                        flag_wait(flags + F_LN * 512, epoch * CNT_LN);
                        fence_proxy_async();
                        TRACE(3);
                    }
                    mbar_wait(empty1(s), ph);
                    mbar_expect_tx(full1(s), G1_STAGE_BYTES);
                    tma_2d(base + s * G1_STAGE_BYTES, it < G1_KSTEPS ? &prm.x : &prm.xn, full1(s), k * 64, mblk * 128);
                    load_b1(s, (it >> 4) * 8 + nslot, k);
                    if (s == 3) ph ^= 1;
                }
                TRACE(4);
                flag_wait(flags + F_EARLY * 512, epoch * CNT_EARLY);
                fence_proxy_async();
                TRACE(5);
                int q = 0; uint32_t ph2 = 1;
                for (int u = 0; u < G2_KSTEPS; u++) {
                    if (u == G2_LATE || u == G2_DSTEPS) {
                        TRACE(u == G2_LATE ? 6 : 32);
                        flag_wait(flags + (u == G2_LATE ? F_LATE : F_O) * 512, epoch * (u == G2_LATE ? CNT_LATE : CNT_O));
                        fence_proxy_async();
                        TRACE(u == G2_LATE ? 7 : 33);
                    }
                    if (u < G2_STAGES) {
                        if (u == 0) mbar_wait(empty1(0), ph);
                        if (u == 1) mbar_wait(empty1(1), ph);
                        if (u == 3) mbar_wait(empty1(2), ph);
                        if (u == 4) mbar_wait(empty1(3), ph);
                    } else {
                        mbar_wait(empty2(q), ph2);
                    }
                    const uint32_t sa = stage2(q);
                    const bool down = u < G2_DSTEPS;
                    const int k = down ? u : u - G2_DSTEPS;
                    mbar_expect_tx(full2(q), G2_STAGE_BYTES);
                    tma_2d(sa, &prm.a2, full2(q), (down ? DM : 0) + k * 64, mblk * 128);
                    tma_5d_mc(sa + A_BYTES + rank * 8192, down ? &prm.wd : &prm.wo, full2(q), nslot * 128 + rank * 64, k * 2);
                    if (++q == G2_STAGES) { q = 0; ph2 ^= 1; }
                }
                g_epoch[blockIdx.x * 8] = epoch;
                TRACE(8);
            }
        } else if (warp == 9) {
            const int ld = nslot < 4 ? NQKV : DF;
            const __nv_bfloat16* w = nslot < 4 ? prm.pwqkv + 2 * DM + nslot * 256 + lane * 8
                                               : (lane < 16 ? prm.pwg : prm.pwu) + (nslot - 4) * 128 + (lane & 15) * 8;
            w += (size_t)mblk * 64 * ld;
            float cs[8];
#pragma unroll
            for (int d = 0; d < 8; d++) cs[d] = 0.f;
#pragma unroll 1
            for (int i = 0; i < 8; i++) {
                uint4 v[8];
#pragma unroll
                for (int j = 0; j < 8; j++) v[j] = __ldg(reinterpret_cast<const uint4*>(w + (size_t)(i * 8 + j) * ld));
#pragma unroll
                for (int j = 0; j < 8; j++) {
                    float f[8];
                    unpack8(v[j], f);
#pragma unroll
                    for (int d = 0; d < 8; d++) cs[d] += f[d];
                }
            }
            float4* cp = reinterpret_cast<float4*>(g_colsum + nslot * 256 + lane * 8);
            cp[mblk * 512] = make_float4(cs[0], cs[1], cs[2], cs[3]);
            cp[mblk * 512 + 1] = make_float4(cs[4], cs[5], cs[6], cs[7]);
            __syncwarp();
            if (lane == 0) {
                TRACE(34);
                flag_add(g_flags + F_CS * 512 + nslot * 32);
                flag_wait(g_flags + F_CS * 512 + nslot * 32, epoch * CNT_CS);
            }
            __syncwarp();
#pragma unroll
            for (int d = 0; d < 8; d++) cs[d] = 0.f;
#pragma unroll 4
            for (int m = 0; m < 16; m++) {
                const float4 a = __ldcg(cp + m * 512), b = __ldcg(cp + m * 512 + 1);
                cs[0] += a.x; cs[1] += a.y; cs[2] += a.z; cs[3] += a.w;
                cs[4] += b.x; cs[5] += b.y; cs[6] += b.z; cs[7] += b.w;
            }
#pragma unroll
            for (int t = 0; t < 4; t++) sts64f(aux + (lane >> 1) * 64 + t * 16 + (lane & 1) * 8, cs[2 * t], cs[2 * t + 1]);
            if (lane == 0) flag_wait(flags + F_LN * 512, epoch * CNT_LN);
            __syncwarp();
            const uint4* sp = reinterpret_cast<const uint4*>(g_stats + mblk * 128) + lane;
            const uint4 s0 = __ldcg(sp), s1 = __ldcg(sp + 32);
            sts128(aux + 1024 + lane * 16, s0);
            sts128(aux + 1536 + lane * 16, s1);
            __syncwarp();
            if (lane == 0) {
                mbar_arrive(fold_bar);
                TRACE(35);
                for (int t = 0; t < G1_TILES; t++) {
                    mbar_wait(sig_bar, t & 1);
                    flag_add(flags + (tile_is_qkv(t * 8 + nslot) ? F_QKV : (t < G1_TILES - 1 ? F_EARLY : F_LATE)) * 512);
                }
            }
        } else {
            const int w = warp - 10;
            const int r0 = mblk * 128 + nslot * 16 + w * 8;
            const uint4* xp = reinterpret_cast<const uint4*>(prm.px + (size_t)r0 * DM) + lane;
            if (lane == 0) asm volatile("cp.async.bulk.prefetch.L2.global [%0], %1;" :: "l"(xp), "r"(8 * DM * 2) : "memory");
            uint4 cur[4], nxt[4];
#pragma unroll
            for (int j = 0; j < 4; j++) cur[j] = __ldg(xp + j * 32);
#pragma unroll 1
            for (int i = 0; i < 8; i++) {
#pragma unroll
                for (int j = 0; j < 4; j++) nxt[j] = __ldg(xp + min(i + 1, 7) * 128 + j * 32);
                layernorm_row(cur, r0 + i, lane);
#pragma unroll
                for (int j = 0; j < 4; j++) cur[j] = nxt[j];
            }
            __syncwarp();
            if (lane == 0) {
                if (w == 0) TRACE(11);
                flag_add(flags + F_LN * 512);
                flag_wait(flags + F_QKV * 512, epoch * CNT_QKV);
                if (mblk > 0) flag_wait(flags - 32 + F_QKV * 512, epoch * CNT_QKV);
                fence_proxy_async();
                if (w == 0) TRACE(9);
            }
            __syncwarp();
            const uint32_t buf = aux + w * 16384;
            attention(&prm.qkv, buf, att_bars + w * 16, att_bars + w * 16 + 8, mblk * 128, nslot * 128 + w * 64, lane);
            if (lane == 0) {
                mbar_expect_tx(x_bar, 16384);
                tma_2d(buf, &prm.x, x_bar, nslot * 128 + w * 64, mblk * 128);
                flag_add(flags + F_O * 512);
                if (w == 0) TRACE(10);
            }
        }
    } else {
        asm volatile("barrier.cluster.arrive.relaxed.aligned;" ::: "memory");
        asm volatile("setmaxnreg.inc.sync.aligned.u32 %0;" :: "n"(CONSUMER_REGS));
        const int wg = warp >> 2;
        const int tid = threadIdx.x & 127;
        float acc[128];
        uint32_t pk[64];
#pragma unroll
        for (int i = 0; i < 64; i++) asm volatile("mov.b32 %0, 0;" : "=r"(pk[i]));
#pragma unroll
        for (int i = 0; i < 128; i++) asm volatile("mov.b32 %0, 0;" : "=f"(acc[i]));
        asm volatile("barrier.cluster.wait.acquire.aligned;" ::: "memory");

        const int orow = mblk * 128 + warp * 16 + (lane >> 2);
        __nv_bfloat16* optr = nullptr;
        auto release = [&](uint32_t bar) { if (tid < 2) mbar_arrive_cluster(bar, tid); };
        auto chunk_geglu = [&](int j) {
            const int c = j >> 1, h = j & 1;
            uint4 v;
            v.x = geglu2(pk[8 * c + h], pk[32 + 8 * c + h]);
            v.y = geglu2(pk[8 * c + 2 + h], pk[32 + 8 * c + 2 + h]);
            v.z = geglu2(pk[8 * c + 4 + h], pk[32 + 8 * c + 4 + h]);
            v.w = geglu2(pk[8 * c + 6 + h], pk[32 + 8 * c + 6 + h]);
            *reinterpret_cast<uint4*>(optr + h * 8 * K2 + c * 32) = v;
        };
        auto chunk_qkv = [&](int c) {
            *reinterpret_cast<uint4*>(optr + c * 32) = make_uint4(pk[8 * c], pk[8 * c + 2], pk[8 * c + 4], pk[8 * c + 6]);
            *reinterpret_cast<uint4*>(optr + 8 * NQKV + c * 32) = make_uint4(pk[8 * c + 1], pk[8 * c + 3], pk[8 * c + 5], pk[8 * c + 7]);
        };
        auto signal_stores = [&]() { __syncwarp(); if (lane == 0) mbar_arrive(sig_bar); };

        int pending = 0;
#pragma unroll 1
        for (int t = 0; t < G1_TILES; t++) {
#pragma unroll
            for (int k = 0; k < G1_KSTEPS; k++) {
                const int s = k & 3;
                mbar_wait(full1(s), (k >> 2) & 1);
                if (t == 0 && k == 0 && threadIdx.x == 0) TRACE(12);
                if (wg == 1 && k == G1_KSTEPS - G1_SKEW) asm volatile("bar.sync 1, 256;" ::: "memory");
                const uint64_t da = desc_a(base + s * G1_STAGE_BYTES + wg * 8192);
                const uint64_t db = desc_b(base + s * G1_STAGE_BYTES + A_BYTES);
                wg_fence();
#pragma unroll
                for (int kk = 0; kk < 4; kk++) wgmma_n256(acc, da + kk * 2, db + kk * 128, (k | kk) != 0);
                wg_commit();
                if (wg == 0 && k == G1_KSTEPS - 1) asm volatile("bar.arrive 1, 256;" ::: "memory");
                if (k >= 1 && k <= 8) {
                    if (pending == 2) chunk_geglu(k - 1);
                    else if (pending == 1) chunk_qkv(k - 1);
                    if (k == 8 && pending) signal_stores();
                }
                wg_wait<1>();
                if (k > 0) release(empty1((k - 1) & 3));
            }
            if (t == 0) mbar_wait(fold_bar, 0);
            wg_wait<0>();
            fence_regs(acc);
            release(empty1(3));
            if (t == 0) {
                const uint32_t sp = aux + 1024 + (warp * 16 + (lane >> 2)) * 8;
                const float2 sa = lds64f(sp), sb = lds64f(sp + 64);
#pragma unroll
                for (int j = 0; j < 16; j++) {
                    const uint4 c = lds128(aux + j * 64 + (lane & 3) * 16);
                    const float c0 = __uint_as_float(c.x), c1 = __uint_as_float(c.y);
                    const float c2 = __uint_as_float(c.z), c3 = __uint_as_float(c.w);
                    const float* a = acc + 8 * j;
                    pk[4 * j] = pack_bf16(fmaf(sa.x, c0, a[0]) * sa.y, fmaf(sa.x, c1, a[1]) * sa.y);
                    pk[4 * j + 1] = pack_bf16(fmaf(sb.x, c0, a[2]) * sb.y, fmaf(sb.x, c1, a[3]) * sb.y);
                    pk[4 * j + 2] = pack_bf16(fmaf(sa.x, c2, a[4]) * sa.y, fmaf(sa.x, c3, a[5]) * sa.y);
                    pk[4 * j + 3] = pack_bf16(fmaf(sb.x, c2, a[6]) * sb.y, fmaf(sb.x, c3, a[7]) * sb.y);
                }
            } else {
#pragma unroll
                for (int i = 0; i < 64; i++) pk[i] = pack_bf16(acc[2 * i], acc[2 * i + 1]);
            }
            const int nt = t * 8 + nslot;
            pending = tile_is_qkv(nt) ? 1 : 2;
            optr = pending == 1 ? g_qkv + (size_t)orow * NQKV + tile_index(nt) * 256 + (lane & 3) * 8
                                : g_a2 + (size_t)orow * K2 + DM + tile_index(nt) * 128 + (lane & 3) * 8;
            if (tid == 0) TRACE(16 + wg * 8 + t);
        }

        float accd[64], accs[64];
#pragma unroll
        for (int i = 0; i < 64; i++) accd[i] = 0.f;
#pragma unroll
        for (int u = 0; u < 9; u++) {
            const int q = u % G2_STAGES;
            mbar_wait(full2(q), (u / G2_STAGES) & 1);
            const uint64_t da = desc_a(stage2(q) + wg * 8192), db = desc_b(stage2(q) + A_BYTES);
            wg_fence();
#pragma unroll
            for (int kk = 0; kk < 4; kk++) wgmma_n128(accd, da + kk * 2, db + kk * 128, (u | kk) != 0);
            wg_commit();
            if (u >= 1) { chunk_geglu(u - 1); if (u == 8) signal_stores(); }
            wg_wait<1>();
            if (u > 0) release(empty2((u - 1) % G2_STAGES));
        }
        {
            int q = 9 % G2_STAGES, qp = 8 % G2_STAGES; uint32_t ph = (9 / G2_STAGES) & 1;
#pragma unroll 1
            for (int u = 9; u < G2_DSTEPS; u++) {
                mbar_wait(full2(q), ph);
                const uint64_t da = desc_a(stage2(q) + wg * 8192), db = desc_b(stage2(q) + A_BYTES);
                wg_fence();
#pragma unroll
                for (int kk = 0; kk < 4; kk++) wgmma_n128(accd, da + kk * 2, db + kk * 128, 1);
                wg_commit();
                wg_wait<1>();
                release(empty2(qp));
                qp = q;
                if (++q == G2_STAGES) { q = 0; ph ^= 1; }
            }
        }
        if (tid == 0) TRACE(16 + wg * 8 + 5);
#pragma unroll
        for (int i = 0; i < 64; i++) accs[i] = 0.f;
        uint32_t gk[32], xr[32];
        const uint32_t xs = aux + warp * 2048;
        const uint32_t xrow = xs + ((lane & 7) + ((lane >> 3) & 1) * 8) * 128;
        auto xaddr = [&](int j) { return xrow + (j >> 2) * 16384 + (((((j & 3) * 2) + (lane >> 4)) ^ (lane & 7)) << 4); };
#pragma unroll
        for (int u = G2_DSTEPS; u < G2_KSTEPS; u++) {
            const int q = u % G2_STAGES, v = u - G2_DSTEPS;
            mbar_wait(full2(q), (u / G2_STAGES) & 1);
            if (G2_SKEW > 0 && wg == 1 && u == G2_KSTEPS - G2_SKEW) asm volatile("bar.sync 1, 256;" ::: "memory");
            const uint64_t da = desc_a(stage2(q) + wg * 8192), db = desc_b(stage2(q) + A_BYTES);
            wg_fence();
#pragma unroll
            for (int kk = 0; kk < 4; kk++) wgmma_n128(accs, da + kk * 2, db + kk * 128, (v | kk) != 0);
            wg_commit();
            if (G2_SKEW > 0 && wg == 0 && u == G2_KSTEPS - 1) asm volatile("bar.arrive 1, 256;" ::: "memory");
            if (v >= 1 && v <= 8) {
#pragma unroll
                for (int i = 4 * (v - 1); i < 4 * v; i++) {
                    const uint32_t d2 = pack_bf16(accd[2 * i], accd[2 * i + 1]);
                    gk[i] = pack_bf16(silu(bf_lo(d2)), silu(bf_hi(d2)));
                }
            }
            if (v == 9) mbar_wait(x_bar, 0);
            if (v >= 9 && v <= 12) {
#pragma unroll
                for (int j = 2 * (v - 9); j < 2 * (v - 8); j++)
                    asm volatile("ldmatrix.sync.aligned.m8n8.x4.shared.b16 {%0,%1,%2,%3}, [%4];"
                                 : "=r"(xr[4 * j]), "=r"(xr[4 * j + 1]), "=r"(xr[4 * j + 2]), "=r"(xr[4 * j + 3])
                                 : "r"(xaddr(j)) : "memory");
            }
            wg_wait<1>();
            if (v == 0) fence_regs(accd);
            if (u - 1 + G2_STAGES < G2_KSTEPS) release(empty2((u - 1) % G2_STAGES));
        }
        wg_wait<0>();
        fence_regs(accs);
        if (tid == 0) TRACE(16 + wg * 8 + 6);
#pragma unroll
        for (int j = 0; j < 8; j++) {
            uint32_t r[4];
#pragma unroll
            for (int i = 0; i < 4; i++) {
                const int e = j * 4 + i;
                r[i] = add_bf16x2(xr[e], mul_bf16x2(pack_bf16(accs[2 * e], accs[2 * e + 1]), gk[e]));
            }
            asm volatile("stmatrix.sync.aligned.m8n8.x4.shared.b16 [%0], {%1,%2,%3,%4};"
                         :: "r"(xaddr(j)), "r"(r[0]), "r"(r[1]), "r"(r[2]), "r"(r[3]) : "memory");
            if (j == 3 || j == 7) {
                asm volatile("fence.proxy.async.shared::cta;" ::: "memory");
                __syncwarp();
                if (lane == 0) {
                    tma_store_2d(&prm.out, xs + (j >> 2) * 16384, nslot * 128 + (j >> 2) * 64, mblk * 128 + warp * 16);
                    asm volatile("cp.async.bulk.commit_group;" ::: "memory");
                }
            }
        }
        if (lane == 0) asm volatile("cp.async.bulk.wait_group.read 0;" ::: "memory");
        if (tid == 0) { TRACE(16 + wg * 8 + 7); if (wg == 1) TRACE_GT(13); }
    }
}

typedef CUresult (*EncodeFn)(CUtensorMap*, CUtensorMapDataType, cuuint32_t, void*, const cuuint64_t*, const cuuint64_t*,
                             const cuuint32_t*, const cuuint32_t*, CUtensorMapInterleave, CUtensorMapSwizzle,
                             CUtensorMapL2promotion, CUtensorMapFloatOOBfill);

void encode(EncodeFn fn, CUtensorMap* m, const void* ptr, int rank, const cuuint64_t* dims, const cuuint64_t* strides,
            const cuuint32_t* box) {
    const cuuint32_t es[5] = {1, 1, 1, 1, 1};
    fn(m, CU_TENSOR_MAP_DATA_TYPE_BFLOAT16, rank, const_cast<void*>(ptr), dims, strides, box, es,
       CU_TENSOR_MAP_INTERLEAVE_NONE, CU_TENSOR_MAP_SWIZZLE_128B, CU_TENSOR_MAP_L2_PROMOTION_L2_128B,
       CU_TENSOR_MAP_FLOAT_OOB_FILL_NONE);
}
void encode_2d(EncodeFn fn, CUtensorMap* m, const void* ptr, int cols, int box_rows) {
    const cuuint64_t dims[2] = {(cuuint64_t)cols, SEQ}, strides[1] = {(cuuint64_t)cols * 2};
    const cuuint32_t box[2] = {64, (cuuint32_t)box_rows};
    encode(fn, m, ptr, 2, dims, strides, box);
}
void encode_w1(EncodeFn fn, CUtensorMap* m, const void* ptr, int cols) {
    const cuuint64_t dims[3] = {64, DM, (cuuint64_t)cols / 64}, strides[2] = {(cuuint64_t)cols * 2, 128};
    const cuuint32_t box[3] = {64, 64, 2};
    encode(fn, m, ptr, 3, dims, strides, box);
}
void encode_w2(EncodeFn fn, CUtensorMap* m, const void* ptr, int rows) {
    const cuuint64_t rb = DM * 2;
    const cuuint64_t dims[5] = {DM, 2, 4, 4, (cuuint64_t)rows / 32}, strides[4] = {rb, 8 * rb, 2 * rb, 32 * rb};
    const cuuint32_t box[5] = {64, 2, 4, 4, 2};
    encode(fn, m, ptr, 5, dims, strides, box);
}

}

extern "C" void kernel_launch(void* const* d_in, const int* in_sizes, int n_in, void* d_out, int out_size) {
    (void)in_sizes; (void)n_in; (void)out_size;
    static EncodeFn fn = nullptr;
    static void *p_xn = nullptr, *p_qkv = nullptr, *p_a2 = nullptr;
    if (!fn) {
        cudaDriverEntryPointQueryResult st;
        cudaGetDriverEntryPoint("cuTensorMapEncodeTiled", (void**)&fn, cudaEnableDefault, &st);
        cudaGetSymbolAddress(&p_xn, g_xn);
        cudaGetSymbolAddress(&p_qkv, g_qkv);
        cudaGetSymbolAddress(&p_a2, g_a2);
        cudaFuncSetAttribute(fused_kernel, cudaFuncAttributeMaxDynamicSharedMemorySize, SMEM_BYTES);
    }
    Params prm;
    encode_2d(fn, &prm.x, d_in[0], DM, 128);
    encode_2d(fn, &prm.xn, p_xn, DM, 128);
    encode_w1(fn, &prm.wqkv, d_in[1], NQKV);
    encode_w1(fn, &prm.wg, d_in[4], DF);
    encode_w1(fn, &prm.wu, d_in[5], DF);
    encode_2d(fn, &prm.qkv, p_qkv, NQKV, 16);
    encode_2d(fn, &prm.a2, p_a2, K2, 128);
    encode_w2(fn, &prm.wo, d_in[2], DM);
    encode_w2(fn, &prm.wd, d_in[6], DF);
    encode_2d(fn, &prm.out, d_out, DM, 16);
    prm.px = (const __nv_bfloat16*)d_in[0];
    prm.pwqkv = (const __nv_bfloat16*)d_in[1];
    prm.pwg = (const __nv_bfloat16*)d_in[4];
    prm.pwu = (const __nv_bfloat16*)d_in[5];
    fused_kernel<<<NCTA, 384, SMEM_BYTES>>>(prm);
}
```

```cpp
#include <cuda_runtime.h>
#include <cuda_bf16.h>
#include <cuda.h>
#include <stdint.h>

namespace {

constexpr int SEQ = 2048, DM = 1024, DF = 3584, K2 = DM + DF, NQKV = 3 * DM;
constexpr int NGEMM = 128, NCTA = 132;
constexpr int G1_STAGES = 4, G1_STAGE_BYTES = 49152, G1_KSTEPS = 16, G1_TILES = 5;
constexpr int G2_STAGES = 6, G2_STAGE_BYTES = 32768, G2_KSTEPS = 72, G2_DSTEPS = 56, G2_LATE = 40;
constexpr int A_BYTES = 16384;
constexpr int AUX_OFF = G1_STAGES * G1_STAGE_BYTES;
constexpr int BAR_OFF = AUX_OFF + 32768;
constexpr int SMEM_BYTES = BAR_OFF + 1024 + 256;
constexpr int G1_SKEW = 2, G2_SKEW = 2;
constexpr int CONSUMER_REGS = 224, AUX_REGS = 56;
constexpr int ATT_STAGES = 4, ATT_STAGE_BYTES = 6144, ATT_STEPS = 64;

enum { F_LN = 0, F_QKV = 1, F_EARLY = 2, F_LATE = 3, F_O = 4, F_CS = 5 };
constexpr unsigned CNT_LN = 8, CNT_QKV = 48, CNT_EARLY = 20, CNT_LATE = 8, CNT_O = 32, CNT_CS = 32;

__device__ __align__(1024) __nv_bfloat16 g_xn[SEQ * DM];
__device__ __align__(1024) __nv_bfloat16 g_qkv[SEQ * NQKV];
__device__ __align__(1024) __nv_bfloat16 g_a2[SEQ * K2];
__device__ __align__(128) float2 g_stats[SEQ];
__device__ __align__(128) float g_colsum[32 * 2048];
__device__ __align__(128) unsigned g_flags[6 * 16 * 32];
__device__ __align__(128) unsigned g_epoch[NCTA * 8];

#define TRACE(slot) do {} while (0)
#define TRACE_GT(slot) do {} while (0)

__device__ __forceinline__ uint32_t smem_u32(const void* p) { return (uint32_t)__cvta_generic_to_shared(p); }
__device__ __forceinline__ void mbar_init(uint32_t bar, uint32_t cnt) {
    asm volatile("mbarrier.init.shared::cta.b64 [%0], %1;" :: "r"(bar), "r"(cnt) : "memory");
}
__device__ __forceinline__ void mbar_expect_tx(uint32_t bar, uint32_t bytes) {
    asm volatile("mbarrier.arrive.expect_tx.shared::cta.b64 _, [%0], %1;" :: "r"(bar), "r"(bytes) : "memory");
}
__device__ __forceinline__ void mbar_arrive(uint32_t bar) {
    asm volatile("mbarrier.arrive.shared::cta.b64 _, [%0];" :: "r"(bar) : "memory");
}
__device__ __forceinline__ void mbar_arrive_cluster(uint32_t bar, uint32_t cta) {
    asm volatile("{\n.reg .b32 ra;\nmapa.shared::cluster.u32 ra, %0, %1;\nmbarrier.arrive.shared::cluster.b64 _, [ra];\n}"
                 :: "r"(bar), "r"(cta) : "memory");
}
__device__ __forceinline__ bool mbar_try_wait(uint32_t bar, uint32_t parity) {
    uint32_t ok;
    asm volatile("{\n.reg .pred p;\nmbarrier.try_wait.parity.shared::cta.b64 p, [%1], %2;\nselp.u32 %0, 1, 0, p;\n}"
                 : "=r"(ok) : "r"(bar), "r"(parity) : "memory");
    return ok;
}
__device__ __forceinline__ void mbar_wait(uint32_t bar, uint32_t parity) {
    int spins = 0;
    while (!mbar_try_wait(bar, parity)) { if (++spins > (1 << 17)) break; }
}
__device__ __forceinline__ void flag_wait(const unsigned* p, unsigned target) {
    for (int spins = 0; spins < (1 << 19); spins++) {
        unsigned v;
        asm volatile("ld.acquire.gpu.global.u32 %0, [%1];" : "=r"(v) : "l"(p) : "memory");
        if ((int)(v - target) >= 0) break;
        __nanosleep(64);
    }
}
__device__ __forceinline__ void flag_add(unsigned* p) {
    asm volatile("red.release.gpu.global.add.u32 [%0], 1;" :: "l"(p) : "memory");
}
__device__ __forceinline__ void fence_proxy_async() { asm volatile("fence.proxy.async;" ::: "memory"); }
__device__ __forceinline__ uint4 lds128(uint32_t addr) {
    uint4 v;
    asm volatile("ld.shared.v4.u32 {%0,%1,%2,%3}, [%4];" : "=r"(v.x), "=r"(v.y), "=r"(v.z), "=r"(v.w) : "r"(addr) : "memory");
    return v;
}
__device__ __forceinline__ float2 lds64f(uint32_t addr) {
    float2 v;
    asm volatile("ld.shared.v2.f32 {%0,%1}, [%2];" : "=f"(v.x), "=f"(v.y) : "r"(addr) : "memory");
    return v;
}
__device__ __forceinline__ void sts128(uint32_t addr, uint4 v) {
    asm volatile("st.shared.v4.u32 [%0], {%1,%2,%3,%4};" :: "r"(addr), "r"(v.x), "r"(v.y), "r"(v.z), "r"(v.w) : "memory");
}
__device__ __forceinline__ void sts64f(uint32_t addr, float a, float b) {
    asm volatile("st.shared.v2.f32 [%0], {%1,%2};" :: "r"(addr), "f"(a), "f"(b) : "memory");
}

__device__ __forceinline__ void tma_2d(uint32_t dst, const CUtensorMap* m, uint32_t bar, int c0, int c1) {
    asm volatile("cp.async.bulk.tensor.2d.shared::cluster.global.mbarrier::complete_tx::bytes [%0], [%1, {%3, %4}], [%2];"
                 :: "r"(dst), "l"(m), "r"(bar), "r"(c0), "r"(c1) : "memory");
}
__device__ __forceinline__ void tma_4d(uint32_t dst, const CUtensorMap* m, uint32_t bar, int c0, int c1, int c3) {
    asm volatile("cp.async.bulk.tensor.4d.shared::cluster.global.mbarrier::complete_tx::bytes [%0], [%1, {%3, %4, %5, %6}], [%2];"
                 :: "r"(dst), "l"(m), "r"(bar), "r"(c0), "r"(c1), "r"(0), "r"(c3) : "memory");
}
__device__ __forceinline__ void tma_3d_mc(uint32_t dst, const CUtensorMap* m, uint32_t bar, int c1, int c2) {
    asm volatile("cp.async.bulk.tensor.3d.shared::cluster.global.mbarrier::complete_tx::bytes.multicast::cluster"
                 " [%0], [%1, {%3, %4, %5}], [%2], %6;"
                 :: "r"(dst), "l"(m), "r"(bar), "r"(0), "r"(c1), "r"(c2), "h"((uint16_t)3) : "memory");
}
__device__ __forceinline__ void tma_5d_mc(uint32_t dst, const CUtensorMap* m, uint32_t bar, int c0, int c4) {
    asm volatile("cp.async.bulk.tensor.5d.shared::cluster.global.mbarrier::complete_tx::bytes.multicast::cluster"
                 " [%0], [%1, {%3, %4, %4, %4, %5}], [%2], %6;"
                 :: "r"(dst), "l"(m), "r"(bar), "r"(c0), "r"(0), "r"(c4), "h"((uint16_t)3) : "memory");
}
__device__ __forceinline__ void tma_store_2d(const CUtensorMap* m, uint32_t src, int c0, int c1) {
    asm volatile("cp.async.bulk.tensor.2d.global.shared::cta.bulk_group [%0, {%2, %3}], [%1];"
                 :: "l"(m), "r"(src), "r"(c0), "r"(c1) : "memory");
}
__device__ __forceinline__ void prefetch_map(const CUtensorMap* m) {
    asm volatile("prefetch.tensormap [%0];" :: "l"(m) : "memory");
}
__device__ __forceinline__ void wg_fence() { asm volatile("wgmma.fence.sync.aligned;" ::: "memory"); }
__device__ __forceinline__ void wg_commit() { asm volatile("wgmma.commit_group.sync.aligned;" ::: "memory"); }
template <int N> __device__ __forceinline__ void wg_wait() { asm volatile("wgmma.wait_group.sync.aligned %0;" :: "n"(N) : "memory"); }

__device__ __forceinline__ uint64_t desc_a(uint32_t addr) {
    return (uint64_t)((addr & 0x3FFFF) >> 4) | (1ull << 16) | (64ull << 32) | (1ull << 62);
}
__device__ __forceinline__ uint64_t desc_b(uint32_t addr) {
    return (uint64_t)((addr & 0x3FFFF) >> 4) | (512ull << 16) | (64ull << 32) | (1ull << 62);
}

#define R8(d, o) "+f"(d[o]), "+f"(d[o+1]), "+f"(d[o+2]), "+f"(d[o+3]), "+f"(d[o+4]), "+f"(d[o+5]), "+f"(d[o+6]), "+f"(d[o+7])
#define R32(d, o) R8(d, o), R8(d, o+8), R8(d, o+16), R8(d, o+24)
#define R64(d, o) R32(d, o), R32(d, o+32)

__device__ __forceinline__ void wgmma_n256(float (&d)[128], uint64_t da, uint64_t db, int scale_d) {
    asm volatile("{\n.reg .pred p;\nsetp.ne.b32 p, %130, 0;\n"
        "wgmma.mma_async.sync.aligned.m64n256k16.f32.bf16.bf16 "
        "{%0,%1,%2,%3,%4,%5,%6,%7,%8,%9,%10,%11,%12,%13,%14,%15,%16,%17,%18,%19,%20,%21,%22,%23,%24,%25,%26,%27,%28,%29,%30,%31,"
        "%32,%33,%34,%35,%36,%37,%38,%39,%40,%41,%42,%43,%44,%45,%46,%47,%48,%49,%50,%51,%52,%53,%54,%55,%56,%57,%58,%59,%60,%61,%62,%63,"
        "%64,%65,%66,%67,%68,%69,%70,%71,%72,%73,%74,%75,%76,%77,%78,%79,%80,%81,%82,%83,%84,%85,%86,%87,%88,%89,%90,%91,%92,%93,%94,%95,"
        "%96,%97,%98,%99,%100,%101,%102,%103,%104,%105,%106,%107,%108,%109,%110,%111,%112,%113,%114,%115,%116,%117,%118,%119,%120,%121,%122,%123,%124,%125,%126,%127},"
        " %128, %129, p, 1, 1, 0, 1;\n}"
        : R64(d, 0), R64(d, 64) : "l"(da), "l"(db), "r"(scale_d));
}
__device__ __forceinline__ void wgmma_n128(float (&d)[64], uint64_t da, uint64_t db, int scale_d) {
    asm volatile("{\n.reg .pred p;\nsetp.ne.b32 p, %66, 0;\n"
        "wgmma.mma_async.sync.aligned.m64n128k16.f32.bf16.bf16 "
        "{%0,%1,%2,%3,%4,%5,%6,%7,%8,%9,%10,%11,%12,%13,%14,%15,%16,%17,%18,%19,%20,%21,%22,%23,%24,%25,%26,%27,%28,%29,%30,%31,"
        "%32,%33,%34,%35,%36,%37,%38,%39,%40,%41,%42,%43,%44,%45,%46,%47,%48,%49,%50,%51,%52,%53,%54,%55,%56,%57,%58,%59,%60,%61,%62,%63},"
        " %64, %65, p, 1, 1, 0, 1;\n}"
        : R64(d, 0) : "l"(da), "l"(db), "r"(scale_d));
}

__device__ __forceinline__ uint32_t pack_bf16(float lo, float hi) {
    uint32_t r; asm("cvt.rn.bf16x2.f32 %0, %1, %2;" : "=r"(r) : "f"(hi), "f"(lo)); return r;
}
__device__ __forceinline__ float bf_lo(uint32_t v) { return __uint_as_float(v << 16); }
__device__ __forceinline__ float bf_hi(uint32_t v) { return __uint_as_float(v & 0xffff0000u); }
__device__ __forceinline__ float round_bf16(float v) { return bf_lo(pack_bf16(v, 0.f)); }
__device__ __forceinline__ uint32_t mul_bf16x2(uint32_t a, uint32_t b) {
    uint32_t r; asm("mul.rn.bf16x2 %0, %1, %2;" : "=r"(r) : "r"(a), "r"(b)); return r;
}
__device__ __forceinline__ uint32_t add_bf16x2(uint32_t a, uint32_t b) {
    uint32_t r; asm("add.rn.bf16x2 %0, %1, %2;" : "=r"(r) : "r"(a), "r"(b)); return r;
}
__device__ __forceinline__ uint32_t sub_bf16x2(uint32_t a, uint32_t b) {
    uint32_t r; asm("sub.rn.bf16x2 %0, %1, %2;" : "=r"(r) : "r"(a), "r"(b)); return r;
}
__device__ __forceinline__ float tanh_fast(float x) { float r; asm("tanh.approx.f32 %0, %1;" : "=f"(r) : "f"(x)); return r; }
__device__ __forceinline__ float gelu_tanh(float g) {
    float t = fmaf(g * g, 0.044715f * 0.7978845608f, 0.7978845608f) * g;
    float hg = 0.5f * g;
    return fmaf(hg, tanh_fast(t), hg);
}
__device__ __forceinline__ uint32_t geglu2(uint32_t g2, uint32_t u2) {
    return mul_bf16x2(pack_bf16(gelu_tanh(bf_lo(g2)), gelu_tanh(bf_hi(g2))), u2);
}
__device__ __forceinline__ float silu(float d) {
    float hd = 0.5f * d;
    return fmaf(hd, tanh_fast(hd), hd);
}
__device__ __forceinline__ float ex2_fast(float x) { float r; asm("ex2.approx.ftz.f32 %0, %1;" : "=f"(r) : "f"(x)); return r; }
__device__ __forceinline__ void unpack8(uint4 v, float (&f)[8]) {
    f[0] = bf_lo(v.x); f[1] = bf_hi(v.x); f[2] = bf_lo(v.y); f[3] = bf_hi(v.y);
    f[4] = bf_lo(v.z); f[5] = bf_hi(v.z); f[6] = bf_lo(v.w); f[7] = bf_hi(v.w);
}
template <int N> __device__ __forceinline__ void fence_regs(float (&d)[N]) {
#pragma unroll
    for (int i = 0; i < N; i++) asm volatile("" : "+f"(d[i]) :: "memory");
}

__device__ __forceinline__ float rcp_fast(float x) { float r; asm("rcp.approx.ftz.f32 %0, %1;" : "=f"(r) : "f"(x)); return r; }
__device__ __forceinline__ uint32_t max_bf16x2(uint32_t a, uint32_t b) {
    uint32_t r; asm("max.bf16x2 %0, %1, %2;" : "=r"(r) : "r"(a), "r"(b)); return r;
}
__device__ __forceinline__ uint4 ldsm4(uint32_t addr) {
    uint4 v;
    asm volatile("ldmatrix.sync.aligned.m8n8.x4.shared.b16 {%0,%1,%2,%3}, [%4];"
                 : "=r"(v.x), "=r"(v.y), "=r"(v.z), "=r"(v.w) : "r"(addr) : "memory");
    return v;
}
__device__ __forceinline__ uint4 ldsm4_t(uint32_t addr) {
    uint4 v;
    asm volatile("ldmatrix.sync.aligned.m8n8.x4.trans.shared.b16 {%0,%1,%2,%3}, [%4];"
                 : "=r"(v.x), "=r"(v.y), "=r"(v.z), "=r"(v.w) : "r"(addr) : "memory");
    return v;
}
__device__ __forceinline__ void mma_16816(float (&c)[4], uint32_t a0, uint32_t a1, uint32_t a2, uint32_t a3, uint32_t b0, uint32_t b1) {
    asm("mma.sync.aligned.m16n8k16.row.col.f32.bf16.bf16.f32 {%0,%1,%2,%3}, {%4,%5,%6,%7}, {%8,%9}, {%0,%1,%2,%3};"
        : "+f"(c[0]), "+f"(c[1]), "+f"(c[2]), "+f"(c[3]) : "r"(a0), "r"(a1), "r"(a2), "r"(a3), "r"(b0), "r"(b1));
}
__device__ __forceinline__ void mma_1688(float (&c)[4], uint32_t a0, uint32_t a1, uint32_t b0) {
    asm("mma.sync.aligned.m16n8k8.row.col.f32.bf16.bf16.f32 {%0,%1,%2,%3}, {%4,%5}, {%6}, {%0,%1,%2,%3};"
        : "+f"(c[0]), "+f"(c[1]), "+f"(c[2]), "+f"(c[3]) : "r"(a0), "r"(a1), "r"(b0));
}
__device__ __forceinline__ void qk_tile(float (&c)[4], const uint4& q0, const uint4& q1, const uint4& k) {
    c[0] = c[1] = c[2] = c[3] = 0.f;
    mma_16816(c, q0.x, q0.y, q0.z, q0.w, k.x, k.y);
    mma_16816(c, q1.x, q1.y, q1.z, q1.w, k.z, k.w);
}
__device__ __forceinline__ uint32_t scaled_logits(float lo, float hi) {
    constexpr float SCALE = 0.17677669529663687f;
    const uint32_t p = pack_bf16(lo, hi);
    return pack_bf16(bf_lo(p) * SCALE, bf_hi(p) * SCALE);
}

__device__ __forceinline__ void attention(const CUtensorMap* map, uint32_t buf, uint32_t bars, int col0, int par, int lane) {
    constexpr float LOG2E = 1.4426950408889634f;
    auto load = [&](int step) {
        const int s = step % ATT_STAGES;
        mbar_expect_tx(bars + s * 8, ATT_STAGE_BYTES);
        tma_4d(buf + s * ATT_STAGE_BYTES, map, bars + s * 8, col0, step * 16, par);
    };
    if (lane == 0) for (int i = 0; i < ATT_STAGES; i++) load(i);
    const int g = lane >> 2, t = lane & 3;
    const bool up0 = 2 * t > g, up1 = 2 * t + 1 > g;
    const uint32_t keep = (up0 ? 0x0000ffffu : 0u) | (up1 ? 0xffff0000u : 0u);
    uint32_t mask0 = up0 ? 0xffffu : 0u, mask1 = up1 ? 0xffffu : 0u;
    const uint32_t neg = pack_bf16(-1e9f, 0.f);
    const uint32_t qoff = (lane & 15) * 128 + (((lane >> 4) ^ (lane & 7)) << 4);
    const uint32_t koff = 2048 + (lane & 7) * 128 + (((lane >> 3) ^ (lane & 7)) << 4);
    __nv_bfloat16* op = g_a2 + (size_t)(2 * g + par) * K2 + col0 + t * 8;
    uint4 k0[2], v0[2];
#pragma unroll
    for (int h = 0; h < 2; h++) { k0[h] = make_uint4(0, 0, 0, 0); v0[h] = make_uint4(0, 0, 0, 0); }
#pragma unroll 1
    for (int step = 0; step < ATT_STEPS; step++) {
        const int s = step % ATT_STAGES;
        const uint32_t st = buf + s * ATT_STAGE_BYTES;
        mbar_wait(bars + s * 8, (step / ATT_STAGES) & 1);
        uint4 q0[2], q1[2], k1[2], k2[2], v1[2], v2[2];
#pragma unroll
        for (int h = 0; h < 2; h++) {
            q0[h] = ldsm4(st + (qoff ^ (h * 64)));
            q1[h] = ldsm4(st + (qoff ^ (h * 64 + 32)));
            k1[h] = ldsm4(st + (koff ^ (h * 64)));
            k2[h] = ldsm4(st + 1024 + (koff ^ (h * 64)));
        }
#pragma unroll
        for (int h = 0; h < 2; h++) {
            v1[h] = ldsm4_t(st + 2048 + (koff ^ (h * 64)));
            v2[h] = ldsm4_t(st + 3072 + (koff ^ (h * 64)));
        }
        uint32_t pa[2], pb[2];
#pragma unroll
        for (int h = 0; h < 2; h++) {
            float s0[4], s1[4], s2[4];
            qk_tile(s0, q0[h], q1[h], k0[h]);
            qk_tile(s1, q0[h], q1[h], k1[h]);
            qk_tile(s2, q0[h], q1[h], k2[h]);
            k0[h] = k2[h];
            uint32_t l0 = scaled_logits(up0 ? s0[0] : s1[0], up0 ? s1[2] : s2[2]);
            uint32_t l1 = scaled_logits(up1 ? s0[1] : s1[1], up1 ? s1[3] : s2[3]);
            l0 = (l0 & ~mask0) | (neg & mask0);
            l1 = (l1 & ~mask1) | (neg & mask1);
            uint32_t m = max_bf16x2(l0, l1);
            m = max_bf16x2(m, __shfl_xor_sync(0xffffffffu, m, 1));
            m = max_bf16x2(m, __shfl_xor_sync(0xffffffffu, m, 2));
            const float ea0 = ex2_fast((bf_lo(l0) - bf_lo(m)) * LOG2E), ea1 = ex2_fast((bf_lo(l1) - bf_lo(m)) * LOG2E);
            const float eb0 = ex2_fast((bf_hi(l0) - bf_hi(m)) * LOG2E), eb1 = ex2_fast((bf_hi(l1) - bf_hi(m)) * LOG2E);
            float sa = ea0 + ea1, sb = eb0 + eb1;
            sa += __shfl_xor_sync(0xffffffffu, sa, 1); sb += __shfl_xor_sync(0xffffffffu, sb, 1);
            sa += __shfl_xor_sync(0xffffffffu, sa, 2); sb += __shfl_xor_sync(0xffffffffu, sb, 2);
            const float ra = rcp_fast(sa), rb = rcp_fast(sb);
            pa[h] = pack_bf16(ea0 * ra, ea1 * ra);
            pb[h] = pack_bf16(eb0 * rb, eb1 * rb);
        }
        mask0 = 0; mask1 = 0;
#pragma unroll
        for (int h = 0; h < 2; h++) {
            const uint32_t a0 = pa[h] & keep, a2 = pa[h] & ~keep, a3 = pb[h] & keep, a5 = pb[h] & ~keep;
            float o[4][4];
#pragma unroll
            for (int i = 0; i < 4; i++) o[i][0] = o[i][1] = o[i][2] = o[i][3] = 0.f;
            mma_16816(o[0], a0, 0u, a2, a3, v0[h].x, v1[h].x); mma_1688(o[0], 0u, a5, v2[h].x);
            mma_16816(o[1], a0, 0u, a2, a3, v0[h].y, v1[h].y); mma_1688(o[1], 0u, a5, v2[h].y);
            mma_16816(o[2], a0, 0u, a2, a3, v0[h].z, v1[h].z); mma_1688(o[2], 0u, a5, v2[h].z);
            mma_16816(o[3], a0, 0u, a2, a3, v0[h].w, v1[h].w); mma_1688(o[3], 0u, a5, v2[h].w);
            v0[h] = v2[h];
            *reinterpret_cast<uint4*>(op + h * 32) = make_uint4(pack_bf16(o[0][0], o[0][1]), pack_bf16(o[1][0], o[1][1]),
                                                                pack_bf16(o[2][0], o[2][1]), pack_bf16(o[3][0], o[3][1]));
            *reinterpret_cast<uint4*>(op + 16 * K2 + h * 32) = make_uint4(pack_bf16(o[0][2], o[0][3]), pack_bf16(o[1][2], o[1][3]),
                                                                          pack_bf16(o[2][2], o[2][3]), pack_bf16(o[3][2], o[3][3]));
        }
        op += 32 * K2;
        __syncwarp();
        if (lane == 0 && step + ATT_STAGES < ATT_STEPS) load(step + ATT_STAGES);
    }
}

__device__ __forceinline__ void warp_sum2(float& a, float& b) {
#pragma unroll
    for (int o = 16; o > 0; o >>= 1) {
        a += __shfl_xor_sync(0xffffffffu, a, o);
        b += __shfl_xor_sync(0xffffffffu, b, o);
    }
}
__device__ __forceinline__ float row_sum(const uint32_t* w) {
    float a = 0.f, b = 0.f;
#pragma unroll
    for (int i = 0; i < 16; i++) { a += bf_lo(w[i]); b += bf_hi(w[i]); }
    return a + b;
}
__device__ __forceinline__ float row_sq(const uint32_t* w, float mean) {
    float a = 0.f, b = 0.f;
#pragma unroll
    for (int i = 0; i < 16; i++) {
        const float lo = bf_lo(w[i]) - mean, hi = bf_hi(w[i]) - mean;
        a = fmaf(lo, lo, a); b = fmaf(hi, hi, b);
    }
    return a + b;
}
__device__ __forceinline__ float row_inv(float sq) {
    return 1.f / round_bf16(sqrtf(round_bf16(round_bf16(sq * (1.f / DM)) + 1e-5f)));
}
__device__ __forceinline__ void row_store(const uint32_t* w, float mean, float inv, int row, int lane) {
    const uint32_t m2 = pack_bf16(mean, mean);
    __nv_bfloat16* dst = g_xn + (size_t)row * DM + lane * 8;
#pragma unroll
    for (int i = 0; i < 4; i++) {
        uint32_t o[4];
#pragma unroll
        for (int j = 0; j < 4; j++) {
            const uint32_t c = sub_bf16x2(w[i * 4 + j], m2);
            o[j] = pack_bf16(bf_lo(c) * inv, bf_hi(c) * inv);
        }
        *reinterpret_cast<uint4*>(dst + i * 256) = make_uint4(o[0], o[1], o[2], o[3]);
    }
    if (lane == 0) g_stats[row] = make_float2(-bf_lo(m2), inv);
}

struct Params {
    CUtensorMap x, xn, wqkv, wg, wu, qkv, a2, wo, wd, out;
    const __nv_bfloat16 *px, *pwqkv, *pwg, *pwu;
};

__device__ __forceinline__ bool tile_is_qkv(int nt) { return nt < 4 || (nt >= 8 && nt < 16); }
__device__ __forceinline__ int tile_index(int nt) { return nt < 4 ? nt + 8 : (nt < 8 ? nt - 4 : (nt < 16 ? nt - 8 : nt - 12)); }

__global__ void __cluster_dims__(2, 1, 1) __launch_bounds__(384, 1)
fused_kernel(const __grid_constant__ Params prm) {
    extern __shared__ __align__(1024) uint8_t smem_raw[];
    const uint32_t base = (smem_u32(smem_raw) + 1023) & ~1023u;
    const uint32_t bars = base + BAR_OFF;
    auto full1 = [&](int s) { return bars + s * 8; };
    auto empty1 = [&](int s) { return bars + 32 + s * 8; };
    auto full2 = [&](int s) { return bars + 64 + s * 8; };
    auto empty2 = [&](int s) { return bars + 128 + s * 8; };
    const uint32_t sig_bar = bars + 192, fold_bar = bars + 200, x_bar = bars + 208;
    auto stage2 = [&](int q) { return base + q * G2_STAGE_BYTES; };
    const uint32_t aux = base + AUX_OFF;

    const int warp = __shfl_sync(0xffffffffu, threadIdx.x >> 5, 0);
    const int lane = threadIdx.x & 31;
    const int rank = blockIdx.x & 1;
    const int mblk = ((blockIdx.x >> 1) & 7) * 2 + rank;
    const int nslot = blockIdx.x >> 4;

    if (blockIdx.x >= NGEMM) {
        if (warp >= 8) return;
        const int grp = blockIdx.x - NGEMM;
        const uint32_t wbars = bars + warp * (ATT_STAGES * 8);
        unsigned epoch = 0;
        if (lane == 0) {
            if (warp == 0) { TRACE_GT(0); TRACE(1); }
            prefetch_map(&prm.qkv);
            for (int s = 0; s < ATT_STAGES; s++) mbar_init(wbars + s * 8, 1);
            epoch = __ldcg(g_epoch + blockIdx.x * 8 + warp) + 1;
            flag_wait(g_flags + F_QKV * 512 + grp * 32, epoch * CNT_QKV);
            fence_proxy_async();
            if (warp == 0) TRACE(9);
        }
        __syncwarp();
        attention(&prm.qkv, base + warp * (ATT_STAGES * ATT_STAGE_BYTES), wbars, grp * 256 + (warp & 3) * 64, warp >> 2, lane);
        if (lane == 0) {
            flag_add(g_flags + F_O * 512);
            g_epoch[blockIdx.x * 8 + warp] = epoch;
            if (warp == 0) TRACE(10);
        }
    } else if (warp >= 8) {
        unsigned* const flags = g_flags + mblk * 32;
        if (warp == 8) {
            if (lane == 0) {
                TRACE_GT(0); TRACE(1);
                prefetch_map(&prm.x); prefetch_map(nslot < 4 ? &prm.wqkv : (rank ? &prm.wu : &prm.wg));
                for (int s = 0; s < G1_STAGES; s++) { mbar_init(full1(s), 1); mbar_init(empty1(s), 4); }
                for (int s = 0; s < G2_STAGES; s++) { mbar_init(full2(s), 1); mbar_init(empty2(s), 4); }
                mbar_init(sig_bar, 8); mbar_init(fold_bar, 2); mbar_init(x_bar, 1);
                asm volatile("fence.mbarrier_init.release.cluster;" ::: "memory");
            }
            __syncwarp();
        }
        asm volatile("barrier.cluster.arrive.relaxed.aligned;" ::: "memory");
        if (warp == 8 && lane == 0) {
            asm volatile("fence.proxy.async.shared::cta;" ::: "memory");
            for (int s = 0; s < G1_STAGES; s++) {
                mbar_expect_tx(full1(s), G1_STAGE_BYTES);
                tma_2d(base + s * G1_STAGE_BYTES, &prm.x, full1(s), s * 64, mblk * 128);
            }
            TRACE(15);
        }
        asm volatile("setmaxnreg.dec.sync.aligned.u32 %0;" :: "n"(AUX_REGS));
        asm volatile("barrier.cluster.wait.acquire.aligned;" ::: "memory");
        auto load_epoch = [&]() { return __ldcg(g_epoch + blockIdx.x * 8) + 1; };

        if (warp == 8) {
            if (lane == 0) {
                TRACE(2);
                auto load_b1 = [&](int s, int nt, int k) {
                    const uint32_t dst = base + s * G1_STAGE_BYTES + A_BYTES + rank * 16384;
                    if (tile_is_qkv(nt)) tma_3d_mc(dst, &prm.wqkv, full1(s), k * 64, tile_index(nt) * 4 + rank * 2);
                    else tma_3d_mc(dst, rank ? &prm.wu : &prm.wg, full1(s), k * 64, tile_index(nt) * 2);
                };
                for (int s = 0; s < G1_STAGES; s++) load_b1(s, nslot, s);
                prefetch_map(&prm.xn); prefetch_map(&prm.wqkv); prefetch_map(rank ? &prm.wu : &prm.wg);
                prefetch_map(&prm.a2); prefetch_map(&prm.wo); prefetch_map(&prm.wd); prefetch_map(&prm.out);
                const unsigned epoch = load_epoch();
                uint32_t ph = 0;
                for (int it = G1_STAGES; it < G1_TILES * G1_KSTEPS; it++) {
                    const int s = it & 3, k = it & 15;
                    if (it == G1_KSTEPS) {
                        TRACE(14);
                        flag_wait(flags + F_LN * 512, epoch * CNT_LN);
                        fence_proxy_async();
                        TRACE(3);
                    }
                    mbar_wait(empty1(s), ph);
                    mbar_expect_tx(full1(s), G1_STAGE_BYTES);
                    tma_2d(base + s * G1_STAGE_BYTES, it < G1_KSTEPS ? &prm.x : &prm.xn, full1(s), k * 64, mblk * 128);
                    load_b1(s, (it >> 4) * 8 + nslot, k);
                    if (s == 3) ph ^= 1;
                }
                mbar_expect_tx(x_bar, 32768);
                tma_2d(aux, &prm.x, x_bar, nslot * 128, mblk * 128);
                tma_2d(aux + 16384, &prm.x, x_bar, nslot * 128 + 64, mblk * 128);
                TRACE(4);
                flag_wait(flags + F_EARLY * 512, epoch * CNT_EARLY);
                fence_proxy_async();
                TRACE(5);
                int q = 0; uint32_t ph2 = 1;
                for (int u = 0; u < G2_KSTEPS; u++) {
                    if (u == G2_LATE || u == G2_DSTEPS) {
                        TRACE(u == G2_LATE ? 6 : 32);
                        flag_wait(u == G2_LATE ? flags + F_LATE * 512 : g_flags + F_O * 512, epoch * (u == G2_LATE ? CNT_LATE : CNT_O));
                        fence_proxy_async();
                        TRACE(u == G2_LATE ? 7 : 33);
                    }
                    if (u < G2_STAGES) {
                        if (u == 0) mbar_wait(empty1(0), ph);
                        if (u == 1) mbar_wait(empty1(1), ph);
                        if (u == 3) mbar_wait(empty1(2), ph);
                        if (u == 4) mbar_wait(empty1(3), ph);
                    } else {
                        mbar_wait(empty2(q), ph2);
                    }
                    const uint32_t sa = stage2(q);
                    const bool down = u < G2_DSTEPS;
                    const int k = down ? u : u - G2_DSTEPS;
                    mbar_expect_tx(full2(q), G2_STAGE_BYTES);
                    tma_2d(sa, &prm.a2, full2(q), (down ? DM : 0) + k * 64, mblk * 128);
                    tma_5d_mc(sa + A_BYTES + rank * 8192, down ? &prm.wd : &prm.wo, full2(q), nslot * 128 + rank * 64, k * 2);
                    if (++q == G2_STAGES) { q = 0; ph2 ^= 1; }
                }
                g_epoch[blockIdx.x * 8] = epoch;
                TRACE(8);
            }
        } else if (warp == 9) {
            if (lane == 0) {
                mbar_wait(sig_bar, 0);
                TRACE(11);
                flag_add(flags + F_LN * 512);
                for (int t = 0; t < G1_TILES; t++) {
                    mbar_wait(sig_bar, (t + 1) & 1);
                    const int nt = t * 8 + nslot;
                    flag_add(tile_is_qkv(nt) ? g_flags + F_QKV * 512 + (nt & 3) * 32
                                             : flags + (t < G1_TILES - 1 ? F_EARLY : F_LATE) * 512);
                }
            }
        } else {
            const int w = warp - 10;
            const int ld = nslot < 4 ? NQKV : DF;
            const __nv_bfloat16* wp = nslot < 4 ? prm.pwqkv + 2 * DM + nslot * 256 + lane * 8
                                                : (lane < 16 ? prm.pwg : prm.pwu) + (nslot - 4) * 128 + (lane & 15) * 8;
            wp += (size_t)(mblk * 64 + w * 32) * ld;
            const unsigned epoch = load_epoch();
            float cs[8];
#pragma unroll
            for (int d = 0; d < 8; d++) cs[d] = 0.f;
            mbar_wait(full1(0), 0);
#pragma unroll 1
            for (int i = 0; i < 4; i++) {
                uint4 v[8];
#pragma unroll
                for (int j = 0; j < 8; j++) v[j] = __ldg(reinterpret_cast<const uint4*>(wp + (size_t)(i * 8 + j) * ld));
#pragma unroll
                for (int j = 0; j < 8; j++) {
                    float f[8];
                    unpack8(v[j], f);
#pragma unroll
                    for (int d = 0; d < 8; d++) cs[d] += f[d];
                }
            }
            float4* cp = reinterpret_cast<float4*>(g_colsum + (mblk * 2 + w) * 2048 + nslot * 256 + lane * 8);
            cp[0] = make_float4(cs[0], cs[1], cs[2], cs[3]);
            cp[1] = make_float4(cs[4], cs[5], cs[6], cs[7]);
            __syncwarp();
            if (lane == 0) {
                if (w == 0) TRACE(34);
                flag_add(g_flags + F_CS * 512 + nslot * 32);
                flag_wait(g_flags + F_CS * 512 + nslot * 32, epoch * CNT_CS);
            }
            __syncwarp();
            const float4* gp = reinterpret_cast<const float4*>(g_colsum + nslot * 256 + w * 128) + lane;
            float4 c = make_float4(0.f, 0.f, 0.f, 0.f);
#pragma unroll 8
            for (int m = 0; m < 32; m++) {
                const float4 a = __ldcg(gp + m * 512);
                c.x += a.x; c.y += a.y; c.z += a.z; c.w += a.w;
            }
            const uint32_t ca = aux + (w * 8 + (lane >> 2)) * 64 + (lane & 1) * 32 + (lane & 2) * 4;
            sts64f(ca, c.x, c.y);
            sts64f(ca + 16, c.z, c.w);
            if (lane == 0) flag_wait(flags + F_LN * 512, epoch * CNT_LN);
            __syncwarp();
            sts128(aux + 1024 + w * 512 + lane * 16, __ldcg(reinterpret_cast<const uint4*>(g_stats + mblk * 128 + w * 64) + lane));
            __syncwarp();
            if (lane == 0) { mbar_arrive(fold_bar); if (w == 0) TRACE(35); }
        }
    } else {
        asm volatile("barrier.cluster.arrive.relaxed.aligned;" ::: "memory");
        asm volatile("setmaxnreg.inc.sync.aligned.u32 %0;" :: "n"(CONSUMER_REGS));
        const int wg = __shfl_sync(0xffffffffu, threadIdx.x >> 7, 0);
        const int cw = threadIdx.x >> 5;
        const int tid = threadIdx.x & 127;
        float acc[128];
        uint32_t pk[64];
#pragma unroll
        for (int i = 0; i < 64; i++) asm volatile("mov.b32 %0, 0;" : "=r"(pk[i]));
#pragma unroll
        for (int i = 0; i < 128; i++) asm volatile("mov.b32 %0, 0;" : "=f"(acc[i]));
        asm volatile("barrier.cluster.wait.acquire.aligned;" ::: "memory");

        const int orow = mblk * 128 + cw * 16 + (lane >> 2);
        __nv_bfloat16* optr = nullptr;
        auto release = [&](uint32_t bar) { if (tid < 2) mbar_arrive_cluster(bar, tid); };
        auto chunk_geglu = [&](int j) {
            const int c = j >> 1, h = j & 1;
            uint4 v;
            v.x = geglu2(pk[8 * c + h], pk[32 + 8 * c + h]);
            v.y = geglu2(pk[8 * c + 2 + h], pk[32 + 8 * c + 2 + h]);
            v.z = geglu2(pk[8 * c + 4 + h], pk[32 + 8 * c + 4 + h]);
            v.w = geglu2(pk[8 * c + 6 + h], pk[32 + 8 * c + 6 + h]);
            *reinterpret_cast<uint4*>(optr + h * 8 * K2 + c * 32) = v;
        };
        auto chunk_qkv = [&](int c) {
            *reinterpret_cast<uint4*>(optr + c * 32) = make_uint4(pk[8 * c], pk[8 * c + 2], pk[8 * c + 4], pk[8 * c + 6]);
            *reinterpret_cast<uint4*>(optr + 8 * NQKV + c * 32) = make_uint4(pk[8 * c + 1], pk[8 * c + 3], pk[8 * c + 5], pk[8 * c + 7]);
        };
        auto signal_stores = [&]() { __syncwarp(); if (lane == 0) mbar_arrive(sig_bar); };

        auto chunk_ln = [&](int k) {
            const int row = mblk * 128 + nslot * 16 + cw * 2;
            if (k == 0) {
                const uint4* xp = reinterpret_cast<const uint4*>(prm.px + (size_t)row * DM) + lane;
#pragma unroll
                for (int i = 0; i < 8; i++) {
                    const uint4 v = __ldg(xp + i * 32);
                    pk[4 * i] = v.x; pk[4 * i + 1] = v.y; pk[4 * i + 2] = v.z; pk[4 * i + 3] = v.w;
                }
            } else if (k == 3) {
                float a = row_sum(pk), b = row_sum(pk + 16);
                warp_sum2(a, b);
                pk[32] = __float_as_uint(a * (1.f / DM)); pk[33] = __float_as_uint(b * (1.f / DM));
            } else if (k == 4) {
                pk[34] = __float_as_uint(row_sq(pk, __uint_as_float(pk[32])));
            } else if (k == 5) {
                float a = __uint_as_float(pk[34]), b = row_sq(pk + 16, __uint_as_float(pk[33]));
                warp_sum2(a, b);
                pk[34] = __float_as_uint(a); pk[35] = __float_as_uint(b);
            } else if (k == 6) {
                row_store(pk, __uint_as_float(pk[32]), row_inv(__uint_as_float(pk[34])), row, lane);
            } else if (k == 7) {
                row_store(pk + 16, __uint_as_float(pk[33]), row_inv(__uint_as_float(pk[35])), row + 1, lane);
                signal_stores();
            }
        };

        int pending = 0;
#pragma unroll 1
        for (int t = 0; t < G1_TILES; t++) {
#pragma unroll
            for (int k = 0; k < G1_KSTEPS; k++) {
                const int s = k & 3;
                mbar_wait(full1(s), (k >> 2) & 1);
                if (t == 0 && k == 0 && threadIdx.x == 0) TRACE(12);
                if (wg == 1 && k == G1_KSTEPS - G1_SKEW) asm volatile("bar.sync 1, 256;" ::: "memory");
                const uint64_t da = desc_a(base + s * G1_STAGE_BYTES + wg * 8192);
                const uint64_t db = desc_b(base + s * G1_STAGE_BYTES + A_BYTES);
                wg_fence();
#pragma unroll
                for (int kk = 0; kk < 4; kk++) wgmma_n256(acc, da + kk * 2, db + kk * 128, (k | kk) != 0);
                wg_commit();
                if (wg == 0 && k == G1_KSTEPS - 1) asm volatile("bar.arrive 1, 256;" ::: "memory");
                if (k <= 7 && pending == 0) chunk_ln(k);
                if (k >= 1 && k <= 8) {
                    if (pending == 2) chunk_geglu(k - 1);
                    else if (pending == 1) chunk_qkv(k - 1);
                    if (k == 8 && pending) signal_stores();
                }
                wg_wait<1>();
                if (k > 0) release(empty1((k - 1) & 3));
            }
            if (t == 0) mbar_wait(fold_bar, 0);
            wg_wait<0>();
            fence_regs(acc);
            release(empty1(3));
            if (t == 0) {
                const uint32_t sp = aux + 1024 + (cw * 16 + (lane >> 2)) * 8;
                const float2 sa = lds64f(sp), sb = lds64f(sp + 64);
#pragma unroll
                for (int j = 0; j < 16; j++) {
                    const uint4 c = lds128(aux + j * 64 + (lane & 3) * 16);
                    const float c0 = __uint_as_float(c.x), c1 = __uint_as_float(c.y);
                    const float c2 = __uint_as_float(c.z), c3 = __uint_as_float(c.w);
                    const float* a = acc + 8 * j;
                    pk[4 * j] = pack_bf16(fmaf(sa.x, c0, a[0]) * sa.y, fmaf(sa.x, c1, a[1]) * sa.y);
                    pk[4 * j + 1] = pack_bf16(fmaf(sb.x, c0, a[2]) * sb.y, fmaf(sb.x, c1, a[3]) * sb.y);
                    pk[4 * j + 2] = pack_bf16(fmaf(sa.x, c2, a[4]) * sa.y, fmaf(sa.x, c3, a[5]) * sa.y);
                    pk[4 * j + 3] = pack_bf16(fmaf(sb.x, c2, a[6]) * sb.y, fmaf(sb.x, c3, a[7]) * sb.y);
                }
            } else {
#pragma unroll
                for (int i = 0; i < 64; i++) pk[i] = pack_bf16(acc[2 * i], acc[2 * i + 1]);
            }
            const int nt = t * 8 + nslot;
            pending = tile_is_qkv(nt) ? 1 : 2;
            optr = pending == 1 ? g_qkv + (size_t)orow * NQKV + tile_index(nt) * 256 + (lane & 3) * 8
                                : g_a2 + (size_t)orow * K2 + DM + tile_index(nt) * 128 + (lane & 3) * 8;
            if (tid == 0) TRACE(16 + wg * 8 + t);
        }

        float accd[64], accs[64];
#pragma unroll
        for (int i = 0; i < 64; i++) accd[i] = 0.f;
#pragma unroll
        for (int u = 0; u < 9; u++) {
            const int q = u % G2_STAGES;
            mbar_wait(full2(q), (u / G2_STAGES) & 1);
            const uint64_t da = desc_a(stage2(q) + wg * 8192), db = desc_b(stage2(q) + A_BYTES);
            wg_fence();
#pragma unroll
            for (int kk = 0; kk < 4; kk++) wgmma_n128(accd, da + kk * 2, db + kk * 128, (u | kk) != 0);
            wg_commit();
            if (u >= 1) { chunk_geglu(u - 1); if (u == 8) signal_stores(); }
            wg_wait<1>();
            if (u > 0) release(empty2((u - 1) % G2_STAGES));
        }
        {
            int q = 9 % G2_STAGES, qp = 8 % G2_STAGES; uint32_t ph = (9 / G2_STAGES) & 1;
#pragma unroll 1
            for (int u = 9; u < G2_DSTEPS; u++) {
                mbar_wait(full2(q), ph);
                const uint64_t da = desc_a(stage2(q) + wg * 8192), db = desc_b(stage2(q) + A_BYTES);
                wg_fence();
#pragma unroll
                for (int kk = 0; kk < 4; kk++) wgmma_n128(accd, da + kk * 2, db + kk * 128, 1);
                wg_commit();
                wg_wait<1>();
                release(empty2(qp));
                qp = q;
                if (++q == G2_STAGES) { q = 0; ph ^= 1; }
            }
        }
        if (tid == 0) TRACE(16 + wg * 8 + 5);
#pragma unroll
        for (int i = 0; i < 64; i++) accs[i] = 0.f;
        uint32_t gk[32], xr[32];
        const uint32_t xs = aux + cw * 2048;
        const uint32_t xrow = xs + ((lane & 7) + ((lane >> 3) & 1) * 8) * 128;
        auto xaddr = [&](int j) { return xrow + (j >> 2) * 16384 + (((((j & 3) * 2) + (lane >> 4)) ^ (lane & 7)) << 4); };
#pragma unroll
        for (int u = G2_DSTEPS; u < G2_KSTEPS; u++) {
            const int q = u % G2_STAGES, v = u - G2_DSTEPS;
            mbar_wait(full2(q), (u / G2_STAGES) & 1);
            if (G2_SKEW > 0 && wg == 1 && u == G2_KSTEPS - G2_SKEW) asm volatile("bar.sync 1, 256;" ::: "memory");
            const uint64_t da = desc_a(stage2(q) + wg * 8192), db = desc_b(stage2(q) + A_BYTES);
            wg_fence();
#pragma unroll
            for (int kk = 0; kk < 4; kk++) wgmma_n128(accs, da + kk * 2, db + kk * 128, (v | kk) != 0);
            wg_commit();
            if (G2_SKEW > 0 && wg == 0 && u == G2_KSTEPS - 1) asm volatile("bar.arrive 1, 256;" ::: "memory");
            if (v >= 1 && v <= 8) {
#pragma unroll
                for (int i = 4 * (v - 1); i < 4 * v; i++) {
                    const uint32_t d2 = pack_bf16(accd[2 * i], accd[2 * i + 1]);
                    gk[i] = pack_bf16(silu(bf_lo(d2)), silu(bf_hi(d2)));
                }
            }
            if (v == 9) mbar_wait(x_bar, 0);
            if (v >= 9 && v <= 12) {
#pragma unroll
                for (int j = 2 * (v - 9); j < 2 * (v - 8); j++)
                    asm volatile("ldmatrix.sync.aligned.m8n8.x4.shared.b16 {%0,%1,%2,%3}, [%4];"
                                 : "=r"(xr[4 * j]), "=r"(xr[4 * j + 1]), "=r"(xr[4 * j + 2]), "=r"(xr[4 * j + 3])
                                 : "r"(xaddr(j)) : "memory");
            }
            wg_wait<1>();
            if (v == 0) fence_regs(accd);
            if (u - 1 + G2_STAGES < G2_KSTEPS) release(empty2((u - 1) % G2_STAGES));
        }
        wg_wait<0>();
        fence_regs(accs);
        if (tid == 0) TRACE(16 + wg * 8 + 6);
#pragma unroll
        for (int j = 0; j < 8; j++) {
            uint32_t r[4];
#pragma unroll
            for (int i = 0; i < 4; i++) {
                const int e = j * 4 + i;
                r[i] = add_bf16x2(xr[e], mul_bf16x2(pack_bf16(accs[2 * e], accs[2 * e + 1]), gk[e]));
            }
            asm volatile("stmatrix.sync.aligned.m8n8.x4.shared.b16 [%0], {%1,%2,%3,%4};"
                         :: "r"(xaddr(j)), "r"(r[0]), "r"(r[1]), "r"(r[2]), "r"(r[3]) : "memory");
            if (j == 3 || j == 7) {
                asm volatile("fence.proxy.async.shared::cta;" ::: "memory");
                __syncwarp();
                if (lane == 0) {
                    tma_store_2d(&prm.out, xs + (j >> 2) * 16384, nslot * 128 + (j >> 2) * 64, mblk * 128 + cw * 16);
                    asm volatile("cp.async.bulk.commit_group;" ::: "memory");
                }
            }
        }
        if (lane == 0) asm volatile("cp.async.bulk.wait_group.read 0;" ::: "memory");
        if (tid == 0) { TRACE(16 + wg * 8 + 7); if (wg == 1) TRACE_GT(13); }
    }
}

typedef CUresult (*EncodeFn)(CUtensorMap*, CUtensorMapDataType, cuuint32_t, void*, const cuuint64_t*, const cuuint64_t*,
                             const cuuint32_t*, const cuuint32_t*, CUtensorMapInterleave, CUtensorMapSwizzle,
                             CUtensorMapL2promotion, CUtensorMapFloatOOBfill);

void encode(EncodeFn fn, CUtensorMap* m, const void* ptr, int rank, const cuuint64_t* dims, const cuuint64_t* strides,
            const cuuint32_t* box) {
    const cuuint32_t es[5] = {1, 1, 1, 1, 1};
    fn(m, CU_TENSOR_MAP_DATA_TYPE_BFLOAT16, rank, const_cast<void*>(ptr), dims, strides, box, es,
       CU_TENSOR_MAP_INTERLEAVE_NONE, CU_TENSOR_MAP_SWIZZLE_128B, CU_TENSOR_MAP_L2_PROMOTION_L2_128B,
       CU_TENSOR_MAP_FLOAT_OOB_FILL_NONE);
}
void encode_2d(EncodeFn fn, CUtensorMap* m, const void* ptr, int cols, int box_rows) {
    const cuuint64_t dims[2] = {(cuuint64_t)cols, SEQ}, strides[1] = {(cuuint64_t)cols * 2};
    const cuuint32_t box[2] = {64, (cuuint32_t)box_rows};
    encode(fn, m, ptr, 2, dims, strides, box);
}
void encode_w1(EncodeFn fn, CUtensorMap* m, const void* ptr, int cols) {
    const cuuint64_t dims[3] = {64, DM, (cuuint64_t)cols / 64}, strides[2] = {(cuuint64_t)cols * 2, 128};
    const cuuint32_t box[3] = {64, 64, 2};
    encode(fn, m, ptr, 3, dims, strides, box);
}
void encode_qkv(EncodeFn fn, CUtensorMap* m, const void* ptr) {
    const cuuint64_t dims[4] = {DM, SEQ / 2, 3, 2}, strides[3] = {NQKV * 4, DM * 2, NQKV * 2};
    const cuuint32_t box[4] = {64, 16, 3, 1};
    encode(fn, m, ptr, 4, dims, strides, box);
}
void encode_w2(EncodeFn fn, CUtensorMap* m, const void* ptr, int rows, bool permuted) {
    const cuuint64_t rb = DM * 2;
    const cuuint64_t dims[5] = {DM, 2, 4, 4, (cuuint64_t)rows / 32};
    const cuuint64_t strides[4] = {rb, (permuted ? 8 : 2) * rb, (permuted ? 2 : 8) * rb, 32 * rb};
    const cuuint32_t box[5] = {64, 2, 4, 4, 2};
    encode(fn, m, ptr, 5, dims, strides, box);
}

}

extern "C" void kernel_launch(void* const* d_in, const int* in_sizes, int n_in, void* d_out, int out_size) {
    (void)in_sizes; (void)n_in; (void)out_size;
    static EncodeFn fn = nullptr;
    static void *p_xn = nullptr, *p_qkv = nullptr, *p_a2 = nullptr;
    if (!fn) {
        cudaDriverEntryPointQueryResult st;
        cudaGetDriverEntryPoint("cuTensorMapEncodeTiled", (void**)&fn, cudaEnableDefault, &st);
        cudaGetSymbolAddress(&p_xn, g_xn);
        cudaGetSymbolAddress(&p_qkv, g_qkv);
        cudaGetSymbolAddress(&p_a2, g_a2);
        cudaFuncSetAttribute(fused_kernel, cudaFuncAttributeMaxDynamicSharedMemorySize, SMEM_BYTES);
    }
    Params prm;
    encode_2d(fn, &prm.x, d_in[0], DM, 128);
    encode_2d(fn, &prm.xn, p_xn, DM, 128);
    encode_w1(fn, &prm.wqkv, d_in[1], NQKV);
    encode_w1(fn, &prm.wg, d_in[4], DF);
    encode_w1(fn, &prm.wu, d_in[5], DF);
    encode_qkv(fn, &prm.qkv, p_qkv);
    encode_2d(fn, &prm.a2, p_a2, K2, 128);
    encode_w2(fn, &prm.wo, d_in[2], DM, false);
    encode_w2(fn, &prm.wd, d_in[6], DF, true);
    encode_2d(fn, &prm.out, d_out, DM, 16);
    prm.px = (const __nv_bfloat16*)d_in[0];
    prm.pwqkv = (const __nv_bfloat16*)d_in[1];
    prm.pwg = (const __nv_bfloat16*)d_in[4];
    prm.pwu = (const __nv_bfloat16*)d_in[5];
    fused_kernel<<<NCTA, 384, SMEM_BYTES>>>(prm);
}
```

```cpp
#include <cuda_runtime.h>
#include <cuda_bf16.h>
#include <cuda.h>
#include <stdint.h>

namespace {

constexpr int SEQ = 2048, DM = 1024, DF = 3584, K2 = DM + DF, NQKV = 3 * DM;
constexpr int NGEMM = 128, NCTA = 132;
constexpr int G1_STAGES = 4, G1_STAGE_BYTES = 49152, G1_KSTEPS = 16, G1_TILES = 5;
constexpr int G2_STAGES = 6, G2_STAGE_BYTES = 32768, G2_KSTEPS = 72, G2_DSTEPS = 56, G2_LATE = 40;
constexpr int A_BYTES = 16384;
constexpr int AUX_OFF = G1_STAGES * G1_STAGE_BYTES;
constexpr int BAR_OFF = AUX_OFF + 32768;
constexpr int SMEM_BYTES = BAR_OFF + 1024 + 256;
constexpr int G1_SKEW = 2, G2_SKEW = 2;
constexpr int CONSUMER_REGS = 224, AUX_REGS = 56;
constexpr int ATT_STEPS = 32;

enum { F_LN = 0, F_QKV = 1, F_EARLY = 2, F_LATE = 3, F_O = 4, F_CS = 5 };
constexpr unsigned CNT_LN = 8, CNT_QKV = 48, CNT_EARLY = 20, CNT_LATE = 8, CNT_O = 4, CNT_CS = 32;

__device__ __align__(1024) __nv_bfloat16 g_xn[SEQ * DM];
__device__ __align__(1024) __nv_bfloat16 g_qkv[SEQ * NQKV];
__device__ __align__(1024) __nv_bfloat16 g_a2[SEQ * K2];
__device__ __align__(128) float2 g_stats[SEQ];
__device__ __align__(128) float g_colsum[32 * 2048];
__device__ __align__(128) unsigned g_flags[6 * 16 * 32];
__device__ __align__(128) unsigned g_epoch[NCTA * 8];

#define TRACE(slot) do {} while (0)
#define TRACE_GT(slot) do {} while (0)

__device__ __forceinline__ uint32_t smem_u32(const void* p) { return (uint32_t)__cvta_generic_to_shared(p); }
__device__ __forceinline__ void mbar_init(uint32_t bar, uint32_t cnt) {
    asm volatile("mbarrier.init.shared::cta.b64 [%0], %1;" :: "r"(bar), "r"(cnt) : "memory");
}
__device__ __forceinline__ void mbar_expect_tx(uint32_t bar, uint32_t bytes) {
    asm volatile("mbarrier.arrive.expect_tx.shared::cta.b64 _, [%0], %1;" :: "r"(bar), "r"(bytes) : "memory");
}
__device__ __forceinline__ void mbar_arrive(uint32_t bar) {
    asm volatile("mbarrier.arrive.shared::cta.b64 _, [%0];" :: "r"(bar) : "memory");
}
__device__ __forceinline__ void mbar_arrive_cluster(uint32_t bar, uint32_t cta) {
    asm volatile("{\n.reg .b32 ra;\nmapa.shared::cluster.u32 ra, %0, %1;\nmbarrier.arrive.shared::cluster.b64 _, [ra];\n}"
                 :: "r"(bar), "r"(cta) : "memory");
}
__device__ __forceinline__ bool mbar_try_wait(uint32_t bar, uint32_t parity) {
    uint32_t ok;
    asm volatile("{\n.reg .pred p;\nmbarrier.try_wait.parity.shared::cta.b64 p, [%1], %2;\nselp.u32 %0, 1, 0, p;\n}"
                 : "=r"(ok) : "r"(bar), "r"(parity) : "memory");
    return ok;
}
__device__ __forceinline__ void mbar_wait(uint32_t bar, uint32_t parity) {
    int spins = 0;
    while (!mbar_try_wait(bar, parity)) { if (++spins > (1 << 17)) break; }
}
__device__ __forceinline__ void flag_wait(const unsigned* p, unsigned target) {
    for (int spins = 0; spins < (1 << 19); spins++) {
        unsigned v;
        asm volatile("ld.acquire.gpu.global.u32 %0, [%1];" : "=r"(v) : "l"(p) : "memory");
        if ((int)(v - target) >= 0) break;
        __nanosleep(64);
    }
}
__device__ __forceinline__ void flag_add(unsigned* p) {
    asm volatile("red.release.gpu.global.add.u32 [%0], 1;" :: "l"(p) : "memory");
}
__device__ __forceinline__ void fence_proxy_async() { asm volatile("fence.proxy.async;" ::: "memory"); }
__device__ __forceinline__ uint4 lds128(uint32_t addr) {
    uint4 v;
    asm volatile("ld.shared.v4.u32 {%0,%1,%2,%3}, [%4];" : "=r"(v.x), "=r"(v.y), "=r"(v.z), "=r"(v.w) : "r"(addr) : "memory");
    return v;
}
__device__ __forceinline__ float2 lds64f(uint32_t addr) {
    float2 v;
    asm volatile("ld.shared.v2.f32 {%0,%1}, [%2];" : "=f"(v.x), "=f"(v.y) : "r"(addr) : "memory");
    return v;
}
__device__ __forceinline__ void sts128(uint32_t addr, uint4 v) {
    asm volatile("st.shared.v4.u32 [%0], {%1,%2,%3,%4};" :: "r"(addr), "r"(v.x), "r"(v.y), "r"(v.z), "r"(v.w) : "memory");
}
__device__ __forceinline__ void sts64f(uint32_t addr, float a, float b) {
    asm volatile("st.shared.v2.f32 [%0], {%1,%2};" :: "r"(addr), "f"(a), "f"(b) : "memory");
}

__device__ __forceinline__ void tma_2d(uint32_t dst, const CUtensorMap* m, uint32_t bar, int c0, int c1) {
    asm volatile("cp.async.bulk.tensor.2d.shared::cluster.global.mbarrier::complete_tx::bytes [%0], [%1, {%3, %4}], [%2];"
                 :: "r"(dst), "l"(m), "r"(bar), "r"(c0), "r"(c1) : "memory");
}
__device__ __forceinline__ void tma_5d(uint32_t dst, const CUtensorMap* m, uint32_t bar, int c1, int c4) {
    asm volatile("cp.async.bulk.tensor.5d.shared::cluster.global.mbarrier::complete_tx::bytes [%0], [%1, {%3, %4, %3, %3, %5}], [%2];"
                 :: "r"(dst), "l"(m), "r"(bar), "r"(0), "r"(c1), "r"(c4) : "memory");
}
__device__ __forceinline__ void tma_store_4d(const CUtensorMap* m, uint32_t src, int c1, int c3) {
    asm volatile("cp.async.bulk.tensor.4d.global.shared::cta.bulk_group [%0, {%2, %3, %2, %4}], [%1];"
                 :: "l"(m), "r"(src), "r"(0), "r"(c1), "r"(c3) : "memory");
}
__device__ __forceinline__ void tma_3d_mc(uint32_t dst, const CUtensorMap* m, uint32_t bar, int c1, int c2) {
    asm volatile("cp.async.bulk.tensor.3d.shared::cluster.global.mbarrier::complete_tx::bytes.multicast::cluster"
                 " [%0], [%1, {%3, %4, %5}], [%2], %6;"
                 :: "r"(dst), "l"(m), "r"(bar), "r"(0), "r"(c1), "r"(c2), "h"((uint16_t)3) : "memory");
}
__device__ __forceinline__ void tma_5d_mc(uint32_t dst, const CUtensorMap* m, uint32_t bar, int c0, int c4) {
    asm volatile("cp.async.bulk.tensor.5d.shared::cluster.global.mbarrier::complete_tx::bytes.multicast::cluster"
                 " [%0], [%1, {%3, %4, %4, %4, %5}], [%2], %6;"
                 :: "r"(dst), "l"(m), "r"(bar), "r"(c0), "r"(0), "r"(c4), "h"((uint16_t)3) : "memory");
}
__device__ __forceinline__ void tma_store_2d(const CUtensorMap* m, uint32_t src, int c0, int c1) {
    asm volatile("cp.async.bulk.tensor.2d.global.shared::cta.bulk_group [%0, {%2, %3}], [%1];"
                 :: "l"(m), "r"(src), "r"(c0), "r"(c1) : "memory");
}
__device__ __forceinline__ void prefetch_map(const CUtensorMap* m) {
    asm volatile("prefetch.tensormap [%0];" :: "l"(m) : "memory");
}
__device__ __forceinline__ void wg_fence() { asm volatile("wgmma.fence.sync.aligned;" ::: "memory"); }
__device__ __forceinline__ void wg_commit() { asm volatile("wgmma.commit_group.sync.aligned;" ::: "memory"); }
template <int N> __device__ __forceinline__ void wg_wait() { asm volatile("wgmma.wait_group.sync.aligned %0;" :: "n"(N) : "memory"); }

__device__ __forceinline__ uint64_t desc_a(uint32_t addr) {
    return (uint64_t)((addr & 0x3FFFF) >> 4) | (1ull << 16) | (64ull << 32) | (1ull << 62);
}
__device__ __forceinline__ uint64_t desc_b(uint32_t addr) {
    return (uint64_t)((addr & 0x3FFFF) >> 4) | (512ull << 16) | (64ull << 32) | (1ull << 62);
}

#define R8(d, o) "+f"(d[o]), "+f"(d[o+1]), "+f"(d[o+2]), "+f"(d[o+3]), "+f"(d[o+4]), "+f"(d[o+5]), "+f"(d[o+6]), "+f"(d[o+7])
#define R32(d, o) R8(d, o), R8(d, o+8), R8(d, o+16), R8(d, o+24)
#define R64(d, o) R32(d, o), R32(d, o+32)

__device__ __forceinline__ void wgmma_n256(float (&d)[128], uint64_t da, uint64_t db, int scale_d) {
    asm volatile("{\n.reg .pred p;\nsetp.ne.b32 p, %130, 0;\n"
        "wgmma.mma_async.sync.aligned.m64n256k16.f32.bf16.bf16 "
        "{%0,%1,%2,%3,%4,%5,%6,%7,%8,%9,%10,%11,%12,%13,%14,%15,%16,%17,%18,%19,%20,%21,%22,%23,%24,%25,%26,%27,%28,%29,%30,%31,"
        "%32,%33,%34,%35,%36,%37,%38,%39,%40,%41,%42,%43,%44,%45,%46,%47,%48,%49,%50,%51,%52,%53,%54,%55,%56,%57,%58,%59,%60,%61,%62,%63,"
        "%64,%65,%66,%67,%68,%69,%70,%71,%72,%73,%74,%75,%76,%77,%78,%79,%80,%81,%82,%83,%84,%85,%86,%87,%88,%89,%90,%91,%92,%93,%94,%95,"
        "%96,%97,%98,%99,%100,%101,%102,%103,%104,%105,%106,%107,%108,%109,%110,%111,%112,%113,%114,%115,%116,%117,%118,%119,%120,%121,%122,%123,%124,%125,%126,%127},"
        " %128, %129, p, 1, 1, 0, 1;\n}"
        : R64(d, 0), R64(d, 64) : "l"(da), "l"(db), "r"(scale_d));
}
__device__ __forceinline__ void wgmma_n128(float (&d)[64], uint64_t da, uint64_t db, int scale_d) {
    asm volatile("{\n.reg .pred p;\nsetp.ne.b32 p, %66, 0;\n"
        "wgmma.mma_async.sync.aligned.m64n128k16.f32.bf16.bf16 "
        "{%0,%1,%2,%3,%4,%5,%6,%7,%8,%9,%10,%11,%12,%13,%14,%15,%16,%17,%18,%19,%20,%21,%22,%23,%24,%25,%26,%27,%28,%29,%30,%31,"
        "%32,%33,%34,%35,%36,%37,%38,%39,%40,%41,%42,%43,%44,%45,%46,%47,%48,%49,%50,%51,%52,%53,%54,%55,%56,%57,%58,%59,%60,%61,%62,%63},"
        " %64, %65, p, 1, 1, 0, 1;\n}"
        : R64(d, 0) : "l"(da), "l"(db), "r"(scale_d));
}

__device__ __forceinline__ uint32_t pack_bf16(float lo, float hi) {
    uint32_t r; asm("cvt.rn.bf16x2.f32 %0, %1, %2;" : "=r"(r) : "f"(hi), "f"(lo)); return r;
}
__device__ __forceinline__ float bf_lo(uint32_t v) { return __uint_as_float(v << 16); }
__device__ __forceinline__ float bf_hi(uint32_t v) { return __uint_as_float(v & 0xffff0000u); }
__device__ __forceinline__ float round_bf16(float v) { return bf_lo(pack_bf16(v, 0.f)); }
__device__ __forceinline__ uint32_t mul_bf16x2(uint32_t a, uint32_t b) {
    uint32_t r; asm("mul.rn.bf16x2 %0, %1, %2;" : "=r"(r) : "r"(a), "r"(b)); return r;
}
__device__ __forceinline__ uint32_t add_bf16x2(uint32_t a, uint32_t b) {
    uint32_t r; asm("add.rn.bf16x2 %0, %1, %2;" : "=r"(r) : "r"(a), "r"(b)); return r;
}
__device__ __forceinline__ uint32_t sub_bf16x2(uint32_t a, uint32_t b) {
    uint32_t r; asm("sub.rn.bf16x2 %0, %1, %2;" : "=r"(r) : "r"(a), "r"(b)); return r;
}
__device__ __forceinline__ float tanh_fast(float x) { float r; asm("tanh.approx.f32 %0, %1;" : "=f"(r) : "f"(x)); return r; }
__device__ __forceinline__ float gelu_tanh(float g) {
    float t = fmaf(g * g, 0.044715f * 0.7978845608f, 0.7978845608f) * g;
    float hg = 0.5f * g;
    return fmaf(hg, tanh_fast(t), hg);
}
__device__ __forceinline__ uint32_t geglu2(uint32_t g2, uint32_t u2) {
    return mul_bf16x2(pack_bf16(gelu_tanh(bf_lo(g2)), gelu_tanh(bf_hi(g2))), u2);
}
__device__ __forceinline__ float silu(float d) {
    float hd = 0.5f * d;
    return fmaf(hd, tanh_fast(hd), hd);
}
__device__ __forceinline__ float ex2_fast(float x) { float r; asm("ex2.approx.ftz.f32 %0, %1;" : "=f"(r) : "f"(x)); return r; }
__device__ __forceinline__ void unpack8(uint4 v, float (&f)[8]) {
    f[0] = bf_lo(v.x); f[1] = bf_hi(v.x); f[2] = bf_lo(v.y); f[3] = bf_hi(v.y);
    f[4] = bf_lo(v.z); f[5] = bf_hi(v.z); f[6] = bf_lo(v.w); f[7] = bf_hi(v.w);
}
template <int N> __device__ __forceinline__ void fence_regs(float (&d)[N]) {
#pragma unroll
    for (int i = 0; i < N; i++) asm volatile("" : "+f"(d[i]) :: "memory");
}

__device__ __forceinline__ float rcp_fast(float x) { float r; asm("rcp.approx.ftz.f32 %0, %1;" : "=f"(r) : "f"(x)); return r; }
__device__ __forceinline__ uint32_t max_bf16x2(uint32_t a, uint32_t b) {
    uint32_t r; asm("max.bf16x2 %0, %1, %2;" : "=r"(r) : "r"(a), "r"(b)); return r;
}
__device__ __forceinline__ uint4 ldsm4(uint32_t addr) {
    uint4 v;
    asm volatile("ldmatrix.sync.aligned.m8n8.x4.shared.b16 {%0,%1,%2,%3}, [%4];"
                 : "=r"(v.x), "=r"(v.y), "=r"(v.z), "=r"(v.w) : "r"(addr) : "memory");
    return v;
}
__device__ __forceinline__ uint4 ldsm4_t(uint32_t addr) {
    uint4 v;
    asm volatile("ldmatrix.sync.aligned.m8n8.x4.trans.shared.b16 {%0,%1,%2,%3}, [%4];"
                 : "=r"(v.x), "=r"(v.y), "=r"(v.z), "=r"(v.w) : "r"(addr) : "memory");
    return v;
}
__device__ __forceinline__ void mma_16816(float (&c)[4], uint32_t a0, uint32_t a1, uint32_t a2, uint32_t a3, uint32_t b0, uint32_t b1) {
    asm("mma.sync.aligned.m16n8k16.row.col.f32.bf16.bf16.f32 {%0,%1,%2,%3}, {%4,%5,%6,%7}, {%8,%9}, {%0,%1,%2,%3};"
        : "+f"(c[0]), "+f"(c[1]), "+f"(c[2]), "+f"(c[3]) : "r"(a0), "r"(a1), "r"(a2), "r"(a3), "r"(b0), "r"(b1));
}
__device__ __forceinline__ void mma_1688(float (&c)[4], uint32_t a0, uint32_t a1, uint32_t b0) {
    asm("mma.sync.aligned.m16n8k8.row.col.f32.bf16.bf16.f32 {%0,%1,%2,%3}, {%4,%5}, {%6}, {%0,%1,%2,%3};"
        : "+f"(c[0]), "+f"(c[1]), "+f"(c[2]), "+f"(c[3]) : "r"(a0), "r"(a1), "r"(b0));
}
__device__ __forceinline__ void qk_tile(float (&c)[4], const uint4& q0, const uint4& q1, const uint4& k) {
    c[0] = c[1] = c[2] = c[3] = 0.f;
    mma_16816(c, q0.x, q0.y, q0.z, q0.w, k.x, k.y);
    mma_16816(c, q1.x, q1.y, q1.z, q1.w, k.z, k.w);
}
__device__ __forceinline__ uint32_t scaled_logits(float lo, float hi) {
    constexpr float SCALE = 0.17677669529663687f;
    const uint32_t p = pack_bf16(lo, hi);
    return pack_bf16(bf_lo(p) * SCALE, bf_hi(p) * SCALE);
}

__device__ __forceinline__ void pv_tile(uint32_t dst, const uint4& vp, const uint4& vo, uint32_t p, uint32_t keep) {
    float a[4] = {0.f, 0.f, 0.f, 0.f}, b[4] = {0.f, 0.f, 0.f, 0.f};
    mma_1688(a, vp.x, vp.y, p & keep); mma_1688(b, vp.z, vp.w, p & keep);
    mma_1688(a, vo.x, vo.y, p & ~keep); mma_1688(b, vo.z, vo.w, p & ~keep);
    asm volatile("stmatrix.sync.aligned.m8n8.x4.trans.shared.b16 [%0], {%1,%2,%3,%4};"
                 :: "r"(dst), "r"(pack_bf16(a[0], a[1])), "r"(pack_bf16(a[2], a[3])),
                    "r"(pack_bf16(b[0], b[1])), "r"(pack_bf16(b[2], b[3])) : "memory");
}

__device__ __forceinline__ void attention(uint32_t in, uint32_t out, uint32_t full, uint32_t empty, uint32_t o_ready,
                                          uint32_t o_free, int lane) {
    constexpr float LOG2E = 1.4426950408889634f;
    const int g = lane >> 2, t = lane & 3;
    const bool up0 = 2 * t > g, up1 = 2 * t + 1 > g;
    const uint32_t keep = (up0 ? 0x0000ffffu : 0u) | (up1 ? 0xffff0000u : 0u);
    uint32_t mask0 = up0 ? 0xffffu : 0u, mask1 = up1 ? 0xffffu : 0u;
    const uint32_t neg = pack_bf16(-1e9f, 0.f);
    const uint32_t qoff = (lane & 15) * 128 + (((lane >> 4) ^ (lane & 7)) << 4);
    const uint32_t koff = (lane & 7) * 128 + (((lane >> 3) ^ (lane & 7)) << 4);
    uint4 k[2][5], v[2][5];
#pragma unroll
    for (int h = 0; h < 2; h++) { k[h][4] = make_uint4(0, 0, 0, 0); v[h][4] = make_uint4(0, 0, 0, 0); }
#pragma unroll 1
    for (int step = 0; step < ATT_STEPS; step++) {
        const int s0 = (step & 1) * 2;
        uint4 q[2][2][2];
#pragma unroll
        for (int h = 0; h < 2; h++) { k[h][0] = k[h][4]; v[h][0] = v[h][4]; }
#pragma unroll
        for (int u = 0; u < 2; u++) {
            const uint32_t st = in + (s0 + u) * G1_STAGE_BYTES;
            mbar_wait(full + (s0 + u) * 8, (step >> 1) & 1);
#pragma unroll
            for (int h = 0; h < 2; h++) {
                q[h][u][0] = ldsm4(st + (qoff ^ (h * 64)));
                q[h][u][1] = ldsm4(st + (qoff ^ (h * 64 + 32)));
                k[h][2 * u + 1] = ldsm4(st + 2048 + (koff ^ (h * 64)));
                k[h][2 * u + 2] = ldsm4(st + 3072 + (koff ^ (h * 64)));
            }
        }
#pragma unroll
        for (int u = 0; u < 2; u++) {
            const uint32_t st = in + (s0 + u) * G1_STAGE_BYTES;
#pragma unroll
            for (int h = 0; h < 2; h++) {
                v[h][2 * u + 1] = ldsm4_t(st + 4096 + (koff ^ (h * 64)));
                v[h][2 * u + 2] = ldsm4_t(st + 5120 + (koff ^ (h * 64)));
            }
        }
        __syncwarp();
        if (lane < 2) mbar_arrive(empty + (s0 + lane) * 8);
        uint32_t p[2][4];
#pragma unroll
        for (int u = 0; u < 2; u++) {
#pragma unroll
            for (int h = 0; h < 2; h++) {
                float s0_[4], s1[4], s2[4];
                qk_tile(s0_, q[h][u][0], q[h][u][1], k[h][2 * u]);
                qk_tile(s1, q[h][u][0], q[h][u][1], k[h][2 * u + 1]);
                qk_tile(s2, q[h][u][0], q[h][u][1], k[h][2 * u + 2]);
                uint32_t l0 = scaled_logits(up0 ? s0_[0] : s1[0], up0 ? s1[2] : s2[2]);
                uint32_t l1 = scaled_logits(up1 ? s0_[1] : s1[1], up1 ? s1[3] : s2[3]);
                if (u == 0) {
                    l0 = (l0 & ~mask0) | (neg & mask0);
                    l1 = (l1 & ~mask1) | (neg & mask1);
                }
                uint32_t m = max_bf16x2(l0, l1);
                m = max_bf16x2(m, __shfl_xor_sync(0xffffffffu, m, 1));
                m = max_bf16x2(m, __shfl_xor_sync(0xffffffffu, m, 2));
                const float ea0 = ex2_fast((bf_lo(l0) - bf_lo(m)) * LOG2E), ea1 = ex2_fast((bf_lo(l1) - bf_lo(m)) * LOG2E);
                const float eb0 = ex2_fast((bf_hi(l0) - bf_hi(m)) * LOG2E), eb1 = ex2_fast((bf_hi(l1) - bf_hi(m)) * LOG2E);
                float sa = ea0 + ea1, sb = eb0 + eb1;
                sa += __shfl_xor_sync(0xffffffffu, sa, 1); sb += __shfl_xor_sync(0xffffffffu, sb, 1);
                sa += __shfl_xor_sync(0xffffffffu, sa, 2); sb += __shfl_xor_sync(0xffffffffu, sb, 2);
                const float ra = rcp_fast(sa), rb = rcp_fast(sb);
                p[h][2 * u] = pack_bf16(ea0 * ra, ea1 * ra);
                p[h][2 * u + 1] = pack_bf16(eb0 * rb, eb1 * rb);
            }
        }
        mask0 = 0; mask1 = 0;
        if (step > 0) mbar_wait(o_free, (step - 1) & 1);
#pragma unroll
        for (int j = 0; j < 4; j++) {
#pragma unroll
            for (int h = 0; h < 2; h++) pv_tile(out + j * 1024 + (koff ^ (h * 64)), v[h][j], v[h][j + 1], p[h][j], keep);
        }
        asm volatile("fence.proxy.async.shared::cta;" ::: "memory");
        __syncwarp();
        if (lane == 0) mbar_arrive(o_ready);
    }
}

__device__ __forceinline__ void warp_sum2(float& a, float& b) {
#pragma unroll
    for (int o = 16; o > 0; o >>= 1) {
        a += __shfl_xor_sync(0xffffffffu, a, o);
        b += __shfl_xor_sync(0xffffffffu, b, o);
    }
}
__device__ __forceinline__ float row_sum(const uint32_t* w) {
    float a = 0.f, b = 0.f;
#pragma unroll
    for (int i = 0; i < 16; i++) { a += bf_lo(w[i]); b += bf_hi(w[i]); }
    return a + b;
}
__device__ __forceinline__ float row_sq(const uint32_t* w, float mean) {
    float a = 0.f, b = 0.f;
#pragma unroll
    for (int i = 0; i < 16; i++) {
        const float lo = bf_lo(w[i]) - mean, hi = bf_hi(w[i]) - mean;
        a = fmaf(lo, lo, a); b = fmaf(hi, hi, b);
    }
    return a + b;
}
__device__ __forceinline__ float row_inv(float sq) {
    return 1.f / round_bf16(sqrtf(round_bf16(round_bf16(sq * (1.f / DM)) + 1e-5f)));
}
__device__ __forceinline__ void row_store(const uint32_t* w, float mean, float inv, int row, int lane) {
    const uint32_t m2 = pack_bf16(mean, mean);
    __nv_bfloat16* dst = g_xn + (size_t)row * DM + lane * 8;
#pragma unroll
    for (int i = 0; i < 4; i++) {
        uint32_t o[4];
#pragma unroll
        for (int j = 0; j < 4; j++) {
            const uint32_t c = sub_bf16x2(w[i * 4 + j], m2);
            o[j] = pack_bf16(bf_lo(c) * inv, bf_hi(c) * inv);
        }
        *reinterpret_cast<uint4*>(dst + i * 256) = make_uint4(o[0], o[1], o[2], o[3]);
    }
    if (lane == 0) g_stats[row] = make_float2(-bf_lo(m2), inv);
}

struct Params {
    CUtensorMap x, xn, wqkv, wg, wu, qkv, o, a2, wo, wd, out;
    const __nv_bfloat16 *px, *pwqkv, *pwg, *pwu;
};

__device__ __forceinline__ bool tile_is_qkv(int nt) { return nt < 4 || (nt >= 8 && nt < 16); }
__device__ __forceinline__ int tile_index(int nt) { return nt < 4 ? nt + 8 : (nt < 8 ? nt - 4 : (nt < 16 ? nt - 8 : nt - 12)); }

__global__ void __cluster_dims__(2, 1, 1) __launch_bounds__(384, 1)
fused_kernel(const __grid_constant__ Params prm) {
    extern __shared__ __align__(1024) uint8_t smem_raw[];
    const uint32_t base = (smem_u32(smem_raw) + 1023) & ~1023u;
    const uint32_t bars = base + BAR_OFF;
    auto full1 = [&](int s) { return bars + s * 8; };
    auto empty1 = [&](int s) { return bars + 32 + s * 8; };
    auto full2 = [&](int s) { return bars + 64 + s * 8; };
    auto empty2 = [&](int s) { return bars + 128 + s * 8; };
    const uint32_t sig_bar = bars + 192, fold_bar = bars + 200, x_bar = bars + 208, dep_bar = bars + 216;
    auto stage2 = [&](int q) { return base + q * G2_STAGE_BYTES; };
    const uint32_t aux = base + AUX_OFF;

    const int warp = __shfl_sync(0xffffffffu, threadIdx.x >> 5, 0);
    const int lane = threadIdx.x & 31;
    const int rank = blockIdx.x & 1;
    const int mblk = ((blockIdx.x >> 1) & 7) * 2 + rank;
    const int nslot = blockIdx.x >> 4;

    if (blockIdx.x >= NGEMM) {
        const int grp = blockIdx.x - NGEMM;
        const uint32_t o_ready = sig_bar, o_free = fold_bar;
        if (threadIdx.x == 0) {
            TRACE_GT(0); TRACE(1);
            for (int s = 0; s < G1_STAGES; s++) { mbar_init(full1(s), 1); mbar_init(empty1(s), 8); }
            mbar_init(o_ready, 8); mbar_init(o_free, 1);
            asm volatile("fence.proxy.async.shared::cta;" ::: "memory");
        }
        __syncthreads();
        if (warp < 8) {
            asm volatile("setmaxnreg.inc.sync.aligned.u32 %0;" :: "n"(CONSUMER_REGS));
            attention(base + warp * 6144, aux + warp * 4096, full1(0), empty1(0), o_ready, o_free, lane);
        } else {
            asm volatile("setmaxnreg.dec.sync.aligned.u32 %0;" :: "n"(AUX_REGS));
            if (warp == 8 && lane == 0) {
                prefetch_map(&prm.qkv);
                const unsigned epoch = __ldcg(g_epoch + blockIdx.x * 8) + 1;
                flag_wait(g_flags + F_QKV * 512 + grp * 32, epoch * CNT_QKV);
                fence_proxy_async();
                g_epoch[blockIdx.x * 8] = epoch;
                TRACE(9);
                for (int i = 0; i < 2 * ATT_STEPS; i++) {
                    const int s = i & 3;
                    if (i >= G1_STAGES) mbar_wait(empty1(s), ((i >> 2) - 1) & 1);
                    mbar_expect_tx(full1(s), G1_STAGE_BYTES);
                    tma_5d(base + s * G1_STAGE_BYTES, &prm.qkv, full1(s), i * 16, grp * 4);
                }
            } else if (warp == 9 && lane == 0) {
                prefetch_map(&prm.o);
                for (int i = 0; i < ATT_STEPS; i++) {
                    mbar_wait(o_ready, i & 1);
                    tma_store_4d(&prm.o, aux, i * 32, grp * 4);
                    asm volatile("cp.async.bulk.commit_group;" ::: "memory");
                    asm volatile("cp.async.bulk.wait_group.read 0;" ::: "memory");
                    mbar_arrive(o_free);
                }
                asm volatile("cp.async.bulk.wait_group 0;" ::: "memory");
                fence_proxy_async();
                flag_add(g_flags + F_O * 512);
                TRACE(10);
            }
        }
    } else if (warp >= 8) {
        unsigned* const flags = g_flags + mblk * 32;
        if (warp == 8) {
            if (lane == 0) {
                TRACE_GT(0); TRACE(1);
                prefetch_map(&prm.x); prefetch_map(nslot < 4 ? &prm.wqkv : (rank ? &prm.wu : &prm.wg));
                for (int s = 0; s < G1_STAGES; s++) { mbar_init(full1(s), 1); mbar_init(empty1(s), 4); }
                for (int s = 0; s < G2_STAGES; s++) { mbar_init(full2(s), 1); mbar_init(empty2(s), 4); }
                mbar_init(sig_bar, 8); mbar_init(fold_bar, 2); mbar_init(x_bar, 1);
                for (int s = 0; s < 4; s++) mbar_init(dep_bar + s * 8, 1);
                asm volatile("fence.mbarrier_init.release.cluster;" ::: "memory");
            }
            __syncwarp();
        }
        asm volatile("barrier.cluster.arrive.relaxed.aligned;" ::: "memory");
        if (warp == 8 && lane == 0) {
            asm volatile("fence.proxy.async.shared::cta;" ::: "memory");
            for (int s = 0; s < G1_STAGES; s++) {
                mbar_expect_tx(full1(s), G1_STAGE_BYTES);
                tma_2d(base + s * G1_STAGE_BYTES, &prm.x, full1(s), s * 64, mblk * 128);
            }
            TRACE(15);
        }
        asm volatile("setmaxnreg.dec.sync.aligned.u32 %0;" :: "n"(AUX_REGS));
        asm volatile("barrier.cluster.wait.acquire.aligned;" ::: "memory");

        if (warp == 8) {
            if (lane == 0) {
                TRACE(2);
                auto load_b1 = [&](int s, int nt, int k) {
                    const uint32_t dst = base + s * G1_STAGE_BYTES + A_BYTES + rank * 16384;
                    if (tile_is_qkv(nt)) tma_3d_mc(dst, &prm.wqkv, full1(s), k * 64, tile_index(nt) * 4 + rank * 2);
                    else tma_3d_mc(dst, rank ? &prm.wu : &prm.wg, full1(s), k * 64, tile_index(nt) * 2);
                };
                for (int s = 0; s < G1_STAGES; s++) load_b1(s, nslot, s);
                prefetch_map(&prm.xn); prefetch_map(&prm.wqkv); prefetch_map(rank ? &prm.wu : &prm.wg);
                prefetch_map(&prm.a2); prefetch_map(&prm.wo); prefetch_map(&prm.wd); prefetch_map(&prm.out);
                uint32_t ph = 0;
                for (int it = G1_STAGES; it < G1_TILES * G1_KSTEPS; it++) {
                    const int s = it & 3, k = it & 15;
                    if (it == G1_KSTEPS) { TRACE(14); mbar_wait(dep_bar, 0); TRACE(3); }
                    mbar_wait(empty1(s), ph);
                    mbar_expect_tx(full1(s), G1_STAGE_BYTES);
                    tma_2d(base + s * G1_STAGE_BYTES, it < G1_KSTEPS ? &prm.x : &prm.xn, full1(s), k * 64, mblk * 128);
                    load_b1(s, (it >> 4) * 8 + nslot, k);
                    if (s == 3) ph ^= 1;
                }
                mbar_expect_tx(x_bar, 32768);
                tma_2d(aux, &prm.x, x_bar, nslot * 128, mblk * 128);
                tma_2d(aux + 16384, &prm.x, x_bar, nslot * 128 + 64, mblk * 128);
                TRACE(4);
                mbar_wait(dep_bar + 8, 0);
                TRACE(5);
                int q = 0; uint32_t ph2 = 1;
                for (int u = 0; u < G2_KSTEPS; u++) {
                    if (u == G2_LATE || u == G2_DSTEPS) {
                        TRACE(u == G2_LATE ? 6 : 32);
                        mbar_wait(dep_bar + (u == G2_LATE ? 16 : 24), 0);
                        TRACE(u == G2_LATE ? 7 : 33);
                    }
                    if (u < G2_STAGES) {
                        if (u == 0) mbar_wait(empty1(0), ph);
                        if (u == 1) mbar_wait(empty1(1), ph);
                        if (u == 3) mbar_wait(empty1(2), ph);
                        if (u == 4) mbar_wait(empty1(3), ph);
                    } else {
                        mbar_wait(empty2(q), ph2);
                    }
                    const uint32_t sa = stage2(q);
                    const bool down = u < G2_DSTEPS;
                    const int k = down ? u : u - G2_DSTEPS;
                    mbar_expect_tx(full2(q), G2_STAGE_BYTES);
                    tma_2d(sa, &prm.a2, full2(q), (down ? DM : 0) + k * 64, mblk * 128);
                    tma_5d_mc(sa + A_BYTES + rank * 8192, down ? &prm.wd : &prm.wo, full2(q), nslot * 128 + rank * 64, k * 2);
                    if (++q == G2_STAGES) { q = 0; ph2 ^= 1; }
                }
                TRACE(8);
            }
        } else if (warp == 9) {
            if (lane == 0) {
                mbar_wait(sig_bar, 0);
                TRACE(11);
                flag_add(flags + F_LN * 512);
                for (int t = 0; t < G1_TILES; t++) {
                    mbar_wait(sig_bar, (t + 1) & 1);
                    const int nt = t * 8 + nslot;
                    flag_add(tile_is_qkv(nt) ? g_flags + F_QKV * 512 + (nt & 3) * 32
                                             : flags + (t < G1_TILES - 1 ? F_EARLY : F_LATE) * 512);
                }
            }
        } else {
            const int w = warp - 10;
            const int ld = nslot < 4 ? NQKV : DF;
            const __nv_bfloat16* wp = nslot < 4 ? prm.pwqkv + 2 * DM + nslot * 256 + lane * 8
                                                : (lane < 16 ? prm.pwg : prm.pwu) + (nslot - 4) * 128 + (lane & 15) * 8;
            wp += (size_t)(mblk * 64 + w * 32) * ld;
            const unsigned epoch = __ldcg(g_epoch + blockIdx.x * 8 + w) + 1;
            float cs[8];
#pragma unroll
            for (int d = 0; d < 8; d++) cs[d] = 0.f;
            mbar_wait(full1(0), 0);
#pragma unroll 1
            for (int i = 0; i < 4; i++) {
                uint4 v[8];
#pragma unroll
                for (int j = 0; j < 8; j++) v[j] = __ldg(reinterpret_cast<const uint4*>(wp + (size_t)(i * 8 + j) * ld));
#pragma unroll
                for (int j = 0; j < 8; j++) {
                    float f[8];
                    unpack8(v[j], f);
#pragma unroll
                    for (int d = 0; d < 8; d++) cs[d] += f[d];
                }
            }
            float4* cp = reinterpret_cast<float4*>(g_colsum + (mblk * 2 + w) * 2048 + nslot * 256 + lane * 8);
            cp[0] = make_float4(cs[0], cs[1], cs[2], cs[3]);
            cp[1] = make_float4(cs[4], cs[5], cs[6], cs[7]);
            __syncwarp();
            if (lane == 0) {
                if (w == 0) TRACE(34);
                flag_add(g_flags + F_CS * 512 + nslot * 32);
                flag_wait(g_flags + F_CS * 512 + nslot * 32, epoch * CNT_CS);
            }
            __syncwarp();
            const float4* gp = reinterpret_cast<const float4*>(g_colsum + nslot * 256 + w * 128) + lane;
            float4 c = make_float4(0.f, 0.f, 0.f, 0.f);
#pragma unroll 8
            for (int m = 0; m < 32; m++) {
                const float4 a = __ldcg(gp + m * 512);
                c.x += a.x; c.y += a.y; c.z += a.z; c.w += a.w;
            }
            const uint32_t ca = aux + (w * 8 + (lane >> 2)) * 64 + (lane & 1) * 32 + (lane & 2) * 4;
            sts64f(ca, c.x, c.y);
            sts64f(ca + 16, c.z, c.w);
            if (lane == 0) {
                flag_wait(flags + F_LN * 512, epoch * CNT_LN);
                if (w == 0) { fence_proxy_async(); mbar_arrive(dep_bar); }
            }
            __syncwarp();
            sts128(aux + 1024 + w * 512 + lane * 16, __ldcg(reinterpret_cast<const uint4*>(g_stats + mblk * 128 + w * 64) + lane));
            __syncwarp();
            if (lane == 0) {
                mbar_arrive(fold_bar);
                g_epoch[blockIdx.x * 8 + w] = epoch;
                if (w == 0) {
                    TRACE(35);
                    flag_wait(flags + F_EARLY * 512, epoch * CNT_EARLY);
                    fence_proxy_async(); mbar_arrive(dep_bar + 8);
                    flag_wait(flags + F_LATE * 512, epoch * CNT_LATE);
                    fence_proxy_async(); mbar_arrive(dep_bar + 16);
                    flag_wait(g_flags + F_O * 512, epoch * CNT_O);
                    fence_proxy_async(); mbar_arrive(dep_bar + 24);
                }
            }
        }
    } else {
        asm volatile("barrier.cluster.arrive.relaxed.aligned;" ::: "memory");
        asm volatile("setmaxnreg.inc.sync.aligned.u32 %0;" :: "n"(CONSUMER_REGS));
        const int wg = __shfl_sync(0xffffffffu, threadIdx.x >> 7, 0);
        const int cw = threadIdx.x >> 5;
        const int tid = threadIdx.x & 127;
        float acc[128];
        uint32_t pk[64];
#pragma unroll
        for (int i = 0; i < 64; i++) asm volatile("mov.b32 %0, 0;" : "=r"(pk[i]));
#pragma unroll
        for (int i = 0; i < 128; i++) asm volatile("mov.b32 %0, 0;" : "=f"(acc[i]));
        asm volatile("barrier.cluster.wait.acquire.aligned;" ::: "memory");

        const int orow = mblk * 128 + cw * 16 + (lane >> 2);
        __nv_bfloat16* optr = nullptr;
        auto release = [&](uint32_t bar) { if (tid < 2) mbar_arrive_cluster(bar, tid); };
        auto chunk_geglu = [&](int j) {
            const int c = j >> 1, h = j & 1;
            uint4 v;
            v.x = geglu2(pk[8 * c + h], pk[32 + 8 * c + h]);
            v.y = geglu2(pk[8 * c + 2 + h], pk[32 + 8 * c + 2 + h]);
            v.z = geglu2(pk[8 * c + 4 + h], pk[32 + 8 * c + 4 + h]);
            v.w = geglu2(pk[8 * c + 6 + h], pk[32 + 8 * c + 6 + h]);
            *reinterpret_cast<uint4*>(optr + h * 8 * K2 + c * 32) = v;
        };
        auto chunk_qkv = [&](int c) {
            *reinterpret_cast<uint4*>(optr + c * 32) = make_uint4(pk[8 * c], pk[8 * c + 2], pk[8 * c + 4], pk[8 * c + 6]);
            *reinterpret_cast<uint4*>(optr + 8 * NQKV + c * 32) = make_uint4(pk[8 * c + 1], pk[8 * c + 3], pk[8 * c + 5], pk[8 * c + 7]);
        };
        auto signal_stores = [&]() { __syncwarp(); if (lane == 0) mbar_arrive(sig_bar); };

        auto chunk_ln = [&](int k) {
            const int row = mblk * 128 + nslot * 16 + cw * 2;
            if (k == 0) {
                const uint4* xp = reinterpret_cast<const uint4*>(prm.px + (size_t)row * DM) + lane;
#pragma unroll
                for (int i = 0; i < 8; i++) {
                    const uint4 v = __ldg(xp + i * 32);
                    pk[4 * i] = v.x; pk[4 * i + 1] = v.y; pk[4 * i + 2] = v.z; pk[4 * i + 3] = v.w;
                }
            } else if (k == 3) {
                float a = row_sum(pk), b = row_sum(pk + 16);
                warp_sum2(a, b);
                pk[32] = __float_as_uint(a * (1.f / DM)); pk[33] = __float_as_uint(b * (1.f / DM));
            } else if (k == 4) {
                pk[34] = __float_as_uint(row_sq(pk, __uint_as_float(pk[32])));
            } else if (k == 5) {
                float a = __uint_as_float(pk[34]), b = row_sq(pk + 16, __uint_as_float(pk[33]));
                warp_sum2(a, b);
                pk[34] = __float_as_uint(a); pk[35] = __float_as_uint(b);
            } else if (k == 6) {
                row_store(pk, __uint_as_float(pk[32]), row_inv(__uint_as_float(pk[34])), row, lane);
            } else if (k == 7) {
                row_store(pk + 16, __uint_as_float(pk[33]), row_inv(__uint_as_float(pk[35])), row + 1, lane);
                signal_stores();
            }
        };

        int pending = 0;
#pragma unroll 1
        for (int t = 0; t < G1_TILES; t++) {
#pragma unroll
            for (int k = 0; k < G1_KSTEPS; k++) {
                const int s = k & 3;
                mbar_wait(full1(s), (k >> 2) & 1);
                if (t == 0 && k == 0 && threadIdx.x == 0) TRACE(12);
                if (wg == 1 && k == G1_KSTEPS - G1_SKEW) asm volatile("bar.sync 1, 256;" ::: "memory");
                const uint64_t da = desc_a(base + s * G1_STAGE_BYTES + wg * 8192);
                const uint64_t db = desc_b(base + s * G1_STAGE_BYTES + A_BYTES);
                wg_fence();
#pragma unroll
                for (int kk = 0; kk < 4; kk++) wgmma_n256(acc, da + kk * 2, db + kk * 128, (k | kk) != 0);
                wg_commit();
                if (wg == 0 && k == G1_KSTEPS - 1) asm volatile("bar.arrive 1, 256;" ::: "memory");
                if (k <= 7 && pending == 0) chunk_ln(k);
                if (k >= 1 && k <= 8) {
                    if (pending == 2) chunk_geglu(k - 1);
                    else if (pending == 1) chunk_qkv(k - 1);
                    if (k == 8 && pending) signal_stores();
                }
                wg_wait<1>();
                if (k > 0) release(empty1((k - 1) & 3));
            }
            if (t == 0) mbar_wait(fold_bar, 0);
            wg_wait<0>();
            fence_regs(acc);
            release(empty1(3));
            if (t == 0) {
                const uint32_t sp = aux + 1024 + (cw * 16 + (lane >> 2)) * 8;
                const float2 sa = lds64f(sp), sb = lds64f(sp + 64);
#pragma unroll
                for (int j = 0; j < 16; j++) {
                    const uint4 c = lds128(aux + j * 64 + (lane & 3) * 16);
                    const float c0 = __uint_as_float(c.x), c1 = __uint_as_float(c.y);
                    const float c2 = __uint_as_float(c.z), c3 = __uint_as_float(c.w);
                    const float* a = acc + 8 * j;
                    pk[4 * j] = pack_bf16(fmaf(sa.x, c0, a[0]) * sa.y, fmaf(sa.x, c1, a[1]) * sa.y);
                    pk[4 * j + 1] = pack_bf16(fmaf(sb.x, c0, a[2]) * sb.y, fmaf(sb.x, c1, a[3]) * sb.y);
                    pk[4 * j + 2] = pack_bf16(fmaf(sa.x, c2, a[4]) * sa.y, fmaf(sa.x, c3, a[5]) * sa.y);
                    pk[4 * j + 3] = pack_bf16(fmaf(sb.x, c2, a[6]) * sb.y, fmaf(sb.x, c3, a[7]) * sb.y);
                }
            } else {
#pragma unroll
                for (int i = 0; i < 64; i++) pk[i] = pack_bf16(acc[2 * i], acc[2 * i + 1]);
            }
            const int nt = t * 8 + nslot;
            pending = tile_is_qkv(nt) ? 1 : 2;
            optr = pending == 1 ? g_qkv + (size_t)orow * NQKV + tile_index(nt) * 256 + (lane & 3) * 8
                                : g_a2 + (size_t)orow * K2 + DM + tile_index(nt) * 128 + (lane & 3) * 8;
            if (tid == 0) TRACE(16 + wg * 8 + t);
        }

        float accd[64], accs[64];
#pragma unroll
        for (int i = 0; i < 64; i++) accd[i] = 0.f;
#pragma unroll
        for (int u = 0; u < 9; u++) {
            const int q = u % G2_STAGES;
            mbar_wait(full2(q), (u / G2_STAGES) & 1);
            const uint64_t da = desc_a(stage2(q) + wg * 8192), db = desc_b(stage2(q) + A_BYTES);
            wg_fence();
#pragma unroll
            for (int kk = 0; kk < 4; kk++) wgmma_n128(accd, da + kk * 2, db + kk * 128, (u | kk) != 0);
            wg_commit();
            if (u >= 1) { chunk_geglu(u - 1); if (u == 8) signal_stores(); }
            wg_wait<1>();
            if (u > 0) release(empty2((u - 1) % G2_STAGES));
        }
        {
            int q = 9 % G2_STAGES, qp = 8 % G2_STAGES; uint32_t ph = (9 / G2_STAGES) & 1;
#pragma unroll 1
            for (int u = 9; u < G2_DSTEPS; u++) {
                mbar_wait(full2(q), ph);
                const uint64_t da = desc_a(stage2(q) + wg * 8192), db = desc_b(stage2(q) + A_BYTES);
                wg_fence();
#pragma unroll
                for (int kk = 0; kk < 4; kk++) wgmma_n128(accd, da + kk * 2, db + kk * 128, 1);
                wg_commit();
                wg_wait<1>();
                release(empty2(qp));
                qp = q;
                if (++q == G2_STAGES) { q = 0; ph ^= 1; }
            }
        }
        if (tid == 0) TRACE(16 + wg * 8 + 5);
#pragma unroll
        for (int i = 0; i < 64; i++) accs[i] = 0.f;
        uint32_t gk[32], xr[32];
        const uint32_t xs = aux + cw * 2048;
        const uint32_t xrow = xs + ((lane & 7) + ((lane >> 3) & 1) * 8) * 128;
        auto xaddr = [&](int j) { return xrow + (j >> 2) * 16384 + (((((j & 3) * 2) + (lane >> 4)) ^ (lane & 7)) << 4); };
#pragma unroll
        for (int u = G2_DSTEPS; u < G2_KSTEPS; u++) {
            const int q = u % G2_STAGES, v = u - G2_DSTEPS;
            mbar_wait(full2(q), (u / G2_STAGES) & 1);
            if (G2_SKEW > 0 && wg == 1 && u == G2_KSTEPS - G2_SKEW) asm volatile("bar.sync 1, 256;" ::: "memory");
            const uint64_t da = desc_a(stage2(q) + wg * 8192), db = desc_b(stage2(q) + A_BYTES);
            wg_fence();
#pragma unroll
            for (int kk = 0; kk < 4; kk++) wgmma_n128(accs, da + kk * 2, db + kk * 128, (v | kk) != 0);
            wg_commit();
            if (G2_SKEW > 0 && wg == 0 && u == G2_KSTEPS - 1) asm volatile("bar.arrive 1, 256;" ::: "memory");
            if (v >= 1 && v <= 8) {
#pragma unroll
                for (int i = 4 * (v - 1); i < 4 * v; i++) {
                    const uint32_t d2 = pack_bf16(accd[2 * i], accd[2 * i + 1]);
                    gk[i] = pack_bf16(silu(bf_lo(d2)), silu(bf_hi(d2)));
                }
            }
            if (v == 9) mbar_wait(x_bar, 0);
            if (v >= 9 && v <= 12) {
#pragma unroll
                for (int j = 2 * (v - 9); j < 2 * (v - 8); j++)
                    asm volatile("ldmatrix.sync.aligned.m8n8.x4.shared.b16 {%0,%1,%2,%3}, [%4];"
                                 : "=r"(xr[4 * j]), "=r"(xr[4 * j + 1]), "=r"(xr[4 * j + 2]), "=r"(xr[4 * j + 3])
                                 : "r"(xaddr(j)) : "memory");
            }
            wg_wait<1>();
            if (v == 0) fence_regs(accd);
            if (u - 1 + G2_STAGES < G2_KSTEPS) release(empty2((u - 1) % G2_STAGES));
        }
        wg_wait<0>();
        fence_regs(accs);
        if (tid == 0) TRACE(16 + wg * 8 + 6);
#pragma unroll
        for (int j = 0; j < 8; j++) {
            uint32_t r[4];
#pragma unroll
            for (int i = 0; i < 4; i++) {
                const int e = j * 4 + i;
                r[i] = add_bf16x2(xr[e], mul_bf16x2(pack_bf16(accs[2 * e], accs[2 * e + 1]), gk[e]));
            }
            asm volatile("stmatrix.sync.aligned.m8n8.x4.shared.b16 [%0], {%1,%2,%3,%4};"
                         :: "r"(xaddr(j)), "r"(r[0]), "r"(r[1]), "r"(r[2]), "r"(r[3]) : "memory");
            if (j == 3 || j == 7) {
                asm volatile("fence.proxy.async.shared::cta;" ::: "memory");
                __syncwarp();
                if (lane == 0) {
                    tma_store_2d(&prm.out, xs + (j >> 2) * 16384, nslot * 128 + (j >> 2) * 64, mblk * 128 + cw * 16);
                    asm volatile("cp.async.bulk.commit_group;" ::: "memory");
                }
            }
        }
        if (lane == 0) asm volatile("cp.async.bulk.wait_group.read 0;" ::: "memory");
        if (tid == 0) { TRACE(16 + wg * 8 + 7); if (wg == 1) TRACE_GT(13); }
    }
}

typedef CUresult (*EncodeFn)(CUtensorMap*, CUtensorMapDataType, cuuint32_t, void*, const cuuint64_t*, const cuuint64_t*,
                             const cuuint32_t*, const cuuint32_t*, CUtensorMapInterleave, CUtensorMapSwizzle,
                             CUtensorMapL2promotion, CUtensorMapFloatOOBfill);

void encode(EncodeFn fn, CUtensorMap* m, const void* ptr, int rank, const cuuint64_t* dims, const cuuint64_t* strides,
            const cuuint32_t* box) {
    const cuuint32_t es[5] = {1, 1, 1, 1, 1};
    fn(m, CU_TENSOR_MAP_DATA_TYPE_BFLOAT16, rank, const_cast<void*>(ptr), dims, strides, box, es,
       CU_TENSOR_MAP_INTERLEAVE_NONE, CU_TENSOR_MAP_SWIZZLE_128B, CU_TENSOR_MAP_L2_PROMOTION_L2_128B,
       CU_TENSOR_MAP_FLOAT_OOB_FILL_NONE);
}
void encode_2d(EncodeFn fn, CUtensorMap* m, const void* ptr, int cols, int box_rows) {
    const cuuint64_t dims[2] = {(cuuint64_t)cols, SEQ}, strides[1] = {(cuuint64_t)cols * 2};
    const cuuint32_t box[2] = {64, (cuuint32_t)box_rows};
    encode(fn, m, ptr, 2, dims, strides, box);
}
void encode_w1(EncodeFn fn, CUtensorMap* m, const void* ptr, int cols) {
    const cuuint64_t dims[3] = {64, DM, (cuuint64_t)cols / 64}, strides[2] = {(cuuint64_t)cols * 2, 128};
    const cuuint32_t box[3] = {64, 64, 2};
    encode(fn, m, ptr, 3, dims, strides, box);
}
void encode_qkv(EncodeFn fn, CUtensorMap* m, const void* ptr) {
    const cuuint64_t dims[5] = {64, SEQ / 2, 3, 2, DM / 64}, strides[4] = {NQKV * 4, DM * 2, NQKV * 2, 128};
    const cuuint32_t box[5] = {64, 16, 3, 2, 4};
    encode(fn, m, ptr, 5, dims, strides, box);
}
void encode_o(EncodeFn fn, CUtensorMap* m, const void* ptr) {
    const cuuint64_t dims[4] = {64, SEQ / 2, 2, DM / 64}, strides[3] = {K2 * 4, K2 * 2, 128};
    const cuuint32_t box[4] = {64, 32, 2, 4};
    encode(fn, m, ptr, 4, dims, strides, box);
}
void encode_w2(EncodeFn fn, CUtensorMap* m, const void* ptr, int rows) {
    const cuuint64_t rb = DM * 2;
    const cuuint64_t dims[5] = {DM, 2, 4, 4, (cuuint64_t)rows / 32}, strides[4] = {rb, 8 * rb, 2 * rb, 32 * rb};
    const cuuint32_t box[5] = {64, 2, 4, 4, 2};
    encode(fn, m, ptr, 5, dims, strides, box);
}

}

extern "C" void kernel_launch(void* const* d_in, const int* in_sizes, int n_in, void* d_out, int out_size) {
    (void)in_sizes; (void)n_in; (void)out_size;
    static EncodeFn fn = nullptr;
    static void *p_xn = nullptr, *p_qkv = nullptr, *p_a2 = nullptr;
    if (!fn) {
        cudaDriverEntryPointQueryResult st;
        cudaGetDriverEntryPoint("cuTensorMapEncodeTiled", (void**)&fn, cudaEnableDefault, &st);
        cudaGetSymbolAddress(&p_xn, g_xn);
        cudaGetSymbolAddress(&p_qkv, g_qkv);
        cudaGetSymbolAddress(&p_a2, g_a2);
        cudaFuncSetAttribute(fused_kernel, cudaFuncAttributeMaxDynamicSharedMemorySize, SMEM_BYTES);
    }
    Params prm;
    encode_2d(fn, &prm.x, d_in[0], DM, 128);
    encode_2d(fn, &prm.xn, p_xn, DM, 128);
    encode_w1(fn, &prm.wqkv, d_in[1], NQKV);
    encode_w1(fn, &prm.wg, d_in[4], DF);
    encode_w1(fn, &prm.wu, d_in[5], DF);
    encode_qkv(fn, &prm.qkv, p_qkv);
    encode_o(fn, &prm.o, p_a2);
    encode_2d(fn, &prm.a2, p_a2, K2, 128);
    encode_w2(fn, &prm.wo, d_in[2], DM);
    encode_w2(fn, &prm.wd, d_in[6], DF);
    encode_2d(fn, &prm.out, d_out, DM, 16);
    prm.px = (const __nv_bfloat16*)d_in[0];
    prm.pwqkv = (const __nv_bfloat16*)d_in[1];
    prm.pwg = (const __nv_bfloat16*)d_in[4];
    prm.pwu = (const __nv_bfloat16*)d_in[5];
    fused_kernel<<<NCTA, 384, SMEM_BYTES>>>(prm);
}
```

```cpp
#include <cuda_runtime.h>
#include <cuda_bf16.h>
#include <cuda.h>
#include <stdint.h>

namespace {

constexpr int SEQ = 2048, DM = 1024, DF = 3584, K2 = DM + DF, NQKV = 3 * DM;
constexpr int NGEMM = 128, NCTA = 132;
constexpr int G1_STAGES = 4, G1_STAGE_BYTES = 49152, G1_KSTEPS = 16, G1_TILES = 5;
constexpr int G2_STAGES = 6, G2_STAGE_BYTES = 32768, G2_KSTEPS = 72, G2_DSTEPS = 56, G2_LATE = 40;
constexpr int A_BYTES = 16384;
constexpr int AUX_OFF = G1_STAGES * G1_STAGE_BYTES;
constexpr int BAR_OFF = AUX_OFF + 32768;
constexpr int SMEM_BYTES = BAR_OFF + 1024 + 256;
constexpr int G1_SKEW = 2, G2_SKEW = 2;
constexpr int CONSUMER_REGS = 224, AUX_REGS = 56;
constexpr int ATT_STEPS = 64;

enum { F_LN = 0, F_QKV = 1, F_EARLY = 2, F_LATE = 3, F_O = 4, F_CS = 5 };
constexpr unsigned CNT_LN = 8, CNT_QKV = 48, CNT_EARLY = 20, CNT_LATE = 8, CNT_O = 4, CNT_CS = 32;

__device__ __align__(1024) __nv_bfloat16 g_xn[SEQ * DM];
__device__ __align__(1024) __nv_bfloat16 g_qkv[SEQ * NQKV];
__device__ __align__(1024) __nv_bfloat16 g_a2[SEQ * K2];
__device__ __align__(128) float2 g_stats[SEQ];
__device__ __align__(128) float g_colsum[32 * 2048];
__device__ __align__(128) unsigned g_flags[6 * 16 * 32];
__device__ __align__(128) unsigned g_epoch[NCTA * 8];

#define TRACE(slot) do {} while (0)
#define TRACE_GT(slot) do {} while (0)

__device__ __forceinline__ uint32_t smem_u32(const void* p) { return (uint32_t)__cvta_generic_to_shared(p); }
__device__ __forceinline__ void mbar_init(uint32_t bar, uint32_t cnt) {
    asm volatile("mbarrier.init.shared::cta.b64 [%0], %1;" :: "r"(bar), "r"(cnt) : "memory");
}
__device__ __forceinline__ void mbar_expect_tx(uint32_t bar, uint32_t bytes) {
    asm volatile("mbarrier.arrive.expect_tx.shared::cta.b64 _, [%0], %1;" :: "r"(bar), "r"(bytes) : "memory");
}
__device__ __forceinline__ void mbar_arrive(uint32_t bar) {
    asm volatile("mbarrier.arrive.shared::cta.b64 _, [%0];" :: "r"(bar) : "memory");
}
__device__ __forceinline__ void mbar_arrive_cluster(uint32_t bar, uint32_t cta) {
    asm volatile("{\n.reg .b32 ra;\nmapa.shared::cluster.u32 ra, %0, %1;\nmbarrier.arrive.shared::cluster.b64 _, [ra];\n}"
                 :: "r"(bar), "r"(cta) : "memory");
}
__device__ __forceinline__ bool mbar_try_wait(uint32_t bar, uint32_t parity) {
    uint32_t ok;
    asm volatile("{\n.reg .pred p;\nmbarrier.try_wait.parity.shared::cta.b64 p, [%1], %2;\nselp.u32 %0, 1, 0, p;\n}"
                 : "=r"(ok) : "r"(bar), "r"(parity) : "memory");
    return ok;
}
__device__ __forceinline__ void mbar_wait(uint32_t bar, uint32_t parity) {
    int spins = 0;
    while (!mbar_try_wait(bar, parity)) { if (++spins > (1 << 17)) break; }
}
__device__ __forceinline__ void flag_wait(const unsigned* p, unsigned target) {
    for (int spins = 0; spins < (1 << 19); spins++) {
        unsigned v;
        asm volatile("ld.acquire.gpu.global.u32 %0, [%1];" : "=r"(v) : "l"(p) : "memory");
        if ((int)(v - target) >= 0) break;
        __nanosleep(64);
    }
}
__device__ __forceinline__ void flag_add(unsigned* p) {
    asm volatile("red.release.gpu.global.add.u32 [%0], 1;" :: "l"(p) : "memory");
}
__device__ __forceinline__ void fence_proxy_async() { asm volatile("fence.proxy.async;" ::: "memory"); }
__device__ __forceinline__ uint4 lds128(uint32_t addr) {
    uint4 v;
    asm volatile("ld.shared.v4.u32 {%0,%1,%2,%3}, [%4];" : "=r"(v.x), "=r"(v.y), "=r"(v.z), "=r"(v.w) : "r"(addr) : "memory");
    return v;
}
__device__ __forceinline__ float2 lds64f(uint32_t addr) {
    float2 v;
    asm volatile("ld.shared.v2.f32 {%0,%1}, [%2];" : "=f"(v.x), "=f"(v.y) : "r"(addr) : "memory");
    return v;
}
__device__ __forceinline__ void sts128(uint32_t addr, uint4 v) {
    asm volatile("st.shared.v4.u32 [%0], {%1,%2,%3,%4};" :: "r"(addr), "r"(v.x), "r"(v.y), "r"(v.z), "r"(v.w) : "memory");
}
__device__ __forceinline__ void sts64f(uint32_t addr, float a, float b) {
    asm volatile("st.shared.v2.f32 [%0], {%1,%2};" :: "r"(addr), "f"(a), "f"(b) : "memory");
}

__device__ __forceinline__ void tma_2d(uint32_t dst, const CUtensorMap* m, uint32_t bar, int c0, int c1) {
    asm volatile("cp.async.bulk.tensor.2d.shared::cluster.global.mbarrier::complete_tx::bytes [%0], [%1, {%3, %4}], [%2];"
                 :: "r"(dst), "l"(m), "r"(bar), "r"(c0), "r"(c1) : "memory");
}
__device__ __forceinline__ void tma_5d(uint32_t dst, const CUtensorMap* m, uint32_t bar, int c1, int c4) {
    asm volatile("cp.async.bulk.tensor.5d.shared::cluster.global.mbarrier::complete_tx::bytes [%0], [%1, {%3, %4, %3, %3, %5}], [%2];"
                 :: "r"(dst), "l"(m), "r"(bar), "r"(0), "r"(c1), "r"(c4) : "memory");
}
__device__ __forceinline__ void tma_store_4d(const CUtensorMap* m, uint32_t src, int c1, int c3) {
    asm volatile("cp.async.bulk.tensor.4d.global.shared::cta.bulk_group [%0, {%2, %3, %2, %4}], [%1];"
                 :: "l"(m), "r"(src), "r"(0), "r"(c1), "r"(c3) : "memory");
}
__device__ __forceinline__ void tma_3d_mc(uint32_t dst, const CUtensorMap* m, uint32_t bar, int c1, int c2) {
    asm volatile("cp.async.bulk.tensor.3d.shared::cluster.global.mbarrier::complete_tx::bytes.multicast::cluster"
                 " [%0], [%1, {%3, %4, %5}], [%2], %6;"
                 :: "r"(dst), "l"(m), "r"(bar), "r"(0), "r"(c1), "r"(c2), "h"((uint16_t)3) : "memory");
}
__device__ __forceinline__ void tma_5d_mc(uint32_t dst, const CUtensorMap* m, uint32_t bar, int c0, int c4) {
    asm volatile("cp.async.bulk.tensor.5d.shared::cluster.global.mbarrier::complete_tx::bytes.multicast::cluster"
                 " [%0], [%1, {%3, %4, %4, %4, %5}], [%2], %6;"
                 :: "r"(dst), "l"(m), "r"(bar), "r"(c0), "r"(0), "r"(c4), "h"((uint16_t)3) : "memory");
}
__device__ __forceinline__ void tma_store_2d(const CUtensorMap* m, uint32_t src, int c0, int c1) {
    asm volatile("cp.async.bulk.tensor.2d.global.shared::cta.bulk_group [%0, {%2, %3}], [%1];"
                 :: "l"(m), "r"(src), "r"(c0), "r"(c1) : "memory");
}
__device__ __forceinline__ void prefetch_map(const CUtensorMap* m) {
    asm volatile("prefetch.tensormap [%0];" :: "l"(m) : "memory");
}
__device__ __forceinline__ void wg_fence() { asm volatile("wgmma.fence.sync.aligned;" ::: "memory"); }
__device__ __forceinline__ void wg_commit() { asm volatile("wgmma.commit_group.sync.aligned;" ::: "memory"); }
template <int N> __device__ __forceinline__ void wg_wait() { asm volatile("wgmma.wait_group.sync.aligned %0;" :: "n"(N) : "memory"); }

__device__ __forceinline__ uint64_t desc_a(uint32_t addr) {
    return (uint64_t)((addr & 0x3FFFF) >> 4) | (1ull << 16) | (64ull << 32) | (1ull << 62);
}
__device__ __forceinline__ uint64_t desc_b(uint32_t addr) {
    return (uint64_t)((addr & 0x3FFFF) >> 4) | (512ull << 16) | (64ull << 32) | (1ull << 62);
}

#define R8(d, o) "+f"(d[o]), "+f"(d[o+1]), "+f"(d[o+2]), "+f"(d[o+3]), "+f"(d[o+4]), "+f"(d[o+5]), "+f"(d[o+6]), "+f"(d[o+7])
#define R32(d, o) R8(d, o), R8(d, o+8), R8(d, o+16), R8(d, o+24)
#define R64(d, o) R32(d, o), R32(d, o+32)

__device__ __forceinline__ void wgmma_n256(float (&d)[128], uint64_t da, uint64_t db, int scale_d) {
    asm volatile("{\n.reg .pred p;\nsetp.ne.b32 p, %130, 0;\n"
        "wgmma.mma_async.sync.aligned.m64n256k16.f32.bf16.bf16 "
        "{%0,%1,%2,%3,%4,%5,%6,%7,%8,%9,%10,%11,%12,%13,%14,%15,%16,%17,%18,%19,%20,%21,%22,%23,%24,%25,%26,%27,%28,%29,%30,%31,"
        "%32,%33,%34,%35,%36,%37,%38,%39,%40,%41,%42,%43,%44,%45,%46,%47,%48,%49,%50,%51,%52,%53,%54,%55,%56,%57,%58,%59,%60,%61,%62,%63,"
        "%64,%65,%66,%67,%68,%69,%70,%71,%72,%73,%74,%75,%76,%77,%78,%79,%80,%81,%82,%83,%84,%85,%86,%87,%88,%89,%90,%91,%92,%93,%94,%95,"
        "%96,%97,%98,%99,%100,%101,%102,%103,%104,%105,%106,%107,%108,%109,%110,%111,%112,%113,%114,%115,%116,%117,%118,%119,%120,%121,%122,%123,%124,%125,%126,%127},"
        " %128, %129, p, 1, 1, 0, 1;\n}"
        : R64(d, 0), R64(d, 64) : "l"(da), "l"(db), "r"(scale_d));
}
__device__ __forceinline__ void wgmma_n128(float (&d)[64], uint64_t da, uint64_t db, int scale_d) {
    asm volatile("{\n.reg .pred p;\nsetp.ne.b32 p, %66, 0;\n"
        "wgmma.mma_async.sync.aligned.m64n128k16.f32.bf16.bf16 "
        "{%0,%1,%2,%3,%4,%5,%6,%7,%8,%9,%10,%11,%12,%13,%14,%15,%16,%17,%18,%19,%20,%21,%22,%23,%24,%25,%26,%27,%28,%29,%30,%31,"
        "%32,%33,%34,%35,%36,%37,%38,%39,%40,%41,%42,%43,%44,%45,%46,%47,%48,%49,%50,%51,%52,%53,%54,%55,%56,%57,%58,%59,%60,%61,%62,%63},"
        " %64, %65, p, 1, 1, 0, 1;\n}"
        : R64(d, 0) : "l"(da), "l"(db), "r"(scale_d));
}

__device__ __forceinline__ uint32_t pack_bf16(float lo, float hi) {
    uint32_t r; asm("cvt.rn.bf16x2.f32 %0, %1, %2;" : "=r"(r) : "f"(hi), "f"(lo)); return r;
}
__device__ __forceinline__ float bf_lo(uint32_t v) { return __uint_as_float(v << 16); }
__device__ __forceinline__ float bf_hi(uint32_t v) { return __uint_as_float(v & 0xffff0000u); }
__device__ __forceinline__ float round_bf16(float v) { return bf_lo(pack_bf16(v, 0.f)); }
__device__ __forceinline__ uint32_t mul_bf16x2(uint32_t a, uint32_t b) {
    uint32_t r; asm("mul.rn.bf16x2 %0, %1, %2;" : "=r"(r) : "r"(a), "r"(b)); return r;
}
__device__ __forceinline__ uint32_t add_bf16x2(uint32_t a, uint32_t b) {
    uint32_t r; asm("add.rn.bf16x2 %0, %1, %2;" : "=r"(r) : "r"(a), "r"(b)); return r;
}
__device__ __forceinline__ uint32_t sub_bf16x2(uint32_t a, uint32_t b) {
    uint32_t r; asm("sub.rn.bf16x2 %0, %1, %2;" : "=r"(r) : "r"(a), "r"(b)); return r;
}
__device__ __forceinline__ float tanh_fast(float x) { float r; asm("tanh.approx.f32 %0, %1;" : "=f"(r) : "f"(x)); return r; }
__device__ __forceinline__ float gelu_tanh(float g) {
    float t = fmaf(g * g, 0.044715f * 0.7978845608f, 0.7978845608f) * g;
    float hg = 0.5f * g;
    return fmaf(hg, tanh_fast(t), hg);
}
__device__ __forceinline__ uint32_t geglu2(uint32_t g2, uint32_t u2) {
    return mul_bf16x2(pack_bf16(gelu_tanh(bf_lo(g2)), gelu_tanh(bf_hi(g2))), u2);
}
__device__ __forceinline__ float silu(float d) {
    float hd = 0.5f * d;
    return fmaf(hd, tanh_fast(hd), hd);
}
__device__ __forceinline__ float ex2_fast(float x) { float r; asm("ex2.approx.ftz.f32 %0, %1;" : "=f"(r) : "f"(x)); return r; }
__device__ __forceinline__ void unpack8(uint4 v, float (&f)[8]) {
    f[0] = bf_lo(v.x); f[1] = bf_hi(v.x); f[2] = bf_lo(v.y); f[3] = bf_hi(v.y);
    f[4] = bf_lo(v.z); f[5] = bf_hi(v.z); f[6] = bf_lo(v.w); f[7] = bf_hi(v.w);
}
template <int N> __device__ __forceinline__ void fence_regs(float (&d)[N]) {
#pragma unroll
    for (int i = 0; i < N; i++) asm volatile("" : "+f"(d[i]) :: "memory");
}

__device__ __forceinline__ float rcp_fast(float x) { float r; asm("rcp.approx.ftz.f32 %0, %1;" : "=f"(r) : "f"(x)); return r; }
__device__ __forceinline__ uint32_t max_bf16x2(uint32_t a, uint32_t b) {
    uint32_t r; asm("max.bf16x2 %0, %1, %2;" : "=r"(r) : "r"(a), "r"(b)); return r;
}
__device__ __forceinline__ uint4 ldsm4(uint32_t addr) {
    uint4 v;
    asm volatile("ldmatrix.sync.aligned.m8n8.x4.shared.b16 {%0,%1,%2,%3}, [%4];"
                 : "=r"(v.x), "=r"(v.y), "=r"(v.z), "=r"(v.w) : "r"(addr) : "memory");
    return v;
}
__device__ __forceinline__ uint4 ldsm4_t(uint32_t addr) {
    uint4 v;
    asm volatile("ldmatrix.sync.aligned.m8n8.x4.trans.shared.b16 {%0,%1,%2,%3}, [%4];"
                 : "=r"(v.x), "=r"(v.y), "=r"(v.z), "=r"(v.w) : "r"(addr) : "memory");
    return v;
}
__device__ __forceinline__ void mma_16816(float (&c)[4], uint32_t a0, uint32_t a1, uint32_t a2, uint32_t a3, uint32_t b0, uint32_t b1) {
    asm("mma.sync.aligned.m16n8k16.row.col.f32.bf16.bf16.f32 {%0,%1,%2,%3}, {%4,%5,%6,%7}, {%8,%9}, {%0,%1,%2,%3};"
        : "+f"(c[0]), "+f"(c[1]), "+f"(c[2]), "+f"(c[3]) : "r"(a0), "r"(a1), "r"(a2), "r"(a3), "r"(b0), "r"(b1));
}
__device__ __forceinline__ void mma_1688(float (&c)[4], uint32_t a0, uint32_t a1, uint32_t b0) {
    asm("mma.sync.aligned.m16n8k8.row.col.f32.bf16.bf16.f32 {%0,%1,%2,%3}, {%4,%5}, {%6}, {%0,%1,%2,%3};"
        : "+f"(c[0]), "+f"(c[1]), "+f"(c[2]), "+f"(c[3]) : "r"(a0), "r"(a1), "r"(b0));
}
__device__ __forceinline__ void qk_tile(float (&c)[4], const uint4& q0, const uint4& q1, const uint4& k) {
    c[0] = c[1] = c[2] = c[3] = 0.f;
    mma_16816(c, q0.x, q0.y, q0.z, q0.w, k.x, k.y);
    mma_16816(c, q1.x, q1.y, q1.z, q1.w, k.z, k.w);
}
__device__ __forceinline__ uint32_t scaled_logits(float lo, float hi) {
    constexpr float SCALE = 0.17677669529663687f;
    const uint32_t p = pack_bf16(lo, hi);
    return pack_bf16(bf_lo(p) * SCALE, bf_hi(p) * SCALE);
}

__device__ __forceinline__ void pv_tile(uint32_t dst, const uint4& vp, const uint4& vo, uint32_t p, uint32_t keep) {
    float a[4] = {0.f, 0.f, 0.f, 0.f}, b[4] = {0.f, 0.f, 0.f, 0.f};
    mma_1688(a, vp.x, vp.y, p & keep); mma_1688(b, vp.z, vp.w, p & keep);
    mma_1688(a, vo.x, vo.y, p & ~keep); mma_1688(b, vo.z, vo.w, p & ~keep);
    asm volatile("stmatrix.sync.aligned.m8n8.x4.trans.shared.b16 [%0], {%1,%2,%3,%4};"
                 :: "r"(dst), "r"(pack_bf16(a[0], a[1])), "r"(pack_bf16(a[2], a[3])),
                    "r"(pack_bf16(b[0], b[1])), "r"(pack_bf16(b[2], b[3])) : "memory");
}

__device__ __forceinline__ void attention(uint32_t in, uint32_t out, uint32_t full, uint32_t empty, uint32_t o_ready,
                                          uint32_t o_free, int lane) {
    constexpr float LOG2E = 1.4426950408889634f;
    const int g = lane >> 2, t = lane & 3;
    const bool up0 = 2 * t > g, up1 = 2 * t + 1 > g;
    const uint32_t keep = (up0 ? 0x0000ffffu : 0u) | (up1 ? 0xffff0000u : 0u);
    uint32_t mask0 = up0 ? 0xffffu : 0u, mask1 = up1 ? 0xffffu : 0u;
    const uint32_t neg = pack_bf16(-1e9f, 0.f);
    const uint32_t qoff = (lane & 15) * 128 + (((lane >> 4) ^ (lane & 7)) << 4);
    const uint32_t koff = (lane & 7) * 128 + (((lane >> 3) ^ (lane & 7)) << 4);
#define TACC(i) do {} while (0)
    uint4 q[2][2][2], k[2][2][2], v[3][2][2];
    auto fetch = [&](int step, int slot, int vslot) {
        const uint32_t st = in + (step & 3) * G1_STAGE_BYTES;
        mbar_wait(full + (step & 3) * 8, (step >> 2) & 1);
#pragma unroll
        for (int h = 0; h < 2; h++) {
            q[slot][h][0] = ldsm4(st + (qoff ^ (h * 64)));
            q[slot][h][1] = ldsm4(st + (qoff ^ (h * 64 + 32)));
            k[slot][h][0] = ldsm4(st + 2048 + (koff ^ (h * 64)));
            k[slot][h][1] = ldsm4(st + 3072 + (koff ^ (h * 64)));
            v[vslot][h][0] = ldsm4_t(st + 4096 + (koff ^ (h * 64)));
            v[vslot][h][1] = ldsm4_t(st + 5120 + (koff ^ (h * 64)));
        }
    };
#pragma unroll
    for (int h = 0; h < 2; h++) { k[1][h][1] = make_uint4(0, 0, 0, 0); v[1][h][1] = make_uint4(0, 0, 0, 0); }
    fetch(0, 0, 0);
#pragma unroll 1
    for (int step2 = 0; step2 < ATT_STEPS; step2 += 2) {
#pragma unroll
        for (int c = 0; c < 2; c++) {
            const int step = step2 + c;
            uint32_t l0[2], l1[2];
#pragma unroll
            for (int h = 0; h < 2; h++) {
                float s0[4], s1[4], s2[4];
                qk_tile(s0, q[c][h][0], q[c][h][1], k[c ^ 1][h][1]);
                qk_tile(s1, q[c][h][0], q[c][h][1], k[c][h][0]);
                qk_tile(s2, q[c][h][0], q[c][h][1], k[c][h][1]);
                l0[h] = scaled_logits(up0 ? s0[0] : s1[0], up0 ? s1[2] : s2[2]);
                l1[h] = scaled_logits(up1 ? s0[1] : s1[1], up1 ? s1[3] : s2[3]);
                if (c == 0) {
                    l0[h] = (l0[h] & ~mask0) | (neg & mask0);
                    l1[h] = (l1[h] & ~mask1) | (neg & mask1);
                }
                v[2][h][1] = v[c ^ 1][h][1];
            }
            mask0 = 0; mask1 = 0;
            __syncwarp();
            if (lane == 0) mbar_arrive(empty + (step & 3) * 8);
            TACC(0);
            if (step + 1 < ATT_STEPS) fetch(step + 1, c ^ 1, c ^ 1);
            TACC(1);
            uint32_t pa[2], pb[2];
#pragma unroll
            for (int h = 0; h < 2; h++) {
                uint32_t m = max_bf16x2(l0[h], l1[h]);
                m = max_bf16x2(m, __shfl_xor_sync(0xffffffffu, m, 1));
                m = max_bf16x2(m, __shfl_xor_sync(0xffffffffu, m, 2));
                const float ea0 = ex2_fast((bf_lo(l0[h]) - bf_lo(m)) * LOG2E), ea1 = ex2_fast((bf_lo(l1[h]) - bf_lo(m)) * LOG2E);
                const float eb0 = ex2_fast((bf_hi(l0[h]) - bf_hi(m)) * LOG2E), eb1 = ex2_fast((bf_hi(l1[h]) - bf_hi(m)) * LOG2E);
                float sa = ea0 + ea1, sb = eb0 + eb1;
                sa += __shfl_xor_sync(0xffffffffu, sa, 1); sb += __shfl_xor_sync(0xffffffffu, sb, 1);
                sa += __shfl_xor_sync(0xffffffffu, sa, 2); sb += __shfl_xor_sync(0xffffffffu, sb, 2);
                const float ra = rcp_fast(sa), rb = rcp_fast(sb);
                pa[h] = pack_bf16(ea0 * ra, ea1 * ra);
                pb[h] = pack_bf16(eb0 * rb, eb1 * rb);
            }
            TACC(2);
            if (step2 > 0) mbar_wait(o_free + c * 8, ((step2 >> 1) - 1) & 1);
            TACC(3);
#pragma unroll
            for (int h = 0; h < 2; h++) {
                pv_tile(out + c * 16384 + (koff ^ (h * 64)), v[2][h][1], v[c][h][0], pa[h], keep);
                pv_tile(out + c * 16384 + 1024 + (koff ^ (h * 64)), v[c][h][0], v[c][h][1], pb[h], keep);
            }
            asm volatile("fence.proxy.async.shared::cta;" ::: "memory");
            __syncwarp();
            if (lane == 0) mbar_arrive(o_ready + c * 8);
            TACC(4);
        }
    }
}

__device__ __forceinline__ void warp_sum2(float& a, float& b) {
#pragma unroll
    for (int o = 16; o > 0; o >>= 1) {
        a += __shfl_xor_sync(0xffffffffu, a, o);
        b += __shfl_xor_sync(0xffffffffu, b, o);
    }
}
__device__ __forceinline__ float row_sum(const uint32_t* w) {
    float a = 0.f, b = 0.f;
#pragma unroll
    for (int i = 0; i < 16; i++) { a += bf_lo(w[i]); b += bf_hi(w[i]); }
    return a + b;
}
__device__ __forceinline__ float row_sq(const uint32_t* w, float mean) {
    float a = 0.f, b = 0.f;
#pragma unroll
    for (int i = 0; i < 16; i++) {
        const float lo = bf_lo(w[i]) - mean, hi = bf_hi(w[i]) - mean;
        a = fmaf(lo, lo, a); b = fmaf(hi, hi, b);
    }
    return a + b;
}
__device__ __forceinline__ float row_inv(float sq) {
    return 1.f / round_bf16(sqrtf(round_bf16(round_bf16(sq * (1.f / DM)) + 1e-5f)));
}
__device__ __forceinline__ void row_store(const uint32_t* w, float mean, float inv, int row, int lane) {
    const uint32_t m2 = pack_bf16(mean, mean);
    __nv_bfloat16* dst = g_xn + (size_t)row * DM + lane * 8;
#pragma unroll
    for (int i = 0; i < 4; i++) {
        uint32_t o[4];
#pragma unroll
        for (int j = 0; j < 4; j++) {
            const uint32_t c = sub_bf16x2(w[i * 4 + j], m2);
            o[j] = pack_bf16(bf_lo(c) * inv, bf_hi(c) * inv);
        }
        *reinterpret_cast<uint4*>(dst + i * 256) = make_uint4(o[0], o[1], o[2], o[3]);
    }
    if (lane == 0) g_stats[row] = make_float2(-bf_lo(m2), inv);
}

struct Params {
    CUtensorMap x, xn, wqkv, wg, wu, qkv, o, a2, wo, wd, out;
    const __nv_bfloat16 *px, *pwqkv, *pwg, *pwu;
};

__device__ __forceinline__ bool tile_is_qkv(int nt) { return nt < 4 || (nt >= 8 && nt < 16); }
__device__ __forceinline__ int tile_index(int nt) { return nt < 4 ? nt + 8 : (nt < 8 ? nt - 4 : (nt < 16 ? nt - 8 : nt - 12)); }

__global__ void __cluster_dims__(2, 1, 1) __launch_bounds__(384, 1)
fused_kernel(const __grid_constant__ Params prm) {
    extern __shared__ __align__(1024) uint8_t smem_raw[];
    const uint32_t base = (smem_u32(smem_raw) + 1023) & ~1023u;
    const uint32_t bars = base + BAR_OFF;
    auto full1 = [&](int s) { return bars + s * 8; };
    auto empty1 = [&](int s) { return bars + 32 + s * 8; };
    auto full2 = [&](int s) { return bars + 64 + s * 8; };
    auto empty2 = [&](int s) { return bars + 128 + s * 8; };
    const uint32_t sig_bar = bars + 192, fold_bar = bars + 200, x_bar = bars + 208, dep_bar = bars + 216;
    auto stage2 = [&](int q) { return base + q * G2_STAGE_BYTES; };
    const uint32_t aux = base + AUX_OFF;

    const int warp = __shfl_sync(0xffffffffu, threadIdx.x >> 5, 0);
    const int lane = threadIdx.x & 31;
    const int rank = blockIdx.x & 1;
    const int mblk = ((blockIdx.x >> 1) & 7) * 2 + rank;
    const int nslot = blockIdx.x >> 4;

    if (blockIdx.x >= NGEMM) {
        const int grp = blockIdx.x - NGEMM;
        const uint32_t o_ready = full2(0), o_free = empty2(0);
        if (threadIdx.x == 0) {
            TRACE_GT(0); TRACE(1);
            for (int s = 0; s < G1_STAGES; s++) { mbar_init(full1(s), 1); mbar_init(empty1(s), 8); }
            for (int s = 0; s < 2; s++) { mbar_init(o_ready + s * 8, 8); mbar_init(o_free + s * 8, 1); }
            asm volatile("fence.proxy.async.shared::cta;" ::: "memory");
        }
        __syncthreads();
        if (warp < 8) {
            asm volatile("setmaxnreg.inc.sync.aligned.u32 %0;" :: "n"(CONSUMER_REGS));
            attention(base + warp * 6144, aux + warp * 2048, full1(0), empty1(0), o_ready, o_free, lane);
        } else {
            asm volatile("setmaxnreg.dec.sync.aligned.u32 %0;" :: "n"(AUX_REGS));
            if (warp == 8 && lane == 0) {
                prefetch_map(&prm.qkv);
                const unsigned epoch = __ldcg(g_epoch + blockIdx.x * 8) + 1;
                flag_wait(g_flags + F_QKV * 512 + grp * 32, epoch * CNT_QKV);
                fence_proxy_async();
                g_epoch[blockIdx.x * 8] = epoch;
                TRACE(9);
                for (int i = 0; i < ATT_STEPS; i++) {
                    const int s = i & 3;
                    if (i >= G1_STAGES) mbar_wait(empty1(s), ((i >> 2) - 1) & 1);
                    mbar_expect_tx(full1(s), G1_STAGE_BYTES);
                    tma_5d(base + s * G1_STAGE_BYTES, &prm.qkv, full1(s), i * 16, grp * 4);
                }
            } else if (warp == 9 && lane == 0) {
                prefetch_map(&prm.o);
                for (int i = 0; i < ATT_STEPS; i++) {
                    mbar_wait(o_ready + (i & 1) * 8, (i >> 1) & 1);
                    tma_store_4d(&prm.o, aux + (i & 1) * 16384, i * 16, grp * 4);
                    asm volatile("cp.async.bulk.commit_group;" ::: "memory");
                    asm volatile("cp.async.bulk.wait_group.read 0;" ::: "memory");
                    mbar_arrive(o_free + (i & 1) * 8);
                }
                asm volatile("cp.async.bulk.wait_group 0;" ::: "memory");
                fence_proxy_async();
                flag_add(g_flags + F_O * 512);
                TRACE(10);
            }
        }
    } else if (warp >= 8) {
        unsigned* const flags = g_flags + mblk * 32;
        if (warp == 8) {
            if (lane == 0) {
                TRACE_GT(0); TRACE(1);
                prefetch_map(&prm.x); prefetch_map(nslot < 4 ? &prm.wqkv : (rank ? &prm.wu : &prm.wg));
                for (int s = 0; s < G1_STAGES; s++) { mbar_init(full1(s), 1); mbar_init(empty1(s), 4); }
                for (int s = 0; s < G2_STAGES; s++) { mbar_init(full2(s), 1); mbar_init(empty2(s), 4); }
                mbar_init(sig_bar, 8); mbar_init(fold_bar, 2); mbar_init(x_bar, 1);
                for (int s = 0; s < 4; s++) mbar_init(dep_bar + s * 8, 1);
                asm volatile("fence.mbarrier_init.release.cluster;" ::: "memory");
            }
            __syncwarp();
        }
        asm volatile("barrier.cluster.arrive.relaxed.aligned;" ::: "memory");
        if (warp == 8 && lane == 0) {
            asm volatile("fence.proxy.async.shared::cta;" ::: "memory");
            for (int s = 0; s < G1_STAGES; s++) {
                mbar_expect_tx(full1(s), G1_STAGE_BYTES);
                tma_2d(base + s * G1_STAGE_BYTES, &prm.x, full1(s), s * 64, mblk * 128);
            }
            TRACE(15);
        }
        asm volatile("setmaxnreg.dec.sync.aligned.u32 %0;" :: "n"(AUX_REGS));
        asm volatile("barrier.cluster.wait.acquire.aligned;" ::: "memory");

        if (warp == 8) {
            if (lane == 0) {
                TRACE(2);
                auto load_b1 = [&](int s, int nt, int k) {
                    const uint32_t dst = base + s * G1_STAGE_BYTES + A_BYTES + rank * 16384;
                    if (tile_is_qkv(nt)) tma_3d_mc(dst, &prm.wqkv, full1(s), k * 64, tile_index(nt) * 4 + rank * 2);
                    else tma_3d_mc(dst, rank ? &prm.wu : &prm.wg, full1(s), k * 64, tile_index(nt) * 2);
                };
                for (int s = 0; s < G1_STAGES; s++) load_b1(s, nslot, s);
                prefetch_map(&prm.xn); prefetch_map(&prm.wqkv); prefetch_map(rank ? &prm.wu : &prm.wg);
                prefetch_map(&prm.a2); prefetch_map(&prm.wo); prefetch_map(&prm.wd); prefetch_map(&prm.out);
                uint32_t ph = 0;
                for (int it = G1_STAGES; it < G1_TILES * G1_KSTEPS; it++) {
                    const int s = it & 3, k = it & 15;
                    if (it == G1_KSTEPS) { TRACE(14); mbar_wait(dep_bar, 0); TRACE(3); }
                    mbar_wait(empty1(s), ph);
                    mbar_expect_tx(full1(s), G1_STAGE_BYTES);
                    tma_2d(base + s * G1_STAGE_BYTES, it < G1_KSTEPS ? &prm.x : &prm.xn, full1(s), k * 64, mblk * 128);
                    load_b1(s, (it >> 4) * 8 + nslot, k);
                    if (s == 3) ph ^= 1;
                }
                mbar_expect_tx(x_bar, 32768);
                tma_2d(aux, &prm.x, x_bar, nslot * 128, mblk * 128);
                tma_2d(aux + 16384, &prm.x, x_bar, nslot * 128 + 64, mblk * 128);
                TRACE(4);
                mbar_wait(dep_bar + 8, 0);
                TRACE(5);
                int q = 0; uint32_t ph2 = 1;
                for (int u = 0; u < G2_KSTEPS; u++) {
                    if (u == G2_LATE || u == G2_DSTEPS) {
                        TRACE(u == G2_LATE ? 6 : 32);
                        mbar_wait(dep_bar + (u == G2_LATE ? 16 : 24), 0);
                        TRACE(u == G2_LATE ? 7 : 33);
                    }
                    if (u < G2_STAGES) {
                        if (u == 0) mbar_wait(empty1(0), ph);
                        if (u == 1) mbar_wait(empty1(1), ph);
                        if (u == 3) mbar_wait(empty1(2), ph);
                        if (u == 4) mbar_wait(empty1(3), ph);
                    } else {
                        mbar_wait(empty2(q), ph2);
                    }
                    const uint32_t sa = stage2(q);
                    const bool down = u < G2_DSTEPS;
                    const int k = down ? u : u - G2_DSTEPS;
                    mbar_expect_tx(full2(q), G2_STAGE_BYTES);
                    tma_2d(sa, &prm.a2, full2(q), (down ? DM : 0) + k * 64, mblk * 128);
                    tma_5d_mc(sa + A_BYTES + rank * 8192, down ? &prm.wd : &prm.wo, full2(q), nslot * 128 + rank * 64, k * 2);
                    if (++q == G2_STAGES) { q = 0; ph2 ^= 1; }
                }
                TRACE(8);
            }
        } else if (warp == 9) {
            if (lane == 0) {
                mbar_wait(sig_bar, 0);
                TRACE(11);
                flag_add(flags + F_LN * 512);
                for (int t = 0; t < G1_TILES; t++) {
                    mbar_wait(sig_bar, (t + 1) & 1);
                    const int nt = t * 8 + nslot;
                    flag_add(tile_is_qkv(nt) ? g_flags + F_QKV * 512 + (nt & 3) * 32
                                             : flags + (t < G1_TILES - 1 ? F_EARLY : F_LATE) * 512);
                }
            }
        } else {
            const int w = warp - 10;
            const int ld = nslot < 4 ? NQKV : DF;
            const __nv_bfloat16* wp = nslot < 4 ? prm.pwqkv + 2 * DM + nslot * 256 + lane * 8
                                                : (lane < 16 ? prm.pwg : prm.pwu) + (nslot - 4) * 128 + (lane & 15) * 8;
            wp += (size_t)(mblk * 64 + w * 32) * ld;
            const unsigned epoch = __ldcg(g_epoch + blockIdx.x * 8 + w) + 1;
            float cs[8];
#pragma unroll
            for (int d = 0; d < 8; d++) cs[d] = 0.f;
            mbar_wait(full1(0), 0);
#pragma unroll 1
            for (int i = 0; i < 4; i++) {
                uint4 v[8];
#pragma unroll
                for (int j = 0; j < 8; j++) v[j] = __ldg(reinterpret_cast<const uint4*>(wp + (size_t)(i * 8 + j) * ld));
#pragma unroll
                for (int j = 0; j < 8; j++) {
                    float f[8];
                    unpack8(v[j], f);
#pragma unroll
                    for (int d = 0; d < 8; d++) cs[d] += f[d];
                }
            }
            float4* cp = reinterpret_cast<float4*>(g_colsum + (mblk * 2 + w) * 2048 + nslot * 256 + lane * 8);
            cp[0] = make_float4(cs[0], cs[1], cs[2], cs[3]);
            cp[1] = make_float4(cs[4], cs[5], cs[6], cs[7]);
            __syncwarp();
            if (lane == 0) {
                if (w == 0) TRACE(34);
                flag_add(g_flags + F_CS * 512 + nslot * 32);
                flag_wait(g_flags + F_CS * 512 + nslot * 32, epoch * CNT_CS);
            }
            __syncwarp();
            const float4* gp = reinterpret_cast<const float4*>(g_colsum + nslot * 256 + w * 128) + lane;
            float4 c = make_float4(0.f, 0.f, 0.f, 0.f);
#pragma unroll 8
            for (int m = 0; m < 32; m++) {
                const float4 a = __ldcg(gp + m * 512);
                c.x += a.x; c.y += a.y; c.z += a.z; c.w += a.w;
            }
            const uint32_t ca = aux + (w * 8 + (lane >> 2)) * 64 + (lane & 1) * 32 + (lane & 2) * 4;
            sts64f(ca, c.x, c.y);
            sts64f(ca + 16, c.z, c.w);
            if (lane == 0) {
                flag_wait(flags + F_LN * 512, epoch * CNT_LN);
                if (w == 0) { fence_proxy_async(); mbar_arrive(dep_bar); }
            }
            __syncwarp();
            sts128(aux + 1024 + w * 512 + lane * 16, __ldcg(reinterpret_cast<const uint4*>(g_stats + mblk * 128 + w * 64) + lane));
            __syncwarp();
            if (lane == 0) {
                mbar_arrive(fold_bar);
                g_epoch[blockIdx.x * 8 + w] = epoch;
                if (w == 0) {
                    TRACE(35);
                    flag_wait(flags + F_EARLY * 512, epoch * CNT_EARLY);
                    fence_proxy_async(); mbar_arrive(dep_bar + 8);
                    flag_wait(flags + F_LATE * 512, epoch * CNT_LATE);
                    fence_proxy_async(); mbar_arrive(dep_bar + 16);
                    flag_wait(g_flags + F_O * 512, epoch * CNT_O);
                    fence_proxy_async(); mbar_arrive(dep_bar + 24);
                }
            }
        }
    } else {
        asm volatile("barrier.cluster.arrive.relaxed.aligned;" ::: "memory");
        asm volatile("setmaxnreg.inc.sync.aligned.u32 %0;" :: "n"(CONSUMER_REGS));
        const int wg = __shfl_sync(0xffffffffu, threadIdx.x >> 7, 0);
        const int cw = threadIdx.x >> 5;
        const int tid = threadIdx.x & 127;
        float acc[128];
        uint32_t pk[64];
#pragma unroll
        for (int i = 0; i < 64; i++) asm volatile("mov.b32 %0, 0;" : "=r"(pk[i]));
#pragma unroll
        for (int i = 0; i < 128; i++) asm volatile("mov.b32 %0, 0;" : "=f"(acc[i]));
        asm volatile("barrier.cluster.wait.acquire.aligned;" ::: "memory");

        const int orow = mblk * 128 + cw * 16 + (lane >> 2);
        __nv_bfloat16* optr = nullptr;
        auto release = [&](uint32_t bar) { if (tid < 2) mbar_arrive_cluster(bar, tid); };
        auto chunk_geglu = [&](int j) {
            const int c = j >> 1, h = j & 1;
            uint4 v;
            v.x = geglu2(pk[8 * c + h], pk[32 + 8 * c + h]);
            v.y = geglu2(pk[8 * c + 2 + h], pk[32 + 8 * c + 2 + h]);
            v.z = geglu2(pk[8 * c + 4 + h], pk[32 + 8 * c + 4 + h]);
            v.w = geglu2(pk[8 * c + 6 + h], pk[32 + 8 * c + 6 + h]);
            *reinterpret_cast<uint4*>(optr + h * 8 * K2 + c * 32) = v;
        };
        auto chunk_qkv = [&](int c) {
            *reinterpret_cast<uint4*>(optr + c * 32) = make_uint4(pk[8 * c], pk[8 * c + 2], pk[8 * c + 4], pk[8 * c + 6]);
            *reinterpret_cast<uint4*>(optr + 8 * NQKV + c * 32) = make_uint4(pk[8 * c + 1], pk[8 * c + 3], pk[8 * c + 5], pk[8 * c + 7]);
        };
        auto signal_stores = [&]() { __syncwarp(); if (lane == 0) mbar_arrive(sig_bar); };

        auto chunk_ln = [&](int k) {
            const int row = mblk * 128 + nslot * 16 + cw * 2;
            if (k == 0) {
                const uint4* xp = reinterpret_cast<const uint4*>(prm.px + (size_t)row * DM) + lane;
#pragma unroll
                for (int i = 0; i < 8; i++) {
                    const uint4 v = __ldg(xp + i * 32);
                    pk[4 * i] = v.x; pk[4 * i + 1] = v.y; pk[4 * i + 2] = v.z; pk[4 * i + 3] = v.w;
                }
            } else if (k == 3) {
                float a = row_sum(pk), b = row_sum(pk + 16);
                warp_sum2(a, b);
                pk[32] = __float_as_uint(a * (1.f / DM)); pk[33] = __float_as_uint(b * (1.f / DM));
            } else if (k == 4) {
                pk[34] = __float_as_uint(row_sq(pk, __uint_as_float(pk[32])));
            } else if (k == 5) {
                float a = __uint_as_float(pk[34]), b = row_sq(pk + 16, __uint_as_float(pk[33]));
                warp_sum2(a, b);
                pk[34] = __float_as_uint(a); pk[35] = __float_as_uint(b);
            } else if (k == 6) {
                row_store(pk, __uint_as_float(pk[32]), row_inv(__uint_as_float(pk[34])), row, lane);
            } else if (k == 7) {
                row_store(pk + 16, __uint_as_float(pk[33]), row_inv(__uint_as_float(pk[35])), row + 1, lane);
                signal_stores();
            }
        };

        int pending = 0;
#pragma unroll 1
        for (int t = 0; t < G1_TILES; t++) {
#pragma unroll
            for (int k = 0; k < G1_KSTEPS; k++) {
                const int s = k & 3;
                mbar_wait(full1(s), (k >> 2) & 1);
                if (t == 0 && k == 0 && threadIdx.x == 0) TRACE(12);
                if (wg == 1 && k == G1_KSTEPS - G1_SKEW) asm volatile("bar.sync 1, 256;" ::: "memory");
                const uint64_t da = desc_a(base + s * G1_STAGE_BYTES + wg * 8192);
                const uint64_t db = desc_b(base + s * G1_STAGE_BYTES + A_BYTES);
                wg_fence();
#pragma unroll
                for (int kk = 0; kk < 4; kk++) wgmma_n256(acc, da + kk * 2, db + kk * 128, (k | kk) != 0);
                wg_commit();
                if (wg == 0 && k == G1_KSTEPS - 1) asm volatile("bar.arrive 1, 256;" ::: "memory");
                if (k <= 7 && pending == 0) chunk_ln(k);
                if (k >= 1 && k <= 8) {
                    if (pending == 2) chunk_geglu(k - 1);
                    else if (pending == 1) chunk_qkv(k - 1);
                    if (k == 8 && pending) signal_stores();
                }
                wg_wait<1>();
                if (k > 0) release(empty1((k - 1) & 3));
            }
            if (t == 0) mbar_wait(fold_bar, 0);
            wg_wait<0>();
            fence_regs(acc);
            release(empty1(3));
            if (t == 0) {
                const uint32_t sp = aux + 1024 + (cw * 16 + (lane >> 2)) * 8;
                const float2 sa = lds64f(sp), sb = lds64f(sp + 64);
#pragma unroll
                for (int j = 0; j < 16; j++) {
                    const uint4 c = lds128(aux + j * 64 + (lane & 3) * 16);
                    const float c0 = __uint_as_float(c.x), c1 = __uint_as_float(c.y);
                    const float c2 = __uint_as_float(c.z), c3 = __uint_as_float(c.w);
                    const float* a = acc + 8 * j;
                    pk[4 * j] = pack_bf16(fmaf(sa.x, c0, a[0]) * sa.y, fmaf(sa.x, c1, a[1]) * sa.y);
                    pk[4 * j + 1] = pack_bf16(fmaf(sb.x, c0, a[2]) * sb.y, fmaf(sb.x, c1, a[3]) * sb.y);
                    pk[4 * j + 2] = pack_bf16(fmaf(sa.x, c2, a[4]) * sa.y, fmaf(sa.x, c3, a[5]) * sa.y);
                    pk[4 * j + 3] = pack_bf16(fmaf(sb.x, c2, a[6]) * sb.y, fmaf(sb.x, c3, a[7]) * sb.y);
                }
            } else {
#pragma unroll
                for (int i = 0; i < 64; i++) pk[i] = pack_bf16(acc[2 * i], acc[2 * i + 1]);
            }
            const int nt = t * 8 + nslot;
            pending = tile_is_qkv(nt) ? 1 : 2;
            optr = pending == 1 ? g_qkv + (size_t)orow * NQKV + tile_index(nt) * 256 + (lane & 3) * 8
                                : g_a2 + (size_t)orow * K2 + DM + tile_index(nt) * 128 + (lane & 3) * 8;
            if (tid == 0) TRACE(16 + wg * 8 + t);
        }

        float accd[64], accs[64];
#pragma unroll
        for (int i = 0; i < 64; i++) accd[i] = 0.f;
#pragma unroll
        for (int u = 0; u < 9; u++) {
            const int q = u % G2_STAGES;
            mbar_wait(full2(q), (u / G2_STAGES) & 1);
            const uint64_t da = desc_a(stage2(q) + wg * 8192), db = desc_b(stage2(q) + A_BYTES);
            wg_fence();
#pragma unroll
            for (int kk = 0; kk < 4; kk++) wgmma_n128(accd, da + kk * 2, db + kk * 128, (u | kk) != 0);
            wg_commit();
            if (u >= 1) { chunk_geglu(u - 1); if (u == 8) signal_stores(); }
            wg_wait<1>();
            if (u > 0) release(empty2((u - 1) % G2_STAGES));
        }
        {
            int q = 9 % G2_STAGES, qp = 8 % G2_STAGES; uint32_t ph = (9 / G2_STAGES) & 1;
#pragma unroll 1
            for (int u = 9; u < G2_DSTEPS; u++) {
                mbar_wait(full2(q), ph);
                const uint64_t da = desc_a(stage2(q) + wg * 8192), db = desc_b(stage2(q) + A_BYTES);
                wg_fence();
#pragma unroll
                for (int kk = 0; kk < 4; kk++) wgmma_n128(accd, da + kk * 2, db + kk * 128, 1);
                wg_commit();
                wg_wait<1>();
                release(empty2(qp));
                qp = q;
                if (++q == G2_STAGES) { q = 0; ph ^= 1; }
            }
        }
        if (tid == 0) TRACE(16 + wg * 8 + 5);
#pragma unroll
        for (int i = 0; i < 64; i++) accs[i] = 0.f;
        uint32_t gk[32], xr[32];
        const uint32_t xs = aux + cw * 2048;
        const uint32_t xrow = xs + ((lane & 7) + ((lane >> 3) & 1) * 8) * 128;
        auto xaddr = [&](int j) { return xrow + (j >> 2) * 16384 + (((((j & 3) * 2) + (lane >> 4)) ^ (lane & 7)) << 4); };
#pragma unroll
        for (int u = G2_DSTEPS; u < G2_KSTEPS; u++) {
            const int q = u % G2_STAGES, v = u - G2_DSTEPS;
            mbar_wait(full2(q), (u / G2_STAGES) & 1);
            if (G2_SKEW > 0 && wg == 1 && u == G2_KSTEPS - G2_SKEW) asm volatile("bar.sync 1, 256;" ::: "memory");
            const uint64_t da = desc_a(stage2(q) + wg * 8192), db = desc_b(stage2(q) + A_BYTES);
            wg_fence();
#pragma unroll
            for (int kk = 0; kk < 4; kk++) wgmma_n128(accs, da + kk * 2, db + kk * 128, (v | kk) != 0);
            wg_commit();
            if (G2_SKEW > 0 && wg == 0 && u == G2_KSTEPS - 1) asm volatile("bar.arrive 1, 256;" ::: "memory");
            if (v >= 1 && v <= 8) {
#pragma unroll
                for (int i = 4 * (v - 1); i < 4 * v; i++) {
                    const uint32_t d2 = pack_bf16(accd[2 * i], accd[2 * i + 1]);
                    gk[i] = pack_bf16(silu(bf_lo(d2)), silu(bf_hi(d2)));
                }
            }
            if (v == 9) mbar_wait(x_bar, 0);
            if (v >= 9 && v <= 12) {
#pragma unroll
                for (int j = 2 * (v - 9); j < 2 * (v - 8); j++)
                    asm volatile("ldmatrix.sync.aligned.m8n8.x4.shared.b16 {%0,%1,%2,%3}, [%4];"
                                 : "=r"(xr[4 * j]), "=r"(xr[4 * j + 1]), "=r"(xr[4 * j + 2]), "=r"(xr[4 * j + 3])
                                 : "r"(xaddr(j)) : "memory");
            }
            wg_wait<1>();
            if (v == 0) fence_regs(accd);
            if (u - 1 + G2_STAGES < G2_KSTEPS) release(empty2((u - 1) % G2_STAGES));
        }
        wg_wait<0>();
        fence_regs(accs);
        if (tid == 0) TRACE(16 + wg * 8 + 6);
#pragma unroll
        for (int j = 0; j < 8; j++) {
            uint32_t r[4];
#pragma unroll
            for (int i = 0; i < 4; i++) {
                const int e = j * 4 + i;
                r[i] = add_bf16x2(xr[e], mul_bf16x2(pack_bf16(accs[2 * e], accs[2 * e + 1]), gk[e]));
            }
            asm volatile("stmatrix.sync.aligned.m8n8.x4.shared.b16 [%0], {%1,%2,%3,%4};"
                         :: "r"(xaddr(j)), "r"(r[0]), "r"(r[1]), "r"(r[2]), "r"(r[3]) : "memory");
            if (j == 3 || j == 7) {
                asm volatile("fence.proxy.async.shared::cta;" ::: "memory");
                __syncwarp();
                if (lane == 0) {
                    tma_store_2d(&prm.out, xs + (j >> 2) * 16384, nslot * 128 + (j >> 2) * 64, mblk * 128 + cw * 16);
                    asm volatile("cp.async.bulk.commit_group;" ::: "memory");
                }
            }
        }
        if (lane == 0) asm volatile("cp.async.bulk.wait_group.read 0;" ::: "memory");
        if (tid == 0) { TRACE(16 + wg * 8 + 7); if (wg == 1) TRACE_GT(13); }
    }
}

typedef CUresult (*EncodeFn)(CUtensorMap*, CUtensorMapDataType, cuuint32_t, void*, const cuuint64_t*, const cuuint64_t*,
                             const cuuint32_t*, const cuuint32_t*, CUtensorMapInterleave, CUtensorMapSwizzle,
                             CUtensorMapL2promotion, CUtensorMapFloatOOBfill);

void encode(EncodeFn fn, CUtensorMap* m, const void* ptr, int rank, const cuuint64_t* dims, const cuuint64_t* strides,
            const cuuint32_t* box) {
    const cuuint32_t es[5] = {1, 1, 1, 1, 1};
    fn(m, CU_TENSOR_MAP_DATA_TYPE_BFLOAT16, rank, const_cast<void*>(ptr), dims, strides, box, es,
       CU_TENSOR_MAP_INTERLEAVE_NONE, CU_TENSOR_MAP_SWIZZLE_128B, CU_TENSOR_MAP_L2_PROMOTION_L2_128B,
       CU_TENSOR_MAP_FLOAT_OOB_FILL_NONE);
}
void encode_2d(EncodeFn fn, CUtensorMap* m, const void* ptr, int cols, int box_rows) {
    const cuuint64_t dims[2] = {(cuuint64_t)cols, SEQ}, strides[1] = {(cuuint64_t)cols * 2};
    const cuuint32_t box[2] = {64, (cuuint32_t)box_rows};
    encode(fn, m, ptr, 2, dims, strides, box);
}
void encode_w1(EncodeFn fn, CUtensorMap* m, const void* ptr, int cols) {
    const cuuint64_t dims[3] = {64, DM, (cuuint64_t)cols / 64}, strides[2] = {(cuuint64_t)cols * 2, 128};
    const cuuint32_t box[3] = {64, 64, 2};
    encode(fn, m, ptr, 3, dims, strides, box);
}
void encode_qkv(EncodeFn fn, CUtensorMap* m, const void* ptr) {
    const cuuint64_t dims[5] = {64, SEQ / 2, 3, 2, DM / 64}, strides[4] = {NQKV * 4, DM * 2, NQKV * 2, 128};
    const cuuint32_t box[5] = {64, 16, 3, 2, 4};
    encode(fn, m, ptr, 5, dims, strides, box);
}
void encode_o(EncodeFn fn, CUtensorMap* m, const void* ptr) {
    const cuuint64_t dims[4] = {64, SEQ / 2, 2, DM / 64}, strides[3] = {K2 * 4, K2 * 2, 128};
    const cuuint32_t box[4] = {64, 16, 2, 4};
    encode(fn, m, ptr, 4, dims, strides, box);
}
void encode_w2(EncodeFn fn, CUtensorMap* m, const void* ptr, int rows) {
    const cuuint64_t rb = DM * 2;
    const cuuint64_t dims[5] = {DM, 2, 4, 4, (cuuint64_t)rows / 32}, strides[4] = {rb, 8 * rb, 2 * rb, 32 * rb};
    const cuuint32_t box[5] = {64, 2, 4, 4, 2};
    encode(fn, m, ptr, 5, dims, strides, box);
}

}

extern "C" void kernel_launch(void* const* d_in, const int* in_sizes, int n_in, void* d_out, int out_size) {
    (void)in_sizes; (void)n_in; (void)out_size;
    static EncodeFn fn = nullptr;
    static void *p_xn = nullptr, *p_qkv = nullptr, *p_a2 = nullptr;
    if (!fn) {
        cudaDriverEntryPointQueryResult st;
        cudaGetDriverEntryPoint("cuTensorMapEncodeTiled", (void**)&fn, cudaEnableDefault, &st);
        cudaGetSymbolAddress(&p_xn, g_xn);
        cudaGetSymbolAddress(&p_qkv, g_qkv);
        cudaGetSymbolAddress(&p_a2, g_a2);
        cudaFuncSetAttribute(fused_kernel, cudaFuncAttributeMaxDynamicSharedMemorySize, SMEM_BYTES);
    }
    Params prm;
    encode_2d(fn, &prm.x, d_in[0], DM, 128);
    encode_2d(fn, &prm.xn, p_xn, DM, 128);
    encode_w1(fn, &prm.wqkv, d_in[1], NQKV);
    encode_w1(fn, &prm.wg, d_in[4], DF);
    encode_w1(fn, &prm.wu, d_in[5], DF);
    encode_qkv(fn, &prm.qkv, p_qkv);
    encode_o(fn, &prm.o, p_a2);
    encode_2d(fn, &prm.a2, p_a2, K2, 128);
    encode_w2(fn, &prm.wo, d_in[2], DM);
    encode_w2(fn, &prm.wd, d_in[6], DF);
    encode_2d(fn, &prm.out, d_out, DM, 16);
    prm.px = (const __nv_bfloat16*)d_in[0];
    prm.pwqkv = (const __nv_bfloat16*)d_in[1];
    prm.pwg = (const __nv_bfloat16*)d_in[4];
    prm.pwu = (const __nv_bfloat16*)d_in[5];
    fused_kernel<<<NCTA, 384, SMEM_BYTES>>>(prm);
}
```

```cpp
#include <cuda_runtime.h>
#include <cuda_bf16.h>
#include <cuda.h>
#include <stdint.h>

namespace {

constexpr int SEQ = 2048, DM = 1024, DF = 3584, K2 = DM + DF, NQKV = 3 * DM;
constexpr int NGEMM = 128, NCTA = 132;
constexpr int G1_STAGES = 4, G1_STAGE_BYTES = 49152, G1_KSTEPS = 16, G1_TILES = 5;
constexpr int G2_STAGES = 6, G2_STAGE_BYTES = 32768, G2_KSTEPS = 72, G2_DSTEPS = 56, G2_LATE = 40;
constexpr int A_BYTES = 16384;
constexpr int AUX_OFF = G1_STAGES * G1_STAGE_BYTES;
constexpr int BAR_OFF = AUX_OFF + 32768;
constexpr int SMEM_BYTES = BAR_OFF + 1024 + 256;
constexpr int G1_SKEW = 2, G2_SKEW = 2;
constexpr int CONSUMER_REGS = 224, AUX_REGS = 56;
constexpr int ATT_STEPS = 32;

enum { F_LN = 0, F_QKV = 1, F_EARLY = 2, F_LATE = 3, F_O = 4, F_CS = 5 };
constexpr unsigned CNT_LN = 8, CNT_QKV = 48, CNT_EARLY = 20, CNT_LATE = 8, CNT_O = 8, CNT_CS = 32;

__device__ __align__(1024) __nv_bfloat16 g_xn[SEQ * DM];
__device__ __align__(1024) __nv_bfloat16 g_qkv[SEQ * NQKV];
__device__ __align__(1024) __nv_bfloat16 g_a2[SEQ * K2];
__device__ __align__(128) float2 g_stats[SEQ];
__device__ __align__(128) float g_colsum[32 * 2048];
__device__ __align__(128) unsigned g_flags[6 * 16 * 32];
__device__ __align__(128) unsigned g_epoch[NCTA * 8];

#define TRACE(slot) do {} while (0)
#define TRACE_GT(slot) do {} while (0)

__device__ __forceinline__ uint32_t smem_u32(const void* p) { return (uint32_t)__cvta_generic_to_shared(p); }
__device__ __forceinline__ void mbar_init(uint32_t bar, uint32_t cnt) {
    asm volatile("mbarrier.init.shared::cta.b64 [%0], %1;" :: "r"(bar), "r"(cnt) : "memory");
}
__device__ __forceinline__ void mbar_expect_tx(uint32_t bar, uint32_t bytes) {
    asm volatile("mbarrier.arrive.expect_tx.shared::cta.b64 _, [%0], %1;" :: "r"(bar), "r"(bytes) : "memory");
}
__device__ __forceinline__ void mbar_arrive(uint32_t bar) {
    asm volatile("mbarrier.arrive.shared::cta.b64 _, [%0];" :: "r"(bar) : "memory");
}
__device__ __forceinline__ void mbar_arrive_cluster(uint32_t bar, uint32_t cta) {
    asm volatile("{\n.reg .b32 ra;\nmapa.shared::cluster.u32 ra, %0, %1;\nmbarrier.arrive.shared::cluster.b64 _, [ra];\n}"
                 :: "r"(bar), "r"(cta) : "memory");
}
__device__ __forceinline__ bool mbar_try_wait(uint32_t bar, uint32_t parity) {
    uint32_t ok;
    asm volatile("{\n.reg .pred p;\nmbarrier.try_wait.parity.shared::cta.b64 p, [%1], %2;\nselp.u32 %0, 1, 0, p;\n}"
                 : "=r"(ok) : "r"(bar), "r"(parity) : "memory");
    return ok;
}
__device__ __forceinline__ void mbar_wait(uint32_t bar, uint32_t parity) {
    int spins = 0;
    while (!mbar_try_wait(bar, parity)) { if (++spins > (1 << 17)) break; }
}
__device__ __forceinline__ void flag_wait(const unsigned* p, unsigned target) {
    for (int spins = 0; spins < (1 << 19); spins++) {
        unsigned v;
        asm volatile("ld.acquire.gpu.global.u32 %0, [%1];" : "=r"(v) : "l"(p) : "memory");
        if ((int)(v - target) >= 0) break;
        __nanosleep(64);
    }
}
__device__ __forceinline__ void flag_add(unsigned* p) {
    asm volatile("red.release.gpu.global.add.u32 [%0], 1;" :: "l"(p) : "memory");
}
__device__ __forceinline__ void fence_proxy_async() { asm volatile("fence.proxy.async;" ::: "memory"); }
__device__ __forceinline__ uint4 lds128(uint32_t addr) {
    uint4 v;
    asm volatile("ld.shared.v4.u32 {%0,%1,%2,%3}, [%4];" : "=r"(v.x), "=r"(v.y), "=r"(v.z), "=r"(v.w) : "r"(addr) : "memory");
    return v;
}
__device__ __forceinline__ float2 lds64f(uint32_t addr) {
    float2 v;
    asm volatile("ld.shared.v2.f32 {%0,%1}, [%2];" : "=f"(v.x), "=f"(v.y) : "r"(addr) : "memory");
    return v;
}
__device__ __forceinline__ void sts128(uint32_t addr, uint4 v) {
    asm volatile("st.shared.v4.u32 [%0], {%1,%2,%3,%4};" :: "r"(addr), "r"(v.x), "r"(v.y), "r"(v.z), "r"(v.w) : "memory");
}
__device__ __forceinline__ void sts64f(uint32_t addr, float a, float b) {
    asm volatile("st.shared.v2.f32 [%0], {%1,%2};" :: "r"(addr), "f"(a), "f"(b) : "memory");
}

__device__ __forceinline__ void tma_2d(uint32_t dst, const CUtensorMap* m, uint32_t bar, int c0, int c1) {
    asm volatile("cp.async.bulk.tensor.2d.shared::cluster.global.mbarrier::complete_tx::bytes [%0], [%1, {%3, %4}], [%2];"
                 :: "r"(dst), "l"(m), "r"(bar), "r"(c0), "r"(c1) : "memory");
}
__device__ __forceinline__ void tma_5d(uint32_t dst, const CUtensorMap* m, uint32_t bar, int c1, int c4) {
    asm volatile("cp.async.bulk.tensor.5d.shared::cluster.global.mbarrier::complete_tx::bytes [%0], [%1, {%3, %4, %3, %3, %5}], [%2];"
                 :: "r"(dst), "l"(m), "r"(bar), "r"(0), "r"(c1), "r"(c4) : "memory");
}
__device__ __forceinline__ void tma_store_4d(const CUtensorMap* m, uint32_t src, int c1, int c3) {
    asm volatile("cp.async.bulk.tensor.4d.global.shared::cta.bulk_group [%0, {%2, %3, %2, %4}], [%1];"
                 :: "l"(m), "r"(src), "r"(0), "r"(c1), "r"(c3) : "memory");
}
__device__ __forceinline__ void tma_3d_mc(uint32_t dst, const CUtensorMap* m, uint32_t bar, int c1, int c2) {
    asm volatile("cp.async.bulk.tensor.3d.shared::cluster.global.mbarrier::complete_tx::bytes.multicast::cluster"
                 " [%0], [%1, {%3, %4, %5}], [%2], %6;"
                 :: "r"(dst), "l"(m), "r"(bar), "r"(0), "r"(c1), "r"(c2), "h"((uint16_t)3) : "memory");
}
__device__ __forceinline__ void tma_5d_mc(uint32_t dst, const CUtensorMap* m, uint32_t bar, int c0, int c4) {
    asm volatile("cp.async.bulk.tensor.5d.shared::cluster.global.mbarrier::complete_tx::bytes.multicast::cluster"
                 " [%0], [%1, {%3, %4, %4, %4, %5}], [%2], %6;"
                 :: "r"(dst), "l"(m), "r"(bar), "r"(c0), "r"(0), "r"(c4), "h"((uint16_t)3) : "memory");
}
__device__ __forceinline__ void tma_store_2d(const CUtensorMap* m, uint32_t src, int c0, int c1) {
    asm volatile("cp.async.bulk.tensor.2d.global.shared::cta.bulk_group [%0, {%2, %3}], [%1];"
                 :: "l"(m), "r"(src), "r"(c0), "r"(c1) : "memory");
}
__device__ __forceinline__ void prefetch_map(const CUtensorMap* m) {
    asm volatile("prefetch.tensormap [%0];" :: "l"(m) : "memory");
}
__device__ __forceinline__ void wg_fence() { asm volatile("wgmma.fence.sync.aligned;" ::: "memory"); }
__device__ __forceinline__ void wg_commit() { asm volatile("wgmma.commit_group.sync.aligned;" ::: "memory"); }
template <int N> __device__ __forceinline__ void wg_wait() { asm volatile("wgmma.wait_group.sync.aligned %0;" :: "n"(N) : "memory"); }

__device__ __forceinline__ uint64_t desc_a(uint32_t addr) {
    return (uint64_t)((addr & 0x3FFFF) >> 4) | (1ull << 16) | (64ull << 32) | (1ull << 62);
}
__device__ __forceinline__ uint64_t desc_b(uint32_t addr) {
    return (uint64_t)((addr & 0x3FFFF) >> 4) | (512ull << 16) | (64ull << 32) | (1ull << 62);
}

#define R8(d, o) "+f"(d[o]), "+f"(d[o+1]), "+f"(d[o+2]), "+f"(d[o+3]), "+f"(d[o+4]), "+f"(d[o+5]), "+f"(d[o+6]), "+f"(d[o+7])
#define R32(d, o) R8(d, o), R8(d, o+8), R8(d, o+16), R8(d, o+24)
#define R64(d, o) R32(d, o), R32(d, o+32)

__device__ __forceinline__ void wgmma_n256(float (&d)[128], uint64_t da, uint64_t db, int scale_d) {
    asm volatile("{\n.reg .pred p;\nsetp.ne.b32 p, %130, 0;\n"
        "wgmma.mma_async.sync.aligned.m64n256k16.f32.bf16.bf16 "
        "{%0,%1,%2,%3,%4,%5,%6,%7,%8,%9,%10,%11,%12,%13,%14,%15,%16,%17,%18,%19,%20,%21,%22,%23,%24,%25,%26,%27,%28,%29,%30,%31,"
        "%32,%33,%34,%35,%36,%37,%38,%39,%40,%41,%42,%43,%44,%45,%46,%47,%48,%49,%50,%51,%52,%53,%54,%55,%56,%57,%58,%59,%60,%61,%62,%63,"
        "%64,%65,%66,%67,%68,%69,%70,%71,%72,%73,%74,%75,%76,%77,%78,%79,%80,%81,%82,%83,%84,%85,%86,%87,%88,%89,%90,%91,%92,%93,%94,%95,"
        "%96,%97,%98,%99,%100,%101,%102,%103,%104,%105,%106,%107,%108,%109,%110,%111,%112,%113,%114,%115,%116,%117,%118,%119,%120,%121,%122,%123,%124,%125,%126,%127},"
        " %128, %129, p, 1, 1, 0, 1;\n}"
        : R64(d, 0), R64(d, 64) : "l"(da), "l"(db), "r"(scale_d));
}
__device__ __forceinline__ void wgmma_n128(float (&d)[64], uint64_t da, uint64_t db, int scale_d) {
    asm volatile("{\n.reg .pred p;\nsetp.ne.b32 p, %66, 0;\n"
        "wgmma.mma_async.sync.aligned.m64n128k16.f32.bf16.bf16 "
        "{%0,%1,%2,%3,%4,%5,%6,%7,%8,%9,%10,%11,%12,%13,%14,%15,%16,%17,%18,%19,%20,%21,%22,%23,%24,%25,%26,%27,%28,%29,%30,%31,"
        "%32,%33,%34,%35,%36,%37,%38,%39,%40,%41,%42,%43,%44,%45,%46,%47,%48,%49,%50,%51,%52,%53,%54,%55,%56,%57,%58,%59,%60,%61,%62,%63},"
        " %64, %65, p, 1, 1, 0, 1;\n}"
        : R64(d, 0) : "l"(da), "l"(db), "r"(scale_d));
}

__device__ __forceinline__ uint32_t pack_bf16(float lo, float hi) {
    uint32_t r; asm("cvt.rn.bf16x2.f32 %0, %1, %2;" : "=r"(r) : "f"(hi), "f"(lo)); return r;
}
__device__ __forceinline__ float bf_lo(uint32_t v) { return __uint_as_float(v << 16); }
__device__ __forceinline__ float bf_hi(uint32_t v) { return __uint_as_float(v & 0xffff0000u); }
__device__ __forceinline__ float round_bf16(float v) { return bf_lo(pack_bf16(v, 0.f)); }
__device__ __forceinline__ uint32_t mul_bf16x2(uint32_t a, uint32_t b) {
    uint32_t r; asm("mul.rn.bf16x2 %0, %1, %2;" : "=r"(r) : "r"(a), "r"(b)); return r;
}
__device__ __forceinline__ uint32_t add_bf16x2(uint32_t a, uint32_t b) {
    uint32_t r; asm("add.rn.bf16x2 %0, %1, %2;" : "=r"(r) : "r"(a), "r"(b)); return r;
}
__device__ __forceinline__ uint32_t sub_bf16x2(uint32_t a, uint32_t b) {
    uint32_t r; asm("sub.rn.bf16x2 %0, %1, %2;" : "=r"(r) : "r"(a), "r"(b)); return r;
}
__device__ __forceinline__ float tanh_fast(float x) { float r; asm("tanh.approx.f32 %0, %1;" : "=f"(r) : "f"(x)); return r; }
__device__ __forceinline__ float gelu_tanh(float g) {
    float t = fmaf(g * g, 0.044715f * 0.7978845608f, 0.7978845608f) * g;
    float hg = 0.5f * g;
    return fmaf(hg, tanh_fast(t), hg);
}
__device__ __forceinline__ uint32_t geglu2(uint32_t g2, uint32_t u2) {
    return mul_bf16x2(pack_bf16(gelu_tanh(bf_lo(g2)), gelu_tanh(bf_hi(g2))), u2);
}
__device__ __forceinline__ float silu(float d) {
    float hd = 0.5f * d;
    return fmaf(hd, tanh_fast(hd), hd);
}
__device__ __forceinline__ float ex2_fast(float x) { float r; asm("ex2.approx.ftz.f32 %0, %1;" : "=f"(r) : "f"(x)); return r; }
__device__ __forceinline__ void unpack8(uint4 v, float (&f)[8]) {
    f[0] = bf_lo(v.x); f[1] = bf_hi(v.x); f[2] = bf_lo(v.y); f[3] = bf_hi(v.y);
    f[4] = bf_lo(v.z); f[5] = bf_hi(v.z); f[6] = bf_lo(v.w); f[7] = bf_hi(v.w);
}
template <int N> __device__ __forceinline__ void fence_regs(float (&d)[N]) {
#pragma unroll
    for (int i = 0; i < N; i++) asm volatile("" : "+f"(d[i]) :: "memory");
}

__device__ __forceinline__ float rcp_fast(float x) { float r; asm("rcp.approx.ftz.f32 %0, %1;" : "=f"(r) : "f"(x)); return r; }
__device__ __forceinline__ uint32_t max_bf16x2(uint32_t a, uint32_t b) {
    uint32_t r; asm("max.bf16x2 %0, %1, %2;" : "=r"(r) : "r"(a), "r"(b)); return r;
}
__device__ __forceinline__ uint4 ldsm4(uint32_t addr) {
    uint4 v;
    asm volatile("ldmatrix.sync.aligned.m8n8.x4.shared.b16 {%0,%1,%2,%3}, [%4];"
                 : "=r"(v.x), "=r"(v.y), "=r"(v.z), "=r"(v.w) : "r"(addr) : "memory");
    return v;
}
__device__ __forceinline__ uint4 ldsm4_t(uint32_t addr) {
    uint4 v;
    asm volatile("ldmatrix.sync.aligned.m8n8.x4.trans.shared.b16 {%0,%1,%2,%3}, [%4];"
                 : "=r"(v.x), "=r"(v.y), "=r"(v.z), "=r"(v.w) : "r"(addr) : "memory");
    return v;
}
__device__ __forceinline__ void mma_16816(float (&c)[4], uint32_t a0, uint32_t a1, uint32_t a2, uint32_t a3, uint32_t b0, uint32_t b1) {
    asm("mma.sync.aligned.m16n8k16.row.col.f32.bf16.bf16.f32 {%0,%1,%2,%3}, {%4,%5,%6,%7}, {%8,%9}, {%0,%1,%2,%3};"
        : "+f"(c[0]), "+f"(c[1]), "+f"(c[2]), "+f"(c[3]) : "r"(a0), "r"(a1), "r"(a2), "r"(a3), "r"(b0), "r"(b1));
}
__device__ __forceinline__ void mma_1688(float (&c)[4], uint32_t a0, uint32_t a1, uint32_t b0) {
    asm("mma.sync.aligned.m16n8k8.row.col.f32.bf16.bf16.f32 {%0,%1,%2,%3}, {%4,%5}, {%6}, {%0,%1,%2,%3};"
        : "+f"(c[0]), "+f"(c[1]), "+f"(c[2]), "+f"(c[3]) : "r"(a0), "r"(a1), "r"(b0));
}
__device__ __forceinline__ void qk_tile(float (&c)[4], const uint4& q0, const uint4& q1, const uint4& k) {
    c[0] = c[1] = c[2] = c[3] = 0.f;
    mma_16816(c, q0.x, q0.y, q0.z, q0.w, k.x, k.y);
    mma_16816(c, q1.x, q1.y, q1.z, q1.w, k.z, k.w);
}
__device__ __forceinline__ uint32_t scaled_logits(float lo, float hi) {
    const uint32_t p = pack_bf16(lo, hi);
    uint32_t r;
    asm("fma.rn.bf16x2 %0, %1, %2, %3;" : "=r"(r) : "r"(p), "r"(0x3e353e35u), "r"(mul_bf16x2(p, 0x379e379eu)));
    return r;
}

__device__ __forceinline__ uint4 pv_tile(const uint4& vp, const uint4& vo, uint32_t p, uint32_t keep) {
    float a[4] = {0.f, 0.f, 0.f, 0.f}, b[4] = {0.f, 0.f, 0.f, 0.f};
    mma_1688(a, vp.x, vp.y, p & keep); mma_1688(b, vp.z, vp.w, p & keep);
    mma_1688(a, vo.x, vo.y, p & ~keep); mma_1688(b, vo.z, vo.w, p & ~keep);
    return make_uint4(pack_bf16(a[0], a[1]), pack_bf16(a[2], a[3]), pack_bf16(b[0], b[1]), pack_bf16(b[2], b[3]));
}

__device__ __forceinline__ void attention(uint32_t in, uint32_t out, uint32_t full, uint32_t empty, uint32_t o_ready,
                                          uint32_t o_free, int lane) {
    constexpr float LOG2E = 1.4426950408889634f;
    const int g = lane >> 2, t = lane & 3;
    const bool up0 = 2 * t > g, up1 = 2 * t + 1 > g;
    const uint32_t keep = (up0 ? 0x0000ffffu : 0u) | (up1 ? 0xffff0000u : 0u);
    uint32_t mask0 = up0 ? 0xffffu : 0u, mask1 = up1 ? 0xffffu : 0u;
    const uint32_t neg = pack_bf16(-1e9f, 0.f);
    const uint32_t qoff = (lane & 15) * 128 + (((lane >> 4) ^ (lane & 7)) << 4);
    const uint32_t koff = (lane & 7) * 128 + (((lane >> 3) ^ (lane & 7)) << 4);
#define TACC(i) do {} while (0)
    uint4 k[2][5], v[2][5];
#pragma unroll
    for (int h = 0; h < 2; h++) { k[h][4] = make_uint4(0, 0, 0, 0); v[h][4] = make_uint4(0, 0, 0, 0); }
#pragma unroll 1
    for (int step = 0; step < ATT_STEPS; step++) {
        const uint32_t st = in + (step & 1) * G1_STAGE_BYTES;
        uint4 q[2][2][2];
#pragma unroll
        for (int h = 0; h < 2; h++) { k[h][0] = k[h][4]; v[h][0] = v[h][4]; }
        mbar_wait(full + (step & 1) * 8, (step >> 1) & 1);
        TACC(0);
#pragma unroll
        for (int u = 0; u < 2; u++) {
#pragma unroll
            for (int h = 0; h < 2; h++) {
                q[h][u][0] = ldsm4(st + u * 2048 + (qoff ^ (h * 64)));
                q[h][u][1] = ldsm4(st + u * 2048 + (qoff ^ (h * 64 + 32)));
                k[h][2 * u + 1] = ldsm4(st + 4096 + u * 2048 + (koff ^ (h * 64)));
                k[h][2 * u + 2] = ldsm4(st + 5120 + u * 2048 + (koff ^ (h * 64)));
            }
        }
#pragma unroll
        for (int j = 0; j < 4; j++) {
#pragma unroll
            for (int h = 0; h < 2; h++) v[h][j + 1] = ldsm4_t(st + 8192 + j * 1024 + (koff ^ (h * 64)));
        }
        __syncwarp();
        if (lane == 0) mbar_arrive(empty + (step & 1) * 8);
        TACC(1);
        uint32_t p[2][4];
#pragma unroll
        for (int u = 0; u < 2; u++) {
#pragma unroll
            for (int h = 0; h < 2; h++) {
                float s0[4], s1[4], s2[4];
                qk_tile(s0, q[h][u][0], q[h][u][1], k[h][2 * u]);
                qk_tile(s1, q[h][u][0], q[h][u][1], k[h][2 * u + 1]);
                qk_tile(s2, q[h][u][0], q[h][u][1], k[h][2 * u + 2]);
                uint32_t l0 = scaled_logits(up0 ? s0[0] : s1[0], up0 ? s1[2] : s2[2]);
                uint32_t l1 = scaled_logits(up1 ? s0[1] : s1[1], up1 ? s1[3] : s2[3]);
                if (u == 0) {
                    l0 = (l0 & ~mask0) | (neg & mask0);
                    l1 = (l1 & ~mask1) | (neg & mask1);
                }
                uint32_t m = max_bf16x2(l0, l1);
                m = max_bf16x2(m, __shfl_xor_sync(0xffffffffu, m, 1));
                m = max_bf16x2(m, __shfl_xor_sync(0xffffffffu, m, 2));
                const float ea0 = ex2_fast((bf_lo(l0) - bf_lo(m)) * LOG2E), ea1 = ex2_fast((bf_lo(l1) - bf_lo(m)) * LOG2E);
                const float eb0 = ex2_fast((bf_hi(l0) - bf_hi(m)) * LOG2E), eb1 = ex2_fast((bf_hi(l1) - bf_hi(m)) * LOG2E);
                float sa = ea0 + ea1, sb = eb0 + eb1;
                sa += __shfl_xor_sync(0xffffffffu, sa, 1); sb += __shfl_xor_sync(0xffffffffu, sb, 1);
                sa += __shfl_xor_sync(0xffffffffu, sa, 2); sb += __shfl_xor_sync(0xffffffffu, sb, 2);
                const float ra = rcp_fast(sa), rb = rcp_fast(sb);
                p[h][2 * u] = pack_bf16(ea0 * ra, ea1 * ra);
                p[h][2 * u + 1] = pack_bf16(eb0 * rb, eb1 * rb);
            }
        }
        mask0 = 0; mask1 = 0;
        uint4 o[2][4];
#pragma unroll
        for (int j = 0; j < 4; j++) {
#pragma unroll
            for (int h = 0; h < 2; h++) o[h][j] = pv_tile(v[h][j], v[h][j + 1], p[h][j], keep);
        }
        TACC(2);
        mbar_wait(o_free, (step & 1) ^ 1);
        TACC(3);
#pragma unroll
        for (int j = 0; j < 4; j++) {
#pragma unroll
            for (int h = 0; h < 2; h++)
                asm volatile("stmatrix.sync.aligned.m8n8.x4.trans.shared.b16 [%0], {%1,%2,%3,%4};"
                             :: "r"(out + j * 1024 + (koff ^ (h * 64))), "r"(o[h][j].x), "r"(o[h][j].y), "r"(o[h][j].z),
                                "r"(o[h][j].w) : "memory");
        }
        asm volatile("fence.proxy.async.shared::cta;" ::: "memory");
        __syncwarp();
        if (lane == 0) mbar_arrive(o_ready);
        TACC(4);
    }
}

__device__ __forceinline__ void warp_sum2(float& a, float& b) {
#pragma unroll
    for (int o = 16; o > 0; o >>= 1) {
        a += __shfl_xor_sync(0xffffffffu, a, o);
        b += __shfl_xor_sync(0xffffffffu, b, o);
    }
}
__device__ __forceinline__ float row_sum(const uint32_t* w) {
    float a = 0.f, b = 0.f;
#pragma unroll
    for (int i = 0; i < 16; i++) { a += bf_lo(w[i]); b += bf_hi(w[i]); }
    return a + b;
}
__device__ __forceinline__ float row_sq(const uint32_t* w, float mean) {
    float a = 0.f, b = 0.f;
#pragma unroll
    for (int i = 0; i < 16; i++) {
        const float lo = bf_lo(w[i]) - mean, hi = bf_hi(w[i]) - mean;
        a = fmaf(lo, lo, a); b = fmaf(hi, hi, b);
    }
    return a + b;
}
__device__ __forceinline__ float row_inv(float sq) {
    return 1.f / round_bf16(sqrtf(round_bf16(round_bf16(sq * (1.f / DM)) + 1e-5f)));
}
__device__ __forceinline__ void row_store(const uint32_t* w, float mean, float inv, int row, int lane) {
    const uint32_t m2 = pack_bf16(mean, mean);
    __nv_bfloat16* dst = g_xn + (size_t)row * DM + lane * 8;
#pragma unroll
    for (int i = 0; i < 4; i++) {
        uint32_t o[4];
#pragma unroll
        for (int j = 0; j < 4; j++) {
            const uint32_t c = sub_bf16x2(w[i * 4 + j], m2);
            o[j] = pack_bf16(bf_lo(c) * inv, bf_hi(c) * inv);
        }
        *reinterpret_cast<uint4*>(dst + i * 256) = make_uint4(o[0], o[1], o[2], o[3]);
    }
    if (lane == 0) g_stats[row] = make_float2(-bf_lo(m2), inv);
}

struct Params {
    CUtensorMap x, xn, wqkv, wg, wu, qkv, o, a2, wo, wd, out;
    const __nv_bfloat16 *px, *pwqkv, *pwg, *pwu;
};

__device__ __forceinline__ bool tile_is_qkv(int nt) { return nt < 4 || (nt >= 8 && nt < 16); }
__device__ __forceinline__ int tile_index(int nt) { return nt < 4 ? nt + 8 : (nt < 8 ? nt - 4 : (nt < 16 ? nt - 8 : nt - 12)); }

__global__ void __cluster_dims__(2, 1, 1) __launch_bounds__(384, 1)
fused_kernel(const __grid_constant__ Params prm) {
    extern __shared__ __align__(1024) uint8_t smem_raw[];
    const uint32_t base = (smem_u32(smem_raw) + 1023) & ~1023u;
    const uint32_t bars = base + BAR_OFF;
    auto full1 = [&](int s) { return bars + s * 8; };
    auto empty1 = [&](int s) { return bars + 32 + s * 8; };
    auto full2 = [&](int s) { return bars + 64 + s * 8; };
    auto empty2 = [&](int s) { return bars + 128 + s * 8; };
    const uint32_t sig_bar = bars + 192, fold_bar = bars + 200, x_bar = bars + 208, dep_bar = bars + 216;
    auto stage2 = [&](int q) { return base + q * G2_STAGE_BYTES; };
    const uint32_t aux = base + AUX_OFF;

    const int warp = __shfl_sync(0xffffffffu, threadIdx.x >> 5, 0);
    const int lane = threadIdx.x & 31;
    const int rank = blockIdx.x & 1;
    const int mblk = ((blockIdx.x >> 1) & 7) * 2 + rank;
    const int nslot = blockIdx.x >> 4;

    if (blockIdx.x >= NGEMM) {
        const int grp = blockIdx.x - NGEMM;
        if (threadIdx.x == 0) {
            TRACE_GT(0); TRACE(1);
            for (int s = 0; s < G1_STAGES; s++) { mbar_init(full1(s), 1); mbar_init(empty1(s), 4); }
            for (int s = 0; s < 2; s++) { mbar_init(full2(s), 4); mbar_init(empty2(s), 1); }
            asm volatile("fence.proxy.async.shared::cta;" ::: "memory");
        }
        __syncthreads();
        if (warp < 8) {
            const int half = warp >> 2;
            asm volatile("setmaxnreg.inc.sync.aligned.u32 %0;" :: "n"(CONSUMER_REGS));
            attention(base + half * 2 * G1_STAGE_BYTES + (warp & 3) * 12288, aux + warp * 4096, full1(half * 2),
                      empty1(half * 2), full2(half), empty2(half), lane);
        } else {
            const int half = warp & 1;
            asm volatile("setmaxnreg.dec.sync.aligned.u32 %0;" :: "n"(AUX_REGS));
            if (warp < 10 && lane == 0) {
                prefetch_map(&prm.qkv);
                const unsigned epoch = __ldcg(g_epoch + blockIdx.x * 8 + half) + 1;
                flag_wait(g_flags + F_QKV * 512 + grp * 32, epoch * CNT_QKV);
                fence_proxy_async();
                g_epoch[blockIdx.x * 8 + half] = epoch;
                if (half == 0) TRACE(9);
                for (int i = 0; i < ATT_STEPS; i++) {
                    const int s = half * 2 + (i & 1);
                    mbar_wait(empty1(s), ((i >> 1) & 1) ^ 1);
                    mbar_expect_tx(full1(s), G1_STAGE_BYTES);
                    tma_5d(base + s * G1_STAGE_BYTES, &prm.qkv, full1(s), i * 32, grp * 4 + half * 2);
                }
            } else if (lane == 0) {
                prefetch_map(&prm.o);
                for (int i = 0; i < ATT_STEPS; i++) {
                    mbar_wait(full2(half), i & 1);
                    tma_store_4d(&prm.o, aux + half * 16384, i * 32, grp * 4 + half * 2);
                    asm volatile("cp.async.bulk.commit_group;" ::: "memory");
                    asm volatile("cp.async.bulk.wait_group.read 0;" ::: "memory");
                    mbar_arrive(empty2(half));
                }
                asm volatile("cp.async.bulk.wait_group 0;" ::: "memory");
                fence_proxy_async();
                flag_add(g_flags + F_O * 512);
                if (half == 0) TRACE(10);
            }
        }
    } else if (warp >= 8) {
        unsigned* const flags = g_flags + mblk * 32;
        if (warp == 8) {
            if (lane == 0) {
                TRACE_GT(0); TRACE(1);
                prefetch_map(&prm.x); prefetch_map(nslot < 4 ? &prm.wqkv : (rank ? &prm.wu : &prm.wg));
                for (int s = 0; s < G1_STAGES; s++) { mbar_init(full1(s), 1); mbar_init(empty1(s), 4); }
                for (int s = 0; s < G2_STAGES; s++) { mbar_init(full2(s), 1); mbar_init(empty2(s), 4); }
                mbar_init(sig_bar, 8); mbar_init(fold_bar, 2); mbar_init(x_bar, 1);
                for (int s = 0; s < 4; s++) mbar_init(dep_bar + s * 8, 1);
                asm volatile("fence.mbarrier_init.release.cluster;" ::: "memory");
            }
            __syncwarp();
        }
        asm volatile("barrier.cluster.arrive.relaxed.aligned;" ::: "memory");
        if (warp == 8 && lane == 0) {
            asm volatile("fence.proxy.async.shared::cta;" ::: "memory");
            for (int s = 0; s < G1_STAGES; s++) {
                mbar_expect_tx(full1(s), G1_STAGE_BYTES);
                tma_2d(base + s * G1_STAGE_BYTES, &prm.x, full1(s), s * 64, mblk * 128);
            }
            TRACE(15);
        }
        asm volatile("setmaxnreg.dec.sync.aligned.u32 %0;" :: "n"(AUX_REGS));
        asm volatile("barrier.cluster.wait.acquire.aligned;" ::: "memory");

        if (warp == 8) {
            if (lane == 0) {
                TRACE(2);
                auto load_b1 = [&](int s, int nt, int k) {
                    const uint32_t dst = base + s * G1_STAGE_BYTES + A_BYTES + rank * 16384;
                    if (tile_is_qkv(nt)) tma_3d_mc(dst, &prm.wqkv, full1(s), k * 64, tile_index(nt) * 4 + rank * 2);
                    else tma_3d_mc(dst, rank ? &prm.wu : &prm.wg, full1(s), k * 64, tile_index(nt) * 2);
                };
                for (int s = 0; s < G1_STAGES; s++) load_b1(s, nslot, s);
                prefetch_map(&prm.xn); prefetch_map(&prm.wqkv); prefetch_map(rank ? &prm.wu : &prm.wg);
                prefetch_map(&prm.a2); prefetch_map(&prm.wo); prefetch_map(&prm.wd); prefetch_map(&prm.out);
                uint32_t ph = 0;
                for (int it = G1_STAGES; it < G1_TILES * G1_KSTEPS; it++) {
                    const int s = it & 3, k = it & 15;
                    if (it == G1_KSTEPS) { TRACE(14); mbar_wait(dep_bar, 0); TRACE(3); }
                    mbar_wait(empty1(s), ph);
                    mbar_expect_tx(full1(s), G1_STAGE_BYTES);
                    tma_2d(base + s * G1_STAGE_BYTES, it < G1_KSTEPS ? &prm.x : &prm.xn, full1(s), k * 64, mblk * 128);
                    load_b1(s, (it >> 4) * 8 + nslot, k);
                    if (s == 3) ph ^= 1;
                }
                mbar_expect_tx(x_bar, 32768);
                tma_2d(aux, &prm.x, x_bar, nslot * 128, mblk * 128);
                tma_2d(aux + 16384, &prm.x, x_bar, nslot * 128 + 64, mblk * 128);
                TRACE(4);
                mbar_wait(dep_bar + 8, 0);
                TRACE(5);
                int q = 0; uint32_t ph2 = 1;
                for (int u = 0; u < G2_KSTEPS; u++) {
                    if (u == G2_LATE || u == G2_DSTEPS) {
                        TRACE(u == G2_LATE ? 6 : 32);
                        mbar_wait(dep_bar + (u == G2_LATE ? 16 : 24), 0);
                        TRACE(u == G2_LATE ? 7 : 33);
                    }
                    if (u < G2_STAGES) {
                        if (u == 0) mbar_wait(empty1(0), ph);
                        if (u == 1) mbar_wait(empty1(1), ph);
                        if (u == 3) mbar_wait(empty1(2), ph);
                        if (u == 4) mbar_wait(empty1(3), ph);
                    } else {
                        mbar_wait(empty2(q), ph2);
                    }
                    const uint32_t sa = stage2(q);
                    const bool down = u < G2_DSTEPS;
                    const int k = down ? u : u - G2_DSTEPS;
                    mbar_expect_tx(full2(q), G2_STAGE_BYTES);
                    tma_2d(sa, &prm.a2, full2(q), (down ? DM : 0) + k * 64, mblk * 128);
                    tma_5d_mc(sa + A_BYTES + rank * 8192, down ? &prm.wd : &prm.wo, full2(q), nslot * 128 + rank * 64, k * 2);
                    if (++q == G2_STAGES) { q = 0; ph2 ^= 1; }
                }
                TRACE(8);
            }
        } else if (warp == 9) {
            if (lane == 0) {
                mbar_wait(sig_bar, 0);
                TRACE(11);
                flag_add(flags + F_LN * 512);
                for (int t = 0; t < G1_TILES; t++) {
                    mbar_wait(sig_bar, (t + 1) & 1);
                    const int nt = t * 8 + nslot;
                    flag_add(tile_is_qkv(nt) ? g_flags + F_QKV * 512 + (nt & 3) * 32
                                             : flags + (t < G1_TILES - 1 ? F_EARLY : F_LATE) * 512);
                }
            }
        } else {
            const int w = warp - 10;
            const int ld = nslot < 4 ? NQKV : DF;
            const __nv_bfloat16* wp = nslot < 4 ? prm.pwqkv + 2 * DM + nslot * 256 + lane * 8
                                                : (lane < 16 ? prm.pwg : prm.pwu) + (nslot - 4) * 128 + (lane & 15) * 8;
            wp += (size_t)(mblk * 64 + w * 32) * ld;
            const unsigned epoch = __ldcg(g_epoch + blockIdx.x * 8 + w) + 1;
            float cs[8];
#pragma unroll
            for (int d = 0; d < 8; d++) cs[d] = 0.f;
            mbar_wait(full1(0), 0);
#pragma unroll 1
            for (int i = 0; i < 4; i++) {
                uint4 v[8];
#pragma unroll
                for (int j = 0; j < 8; j++) v[j] = __ldg(reinterpret_cast<const uint4*>(wp + (size_t)(i * 8 + j) * ld));
#pragma unroll
                for (int j = 0; j < 8; j++) {
                    float f[8];
                    unpack8(v[j], f);
#pragma unroll
                    for (int d = 0; d < 8; d++) cs[d] += f[d];
                }
            }
            float4* cp = reinterpret_cast<float4*>(g_colsum + (mblk * 2 + w) * 2048 + nslot * 256 + lane * 8);
            cp[0] = make_float4(cs[0], cs[1], cs[2], cs[3]);
            cp[1] = make_float4(cs[4], cs[5], cs[6], cs[7]);
            __syncwarp();
            if (lane == 0) {
                if (w == 0) TRACE(34);
                flag_add(g_flags + F_CS * 512 + nslot * 32);
                flag_wait(g_flags + F_CS * 512 + nslot * 32, epoch * CNT_CS);
            }
            __syncwarp();
            const float4* gp = reinterpret_cast<const float4*>(g_colsum + nslot * 256 + w * 128) + lane;
            float4 c = make_float4(0.f, 0.f, 0.f, 0.f);
#pragma unroll 8
            for (int m = 0; m < 32; m++) {
                const float4 a = __ldcg(gp + m * 512);
                c.x += a.x; c.y += a.y; c.z += a.z; c.w += a.w;
            }
            const uint32_t ca = aux + (w * 8 + (lane >> 2)) * 64 + (lane & 1) * 32 + (lane & 2) * 4;
            sts64f(ca, c.x, c.y);
            sts64f(ca + 16, c.z, c.w);
            if (lane == 0) {
                flag_wait(flags + F_LN * 512, epoch * CNT_LN);
                if (w == 0) { fence_proxy_async(); mbar_arrive(dep_bar); }
            }
            __syncwarp();
            sts128(aux + 1024 + w * 512 + lane * 16, __ldcg(reinterpret_cast<const uint4*>(g_stats + mblk * 128 + w * 64) + lane));
            __syncwarp();
            if (lane == 0) {
                mbar_arrive(fold_bar);
                g_epoch[blockIdx.x * 8 + w] = epoch;
                if (w == 0) {
                    TRACE(35);
                    flag_wait(flags + F_EARLY * 512, epoch * CNT_EARLY);
                    fence_proxy_async(); mbar_arrive(dep_bar + 8);
                    flag_wait(flags + F_LATE * 512, epoch * CNT_LATE);
                    fence_proxy_async(); mbar_arrive(dep_bar + 16);
                    flag_wait(g_flags + F_O * 512, epoch * CNT_O);
                    fence_proxy_async(); mbar_arrive(dep_bar + 24);
                }
            }
        }
    } else {
        asm volatile("barrier.cluster.arrive.relaxed.aligned;" ::: "memory");
        asm volatile("setmaxnreg.inc.sync.aligned.u32 %0;" :: "n"(CONSUMER_REGS));
        const int wg = __shfl_sync(0xffffffffu, threadIdx.x >> 7, 0);
        const int cw = threadIdx.x >> 5;
        const int tid = threadIdx.x & 127;
        float acc[128];
        uint32_t pk[64];
#pragma unroll
        for (int i = 0; i < 64; i++) asm volatile("mov.b32 %0, 0;" : "=r"(pk[i]));
#pragma unroll
        for (int i = 0; i < 128; i++) asm volatile("mov.b32 %0, 0;" : "=f"(acc[i]));
        asm volatile("barrier.cluster.wait.acquire.aligned;" ::: "memory");

        const int orow = mblk * 128 + cw * 16 + (lane >> 2);
        __nv_bfloat16* optr = nullptr;
        auto release = [&](uint32_t bar) { if (tid < 2) mbar_arrive_cluster(bar, tid); };
        auto chunk_geglu = [&](int j) {
            const int c = j >> 1, h = j & 1;
            uint4 v;
            v.x = geglu2(pk[8 * c + h], pk[32 + 8 * c + h]);
            v.y = geglu2(pk[8 * c + 2 + h], pk[32 + 8 * c + 2 + h]);
            v.z = geglu2(pk[8 * c + 4 + h], pk[32 + 8 * c + 4 + h]);
            v.w = geglu2(pk[8 * c + 6 + h], pk[32 + 8 * c + 6 + h]);
            *reinterpret_cast<uint4*>(optr + h * 8 * K2 + c * 32) = v;
        };
        auto chunk_qkv = [&](int c) {
            *reinterpret_cast<uint4*>(optr + c * 32) = make_uint4(pk[8 * c], pk[8 * c + 2], pk[8 * c + 4], pk[8 * c + 6]);
            *reinterpret_cast<uint4*>(optr + 8 * NQKV + c * 32) = make_uint4(pk[8 * c + 1], pk[8 * c + 3], pk[8 * c + 5], pk[8 * c + 7]);
        };
        auto signal_stores = [&]() { __syncwarp(); if (lane == 0) mbar_arrive(sig_bar); };

        auto chunk_ln = [&](int k) {
            const int row = mblk * 128 + nslot * 16 + cw * 2;
            if (k == 0) {
                const uint4* xp = reinterpret_cast<const uint4*>(prm.px + (size_t)row * DM) + lane;
#pragma unroll
                for (int i = 0; i < 8; i++) {
                    const uint4 v = __ldg(xp + i * 32);
                    pk[4 * i] = v.x; pk[4 * i + 1] = v.y; pk[4 * i + 2] = v.z; pk[4 * i + 3] = v.w;
                }
            } else if (k == 3) {
                float a = row_sum(pk), b = row_sum(pk + 16);
                warp_sum2(a, b);
                pk[32] = __float_as_uint(a * (1.f / DM)); pk[33] = __float_as_uint(b * (1.f / DM));
            } else if (k == 4) {
                pk[34] = __float_as_uint(row_sq(pk, __uint_as_float(pk[32])));
            } else if (k == 5) {
                float a = __uint_as_float(pk[34]), b = row_sq(pk + 16, __uint_as_float(pk[33]));
                warp_sum2(a, b);
                pk[34] = __float_as_uint(a); pk[35] = __float_as_uint(b);
            } else if (k == 6) {
                row_store(pk, __uint_as_float(pk[32]), row_inv(__uint_as_float(pk[34])), row, lane);
            } else if (k == 7) {
                row_store(pk + 16, __uint_as_float(pk[33]), row_inv(__uint_as_float(pk[35])), row + 1, lane);
                signal_stores();
            }
        };

        int pending = 0;
#pragma unroll 1
        for (int t = 0; t < G1_TILES; t++) {
#pragma unroll
            for (int k = 0; k < G1_KSTEPS; k++) {
                const int s = k & 3;
                mbar_wait(full1(s), (k >> 2) & 1);
                if (t == 0 && k == 0 && threadIdx.x == 0) TRACE(12);
                if (wg == 1 && k == G1_KSTEPS - G1_SKEW) asm volatile("bar.sync 1, 256;" ::: "memory");
                const uint64_t da = desc_a(base + s * G1_STAGE_BYTES + wg * 8192);
                const uint64_t db = desc_b(base + s * G1_STAGE_BYTES + A_BYTES);
                wg_fence();
#pragma unroll
                for (int kk = 0; kk < 4; kk++) wgmma_n256(acc, da + kk * 2, db + kk * 128, (k | kk) != 0);
                wg_commit();
                if (wg == 0 && k == G1_KSTEPS - 1) asm volatile("bar.arrive 1, 256;" ::: "memory");
                if (k <= 7 && pending == 0) chunk_ln(k);
                if (k >= 1 && k <= 8) {
                    if (pending == 2) chunk_geglu(k - 1);
                    else if (pending == 1) chunk_qkv(k - 1);
                    if (k == 8 && pending) signal_stores();
                }
                wg_wait<1>();
                if (k > 0) release(empty1((k - 1) & 3));
            }
            if (t == 0) mbar_wait(fold_bar, 0);
            wg_wait<0>();
            fence_regs(acc);
            release(empty1(3));
            if (t == 0) {
                const uint32_t sp = aux + 1024 + (cw * 16 + (lane >> 2)) * 8;
                const float2 sa = lds64f(sp), sb = lds64f(sp + 64);
#pragma unroll
                for (int j = 0; j < 16; j++) {
                    const uint4 c = lds128(aux + j * 64 + (lane & 3) * 16);
                    const float c0 = __uint_as_float(c.x), c1 = __uint_as_float(c.y);
                    const float c2 = __uint_as_float(c.z), c3 = __uint_as_float(c.w);
                    const float* a = acc + 8 * j;
                    pk[4 * j] = pack_bf16(fmaf(sa.x, c0, a[0]) * sa.y, fmaf(sa.x, c1, a[1]) * sa.y);
                    pk[4 * j + 1] = pack_bf16(fmaf(sb.x, c0, a[2]) * sb.y, fmaf(sb.x, c1, a[3]) * sb.y);
                    pk[4 * j + 2] = pack_bf16(fmaf(sa.x, c2, a[4]) * sa.y, fmaf(sa.x, c3, a[5]) * sa.y);
                    pk[4 * j + 3] = pack_bf16(fmaf(sb.x, c2, a[6]) * sb.y, fmaf(sb.x, c3, a[7]) * sb.y);
                }
            } else {
#pragma unroll
                for (int i = 0; i < 64; i++) pk[i] = pack_bf16(acc[2 * i], acc[2 * i + 1]);
            }
            const int nt = t * 8 + nslot;
            pending = tile_is_qkv(nt) ? 1 : 2;
            optr = pending == 1 ? g_qkv + (size_t)orow * NQKV + tile_index(nt) * 256 + (lane & 3) * 8
                                : g_a2 + (size_t)orow * K2 + DM + tile_index(nt) * 128 + (lane & 3) * 8;
            if (tid == 0) TRACE(16 + wg * 8 + t);
        }

        float accd[64], accs[64];
#pragma unroll
        for (int i = 0; i < 64; i++) accd[i] = 0.f;
#pragma unroll
        for (int u = 0; u < 9; u++) {
            const int q = u % G2_STAGES;
            mbar_wait(full2(q), (u / G2_STAGES) & 1);
            const uint64_t da = desc_a(stage2(q) + wg * 8192), db = desc_b(stage2(q) + A_BYTES);
            wg_fence();
#pragma unroll
            for (int kk = 0; kk < 4; kk++) wgmma_n128(accd, da + kk * 2, db + kk * 128, (u | kk) != 0);
            wg_commit();
            if (u >= 1) { chunk_geglu(u - 1); if (u == 8) signal_stores(); }
            wg_wait<1>();
            if (u > 0) release(empty2((u - 1) % G2_STAGES));
        }
        {
            int q = 9 % G2_STAGES, qp = 8 % G2_STAGES; uint32_t ph = (9 / G2_STAGES) & 1;
#pragma unroll 1
            for (int u = 9; u < G2_DSTEPS; u++) {
                mbar_wait(full2(q), ph);
                const uint64_t da = desc_a(stage2(q) + wg * 8192), db = desc_b(stage2(q) + A_BYTES);
                wg_fence();
#pragma unroll
                for (int kk = 0; kk < 4; kk++) wgmma_n128(accd, da + kk * 2, db + kk * 128, 1);
                wg_commit();
                wg_wait<1>();
                release(empty2(qp));
                qp = q;
                if (++q == G2_STAGES) { q = 0; ph ^= 1; }
            }
        }
        if (tid == 0) TRACE(16 + wg * 8 + 5);
#pragma unroll
        for (int i = 0; i < 64; i++) accs[i] = 0.f;
        uint32_t gk[32], xr[32];
        const uint32_t xs = aux + cw * 2048;
        const uint32_t xrow = xs + ((lane & 7) + ((lane >> 3) & 1) * 8) * 128;
        auto xaddr = [&](int j) { return xrow + (j >> 2) * 16384 + (((((j & 3) * 2) + (lane >> 4)) ^ (lane & 7)) << 4); };
#pragma unroll
        for (int u = G2_DSTEPS; u < G2_KSTEPS; u++) {
            const int q = u % G2_STAGES, v = u - G2_DSTEPS;
            mbar_wait(full2(q), (u / G2_STAGES) & 1);
            if (G2_SKEW > 0 && wg == 1 && u == G2_KSTEPS - G2_SKEW) asm volatile("bar.sync 1, 256;" ::: "memory");
            const uint64_t da = desc_a(stage2(q) + wg * 8192), db = desc_b(stage2(q) + A_BYTES);
            wg_fence();
#pragma unroll
            for (int kk = 0; kk < 4; kk++) wgmma_n128(accs, da + kk * 2, db + kk * 128, (v | kk) != 0);
            wg_commit();
            if (G2_SKEW > 0 && wg == 0 && u == G2_KSTEPS - 1) asm volatile("bar.arrive 1, 256;" ::: "memory");
            if (v >= 1 && v <= 8) {
#pragma unroll
                for (int i = 4 * (v - 1); i < 4 * v; i++) {
                    const uint32_t d2 = pack_bf16(accd[2 * i], accd[2 * i + 1]);
                    gk[i] = pack_bf16(silu(bf_lo(d2)), silu(bf_hi(d2)));
                }
            }
            if (v == 9) mbar_wait(x_bar, 0);
            if (v >= 9 && v <= 12) {
#pragma unroll
                for (int j = 2 * (v - 9); j < 2 * (v - 8); j++)
                    asm volatile("ldmatrix.sync.aligned.m8n8.x4.shared.b16 {%0,%1,%2,%3}, [%4];"
                                 : "=r"(xr[4 * j]), "=r"(xr[4 * j + 1]), "=r"(xr[4 * j + 2]), "=r"(xr[4 * j + 3])
                                 : "r"(xaddr(j)) : "memory");
            }
            wg_wait<1>();
            if (v == 0) fence_regs(accd);
            if (u - 1 + G2_STAGES < G2_KSTEPS) release(empty2((u - 1) % G2_STAGES));
        }
        wg_wait<0>();
        fence_regs(accs);
        if (tid == 0) TRACE(16 + wg * 8 + 6);
#pragma unroll
        for (int j = 0; j < 8; j++) {
            uint32_t r[4];
#pragma unroll
            for (int i = 0; i < 4; i++) {
                const int e = j * 4 + i;
                r[i] = add_bf16x2(xr[e], mul_bf16x2(pack_bf16(accs[2 * e], accs[2 * e + 1]), gk[e]));
            }
            asm volatile("stmatrix.sync.aligned.m8n8.x4.shared.b16 [%0], {%1,%2,%3,%4};"
                         :: "r"(xaddr(j)), "r"(r[0]), "r"(r[1]), "r"(r[2]), "r"(r[3]) : "memory");
            if (j == 3 || j == 7) {
                asm volatile("fence.proxy.async.shared::cta;" ::: "memory");
                __syncwarp();
                if (lane == 0) {
                    tma_store_2d(&prm.out, xs + (j >> 2) * 16384, nslot * 128 + (j >> 2) * 64, mblk * 128 + cw * 16);
                    asm volatile("cp.async.bulk.commit_group;" ::: "memory");
                }
            }
        }
        if (lane == 0) asm volatile("cp.async.bulk.wait_group.read 0;" ::: "memory");
        if (tid == 0) { TRACE(16 + wg * 8 + 7); if (wg == 1) TRACE_GT(13); }
    }
}

typedef CUresult (*EncodeFn)(CUtensorMap*, CUtensorMapDataType, cuuint32_t, void*, const cuuint64_t*, const cuuint64_t*,
                             const cuuint32_t*, const cuuint32_t*, CUtensorMapInterleave, CUtensorMapSwizzle,
                             CUtensorMapL2promotion, CUtensorMapFloatOOBfill);

void encode(EncodeFn fn, CUtensorMap* m, const void* ptr, int rank, const cuuint64_t* dims, const cuuint64_t* strides,
            const cuuint32_t* box) {
    const cuuint32_t es[5] = {1, 1, 1, 1, 1};
    fn(m, CU_TENSOR_MAP_DATA_TYPE_BFLOAT16, rank, const_cast<void*>(ptr), dims, strides, box, es,
       CU_TENSOR_MAP_INTERLEAVE_NONE, CU_TENSOR_MAP_SWIZZLE_128B, CU_TENSOR_MAP_L2_PROMOTION_L2_128B,
       CU_TENSOR_MAP_FLOAT_OOB_FILL_NONE);
}
void encode_2d(EncodeFn fn, CUtensorMap* m, const void* ptr, int cols, int box_rows) {
    const cuuint64_t dims[2] = {(cuuint64_t)cols, SEQ}, strides[1] = {(cuuint64_t)cols * 2};
    const cuuint32_t box[2] = {64, (cuuint32_t)box_rows};
    encode(fn, m, ptr, 2, dims, strides, box);
}
void encode_w1(EncodeFn fn, CUtensorMap* m, const void* ptr, int cols) {
    const cuuint64_t dims[3] = {64, DM, (cuuint64_t)cols / 64}, strides[2] = {(cuuint64_t)cols * 2, 128};
    const cuuint32_t box[3] = {64, 64, 2};
    encode(fn, m, ptr, 3, dims, strides, box);
}
void encode_qkv(EncodeFn fn, CUtensorMap* m, const void* ptr) {
    const cuuint64_t dims[5] = {64, SEQ / 2, 3, 2, DM / 64}, strides[4] = {NQKV * 4, DM * 2, NQKV * 2, 128};
    const cuuint32_t box[5] = {64, 32, 3, 2, 2};
    encode(fn, m, ptr, 5, dims, strides, box);
}
void encode_o(EncodeFn fn, CUtensorMap* m, const void* ptr) {
    const cuuint64_t dims[4] = {64, SEQ / 2, 2, DM / 64}, strides[3] = {K2 * 4, K2 * 2, 128};
    const cuuint32_t box[4] = {64, 32, 2, 2};
    encode(fn, m, ptr, 4, dims, strides, box);
}
void encode_w2(EncodeFn fn, CUtensorMap* m, const void* ptr, int rows) {
    const cuuint64_t rb = DM * 2;
    const cuuint64_t dims[5] = {DM, 2, 4, 4, (cuuint64_t)rows / 32}, strides[4] = {rb, 8 * rb, 2 * rb, 32 * rb};
    const cuuint32_t box[5] = {64, 2, 4, 4, 2};
    encode(fn, m, ptr, 5, dims, strides, box);
}

}

extern "C" void kernel_launch(void* const* d_in, const int* in_sizes, int n_in, void* d_out, int out_size) {
    (void)in_sizes; (void)n_in; (void)out_size;
    static EncodeFn fn = nullptr;
    static void *p_xn = nullptr, *p_qkv = nullptr, *p_a2 = nullptr;
    if (!fn) {
        cudaDriverEntryPointQueryResult st;
        cudaGetDriverEntryPoint("cuTensorMapEncodeTiled", (void**)&fn, cudaEnableDefault, &st);
        cudaGetSymbolAddress(&p_xn, g_xn);
        cudaGetSymbolAddress(&p_qkv, g_qkv);
        cudaGetSymbolAddress(&p_a2, g_a2);
        cudaFuncSetAttribute(fused_kernel, cudaFuncAttributeMaxDynamicSharedMemorySize, SMEM_BYTES);
    }
    Params prm;
    encode_2d(fn, &prm.x, d_in[0], DM, 128);
    encode_2d(fn, &prm.xn, p_xn, DM, 128);
    encode_w1(fn, &prm.wqkv, d_in[1], NQKV);
    encode_w1(fn, &prm.wg, d_in[4], DF);
    encode_w1(fn, &prm.wu, d_in[5], DF);
    encode_qkv(fn, &prm.qkv, p_qkv);
    encode_o(fn, &prm.o, p_a2);
    encode_2d(fn, &prm.a2, p_a2, K2, 128);
    encode_w2(fn, &prm.wo, d_in[2], DM);
    encode_w2(fn, &prm.wd, d_in[6], DF);
    encode_2d(fn, &prm.out, d_out, DM, 16);
    prm.px = (const __nv_bfloat16*)d_in[0];
    prm.pwqkv = (const __nv_bfloat16*)d_in[1];
    prm.pwg = (const __nv_bfloat16*)d_in[4];
    prm.pwu = (const __nv_bfloat16*)d_in[5];
    fused_kernel<<<NCTA, 384, SMEM_BYTES>>>(prm);
}
```

```cpp
#include <cuda_runtime.h>
#include <cuda_bf16.h>
#include <cuda.h>
#include <stdint.h>

namespace {

constexpr int SEQ = 2048, DM = 1024, DF = 3584, K2 = DM + DF, NQKV = 3 * DM;
constexpr int NGEMM = 128, NCTA = 132;
constexpr int G1_STAGES = 4, G1_STAGE_BYTES = 49152, G1_KSTEPS = 16, G1_TILES = 5;
constexpr int G2_STAGES = 6, G2_STAGE_BYTES = 32768, G2_KSTEPS = 72, G2_DSTEPS = 56, G2_LATE = 40;
constexpr int A_BYTES = 16384;
constexpr int AUX_OFF = G1_STAGES * G1_STAGE_BYTES;
constexpr int BAR_OFF = AUX_OFF + 32768;
constexpr int SMEM_BYTES = BAR_OFF + 1024 + 256;
constexpr int G1_SKEW = 2, G2_SKEW = 2;
constexpr int CONSUMER_REGS = 224, AUX_REGS = 56;
constexpr int ATT_STEPS = 32;

enum { F_LN = 0, F_QKV = 1, F_EARLY = 2, F_LATE = 3, F_O = 4, F_CS = 5 };
constexpr unsigned CNT_LN = 8, CNT_QKV = 48, CNT_EARLY = 20, CNT_LATE = 8, CNT_O = 8, CNT_CS = 32;

__device__ __align__(1024) __nv_bfloat16 g_xn[SEQ * DM];
__device__ __align__(1024) __nv_bfloat16 g_qkv[SEQ * NQKV];
__device__ __align__(1024) __nv_bfloat16 g_a2[SEQ * K2];
__device__ __align__(128) float2 g_stats[SEQ];
__device__ __align__(128) float g_colsum[32 * 2048];
__device__ __align__(128) unsigned g_flags[6 * 16 * 32];
__device__ __align__(128) unsigned g_epoch[NCTA * 8];

#define TRACE(slot) do {} while (0)
#define TRACE_GT(slot) do {} while (0)

__device__ __forceinline__ uint32_t smem_u32(const void* p) { return (uint32_t)__cvta_generic_to_shared(p); }
__device__ __forceinline__ void mbar_init(uint32_t bar, uint32_t cnt) {
    asm volatile("mbarrier.init.shared::cta.b64 [%0], %1;" :: "r"(bar), "r"(cnt) : "memory");
}
__device__ __forceinline__ void mbar_expect_tx(uint32_t bar, uint32_t bytes) {
    asm volatile("mbarrier.arrive.expect_tx.shared::cta.b64 _, [%0], %1;" :: "r"(bar), "r"(bytes) : "memory");
}
__device__ __forceinline__ void mbar_arrive(uint32_t bar) {
    asm volatile("mbarrier.arrive.shared::cta.b64 _, [%0];" :: "r"(bar) : "memory");
}
__device__ __forceinline__ void mbar_arrive_cluster(uint32_t bar, uint32_t cta) {
    asm volatile("{\n.reg .b32 ra;\nmapa.shared::cluster.u32 ra, %0, %1;\nmbarrier.arrive.shared::cluster.b64 _, [ra];\n}"
                 :: "r"(bar), "r"(cta) : "memory");
}
__device__ __forceinline__ bool mbar_try_wait(uint32_t bar, uint32_t parity) {
    uint32_t ok;
    asm volatile("{\n.reg .pred p;\nmbarrier.try_wait.parity.shared::cta.b64 p, [%1], %2;\nselp.u32 %0, 1, 0, p;\n}"
                 : "=r"(ok) : "r"(bar), "r"(parity) : "memory");
    return ok;
}
__device__ __forceinline__ void mbar_wait(uint32_t bar, uint32_t parity) {
    int spins = 0;
    while (!mbar_try_wait(bar, parity)) { if (++spins > (1 << 17)) break; }
}
__device__ __forceinline__ void flag_wait(const unsigned* p, unsigned target) {
    for (int spins = 0; spins < (1 << 19); spins++) {
        unsigned v;
        asm volatile("ld.acquire.gpu.global.u32 %0, [%1];" : "=r"(v) : "l"(p) : "memory");
        if ((int)(v - target) >= 0) break;
        __nanosleep(64);
    }
}
__device__ __forceinline__ void flag_add(unsigned* p) {
    asm volatile("red.release.gpu.global.add.u32 [%0], 1;" :: "l"(p) : "memory");
}
__device__ __forceinline__ void fence_proxy_async() { asm volatile("fence.proxy.async;" ::: "memory"); }
__device__ __forceinline__ uint4 lds128(uint32_t addr) {
    uint4 v;
    asm volatile("ld.shared.v4.u32 {%0,%1,%2,%3}, [%4];" : "=r"(v.x), "=r"(v.y), "=r"(v.z), "=r"(v.w) : "r"(addr) : "memory");
    return v;
}
__device__ __forceinline__ float2 lds64f(uint32_t addr) {
    float2 v;
    asm volatile("ld.shared.v2.f32 {%0,%1}, [%2];" : "=f"(v.x), "=f"(v.y) : "r"(addr) : "memory");
    return v;
}
__device__ __forceinline__ void sts128(uint32_t addr, uint4 v) {
    asm volatile("st.shared.v4.u32 [%0], {%1,%2,%3,%4};" :: "r"(addr), "r"(v.x), "r"(v.y), "r"(v.z), "r"(v.w) : "memory");
}
__device__ __forceinline__ void sts64f(uint32_t addr, float a, float b) {
    asm volatile("st.shared.v2.f32 [%0], {%1,%2};" :: "r"(addr), "f"(a), "f"(b) : "memory");
}

__device__ __forceinline__ void tma_2d(uint32_t dst, const CUtensorMap* m, uint32_t bar, int c0, int c1) {
    asm volatile("cp.async.bulk.tensor.2d.shared::cluster.global.mbarrier::complete_tx::bytes [%0], [%1, {%3, %4}], [%2];"
                 :: "r"(dst), "l"(m), "r"(bar), "r"(c0), "r"(c1) : "memory");
}
__device__ __forceinline__ void tma_5d(uint32_t dst, const CUtensorMap* m, uint32_t bar, int c1, int c4) {
    asm volatile("cp.async.bulk.tensor.5d.shared::cluster.global.mbarrier::complete_tx::bytes [%0], [%1, {%3, %4, %3, %3, %5}], [%2];"
                 :: "r"(dst), "l"(m), "r"(bar), "r"(0), "r"(c1), "r"(c4) : "memory");
}
__device__ __forceinline__ void tma_store_4d(const CUtensorMap* m, uint32_t src, int c1, int c3) {
    asm volatile("cp.async.bulk.tensor.4d.global.shared::cta.bulk_group [%0, {%2, %3, %2, %4}], [%1];"
                 :: "l"(m), "r"(src), "r"(0), "r"(c1), "r"(c3) : "memory");
}
__device__ __forceinline__ void tma_3d_mc(uint32_t dst, const CUtensorMap* m, uint32_t bar, int c1, int c2) {
    asm volatile("cp.async.bulk.tensor.3d.shared::cluster.global.mbarrier::complete_tx::bytes.multicast::cluster"
                 " [%0], [%1, {%3, %4, %5}], [%2], %6;"
                 :: "r"(dst), "l"(m), "r"(bar), "r"(0), "r"(c1), "r"(c2), "h"((uint16_t)3) : "memory");
}
__device__ __forceinline__ void tma_5d_mc(uint32_t dst, const CUtensorMap* m, uint32_t bar, int c0, int c4) {
    asm volatile("cp.async.bulk.tensor.5d.shared::cluster.global.mbarrier::complete_tx::bytes.multicast::cluster"
                 " [%0], [%1, {%3, %4, %4, %4, %5}], [%2], %6;"
                 :: "r"(dst), "l"(m), "r"(bar), "r"(c0), "r"(0), "r"(c4), "h"((uint16_t)3) : "memory");
}
__device__ __forceinline__ void tma_store_2d(const CUtensorMap* m, uint32_t src, int c0, int c1) {
    asm volatile("cp.async.bulk.tensor.2d.global.shared::cta.bulk_group [%0, {%2, %3}], [%1];"
                 :: "l"(m), "r"(src), "r"(c0), "r"(c1) : "memory");
}
__device__ __forceinline__ void prefetch_map(const CUtensorMap* m) {
    asm volatile("prefetch.tensormap [%0];" :: "l"(m) : "memory");
}
__device__ __forceinline__ void wg_fence() { asm volatile("wgmma.fence.sync.aligned;" ::: "memory"); }
__device__ __forceinline__ void wg_commit() { asm volatile("wgmma.commit_group.sync.aligned;" ::: "memory"); }
template <int N> __device__ __forceinline__ void wg_wait() { asm volatile("wgmma.wait_group.sync.aligned %0;" :: "n"(N) : "memory"); }

__device__ __forceinline__ uint64_t desc_a(uint32_t addr) {
    return (uint64_t)((addr & 0x3FFFF) >> 4) | (1ull << 16) | (64ull << 32) | (1ull << 62);
}
__device__ __forceinline__ uint64_t desc_b(uint32_t addr) {
    return (uint64_t)((addr & 0x3FFFF) >> 4) | (512ull << 16) | (64ull << 32) | (1ull << 62);
}

#define R8(d, o) "+f"(d[o]), "+f"(d[o+1]), "+f"(d[o+2]), "+f"(d[o+3]), "+f"(d[o+4]), "+f"(d[o+5]), "+f"(d[o+6]), "+f"(d[o+7])
#define R32(d, o) R8(d, o), R8(d, o+8), R8(d, o+16), R8(d, o+24)
#define R64(d, o) R32(d, o), R32(d, o+32)

__device__ __forceinline__ void wgmma_n256(float (&d)[128], uint64_t da, uint64_t db, int scale_d) {
    asm volatile("{\n.reg .pred p;\nsetp.ne.b32 p, %130, 0;\n"
        "wgmma.mma_async.sync.aligned.m64n256k16.f32.bf16.bf16 "
        "{%0,%1,%2,%3,%4,%5,%6,%7,%8,%9,%10,%11,%12,%13,%14,%15,%16,%17,%18,%19,%20,%21,%22,%23,%24,%25,%26,%27,%28,%29,%30,%31,"
        "%32,%33,%34,%35,%36,%37,%38,%39,%40,%41,%42,%43,%44,%45,%46,%47,%48,%49,%50,%51,%52,%53,%54,%55,%56,%57,%58,%59,%60,%61,%62,%63,"
        "%64,%65,%66,%67,%68,%69,%70,%71,%72,%73,%74,%75,%76,%77,%78,%79,%80,%81,%82,%83,%84,%85,%86,%87,%88,%89,%90,%91,%92,%93,%94,%95,"
        "%96,%97,%98,%99,%100,%101,%102,%103,%104,%105,%106,%107,%108,%109,%110,%111,%112,%113,%114,%115,%116,%117,%118,%119,%120,%121,%122,%123,%124,%125,%126,%127},"
        " %128, %129, p, 1, 1, 0, 1;\n}"
        : R64(d, 0), R64(d, 64) : "l"(da), "l"(db), "r"(scale_d));
}
__device__ __forceinline__ void wgmma_n128(float (&d)[64], uint64_t da, uint64_t db, int scale_d) {
    asm volatile("{\n.reg .pred p;\nsetp.ne.b32 p, %66, 0;\n"
        "wgmma.mma_async.sync.aligned.m64n128k16.f32.bf16.bf16 "
        "{%0,%1,%2,%3,%4,%5,%6,%7,%8,%9,%10,%11,%12,%13,%14,%15,%16,%17,%18,%19,%20,%21,%22,%23,%24,%25,%26,%27,%28,%29,%30,%31,"
        "%32,%33,%34,%35,%36,%37,%38,%39,%40,%41,%42,%43,%44,%45,%46,%47,%48,%49,%50,%51,%52,%53,%54,%55,%56,%57,%58,%59,%60,%61,%62,%63},"
        " %64, %65, p, 1, 1, 0, 1;\n}"
        : R64(d, 0) : "l"(da), "l"(db), "r"(scale_d));
}

__device__ __forceinline__ uint32_t pack_bf16(float lo, float hi) {
    uint32_t r; asm("cvt.rn.bf16x2.f32 %0, %1, %2;" : "=r"(r) : "f"(hi), "f"(lo)); return r;
}
__device__ __forceinline__ float bf_lo(uint32_t v) { return __uint_as_float(v << 16); }
__device__ __forceinline__ float bf_hi(uint32_t v) { return __uint_as_float(v & 0xffff0000u); }
__device__ __forceinline__ float round_bf16(float v) { return bf_lo(pack_bf16(v, 0.f)); }
__device__ __forceinline__ uint32_t mul_bf16x2(uint32_t a, uint32_t b) {
    uint32_t r; asm("mul.rn.bf16x2 %0, %1, %2;" : "=r"(r) : "r"(a), "r"(b)); return r;
}
__device__ __forceinline__ uint32_t add_bf16x2(uint32_t a, uint32_t b) {
    uint32_t r; asm("add.rn.bf16x2 %0, %1, %2;" : "=r"(r) : "r"(a), "r"(b)); return r;
}
__device__ __forceinline__ uint32_t sub_bf16x2(uint32_t a, uint32_t b) {
    uint32_t r; asm("sub.rn.bf16x2 %0, %1, %2;" : "=r"(r) : "r"(a), "r"(b)); return r;
}
__device__ __forceinline__ float tanh_fast(float x) { float r; asm("tanh.approx.f32 %0, %1;" : "=f"(r) : "f"(x)); return r; }
__device__ __forceinline__ float gelu_tanh(float g) {
    float t = fmaf(g * g, 0.044715f * 0.7978845608f, 0.7978845608f) * g;
    float hg = 0.5f * g;
    return fmaf(hg, tanh_fast(t), hg);
}
__device__ __forceinline__ uint32_t geglu2(uint32_t g2, uint32_t u2) {
    return mul_bf16x2(pack_bf16(gelu_tanh(bf_lo(g2)), gelu_tanh(bf_hi(g2))), u2);
}
__device__ __forceinline__ float silu(float d) {
    float hd = 0.5f * d;
    return fmaf(hd, tanh_fast(hd), hd);
}
__device__ __forceinline__ float ex2_fast(float x) { float r; asm("ex2.approx.ftz.f32 %0, %1;" : "=f"(r) : "f"(x)); return r; }
__device__ __forceinline__ void unpack8(uint4 v, float (&f)[8]) {
    f[0] = bf_lo(v.x); f[1] = bf_hi(v.x); f[2] = bf_lo(v.y); f[3] = bf_hi(v.y);
    f[4] = bf_lo(v.z); f[5] = bf_hi(v.z); f[6] = bf_lo(v.w); f[7] = bf_hi(v.w);
}
template <int N> __device__ __forceinline__ void fence_regs(float (&d)[N]) {
#pragma unroll
    for (int i = 0; i < N; i++) asm volatile("" : "+f"(d[i]) :: "memory");
}

__device__ __forceinline__ float rcp_fast(float x) { float r; asm("rcp.approx.ftz.f32 %0, %1;" : "=f"(r) : "f"(x)); return r; }
__device__ __forceinline__ uint32_t max_bf16x2(uint32_t a, uint32_t b) {
    uint32_t r; asm("max.bf16x2 %0, %1, %2;" : "=r"(r) : "r"(a), "r"(b)); return r;
}
__device__ __forceinline__ uint4 ldsm4(uint32_t addr) {
    uint4 v;
    asm volatile("ldmatrix.sync.aligned.m8n8.x4.shared.b16 {%0,%1,%2,%3}, [%4];"
                 : "=r"(v.x), "=r"(v.y), "=r"(v.z), "=r"(v.w) : "r"(addr) : "memory");
    return v;
}
__device__ __forceinline__ uint4 ldsm4_t(uint32_t addr) {
    uint4 v;
    asm volatile("ldmatrix.sync.aligned.m8n8.x4.trans.shared.b16 {%0,%1,%2,%3}, [%4];"
                 : "=r"(v.x), "=r"(v.y), "=r"(v.z), "=r"(v.w) : "r"(addr) : "memory");
    return v;
}
__device__ __forceinline__ void mma_16816(float (&c)[4], uint32_t a0, uint32_t a1, uint32_t a2, uint32_t a3, uint32_t b0, uint32_t b1) {
    asm("mma.sync.aligned.m16n8k16.row.col.f32.bf16.bf16.f32 {%0,%1,%2,%3}, {%4,%5,%6,%7}, {%8,%9}, {%0,%1,%2,%3};"
        : "+f"(c[0]), "+f"(c[1]), "+f"(c[2]), "+f"(c[3]) : "r"(a0), "r"(a1), "r"(a2), "r"(a3), "r"(b0), "r"(b1));
}
__device__ __forceinline__ void mma_1688(float (&c)[4], uint32_t a0, uint32_t a1, uint32_t b0) {
    asm("mma.sync.aligned.m16n8k8.row.col.f32.bf16.bf16.f32 {%0,%1,%2,%3}, {%4,%5}, {%6}, {%0,%1,%2,%3};"
        : "+f"(c[0]), "+f"(c[1]), "+f"(c[2]), "+f"(c[3]) : "r"(a0), "r"(a1), "r"(b0));
}
__device__ __forceinline__ void qk_tile(float (&c)[4], const uint4& q0, const uint4& q1, const uint4& k) {
    c[0] = c[1] = c[2] = c[3] = 0.f;
    mma_16816(c, q0.x, q0.y, q0.z, q0.w, k.x, k.y);
    mma_16816(c, q1.x, q1.y, q1.z, q1.w, k.z, k.w);
}
__device__ __forceinline__ uint32_t scaled_logits(float lo, float hi) {
    const uint32_t p = pack_bf16(lo, hi);
    uint32_t r;
    asm("fma.rn.bf16x2 %0, %1, %2, %3;" : "=r"(r) : "r"(p), "r"(0x3e353e35u), "r"(mul_bf16x2(p, 0x379e379eu)));
    return r;
}

__device__ __forceinline__ float2 quad_sum2(float a, float b) {
    const float ah = __uint_as_float(__float_as_uint(a) & 0xffffe000u), bh = __uint_as_float(__float_as_uint(b) & 0xffffe000u);
    float c0, c1, c2, c3;
    asm("mma.sync.aligned.m16n8k8.row.col.f32.tf32.tf32.f32 {%0,%1,%2,%3}, {%4,%5,%6,%7}, {%8,%8}, {%9,%9,%9,%9};"
        : "=f"(c0), "=f"(c1), "=f"(c2), "=f"(c3)
        : "r"(__float_as_uint(ah)), "r"(__float_as_uint(bh)), "r"(__float_as_uint(a - ah)), "r"(__float_as_uint(b - bh)),
          "r"(0x3f800000u), "f"(0.f));
    return make_float2(c0, c2);
}
__device__ __forceinline__ uint4 pv_tile(const uint4& vp, const uint4& vo, uint32_t p, uint32_t keep) {
    float a[4] = {0.f, 0.f, 0.f, 0.f}, b[4] = {0.f, 0.f, 0.f, 0.f};
    mma_1688(a, vp.x, vp.y, p & keep); mma_1688(b, vp.z, vp.w, p & keep);
    mma_1688(a, vo.x, vo.y, p & ~keep); mma_1688(b, vo.z, vo.w, p & ~keep);
    return make_uint4(pack_bf16(a[0], a[1]), pack_bf16(a[2], a[3]), pack_bf16(b[0], b[1]), pack_bf16(b[2], b[3]));
}

__device__ __forceinline__ void attention(uint32_t in, uint32_t out, uint32_t full, uint32_t empty, uint32_t o_ready,
                                          uint32_t o_free, int lane) {
    constexpr float LOG2E = 1.4426950408889634f;
    const int g = lane >> 2, t = lane & 3;
    const bool up0 = 2 * t > g, up1 = 2 * t + 1 > g;
    const uint32_t keep = (up0 ? 0x0000ffffu : 0u) | (up1 ? 0xffff0000u : 0u);
    uint32_t mask0 = up0 ? 0xffffu : 0u, mask1 = up1 ? 0xffffu : 0u;
    const uint32_t neg = pack_bf16(-1e9f, 0.f);
    const uint32_t qoff = (lane & 15) * 128 + (((lane >> 4) ^ (lane & 7)) << 4);
    const uint32_t koff = (lane & 7) * 128 + (((lane >> 3) ^ (lane & 7)) << 4);
    uint4 q[2][2][2], k[2][5], v[2][5];
    auto fetch = [&](int step) {
        const uint32_t st = in + (step & 1) * G1_STAGE_BYTES;
        mbar_wait(full + (step & 1) * 8, (step >> 1) & 1);
#pragma unroll
        for (int u = 0; u < 2; u++) {
#pragma unroll
            for (int h = 0; h < 2; h++) {
                q[h][u][0] = ldsm4(st + u * 2048 + (qoff ^ (h * 64)));
                q[h][u][1] = ldsm4(st + u * 2048 + (qoff ^ (h * 64 + 32)));
                k[h][2 * u + 1] = ldsm4(st + 4096 + u * 2048 + (koff ^ (h * 64)));
                k[h][2 * u + 2] = ldsm4(st + 5120 + u * 2048 + (koff ^ (h * 64)));
            }
        }
#pragma unroll
        for (int j = 0; j < 4; j++) {
#pragma unroll
            for (int h = 0; h < 2; h++) v[h][j + 1] = ldsm4_t(st + 8192 + j * 1024 + (koff ^ (h * 64)));
        }
        __syncwarp();
        if (lane == 0) mbar_arrive(empty + (step & 1) * 8);
    };
#pragma unroll
    for (int h = 0; h < 2; h++) { k[h][0] = make_uint4(0, 0, 0, 0); v[h][0] = make_uint4(0, 0, 0, 0); }
    fetch(0);
#pragma unroll 1
    for (int step = 0; step < ATT_STEPS; step++) {
        uint32_t l0[4], l1[4], m[4];
#pragma unroll
        for (int c = 0; c < 4; c++) {
            const int u = c >> 1, h = c & 1;
            float s0[4], s1[4], s2[4];
            qk_tile(s0, q[h][u][0], q[h][u][1], k[h][2 * u]);
            qk_tile(s1, q[h][u][0], q[h][u][1], k[h][2 * u + 1]);
            qk_tile(s2, q[h][u][0], q[h][u][1], k[h][2 * u + 2]);
            l0[c] = scaled_logits(up0 ? s0[0] : s1[0], up0 ? s1[2] : s2[2]);
            l1[c] = scaled_logits(up1 ? s0[1] : s1[1], up1 ? s1[3] : s2[3]);
            if (u == 0) {
                l0[c] = (l0[c] & ~mask0) | (neg & mask0);
                l1[c] = (l1[c] & ~mask1) | (neg & mask1);
            }
            m[c] = max_bf16x2(l0[c], l1[c]);
        }
        mask0 = 0; mask1 = 0;
#pragma unroll
        for (int c = 0; c < 4; c++) m[c] = max_bf16x2(m[c], __shfl_xor_sync(0xffffffffu, m[c], 1));
#pragma unroll
        for (int c = 0; c < 4; c++) m[c] = max_bf16x2(m[c], __shfl_xor_sync(0xffffffffu, m[c], 2));
        uint4 o[2][4];
#pragma unroll
        for (int c = 0; c < 4; c++) {
            const int u = c >> 1, h = c & 1;
            const float ma = -LOG2E * bf_lo(m[c]), mb = -LOG2E * bf_hi(m[c]);
            const float ea0 = ex2_fast(fmaf(bf_lo(l0[c]), LOG2E, ma)), ea1 = ex2_fast(fmaf(bf_lo(l1[c]), LOG2E, ma));
            const float eb0 = ex2_fast(fmaf(bf_hi(l0[c]), LOG2E, mb)), eb1 = ex2_fast(fmaf(bf_hi(l1[c]), LOG2E, mb));
            const float2 sum = quad_sum2(ea0 + ea1, eb0 + eb1);
            const float ra = rcp_fast(sum.x), rb = rcp_fast(sum.y);
            o[h][2 * u] = pv_tile(v[h][2 * u], v[h][2 * u + 1], pack_bf16(ea0 * ra, ea1 * ra), keep);
            o[h][2 * u + 1] = pv_tile(v[h][2 * u + 1], v[h][2 * u + 2], pack_bf16(eb0 * rb, eb1 * rb), keep);
        }
#pragma unroll
        for (int h = 0; h < 2; h++) { k[h][0] = k[h][4]; v[h][0] = v[h][4]; }
        if (step + 1 < ATT_STEPS) fetch(step + 1);
        mbar_wait(o_free, (step & 1) ^ 1);
#pragma unroll
        for (int j = 0; j < 4; j++) {
#pragma unroll
            for (int h = 0; h < 2; h++)
                asm volatile("stmatrix.sync.aligned.m8n8.x4.trans.shared.b16 [%0], {%1,%2,%3,%4};"
                             :: "r"(out + j * 1024 + (koff ^ (h * 64))), "r"(o[h][j].x), "r"(o[h][j].y), "r"(o[h][j].z),
                                "r"(o[h][j].w) : "memory");
        }
        asm volatile("fence.proxy.async.shared::cta;" ::: "memory");
        __syncwarp();
        if (lane == 0) mbar_arrive(o_ready);
    }
}

__device__ __forceinline__ void warp_sum2(float& a, float& b) {
#pragma unroll
    for (int o = 16; o > 0; o >>= 1) {
        a += __shfl_xor_sync(0xffffffffu, a, o);
        b += __shfl_xor_sync(0xffffffffu, b, o);
    }
}
__device__ __forceinline__ float row_sum(const uint32_t* w) {
    float a = 0.f, b = 0.f;
#pragma unroll
    for (int i = 0; i < 16; i++) { a += bf_lo(w[i]); b += bf_hi(w[i]); }
    return a + b;
}
__device__ __forceinline__ float row_sq(const uint32_t* w, float mean) {
    float a = 0.f, b = 0.f;
#pragma unroll
    for (int i = 0; i < 16; i++) {
        const float lo = bf_lo(w[i]) - mean, hi = bf_hi(w[i]) - mean;
        a = fmaf(lo, lo, a); b = fmaf(hi, hi, b);
    }
    return a + b;
}
__device__ __forceinline__ float row_inv(float sq) {
    return 1.f / round_bf16(sqrtf(round_bf16(round_bf16(sq * (1.f / DM)) + 1e-5f)));
}
__device__ __forceinline__ void row_store(const uint32_t* w, float mean, float inv, int row, int lane) {
    const uint32_t m2 = pack_bf16(mean, mean);
    __nv_bfloat16* dst = g_xn + (size_t)row * DM + lane * 8;
#pragma unroll
    for (int i = 0; i < 4; i++) {
        uint32_t o[4];
#pragma unroll
        for (int j = 0; j < 4; j++) {
            const uint32_t c = sub_bf16x2(w[i * 4 + j], m2);
            o[j] = pack_bf16(bf_lo(c) * inv, bf_hi(c) * inv);
        }
        *reinterpret_cast<uint4*>(dst + i * 256) = make_uint4(o[0], o[1], o[2], o[3]);
    }
    if (lane == 0) g_stats[row] = make_float2(-bf_lo(m2), inv);
}

struct Params {
    CUtensorMap x, xn, wqkv, wg, wu, qkv, o, a2, wo, wd, out;
    const __nv_bfloat16 *px, *pwqkv, *pwg, *pwu;
};

__device__ __forceinline__ bool tile_is_qkv(int nt) { return nt < 4 || (nt >= 8 && nt < 16); }
__device__ __forceinline__ int tile_index(int nt) { return nt < 4 ? nt + 8 : (nt < 8 ? nt - 4 : (nt < 16 ? nt - 8 : nt - 12)); }

__global__ void __cluster_dims__(2, 1, 1) __launch_bounds__(384, 1)
fused_kernel(const __grid_constant__ Params prm) {
    extern __shared__ __align__(1024) uint8_t smem_raw[];
    const uint32_t base = (smem_u32(smem_raw) + 1023) & ~1023u;
    const uint32_t bars = base + BAR_OFF;
    auto full1 = [&](int s) { return bars + s * 8; };
    auto empty1 = [&](int s) { return bars + 32 + s * 8; };
    auto full2 = [&](int s) { return bars + 64 + s * 8; };
    auto empty2 = [&](int s) { return bars + 128 + s * 8; };
    const uint32_t sig_bar = bars + 192, fold_bar = bars + 200, x_bar = bars + 208, dep_bar = bars + 216;
    auto stage2 = [&](int q) { return base + q * G2_STAGE_BYTES; };
    const uint32_t aux = base + AUX_OFF;

    const int warp = __shfl_sync(0xffffffffu, threadIdx.x >> 5, 0);
    const int lane = threadIdx.x & 31;
    const int rank = blockIdx.x & 1;
    const int mblk = ((blockIdx.x >> 1) & 7) * 2 + rank;
    const int nslot = blockIdx.x >> 4;

    if (blockIdx.x >= NGEMM) {
        const int grp = blockIdx.x - NGEMM;
        if (threadIdx.x == 0) {
            TRACE_GT(0); TRACE(1);
            for (int s = 0; s < G1_STAGES; s++) { mbar_init(full1(s), 1); mbar_init(empty1(s), 4); }
            for (int s = 0; s < 2; s++) { mbar_init(full2(s), 4); mbar_init(empty2(s), 1); }
            asm volatile("fence.proxy.async.shared::cta;" ::: "memory");
        }
        __syncthreads();
        if (warp < 8) {
            const int half = warp >> 2;
            asm volatile("setmaxnreg.inc.sync.aligned.u32 %0;" :: "n"(CONSUMER_REGS));
            attention(base + half * 2 * G1_STAGE_BYTES + (warp & 3) * 12288, aux + warp * 4096, full1(half * 2),
                      empty1(half * 2), full2(half), empty2(half), lane);
        } else {
            const int half = warp & 1;
            asm volatile("setmaxnreg.dec.sync.aligned.u32 %0;" :: "n"(AUX_REGS));
            if (warp < 10 && lane == 0) {
                prefetch_map(&prm.qkv);
                const unsigned epoch = __ldcg(g_epoch + blockIdx.x * 8 + half) + 1;
                flag_wait(g_flags + F_QKV * 512 + grp * 32, epoch * CNT_QKV);
                fence_proxy_async();
                g_epoch[blockIdx.x * 8 + half] = epoch;
                if (half == 0) TRACE(9);
                for (int i = 0; i < ATT_STEPS; i++) {
                    const int s = half * 2 + (i & 1);
                    mbar_wait(empty1(s), ((i >> 1) & 1) ^ 1);
                    mbar_expect_tx(full1(s), G1_STAGE_BYTES);
                    tma_5d(base + s * G1_STAGE_BYTES, &prm.qkv, full1(s), i * 32, grp * 4 + half * 2);
                }
            } else if (lane == 0) {
                prefetch_map(&prm.o);
                for (int i = 0; i < ATT_STEPS; i++) {
                    mbar_wait(full2(half), i & 1);
                    tma_store_4d(&prm.o, aux + half * 16384, i * 32, grp * 4 + half * 2);
                    asm volatile("cp.async.bulk.commit_group;" ::: "memory");
                    asm volatile("cp.async.bulk.wait_group.read 0;" ::: "memory");
                    mbar_arrive(empty2(half));
                }
                asm volatile("cp.async.bulk.wait_group 0;" ::: "memory");
                fence_proxy_async();
                flag_add(g_flags + F_O * 512);
                if (half == 0) TRACE(10);
            }
        }
    } else if (warp >= 8) {
        unsigned* const flags = g_flags + mblk * 32;
        if (warp == 8) {
            if (lane == 0) {
                TRACE_GT(0); TRACE(1);
                prefetch_map(&prm.x); prefetch_map(nslot < 4 ? &prm.wqkv : (rank ? &prm.wu : &prm.wg));
                for (int s = 0; s < G1_STAGES; s++) { mbar_init(full1(s), 1); mbar_init(empty1(s), 4); }
                for (int s = 0; s < G2_STAGES; s++) { mbar_init(full2(s), 1); mbar_init(empty2(s), 4); }
                mbar_init(sig_bar, 8); mbar_init(fold_bar, 2); mbar_init(x_bar, 1);
                for (int s = 0; s < 4; s++) mbar_init(dep_bar + s * 8, 1);
                asm volatile("fence.mbarrier_init.release.cluster;" ::: "memory");
            }
            __syncwarp();
        }
        asm volatile("barrier.cluster.arrive.relaxed.aligned;" ::: "memory");
        if (warp == 8 && lane == 0) {
            asm volatile("fence.proxy.async.shared::cta;" ::: "memory");
            for (int s = 0; s < G1_STAGES; s++) {
                mbar_expect_tx(full1(s), G1_STAGE_BYTES);
                tma_2d(base + s * G1_STAGE_BYTES, &prm.x, full1(s), s * 64, mblk * 128);
            }
            TRACE(15);
        }
        asm volatile("setmaxnreg.dec.sync.aligned.u32 %0;" :: "n"(AUX_REGS));
        asm volatile("barrier.cluster.wait.acquire.aligned;" ::: "memory");

        if (warp == 8) {
            if (lane == 0) {
                TRACE(2);
                auto load_b1 = [&](int s, int nt, int k) {
                    const uint32_t dst = base + s * G1_STAGE_BYTES + A_BYTES + rank * 16384;
                    if (tile_is_qkv(nt)) tma_3d_mc(dst, &prm.wqkv, full1(s), k * 64, tile_index(nt) * 4 + rank * 2);
                    else tma_3d_mc(dst, rank ? &prm.wu : &prm.wg, full1(s), k * 64, tile_index(nt) * 2);
                };
                for (int s = 0; s < G1_STAGES; s++) load_b1(s, nslot, s);
                prefetch_map(&prm.xn); prefetch_map(&prm.wqkv); prefetch_map(rank ? &prm.wu : &prm.wg);
                prefetch_map(&prm.a2); prefetch_map(&prm.wo); prefetch_map(&prm.wd); prefetch_map(&prm.out);
                uint32_t ph = 0;
                for (int it = G1_STAGES; it < G1_TILES * G1_KSTEPS; it++) {
                    const int s = it & 3, k = it & 15;
                    if (it == G1_KSTEPS) { TRACE(14); mbar_wait(dep_bar, 0); TRACE(3); }
                    mbar_wait(empty1(s), ph);
                    mbar_expect_tx(full1(s), G1_STAGE_BYTES);
                    tma_2d(base + s * G1_STAGE_BYTES, it < G1_KSTEPS ? &prm.x : &prm.xn, full1(s), k * 64, mblk * 128);
                    load_b1(s, (it >> 4) * 8 + nslot, k);
                    if (s == 3) ph ^= 1;
                }
                mbar_expect_tx(x_bar, 32768);
                tma_2d(aux, &prm.x, x_bar, nslot * 128, mblk * 128);
                tma_2d(aux + 16384, &prm.x, x_bar, nslot * 128 + 64, mblk * 128);
                TRACE(4);
                mbar_wait(dep_bar + 8, 0);
                TRACE(5);
                int q = 0; uint32_t ph2 = 1;
                for (int u = 0; u < G2_KSTEPS; u++) {
                    if (u == G2_LATE || u == G2_DSTEPS) {
                        TRACE(u == G2_LATE ? 6 : 32);
                        mbar_wait(dep_bar + (u == G2_LATE ? 16 : 24), 0);
                        TRACE(u == G2_LATE ? 7 : 33);
                    }
                    if (u < G2_STAGES) {
                        if (u == 0) mbar_wait(empty1(0), ph);
                        if (u == 1) mbar_wait(empty1(1), ph);
                        if (u == 3) mbar_wait(empty1(2), ph);
                        if (u == 4) mbar_wait(empty1(3), ph);
                    } else {
                        mbar_wait(empty2(q), ph2);
                    }
                    const uint32_t sa = stage2(q);
                    const bool down = u < G2_DSTEPS;
                    const int k = down ? u : u - G2_DSTEPS;
                    mbar_expect_tx(full2(q), G2_STAGE_BYTES);
                    tma_2d(sa, &prm.a2, full2(q), (down ? DM : 0) + k * 64, mblk * 128);
                    tma_5d_mc(sa + A_BYTES + rank * 8192, down ? &prm.wd : &prm.wo, full2(q), nslot * 128 + rank * 64, k * 2);
                    if (++q == G2_STAGES) { q = 0; ph2 ^= 1; }
                }
                TRACE(8);
            }
        } else if (warp == 9) {
            if (lane == 0) {
                mbar_wait(sig_bar, 0);
                TRACE(11);
                flag_add(flags + F_LN * 512);
                for (int t = 0; t < G1_TILES; t++) {
                    mbar_wait(sig_bar, (t + 1) & 1);
                    const int nt = t * 8 + nslot;
                    flag_add(tile_is_qkv(nt) ? g_flags + F_QKV * 512 + (nt & 3) * 32
                                             : flags + (t < G1_TILES - 1 ? F_EARLY : F_LATE) * 512);
                }
            }
        } else {
            const int w = warp - 10;
            const int ld = nslot < 4 ? NQKV : DF;
            const __nv_bfloat16* wp = nslot < 4 ? prm.pwqkv + 2 * DM + nslot * 256 + lane * 8
                                                : (lane < 16 ? prm.pwg : prm.pwu) + (nslot - 4) * 128 + (lane & 15) * 8;
            wp += (size_t)(mblk * 64 + w * 32) * ld;
            const unsigned epoch = __ldcg(g_epoch + blockIdx.x * 8 + w) + 1;
            float cs[8];
#pragma unroll
            for (int d = 0; d < 8; d++) cs[d] = 0.f;
            mbar_wait(full1(0), 0);
#pragma unroll 1
            for (int i = 0; i < 4; i++) {
                uint4 v[8];
#pragma unroll
                for (int j = 0; j < 8; j++) v[j] = __ldg(reinterpret_cast<const uint4*>(wp + (size_t)(i * 8 + j) * ld));
#pragma unroll
                for (int j = 0; j < 8; j++) {
                    float f[8];
                    unpack8(v[j], f);
#pragma unroll
                    for (int d = 0; d < 8; d++) cs[d] += f[d];
                }
            }
            float4* cp = reinterpret_cast<float4*>(g_colsum + (mblk * 2 + w) * 2048 + nslot * 256 + lane * 8);
            cp[0] = make_float4(cs[0], cs[1], cs[2], cs[3]);
            cp[1] = make_float4(cs[4], cs[5], cs[6], cs[7]);
            __syncwarp();
            if (lane == 0) {
                if (w == 0) TRACE(34);
                flag_add(g_flags + F_CS * 512 + nslot * 32);
                flag_wait(g_flags + F_CS * 512 + nslot * 32, epoch * CNT_CS);
            }
            __syncwarp();
            const float4* gp = reinterpret_cast<const float4*>(g_colsum + nslot * 256 + w * 128) + lane;
            float4 c = make_float4(0.f, 0.f, 0.f, 0.f);
#pragma unroll 8
            for (int m = 0; m < 32; m++) {
                const float4 a = __ldcg(gp + m * 512);
                c.x += a.x; c.y += a.y; c.z += a.z; c.w += a.w;
            }
            const uint32_t ca = aux + (w * 8 + (lane >> 2)) * 64 + (lane & 1) * 32 + (lane & 2) * 4;
            sts64f(ca, c.x, c.y);
            sts64f(ca + 16, c.z, c.w);
            if (lane == 0) {
                flag_wait(flags + F_LN * 512, epoch * CNT_LN);
                if (w == 0) { fence_proxy_async(); mbar_arrive(dep_bar); }
            }
            __syncwarp();
            sts128(aux + 1024 + w * 512 + lane * 16, __ldcg(reinterpret_cast<const uint4*>(g_stats + mblk * 128 + w * 64) + lane));
            __syncwarp();
            if (lane == 0) {
                mbar_arrive(fold_bar);
                g_epoch[blockIdx.x * 8 + w] = epoch;
                if (w == 0) {
                    TRACE(35);
                    flag_wait(flags + F_EARLY * 512, epoch * CNT_EARLY);
                    fence_proxy_async(); mbar_arrive(dep_bar + 8);
                    flag_wait(flags + F_LATE * 512, epoch * CNT_LATE);
                    fence_proxy_async(); mbar_arrive(dep_bar + 16);
                    flag_wait(g_flags + F_O * 512, epoch * CNT_O);
                    fence_proxy_async(); mbar_arrive(dep_bar + 24);
                }
            }
        }
    } else {
        asm volatile("barrier.cluster.arrive.relaxed.aligned;" ::: "memory");
        asm volatile("setmaxnreg.inc.sync.aligned.u32 %0;" :: "n"(CONSUMER_REGS));
        const int wg = __shfl_sync(0xffffffffu, threadIdx.x >> 7, 0);
        const int cw = threadIdx.x >> 5;
        const int tid = threadIdx.x & 127;
        float acc[128];
        uint32_t pk[64];
#pragma unroll
        for (int i = 0; i < 64; i++) asm volatile("mov.b32 %0, 0;" : "=r"(pk[i]));
#pragma unroll
        for (int i = 0; i < 128; i++) asm volatile("mov.b32 %0, 0;" : "=f"(acc[i]));
        asm volatile("barrier.cluster.wait.acquire.aligned;" ::: "memory");

        const int orow = mblk * 128 + cw * 16 + (lane >> 2);
        __nv_bfloat16* optr = nullptr;
        auto release = [&](uint32_t bar) { if (tid < 2) mbar_arrive_cluster(bar, tid); };
        auto chunk_geglu = [&](int j) {
            const int c = j >> 1, h = j & 1;
            uint4 v;
            v.x = geglu2(pk[8 * c + h], pk[32 + 8 * c + h]);
            v.y = geglu2(pk[8 * c + 2 + h], pk[32 + 8 * c + 2 + h]);
            v.z = geglu2(pk[8 * c + 4 + h], pk[32 + 8 * c + 4 + h]);
            v.w = geglu2(pk[8 * c + 6 + h], pk[32 + 8 * c + 6 + h]);
            *reinterpret_cast<uint4*>(optr + h * 8 * K2 + c * 32) = v;
        };
        auto chunk_qkv = [&](int c) {
            *reinterpret_cast<uint4*>(optr + c * 32) = make_uint4(pk[8 * c], pk[8 * c + 2], pk[8 * c + 4], pk[8 * c + 6]);
            *reinterpret_cast<uint4*>(optr + 8 * NQKV + c * 32) = make_uint4(pk[8 * c + 1], pk[8 * c + 3], pk[8 * c + 5], pk[8 * c + 7]);
        };
        auto signal_stores = [&]() { __syncwarp(); if (lane == 0) mbar_arrive(sig_bar); };

        auto chunk_ln = [&](int k) {
            const int row = mblk * 128 + nslot * 16 + cw * 2;
            if (k == 0) {
                const uint4* xp = reinterpret_cast<const uint4*>(prm.px + (size_t)row * DM) + lane;
#pragma unroll
                for (int i = 0; i < 8; i++) {
                    const uint4 v = __ldg(xp + i * 32);
                    pk[4 * i] = v.x; pk[4 * i + 1] = v.y; pk[4 * i + 2] = v.z; pk[4 * i + 3] = v.w;
                }
            } else if (k == 3) {
                float a = row_sum(pk), b = row_sum(pk + 16);
                warp_sum2(a, b);
                pk[32] = __float_as_uint(a * (1.f / DM)); pk[33] = __float_as_uint(b * (1.f / DM));
            } else if (k == 4) {
                pk[34] = __float_as_uint(row_sq(pk, __uint_as_float(pk[32])));
            } else if (k == 5) {
                float a = __uint_as_float(pk[34]), b = row_sq(pk + 16, __uint_as_float(pk[33]));
                warp_sum2(a, b);
                pk[34] = __float_as_uint(a); pk[35] = __float_as_uint(b);
            } else if (k == 6) {
                row_store(pk, __uint_as_float(pk[32]), row_inv(__uint_as_float(pk[34])), row, lane);
            } else if (k == 7) {
                row_store(pk + 16, __uint_as_float(pk[33]), row_inv(__uint_as_float(pk[35])), row + 1, lane);
                signal_stores();
            }
        };

        int pending = 0;
#pragma unroll 1
        for (int t = 0; t < G1_TILES; t++) {
#pragma unroll
            for (int k = 0; k < G1_KSTEPS; k++) {
                const int s = k & 3;
                mbar_wait(full1(s), (k >> 2) & 1);
                if (t == 0 && k == 0 && threadIdx.x == 0) TRACE(12);
                if (wg == 1 && k == G1_KSTEPS - G1_SKEW) asm volatile("bar.sync 1, 256;" ::: "memory");
                const uint64_t da = desc_a(base + s * G1_STAGE_BYTES + wg * 8192);
                const uint64_t db = desc_b(base + s * G1_STAGE_BYTES + A_BYTES);
                wg_fence();
#pragma unroll
                for (int kk = 0; kk < 4; kk++) wgmma_n256(acc, da + kk * 2, db + kk * 128, (k | kk) != 0);
                wg_commit();
                if (wg == 0 && k == G1_KSTEPS - 1) asm volatile("bar.arrive 1, 256;" ::: "memory");
                if (k <= 7 && pending == 0) chunk_ln(k);
                if (k >= 1 && k <= 8) {
                    if (pending == 2) chunk_geglu(k - 1);
                    else if (pending == 1) chunk_qkv(k - 1);
                    if (k == 8 && pending) signal_stores();
                }
                wg_wait<1>();
                if (k > 0) release(empty1((k - 1) & 3));
            }
            if (t == 0) mbar_wait(fold_bar, 0);
            wg_wait<0>();
            fence_regs(acc);
            release(empty1(3));
            if (t == 0) {
                const uint32_t sp = aux + 1024 + (cw * 16 + (lane >> 2)) * 8;
                const float2 sa = lds64f(sp), sb = lds64f(sp + 64);
#pragma unroll
                for (int j = 0; j < 16; j++) {
                    const uint4 c = lds128(aux + j * 64 + (lane & 3) * 16);
                    const float c0 = __uint_as_float(c.x), c1 = __uint_as_float(c.y);
                    const float c2 = __uint_as_float(c.z), c3 = __uint_as_float(c.w);
                    const float* a = acc + 8 * j;
                    pk[4 * j] = pack_bf16(fmaf(sa.x, c0, a[0]) * sa.y, fmaf(sa.x, c1, a[1]) * sa.y);
                    pk[4 * j + 1] = pack_bf16(fmaf(sb.x, c0, a[2]) * sb.y, fmaf(sb.x, c1, a[3]) * sb.y);
                    pk[4 * j + 2] = pack_bf16(fmaf(sa.x, c2, a[4]) * sa.y, fmaf(sa.x, c3, a[5]) * sa.y);
                    pk[4 * j + 3] = pack_bf16(fmaf(sb.x, c2, a[6]) * sb.y, fmaf(sb.x, c3, a[7]) * sb.y);
                }
            } else {
#pragma unroll
                for (int i = 0; i < 64; i++) pk[i] = pack_bf16(acc[2 * i], acc[2 * i + 1]);
            }
            const int nt = t * 8 + nslot;
            pending = tile_is_qkv(nt) ? 1 : 2;
            optr = pending == 1 ? g_qkv + (size_t)orow * NQKV + tile_index(nt) * 256 + (lane & 3) * 8
                                : g_a2 + (size_t)orow * K2 + DM + tile_index(nt) * 128 + (lane & 3) * 8;
            if (tid == 0) TRACE(16 + wg * 8 + t);
        }

        float accd[64], accs[64];
#pragma unroll
        for (int i = 0; i < 64; i++) accd[i] = 0.f;
#pragma unroll
        for (int u = 0; u < 9; u++) {
            const int q = u % G2_STAGES;
            mbar_wait(full2(q), (u / G2_STAGES) & 1);
            const uint64_t da = desc_a(stage2(q) + wg * 8192), db = desc_b(stage2(q) + A_BYTES);
            wg_fence();
#pragma unroll
            for (int kk = 0; kk < 4; kk++) wgmma_n128(accd, da + kk * 2, db + kk * 128, (u | kk) != 0);
            wg_commit();
            if (u >= 1) { chunk_geglu(u - 1); if (u == 8) signal_stores(); }
            wg_wait<1>();
            if (u > 0) release(empty2((u - 1) % G2_STAGES));
        }
        {
            int q = 9 % G2_STAGES, qp = 8 % G2_STAGES; uint32_t ph = (9 / G2_STAGES) & 1;
#pragma unroll 1
            for (int u = 9; u < G2_DSTEPS; u++) {
                mbar_wait(full2(q), ph);
                const uint64_t da = desc_a(stage2(q) + wg * 8192), db = desc_b(stage2(q) + A_BYTES);
                wg_fence();
#pragma unroll
                for (int kk = 0; kk < 4; kk++) wgmma_n128(accd, da + kk * 2, db + kk * 128, 1);
                wg_commit();
                wg_wait<1>();
                release(empty2(qp));
                qp = q;
                if (++q == G2_STAGES) { q = 0; ph ^= 1; }
            }
        }
        if (tid == 0) TRACE(16 + wg * 8 + 5);
#pragma unroll
        for (int i = 0; i < 64; i++) accs[i] = 0.f;
        uint32_t gk[32], xr[32];
        const uint32_t xs = aux + cw * 2048;
        const uint32_t xrow = xs + ((lane & 7) + ((lane >> 3) & 1) * 8) * 128;
        auto xaddr = [&](int j) { return xrow + (j >> 2) * 16384 + (((((j & 3) * 2) + (lane >> 4)) ^ (lane & 7)) << 4); };
#pragma unroll
        for (int u = G2_DSTEPS; u < G2_KSTEPS; u++) {
            const int q = u % G2_STAGES, v = u - G2_DSTEPS;
            mbar_wait(full2(q), (u / G2_STAGES) & 1);
            if (G2_SKEW > 0 && wg == 1 && u == G2_KSTEPS - G2_SKEW) asm volatile("bar.sync 1, 256;" ::: "memory");
            const uint64_t da = desc_a(stage2(q) + wg * 8192), db = desc_b(stage2(q) + A_BYTES);
            wg_fence();
#pragma unroll
            for (int kk = 0; kk < 4; kk++) wgmma_n128(accs, da + kk * 2, db + kk * 128, (v | kk) != 0);
            wg_commit();
            if (G2_SKEW > 0 && wg == 0 && u == G2_KSTEPS - 1) asm volatile("bar.arrive 1, 256;" ::: "memory");
            if (v >= 1 && v <= 8) {
#pragma unroll
                for (int i = 4 * (v - 1); i < 4 * v; i++) {
                    const uint32_t d2 = pack_bf16(accd[2 * i], accd[2 * i + 1]);
                    gk[i] = pack_bf16(silu(bf_lo(d2)), silu(bf_hi(d2)));
                }
            }
            if (v == 9) mbar_wait(x_bar, 0);
            if (v >= 9 && v <= 12) {
#pragma unroll
                for (int j = 2 * (v - 9); j < 2 * (v - 8); j++)
                    asm volatile("ldmatrix.sync.aligned.m8n8.x4.shared.b16 {%0,%1,%2,%3}, [%4];"
                                 : "=r"(xr[4 * j]), "=r"(xr[4 * j + 1]), "=r"(xr[4 * j + 2]), "=r"(xr[4 * j + 3])
                                 : "r"(xaddr(j)) : "memory");
            }
            wg_wait<1>();
            if (v == 0) fence_regs(accd);
            if (u - 1 + G2_STAGES < G2_KSTEPS) release(empty2((u - 1) % G2_STAGES));
        }
        wg_wait<0>();
        fence_regs(accs);
        if (tid == 0) TRACE(16 + wg * 8 + 6);
#pragma unroll
        for (int j = 0; j < 8; j++) {
            uint32_t r[4];
#pragma unroll
            for (int i = 0; i < 4; i++) {
                const int e = j * 4 + i;
                r[i] = add_bf16x2(xr[e], mul_bf16x2(pack_bf16(accs[2 * e], accs[2 * e + 1]), gk[e]));
            }
            asm volatile("stmatrix.sync.aligned.m8n8.x4.shared.b16 [%0], {%1,%2,%3,%4};"
                         :: "r"(xaddr(j)), "r"(r[0]), "r"(r[1]), "r"(r[2]), "r"(r[3]) : "memory");
            if (j == 3 || j == 7) {
                asm volatile("fence.proxy.async.shared::cta;" ::: "memory");
                __syncwarp();
                if (lane == 0) {
                    tma_store_2d(&prm.out, xs + (j >> 2) * 16384, nslot * 128 + (j >> 2) * 64, mblk * 128 + cw * 16);
                    asm volatile("cp.async.bulk.commit_group;" ::: "memory");
                }
            }
        }
        if (lane == 0) asm volatile("cp.async.bulk.wait_group.read 0;" ::: "memory");
        if (tid == 0) { TRACE(16 + wg * 8 + 7); if (wg == 1) TRACE_GT(13); }
    }
}

typedef CUresult (*EncodeFn)(CUtensorMap*, CUtensorMapDataType, cuuint32_t, void*, const cuuint64_t*, const cuuint64_t*,
                             const cuuint32_t*, const cuuint32_t*, CUtensorMapInterleave, CUtensorMapSwizzle,
                             CUtensorMapL2promotion, CUtensorMapFloatOOBfill);

void encode(EncodeFn fn, CUtensorMap* m, const void* ptr, int rank, const cuuint64_t* dims, const cuuint64_t* strides,
            const cuuint32_t* box) {
    const cuuint32_t es[5] = {1, 1, 1, 1, 1};
    fn(m, CU_TENSOR_MAP_DATA_TYPE_BFLOAT16, rank, const_cast<void*>(ptr), dims, strides, box, es,
       CU_TENSOR_MAP_INTERLEAVE_NONE, CU_TENSOR_MAP_SWIZZLE_128B, CU_TENSOR_MAP_L2_PROMOTION_L2_128B,
       CU_TENSOR_MAP_FLOAT_OOB_FILL_NONE);
}
void encode_2d(EncodeFn fn, CUtensorMap* m, const void* ptr, int cols, int box_rows) {
    const cuuint64_t dims[2] = {(cuuint64_t)cols, SEQ}, strides[1] = {(cuuint64_t)cols * 2};
    const cuuint32_t box[2] = {64, (cuuint32_t)box_rows};
    encode(fn, m, ptr, 2, dims, strides, box);
}
void encode_w1(EncodeFn fn, CUtensorMap* m, const void* ptr, int cols) {
    const cuuint64_t dims[3] = {64, DM, (cuuint64_t)cols / 64}, strides[2] = {(cuuint64_t)cols * 2, 128};
    const cuuint32_t box[3] = {64, 64, 2};
    encode(fn, m, ptr, 3, dims, strides, box);
}
void encode_qkv(EncodeFn fn, CUtensorMap* m, const void* ptr) {
    const cuuint64_t dims[5] = {64, SEQ / 2, 3, 2, DM / 64}, strides[4] = {NQKV * 4, DM * 2, NQKV * 2, 128};
    const cuuint32_t box[5] = {64, 32, 3, 2, 2};
    encode(fn, m, ptr, 5, dims, strides, box);
}
void encode_o(EncodeFn fn, CUtensorMap* m, const void* ptr) {
    const cuuint64_t dims[4] = {64, SEQ / 2, 2, DM / 64}, strides[3] = {K2 * 4, K2 * 2, 128};
    const cuuint32_t box[4] = {64, 32, 2, 2};
    encode(fn, m, ptr, 4, dims, strides, box);
}
void encode_w2(EncodeFn fn, CUtensorMap* m, const void* ptr, int rows) {
    const cuuint64_t rb = DM * 2;
    const cuuint64_t dims[5] = {DM, 2, 4, 4, (cuuint64_t)rows / 32}, strides[4] = {rb, 8 * rb, 2 * rb, 32 * rb};
    const cuuint32_t box[5] = {64, 2, 4, 4, 2};
    encode(fn, m, ptr, 5, dims, strides, box);
}

}

extern "C" void kernel_launch(void* const* d_in, const int* in_sizes, int n_in, void* d_out, int out_size) {
    (void)in_sizes; (void)n_in; (void)out_size;
    static EncodeFn fn = nullptr;
    static void *p_xn = nullptr, *p_qkv = nullptr, *p_a2 = nullptr;
    if (!fn) {
        cudaDriverEntryPointQueryResult st;
        cudaGetDriverEntryPoint("cuTensorMapEncodeTiled", (void**)&fn, cudaEnableDefault, &st);
        cudaGetSymbolAddress(&p_xn, g_xn);
        cudaGetSymbolAddress(&p_qkv, g_qkv);
        cudaGetSymbolAddress(&p_a2, g_a2);
        cudaFuncSetAttribute(fused_kernel, cudaFuncAttributeMaxDynamicSharedMemorySize, SMEM_BYTES);
    }
    Params prm;
    encode_2d(fn, &prm.x, d_in[0], DM, 128);
    encode_2d(fn, &prm.xn, p_xn, DM, 128);
    encode_w1(fn, &prm.wqkv, d_in[1], NQKV);
    encode_w1(fn, &prm.wg, d_in[4], DF);
    encode_w1(fn, &prm.wu, d_in[5], DF);
    encode_qkv(fn, &prm.qkv, p_qkv);
    encode_o(fn, &prm.o, p_a2);
    encode_2d(fn, &prm.a2, p_a2, K2, 128);
    encode_w2(fn, &prm.wo, d_in[2], DM);
    encode_w2(fn, &prm.wd, d_in[6], DF);
    encode_2d(fn, &prm.out, d_out, DM, 16);
    prm.px = (const __nv_bfloat16*)d_in[0];
    prm.pwqkv = (const __nv_bfloat16*)d_in[1];
    prm.pwg = (const __nv_bfloat16*)d_in[4];
    prm.pwu = (const __nv_bfloat16*)d_in[5];
    fused_kernel<<<NCTA, 384, SMEM_BYTES>>>(prm);
}
```

```cpp
#include <cuda_runtime.h>
#include <cuda_bf16.h>
#include <cuda.h>
#include <stdint.h>

namespace {

constexpr int SEQ = 2048, DM = 1024, DF = 3584, K2 = DM + DF, NQKV = 3 * DM;
constexpr int NGEMM = 128, NCTA = 132;
constexpr int G1_STAGES = 4, G1_STAGE_BYTES = 49152, G1_KSTEPS = 16, G1_TILES = 5;
constexpr int G2_STAGES = 6, G2_STAGE_BYTES = 32768, G2_KSTEPS = 72, G2_DSTEPS = 56, G2_LATE = 40;
constexpr int A_BYTES = 16384;
constexpr int AUX_OFF = G1_STAGES * G1_STAGE_BYTES;
constexpr int BAR_OFF = AUX_OFF + 32768;
constexpr int SMEM_BYTES = BAR_OFF + 1024 + 256;
constexpr int G1_SKEW = 2, G2_SKEW = 2;
constexpr int CONSUMER_REGS = 224, AUX_REGS = 56;
constexpr int ATT_SLOTS = 3, ATT_BYTES = 6144;

enum { F_LN = 0, F_QKV = 1, F_EARLY = 2, F_LATE = 3, F_O = 4, F_CS = 5 };
constexpr unsigned CNT_LN = 8, CNT_QKV = 48, CNT_EARLY = 20, CNT_LATE = 8, CNT_O = 48, CNT_CS = 32;

__device__ __align__(1024) __nv_bfloat16 g_xn[SEQ * DM];
__device__ __align__(1024) __nv_bfloat16 g_qkv[SEQ * NQKV];
__device__ __align__(1024) __nv_bfloat16 g_a2[SEQ * K2];
__device__ __align__(128) float2 g_stats[SEQ];
__device__ __align__(128) float g_colsum[32 * 2048];
__device__ __align__(128) unsigned g_flags[6 * 16 * 32];
__device__ __align__(128) unsigned g_epoch[NCTA * 16];

#define TRACE(slot) do {} while (0)
#define TRACE_GT(slot) do {} while (0)

__device__ __forceinline__ uint32_t smem_u32(const void* p) { return (uint32_t)__cvta_generic_to_shared(p); }
__device__ __forceinline__ void mbar_init(uint32_t bar, uint32_t cnt) {
    asm volatile("mbarrier.init.shared::cta.b64 [%0], %1;" :: "r"(bar), "r"(cnt) : "memory");
}
__device__ __forceinline__ void mbar_expect_tx(uint32_t bar, uint32_t bytes) {
    asm volatile("mbarrier.arrive.expect_tx.shared::cta.b64 _, [%0], %1;" :: "r"(bar), "r"(bytes) : "memory");
}
__device__ __forceinline__ void mbar_arrive(uint32_t bar) {
    asm volatile("mbarrier.arrive.shared::cta.b64 _, [%0];" :: "r"(bar) : "memory");
}
__device__ __forceinline__ void mbar_arrive_cluster(uint32_t bar, uint32_t cta) {
    asm volatile("{\n.reg .b32 ra;\nmapa.shared::cluster.u32 ra, %0, %1;\nmbarrier.arrive.shared::cluster.b64 _, [ra];\n}"
                 :: "r"(bar), "r"(cta) : "memory");
}
__device__ __forceinline__ bool mbar_try_wait(uint32_t bar, uint32_t parity) {
    uint32_t ok;
    asm volatile("{\n.reg .pred p;\nmbarrier.try_wait.parity.shared::cta.b64 p, [%1], %2;\nselp.u32 %0, 1, 0, p;\n}"
                 : "=r"(ok) : "r"(bar), "r"(parity) : "memory");
    return ok;
}
__device__ __forceinline__ void mbar_wait(uint32_t bar, uint32_t parity) {
    int spins = 0;
    while (!mbar_try_wait(bar, parity)) { if (++spins > (1 << 17)) break; }
}
__device__ __forceinline__ void flag_wait(const unsigned* p, unsigned target) {
    for (int spins = 0; spins < (1 << 19); spins++) {
        unsigned v;
        asm volatile("ld.acquire.gpu.global.u32 %0, [%1];" : "=r"(v) : "l"(p) : "memory");
        if ((int)(v - target) >= 0) break;
        __nanosleep(64);
    }
}
__device__ __forceinline__ void flag_add(unsigned* p) {
    asm volatile("red.release.gpu.global.add.u32 [%0], 1;" :: "l"(p) : "memory");
}
__device__ __forceinline__ void fence_proxy_async() { asm volatile("fence.proxy.async;" ::: "memory"); }
__device__ __forceinline__ uint4 lds128(uint32_t addr) {
    uint4 v;
    asm volatile("ld.shared.v4.u32 {%0,%1,%2,%3}, [%4];" : "=r"(v.x), "=r"(v.y), "=r"(v.z), "=r"(v.w) : "r"(addr) : "memory");
    return v;
}
__device__ __forceinline__ float2 lds64f(uint32_t addr) {
    float2 v;
    asm volatile("ld.shared.v2.f32 {%0,%1}, [%2];" : "=f"(v.x), "=f"(v.y) : "r"(addr) : "memory");
    return v;
}
__device__ __forceinline__ void sts128(uint32_t addr, uint4 v) {
    asm volatile("st.shared.v4.u32 [%0], {%1,%2,%3,%4};" :: "r"(addr), "r"(v.x), "r"(v.y), "r"(v.z), "r"(v.w) : "memory");
}
__device__ __forceinline__ void sts64f(uint32_t addr, float a, float b) {
    asm volatile("st.shared.v2.f32 [%0], {%1,%2};" :: "r"(addr), "f"(a), "f"(b) : "memory");
}

__device__ __forceinline__ void tma_2d(uint32_t dst, const CUtensorMap* m, uint32_t bar, int c0, int c1) {
    asm volatile("cp.async.bulk.tensor.2d.shared::cluster.global.mbarrier::complete_tx::bytes [%0], [%1, {%3, %4}], [%2];"
                 :: "r"(dst), "l"(m), "r"(bar), "r"(c0), "r"(c1) : "memory");
}
__device__ __forceinline__ void tma_5d(uint32_t dst, const CUtensorMap* m, uint32_t bar, int c1, int c3, int c4) {
    asm volatile("cp.async.bulk.tensor.5d.shared::cluster.global.mbarrier::complete_tx::bytes [%0], [%1, {%3, %4, %3, %5, %6}], [%2];"
                 :: "r"(dst), "l"(m), "r"(bar), "r"(0), "r"(c1), "r"(c3), "r"(c4) : "memory");
}
__device__ __forceinline__ void tma_3d_mc(uint32_t dst, const CUtensorMap* m, uint32_t bar, int c1, int c2) {
    asm volatile("cp.async.bulk.tensor.3d.shared::cluster.global.mbarrier::complete_tx::bytes.multicast::cluster"
                 " [%0], [%1, {%3, %4, %5}], [%2], %6;"
                 :: "r"(dst), "l"(m), "r"(bar), "r"(0), "r"(c1), "r"(c2), "h"((uint16_t)3) : "memory");
}
__device__ __forceinline__ void tma_5d_mc(uint32_t dst, const CUtensorMap* m, uint32_t bar, int c0, int c4) {
    asm volatile("cp.async.bulk.tensor.5d.shared::cluster.global.mbarrier::complete_tx::bytes.multicast::cluster"
                 " [%0], [%1, {%3, %4, %4, %4, %5}], [%2], %6;"
                 :: "r"(dst), "l"(m), "r"(bar), "r"(c0), "r"(0), "r"(c4), "h"((uint16_t)3) : "memory");
}
__device__ __forceinline__ void tma_store_2d(const CUtensorMap* m, uint32_t src, int c0, int c1) {
    asm volatile("cp.async.bulk.tensor.2d.global.shared::cta.bulk_group [%0, {%2, %3}], [%1];"
                 :: "l"(m), "r"(src), "r"(c0), "r"(c1) : "memory");
}
__device__ __forceinline__ void prefetch_map(const CUtensorMap* m) {
    asm volatile("prefetch.tensormap [%0];" :: "l"(m) : "memory");
}
__device__ __forceinline__ void wg_fence() { asm volatile("wgmma.fence.sync.aligned;" ::: "memory"); }
__device__ __forceinline__ void wg_commit() { asm volatile("wgmma.commit_group.sync.aligned;" ::: "memory"); }
template <int N> __device__ __forceinline__ void wg_wait() { asm volatile("wgmma.wait_group.sync.aligned %0;" :: "n"(N) : "memory"); }

__device__ __forceinline__ uint64_t desc_a(uint32_t addr) {
    return (uint64_t)((addr & 0x3FFFF) >> 4) | (1ull << 16) | (64ull << 32) | (1ull << 62);
}
__device__ __forceinline__ uint64_t desc_b(uint32_t addr) {
    return (uint64_t)((addr & 0x3FFFF) >> 4) | (512ull << 16) | (64ull << 32) | (1ull << 62);
}

#define R8(d, o) "+f"(d[o]), "+f"(d[o+1]), "+f"(d[o+2]), "+f"(d[o+3]), "+f"(d[o+4]), "+f"(d[o+5]), "+f"(d[o+6]), "+f"(d[o+7])
#define R32(d, o) R8(d, o), R8(d, o+8), R8(d, o+16), R8(d, o+24)
#define R64(d, o) R32(d, o), R32(d, o+32)

__device__ __forceinline__ void wgmma_n256(float (&d)[128], uint64_t da, uint64_t db, int scale_d) {
    asm volatile("{\n.reg .pred p;\nsetp.ne.b32 p, %130, 0;\n"
        "wgmma.mma_async.sync.aligned.m64n256k16.f32.bf16.bf16 "
        "{%0,%1,%2,%3,%4,%5,%6,%7,%8,%9,%10,%11,%12,%13,%14,%15,%16,%17,%18,%19,%20,%21,%22,%23,%24,%25,%26,%27,%28,%29,%30,%31,"
        "%32,%33,%34,%35,%36,%37,%38,%39,%40,%41,%42,%43,%44,%45,%46,%47,%48,%49,%50,%51,%52,%53,%54,%55,%56,%57,%58,%59,%60,%61,%62,%63,"
        "%64,%65,%66,%67,%68,%69,%70,%71,%72,%73,%74,%75,%76,%77,%78,%79,%80,%81,%82,%83,%84,%85,%86,%87,%88,%89,%90,%91,%92,%93,%94,%95,"
        "%96,%97,%98,%99,%100,%101,%102,%103,%104,%105,%106,%107,%108,%109,%110,%111,%112,%113,%114,%115,%116,%117,%118,%119,%120,%121,%122,%123,%124,%125,%126,%127},"
        " %128, %129, p, 1, 1, 0, 1;\n}"
        : R64(d, 0), R64(d, 64) : "l"(da), "l"(db), "r"(scale_d));
}
__device__ __forceinline__ void wgmma_n128(float (&d)[64], uint64_t da, uint64_t db, int scale_d) {
    asm volatile("{\n.reg .pred p;\nsetp.ne.b32 p, %66, 0;\n"
        "wgmma.mma_async.sync.aligned.m64n128k16.f32.bf16.bf16 "
        "{%0,%1,%2,%3,%4,%5,%6,%7,%8,%9,%10,%11,%12,%13,%14,%15,%16,%17,%18,%19,%20,%21,%22,%23,%24,%25,%26,%27,%28,%29,%30,%31,"
        "%32,%33,%34,%35,%36,%37,%38,%39,%40,%41,%42,%43,%44,%45,%46,%47,%48,%49,%50,%51,%52,%53,%54,%55,%56,%57,%58,%59,%60,%61,%62,%63},"
        " %64, %65, p, 1, 1, 0, 1;\n}"
        : R64(d, 0) : "l"(da), "l"(db), "r"(scale_d));
}

__device__ __forceinline__ uint32_t pack_bf16(float lo, float hi) {
    uint32_t r; asm("cvt.rn.bf16x2.f32 %0, %1, %2;" : "=r"(r) : "f"(hi), "f"(lo)); return r;
}
__device__ __forceinline__ float bf_lo(uint32_t v) { return __uint_as_float(v << 16); }
__device__ __forceinline__ float bf_hi(uint32_t v) { return __uint_as_float(v & 0xffff0000u); }
__device__ __forceinline__ float round_bf16(float v) { return bf_lo(pack_bf16(v, 0.f)); }
__device__ __forceinline__ uint32_t mul_bf16x2(uint32_t a, uint32_t b) {
    uint32_t r; asm("mul.rn.bf16x2 %0, %1, %2;" : "=r"(r) : "r"(a), "r"(b)); return r;
}
__device__ __forceinline__ uint32_t add_bf16x2(uint32_t a, uint32_t b) {
    uint32_t r; asm("add.rn.bf16x2 %0, %1, %2;" : "=r"(r) : "r"(a), "r"(b)); return r;
}
__device__ __forceinline__ uint32_t sub_bf16x2(uint32_t a, uint32_t b) {
    uint32_t r; asm("sub.rn.bf16x2 %0, %1, %2;" : "=r"(r) : "r"(a), "r"(b)); return r;
}
__device__ __forceinline__ float tanh_fast(float x) { float r; asm("tanh.approx.f32 %0, %1;" : "=f"(r) : "f"(x)); return r; }
__device__ __forceinline__ float gelu_tanh(float g) {
    float t = fmaf(g * g, 0.044715f * 0.7978845608f, 0.7978845608f) * g;
    float hg = 0.5f * g;
    return fmaf(hg, tanh_fast(t), hg);
}
__device__ __forceinline__ uint32_t geglu2(uint32_t g2, uint32_t u2) {
    return mul_bf16x2(pack_bf16(gelu_tanh(bf_lo(g2)), gelu_tanh(bf_hi(g2))), u2);
}
__device__ __forceinline__ float silu(float d) {
    float hd = 0.5f * d;
    return fmaf(hd, tanh_fast(hd), hd);
}
__device__ __forceinline__ float ex2_fast(float x) { float r; asm("ex2.approx.ftz.f32 %0, %1;" : "=f"(r) : "f"(x)); return r; }
__device__ __forceinline__ void unpack8(uint4 v, float (&f)[8]) {
    f[0] = bf_lo(v.x); f[1] = bf_hi(v.x); f[2] = bf_lo(v.y); f[3] = bf_hi(v.y);
    f[4] = bf_lo(v.z); f[5] = bf_hi(v.z); f[6] = bf_lo(v.w); f[7] = bf_hi(v.w);
}
template <int N> __device__ __forceinline__ void fence_regs(float (&d)[N]) {
#pragma unroll
    for (int i = 0; i < N; i++) asm volatile("" : "+f"(d[i]) :: "memory");
}

__device__ __forceinline__ float rcp_fast(float x) { float r; asm("rcp.approx.ftz.f32 %0, %1;" : "=f"(r) : "f"(x)); return r; }
__device__ __forceinline__ uint32_t max_bf16x2(uint32_t a, uint32_t b) {
    uint32_t r; asm("max.bf16x2 %0, %1, %2;" : "=r"(r) : "r"(a), "r"(b)); return r;
}
__device__ __forceinline__ uint4 ldsm4(uint32_t addr) {
    uint4 v;
    asm volatile("ldmatrix.sync.aligned.m8n8.x4.shared.b16 {%0,%1,%2,%3}, [%4];"
                 : "=r"(v.x), "=r"(v.y), "=r"(v.z), "=r"(v.w) : "r"(addr) : "memory");
    return v;
}
__device__ __forceinline__ uint4 ldsm4_t(uint32_t addr) {
    uint4 v;
    asm volatile("ldmatrix.sync.aligned.m8n8.x4.trans.shared.b16 {%0,%1,%2,%3}, [%4];"
                 : "=r"(v.x), "=r"(v.y), "=r"(v.z), "=r"(v.w) : "r"(addr) : "memory");
    return v;
}
__device__ __forceinline__ void mma_16816(float (&c)[4], uint32_t a0, uint32_t a1, uint32_t a2, uint32_t a3, uint32_t b0, uint32_t b1) {
    asm("mma.sync.aligned.m16n8k16.row.col.f32.bf16.bf16.f32 {%0,%1,%2,%3}, {%4,%5,%6,%7}, {%8,%9}, {%0,%1,%2,%3};"
        : "+f"(c[0]), "+f"(c[1]), "+f"(c[2]), "+f"(c[3]) : "r"(a0), "r"(a1), "r"(a2), "r"(a3), "r"(b0), "r"(b1));
}
__device__ __forceinline__ void mma_1688(float (&c)[4], uint32_t a0, uint32_t a1, uint32_t b0) {
    asm("mma.sync.aligned.m16n8k8.row.col.f32.bf16.bf16.f32 {%0,%1,%2,%3}, {%4,%5}, {%6}, {%0,%1,%2,%3};"
        : "+f"(c[0]), "+f"(c[1]), "+f"(c[2]), "+f"(c[3]) : "r"(a0), "r"(a1), "r"(b0));
}
__device__ __forceinline__ void qk_tile(float (&c)[4], const uint4& q0, const uint4& q1, const uint4& k, float init) {
    c[0] = c[1] = c[2] = c[3] = init;
    mma_16816(c, q0.x, q0.y, q0.z, q0.w, k.x, k.y);
    mma_16816(c, q1.x, q1.y, q1.z, q1.w, k.z, k.w);
}
__device__ __forceinline__ uint32_t scaled_logits(float lo, float hi) {
    const uint32_t p = pack_bf16(lo, hi);
    uint32_t r;
    asm("fma.rn.bf16x2 %0, %1, %2, %3;" : "=r"(r) : "r"(p), "r"(0x3e353e35u), "r"(mul_bf16x2(p, 0x379e379eu)));
    return r;
}

__device__ __forceinline__ void attention(const CUtensorMap* map, uint32_t base, int grp, int warp, int lane) {
    constexpr float LOG2E = 1.4426950408889634f;
    const int g = lane >> 2, t = lane & 3;
    const bool up0 = 2 * t > g, up1 = 2 * t + 1 > g;
    const uint32_t keep = (up0 ? 0x0000ffffu : 0u) | (up1 ? 0xffff0000u : 0u);
    const uint32_t buf = base + warp * ATT_SLOTS * ATT_BYTES, bar = base + 12 * ATT_SLOTS * ATT_BYTES + warp * 32;
    const uint32_t qoff = (lane & 15) * 128 + (((lane >> 4) ^ (lane & 7)) << 4);
    const uint32_t koff = 2048 + (lane & 7) * 128 + (((lane >> 3) ^ (lane & 7)) << 4);
    const int first = (warp * 128 + 2) / 3, last = (warp * 128 + 130) / 3;
    auto load = [&](int n, int slot) {
        mbar_expect_tx(bar + slot * 8, ATT_BYTES);
        tma_5d(buf + slot * ATT_BYTES, map, bar + slot * 8, (n & 63) * 16, (n >> 6) & 1, grp * 4 + (n >> 7));
    };
    const bool warm = (first & 63) != 0;
    if (lane == 0) {
        for (int s = 0; s < ATT_SLOTS; s++) mbar_init(bar + s * 8, 1);
        prefetch_map(map);
        const unsigned epoch = __ldcg(g_epoch + blockIdx.x * 16 + warp) + 1;
        flag_wait(g_flags + F_QKV * 512 + grp * 32, epoch * CNT_QKV);
        fence_proxy_async();
        load(first - warm, 0); load(first, 1); load(first + 1, 2);
        g_epoch[blockIdx.x * 16 + warp] = epoch;
        if (warp == 0) TRACE(9);
    }
    __syncwarp();
    uint4 kp[2], vp[2];
    mbar_wait(bar, 0);
#pragma unroll
    for (int h = 0; h < 2; h++) {
        kp[h] = ldsm4(buf + 1024 + (koff ^ (h * 64)));
        const uint4 v = ldsm4_t(buf + 3072 + (koff ^ (h * 64)));
        vp[h] = warm ? v : make_uint4(0, 0, 0, 0);
        kp[h].x = warm ? kp[h].x : 0;
    }
    int slot = 1; uint32_t ph = 0;
#pragma unroll 1
    for (int n = first; n < last; n++) {
        const uint32_t st = buf + slot * ATT_BYTES;
        mbar_wait(bar + slot * 8, ph);
        if (lane == 0 && n + 2 < last) load(n + 2, slot == 0 ? ATT_SLOTS - 1 : slot - 1);
        if (++slot == ATT_SLOTS) { slot = 0; ph ^= 1; }
        uint4 q[2][2], k[2][2], v[2][2];
#pragma unroll
        for (int h = 0; h < 2; h++) {
            q[h][0] = ldsm4(st + (qoff ^ (h * 64)));
            q[h][1] = ldsm4(st + (qoff ^ (h * 64 + 32)));
            k[h][0] = ldsm4(st + (koff ^ (h * 64)));
            k[h][1] = ldsm4(st + 1024 + (koff ^ (h * 64)));
        }
#pragma unroll
        for (int h = 0; h < 2; h++) {
            v[h][0] = ldsm4_t(st + 4096 + (qoff ^ (h * 64)));
            v[h][1] = ldsm4_t(st + 4096 + (qoff ^ (h * 64 + 32)));
        }
        const float before = (n & 63) == 0 ? -5.656854e9f : 0.f;
        __nv_bfloat16* op = g_a2 + (size_t)((n & 63) * 32 + g * 2 + ((n >> 6) & 1)) * K2 + (grp * 4 + (n >> 7)) * 64 + t * 8;
        uint32_t l0[2], l1[2], m[2];
#pragma unroll
        for (int h = 0; h < 2; h++) {
            float s0[4], s1[4], s2[4];
            qk_tile(s0, q[h][0], q[h][1], kp[h], before);
            qk_tile(s1, q[h][0], q[h][1], k[h][0], 0.f);
            qk_tile(s2, q[h][0], q[h][1], k[h][1], 0.f);
            l0[h] = scaled_logits(up0 ? s0[0] : s1[0], up0 ? s1[2] : s2[2]);
            l1[h] = scaled_logits(up1 ? s0[1] : s1[1], up1 ? s1[3] : s2[3]);
            m[h] = max_bf16x2(l0[h], l1[h]);
        }
#pragma unroll
        for (int h = 0; h < 2; h++) m[h] = max_bf16x2(m[h], __shfl_xor_sync(0xffffffffu, m[h], 1));
#pragma unroll
        for (int h = 0; h < 2; h++) m[h] = max_bf16x2(m[h], __shfl_xor_sync(0xffffffffu, m[h], 2));
#pragma unroll
        for (int h = 0; h < 2; h++) {
            const float ma = -LOG2E * bf_lo(m[h]), mb = -LOG2E * bf_hi(m[h]);
            const uint32_t pa = pack_bf16(ex2_fast(fmaf(bf_lo(l0[h]), LOG2E, ma)), ex2_fast(fmaf(bf_lo(l1[h]), LOG2E, ma)));
            const uint32_t pb = pack_bf16(ex2_fast(fmaf(bf_hi(l0[h]), LOG2E, mb)), ex2_fast(fmaf(bf_hi(l1[h]), LOG2E, mb)));
            float sum[4] = {0.f, 0.f, 0.f, 0.f}, o[4][4];
            mma_1688(sum, pa, pb, 0x3f803f80u);
            const uint32_t prev[4] = {vp[h].x, vp[h].y, vp[h].z, vp[h].w};
            const uint32_t own[8] = {v[h][0].x, v[h][0].y, v[h][0].z, v[h][0].w, v[h][1].x, v[h][1].y, v[h][1].z, v[h][1].w};
#pragma unroll
            for (int j = 0; j < 4; j++) {
                o[j][0] = o[j][1] = o[j][2] = o[j][3] = 0.f;
                mma_1688(o[j], pa & keep, 0u, prev[j]);
                mma_16816(o[j], pa & ~keep, pb & keep, 0u, pb & ~keep, own[2 * j], own[2 * j + 1]);
            }
            const float ra = rcp_fast(sum[0]), rb = rcp_fast(sum[2]);
            *reinterpret_cast<uint4*>(op + h * 32) =
                make_uint4(pack_bf16(o[0][0] * ra, o[0][1] * ra), pack_bf16(o[1][0] * ra, o[1][1] * ra),
                           pack_bf16(o[2][0] * ra, o[2][1] * ra), pack_bf16(o[3][0] * ra, o[3][1] * ra));
            *reinterpret_cast<uint4*>(op + h * 32 + 16 * K2) =
                make_uint4(pack_bf16(o[0][2] * rb, o[0][3] * rb), pack_bf16(o[1][2] * rb, o[1][3] * rb),
                           pack_bf16(o[2][2] * rb, o[2][3] * rb), pack_bf16(o[3][2] * rb, o[3][3] * rb));
            kp[h] = k[h][1];
            vp[h] = make_uint4(own[1], own[3], own[5], own[7]);
        }
    }
    __syncwarp();
    if (lane == 0) {
        flag_add(g_flags + F_O * 512);
        if (warp == 0) TRACE(10);
    }
}

__device__ __forceinline__ void warp_sum2(float& a, float& b) {
#pragma unroll
    for (int o = 16; o > 0; o >>= 1) {
        a += __shfl_xor_sync(0xffffffffu, a, o);
        b += __shfl_xor_sync(0xffffffffu, b, o);
    }
}
__device__ __forceinline__ float row_sum(const uint32_t* w) {
    float a = 0.f, b = 0.f;
#pragma unroll
    for (int i = 0; i < 16; i++) { a += bf_lo(w[i]); b += bf_hi(w[i]); }
    return a + b;
}
__device__ __forceinline__ float row_sq(const uint32_t* w, float mean) {
    float a = 0.f, b = 0.f;
#pragma unroll
    for (int i = 0; i < 16; i++) {
        const float lo = bf_lo(w[i]) - mean, hi = bf_hi(w[i]) - mean;
        a = fmaf(lo, lo, a); b = fmaf(hi, hi, b);
    }
    return a + b;
}
__device__ __forceinline__ float row_inv(float sq) {
    return 1.f / round_bf16(sqrtf(round_bf16(round_bf16(sq * (1.f / DM)) + 1e-5f)));
}
__device__ __forceinline__ void row_store(const uint32_t* w, float mean, float inv, int row, int lane) {
    const uint32_t m2 = pack_bf16(mean, mean);
    __nv_bfloat16* dst = g_xn + (size_t)row * DM + lane * 8;
#pragma unroll
    for (int i = 0; i < 4; i++) {
        uint32_t o[4];
#pragma unroll
        for (int j = 0; j < 4; j++) {
            const uint32_t c = sub_bf16x2(w[i * 4 + j], m2);
            o[j] = pack_bf16(bf_lo(c) * inv, bf_hi(c) * inv);
        }
        *reinterpret_cast<uint4*>(dst + i * 256) = make_uint4(o[0], o[1], o[2], o[3]);
    }
    if (lane == 0) g_stats[row] = make_float2(-bf_lo(m2), inv);
}

struct Params {
    CUtensorMap x, xn, wqkv, wg, wu, qkv, a2, wo, wd, out;
    const __nv_bfloat16 *px, *pwqkv, *pwg, *pwu;
};

__device__ __forceinline__ bool tile_is_qkv(int nt) { return nt < 4 || (nt >= 8 && nt < 16); }
__device__ __forceinline__ int tile_index(int nt) { return nt < 4 ? nt + 8 : (nt < 8 ? nt - 4 : (nt < 16 ? nt - 8 : nt - 12)); }

__global__ void __cluster_dims__(2, 1, 1) __launch_bounds__(384, 1)
fused_kernel(const __grid_constant__ Params prm) {
    extern __shared__ __align__(1024) uint8_t smem_raw[];
    const uint32_t base = (smem_u32(smem_raw) + 1023) & ~1023u;
    const uint32_t bars = base + BAR_OFF;
    auto full1 = [&](int s) { return bars + s * 8; };
    auto empty1 = [&](int s) { return bars + 32 + s * 8; };
    auto full2 = [&](int s) { return bars + 64 + s * 8; };
    auto empty2 = [&](int s) { return bars + 128 + s * 8; };
    const uint32_t sig_bar = bars + 192, fold_bar = bars + 200, x_bar = bars + 208, dep_bar = bars + 216;
    auto stage2 = [&](int q) { return base + q * G2_STAGE_BYTES; };
    const uint32_t aux = base + AUX_OFF;

    const int warp = __shfl_sync(0xffffffffu, threadIdx.x >> 5, 0);
    const int lane = threadIdx.x & 31;
    const int rank = blockIdx.x & 1;
    const int mblk = ((blockIdx.x >> 1) & 7) * 2 + rank;
    const int nslot = blockIdx.x >> 4;

    if (blockIdx.x >= NGEMM) {
        if (threadIdx.x == 0) { TRACE_GT(0); TRACE(1); }
        attention(&prm.qkv, base, blockIdx.x - NGEMM, warp, lane);
    } else if (warp >= 8) {
        unsigned* const flags = g_flags + mblk * 32;
        if (warp == 8) {
            if (lane == 0) {
                TRACE_GT(0); TRACE(1);
                prefetch_map(&prm.x); prefetch_map(nslot < 4 ? &prm.wqkv : (rank ? &prm.wu : &prm.wg));
                for (int s = 0; s < G1_STAGES; s++) { mbar_init(full1(s), 1); mbar_init(empty1(s), 4); }
                for (int s = 0; s < G2_STAGES; s++) { mbar_init(full2(s), 1); mbar_init(empty2(s), 4); }
                mbar_init(sig_bar, 8); mbar_init(fold_bar, 2); mbar_init(x_bar, 1);
                for (int s = 0; s < 4; s++) mbar_init(dep_bar + s * 8, 1);
                asm volatile("fence.mbarrier_init.release.cluster;" ::: "memory");
            }
            __syncwarp();
        }
        asm volatile("barrier.cluster.arrive.relaxed.aligned;" ::: "memory");
        if (warp == 8 && lane == 0) {
            asm volatile("fence.proxy.async.shared::cta;" ::: "memory");
            for (int s = 0; s < G1_STAGES; s++) {
                mbar_expect_tx(full1(s), G1_STAGE_BYTES);
                tma_2d(base + s * G1_STAGE_BYTES, &prm.x, full1(s), s * 64, mblk * 128);
            }
            TRACE(15);
        }
        asm volatile("setmaxnreg.dec.sync.aligned.u32 %0;" :: "n"(AUX_REGS));
        asm volatile("barrier.cluster.wait.acquire.aligned;" ::: "memory");

        if (warp == 8) {
            if (lane == 0) {
                TRACE(2);
                auto load_b1 = [&](int s, int nt, int k) {
                    const uint32_t dst = base + s * G1_STAGE_BYTES + A_BYTES + rank * 16384;
                    if (tile_is_qkv(nt)) tma_3d_mc(dst, &prm.wqkv, full1(s), k * 64, tile_index(nt) * 4 + rank * 2);
                    else tma_3d_mc(dst, rank ? &prm.wu : &prm.wg, full1(s), k * 64, tile_index(nt) * 2);
                };
                for (int s = 0; s < G1_STAGES; s++) load_b1(s, nslot, s);
                prefetch_map(&prm.xn); prefetch_map(&prm.wqkv); prefetch_map(rank ? &prm.wu : &prm.wg);
                prefetch_map(&prm.a2); prefetch_map(&prm.wo); prefetch_map(&prm.wd); prefetch_map(&prm.out);
                uint32_t ph = 0;
                for (int it = G1_STAGES; it < G1_TILES * G1_KSTEPS; it++) {
                    const int s = it & 3, k = it & 15;
                    if (it == G1_KSTEPS) { TRACE(14); mbar_wait(dep_bar, 0); TRACE(3); }
                    mbar_wait(empty1(s), ph);
                    mbar_expect_tx(full1(s), G1_STAGE_BYTES);
                    tma_2d(base + s * G1_STAGE_BYTES, it < G1_KSTEPS ? &prm.x : &prm.xn, full1(s), k * 64, mblk * 128);
                    load_b1(s, (it >> 4) * 8 + nslot, k);
                    if (s == 3) ph ^= 1;
                }
                mbar_expect_tx(x_bar, 32768);
                tma_2d(aux, &prm.x, x_bar, nslot * 128, mblk * 128);
                tma_2d(aux + 16384, &prm.x, x_bar, nslot * 128 + 64, mblk * 128);
                TRACE(4);
                mbar_wait(dep_bar + 8, 0);
                TRACE(5);
                int q = 0; uint32_t ph2 = 1;
                for (int u = 0; u < G2_KSTEPS; u++) {
                    if (u == G2_LATE || u == G2_DSTEPS) {
                        TRACE(u == G2_LATE ? 6 : 32);
                        mbar_wait(dep_bar + (u == G2_LATE ? 16 : 24), 0);
                        TRACE(u == G2_LATE ? 7 : 33);
                    }
                    if (u < G2_STAGES) {
                        if (u == 0) mbar_wait(empty1(0), ph);
                        if (u == 1) mbar_wait(empty1(1), ph);
                        if (u == 3) mbar_wait(empty1(2), ph);
                        if (u == 4) mbar_wait(empty1(3), ph);
                    } else {
                        mbar_wait(empty2(q), ph2);
                    }
                    const uint32_t sa = stage2(q);
                    const bool down = u < G2_DSTEPS;
                    const int k = down ? u : u - G2_DSTEPS;
                    mbar_expect_tx(full2(q), G2_STAGE_BYTES);
                    tma_2d(sa, &prm.a2, full2(q), (down ? DM : 0) + k * 64, mblk * 128);
                    tma_5d_mc(sa + A_BYTES + rank * 8192, down ? &prm.wd : &prm.wo, full2(q), nslot * 128 + rank * 64, k * 2);
                    if (++q == G2_STAGES) { q = 0; ph2 ^= 1; }
                }
                TRACE(8);
            }
        } else if (warp == 9) {
            if (lane == 0) {
                mbar_wait(sig_bar, 0);
                TRACE(11);
                flag_add(flags + F_LN * 512);
                for (int t = 0; t < G1_TILES; t++) {
                    mbar_wait(sig_bar, (t + 1) & 1);
                    const int nt = t * 8 + nslot;
                    flag_add(tile_is_qkv(nt) ? g_flags + F_QKV * 512 + (nt & 3) * 32
                                             : flags + (t < G1_TILES - 1 ? F_EARLY : F_LATE) * 512);
                }
            }
        } else {
            const int w = warp - 10;
            const int ld = nslot < 4 ? NQKV : DF;
            const __nv_bfloat16* wp = nslot < 4 ? prm.pwqkv + 2 * DM + nslot * 256 + lane * 8
                                                : (lane < 16 ? prm.pwg : prm.pwu) + (nslot - 4) * 128 + (lane & 15) * 8;
            wp += (size_t)(mblk * 64 + w * 32) * ld;
            const unsigned epoch = __ldcg(g_epoch + blockIdx.x * 16 + w) + 1;
            float cs[8];
#pragma unroll
            for (int d = 0; d < 8; d++) cs[d] = 0.f;
            mbar_wait(full1(0), 0);
#pragma unroll 1
            for (int i = 0; i < 4; i++) {
                uint4 v[8];
#pragma unroll
                for (int j = 0; j < 8; j++) v[j] = __ldg(reinterpret_cast<const uint4*>(wp + (size_t)(i * 8 + j) * ld));
#pragma unroll
                for (int j = 0; j < 8; j++) {
                    float f[8];
                    unpack8(v[j], f);
#pragma unroll
                    for (int d = 0; d < 8; d++) cs[d] += f[d];
                }
            }
            float4* cp = reinterpret_cast<float4*>(g_colsum + (mblk * 2 + w) * 2048 + nslot * 256 + lane * 8);
            cp[0] = make_float4(cs[0], cs[1], cs[2], cs[3]);
            cp[1] = make_float4(cs[4], cs[5], cs[6], cs[7]);
            __syncwarp();
            if (lane == 0) {
                if (w == 0) TRACE(34);
                flag_add(g_flags + F_CS * 512 + nslot * 32);
                flag_wait(g_flags + F_CS * 512 + nslot * 32, epoch * CNT_CS);
            }
            __syncwarp();
            const float4* gp = reinterpret_cast<const float4*>(g_colsum + nslot * 256 + w * 128) + lane;
            float4 c = make_float4(0.f, 0.f, 0.f, 0.f);
#pragma unroll 8
            for (int m = 0; m < 32; m++) {
                const float4 a = __ldcg(gp + m * 512);
                c.x += a.x; c.y += a.y; c.z += a.z; c.w += a.w;
            }
            const uint32_t ca = aux + (w * 8 + (lane >> 2)) * 64 + (lane & 1) * 32 + (lane & 2) * 4;
            sts64f(ca, c.x, c.y);
            sts64f(ca + 16, c.z, c.w);
            if (lane == 0) {
                flag_wait(flags + F_LN * 512, epoch * CNT_LN);
                if (w == 0) { fence_proxy_async(); mbar_arrive(dep_bar); }
            }
            __syncwarp();
            sts128(aux + 1024 + w * 512 + lane * 16, __ldcg(reinterpret_cast<const uint4*>(g_stats + mblk * 128 + w * 64) + lane));
            __syncwarp();
            if (lane == 0) {
                mbar_arrive(fold_bar);
                g_epoch[blockIdx.x * 16 + w] = epoch;
                if (w == 0) {
                    TRACE(35);
                    flag_wait(flags + F_EARLY * 512, epoch * CNT_EARLY);
                    fence_proxy_async(); mbar_arrive(dep_bar + 8);
                    flag_wait(flags + F_LATE * 512, epoch * CNT_LATE);
                    fence_proxy_async(); mbar_arrive(dep_bar + 16);
                    flag_wait(g_flags + F_O * 512, epoch * CNT_O);
                    fence_proxy_async(); mbar_arrive(dep_bar + 24);
                }
            }
        }
    } else {
        asm volatile("barrier.cluster.arrive.relaxed.aligned;" ::: "memory");
        asm volatile("setmaxnreg.inc.sync.aligned.u32 %0;" :: "n"(CONSUMER_REGS));
        const int wg = __shfl_sync(0xffffffffu, threadIdx.x >> 7, 0);
        const int cw = threadIdx.x >> 5;
        const int tid = threadIdx.x & 127;
        float acc[128];
        uint32_t pk[64];
#pragma unroll
        for (int i = 0; i < 64; i++) asm volatile("mov.b32 %0, 0;" : "=r"(pk[i]));
#pragma unroll
        for (int i = 0; i < 128; i++) asm volatile("mov.b32 %0, 0;" : "=f"(acc[i]));
        asm volatile("barrier.cluster.wait.acquire.aligned;" ::: "memory");

        const int orow = mblk * 128 + cw * 16 + (lane >> 2);
        __nv_bfloat16* optr = nullptr;
        auto release = [&](uint32_t bar) { if (tid < 2) mbar_arrive_cluster(bar, tid); };
        auto chunk_geglu = [&](int j) {
            const int c = j >> 1, h = j & 1;
            uint4 v;
            v.x = geglu2(pk[8 * c + h], pk[32 + 8 * c + h]);
            v.y = geglu2(pk[8 * c + 2 + h], pk[32 + 8 * c + 2 + h]);
            v.z = geglu2(pk[8 * c + 4 + h], pk[32 + 8 * c + 4 + h]);
            v.w = geglu2(pk[8 * c + 6 + h], pk[32 + 8 * c + 6 + h]);
            *reinterpret_cast<uint4*>(optr + h * 8 * K2 + c * 32) = v;
        };
        auto chunk_qkv = [&](int c) {
            *reinterpret_cast<uint4*>(optr + c * 32) = make_uint4(pk[8 * c], pk[8 * c + 2], pk[8 * c + 4], pk[8 * c + 6]);
            *reinterpret_cast<uint4*>(optr + 8 * NQKV + c * 32) = make_uint4(pk[8 * c + 1], pk[8 * c + 3], pk[8 * c + 5], pk[8 * c + 7]);
        };
        auto signal_stores = [&]() { __syncwarp(); if (lane == 0) mbar_arrive(sig_bar); };

        auto chunk_ln = [&](int k) {
            const int row = mblk * 128 + nslot * 16 + cw * 2;
            if (k == 0) {
                const uint4* xp = reinterpret_cast<const uint4*>(prm.px + (size_t)row * DM) + lane;
#pragma unroll
                for (int i = 0; i < 8; i++) {
                    const uint4 v = __ldg(xp + i * 32);
                    pk[4 * i] = v.x; pk[4 * i + 1] = v.y; pk[4 * i + 2] = v.z; pk[4 * i + 3] = v.w;
                }
            } else if (k == 3) {
                float a = row_sum(pk), b = row_sum(pk + 16);
                warp_sum2(a, b);
                pk[32] = __float_as_uint(a * (1.f / DM)); pk[33] = __float_as_uint(b * (1.f / DM));
            } else if (k == 4) {
                pk[34] = __float_as_uint(row_sq(pk, __uint_as_float(pk[32])));
            } else if (k == 5) {
                float a = __uint_as_float(pk[34]), b = row_sq(pk + 16, __uint_as_float(pk[33]));
                warp_sum2(a, b);
                pk[34] = __float_as_uint(a); pk[35] = __float_as_uint(b);
            } else if (k == 6) {
                row_store(pk, __uint_as_float(pk[32]), row_inv(__uint_as_float(pk[34])), row, lane);
            } else if (k == 7) {
                row_store(pk + 16, __uint_as_float(pk[33]), row_inv(__uint_as_float(pk[35])), row + 1, lane);
                signal_stores();
            }
        };

        int pending = 0;
#pragma unroll 1
        for (int t = 0; t < G1_TILES; t++) {
#pragma unroll
            for (int k = 0; k < G1_KSTEPS; k++) {
                const int s = k & 3;
                mbar_wait(full1(s), (k >> 2) & 1);
                if (t == 0 && k == 0 && threadIdx.x == 0) TRACE(12);
                if (wg == 1 && k == G1_KSTEPS - G1_SKEW) asm volatile("bar.sync 1, 256;" ::: "memory");
                const uint64_t da = desc_a(base + s * G1_STAGE_BYTES + wg * 8192);
                const uint64_t db = desc_b(base + s * G1_STAGE_BYTES + A_BYTES);
                wg_fence();
#pragma unroll
                for (int kk = 0; kk < 4; kk++) wgmma_n256(acc, da + kk * 2, db + kk * 128, (k | kk) != 0);
                wg_commit();
                if (wg == 0 && k == G1_KSTEPS - 1) asm volatile("bar.arrive 1, 256;" ::: "memory");
                if (k <= 7 && pending == 0) chunk_ln(k);
                if (k >= 1 && k <= 8) {
                    if (pending == 2) chunk_geglu(k - 1);
                    else if (pending == 1) chunk_qkv(k - 1);
                    if (k == 8 && pending) signal_stores();
                }
                wg_wait<1>();
                if (k > 0) release(empty1((k - 1) & 3));
            }
            if (t == 0) mbar_wait(fold_bar, 0);
            wg_wait<0>();
            fence_regs(acc);
            release(empty1(3));
            if (t == 0) {
                const uint32_t sp = aux + 1024 + (cw * 16 + (lane >> 2)) * 8;
                const float2 sa = lds64f(sp), sb = lds64f(sp + 64);
#pragma unroll
                for (int j = 0; j < 16; j++) {
                    const uint4 c = lds128(aux + j * 64 + (lane & 3) * 16);
                    const float c0 = __uint_as_float(c.x), c1 = __uint_as_float(c.y);
                    const float c2 = __uint_as_float(c.z), c3 = __uint_as_float(c.w);
                    const float* a = acc + 8 * j;
                    pk[4 * j] = pack_bf16(fmaf(sa.x, c0, a[0]) * sa.y, fmaf(sa.x, c1, a[1]) * sa.y);
                    pk[4 * j + 1] = pack_bf16(fmaf(sb.x, c0, a[2]) * sb.y, fmaf(sb.x, c1, a[3]) * sb.y);
                    pk[4 * j + 2] = pack_bf16(fmaf(sa.x, c2, a[4]) * sa.y, fmaf(sa.x, c3, a[5]) * sa.y);
                    pk[4 * j + 3] = pack_bf16(fmaf(sb.x, c2, a[6]) * sb.y, fmaf(sb.x, c3, a[7]) * sb.y);
                }
            } else {
#pragma unroll
                for (int i = 0; i < 64; i++) pk[i] = pack_bf16(acc[2 * i], acc[2 * i + 1]);
            }
            const int nt = t * 8 + nslot;
            pending = tile_is_qkv(nt) ? 1 : 2;
            optr = pending == 1 ? g_qkv + (size_t)orow * NQKV + tile_index(nt) * 256 + (lane & 3) * 8
                                : g_a2 + (size_t)orow * K2 + DM + tile_index(nt) * 128 + (lane & 3) * 8;
            if (tid == 0) TRACE(16 + wg * 8 + t);
        }

        float accd[64], accs[64];
#pragma unroll
        for (int i = 0; i < 64; i++) accd[i] = 0.f;
#pragma unroll
        for (int u = 0; u < 9; u++) {
            const int q = u % G2_STAGES;
            mbar_wait(full2(q), (u / G2_STAGES) & 1);
            const uint64_t da = desc_a(stage2(q) + wg * 8192), db = desc_b(stage2(q) + A_BYTES);
            wg_fence();
#pragma unroll
            for (int kk = 0; kk < 4; kk++) wgmma_n128(accd, da + kk * 2, db + kk * 128, (u | kk) != 0);
            wg_commit();
            if (u >= 1) { chunk_geglu(u - 1); if (u == 8) signal_stores(); }
            wg_wait<1>();
            if (u > 0) release(empty2((u - 1) % G2_STAGES));
        }
        {
            int q = 9 % G2_STAGES, qp = 8 % G2_STAGES; uint32_t ph = (9 / G2_STAGES) & 1;
#pragma unroll 1
            for (int u = 9; u < G2_DSTEPS; u++) {
                mbar_wait(full2(q), ph);
                const uint64_t da = desc_a(stage2(q) + wg * 8192), db = desc_b(stage2(q) + A_BYTES);
                wg_fence();
#pragma unroll
                for (int kk = 0; kk < 4; kk++) wgmma_n128(accd, da + kk * 2, db + kk * 128, 1);
                wg_commit();
                wg_wait<1>();
                release(empty2(qp));
                qp = q;
                if (++q == G2_STAGES) { q = 0; ph ^= 1; }
            }
        }
        if (tid == 0) TRACE(16 + wg * 8 + 5);
#pragma unroll
        for (int i = 0; i < 64; i++) accs[i] = 0.f;
        uint32_t gk[32], xr[32];
        const uint32_t xs = aux + cw * 2048;
        const uint32_t xrow = xs + ((lane & 7) + ((lane >> 3) & 1) * 8) * 128;
        auto xaddr = [&](int j) { return xrow + (j >> 2) * 16384 + (((((j & 3) * 2) + (lane >> 4)) ^ (lane & 7)) << 4); };
#pragma unroll
        for (int u = G2_DSTEPS; u < G2_KSTEPS; u++) {
            const int q = u % G2_STAGES, v = u - G2_DSTEPS;
            mbar_wait(full2(q), (u / G2_STAGES) & 1);
            if (G2_SKEW > 0 && wg == 1 && u == G2_KSTEPS - G2_SKEW) asm volatile("bar.sync 1, 256;" ::: "memory");
            const uint64_t da = desc_a(stage2(q) + wg * 8192), db = desc_b(stage2(q) + A_BYTES);
            wg_fence();
#pragma unroll
            for (int kk = 0; kk < 4; kk++) wgmma_n128(accs, da + kk * 2, db + kk * 128, (v | kk) != 0);
            wg_commit();
            if (G2_SKEW > 0 && wg == 0 && u == G2_KSTEPS - 1) asm volatile("bar.arrive 1, 256;" ::: "memory");
            if (v >= 1 && v <= 8) {
#pragma unroll
                for (int i = 4 * (v - 1); i < 4 * v; i++) {
                    const uint32_t d2 = pack_bf16(accd[2 * i], accd[2 * i + 1]);
                    gk[i] = pack_bf16(silu(bf_lo(d2)), silu(bf_hi(d2)));
                }
            }
            if (v == 9) mbar_wait(x_bar, 0);
            if (v >= 9 && v <= 12) {
#pragma unroll
                for (int j = 2 * (v - 9); j < 2 * (v - 8); j++)
                    asm volatile("ldmatrix.sync.aligned.m8n8.x4.shared.b16 {%0,%1,%2,%3}, [%4];"
                                 : "=r"(xr[4 * j]), "=r"(xr[4 * j + 1]), "=r"(xr[4 * j + 2]), "=r"(xr[4 * j + 3])
                                 : "r"(xaddr(j)) : "memory");
            }
            wg_wait<1>();
            if (v == 0) fence_regs(accd);
            if (u - 1 + G2_STAGES < G2_KSTEPS) release(empty2((u - 1) % G2_STAGES));
        }
        wg_wait<0>();
        fence_regs(accs);
        if (tid == 0) TRACE(16 + wg * 8 + 6);
#pragma unroll
        for (int j = 0; j < 8; j++) {
            uint32_t r[4];
#pragma unroll
            for (int i = 0; i < 4; i++) {
                const int e = j * 4 + i;
                r[i] = add_bf16x2(xr[e], mul_bf16x2(pack_bf16(accs[2 * e], accs[2 * e + 1]), gk[e]));
            }
            asm volatile("stmatrix.sync.aligned.m8n8.x4.shared.b16 [%0], {%1,%2,%3,%4};"
                         :: "r"(xaddr(j)), "r"(r[0]), "r"(r[1]), "r"(r[2]), "r"(r[3]) : "memory");
            if (j == 3 || j == 7) {
                asm volatile("fence.proxy.async.shared::cta;" ::: "memory");
                __syncwarp();
                if (lane == 0) {
                    tma_store_2d(&prm.out, xs + (j >> 2) * 16384, nslot * 128 + (j >> 2) * 64, mblk * 128 + cw * 16);
                    asm volatile("cp.async.bulk.commit_group;" ::: "memory");
                }
            }
        }
        if (lane == 0) asm volatile("cp.async.bulk.wait_group.read 0;" ::: "memory");
        if (tid == 0) { TRACE(16 + wg * 8 + 7); if (wg == 1) TRACE_GT(13); }
    }
}

typedef CUresult (*EncodeFn)(CUtensorMap*, CUtensorMapDataType, cuuint32_t, void*, const cuuint64_t*, const cuuint64_t*,
                             const cuuint32_t*, const cuuint32_t*, CUtensorMapInterleave, CUtensorMapSwizzle,
                             CUtensorMapL2promotion, CUtensorMapFloatOOBfill);

void encode(EncodeFn fn, CUtensorMap* m, const void* ptr, int rank, const cuuint64_t* dims, const cuuint64_t* strides,
            const cuuint32_t* box) {
    const cuuint32_t es[5] = {1, 1, 1, 1, 1};
    fn(m, CU_TENSOR_MAP_DATA_TYPE_BFLOAT16, rank, const_cast<void*>(ptr), dims, strides, box, es,
       CU_TENSOR_MAP_INTERLEAVE_NONE, CU_TENSOR_MAP_SWIZZLE_128B, CU_TENSOR_MAP_L2_PROMOTION_L2_128B,
       CU_TENSOR_MAP_FLOAT_OOB_FILL_NONE);
}
void encode_2d(EncodeFn fn, CUtensorMap* m, const void* ptr, int cols, int box_rows) {
    const cuuint64_t dims[2] = {(cuuint64_t)cols, SEQ}, strides[1] = {(cuuint64_t)cols * 2};
    const cuuint32_t box[2] = {64, (cuuint32_t)box_rows};
    encode(fn, m, ptr, 2, dims, strides, box);
}
void encode_w1(EncodeFn fn, CUtensorMap* m, const void* ptr, int cols) {
    const cuuint64_t dims[3] = {64, DM, (cuuint64_t)cols / 64}, strides[2] = {(cuuint64_t)cols * 2, 128};
    const cuuint32_t box[3] = {64, 64, 2};
    encode(fn, m, ptr, 3, dims, strides, box);
}
void encode_qkv(EncodeFn fn, CUtensorMap* m, const void* ptr) {
    const cuuint64_t dims[5] = {64, SEQ / 2, 3, 2, DM / 64}, strides[4] = {NQKV * 4, DM * 2, NQKV * 2, 128};
    const cuuint32_t box[5] = {64, 16, 3, 1, 1};
    encode(fn, m, ptr, 5, dims, strides, box);
}
void encode_w2(EncodeFn fn, CUtensorMap* m, const void* ptr, int rows, bool permuted) {
    const cuuint64_t rb = DM * 2;
    const cuuint64_t dims[5] = {DM, 2, 4, 4, (cuuint64_t)rows / 32};
    const cuuint64_t strides[4] = {rb, (permuted ? 8 : 2) * rb, (permuted ? 2 : 8) * rb, 32 * rb};
    const cuuint32_t box[5] = {64, 2, 4, 4, 2};
    encode(fn, m, ptr, 5, dims, strides, box);
}

}

extern "C" void kernel_launch(void* const* d_in, const int* in_sizes, int n_in, void* d_out, int out_size) {
    (void)in_sizes; (void)n_in; (void)out_size;
    static EncodeFn fn = nullptr;
    static void *p_xn = nullptr, *p_qkv = nullptr, *p_a2 = nullptr;
    if (!fn) {
        cudaDriverEntryPointQueryResult st;
        cudaGetDriverEntryPoint("cuTensorMapEncodeTiled", (void**)&fn, cudaEnableDefault, &st);
        cudaGetSymbolAddress(&p_xn, g_xn);
        cudaGetSymbolAddress(&p_qkv, g_qkv);
        cudaGetSymbolAddress(&p_a2, g_a2);
        cudaFuncSetAttribute(fused_kernel, cudaFuncAttributeMaxDynamicSharedMemorySize, SMEM_BYTES);
    }
    Params prm;
    encode_2d(fn, &prm.x, d_in[0], DM, 128);
    encode_2d(fn, &prm.xn, p_xn, DM, 128);
    encode_w1(fn, &prm.wqkv, d_in[1], NQKV);
    encode_w1(fn, &prm.wg, d_in[4], DF);
    encode_w1(fn, &prm.wu, d_in[5], DF);
    encode_qkv(fn, &prm.qkv, p_qkv);
    encode_2d(fn, &prm.a2, p_a2, K2, 128);
    encode_w2(fn, &prm.wo, d_in[2], DM, false);
    encode_w2(fn, &prm.wd, d_in[6], DF, true);
    encode_2d(fn, &prm.out, d_out, DM, 16);
    prm.px = (const __nv_bfloat16*)d_in[0];
    prm.pwqkv = (const __nv_bfloat16*)d_in[1];
    prm.pwg = (const __nv_bfloat16*)d_in[4];
    prm.pwu = (const __nv_bfloat16*)d_in[5];
    fused_kernel<<<NCTA, 384, SMEM_BYTES>>>(prm);
}
```

```cpp
#include <cuda_runtime.h>
#include <cuda_bf16.h>
#include <cuda.h>
#include <stdint.h>

namespace {

constexpr int SEQ = 2048, DM = 1024, DF = 3584, K2 = DM + DF, NQKV = 3 * DM;
constexpr int NGEMM = 128, NCTA = 132;
constexpr int G1_STAGES = 4, G1_STAGE_BYTES = 49152, G1_KSTEPS = 16, G1_TILES = 5;
constexpr int G2_STAGES = 6, G2_STAGE_BYTES = 32768, G2_KSTEPS = 72, G2_DSTEPS = 56, G2_LATE = 40;
constexpr int A_BYTES = 16384;
constexpr int AUX_OFF = G1_STAGES * G1_STAGE_BYTES;
constexpr int BAR_OFF = AUX_OFF + 32768;
constexpr int SMEM_BYTES = BAR_OFF + 1024 + 256;
constexpr int G1_SKEW = 2, G2_SKEW = 2;
constexpr int CONSUMER_REGS = 224, AUX_REGS = 56;
constexpr int ATT_SLOTS = 3, ATT_BYTES = 6144;

enum { F_LN = 0, F_QKV = 1, F_EARLY = 2, F_LATE = 3, F_O = 4, F_CS = 5 };
constexpr unsigned CNT_LN = 8, CNT_QKV = 48, CNT_EARLY = 20, CNT_LATE = 8, CNT_O = 48, CNT_CS = 32;

__device__ __align__(1024) __nv_bfloat16 g_xn[SEQ * DM];
__device__ __align__(1024) __nv_bfloat16 g_qkv[SEQ * NQKV];
__device__ __align__(1024) __nv_bfloat16 g_a2[SEQ * K2];
__device__ __align__(128) float2 g_stats[SEQ];
__device__ __align__(128) float g_colsum[32 * 2048];
__device__ __align__(128) unsigned g_flags[6 * 16 * 32];
__device__ __align__(128) unsigned g_epoch[NCTA * 16];

#define TRACE(slot) do {} while (0)
#define TRACE_GT(slot) do {} while (0)

__device__ __forceinline__ uint32_t smem_u32(const void* p) { return (uint32_t)__cvta_generic_to_shared(p); }
__device__ __forceinline__ void mbar_init(uint32_t bar, uint32_t cnt) {
    asm volatile("mbarrier.init.shared::cta.b64 [%0], %1;" :: "r"(bar), "r"(cnt) : "memory");
}
__device__ __forceinline__ void mbar_expect_tx(uint32_t bar, uint32_t bytes) {
    asm volatile("mbarrier.arrive.expect_tx.shared::cta.b64 _, [%0], %1;" :: "r"(bar), "r"(bytes) : "memory");
}
__device__ __forceinline__ void mbar_arrive(uint32_t bar) {
    asm volatile("mbarrier.arrive.shared::cta.b64 _, [%0];" :: "r"(bar) : "memory");
}
__device__ __forceinline__ void mbar_arrive_cluster(uint32_t bar, uint32_t cta) {
    asm volatile("{\n.reg .b32 ra;\nmapa.shared::cluster.u32 ra, %0, %1;\nmbarrier.arrive.shared::cluster.b64 _, [ra];\n}"
                 :: "r"(bar), "r"(cta) : "memory");
}
__device__ __forceinline__ bool mbar_try_wait(uint32_t bar, uint32_t parity) {
    uint32_t ok;
    asm volatile("{\n.reg .pred p;\nmbarrier.try_wait.parity.shared::cta.b64 p, [%1], %2;\nselp.u32 %0, 1, 0, p;\n}"
                 : "=r"(ok) : "r"(bar), "r"(parity) : "memory");
    return ok;
}
__device__ __forceinline__ void mbar_wait(uint32_t bar, uint32_t parity) {
    int spins = 0;
    while (!mbar_try_wait(bar, parity)) { if (++spins > (1 << 17)) break; }
}
__device__ __forceinline__ void flag_wait(const unsigned* p, unsigned target) {
    for (int spins = 0; spins < (1 << 19); spins++) {
        unsigned v;
        asm volatile("ld.acquire.gpu.global.u32 %0, [%1];" : "=r"(v) : "l"(p) : "memory");
        if ((int)(v - target) >= 0) break;
        __nanosleep(64);
    }
}
__device__ __forceinline__ void flag_add(unsigned* p) {
    asm volatile("red.release.gpu.global.add.u32 [%0], 1;" :: "l"(p) : "memory");
}
__device__ __forceinline__ bool elect_one() {
    uint32_t ok;
    asm volatile("{\n.reg .pred p;\nelect.sync _|p, 0xffffffff;\nselp.u32 %0, 1, 0, p;\n}" : "=r"(ok));
    return ok;
}
__device__ __forceinline__ void fence_proxy_async() { asm volatile("fence.proxy.async;" ::: "memory"); }
__device__ __forceinline__ uint4 lds128(uint32_t addr) {
    uint4 v;
    asm volatile("ld.shared.v4.u32 {%0,%1,%2,%3}, [%4];" : "=r"(v.x), "=r"(v.y), "=r"(v.z), "=r"(v.w) : "r"(addr) : "memory");
    return v;
}
__device__ __forceinline__ float2 lds64f(uint32_t addr) {
    float2 v;
    asm volatile("ld.shared.v2.f32 {%0,%1}, [%2];" : "=f"(v.x), "=f"(v.y) : "r"(addr) : "memory");
    return v;
}
__device__ __forceinline__ void sts128(uint32_t addr, uint4 v) {
    asm volatile("st.shared.v4.u32 [%0], {%1,%2,%3,%4};" :: "r"(addr), "r"(v.x), "r"(v.y), "r"(v.z), "r"(v.w) : "memory");
}
__device__ __forceinline__ void sts64f(uint32_t addr, float a, float b) {
    asm volatile("st.shared.v2.f32 [%0], {%1,%2};" :: "r"(addr), "f"(a), "f"(b) : "memory");
}

__device__ __forceinline__ void tma_2d(uint32_t dst, const CUtensorMap* m, uint32_t bar, int c0, int c1) {
    asm volatile("cp.async.bulk.tensor.2d.shared::cluster.global.mbarrier::complete_tx::bytes [%0], [%1, {%3, %4}], [%2];"
                 :: "r"(dst), "l"(m), "r"(bar), "r"(c0), "r"(c1) : "memory");
}
__device__ __forceinline__ void tma_5d(uint32_t dst, const CUtensorMap* m, uint32_t bar, int c1, int c2, int c3, int c4) {
    asm volatile("cp.async.bulk.tensor.5d.shared::cluster.global.mbarrier::complete_tx::bytes [%0], [%1, {%3, %4, %5, %6, %7}], [%2];"
                 :: "r"(dst), "l"(m), "r"(bar), "r"(0), "r"(c1), "r"(c2), "r"(c3), "r"(c4) : "memory");
}
__device__ __forceinline__ void tma_store_4d(const CUtensorMap* m, uint32_t src, int c1, int c2, int c3) {
    asm volatile("cp.async.bulk.tensor.4d.global.shared::cta.bulk_group [%0, {%2, %3, %4, %5}], [%1];"
                 :: "l"(m), "r"(src), "r"(0), "r"(c1), "r"(c2), "r"(c3) : "memory");
}
__device__ __forceinline__ void tma_3d_mc(uint32_t dst, const CUtensorMap* m, uint32_t bar, int c1, int c2) {
    asm volatile("cp.async.bulk.tensor.3d.shared::cluster.global.mbarrier::complete_tx::bytes.multicast::cluster"
                 " [%0], [%1, {%3, %4, %5}], [%2], %6;"
                 :: "r"(dst), "l"(m), "r"(bar), "r"(0), "r"(c1), "r"(c2), "h"((uint16_t)3) : "memory");
}
__device__ __forceinline__ void tma_5d_mc(uint32_t dst, const CUtensorMap* m, uint32_t bar, int c0, int c4) {
    asm volatile("cp.async.bulk.tensor.5d.shared::cluster.global.mbarrier::complete_tx::bytes.multicast::cluster"
                 " [%0], [%1, {%3, %4, %4, %4, %5}], [%2], %6;"
                 :: "r"(dst), "l"(m), "r"(bar), "r"(c0), "r"(0), "r"(c4), "h"((uint16_t)3) : "memory");
}
__device__ __forceinline__ void tma_store_2d(const CUtensorMap* m, uint32_t src, int c0, int c1) {
    asm volatile("cp.async.bulk.tensor.2d.global.shared::cta.bulk_group [%0, {%2, %3}], [%1];"
                 :: "l"(m), "r"(src), "r"(c0), "r"(c1) : "memory");
}
__device__ __forceinline__ void prefetch_map(const CUtensorMap* m) {
    asm volatile("prefetch.tensormap [%0];" :: "l"(m) : "memory");
}
__device__ __forceinline__ void wg_fence() { asm volatile("wgmma.fence.sync.aligned;" ::: "memory"); }
__device__ __forceinline__ void wg_commit() { asm volatile("wgmma.commit_group.sync.aligned;" ::: "memory"); }
template <int N> __device__ __forceinline__ void wg_wait() { asm volatile("wgmma.wait_group.sync.aligned %0;" :: "n"(N) : "memory"); }

__device__ __forceinline__ uint64_t desc_a(uint32_t addr) {
    return (uint64_t)((addr & 0x3FFFF) >> 4) | (1ull << 16) | (64ull << 32) | (1ull << 62);
}
__device__ __forceinline__ uint64_t desc_b(uint32_t addr) {
    return (uint64_t)((addr & 0x3FFFF) >> 4) | (512ull << 16) | (64ull << 32) | (1ull << 62);
}

#define R8(d, o) "+f"(d[o]), "+f"(d[o+1]), "+f"(d[o+2]), "+f"(d[o+3]), "+f"(d[o+4]), "+f"(d[o+5]), "+f"(d[o+6]), "+f"(d[o+7])
#define R32(d, o) R8(d, o), R8(d, o+8), R8(d, o+16), R8(d, o+24)
#define R64(d, o) R32(d, o), R32(d, o+32)

__device__ __forceinline__ void wgmma_n256(float (&d)[128], uint64_t da, uint64_t db, int scale_d) {
    asm volatile("{\n.reg .pred p;\nsetp.ne.b32 p, %130, 0;\n"
        "wgmma.mma_async.sync.aligned.m64n256k16.f32.bf16.bf16 "
        "{%0,%1,%2,%3,%4,%5,%6,%7,%8,%9,%10,%11,%12,%13,%14,%15,%16,%17,%18,%19,%20,%21,%22,%23,%24,%25,%26,%27,%28,%29,%30,%31,"
        "%32,%33,%34,%35,%36,%37,%38,%39,%40,%41,%42,%43,%44,%45,%46,%47,%48,%49,%50,%51,%52,%53,%54,%55,%56,%57,%58,%59,%60,%61,%62,%63,"
        "%64,%65,%66,%67,%68,%69,%70,%71,%72,%73,%74,%75,%76,%77,%78,%79,%80,%81,%82,%83,%84,%85,%86,%87,%88,%89,%90,%91,%92,%93,%94,%95,"
        "%96,%97,%98,%99,%100,%101,%102,%103,%104,%105,%106,%107,%108,%109,%110,%111,%112,%113,%114,%115,%116,%117,%118,%119,%120,%121,%122,%123,%124,%125,%126,%127},"
        " %128, %129, p, 1, 1, 0, 1;\n}"
        : R64(d, 0), R64(d, 64) : "l"(da), "l"(db), "r"(scale_d));
}
__device__ __forceinline__ void wgmma_n128(float (&d)[64], uint64_t da, uint64_t db, int scale_d) {
    asm volatile("{\n.reg .pred p;\nsetp.ne.b32 p, %66, 0;\n"
        "wgmma.mma_async.sync.aligned.m64n128k16.f32.bf16.bf16 "
        "{%0,%1,%2,%3,%4,%5,%6,%7,%8,%9,%10,%11,%12,%13,%14,%15,%16,%17,%18,%19,%20,%21,%22,%23,%24,%25,%26,%27,%28,%29,%30,%31,"
        "%32,%33,%34,%35,%36,%37,%38,%39,%40,%41,%42,%43,%44,%45,%46,%47,%48,%49,%50,%51,%52,%53,%54,%55,%56,%57,%58,%59,%60,%61,%62,%63},"
        " %64, %65, p, 1, 1, 0, 1;\n}"
        : R64(d, 0) : "l"(da), "l"(db), "r"(scale_d));
}

__device__ __forceinline__ uint32_t pack_bf16(float lo, float hi) {
    uint32_t r; asm("cvt.rn.bf16x2.f32 %0, %1, %2;" : "=r"(r) : "f"(hi), "f"(lo)); return r;
}
__device__ __forceinline__ float bf_lo(uint32_t v) { return __uint_as_float(v << 16); }
__device__ __forceinline__ float bf_hi(uint32_t v) { return __uint_as_float(v & 0xffff0000u); }
__device__ __forceinline__ float round_bf16(float v) { return bf_lo(pack_bf16(v, 0.f)); }
__device__ __forceinline__ uint32_t mul_bf16x2(uint32_t a, uint32_t b) {
    uint32_t r; asm("mul.rn.bf16x2 %0, %1, %2;" : "=r"(r) : "r"(a), "r"(b)); return r;
}
__device__ __forceinline__ uint32_t add_bf16x2(uint32_t a, uint32_t b) {
    uint32_t r; asm("add.rn.bf16x2 %0, %1, %2;" : "=r"(r) : "r"(a), "r"(b)); return r;
}
__device__ __forceinline__ uint32_t sub_bf16x2(uint32_t a, uint32_t b) {
    uint32_t r; asm("sub.rn.bf16x2 %0, %1, %2;" : "=r"(r) : "r"(a), "r"(b)); return r;
}
__device__ __forceinline__ float tanh_fast(float x) { float r; asm("tanh.approx.f32 %0, %1;" : "=f"(r) : "f"(x)); return r; }
__device__ __forceinline__ float gelu_tanh(float g) {
    float t = fmaf(g * g, 0.044715f * 0.7978845608f, 0.7978845608f) * g;
    float hg = 0.5f * g;
    return fmaf(hg, tanh_fast(t), hg);
}
__device__ __forceinline__ uint32_t geglu2(uint32_t g2, uint32_t u2) {
    return mul_bf16x2(pack_bf16(gelu_tanh(bf_lo(g2)), gelu_tanh(bf_hi(g2))), u2);
}
__device__ __forceinline__ float silu(float d) {
    float hd = 0.5f * d;
    return fmaf(hd, tanh_fast(hd), hd);
}
__device__ __forceinline__ float ex2_fast(float x) { float r; asm("ex2.approx.ftz.f32 %0, %1;" : "=f"(r) : "f"(x)); return r; }
__device__ __forceinline__ void unpack8(uint4 v, float (&f)[8]) {
    f[0] = bf_lo(v.x); f[1] = bf_hi(v.x); f[2] = bf_lo(v.y); f[3] = bf_hi(v.y);
    f[4] = bf_lo(v.z); f[5] = bf_hi(v.z); f[6] = bf_lo(v.w); f[7] = bf_hi(v.w);
}
template <int N> __device__ __forceinline__ void fence_regs(float (&d)[N]) {
#pragma unroll
    for (int i = 0; i < N; i++) asm volatile("" : "+f"(d[i]) :: "memory");
}

__device__ __forceinline__ float rcp_fast(float x) { float r; asm("rcp.approx.ftz.f32 %0, %1;" : "=f"(r) : "f"(x)); return r; }
__device__ __forceinline__ uint32_t max_bf16x2(uint32_t a, uint32_t b) {
    uint32_t r; asm("max.bf16x2 %0, %1, %2;" : "=r"(r) : "r"(a), "r"(b)); return r;
}
__device__ __forceinline__ uint4 ldsm4(uint32_t addr) {
    uint4 v;
    asm volatile("ldmatrix.sync.aligned.m8n8.x4.shared.b16 {%0,%1,%2,%3}, [%4];"
                 : "=r"(v.x), "=r"(v.y), "=r"(v.z), "=r"(v.w) : "r"(addr) : "memory");
    return v;
}
__device__ __forceinline__ uint4 ldsm4_t(uint32_t addr) {
    uint4 v;
    asm volatile("ldmatrix.sync.aligned.m8n8.x4.trans.shared.b16 {%0,%1,%2,%3}, [%4];"
                 : "=r"(v.x), "=r"(v.y), "=r"(v.z), "=r"(v.w) : "r"(addr) : "memory");
    return v;
}
__device__ __forceinline__ void mma_16816(float (&c)[4], uint32_t a0, uint32_t a1, uint32_t a2, uint32_t a3, uint32_t b0, uint32_t b1) {
    asm("mma.sync.aligned.m16n8k16.row.col.f32.bf16.bf16.f32 {%0,%1,%2,%3}, {%4,%5,%6,%7}, {%8,%9}, {%0,%1,%2,%3};"
        : "+f"(c[0]), "+f"(c[1]), "+f"(c[2]), "+f"(c[3]) : "r"(a0), "r"(a1), "r"(a2), "r"(a3), "r"(b0), "r"(b1));
}
__device__ __forceinline__ void mma_1688(float (&c)[4], uint32_t a0, uint32_t a1, uint32_t b0) {
    asm("mma.sync.aligned.m16n8k8.row.col.f32.bf16.bf16.f32 {%0,%1,%2,%3}, {%4,%5}, {%6}, {%0,%1,%2,%3};"
        : "+f"(c[0]), "+f"(c[1]), "+f"(c[2]), "+f"(c[3]) : "r"(a0), "r"(a1), "r"(b0));
}
__device__ __forceinline__ void qk_tile(float (&c)[4], const uint4& q0, const uint4& q1, const uint4& k, float init) {
    c[0] = c[1] = c[2] = c[3] = init;
    mma_16816(c, q0.x, q0.y, q0.z, q0.w, k.x, k.y);
    mma_16816(c, q1.x, q1.y, q1.z, q1.w, k.z, k.w);
}
__device__ __forceinline__ uint32_t scaled_logits(float lo, float hi) {
    const uint32_t p = pack_bf16(lo, hi);
    uint32_t r;
    asm("fma.rn.bf16x2 %0, %1, %2, %3;" : "=r"(r) : "r"(p), "r"(0x3e353e35u), "r"(mul_bf16x2(p, 0x379e379eu)));
    return r;
}

__device__ __forceinline__ void attention(const CUtensorMap* mqk, const CUtensorMap* mv, const CUtensorMap* mo,
                                          uint32_t base, int grp, int warp, int lane) {
    constexpr float LOG2E = 1.4426950408889634f;
    const int g = lane >> 2, t = lane & 3;
    const bool up0 = 2 * t > g, up1 = 2 * t + 1 > g;
    const uint32_t keep = (up0 ? 0x0000ffffu : 0u) | (up1 ? 0xffff0000u : 0u);
    const uint32_t buf = base + warp * ATT_SLOTS * ATT_BYTES, bar = base + 12 * ATT_SLOTS * ATT_BYTES + warp * 32;
    const uint32_t qoff = (lane & 15) * 128 + (((lane >> 4) ^ (lane & 7)) << 4);
    const uint32_t koff = 2048 + (lane & 7) * 128 + (((lane >> 3) ^ (lane & 7)) << 4);
    const int first = (warp * 128 + 2) / 3, last = (warp * 128 + 130) / 3;
    auto load = [&](int nqk, int nv, int slot) {
        const uint32_t dst = buf + slot * ATT_BYTES, b = bar + slot * 8;
        mbar_expect_tx(b, ATT_BYTES);
        tma_5d(dst, mqk, b, (nqk & 63) * 16, 0, (nqk >> 6) & 1, grp * 4 + (nqk >> 7));
        tma_5d(dst + 4096, mv, b, (nv & 63) * 16, 2, (nv >> 6) & 1, grp * 4 + (nv >> 7));
    };
    auto fence_slot = [&]() { asm volatile("fence.proxy.async.shared::cta;" ::: "memory"); __syncwarp(); };
    uint4 kp[2], vp[2];
    uint32_t l0[2], l1[2];
    auto logits = [&](uint32_t st, int n) {
        const float before = (n & 63) == 0 ? -5.656854e9f : 0.f;
#pragma unroll
        for (int h = 0; h < 2; h++) {
            const uint4 q0 = ldsm4(st + (qoff ^ (h * 64))), q1 = ldsm4(st + (qoff ^ (h * 64 + 32)));
            const uint4 k0 = ldsm4(st + (koff ^ (h * 64))), k1 = ldsm4(st + 1024 + (koff ^ (h * 64)));
            float s0[4], s1[4], s2[4];
            qk_tile(s0, q0, q1, kp[h], before);
            qk_tile(s1, q0, q1, k0, 0.f);
            qk_tile(s2, q0, q1, k1, 0.f);
            l0[h] = scaled_logits(up0 ? s0[0] : s1[0], up0 ? s1[2] : s2[2]);
            l1[h] = scaled_logits(up1 ? s0[1] : s1[1], up1 ? s1[3] : s2[3]);
            kp[h] = k1;
        }
    };
    if (elect_one()) {
        for (int s = 0; s < ATT_SLOTS; s++) mbar_init(bar + s * 8, 1);
        prefetch_map(mqk); prefetch_map(mv); prefetch_map(mo);
        const unsigned epoch = __ldcg(g_epoch + blockIdx.x * 16 + warp) + 1;
        flag_wait(g_flags + F_QKV * 512 + grp * 32, epoch * CNT_QKV);
        fence_proxy_async();
        const int before = first - ((first & 63) != 0);
        load(before, before, 0); load(first, before, 1); load(first + 1, first, 2);
        g_epoch[blockIdx.x * 16 + warp] = epoch;
        if (warp == 0) TRACE(9);
    }
    __syncwarp();
    mbar_wait(bar, 0);
#pragma unroll
    for (int h = 0; h < 2; h++) {
        kp[h] = ldsm4(buf + 1024 + (koff ^ (h * 64)));
        vp[h] = ldsm4_t(buf + 3072 + (koff ^ (h * 64)));
    }
    fence_slot();
    if (elect_one()) load(first + 2, first + 1, 0);
    mbar_wait(bar + 8, 0);
    logits(buf + ATT_BYTES, first);
    fence_slot();
    int slot = 2; uint32_t ph = 0;
#pragma unroll 1
    for (int n = first; n < last; n++) {
        const uint32_t st = buf + slot * ATT_BYTES;
        uint32_t m[2];
#pragma unroll
        for (int h = 0; h < 2; h++) m[h] = max_bf16x2(l0[h], l1[h]);
#pragma unroll
        for (int h = 0; h < 2; h++) m[h] = max_bf16x2(m[h], __shfl_xor_sync(0xffffffffu, m[h], 1));
        mbar_wait(bar + slot * 8, ph);
#pragma unroll
        for (int h = 0; h < 2; h++) m[h] = max_bf16x2(m[h], __shfl_xor_sync(0xffffffffu, m[h], 2));
        uint4 v[2][2];
        uint32_t pa[2], pb[2];
#pragma unroll
        for (int h = 0; h < 2; h++) {
            v[h][0] = ldsm4_t(st + 4096 + (qoff ^ (h * 64)));
            v[h][1] = ldsm4_t(st + 4096 + (qoff ^ (h * 64 + 32)));
            const float ma = -LOG2E * bf_lo(m[h]), mb = -LOG2E * bf_hi(m[h]);
            pa[h] = pack_bf16(ex2_fast(fmaf(bf_lo(l0[h]), LOG2E, ma)), ex2_fast(fmaf(bf_lo(l1[h]), LOG2E, ma)));
            pb[h] = pack_bf16(ex2_fast(fmaf(bf_hi(l0[h]), LOG2E, mb)), ex2_fast(fmaf(bf_hi(l1[h]), LOG2E, mb)));
        }
        logits(st, n + 1);
        if (n + 2 < last && elect_one()) {
            asm volatile("cp.async.bulk.wait_group.read 0;" ::: "memory");
            load(n + 3, n + 2, slot == 0 ? ATT_SLOTS - 1 : slot - 1);
        }
#pragma unroll
        for (int h = 0; h < 2; h++) {
            float sum[4] = {0.f, 0.f, 0.f, 0.f}, o[4][4];
            mma_1688(sum, pa[h], pb[h], 0x3f803f80u);
            const uint32_t prev[4] = {vp[h].x, vp[h].y, vp[h].z, vp[h].w};
            const uint32_t own[8] = {v[h][0].x, v[h][0].y, v[h][0].z, v[h][0].w, v[h][1].x, v[h][1].y, v[h][1].z, v[h][1].w};
#pragma unroll
            for (int j = 0; j < 4; j++) {
                o[j][0] = o[j][1] = o[j][2] = o[j][3] = 0.f;
                mma_1688(o[j], pa[h] & keep, 0u, prev[j]);
                mma_16816(o[j], pa[h] & ~keep, pb[h] & keep, 0u, pb[h] & ~keep, own[2 * j], own[2 * j + 1]);
            }
            const float ra = rcp_fast(sum[0]), rb = rcp_fast(sum[2]);
#pragma unroll
            for (int d = 0; d < 2; d++)
                asm volatile("stmatrix.sync.aligned.m8n8.x4.shared.b16 [%0], {%1,%2,%3,%4};"
                             :: "r"(st + 4096 + (qoff ^ (h * 64 + d * 32))),
                                "r"(pack_bf16(o[2 * d][0] * ra, o[2 * d][1] * ra)), "r"(pack_bf16(o[2 * d][2] * rb, o[2 * d][3] * rb)),
                                "r"(pack_bf16(o[2 * d + 1][0] * ra, o[2 * d + 1][1] * ra)),
                                "r"(pack_bf16(o[2 * d + 1][2] * rb, o[2 * d + 1][3] * rb)) : "memory");
            vp[h] = make_uint4(own[1], own[3], own[5], own[7]);
        }
        fence_slot();
        if (elect_one()) {
            tma_store_4d(mo, st + 4096, (n & 63) * 16, (n >> 6) & 1, grp * 4 + (n >> 7));
            asm volatile("cp.async.bulk.commit_group;" ::: "memory");
        }
        if (++slot == ATT_SLOTS) { slot = 0; ph ^= 1; }
    }
    if (elect_one()) {
        asm volatile("cp.async.bulk.wait_group 0;" ::: "memory");
        fence_proxy_async();
        flag_add(g_flags + F_O * 512);
        if (warp == 0) TRACE(10);
    }
}

__device__ __forceinline__ void warp_sum2(float& a, float& b) {
#pragma unroll
    for (int o = 16; o > 0; o >>= 1) {
        a += __shfl_xor_sync(0xffffffffu, a, o);
        b += __shfl_xor_sync(0xffffffffu, b, o);
    }
}
__device__ __forceinline__ float row_sum(const uint32_t* w) {
    float a = 0.f, b = 0.f;
#pragma unroll
    for (int i = 0; i < 16; i++) { a += bf_lo(w[i]); b += bf_hi(w[i]); }
    return a + b;
}
__device__ __forceinline__ float row_sq(const uint32_t* w, float mean) {
    float a = 0.f, b = 0.f;
#pragma unroll
    for (int i = 0; i < 16; i++) {
        const float lo = bf_lo(w[i]) - mean, hi = bf_hi(w[i]) - mean;
        a = fmaf(lo, lo, a); b = fmaf(hi, hi, b);
    }
    return a + b;
}
__device__ __forceinline__ float row_inv(float sq) {
    return 1.f / round_bf16(sqrtf(round_bf16(round_bf16(sq * (1.f / DM)) + 1e-5f)));
}
__device__ __forceinline__ void row_store(const uint32_t* w, float mean, float inv, int row, int lane) {
    const uint32_t m2 = pack_bf16(mean, mean);
    __nv_bfloat16* dst = g_xn + (size_t)row * DM + lane * 8;
#pragma unroll
    for (int i = 0; i < 4; i++) {
        uint32_t o[4];
#pragma unroll
        for (int j = 0; j < 4; j++) {
            const uint32_t c = sub_bf16x2(w[i * 4 + j], m2);
            o[j] = pack_bf16(bf_lo(c) * inv, bf_hi(c) * inv);
        }
        *reinterpret_cast<uint4*>(dst + i * 256) = make_uint4(o[0], o[1], o[2], o[3]);
    }
    if (lane == 0) g_stats[row] = make_float2(-bf_lo(m2), inv);
}

struct Params {
    CUtensorMap x, xn, wqkv, wg, wu, qk, v, o, a2, wo, wd, out;
    const __nv_bfloat16 *px, *pwqkv, *pwg, *pwu;
};

__device__ __forceinline__ bool tile_is_qkv(int nt) { return nt < 4 || (nt >= 8 && nt < 16); }
__device__ __forceinline__ int tile_index(int nt) { return nt < 4 ? nt + 8 : (nt < 8 ? nt - 4 : (nt < 16 ? nt - 8 : nt - 12)); }

__global__ void __cluster_dims__(2, 1, 1) __launch_bounds__(384, 1)
fused_kernel(const __grid_constant__ Params prm) {
    extern __shared__ __align__(1024) uint8_t smem_raw[];
    const uint32_t base = (smem_u32(smem_raw) + 1023) & ~1023u;
    const uint32_t bars = base + BAR_OFF;
    auto full1 = [&](int s) { return bars + s * 8; };
    auto empty1 = [&](int s) { return bars + 32 + s * 8; };
    auto full2 = [&](int s) { return bars + 64 + s * 8; };
    auto empty2 = [&](int s) { return bars + 128 + s * 8; };
    const uint32_t sig_bar = bars + 192, fold_bar = bars + 200, x_bar = bars + 208, dep_bar = bars + 216;
    auto stage2 = [&](int q) { return base + q * G2_STAGE_BYTES; };
    const uint32_t aux = base + AUX_OFF;

    const int warp = __shfl_sync(0xffffffffu, threadIdx.x >> 5, 0);
    const int lane = threadIdx.x & 31;
    const int rank = blockIdx.x & 1;
    const int mblk = ((blockIdx.x >> 1) & 7) * 2 + rank;
    const int nslot = blockIdx.x >> 4;

    if (blockIdx.x >= NGEMM) {
        if (threadIdx.x == 0) { TRACE_GT(0); TRACE(1); }
        attention(&prm.qk, &prm.v, &prm.o, base, blockIdx.x - NGEMM, warp, lane);
    } else if (warp >= 8) {
        unsigned* const flags = g_flags + mblk * 32;
        if (warp == 8) {
            if (lane == 0) {
                TRACE_GT(0); TRACE(1);
                prefetch_map(&prm.x); prefetch_map(nslot < 4 ? &prm.wqkv : (rank ? &prm.wu : &prm.wg));
                for (int s = 0; s < G1_STAGES; s++) { mbar_init(full1(s), 1); mbar_init(empty1(s), 4); }
                for (int s = 0; s < G2_STAGES; s++) { mbar_init(full2(s), 1); mbar_init(empty2(s), 4); }
                mbar_init(sig_bar, 8); mbar_init(fold_bar, 2); mbar_init(x_bar, 1);
                for (int s = 0; s < 4; s++) mbar_init(dep_bar + s * 8, 1);
                asm volatile("fence.mbarrier_init.release.cluster;" ::: "memory");
            }
            __syncwarp();
        }
        asm volatile("barrier.cluster.arrive.relaxed.aligned;" ::: "memory");
        if (warp == 8 && lane == 0) {
            asm volatile("fence.proxy.async.shared::cta;" ::: "memory");
            for (int s = 0; s < G1_STAGES; s++) {
                mbar_expect_tx(full1(s), G1_STAGE_BYTES);
                tma_2d(base + s * G1_STAGE_BYTES, &prm.x, full1(s), s * 64, mblk * 128);
            }
            TRACE(15);
        }
        asm volatile("setmaxnreg.dec.sync.aligned.u32 %0;" :: "n"(AUX_REGS));
        asm volatile("barrier.cluster.wait.acquire.aligned;" ::: "memory");

        if (warp == 8) {
            if (lane == 0) {
                TRACE(2);
                auto load_b1 = [&](int s, int nt, int k) {
                    const uint32_t dst = base + s * G1_STAGE_BYTES + A_BYTES + rank * 16384;
                    if (tile_is_qkv(nt)) tma_3d_mc(dst, &prm.wqkv, full1(s), k * 64, tile_index(nt) * 4 + rank * 2);
                    else tma_3d_mc(dst, rank ? &prm.wu : &prm.wg, full1(s), k * 64, tile_index(nt) * 2);
                };
                for (int s = 0; s < G1_STAGES; s++) load_b1(s, nslot, s);
                prefetch_map(&prm.xn); prefetch_map(&prm.wqkv); prefetch_map(rank ? &prm.wu : &prm.wg);
                prefetch_map(&prm.a2); prefetch_map(&prm.wo); prefetch_map(&prm.wd); prefetch_map(&prm.out);
                uint32_t ph = 0;
                for (int it = G1_STAGES; it < G1_TILES * G1_KSTEPS; it++) {
                    const int s = it & 3, k = it & 15;
                    if (it == G1_KSTEPS) { TRACE(14); mbar_wait(dep_bar, 0); TRACE(3); }
                    mbar_wait(empty1(s), ph);
                    mbar_expect_tx(full1(s), G1_STAGE_BYTES);
                    tma_2d(base + s * G1_STAGE_BYTES, it < G1_KSTEPS ? &prm.x : &prm.xn, full1(s), k * 64, mblk * 128);
                    load_b1(s, (it >> 4) * 8 + nslot, k);
                    if (s == 3) ph ^= 1;
                }
                mbar_expect_tx(x_bar, 32768);
                tma_2d(aux, &prm.x, x_bar, nslot * 128, mblk * 128);
                tma_2d(aux + 16384, &prm.x, x_bar, nslot * 128 + 64, mblk * 128);
                TRACE(4);
                mbar_wait(dep_bar + 8, 0);
                TRACE(5);
                int q = 0; uint32_t ph2 = 1;
                for (int u = 0; u < G2_KSTEPS; u++) {
                    if (u == G2_LATE || u == G2_DSTEPS) {
                        TRACE(u == G2_LATE ? 6 : 32);
                        mbar_wait(dep_bar + (u == G2_LATE ? 16 : 24), 0);
                        TRACE(u == G2_LATE ? 7 : 33);
                    }
                    if (u < G2_STAGES) {
                        if (u == 0) mbar_wait(empty1(0), ph);
                        if (u == 1) mbar_wait(empty1(1), ph);
                        if (u == 3) mbar_wait(empty1(2), ph);
                        if (u == 4) mbar_wait(empty1(3), ph);
                    } else {
                        mbar_wait(empty2(q), ph2);
                    }
                    const uint32_t sa = stage2(q);
                    const bool down = u < G2_DSTEPS;
                    const int k = down ? u : u - G2_DSTEPS;
                    mbar_expect_tx(full2(q), G2_STAGE_BYTES);
                    tma_2d(sa, &prm.a2, full2(q), (down ? DM : 0) + k * 64, mblk * 128);
                    tma_5d_mc(sa + A_BYTES + rank * 8192, down ? &prm.wd : &prm.wo, full2(q), nslot * 128 + rank * 64, k * 2);
                    if (++q == G2_STAGES) { q = 0; ph2 ^= 1; }
                }
                TRACE(8);
            }
        } else if (warp == 9) {
            if (lane == 0) {
                mbar_wait(sig_bar, 0);
                TRACE(11);
                flag_add(flags + F_LN * 512);
                for (int t = 0; t < G1_TILES; t++) {
                    mbar_wait(sig_bar, (t + 1) & 1);
                    const int nt = t * 8 + nslot;
                    flag_add(tile_is_qkv(nt) ? g_flags + F_QKV * 512 + (nt & 3) * 32
                                             : flags + (t < G1_TILES - 1 ? F_EARLY : F_LATE) * 512);
                }
            }
        } else {
            const int w = warp - 10;
            const int ld = nslot < 4 ? NQKV : DF;
            const __nv_bfloat16* wp = nslot < 4 ? prm.pwqkv + 2 * DM + nslot * 256 + lane * 8
                                                : (lane < 16 ? prm.pwg : prm.pwu) + (nslot - 4) * 128 + (lane & 15) * 8;
            wp += (size_t)(mblk * 64 + w * 32) * ld;
            const unsigned epoch = __ldcg(g_epoch + blockIdx.x * 16 + w) + 1;
            float cs[8];
#pragma unroll
            for (int d = 0; d < 8; d++) cs[d] = 0.f;
            mbar_wait(full1(0), 0);
#pragma unroll 1
            for (int i = 0; i < 4; i++) {
                uint4 v[8];
#pragma unroll
                for (int j = 0; j < 8; j++) v[j] = __ldg(reinterpret_cast<const uint4*>(wp + (size_t)(i * 8 + j) * ld));
#pragma unroll
                for (int j = 0; j < 8; j++) {
                    float f[8];
                    unpack8(v[j], f);
#pragma unroll
                    for (int d = 0; d < 8; d++) cs[d] += f[d];
                }
            }
            float4* cp = reinterpret_cast<float4*>(g_colsum + (mblk * 2 + w) * 2048 + nslot * 256 + lane * 8);
            cp[0] = make_float4(cs[0], cs[1], cs[2], cs[3]);
            cp[1] = make_float4(cs[4], cs[5], cs[6], cs[7]);
            __syncwarp();
            if (lane == 0) {
                if (w == 0) TRACE(34);
                flag_add(g_flags + F_CS * 512 + nslot * 32);
                flag_wait(g_flags + F_CS * 512 + nslot * 32, epoch * CNT_CS);
            }
            __syncwarp();
            const float4* gp = reinterpret_cast<const float4*>(g_colsum + nslot * 256 + w * 128) + lane;
            float4 c = make_float4(0.f, 0.f, 0.f, 0.f);
#pragma unroll 8
            for (int m = 0; m < 32; m++) {
                const float4 a = __ldcg(gp + m * 512);
                c.x += a.x; c.y += a.y; c.z += a.z; c.w += a.w;
            }
            const uint32_t ca = aux + (w * 8 + (lane >> 2)) * 64 + (lane & 1) * 32 + (lane & 2) * 4;
            sts64f(ca, c.x, c.y);
            sts64f(ca + 16, c.z, c.w);
            if (lane == 0) {
                flag_wait(flags + F_LN * 512, epoch * CNT_LN);
                if (w == 0) { fence_proxy_async(); mbar_arrive(dep_bar); }
            }
            __syncwarp();
            sts128(aux + 1024 + w * 512 + lane * 16, __ldcg(reinterpret_cast<const uint4*>(g_stats + mblk * 128 + w * 64) + lane));
            __syncwarp();
            if (lane == 0) {
                mbar_arrive(fold_bar);
                g_epoch[blockIdx.x * 16 + w] = epoch;
                if (w == 0) {
                    TRACE(35);
                    flag_wait(flags + F_EARLY * 512, epoch * CNT_EARLY);
                    fence_proxy_async(); mbar_arrive(dep_bar + 8);
                    flag_wait(flags + F_LATE * 512, epoch * CNT_LATE);
                    fence_proxy_async(); mbar_arrive(dep_bar + 16);
                    flag_wait(g_flags + F_O * 512, epoch * CNT_O);
                    fence_proxy_async(); mbar_arrive(dep_bar + 24);
                }
            }
        }
    } else {
        asm volatile("barrier.cluster.arrive.relaxed.aligned;" ::: "memory");
        asm volatile("setmaxnreg.inc.sync.aligned.u32 %0;" :: "n"(CONSUMER_REGS));
        const int wg = __shfl_sync(0xffffffffu, threadIdx.x >> 7, 0);
        const int cw = threadIdx.x >> 5;
        const int tid = threadIdx.x & 127;
        float acc[128];
        uint32_t pk[64];
#pragma unroll
        for (int i = 0; i < 64; i++) asm volatile("mov.b32 %0, 0;" : "=r"(pk[i]));
#pragma unroll
        for (int i = 0; i < 128; i++) asm volatile("mov.b32 %0, 0;" : "=f"(acc[i]));
        asm volatile("barrier.cluster.wait.acquire.aligned;" ::: "memory");

        const int orow = mblk * 128 + cw * 16 + (lane >> 2);
        __nv_bfloat16* optr = nullptr;
        auto release = [&](uint32_t bar) { if (tid < 2) mbar_arrive_cluster(bar, tid); };
        auto chunk_geglu = [&](int j) {
            const int c = j >> 1, h = j & 1;
            uint4 v;
            v.x = geglu2(pk[8 * c + h], pk[32 + 8 * c + h]);
            v.y = geglu2(pk[8 * c + 2 + h], pk[32 + 8 * c + 2 + h]);
            v.z = geglu2(pk[8 * c + 4 + h], pk[32 + 8 * c + 4 + h]);
            v.w = geglu2(pk[8 * c + 6 + h], pk[32 + 8 * c + 6 + h]);
            *reinterpret_cast<uint4*>(optr + h * 8 * K2 + c * 32) = v;
        };
        auto chunk_qkv = [&](int c) {
            *reinterpret_cast<uint4*>(optr + c * 32) = make_uint4(pk[8 * c], pk[8 * c + 2], pk[8 * c + 4], pk[8 * c + 6]);
            *reinterpret_cast<uint4*>(optr + 8 * NQKV + c * 32) = make_uint4(pk[8 * c + 1], pk[8 * c + 3], pk[8 * c + 5], pk[8 * c + 7]);
        };
        auto signal_stores = [&]() { __syncwarp(); if (lane == 0) mbar_arrive(sig_bar); };

        auto chunk_ln = [&](int k) {
            const int row = mblk * 128 + nslot * 16 + cw * 2;
            if (k == 0) {
                const uint4* xp = reinterpret_cast<const uint4*>(prm.px + (size_t)row * DM) + lane;
#pragma unroll
                for (int i = 0; i < 8; i++) {
                    const uint4 v = __ldg(xp + i * 32);
                    pk[4 * i] = v.x; pk[4 * i + 1] = v.y; pk[4 * i + 2] = v.z; pk[4 * i + 3] = v.w;
                }
            } else if (k == 3) {
                float a = row_sum(pk), b = row_sum(pk + 16);
                warp_sum2(a, b);
                pk[32] = __float_as_uint(a * (1.f / DM)); pk[33] = __float_as_uint(b * (1.f / DM));
            } else if (k == 4) {
                pk[34] = __float_as_uint(row_sq(pk, __uint_as_float(pk[32])));
            } else if (k == 5) {
                float a = __uint_as_float(pk[34]), b = row_sq(pk + 16, __uint_as_float(pk[33]));
                warp_sum2(a, b);
                pk[34] = __float_as_uint(a); pk[35] = __float_as_uint(b);
            } else if (k == 6) {
                row_store(pk, __uint_as_float(pk[32]), row_inv(__uint_as_float(pk[34])), row, lane);
            } else if (k == 7) {
                row_store(pk + 16, __uint_as_float(pk[33]), row_inv(__uint_as_float(pk[35])), row + 1, lane);
                signal_stores();
            }
        };

        int pending = 0;
#pragma unroll 1
        for (int t = 0; t < G1_TILES; t++) {
#pragma unroll
            for (int k = 0; k < G1_KSTEPS; k++) {
                const int s = k & 3;
                mbar_wait(full1(s), (k >> 2) & 1);
                if (t == 0 && k == 0 && threadIdx.x == 0) TRACE(12);
                if (wg == 1 && k == G1_KSTEPS - G1_SKEW) asm volatile("bar.sync 1, 256;" ::: "memory");
                const uint64_t da = desc_a(base + s * G1_STAGE_BYTES + wg * 8192);
                const uint64_t db = desc_b(base + s * G1_STAGE_BYTES + A_BYTES);
                wg_fence();
#pragma unroll
                for (int kk = 0; kk < 4; kk++) wgmma_n256(acc, da + kk * 2, db + kk * 128, (k | kk) != 0);
                wg_commit();
                if (wg == 0 && k == G1_KSTEPS - 1) asm volatile("bar.arrive 1, 256;" ::: "memory");
                if (k <= 7 && pending == 0) chunk_ln(k);
                if (k >= 1 && k <= 8) {
                    if (pending == 2) chunk_geglu(k - 1);
                    else if (pending == 1) chunk_qkv(k - 1);
                    if (k == 8 && pending) signal_stores();
                }
                wg_wait<1>();
                if (k > 0) release(empty1((k - 1) & 3));
            }
            if (t == 0) mbar_wait(fold_bar, 0);
            wg_wait<0>();
            fence_regs(acc);
            release(empty1(3));
            if (t == 0) {
                const uint32_t sp = aux + 1024 + (cw * 16 + (lane >> 2)) * 8;
                const float2 sa = lds64f(sp), sb = lds64f(sp + 64);
#pragma unroll
                for (int j = 0; j < 16; j++) {
                    const uint4 c = lds128(aux + j * 64 + (lane & 3) * 16);
                    const float c0 = __uint_as_float(c.x), c1 = __uint_as_float(c.y);
                    const float c2 = __uint_as_float(c.z), c3 = __uint_as_float(c.w);
                    const float* a = acc + 8 * j;
                    pk[4 * j] = pack_bf16(fmaf(sa.x, c0, a[0]) * sa.y, fmaf(sa.x, c1, a[1]) * sa.y);
                    pk[4 * j + 1] = pack_bf16(fmaf(sb.x, c0, a[2]) * sb.y, fmaf(sb.x, c1, a[3]) * sb.y);
                    pk[4 * j + 2] = pack_bf16(fmaf(sa.x, c2, a[4]) * sa.y, fmaf(sa.x, c3, a[5]) * sa.y);
                    pk[4 * j + 3] = pack_bf16(fmaf(sb.x, c2, a[6]) * sb.y, fmaf(sb.x, c3, a[7]) * sb.y);
                }
            } else {
#pragma unroll
                for (int i = 0; i < 64; i++) pk[i] = pack_bf16(acc[2 * i], acc[2 * i + 1]);
            }
            const int nt = t * 8 + nslot;
            pending = tile_is_qkv(nt) ? 1 : 2;
            optr = pending == 1 ? g_qkv + (size_t)orow * NQKV + tile_index(nt) * 256 + (lane & 3) * 8
                                : g_a2 + (size_t)orow * K2 + DM + tile_index(nt) * 128 + (lane & 3) * 8;
            if (tid == 0) TRACE(16 + wg * 8 + t);
        }

        float accd[64], accs[64];
#pragma unroll
        for (int i = 0; i < 64; i++) accd[i] = 0.f;
#pragma unroll
        for (int u = 0; u < 9; u++) {
            const int q = u % G2_STAGES;
            mbar_wait(full2(q), (u / G2_STAGES) & 1);
            const uint64_t da = desc_a(stage2(q) + wg * 8192), db = desc_b(stage2(q) + A_BYTES);
            wg_fence();
#pragma unroll
            for (int kk = 0; kk < 4; kk++) wgmma_n128(accd, da + kk * 2, db + kk * 128, (u | kk) != 0);
            wg_commit();
            if (u >= 1) { chunk_geglu(u - 1); if (u == 8) signal_stores(); }
            wg_wait<1>();
            if (u > 0) release(empty2((u - 1) % G2_STAGES));
        }
        {
            int q = 9 % G2_STAGES, qp = 8 % G2_STAGES; uint32_t ph = (9 / G2_STAGES) & 1;
#pragma unroll 1
            for (int u = 9; u < G2_DSTEPS; u++) {
                mbar_wait(full2(q), ph);
                const uint64_t da = desc_a(stage2(q) + wg * 8192), db = desc_b(stage2(q) + A_BYTES);
                wg_fence();
#pragma unroll
                for (int kk = 0; kk < 4; kk++) wgmma_n128(accd, da + kk * 2, db + kk * 128, 1);
                wg_commit();
                wg_wait<1>();
                release(empty2(qp));
                qp = q;
                if (++q == G2_STAGES) { q = 0; ph ^= 1; }
            }
        }
        if (tid == 0) TRACE(16 + wg * 8 + 5);
#pragma unroll
        for (int i = 0; i < 64; i++) accs[i] = 0.f;
        uint32_t gk[32], xr[32];
        const uint32_t xs = aux + cw * 2048;
        const uint32_t xrow = xs + ((lane & 7) + ((lane >> 3) & 1) * 8) * 128;
        auto xaddr = [&](int j) { return xrow + (j >> 2) * 16384 + (((((j & 3) * 2) + (lane >> 4)) ^ (lane & 7)) << 4); };
#pragma unroll
        for (int u = G2_DSTEPS; u < G2_KSTEPS; u++) {
            const int q = u % G2_STAGES, v = u - G2_DSTEPS;
            mbar_wait(full2(q), (u / G2_STAGES) & 1);
            if (G2_SKEW > 0 && wg == 1 && u == G2_KSTEPS - G2_SKEW) asm volatile("bar.sync 1, 256;" ::: "memory");
            const uint64_t da = desc_a(stage2(q) + wg * 8192), db = desc_b(stage2(q) + A_BYTES);
            wg_fence();
#pragma unroll
            for (int kk = 0; kk < 4; kk++) wgmma_n128(accs, da + kk * 2, db + kk * 128, (v | kk) != 0);
            wg_commit();
            if (G2_SKEW > 0 && wg == 0 && u == G2_KSTEPS - 1) asm volatile("bar.arrive 1, 256;" ::: "memory");
            if (v >= 1 && v <= 8) {
#pragma unroll
                for (int i = 4 * (v - 1); i < 4 * v; i++) {
                    const uint32_t d2 = pack_bf16(accd[2 * i], accd[2 * i + 1]);
                    gk[i] = pack_bf16(silu(bf_lo(d2)), silu(bf_hi(d2)));
                }
            }
            if (v == 9) mbar_wait(x_bar, 0);
            if (v >= 9 && v <= 12) {
#pragma unroll
                for (int j = 2 * (v - 9); j < 2 * (v - 8); j++)
                    asm volatile("ldmatrix.sync.aligned.m8n8.x4.shared.b16 {%0,%1,%2,%3}, [%4];"
                                 : "=r"(xr[4 * j]), "=r"(xr[4 * j + 1]), "=r"(xr[4 * j + 2]), "=r"(xr[4 * j + 3])
                                 : "r"(xaddr(j)) : "memory");
            }
            wg_wait<1>();
            if (v == 0) fence_regs(accd);
            if (u - 1 + G2_STAGES < G2_KSTEPS) release(empty2((u - 1) % G2_STAGES));
        }
        wg_wait<0>();
        fence_regs(accs);
        if (tid == 0) TRACE(16 + wg * 8 + 6);
#pragma unroll
        for (int j = 0; j < 8; j++) {
            uint32_t r[4];
#pragma unroll
            for (int i = 0; i < 4; i++) {
                const int e = j * 4 + i;
                r[i] = add_bf16x2(xr[e], mul_bf16x2(pack_bf16(accs[2 * e], accs[2 * e + 1]), gk[e]));
            }
            asm volatile("stmatrix.sync.aligned.m8n8.x4.shared.b16 [%0], {%1,%2,%3,%4};"
                         :: "r"(xaddr(j)), "r"(r[0]), "r"(r[1]), "r"(r[2]), "r"(r[3]) : "memory");
            if (j == 3 || j == 7) {
                asm volatile("fence.proxy.async.shared::cta;" ::: "memory");
                __syncwarp();
                if (lane == 0) {
                    tma_store_2d(&prm.out, xs + (j >> 2) * 16384, nslot * 128 + (j >> 2) * 64, mblk * 128 + cw * 16);
                    asm volatile("cp.async.bulk.commit_group;" ::: "memory");
                }
            }
        }
        if (lane == 0) asm volatile("cp.async.bulk.wait_group.read 0;" ::: "memory");
        if (tid == 0) { TRACE(16 + wg * 8 + 7); if (wg == 1) TRACE_GT(13); }
    }
}

typedef CUresult (*EncodeFn)(CUtensorMap*, CUtensorMapDataType, cuuint32_t, void*, const cuuint64_t*, const cuuint64_t*,
                             const cuuint32_t*, const cuuint32_t*, CUtensorMapInterleave, CUtensorMapSwizzle,
                             CUtensorMapL2promotion, CUtensorMapFloatOOBfill);

void encode(EncodeFn fn, CUtensorMap* m, const void* ptr, int rank, const cuuint64_t* dims, const cuuint64_t* strides,
            const cuuint32_t* box) {
    const cuuint32_t es[5] = {1, 1, 1, 1, 1};
    fn(m, CU_TENSOR_MAP_DATA_TYPE_BFLOAT16, rank, const_cast<void*>(ptr), dims, strides, box, es,
       CU_TENSOR_MAP_INTERLEAVE_NONE, CU_TENSOR_MAP_SWIZZLE_128B, CU_TENSOR_MAP_L2_PROMOTION_L2_128B,
       CU_TENSOR_MAP_FLOAT_OOB_FILL_NONE);
}
void encode_2d(EncodeFn fn, CUtensorMap* m, const void* ptr, int cols, int box_rows) {
    const cuuint64_t dims[2] = {(cuuint64_t)cols, SEQ}, strides[1] = {(cuuint64_t)cols * 2};
    const cuuint32_t box[2] = {64, (cuuint32_t)box_rows};
    encode(fn, m, ptr, 2, dims, strides, box);
}
void encode_w1(EncodeFn fn, CUtensorMap* m, const void* ptr, int cols) {
    const cuuint64_t dims[3] = {64, DM, (cuuint64_t)cols / 64}, strides[2] = {(cuuint64_t)cols * 2, 128};
    const cuuint32_t box[3] = {64, 64, 2};
    encode(fn, m, ptr, 3, dims, strides, box);
}
void encode_qkv(EncodeFn fn, CUtensorMap* m, const void* ptr, int parts) {
    const cuuint64_t dims[5] = {64, SEQ / 2, 3, 2, DM / 64}, strides[4] = {NQKV * 4, DM * 2, NQKV * 2, 128};
    const cuuint32_t box[5] = {64, 16, (cuuint32_t)parts, 1, 1};
    encode(fn, m, ptr, 5, dims, strides, box);
}
void encode_o(EncodeFn fn, CUtensorMap* m, const void* ptr) {
    const cuuint64_t dims[4] = {64, SEQ / 2, 2, DM / 64}, strides[3] = {K2 * 4, K2 * 2, 128};
    const cuuint32_t box[4] = {64, 16, 1, 1};
    encode(fn, m, ptr, 4, dims, strides, box);
}
void encode_w2(EncodeFn fn, CUtensorMap* m, const void* ptr, int rows) {
    const cuuint64_t rb = DM * 2;
    const cuuint64_t dims[5] = {DM, 2, 4, 4, (cuuint64_t)rows / 32}, strides[4] = {rb, 8 * rb, 2 * rb, 32 * rb};
    const cuuint32_t box[5] = {64, 2, 4, 4, 2};
    encode(fn, m, ptr, 5, dims, strides, box);
}

}

extern "C" void kernel_launch(void* const* d_in, const int* in_sizes, int n_in, void* d_out, int out_size) {
    (void)in_sizes; (void)n_in; (void)out_size;
    static EncodeFn fn = nullptr;
    static void *p_xn = nullptr, *p_qkv = nullptr, *p_a2 = nullptr;
    if (!fn) {
        cudaDriverEntryPointQueryResult st;
        cudaGetDriverEntryPoint("cuTensorMapEncodeTiled", (void**)&fn, cudaEnableDefault, &st);
        cudaGetSymbolAddress(&p_xn, g_xn);
        cudaGetSymbolAddress(&p_qkv, g_qkv);
        cudaGetSymbolAddress(&p_a2, g_a2);
        cudaFuncSetAttribute(fused_kernel, cudaFuncAttributeMaxDynamicSharedMemorySize, SMEM_BYTES);
    }
    Params prm;
    encode_2d(fn, &prm.x, d_in[0], DM, 128);
    encode_2d(fn, &prm.xn, p_xn, DM, 128);
    encode_w1(fn, &prm.wqkv, d_in[1], NQKV);
    encode_w1(fn, &prm.wg, d_in[4], DF);
    encode_w1(fn, &prm.wu, d_in[5], DF);
    encode_qkv(fn, &prm.qk, p_qkv, 2);
    encode_qkv(fn, &prm.v, p_qkv, 1);
    encode_o(fn, &prm.o, p_a2);
    encode_2d(fn, &prm.a2, p_a2, K2, 128);
    encode_w2(fn, &prm.wo, d_in[2], DM);
    encode_w2(fn, &prm.wd, d_in[6], DF);
    encode_2d(fn, &prm.out, d_out, DM, 16);
    prm.px = (const __nv_bfloat16*)d_in[0];
    prm.pwqkv = (const __nv_bfloat16*)d_in[1];
    prm.pwg = (const __nv_bfloat16*)d_in[4];
    prm.pwu = (const __nv_bfloat16*)d_in[5];
    fused_kernel<<<NCTA, 384, SMEM_BYTES>>>(prm);
}
```

```cpp
#include <cuda_runtime.h>
#include <cuda_bf16.h>
#include <cuda.h>
#include <stdint.h>

namespace {

constexpr int SEQ = 2048, DM = 1024, DF = 3584, K2 = DM + DF, NQKV = 3 * DM;
constexpr int NGEMM = 128, NCTA = 132;
constexpr int G1_STAGES = 4, G1_STAGE_BYTES = 49152, G1_KSTEPS = 16, G1_TILES = 5;
constexpr int G2_STAGES = 6, G2_STAGE_BYTES = 32768, G2_KSTEPS = 72, G2_DSTEPS = 56, G2_LATE = 40;
constexpr int A_BYTES = 16384;
constexpr int AUX_OFF = G1_STAGES * G1_STAGE_BYTES;
constexpr int BAR_OFF = AUX_OFF + 32768;
constexpr int SMEM_BYTES = BAR_OFF + 1024 + 256;
constexpr int G1_SKEW = 2, G2_SKEW = 2;
constexpr int CONSUMER_REGS = 224, AUX_REGS = 56;
constexpr int ATT_SLOT = 8192;

enum { F_LN = 0, F_QKV = 1, F_EARLY = 2, F_LATE = 3, F_O = 4, F_CS = 5 };
constexpr unsigned CNT_LN = 8, CNT_QKV = 48, CNT_EARLY = 20, CNT_LATE = 8, CNT_O = 48, CNT_CS = 32;

__device__ __align__(1024) __nv_bfloat16 g_xn[SEQ * DM];
__device__ __align__(1024) __nv_bfloat16 g_qkv[SEQ * NQKV];
__device__ __align__(1024) __nv_bfloat16 g_a2[SEQ * K2];
__device__ __align__(128) float2 g_stats[SEQ];
__device__ __align__(128) float g_colsum[32 * 2048];
__device__ __align__(128) unsigned g_flags[6 * 16 * 32];
__device__ __align__(128) unsigned g_epoch[NCTA * 16];

#define TRACE(slot) do {} while (0)
#define TRACE_GT(slot) do {} while (0)

__device__ __forceinline__ uint32_t smem_u32(const void* p) { return (uint32_t)__cvta_generic_to_shared(p); }
__device__ __forceinline__ void mbar_init(uint32_t bar, uint32_t cnt) {
    asm volatile("mbarrier.init.shared::cta.b64 [%0], %1;" :: "r"(bar), "r"(cnt) : "memory");
}
__device__ __forceinline__ void mbar_expect_tx(uint32_t bar, uint32_t bytes) {
    asm volatile("mbarrier.arrive.expect_tx.shared::cta.b64 _, [%0], %1;" :: "r"(bar), "r"(bytes) : "memory");
}
__device__ __forceinline__ void mbar_arrive(uint32_t bar) {
    asm volatile("mbarrier.arrive.shared::cta.b64 _, [%0];" :: "r"(bar) : "memory");
}
__device__ __forceinline__ void mbar_arrive_cluster(uint32_t bar, uint32_t cta) {
    asm volatile("{\n.reg .b32 ra;\nmapa.shared::cluster.u32 ra, %0, %1;\nmbarrier.arrive.shared::cluster.b64 _, [ra];\n}"
                 :: "r"(bar), "r"(cta) : "memory");
}
__device__ __forceinline__ bool mbar_try_wait(uint32_t bar, uint32_t parity) {
    uint32_t ok;
    asm volatile("{\n.reg .pred p;\nmbarrier.try_wait.parity.shared::cta.b64 p, [%1], %2;\nselp.u32 %0, 1, 0, p;\n}"
                 : "=r"(ok) : "r"(bar), "r"(parity) : "memory");
    return ok;
}
__device__ __forceinline__ void mbar_wait(uint32_t bar, uint32_t parity) {
    int spins = 0;
    while (!mbar_try_wait(bar, parity)) { if (++spins > (1 << 17)) break; }
}
__device__ __forceinline__ void flag_wait(const unsigned* p, unsigned target) {
    for (int spins = 0; spins < (1 << 19); spins++) {
        unsigned v;
        asm volatile("ld.acquire.gpu.global.u32 %0, [%1];" : "=r"(v) : "l"(p) : "memory");
        if ((int)(v - target) >= 0) break;
        __nanosleep(64);
    }
}
__device__ __forceinline__ void flag_add(unsigned* p) {
    asm volatile("red.release.gpu.global.add.u32 [%0], 1;" :: "l"(p) : "memory");
}
__device__ __forceinline__ bool elect_one() {
    uint32_t ok;
    asm volatile("{\n.reg .pred p;\nelect.sync _|p, 0xffffffff;\nselp.u32 %0, 1, 0, p;\n}" : "=r"(ok));
    return ok;
}
__device__ __forceinline__ void fence_proxy_async() { asm volatile("fence.proxy.async;" ::: "memory"); }
__device__ __forceinline__ uint4 lds128(uint32_t addr) {
    uint4 v;
    asm volatile("ld.shared.v4.u32 {%0,%1,%2,%3}, [%4];" : "=r"(v.x), "=r"(v.y), "=r"(v.z), "=r"(v.w) : "r"(addr) : "memory");
    return v;
}
__device__ __forceinline__ float2 lds64f(uint32_t addr) {
    float2 v;
    asm volatile("ld.shared.v2.f32 {%0,%1}, [%2];" : "=f"(v.x), "=f"(v.y) : "r"(addr) : "memory");
    return v;
}
__device__ __forceinline__ void sts128(uint32_t addr, uint4 v) {
    asm volatile("st.shared.v4.u32 [%0], {%1,%2,%3,%4};" :: "r"(addr), "r"(v.x), "r"(v.y), "r"(v.z), "r"(v.w) : "memory");
}
__device__ __forceinline__ void sts64f(uint32_t addr, float a, float b) {
    asm volatile("st.shared.v2.f32 [%0], {%1,%2};" :: "r"(addr), "f"(a), "f"(b) : "memory");
}

__device__ __forceinline__ void tma_2d(uint32_t dst, const CUtensorMap* m, uint32_t bar, int c0, int c1) {
    asm volatile("cp.async.bulk.tensor.2d.shared::cluster.global.mbarrier::complete_tx::bytes [%0], [%1, {%3, %4}], [%2];"
                 :: "r"(dst), "l"(m), "r"(bar), "r"(c0), "r"(c1) : "memory");
}
__device__ __forceinline__ void tma_3d(uint32_t dst, const CUtensorMap* m, uint32_t bar, int c0, int c1, int c2) {
    asm volatile("cp.async.bulk.tensor.3d.shared::cluster.global.mbarrier::complete_tx::bytes [%0], [%1, {%3, %4, %5}], [%2];"
                 :: "r"(dst), "l"(m), "r"(bar), "r"(c0), "r"(c1), "r"(c2) : "memory");
}
__device__ __forceinline__ void tma_3d_mc(uint32_t dst, const CUtensorMap* m, uint32_t bar, int c1, int c2) {
    asm volatile("cp.async.bulk.tensor.3d.shared::cluster.global.mbarrier::complete_tx::bytes.multicast::cluster"
                 " [%0], [%1, {%3, %4, %5}], [%2], %6;"
                 :: "r"(dst), "l"(m), "r"(bar), "r"(0), "r"(c1), "r"(c2), "h"((uint16_t)3) : "memory");
}
__device__ __forceinline__ void tma_5d_mc(uint32_t dst, const CUtensorMap* m, uint32_t bar, int c0, int c4) {
    asm volatile("cp.async.bulk.tensor.5d.shared::cluster.global.mbarrier::complete_tx::bytes.multicast::cluster"
                 " [%0], [%1, {%3, %4, %4, %4, %5}], [%2], %6;"
                 :: "r"(dst), "l"(m), "r"(bar), "r"(c0), "r"(0), "r"(c4), "h"((uint16_t)3) : "memory");
}
__device__ __forceinline__ void tma_store_2d(const CUtensorMap* m, uint32_t src, int c0, int c1) {
    asm volatile("cp.async.bulk.tensor.2d.global.shared::cta.bulk_group [%0, {%2, %3}], [%1];"
                 :: "l"(m), "r"(src), "r"(c0), "r"(c1) : "memory");
}
__device__ __forceinline__ void prefetch_map(const CUtensorMap* m) {
    asm volatile("prefetch.tensormap [%0];" :: "l"(m) : "memory");
}
__device__ __forceinline__ void wg_fence() { asm volatile("wgmma.fence.sync.aligned;" ::: "memory"); }
__device__ __forceinline__ void wg_commit() { asm volatile("wgmma.commit_group.sync.aligned;" ::: "memory"); }
template <int N> __device__ __forceinline__ void wg_wait() { asm volatile("wgmma.wait_group.sync.aligned %0;" :: "n"(N) : "memory"); }

__device__ __forceinline__ uint64_t desc_a(uint32_t addr) {
    return (uint64_t)((addr & 0x3FFFF) >> 4) | (1ull << 16) | (64ull << 32) | (1ull << 62);
}
__device__ __forceinline__ uint64_t desc_b(uint32_t addr) {
    return (uint64_t)((addr & 0x3FFFF) >> 4) | (512ull << 16) | (64ull << 32) | (1ull << 62);
}

#define R8(d, o) "+f"(d[o]), "+f"(d[o+1]), "+f"(d[o+2]), "+f"(d[o+3]), "+f"(d[o+4]), "+f"(d[o+5]), "+f"(d[o+6]), "+f"(d[o+7])
#define R32(d, o) R8(d, o), R8(d, o+8), R8(d, o+16), R8(d, o+24)
#define R64(d, o) R32(d, o), R32(d, o+32)

__device__ __forceinline__ void wgmma_n256(float (&d)[128], uint64_t da, uint64_t db, int scale_d) {
    asm volatile("{\n.reg .pred p;\nsetp.ne.b32 p, %130, 0;\n"
        "wgmma.mma_async.sync.aligned.m64n256k16.f32.bf16.bf16 "
        "{%0,%1,%2,%3,%4,%5,%6,%7,%8,%9,%10,%11,%12,%13,%14,%15,%16,%17,%18,%19,%20,%21,%22,%23,%24,%25,%26,%27,%28,%29,%30,%31,"
        "%32,%33,%34,%35,%36,%37,%38,%39,%40,%41,%42,%43,%44,%45,%46,%47,%48,%49,%50,%51,%52,%53,%54,%55,%56,%57,%58,%59,%60,%61,%62,%63,"
        "%64,%65,%66,%67,%68,%69,%70,%71,%72,%73,%74,%75,%76,%77,%78,%79,%80,%81,%82,%83,%84,%85,%86,%87,%88,%89,%90,%91,%92,%93,%94,%95,"
        "%96,%97,%98,%99,%100,%101,%102,%103,%104,%105,%106,%107,%108,%109,%110,%111,%112,%113,%114,%115,%116,%117,%118,%119,%120,%121,%122,%123,%124,%125,%126,%127},"
        " %128, %129, p, 1, 1, 0, 1;\n}"
        : R64(d, 0), R64(d, 64) : "l"(da), "l"(db), "r"(scale_d));
}
__device__ __forceinline__ void wgmma_n128(float (&d)[64], uint64_t da, uint64_t db, int scale_d) {
    asm volatile("{\n.reg .pred p;\nsetp.ne.b32 p, %66, 0;\n"
        "wgmma.mma_async.sync.aligned.m64n128k16.f32.bf16.bf16 "
        "{%0,%1,%2,%3,%4,%5,%6,%7,%8,%9,%10,%11,%12,%13,%14,%15,%16,%17,%18,%19,%20,%21,%22,%23,%24,%25,%26,%27,%28,%29,%30,%31,"
        "%32,%33,%34,%35,%36,%37,%38,%39,%40,%41,%42,%43,%44,%45,%46,%47,%48,%49,%50,%51,%52,%53,%54,%55,%56,%57,%58,%59,%60,%61,%62,%63},"
        " %64, %65, p, 1, 1, 0, 1;\n}"
        : R64(d, 0) : "l"(da), "l"(db), "r"(scale_d));
}

__device__ __forceinline__ uint32_t pack_bf16(float lo, float hi) {
    uint32_t r; asm("cvt.rn.bf16x2.f32 %0, %1, %2;" : "=r"(r) : "f"(hi), "f"(lo)); return r;
}
__device__ __forceinline__ float bf_lo(uint32_t v) { return __uint_as_float(v << 16); }
__device__ __forceinline__ float bf_hi(uint32_t v) { return __uint_as_float(v & 0xffff0000u); }
__device__ __forceinline__ float round_bf16(float v) { return bf_lo(pack_bf16(v, 0.f)); }
__device__ __forceinline__ uint32_t mul_bf16x2(uint32_t a, uint32_t b) {
    uint32_t r; asm("mul.rn.bf16x2 %0, %1, %2;" : "=r"(r) : "r"(a), "r"(b)); return r;
}
__device__ __forceinline__ uint32_t add_bf16x2(uint32_t a, uint32_t b) {
    uint32_t r; asm("add.rn.bf16x2 %0, %1, %2;" : "=r"(r) : "r"(a), "r"(b)); return r;
}
__device__ __forceinline__ uint32_t sub_bf16x2(uint32_t a, uint32_t b) {
    uint32_t r; asm("sub.rn.bf16x2 %0, %1, %2;" : "=r"(r) : "r"(a), "r"(b)); return r;
}
__device__ __forceinline__ float tanh_fast(float x) { float r; asm("tanh.approx.f32 %0, %1;" : "=f"(r) : "f"(x)); return r; }
__device__ __forceinline__ float gelu_tanh(float g) {
    float t = fmaf(g * g, 0.044715f * 0.7978845608f, 0.7978845608f) * g;
    float hg = 0.5f * g;
    return fmaf(hg, tanh_fast(t), hg);
}
__device__ __forceinline__ uint32_t geglu2(uint32_t g2, uint32_t u2) {
    return mul_bf16x2(pack_bf16(gelu_tanh(bf_lo(g2)), gelu_tanh(bf_hi(g2))), u2);
}
__device__ __forceinline__ float silu(float d) {
    float hd = 0.5f * d;
    return fmaf(hd, tanh_fast(hd), hd);
}
__device__ __forceinline__ float ex2_fast(float x) { float r; asm("ex2.approx.ftz.f32 %0, %1;" : "=f"(r) : "f"(x)); return r; }
__device__ __forceinline__ void unpack8(uint4 v, float (&f)[8]) {
    f[0] = bf_lo(v.x); f[1] = bf_hi(v.x); f[2] = bf_lo(v.y); f[3] = bf_hi(v.y);
    f[4] = bf_lo(v.z); f[5] = bf_hi(v.z); f[6] = bf_lo(v.w); f[7] = bf_hi(v.w);
}
template <int N> __device__ __forceinline__ void fence_regs(float (&d)[N]) {
#pragma unroll
    for (int i = 0; i < N; i++) asm volatile("" : "+f"(d[i]) :: "memory");
}

__device__ __forceinline__ float rcp_fast(float x) { float r; asm("rcp.approx.ftz.f32 %0, %1;" : "=f"(r) : "f"(x)); return r; }
__device__ __forceinline__ uint32_t max_bf16x2(uint32_t a, uint32_t b) {
    uint32_t r; asm("max.bf16x2 %0, %1, %2;" : "=r"(r) : "r"(a), "r"(b)); return r;
}
__device__ __forceinline__ uint4 ldsm4(uint32_t addr) {
    uint4 v;
    asm volatile("ldmatrix.sync.aligned.m8n8.x4.shared.b16 {%0,%1,%2,%3}, [%4];"
                 : "=r"(v.x), "=r"(v.y), "=r"(v.z), "=r"(v.w) : "r"(addr) : "memory");
    return v;
}
__device__ __forceinline__ uint4 ldsm4_t(uint32_t addr) {
    uint4 v;
    asm volatile("ldmatrix.sync.aligned.m8n8.x4.trans.shared.b16 {%0,%1,%2,%3}, [%4];"
                 : "=r"(v.x), "=r"(v.y), "=r"(v.z), "=r"(v.w) : "r"(addr) : "memory");
    return v;
}
__device__ __forceinline__ void mma_16816(float (&c)[4], uint32_t a0, uint32_t a1, uint32_t a2, uint32_t a3, uint32_t b0, uint32_t b1) {
    asm("mma.sync.aligned.m16n8k16.row.col.f32.bf16.bf16.f32 {%0,%1,%2,%3}, {%4,%5,%6,%7}, {%8,%9}, {%0,%1,%2,%3};"
        : "+f"(c[0]), "+f"(c[1]), "+f"(c[2]), "+f"(c[3]) : "r"(a0), "r"(a1), "r"(a2), "r"(a3), "r"(b0), "r"(b1));
}
__device__ __forceinline__ void mma_1688(float (&c)[4], uint32_t a0, uint32_t a1, uint32_t b0) {
    asm("mma.sync.aligned.m16n8k8.row.col.f32.bf16.bf16.f32 {%0,%1,%2,%3}, {%4,%5}, {%6}, {%0,%1,%2,%3};"
        : "+f"(c[0]), "+f"(c[1]), "+f"(c[2]), "+f"(c[3]) : "r"(a0), "r"(a1), "r"(b0));
}
__device__ __forceinline__ void qk_tile(float (&c)[4], const uint4& q0, const uint4& q1, const uint4& k, float init) {
    c[0] = c[1] = c[2] = c[3] = init;
    mma_16816(c, q0.x, q0.y, q0.z, q0.w, k.x, k.y);
    mma_16816(c, q1.x, q1.y, q1.z, q1.w, k.z, k.w);
}
__device__ __forceinline__ uint32_t scaled_logits(bool first, float a0, float a1, float b0, float b1) {
    uint32_t p, r;
    asm("{\n.reg .pred p;\nsetp.ne.u32 p, %1, 0;\n@p cvt.rn.bf16x2.f32 %0, %3, %2;\n@!p cvt.rn.bf16x2.f32 %0, %5, %4;\n}"
        : "=r"(p) : "r"((uint32_t)first), "f"(a0), "f"(a1), "f"(b0), "f"(b1));
    asm("fma.rn.bf16x2 %0, %1, %2, %3;" : "=r"(r) : "r"(p), "r"(0x3e353e35u), "r"(mul_bf16x2(p, 0x379e379eu)));
    return r;
}
template <typename T> __device__ __forceinline__ T uniform(T v) { return __shfl_sync(0xffffffffu, v, 0); }

__device__ __forceinline__ void attention(const CUtensorMap* maps, uint32_t base, uint32_t zero, int grp, int warp, int lane) {
    constexpr float LOG2E = 1.4426950408889634f;
    const int g = lane >> 2, t = lane & 3;
    const bool up0 = 2 * t > g, up1 = 2 * t + 1 > g;
    const uint32_t keep = (up0 ? 0x0000ffffu : 0u) | (up1 ? 0xffff0000u : 0u);
    const uint32_t buf = base + warp * 2 * ATT_SLOT, bar = base + AUX_OFF + warp * 16;
    const uint32_t qoff = (lane & 15) * 128 + (((lane >> 4) ^ (lane & 7)) << 4);
    const uint32_t koff = 2048 + (lane & 7) * 128 + (((lane >> 3) ^ (lane & 7)) << 4);
    const int col = uniform((grp * 4 + warp / 3) * 64), first = uniform(warp % 3 * 43 * 16), last = min(first + 43 * 16, SEQ);
    const CUtensorMap* const mqk = reinterpret_cast<const CUtensorMap*>(uniform(reinterpret_cast<uint64_t>(maps)));
    const CUtensorMap *const mv = mqk + 1, *const mo = mqk + 2;
    uint4 kp[2], vp[2];
    uint32_t l0[2], l1[2], m[2];
    float s[2][3][4];
    auto scores = [&](uint32_t st, int row) {
        const float before = (row & 1023) == 0 ? -5.656854e9f : 0.f;
#pragma unroll
        for (int h = 0; h < 2; h++) {
            const uint4 q0 = ldsm4(st + (qoff ^ (h * 64))), q1 = ldsm4(st + (qoff ^ (h * 64 + 32)));
            const uint4 k0 = ldsm4(st + (koff ^ (h * 64))), k1 = ldsm4(st + 1024 + (koff ^ (h * 64)));
            qk_tile(s[h][0], q0, q1, kp[h], before);
            qk_tile(s[h][1], q0, q1, k0, 0.f);
            qk_tile(s[h][2], q0, q1, k1, 0.f);
            kp[h] = k1;
        }
    };
    auto logits = [&]() {
#pragma unroll
        for (int h = 0; h < 2; h++) {
            l0[h] = scaled_logits(up0, s[h][0][0], s[h][1][2], s[h][1][0], s[h][2][2]);
            l1[h] = scaled_logits(up1, s[h][0][1], s[h][1][3], s[h][1][1], s[h][2][3]);
            m[h] = max_bf16x2(l0[h], l1[h]);
            m[h] = max_bf16x2(m[h], __shfl_xor_sync(0xffffffffu, m[h], 1));
        }
    };
    auto row_max = [&]() {
#pragma unroll
        for (int h = 0; h < 2; h++) m[h] = max_bf16x2(m[h], __shfl_xor_sync(0xffffffffu, m[h], 2));
    };
    auto exchange = [&](uint32_t st, uint32_t b, int row, int store, int load) {
        asm volatile("{\n.reg .pred e, p, q;\n"
            "fence.proxy.async.shared::cta;\n"
            "bar.warp.sync 0xffffffff;\n"
            "elect.sync _|e, 0xffffffff;\n"
            "setp.ne.and.b32 p, %10, 0, e;\n"
            "setp.ne.and.b32 q, %11, 0, e;\n"
            "@q mbarrier.arrive.expect_tx.shared::cta.b64 _, [%2], 6144;\n"
            "@q cp.async.bulk.tensor.3d.shared::cluster.global.mbarrier::complete_tx::bytes [%0], [%3, {%6, %7, %12}], [%2];\n"
            "@q cp.async.bulk.tensor.2d.shared::cluster.global.mbarrier::complete_tx::bytes [%0 + 4096], [%4, {%13, %8}], [%2];\n"
            "@e cp.async.bulk.wait_group.read 0;\n"
            "@p cp.async.bulk.tensor.2d.global.shared::cta.bulk_group [%5, {%6, %9}], [%1 + 6144];\n"
            "@e cp.async.bulk.commit_group;\n"
            "bar.warp.sync 0xffffffff;\n}"
            :: "r"(st), "r"(st ^ ATT_SLOT), "r"(b), "l"(mqk), "l"(mv), "l"(mo), "r"(col), "r"(row + 48), "r"(row + 32),
               "r"(row - 16), "r"(store), "r"(load), "r"(0), "r"(col + 2 * DM) : "memory");
    };
    if (elect_one()) {
        mbar_init(bar, 1); mbar_init(bar + 8, 1);
        prefetch_map(mqk); prefetch_map(mv); prefetch_map(mo);
        const unsigned epoch = __ldcg(g_epoch + blockIdx.x * 16 + warp) + 1;
        flag_wait(g_flags + F_QKV * 512 + grp * 32, epoch * CNT_QKV);
        fence_proxy_async();
        mbar_expect_tx(bar + 8, 8192);
        tma_3d(buf + ATT_SLOT, mqk, bar + 8, col, first, 0);
        tma_2d(buf + ATT_SLOT + 4096, mv, bar + 8, col + 2 * DM, first - 16);
        tma_2d(buf + ATT_SLOT + 6144, mv, bar + 8, col + DM, first - 16);
        mbar_expect_tx(bar, 6144);
        tma_3d(buf, mqk, bar, col, first + 16, 0);
        tma_2d(buf + 4096, mv, bar, col + 2 * DM, first);
        g_epoch[blockIdx.x * 16 + warp] = epoch;
        if (warp == 0) TRACE(9);
    }
    __syncwarp();
    mbar_wait(bar + 8, 0);
#pragma unroll
    for (int h = 0; h < 2; h++) {
        kp[h] = ldsm4(buf + ATT_SLOT + 5120 + (koff ^ (h * 64)));
        vp[h] = ldsm4_t(buf + ATT_SLOT + 3072 + (koff ^ (h * 64)));
    }
    scores(buf + ATT_SLOT, first);
    exchange(buf + ATT_SLOT, bar + 8, first - 16, 0, 1);
    logits();
    row_max();
    uint32_t st = buf, b = bar, cnt = 1;
    bool ready = mbar_try_wait(b, 0);
#pragma unroll 1
    for (int row = first; row < last; row += 16) {
        uint32_t pa[2], pb[2];
        if (!ready) mbar_wait(b, (cnt >> 1) & 1);
        uint4 v[2][2];
#pragma unroll
        for (int h = 0; h < 2; h++) {
            const float ma = -LOG2E * bf_lo(m[h]), mb = -LOG2E * bf_hi(m[h]);
            const float a0 = ex2_fast(fmaf(bf_lo(l0[h]), LOG2E, ma)), a1 = ex2_fast(fmaf(bf_lo(l1[h]), LOG2E, ma));
            const float b0 = ex2_fast(fmaf(bf_hi(l0[h]), LOG2E, mb)), b1 = ex2_fast(fmaf(bf_hi(l1[h]), LOG2E, mb));
            float sum[4] = {0.f, 0.f, 0.f, 0.f};
            mma_1688(sum, pack_bf16(a0, a1), pack_bf16(b0, b1), 0x3f803f80u);
            const float ra = rcp_fast(sum[0]), rb = rcp_fast(sum[2]);
            pa[h] = pack_bf16(a0 * ra, a1 * ra);
            pb[h] = pack_bf16(b0 * rb, b1 * rb);
        }
        scores(st, row + 16);
#pragma unroll
        for (int h = 0; h < 2; h++) {
            v[h][0] = ldsm4_t(st + 4096 + (qoff ^ (h * 64)));
            v[h][1] = ldsm4_t(st + 4096 + (qoff ^ (h * 64 + 32)));
        }
        exchange(st, b, row, row > first, row + 32 < last);
        logits();
        float o[2][4][4];
#pragma unroll
        for (int h = 0; h < 2; h++) {
            const uint32_t prev[4] = {vp[h].x, vp[h].y, vp[h].z, vp[h].w};
            const uint32_t own[8] = {v[h][0].x, v[h][0].y, v[h][0].z, v[h][0].w, v[h][1].x, v[h][1].y, v[h][1].z, v[h][1].w};
            const uint32_t a0 = pa[h] & keep, a1 = pa[h] & ~keep, a2 = pb[h] & keep, a3 = pb[h] & ~keep;
            const uint32_t z0 = pa[h] & zero, z1 = pb[h] & zero;
#pragma unroll
            for (int j = 0; j < 4; j++) {
                o[h][j][0] = o[h][j][1] = o[h][j][2] = o[h][j][3] = 0.f;
                mma_1688(o[h][j], a0, z0, prev[j]);
                mma_16816(o[h][j], a1, a2, z1, a3, own[2 * j], own[2 * j + 1]);
            }
            vp[h] = make_uint4(own[1], own[3], own[5], own[7]);
        }
        row_max();
        b ^= 8; cnt++;
        ready = mbar_try_wait(b, (cnt >> 1) & 1);
#pragma unroll
        for (int h = 0; h < 2; h++) {
#pragma unroll
            for (int d = 0; d < 2; d++)
                asm volatile("stmatrix.sync.aligned.m8n8.x4.shared.b16 [%0], {%1,%2,%3,%4};"
                             :: "r"(st + 6144 + (qoff ^ (h * 64 + d * 32))),
                                "r"(pack_bf16(o[h][2 * d][0], o[h][2 * d][1])), "r"(pack_bf16(o[h][2 * d][2], o[h][2 * d][3])),
                                "r"(pack_bf16(o[h][2 * d + 1][0], o[h][2 * d + 1][1])),
                                "r"(pack_bf16(o[h][2 * d + 1][2], o[h][2 * d + 1][3])) : "memory");
        }
        st ^= ATT_SLOT;
    }
    exchange(st, b, last, 1, 0);
    if (elect_one()) {
        asm volatile("cp.async.bulk.wait_group 0;" ::: "memory");
        fence_proxy_async();
        flag_add(g_flags + F_O * 512);
        if (warp == 0) TRACE(10);
    }
}

__device__ __forceinline__ void warp_sum2(float& a, float& b) {
#pragma unroll
    for (int o = 16; o > 0; o >>= 1) {
        a += __shfl_xor_sync(0xffffffffu, a, o);
        b += __shfl_xor_sync(0xffffffffu, b, o);
    }
}
__device__ __forceinline__ float row_sum(const uint32_t* w) {
    float a = 0.f, b = 0.f;
#pragma unroll
    for (int i = 0; i < 16; i++) { a += bf_lo(w[i]); b += bf_hi(w[i]); }
    return a + b;
}
__device__ __forceinline__ float row_sq(const uint32_t* w, float mean) {
    float a = 0.f, b = 0.f;
#pragma unroll
    for (int i = 0; i < 16; i++) {
        const float lo = bf_lo(w[i]) - mean, hi = bf_hi(w[i]) - mean;
        a = fmaf(lo, lo, a); b = fmaf(hi, hi, b);
    }
    return a + b;
}
__device__ __forceinline__ float row_inv(float sq) {
    return 1.f / round_bf16(sqrtf(round_bf16(round_bf16(sq * (1.f / DM)) + 1e-5f)));
}
__device__ __forceinline__ void row_store(const uint32_t* w, float mean, float inv, int row, int lane) {
    const uint32_t m2 = pack_bf16(mean, mean);
    __nv_bfloat16* dst = g_xn + (size_t)row * DM + lane * 8;
#pragma unroll
    for (int i = 0; i < 4; i++) {
        uint32_t o[4];
#pragma unroll
        for (int j = 0; j < 4; j++) {
            const uint32_t c = sub_bf16x2(w[i * 4 + j], m2);
            o[j] = pack_bf16(bf_lo(c) * inv, bf_hi(c) * inv);
        }
        *reinterpret_cast<uint4*>(dst + i * 256) = make_uint4(o[0], o[1], o[2], o[3]);
    }
    if (lane == 0) g_stats[row] = make_float2(-bf_lo(m2), inv);
}

struct Params {
    CUtensorMap x, xn, wqkv, wg, wu, qk, v, o, a2, wo, wd, out;
    const __nv_bfloat16 *px, *pwqkv, *pwg, *pwu;
    uint32_t zero;
};

__device__ __forceinline__ bool tile_is_qkv(int nt) { return nt < 4 || (nt >= 8 && nt < 16); }
__device__ __forceinline__ int tile_index(int nt) { return nt < 4 ? nt + 8 : (nt < 8 ? nt - 4 : (nt < 16 ? nt - 8 : nt - 12)); }

__global__ void __cluster_dims__(2, 1, 1) __launch_bounds__(384, 1)
fused_kernel(const __grid_constant__ Params prm) {
    extern __shared__ __align__(1024) uint8_t smem_raw[];
    const uint32_t base = (smem_u32(smem_raw) + 1023) & ~1023u;
    const uint32_t bars = base + BAR_OFF;
    auto full1 = [&](int s) { return bars + s * 8; };
    auto empty1 = [&](int s) { return bars + 32 + s * 8; };
    auto full2 = [&](int s) { return bars + 64 + s * 8; };
    auto empty2 = [&](int s) { return bars + 128 + s * 8; };
    const uint32_t sig_bar = bars + 192, fold_bar = bars + 200, x_bar = bars + 208, dep_bar = bars + 216;
    auto stage2 = [&](int q) { return base + q * G2_STAGE_BYTES; };
    const uint32_t aux = base + AUX_OFF;

    const int warp = __shfl_sync(0xffffffffu, threadIdx.x >> 5, 0);
    const int lane = threadIdx.x & 31;
    const int rank = blockIdx.x & 1;
    const int mblk = ((blockIdx.x >> 1) & 7) * 2 + rank;
    const int nslot = blockIdx.x >> 4;

    if (blockIdx.x >= NGEMM) {
        if (threadIdx.x == 0) { TRACE_GT(0); TRACE(1); }
        attention(&prm.qk, (base + 2 * ATT_SLOT - 1) & ~(2u * ATT_SLOT - 1), prm.zero, blockIdx.x - NGEMM, warp, lane);
    } else if (warp >= 8) {
        unsigned* const flags = g_flags + mblk * 32;
        if (warp == 8) {
            if (lane == 0) {
                TRACE_GT(0); TRACE(1);
                prefetch_map(&prm.x); prefetch_map(nslot < 4 ? &prm.wqkv : (rank ? &prm.wu : &prm.wg));
                for (int s = 0; s < G1_STAGES; s++) { mbar_init(full1(s), 1); mbar_init(empty1(s), 4); }
                for (int s = 0; s < G2_STAGES; s++) { mbar_init(full2(s), 1); mbar_init(empty2(s), 4); }
                mbar_init(sig_bar, 8); mbar_init(fold_bar, 2); mbar_init(x_bar, 1);
                for (int s = 0; s < 4; s++) mbar_init(dep_bar + s * 8, 1);
                asm volatile("fence.mbarrier_init.release.cluster;" ::: "memory");
            }
            __syncwarp();
        }
        asm volatile("barrier.cluster.arrive.relaxed.aligned;" ::: "memory");
        if (warp == 8 && lane == 0) {
            asm volatile("fence.proxy.async.shared::cta;" ::: "memory");
            for (int s = 0; s < G1_STAGES; s++) {
                mbar_expect_tx(full1(s), G1_STAGE_BYTES);
                tma_2d(base + s * G1_STAGE_BYTES, &prm.x, full1(s), s * 64, mblk * 128);
            }
            TRACE(15);
        }
        asm volatile("setmaxnreg.dec.sync.aligned.u32 %0;" :: "n"(AUX_REGS));
        asm volatile("barrier.cluster.wait.acquire.aligned;" ::: "memory");

        if (warp == 8) {
            if (lane == 0) {
                TRACE(2);
                auto load_b1 = [&](int s, int nt, int k) {
                    const uint32_t dst = base + s * G1_STAGE_BYTES + A_BYTES + rank * 16384;
                    if (tile_is_qkv(nt)) tma_3d_mc(dst, &prm.wqkv, full1(s), k * 64, tile_index(nt) * 4 + rank * 2);
                    else tma_3d_mc(dst, rank ? &prm.wu : &prm.wg, full1(s), k * 64, tile_index(nt) * 2);
                };
                for (int s = 0; s < G1_STAGES; s++) load_b1(s, nslot, s);
                prefetch_map(&prm.xn); prefetch_map(&prm.wqkv); prefetch_map(rank ? &prm.wu : &prm.wg);
                prefetch_map(&prm.a2); prefetch_map(&prm.wo); prefetch_map(&prm.wd); prefetch_map(&prm.out);
                uint32_t ph = 0;
                for (int it = G1_STAGES; it < G1_TILES * G1_KSTEPS; it++) {
                    const int s = it & 3, k = it & 15;
                    if (it == G1_KSTEPS) { TRACE(14); mbar_wait(dep_bar, 0); TRACE(3); }
                    mbar_wait(empty1(s), ph);
                    mbar_expect_tx(full1(s), G1_STAGE_BYTES);
                    tma_2d(base + s * G1_STAGE_BYTES, it < G1_KSTEPS ? &prm.x : &prm.xn, full1(s), k * 64, mblk * 128);
                    load_b1(s, (it >> 4) * 8 + nslot, k);
                    if (s == 3) ph ^= 1;
                }
                mbar_expect_tx(x_bar, 32768);
                tma_2d(aux, &prm.x, x_bar, nslot * 128, mblk * 128);
                tma_2d(aux + 16384, &prm.x, x_bar, nslot * 128 + 64, mblk * 128);
                TRACE(4);
                mbar_wait(dep_bar + 8, 0);
                TRACE(5);
                int q = 0; uint32_t ph2 = 1;
                for (int u = 0; u < G2_KSTEPS; u++) {
                    if (u == G2_LATE || u == G2_DSTEPS) {
                        TRACE(u == G2_LATE ? 6 : 32);
                        mbar_wait(dep_bar + (u == G2_LATE ? 16 : 24), 0);
                        TRACE(u == G2_LATE ? 7 : 33);
                    }
                    if (u < G2_STAGES) {
                        if (u == 0) mbar_wait(empty1(0), ph);
                        if (u == 1) mbar_wait(empty1(1), ph);
                        if (u == 3) mbar_wait(empty1(2), ph);
                        if (u == 4) mbar_wait(empty1(3), ph);
                    } else {
                        mbar_wait(empty2(q), ph2);
                    }
                    const uint32_t sa = stage2(q);
                    const bool down = u < G2_DSTEPS;
                    const int k = down ? u : u - G2_DSTEPS;
                    mbar_expect_tx(full2(q), G2_STAGE_BYTES);
                    tma_3d(sa, &prm.a2, full2(q), (down ? DM : 0) + k * 64, 0, mblk * 64);
                    tma_5d_mc(sa + A_BYTES + rank * 8192, down ? &prm.wd : &prm.wo, full2(q), nslot * 128 + rank * 64, k * 2);
                    if (++q == G2_STAGES) { q = 0; ph2 ^= 1; }
                }
                TRACE(8);
            }
        } else if (warp == 9) {
            if (lane == 0) {
                mbar_wait(sig_bar, 0);
                TRACE(11);
                flag_add(flags + F_LN * 512);
                for (int t = 0; t < G1_TILES; t++) {
                    mbar_wait(sig_bar, (t + 1) & 1);
                    const int nt = t * 8 + nslot;
                    flag_add(tile_is_qkv(nt) ? g_flags + F_QKV * 512 + (nt & 3) * 32
                                             : flags + (t < G1_TILES - 1 ? F_EARLY : F_LATE) * 512);
                }
            }
        } else {
            const int w = warp - 10;
            const int ld = nslot < 4 ? NQKV : DF;
            const __nv_bfloat16* wp = nslot < 4 ? prm.pwqkv + 2 * DM + nslot * 256 + lane * 8
                                                : (lane < 16 ? prm.pwg : prm.pwu) + (nslot - 4) * 128 + (lane & 15) * 8;
            wp += (size_t)(mblk * 64 + w * 32) * ld;
            const unsigned epoch = __ldcg(g_epoch + blockIdx.x * 16 + w) + 1;
            float cs[8];
#pragma unroll
            for (int d = 0; d < 8; d++) cs[d] = 0.f;
            mbar_wait(full1(0), 0);
#pragma unroll 1
            for (int i = 0; i < 4; i++) {
                uint4 v[8];
#pragma unroll
                for (int j = 0; j < 8; j++) v[j] = __ldg(reinterpret_cast<const uint4*>(wp + (size_t)(i * 8 + j) * ld));
#pragma unroll
                for (int j = 0; j < 8; j++) {
                    float f[8];
                    unpack8(v[j], f);
#pragma unroll
                    for (int d = 0; d < 8; d++) cs[d] += f[d];
                }
            }
            float4* cp = reinterpret_cast<float4*>(g_colsum + (mblk * 2 + w) * 2048 + nslot * 256 + lane * 8);
            cp[0] = make_float4(cs[0], cs[1], cs[2], cs[3]);
            cp[1] = make_float4(cs[4], cs[5], cs[6], cs[7]);
            __syncwarp();
            if (lane == 0) {
                if (w == 0) TRACE(34);
                flag_add(g_flags + F_CS * 512 + nslot * 32);
                flag_wait(g_flags + F_CS * 512 + nslot * 32, epoch * CNT_CS);
            }
            __syncwarp();
            const float4* gp = reinterpret_cast<const float4*>(g_colsum + nslot * 256 + w * 128) + lane;
            float4 c = make_float4(0.f, 0.f, 0.f, 0.f);
#pragma unroll 8
            for (int m = 0; m < 32; m++) {
                const float4 a = __ldcg(gp + m * 512);
                c.x += a.x; c.y += a.y; c.z += a.z; c.w += a.w;
            }
            const uint32_t ca = aux + (w * 8 + (lane >> 2)) * 64 + (lane & 1) * 32 + (lane & 2) * 4;
            sts64f(ca, c.x, c.y);
            sts64f(ca + 16, c.z, c.w);
            if (lane == 0) {
                flag_wait(flags + F_LN * 512, epoch * CNT_LN);
                if (w == 0) { fence_proxy_async(); mbar_arrive(dep_bar); }
            }
            __syncwarp();
            sts128(aux + 1024 + w * 512 + lane * 16, __ldcg(reinterpret_cast<const uint4*>(g_stats + mblk * 128 + w * 64) + lane));
            __syncwarp();
            if (lane == 0) {
                mbar_arrive(fold_bar);
                g_epoch[blockIdx.x * 16 + w] = epoch;
                if (w == 0) {
                    TRACE(35);
                    flag_wait(flags + F_EARLY * 512, epoch * CNT_EARLY);
                    fence_proxy_async(); mbar_arrive(dep_bar + 8);
                    flag_wait(flags + F_LATE * 512, epoch * CNT_LATE);
                    fence_proxy_async(); mbar_arrive(dep_bar + 16);
                    flag_wait(g_flags + F_O * 512, epoch * CNT_O);
                    fence_proxy_async(); mbar_arrive(dep_bar + 24);
                }
            }
        }
    } else {
        asm volatile("barrier.cluster.arrive.relaxed.aligned;" ::: "memory");
        asm volatile("setmaxnreg.inc.sync.aligned.u32 %0;" :: "n"(CONSUMER_REGS));
        const int wg = __shfl_sync(0xffffffffu, threadIdx.x >> 7, 0);
        const int cw = threadIdx.x >> 5;
        const int tid = threadIdx.x & 127;
        float acc[128];
        uint32_t pk[64];
#pragma unroll
        for (int i = 0; i < 64; i++) asm volatile("mov.b32 %0, 0;" : "=r"(pk[i]));
#pragma unroll
        for (int i = 0; i < 128; i++) asm volatile("mov.b32 %0, 0;" : "=f"(acc[i]));
        asm volatile("barrier.cluster.wait.acquire.aligned;" ::: "memory");

        const int orow = ((lane >> 2) & 1) * (SEQ / 2) + mblk * 64 + cw * 8 + (lane >> 3);
        __nv_bfloat16* optr = nullptr;
        auto release = [&](uint32_t bar) { if (tid < 2) mbar_arrive_cluster(bar, tid); };
        auto chunk_geglu = [&](int j) {
            const int c = j >> 1, h = j & 1;
            uint4 v;
            v.x = geglu2(pk[8 * c + h], pk[32 + 8 * c + h]);
            v.y = geglu2(pk[8 * c + 2 + h], pk[32 + 8 * c + 2 + h]);
            v.z = geglu2(pk[8 * c + 4 + h], pk[32 + 8 * c + 4 + h]);
            v.w = geglu2(pk[8 * c + 6 + h], pk[32 + 8 * c + 6 + h]);
            *reinterpret_cast<uint4*>(optr + h * 4 * K2 + c * 32) = v;
        };
        auto chunk_qkv = [&](int c) {
            *reinterpret_cast<uint4*>(optr + c * 32) = make_uint4(pk[8 * c], pk[8 * c + 2], pk[8 * c + 4], pk[8 * c + 6]);
            *reinterpret_cast<uint4*>(optr + 4 * NQKV + c * 32) = make_uint4(pk[8 * c + 1], pk[8 * c + 3], pk[8 * c + 5], pk[8 * c + 7]);
        };
        auto signal_stores = [&]() { __syncwarp(); if (lane == 0) mbar_arrive(sig_bar); };

        auto chunk_ln = [&](int k) {
            const int row = mblk * 128 + nslot * 16 + cw * 2;
            if (k == 0) {
                const uint4* xp = reinterpret_cast<const uint4*>(prm.px + (size_t)row * DM) + lane;
#pragma unroll
                for (int i = 0; i < 8; i++) {
                    const uint4 v = __ldg(xp + i * 32);
                    pk[4 * i] = v.x; pk[4 * i + 1] = v.y; pk[4 * i + 2] = v.z; pk[4 * i + 3] = v.w;
                }
            } else if (k == 3) {
                float a = row_sum(pk), b = row_sum(pk + 16);
                warp_sum2(a, b);
                pk[32] = __float_as_uint(a * (1.f / DM)); pk[33] = __float_as_uint(b * (1.f / DM));
            } else if (k == 4) {
                pk[34] = __float_as_uint(row_sq(pk, __uint_as_float(pk[32])));
            } else if (k == 5) {
                float a = __uint_as_float(pk[34]), b = row_sq(pk + 16, __uint_as_float(pk[33]));
                warp_sum2(a, b);
                pk[34] = __float_as_uint(a); pk[35] = __float_as_uint(b);
            } else if (k == 6) {
                row_store(pk, __uint_as_float(pk[32]), row_inv(__uint_as_float(pk[34])), row, lane);
            } else if (k == 7) {
                row_store(pk + 16, __uint_as_float(pk[33]), row_inv(__uint_as_float(pk[35])), row + 1, lane);
                signal_stores();
            }
        };

        int pending = 0;
#pragma unroll 1
        for (int t = 0; t < G1_TILES; t++) {
#pragma unroll
            for (int k = 0; k < G1_KSTEPS; k++) {
                const int s = k & 3;
                mbar_wait(full1(s), (k >> 2) & 1);
                if (t == 0 && k == 0 && threadIdx.x == 0) TRACE(12);
                if (wg == 1 && k == G1_KSTEPS - G1_SKEW) asm volatile("bar.sync 1, 256;" ::: "memory");
                const uint64_t da = desc_a(base + s * G1_STAGE_BYTES + wg * 8192);
                const uint64_t db = desc_b(base + s * G1_STAGE_BYTES + A_BYTES);
                wg_fence();
#pragma unroll
                for (int kk = 0; kk < 4; kk++) wgmma_n256(acc, da + kk * 2, db + kk * 128, (k | kk) != 0);
                wg_commit();
                if (wg == 0 && k == G1_KSTEPS - 1) asm volatile("bar.arrive 1, 256;" ::: "memory");
                if (k <= 7 && pending == 0) chunk_ln(k);
                if (k >= 1 && k <= 8) {
                    if (pending == 2) chunk_geglu(k - 1);
                    else if (pending == 1) chunk_qkv(k - 1);
                    if (k == 8 && pending) signal_stores();
                }
                wg_wait<1>();
                if (k > 0) release(empty1((k - 1) & 3));
            }
            if (t == 0) mbar_wait(fold_bar, 0);
            wg_wait<0>();
            fence_regs(acc);
            release(empty1(3));
            if (t == 0) {
                const uint32_t sp = aux + 1024 + (cw * 16 + (lane >> 2)) * 8;
                const float2 sa = lds64f(sp), sb = lds64f(sp + 64);
#pragma unroll
                for (int j = 0; j < 16; j++) {
                    const uint4 c = lds128(aux + j * 64 + (lane & 3) * 16);
                    const float c0 = __uint_as_float(c.x), c1 = __uint_as_float(c.y);
                    const float c2 = __uint_as_float(c.z), c3 = __uint_as_float(c.w);
                    const float* a = acc + 8 * j;
                    pk[4 * j] = pack_bf16(fmaf(sa.x, c0, a[0]) * sa.y, fmaf(sa.x, c1, a[1]) * sa.y);
                    pk[4 * j + 1] = pack_bf16(fmaf(sb.x, c0, a[2]) * sb.y, fmaf(sb.x, c1, a[3]) * sb.y);
                    pk[4 * j + 2] = pack_bf16(fmaf(sa.x, c2, a[4]) * sa.y, fmaf(sa.x, c3, a[5]) * sa.y);
                    pk[4 * j + 3] = pack_bf16(fmaf(sb.x, c2, a[6]) * sb.y, fmaf(sb.x, c3, a[7]) * sb.y);
                }
            } else {
#pragma unroll
                for (int i = 0; i < 64; i++) pk[i] = pack_bf16(acc[2 * i], acc[2 * i + 1]);
            }
            const int nt = t * 8 + nslot;
            pending = tile_is_qkv(nt) ? 1 : 2;
            optr = pending == 1 ? g_qkv + (size_t)orow * NQKV + tile_index(nt) * 256 + (lane & 3) * 8
                                : g_a2 + (size_t)orow * K2 + DM + tile_index(nt) * 128 + (lane & 3) * 8;
            if (tid == 0) TRACE(16 + wg * 8 + t);
        }

        float accd[64], accs[64];
#pragma unroll
        for (int i = 0; i < 64; i++) accd[i] = 0.f;
#pragma unroll
        for (int u = 0; u < 9; u++) {
            const int q = u % G2_STAGES;
            mbar_wait(full2(q), (u / G2_STAGES) & 1);
            const uint64_t da = desc_a(stage2(q) + wg * 8192), db = desc_b(stage2(q) + A_BYTES);
            wg_fence();
#pragma unroll
            for (int kk = 0; kk < 4; kk++) wgmma_n128(accd, da + kk * 2, db + kk * 128, (u | kk) != 0);
            wg_commit();
            if (u >= 1) { chunk_geglu(u - 1); if (u == 8) signal_stores(); }
            wg_wait<1>();
            if (u > 0) release(empty2((u - 1) % G2_STAGES));
        }
        {
            int q = 9 % G2_STAGES, qp = 8 % G2_STAGES; uint32_t ph = (9 / G2_STAGES) & 1;
#pragma unroll 1
            for (int u = 9; u < G2_DSTEPS; u++) {
                mbar_wait(full2(q), ph);
                const uint64_t da = desc_a(stage2(q) + wg * 8192), db = desc_b(stage2(q) + A_BYTES);
                wg_fence();
#pragma unroll
                for (int kk = 0; kk < 4; kk++) wgmma_n128(accd, da + kk * 2, db + kk * 128, 1);
                wg_commit();
                wg_wait<1>();
                release(empty2(qp));
                qp = q;
                if (++q == G2_STAGES) { q = 0; ph ^= 1; }
            }
        }
        if (tid == 0) TRACE(16 + wg * 8 + 5);
#pragma unroll
        for (int i = 0; i < 64; i++) accs[i] = 0.f;
        uint32_t gk[32], xr[32];
        const uint32_t xs = aux + cw * 2048;
        const uint32_t xrow = xs + ((lane & 7) + ((lane >> 3) & 1) * 8) * 128;
        auto xaddr = [&](int j) { return xrow + (j >> 2) * 16384 + (((((j & 3) * 2) + (lane >> 4)) ^ (lane & 7)) << 4); };
#pragma unroll
        for (int u = G2_DSTEPS; u < G2_KSTEPS; u++) {
            const int q = u % G2_STAGES, v = u - G2_DSTEPS;
            mbar_wait(full2(q), (u / G2_STAGES) & 1);
            if (G2_SKEW > 0 && wg == 1 && u == G2_KSTEPS - G2_SKEW) asm volatile("bar.sync 1, 256;" ::: "memory");
            const uint64_t da = desc_a(stage2(q) + wg * 8192), db = desc_b(stage2(q) + A_BYTES);
            wg_fence();
#pragma unroll
            for (int kk = 0; kk < 4; kk++) wgmma_n128(accs, da + kk * 2, db + kk * 128, (v | kk) != 0);
            wg_commit();
            if (G2_SKEW > 0 && wg == 0 && u == G2_KSTEPS - 1) asm volatile("bar.arrive 1, 256;" ::: "memory");
            if (v >= 1 && v <= 8) {
#pragma unroll
                for (int i = 4 * (v - 1); i < 4 * v; i++) {
                    const uint32_t d2 = pack_bf16(accd[2 * i], accd[2 * i + 1]);
                    gk[i] = pack_bf16(silu(bf_lo(d2)), silu(bf_hi(d2)));
                }
            }
            if (v == 9) mbar_wait(x_bar, 0);
            if (v >= 9 && v <= 12) {
#pragma unroll
                for (int j = 2 * (v - 9); j < 2 * (v - 8); j++)
                    asm volatile("ldmatrix.sync.aligned.m8n8.x4.shared.b16 {%0,%1,%2,%3}, [%4];"
                                 : "=r"(xr[4 * j]), "=r"(xr[4 * j + 1]), "=r"(xr[4 * j + 2]), "=r"(xr[4 * j + 3])
                                 : "r"(xaddr(j)) : "memory");
            }
            wg_wait<1>();
            if (v == 0) fence_regs(accd);
            if (u - 1 + G2_STAGES < G2_KSTEPS) release(empty2((u - 1) % G2_STAGES));
        }
        wg_wait<0>();
        fence_regs(accs);
        if (tid == 0) TRACE(16 + wg * 8 + 6);
#pragma unroll
        for (int j = 0; j < 8; j++) {
            uint32_t r[4];
#pragma unroll
            for (int i = 0; i < 4; i++) {
                const int e = j * 4 + i;
                r[i] = add_bf16x2(xr[e], mul_bf16x2(pack_bf16(accs[2 * e], accs[2 * e + 1]), gk[e]));
            }
            asm volatile("stmatrix.sync.aligned.m8n8.x4.shared.b16 [%0], {%1,%2,%3,%4};"
                         :: "r"(xaddr(j)), "r"(r[0]), "r"(r[1]), "r"(r[2]), "r"(r[3]) : "memory");
            if (j == 3 || j == 7) {
                asm volatile("fence.proxy.async.shared::cta;" ::: "memory");
                __syncwarp();
                if (lane == 0) {
                    tma_store_2d(&prm.out, xs + (j >> 2) * 16384, nslot * 128 + (j >> 2) * 64, mblk * 128 + cw * 16);
                    asm volatile("cp.async.bulk.commit_group;" ::: "memory");
                }
            }
        }
        if (lane == 0) asm volatile("cp.async.bulk.wait_group.read 0;" ::: "memory");
        if (tid == 0) { TRACE(16 + wg * 8 + 7); if (wg == 1) TRACE_GT(13); }
    }
}

typedef CUresult (*EncodeFn)(CUtensorMap*, CUtensorMapDataType, cuuint32_t, void*, const cuuint64_t*, const cuuint64_t*,
                             const cuuint32_t*, const cuuint32_t*, CUtensorMapInterleave, CUtensorMapSwizzle,
                             CUtensorMapL2promotion, CUtensorMapFloatOOBfill);

void encode(EncodeFn fn, CUtensorMap* m, const void* ptr, int rank, const cuuint64_t* dims, const cuuint64_t* strides,
            const cuuint32_t* box) {
    const cuuint32_t es[5] = {1, 1, 1, 1, 1};
    fn(m, CU_TENSOR_MAP_DATA_TYPE_BFLOAT16, rank, const_cast<void*>(ptr), dims, strides, box, es,
       CU_TENSOR_MAP_INTERLEAVE_NONE, CU_TENSOR_MAP_SWIZZLE_128B, CU_TENSOR_MAP_L2_PROMOTION_L2_128B,
       CU_TENSOR_MAP_FLOAT_OOB_FILL_NONE);
}
void encode_2d(EncodeFn fn, CUtensorMap* m, const void* ptr, int cols, int box_rows) {
    const cuuint64_t dims[2] = {(cuuint64_t)cols, SEQ}, strides[1] = {(cuuint64_t)cols * 2};
    const cuuint32_t box[2] = {64, (cuuint32_t)box_rows};
    encode(fn, m, ptr, 2, dims, strides, box);
}
void encode_w1(EncodeFn fn, CUtensorMap* m, const void* ptr, int cols) {
    const cuuint64_t dims[3] = {64, DM, (cuuint64_t)cols / 64}, strides[2] = {(cuuint64_t)cols * 2, 128};
    const cuuint32_t box[3] = {64, 64, 2};
    encode(fn, m, ptr, 3, dims, strides, box);
}
void encode_qk(EncodeFn fn, CUtensorMap* m, const void* ptr) {
    const cuuint64_t dims[3] = {DM, SEQ, 3}, strides[2] = {NQKV * 2, DM * 2};
    const cuuint32_t box[3] = {64, 16, 2};
    encode(fn, m, ptr, 3, dims, strides, box);
}
void encode_a2(EncodeFn fn, CUtensorMap* m, const void* ptr) {
    const cuuint64_t dims[3] = {K2, 2, SEQ / 2}, strides[2] = {(cuuint64_t)SEQ * K2, K2 * 2};
    const cuuint32_t box[3] = {64, 2, 64};
    encode(fn, m, ptr, 3, dims, strides, box);
}
void encode_w2(EncodeFn fn, CUtensorMap* m, const void* ptr, int rows) {
    const cuuint64_t rb = DM * 2;
    const cuuint64_t dims[5] = {DM, 2, 4, 4, (cuuint64_t)rows / 32}, strides[4] = {rb, 8 * rb, 2 * rb, 32 * rb};
    const cuuint32_t box[5] = {64, 2, 4, 4, 2};
    encode(fn, m, ptr, 5, dims, strides, box);
}

}

extern "C" void kernel_launch(void* const* d_in, const int* in_sizes, int n_in, void* d_out, int out_size) {
    (void)in_sizes; (void)n_in; (void)out_size;
    static EncodeFn fn = nullptr;
    static void *p_xn = nullptr, *p_qkv = nullptr, *p_a2 = nullptr;
    if (!fn) {
        cudaDriverEntryPointQueryResult st;
        cudaGetDriverEntryPoint("cuTensorMapEncodeTiled", (void**)&fn, cudaEnableDefault, &st);
        cudaGetSymbolAddress(&p_xn, g_xn);
        cudaGetSymbolAddress(&p_qkv, g_qkv);
        cudaGetSymbolAddress(&p_a2, g_a2);
        cudaFuncSetAttribute(fused_kernel, cudaFuncAttributeMaxDynamicSharedMemorySize, SMEM_BYTES);
    }
    Params prm;
    encode_2d(fn, &prm.x, d_in[0], DM, 128);
    encode_2d(fn, &prm.xn, p_xn, DM, 128);
    encode_w1(fn, &prm.wqkv, d_in[1], NQKV);
    encode_w1(fn, &prm.wg, d_in[4], DF);
    encode_w1(fn, &prm.wu, d_in[5], DF);
    encode_qk(fn, &prm.qk, p_qkv);
    encode_2d(fn, &prm.v, p_qkv, NQKV, 16);
    encode_2d(fn, &prm.o, p_a2, K2, 16);
    encode_a2(fn, &prm.a2, p_a2);
    encode_w2(fn, &prm.wo, d_in[2], DM);
    encode_w2(fn, &prm.wd, d_in[6], DF);
    encode_2d(fn, &prm.out, d_out, DM, 16);
    prm.px = (const __nv_bfloat16*)d_in[0];
    prm.pwqkv = (const __nv_bfloat16*)d_in[1];
    prm.pwg = (const __nv_bfloat16*)d_in[4];
    prm.pwu = (const __nv_bfloat16*)d_in[5];
    prm.zero = 0;
    fused_kernel<<<NCTA, 384, SMEM_BYTES>>>(prm);
}
```

```cpp
#include <cuda_runtime.h>
#include <cuda_bf16.h>
#include <cuda.h>
#include <stdint.h>

#define P_W1 1
#define P_X 1
#define P_XN4 1
#define P_W2 1
#define P_A2 1
#define P_QKV 1

namespace {

constexpr int SEQ = 2048, DM = 1024, DF = 3584, K2 = DM + DF, NQKV = 3 * DM;
constexpr int NGEMM = 128, NCTA = 132;
constexpr int G1_STAGES = 4, G1_STAGE_BYTES = 49152, G1_KSTEPS = 16, G1_TILES = 5;
constexpr int G2_STAGES = 6, G2_STAGE_BYTES = 32768, G2_KSTEPS = 72, G2_DSTEPS = 56, G2_LATE = 40;
constexpr int A_BYTES = 16384;
constexpr int AUX_OFF = G1_STAGES * G1_STAGE_BYTES;
constexpr int BAR_OFF = AUX_OFF + 32768;
constexpr int SMEM_BYTES = BAR_OFF + 1024 + 256;
constexpr int G1_SKEW = 2, G2_SKEW = 2;
constexpr int CONSUMER_REGS = 224, AUX_REGS = 56;
constexpr int ATT_SLOT = 8192;

enum { F_LN = 0, F_QKV = 1, F_EARLY = 2, F_LATE = 3, F_O = 4, F_CS = 5 };
constexpr unsigned CNT_LN = 8, CNT_QKV = 48, CNT_EARLY = 20, CNT_LATE = 8, CNT_O = 48, CNT_CS = 32;

__device__ __align__(1024) __nv_bfloat16 g_xn[SEQ * DM];
__device__ __align__(1024) __nv_bfloat16 g_qkv[SEQ * NQKV];
__device__ __align__(1024) __nv_bfloat16 g_a2[SEQ * K2];
__device__ __align__(128) float2 g_stats[SEQ];
__device__ __align__(128) float g_colsum[32 * 2048];
__device__ __align__(128) unsigned g_flags[6 * 16 * 32];
__device__ __align__(128) unsigned g_epoch[NCTA * 16];

#define TRACE(slot) do {} while (0)
#define TRACE_GT(slot) do {} while (0)

__device__ __forceinline__ uint32_t smem_u32(const void* p) { return (uint32_t)__cvta_generic_to_shared(p); }
__device__ __forceinline__ void mbar_init(uint32_t bar, uint32_t cnt) {
    asm volatile("mbarrier.init.shared::cta.b64 [%0], %1;" :: "r"(bar), "r"(cnt) : "memory");
}
__device__ __forceinline__ void mbar_expect_tx(uint32_t bar, uint32_t bytes) {
    asm volatile("mbarrier.arrive.expect_tx.shared::cta.b64 _, [%0], %1;" :: "r"(bar), "r"(bytes) : "memory");
}
__device__ __forceinline__ void mbar_arrive(uint32_t bar) {
    asm volatile("mbarrier.arrive.shared::cta.b64 _, [%0];" :: "r"(bar) : "memory");
}
__device__ __forceinline__ void mbar_arrive_cluster(uint32_t bar, uint32_t cta) {
    asm volatile("{\n.reg .b32 ra;\nmapa.shared::cluster.u32 ra, %0, %1;\nmbarrier.arrive.shared::cluster.b64 _, [ra];\n}"
                 :: "r"(bar), "r"(cta) : "memory");
}
__device__ __forceinline__ bool mbar_try_wait(uint32_t bar, uint32_t parity) {
    uint32_t ok;
    asm volatile("{\n.reg .pred p;\nmbarrier.try_wait.parity.shared::cta.b64 p, [%1], %2;\nselp.u32 %0, 1, 0, p;\n}"
                 : "=r"(ok) : "r"(bar), "r"(parity) : "memory");
    return ok;
}
__device__ __forceinline__ void mbar_wait(uint32_t bar, uint32_t parity) {
    int spins = 0;
    while (!mbar_try_wait(bar, parity)) { if (++spins > (1 << 17)) break; }
}
__device__ __forceinline__ void flag_wait(const unsigned* p, unsigned target) {
    for (int spins = 0; spins < (1 << 19); spins++) {
        unsigned v;
        asm volatile("ld.acquire.gpu.global.u32 %0, [%1];" : "=r"(v) : "l"(p) : "memory");
        if ((int)(v - target) >= 0) break;
        __nanosleep(64);
    }
}
__device__ __forceinline__ void flag_add(unsigned* p) {
    asm volatile("red.release.gpu.global.add.u32 [%0], 1;" :: "l"(p) : "memory");
}
__device__ __forceinline__ bool elect_one() {
    uint32_t ok;
    asm volatile("{\n.reg .pred p;\nelect.sync _|p, 0xffffffff;\nselp.u32 %0, 1, 0, p;\n}" : "=r"(ok));
    return ok;
}
__device__ __forceinline__ void fence_proxy_async() { asm volatile("fence.proxy.async;" ::: "memory"); }
__device__ __forceinline__ uint4 lds128(uint32_t addr) {
    uint4 v;
    asm volatile("ld.shared.v4.u32 {%0,%1,%2,%3}, [%4];" : "=r"(v.x), "=r"(v.y), "=r"(v.z), "=r"(v.w) : "r"(addr) : "memory");
    return v;
}
__device__ __forceinline__ float2 lds64f(uint32_t addr) {
    float2 v;
    asm volatile("ld.shared.v2.f32 {%0,%1}, [%2];" : "=f"(v.x), "=f"(v.y) : "r"(addr) : "memory");
    return v;
}
__device__ __forceinline__ void sts128(uint32_t addr, uint4 v) {
    asm volatile("st.shared.v4.u32 [%0], {%1,%2,%3,%4};" :: "r"(addr), "r"(v.x), "r"(v.y), "r"(v.z), "r"(v.w) : "memory");
}
__device__ __forceinline__ void sts64f(uint32_t addr, float a, float b) {
    asm volatile("st.shared.v2.f32 [%0], {%1,%2};" :: "r"(addr), "f"(a), "f"(b) : "memory");
}

__device__ __forceinline__ uint64_t policy(bool stream) {
    uint64_t p;
    if (stream) asm("createpolicy.fractional.L2::evict_first.b64 %0, 1.0;" : "=l"(p));
    else asm("createpolicy.fractional.L2::evict_normal.b64 %0, 1.0;" : "=l"(p));
    return p;
}
__device__ __forceinline__ void tma_2d(uint32_t dst, const CUtensorMap* m, uint32_t bar, int c0, int c1, uint64_t pol) {
    asm volatile("cp.async.bulk.tensor.2d.shared::cluster.global.mbarrier::complete_tx::bytes.L2::cache_hint"
                 " [%0], [%1, {%3, %4}], [%2], %5;"
                 :: "r"(dst), "l"(m), "r"(bar), "r"(c0), "r"(c1), "l"(pol) : "memory");
}
__device__ __forceinline__ void tma_3d(uint32_t dst, const CUtensorMap* m, uint32_t bar, int c0, int c1, int c2, uint64_t pol) {
    asm volatile("cp.async.bulk.tensor.3d.shared::cluster.global.mbarrier::complete_tx::bytes.L2::cache_hint"
                 " [%0], [%1, {%3, %4, %5}], [%2], %6;"
                 :: "r"(dst), "l"(m), "r"(bar), "r"(c0), "r"(c1), "r"(c2), "l"(pol) : "memory");
}
__device__ __forceinline__ void tma_3d_mc(uint32_t dst, const CUtensorMap* m, uint32_t bar, int c1, int c2, uint64_t pol) {
    asm volatile("cp.async.bulk.tensor.3d.shared::cluster.global.mbarrier::complete_tx::bytes.multicast::cluster.L2::cache_hint"
                 " [%0], [%1, {%3, %4, %5}], [%2], %6, %7;"
                 :: "r"(dst), "l"(m), "r"(bar), "r"(0), "r"(c1), "r"(c2), "h"((uint16_t)3), "l"(pol) : "memory");
}
__device__ __forceinline__ void tma_5d_mc(uint32_t dst, const CUtensorMap* m, uint32_t bar, int c0, int c4, uint64_t pol) {
    asm volatile("cp.async.bulk.tensor.5d.shared::cluster.global.mbarrier::complete_tx::bytes.multicast::cluster.L2::cache_hint"
                 " [%0], [%1, {%3, %4, %4, %4, %5}], [%2], %6, %7;"
                 :: "r"(dst), "l"(m), "r"(bar), "r"(c0), "r"(0), "r"(c4), "h"((uint16_t)3), "l"(pol) : "memory");
}
__device__ __forceinline__ void tma_store_2d(const CUtensorMap* m, uint32_t src, int c0, int c1) {
    asm volatile("cp.async.bulk.tensor.2d.global.shared::cta.bulk_group [%0, {%2, %3}], [%1];"
                 :: "l"(m), "r"(src), "r"(c0), "r"(c1) : "memory");
}
__device__ __forceinline__ uint4 ldg_stream(const void* p, uint64_t pol) {
    uint4 v;
    asm volatile("ld.global.nc.L1::no_allocate.L2::cache_hint.v4.u32 {%0,%1,%2,%3}, [%4], %5;"
                 : "=r"(v.x), "=r"(v.y), "=r"(v.z), "=r"(v.w) : "l"(p), "l"(pol));
    return v;
}
__device__ __forceinline__ void prefetch_map(const CUtensorMap* m) {
    asm volatile("prefetch.tensormap [%0];" :: "l"(m) : "memory");
}
__device__ __forceinline__ void wg_fence() { asm volatile("wgmma.fence.sync.aligned;" ::: "memory"); }
__device__ __forceinline__ void wg_commit() { asm volatile("wgmma.commit_group.sync.aligned;" ::: "memory"); }
template <int N> __device__ __forceinline__ void wg_wait() { asm volatile("wgmma.wait_group.sync.aligned %0;" :: "n"(N) : "memory"); }

__device__ __forceinline__ uint64_t desc_a(uint32_t addr) {
    return (uint64_t)((addr & 0x3FFFF) >> 4) | (1ull << 16) | (64ull << 32) | (1ull << 62);
}
__device__ __forceinline__ uint64_t desc_b(uint32_t addr) {
    return (uint64_t)((addr & 0x3FFFF) >> 4) | (512ull << 16) | (64ull << 32) | (1ull << 62);
}

#define R8(d, o) "+f"(d[o]), "+f"(d[o+1]), "+f"(d[o+2]), "+f"(d[o+3]), "+f"(d[o+4]), "+f"(d[o+5]), "+f"(d[o+6]), "+f"(d[o+7])
#define R32(d, o) R8(d, o), R8(d, o+8), R8(d, o+16), R8(d, o+24)
#define R64(d, o) R32(d, o), R32(d, o+32)

__device__ __forceinline__ void wgmma_n256(float (&d)[128], uint64_t da, uint64_t db, int scale_d) {
    asm volatile("{\n.reg .pred p;\nsetp.ne.b32 p, %130, 0;\n"
        "wgmma.mma_async.sync.aligned.m64n256k16.f32.bf16.bf16 "
        "{%0,%1,%2,%3,%4,%5,%6,%7,%8,%9,%10,%11,%12,%13,%14,%15,%16,%17,%18,%19,%20,%21,%22,%23,%24,%25,%26,%27,%28,%29,%30,%31,"
        "%32,%33,%34,%35,%36,%37,%38,%39,%40,%41,%42,%43,%44,%45,%46,%47,%48,%49,%50,%51,%52,%53,%54,%55,%56,%57,%58,%59,%60,%61,%62,%63,"
        "%64,%65,%66,%67,%68,%69,%70,%71,%72,%73,%74,%75,%76,%77,%78,%79,%80,%81,%82,%83,%84,%85,%86,%87,%88,%89,%90,%91,%92,%93,%94,%95,"
        "%96,%97,%98,%99,%100,%101,%102,%103,%104,%105,%106,%107,%108,%109,%110,%111,%112,%113,%114,%115,%116,%117,%118,%119,%120,%121,%122,%123,%124,%125,%126,%127},"
        " %128, %129, p, 1, 1, 0, 1;\n}"
        : R64(d, 0), R64(d, 64) : "l"(da), "l"(db), "r"(scale_d));
}
__device__ __forceinline__ void wgmma_n128(float (&d)[64], uint64_t da, uint64_t db, int scale_d) {
    asm volatile("{\n.reg .pred p;\nsetp.ne.b32 p, %66, 0;\n"
        "wgmma.mma_async.sync.aligned.m64n128k16.f32.bf16.bf16 "
        "{%0,%1,%2,%3,%4,%5,%6,%7,%8,%9,%10,%11,%12,%13,%14,%15,%16,%17,%18,%19,%20,%21,%22,%23,%24,%25,%26,%27,%28,%29,%30,%31,"
        "%32,%33,%34,%35,%36,%37,%38,%39,%40,%41,%42,%43,%44,%45,%46,%47,%48,%49,%50,%51,%52,%53,%54,%55,%56,%57,%58,%59,%60,%61,%62,%63},"
        " %64, %65, p, 1, 1, 0, 1;\n}"
        : R64(d, 0) : "l"(da), "l"(db), "r"(scale_d));
}

__device__ __forceinline__ uint32_t pack_bf16(float lo, float hi) {
    uint32_t r; asm("cvt.rn.bf16x2.f32 %0, %1, %2;" : "=r"(r) : "f"(hi), "f"(lo)); return r;
}
__device__ __forceinline__ float bf_lo(uint32_t v) { return __uint_as_float(v << 16); }
__device__ __forceinline__ float bf_hi(uint32_t v) { return __uint_as_float(v & 0xffff0000u); }
__device__ __forceinline__ float round_bf16(float v) { return bf_lo(pack_bf16(v, 0.f)); }
__device__ __forceinline__ uint32_t mul_bf16x2(uint32_t a, uint32_t b) {
    uint32_t r; asm("mul.rn.bf16x2 %0, %1, %2;" : "=r"(r) : "r"(a), "r"(b)); return r;
}
__device__ __forceinline__ uint32_t add_bf16x2(uint32_t a, uint32_t b) {
    uint32_t r; asm("add.rn.bf16x2 %0, %1, %2;" : "=r"(r) : "r"(a), "r"(b)); return r;
}
__device__ __forceinline__ uint32_t sub_bf16x2(uint32_t a, uint32_t b) {
    uint32_t r; asm("sub.rn.bf16x2 %0, %1, %2;" : "=r"(r) : "r"(a), "r"(b)); return r;
}
__device__ __forceinline__ float tanh_fast(float x) { float r; asm("tanh.approx.f32 %0, %1;" : "=f"(r) : "f"(x)); return r; }
__device__ __forceinline__ float gelu_tanh(float g) {
    float t = fmaf(g * g, 0.044715f * 0.7978845608f, 0.7978845608f) * g;
    float hg = 0.5f * g;
    return fmaf(hg, tanh_fast(t), hg);
}
__device__ __forceinline__ uint32_t geglu2(uint32_t g2, uint32_t u2) {
    return mul_bf16x2(pack_bf16(gelu_tanh(bf_lo(g2)), gelu_tanh(bf_hi(g2))), u2);
}
__device__ __forceinline__ float silu(float d) {
    float hd = 0.5f * d;
    return fmaf(hd, tanh_fast(hd), hd);
}
__device__ __forceinline__ float ex2_fast(float x) { float r; asm("ex2.approx.ftz.f32 %0, %1;" : "=f"(r) : "f"(x)); return r; }
__device__ __forceinline__ void unpack8(uint4 v, float (&f)[8]) {
    f[0] = bf_lo(v.x); f[1] = bf_hi(v.x); f[2] = bf_lo(v.y); f[3] = bf_hi(v.y);
    f[4] = bf_lo(v.z); f[5] = bf_hi(v.z); f[6] = bf_lo(v.w); f[7] = bf_hi(v.w);
}
template <int N> __device__ __forceinline__ void fence_regs(float (&d)[N]) {
#pragma unroll
    for (int i = 0; i < N; i++) asm volatile("" : "+f"(d[i]) :: "memory");
}

__device__ __forceinline__ float rcp_fast(float x) { float r; asm("rcp.approx.ftz.f32 %0, %1;" : "=f"(r) : "f"(x)); return r; }
__device__ __forceinline__ uint32_t max_bf16x2(uint32_t a, uint32_t b) {
    uint32_t r; asm("max.bf16x2 %0, %1, %2;" : "=r"(r) : "r"(a), "r"(b)); return r;
}
__device__ __forceinline__ uint4 ldsm4(uint32_t addr) {
    uint4 v;
    asm volatile("ldmatrix.sync.aligned.m8n8.x4.shared.b16 {%0,%1,%2,%3}, [%4];"
                 : "=r"(v.x), "=r"(v.y), "=r"(v.z), "=r"(v.w) : "r"(addr) : "memory");
    return v;
}
__device__ __forceinline__ uint4 ldsm4_t(uint32_t addr) {
    uint4 v;
    asm volatile("ldmatrix.sync.aligned.m8n8.x4.trans.shared.b16 {%0,%1,%2,%3}, [%4];"
                 : "=r"(v.x), "=r"(v.y), "=r"(v.z), "=r"(v.w) : "r"(addr) : "memory");
    return v;
}
__device__ __forceinline__ void mma_16816(float (&c)[4], uint32_t a0, uint32_t a1, uint32_t a2, uint32_t a3, uint32_t b0, uint32_t b1) {
    asm("mma.sync.aligned.m16n8k16.row.col.f32.bf16.bf16.f32 {%0,%1,%2,%3}, {%4,%5,%6,%7}, {%8,%9}, {%0,%1,%2,%3};"
        : "+f"(c[0]), "+f"(c[1]), "+f"(c[2]), "+f"(c[3]) : "r"(a0), "r"(a1), "r"(a2), "r"(a3), "r"(b0), "r"(b1));
}
__device__ __forceinline__ void mma_1688(float (&c)[4], uint32_t a0, uint32_t a1, uint32_t b0) {
    asm("mma.sync.aligned.m16n8k8.row.col.f32.bf16.bf16.f32 {%0,%1,%2,%3}, {%4,%5}, {%6}, {%0,%1,%2,%3};"
        : "+f"(c[0]), "+f"(c[1]), "+f"(c[2]), "+f"(c[3]) : "r"(a0), "r"(a1), "r"(b0));
}
__device__ __forceinline__ void qk_tile(float (&c)[4], const uint4& q0, const uint4& q1, const uint4& k, float init) {
    c[0] = c[1] = c[2] = c[3] = init;
    mma_16816(c, q0.x, q0.y, q0.z, q0.w, k.x, k.y);
    mma_16816(c, q1.x, q1.y, q1.z, q1.w, k.z, k.w);
}
__device__ __forceinline__ uint32_t scaled_logits(bool first, float a0, float a1, float b0, float b1) {
    uint32_t p, r;
    asm("{\n.reg .pred p;\nsetp.ne.u32 p, %1, 0;\n@p cvt.rn.bf16x2.f32 %0, %3, %2;\n@!p cvt.rn.bf16x2.f32 %0, %5, %4;\n}"
        : "=r"(p) : "r"((uint32_t)first), "f"(a0), "f"(a1), "f"(b0), "f"(b1));
    asm("fma.rn.bf16x2 %0, %1, %2, %3;" : "=r"(r) : "r"(p), "r"(0x3e353e35u), "r"(mul_bf16x2(p, 0x379e379eu)));
    return r;
}
template <typename T> __device__ __forceinline__ T uniform(T v) { return __shfl_sync(0xffffffffu, v, 0); }

__device__ __forceinline__ void attention(const CUtensorMap* maps, uint32_t base, uint32_t zero, int grp, int warp, int lane) {
    constexpr float LOG2E = 1.4426950408889634f;
    const int g = lane >> 2, t = lane & 3;
    const bool up0 = 2 * t > g, up1 = 2 * t + 1 > g;
    const uint32_t keep = (up0 ? 0x0000ffffu : 0u) | (up1 ? 0xffff0000u : 0u);
    const uint32_t buf = base + warp * 2 * ATT_SLOT, bar = base + AUX_OFF + warp * 16;
    const uint32_t qoff = (lane & 15) * 128 + (((lane >> 4) ^ (lane & 7)) << 4);
    const uint32_t koff = 2048 + (lane & 7) * 128 + (((lane >> 3) ^ (lane & 7)) << 4);
    const int col = uniform((grp * 4 + warp / 3) * 64), first = uniform(warp % 3 * 43 * 16), last = min(first + 43 * 16, SEQ);
    const CUtensorMap* const mqk = reinterpret_cast<const CUtensorMap*>(uniform(reinterpret_cast<uint64_t>(maps)));
    const CUtensorMap *const mv = mqk + 1, *const mo = mqk + 2;
    const uint64_t pol = policy(P_QKV);
    uint4 kp[2], vp[2];
    uint32_t l0[2], l1[2], m[2];
    float s[2][3][4];
    auto scores = [&](uint32_t st, int row) {
        const float before = (row & 1023) == 0 ? -5.656854e9f : 0.f;
#pragma unroll
        for (int h = 0; h < 2; h++) {
            const uint4 q0 = ldsm4(st + (qoff ^ (h * 64))), q1 = ldsm4(st + (qoff ^ (h * 64 + 32)));
            const uint4 k0 = ldsm4(st + (koff ^ (h * 64))), k1 = ldsm4(st + 1024 + (koff ^ (h * 64)));
            qk_tile(s[h][0], q0, q1, kp[h], before);
            qk_tile(s[h][1], q0, q1, k0, 0.f);
            qk_tile(s[h][2], q0, q1, k1, 0.f);
            kp[h] = k1;
        }
    };
    auto logits = [&]() {
#pragma unroll
        for (int h = 0; h < 2; h++) {
            l0[h] = scaled_logits(up0, s[h][0][0], s[h][1][2], s[h][1][0], s[h][2][2]);
            l1[h] = scaled_logits(up1, s[h][0][1], s[h][1][3], s[h][1][1], s[h][2][3]);
            m[h] = max_bf16x2(l0[h], l1[h]);
            m[h] = max_bf16x2(m[h], __shfl_xor_sync(0xffffffffu, m[h], 1));
        }
    };
    auto row_max = [&]() {
#pragma unroll
        for (int h = 0; h < 2; h++) m[h] = max_bf16x2(m[h], __shfl_xor_sync(0xffffffffu, m[h], 2));
    };
    auto exchange = [&](uint32_t st, uint32_t b, int row, int store, int load) {
        asm volatile("{\n.reg .pred e, p, q;\n"
            "fence.proxy.async.shared::cta;\n"
            "bar.warp.sync 0xffffffff;\n"
            "elect.sync _|e, 0xffffffff;\n"
            "setp.ne.and.b32 p, %10, 0, e;\n"
            "setp.ne.and.b32 q, %11, 0, e;\n"
            "@q mbarrier.arrive.expect_tx.shared::cta.b64 _, [%2], 6144;\n"
            "@q cp.async.bulk.tensor.3d.shared::cluster.global.mbarrier::complete_tx::bytes.L2::cache_hint [%0], [%3, {%6, %7, %12}], [%2], %14;\n"
            "@q cp.async.bulk.tensor.2d.shared::cluster.global.mbarrier::complete_tx::bytes.L2::cache_hint [%0 + 4096], [%4, {%13, %8}], [%2], %14;\n"
            "@e cp.async.bulk.wait_group.read 0;\n"
            "@p cp.async.bulk.tensor.2d.global.shared::cta.bulk_group [%5, {%6, %9}], [%1 + 6144];\n"
            "@e cp.async.bulk.commit_group;\n"
            "bar.warp.sync 0xffffffff;\n}"
            :: "r"(st), "r"(st ^ ATT_SLOT), "r"(b), "l"(mqk), "l"(mv), "l"(mo), "r"(col), "r"(row + 48), "r"(row + 32),
               "r"(row - 16), "r"(store), "r"(load), "r"(0), "r"(col + 2 * DM), "l"(pol) : "memory");
    };
    if (elect_one()) {
        mbar_init(bar, 1); mbar_init(bar + 8, 1);
        prefetch_map(mqk); prefetch_map(mv); prefetch_map(mo);
        const unsigned epoch = __ldcg(g_epoch + blockIdx.x * 16 + warp) + 1;
        flag_wait(g_flags + F_QKV * 512 + grp * 32, epoch * CNT_QKV);
        fence_proxy_async();
        mbar_expect_tx(bar + 8, 8192);
        tma_3d(buf + ATT_SLOT, mqk, bar + 8, col, first, 0, pol);
        tma_2d(buf + ATT_SLOT + 4096, mv, bar + 8, col + 2 * DM, first - 16, policy(false));
        tma_2d(buf + ATT_SLOT + 6144, mv, bar + 8, col + DM, first - 16, policy(false));
        mbar_expect_tx(bar, 6144);
        tma_3d(buf, mqk, bar, col, first + 16, 0, pol);
        tma_2d(buf + 4096, mv, bar, col + 2 * DM, first, pol);
        g_epoch[blockIdx.x * 16 + warp] = epoch;
        if (warp == 0) TRACE(9);
    }
    __syncwarp();
    mbar_wait(bar + 8, 0);
#pragma unroll
    for (int h = 0; h < 2; h++) {
        kp[h] = ldsm4(buf + ATT_SLOT + 5120 + (koff ^ (h * 64)));
        vp[h] = ldsm4_t(buf + ATT_SLOT + 3072 + (koff ^ (h * 64)));
    }
    scores(buf + ATT_SLOT, first);
    exchange(buf + ATT_SLOT, bar + 8, first - 16, 0, 1);
    logits();
    row_max();
    uint32_t st = buf, b = bar, cnt = 1;
    bool ready = mbar_try_wait(b, 0);
#pragma unroll 1
    for (int row = first; row < last; row += 16) {
        uint32_t pa[2], pb[2];
        if (!ready) mbar_wait(b, (cnt >> 1) & 1);
        uint4 v[2][2];
#pragma unroll
        for (int h = 0; h < 2; h++) {
            const float ma = -LOG2E * bf_lo(m[h]), mb = -LOG2E * bf_hi(m[h]);
            const float a0 = ex2_fast(fmaf(bf_lo(l0[h]), LOG2E, ma)), a1 = ex2_fast(fmaf(bf_lo(l1[h]), LOG2E, ma));
            const float b0 = ex2_fast(fmaf(bf_hi(l0[h]), LOG2E, mb)), b1 = ex2_fast(fmaf(bf_hi(l1[h]), LOG2E, mb));
            float sum[4] = {0.f, 0.f, 0.f, 0.f};
            mma_1688(sum, pack_bf16(a0, a1), pack_bf16(b0, b1), 0x3f803f80u);
            const float ra = rcp_fast(sum[0]), rb = rcp_fast(sum[2]);
            pa[h] = pack_bf16(a0 * ra, a1 * ra);
            pb[h] = pack_bf16(b0 * rb, b1 * rb);
        }
        scores(st, row + 16);
#pragma unroll
        for (int h = 0; h < 2; h++) {
            v[h][0] = ldsm4_t(st + 4096 + (qoff ^ (h * 64)));
            v[h][1] = ldsm4_t(st + 4096 + (qoff ^ (h * 64 + 32)));
        }
        exchange(st, b, row, row > first, row + 32 < last);
        logits();
        float o[2][4][4];
#pragma unroll
        for (int h = 0; h < 2; h++) {
            const uint32_t prev[4] = {vp[h].x, vp[h].y, vp[h].z, vp[h].w};
            const uint32_t own[8] = {v[h][0].x, v[h][0].y, v[h][0].z, v[h][0].w, v[h][1].x, v[h][1].y, v[h][1].z, v[h][1].w};
            const uint32_t a0 = pa[h] & keep, a1 = pa[h] & ~keep, a2 = pb[h] & keep, a3 = pb[h] & ~keep;
            const uint32_t z0 = pa[h] & zero, z1 = pb[h] & zero;
#pragma unroll
            for (int j = 0; j < 4; j++) {
                o[h][j][0] = o[h][j][1] = o[h][j][2] = o[h][j][3] = 0.f;
                mma_1688(o[h][j], a0, z0, prev[j]);
                mma_16816(o[h][j], a1, a2, z1, a3, own[2 * j], own[2 * j + 1]);
            }
            vp[h] = make_uint4(own[1], own[3], own[5], own[7]);
        }
        row_max();
        b ^= 8; cnt++;
        ready = mbar_try_wait(b, (cnt >> 1) & 1);
#pragma unroll
        for (int h = 0; h < 2; h++) {
#pragma unroll
            for (int d = 0; d < 2; d++)
                asm volatile("stmatrix.sync.aligned.m8n8.x4.shared.b16 [%0], {%1,%2,%3,%4};"
                             :: "r"(st + 6144 + (qoff ^ (h * 64 + d * 32))),
                                "r"(pack_bf16(o[h][2 * d][0], o[h][2 * d][1])), "r"(pack_bf16(o[h][2 * d][2], o[h][2 * d][3])),
                                "r"(pack_bf16(o[h][2 * d + 1][0], o[h][2 * d + 1][1])),
                                "r"(pack_bf16(o[h][2 * d + 1][2], o[h][2 * d + 1][3])) : "memory");
        }
        st ^= ATT_SLOT;
    }
    exchange(st, b, last, 1, 0);
    if (elect_one()) {
        asm volatile("cp.async.bulk.wait_group 0;" ::: "memory");
        fence_proxy_async();
        flag_add(g_flags + F_O * 512);
        if (warp == 0) TRACE(10);
    }
}

__device__ __forceinline__ void warp_sum2(float& a, float& b) {
#pragma unroll
    for (int o = 16; o > 0; o >>= 1) {
        a += __shfl_xor_sync(0xffffffffu, a, o);
        b += __shfl_xor_sync(0xffffffffu, b, o);
    }
}
__device__ __forceinline__ float row_sum(const uint32_t* w) {
    float a = 0.f, b = 0.f;
#pragma unroll
    for (int i = 0; i < 16; i++) { a += bf_lo(w[i]); b += bf_hi(w[i]); }
    return a + b;
}
__device__ __forceinline__ float row_sq(const uint32_t* w, float mean) {
    float a = 0.f, b = 0.f;
#pragma unroll
    for (int i = 0; i < 16; i++) {
        const float lo = bf_lo(w[i]) - mean, hi = bf_hi(w[i]) - mean;
        a = fmaf(lo, lo, a); b = fmaf(hi, hi, b);
    }
    return a + b;
}
__device__ __forceinline__ float row_inv(float sq) {
    return 1.f / round_bf16(sqrtf(round_bf16(round_bf16(sq * (1.f / DM)) + 1e-5f)));
}
__device__ __forceinline__ void row_store(const uint32_t* w, float mean, float inv, int row, int lane) {
    const uint32_t m2 = pack_bf16(mean, mean);
    __nv_bfloat16* dst = g_xn + (size_t)row * DM + lane * 8;
#pragma unroll
    for (int i = 0; i < 4; i++) {
        uint32_t o[4];
#pragma unroll
        for (int j = 0; j < 4; j++) {
            const uint32_t c = sub_bf16x2(w[i * 4 + j], m2);
            o[j] = pack_bf16(bf_lo(c) * inv, bf_hi(c) * inv);
        }
        *reinterpret_cast<uint4*>(dst + i * 256) = make_uint4(o[0], o[1], o[2], o[3]);
    }
    if (lane == 0) g_stats[row] = make_float2(-bf_lo(m2), inv);
}

struct Params {
    CUtensorMap x, xn, wqkv, wg, wu, qk, v, o, a2, wo, wd, out;
    const __nv_bfloat16 *px, *pwqkv, *pwg, *pwu;
    uint32_t zero;
};

__device__ __forceinline__ bool tile_is_qkv(int nt) { return nt < 4 || (nt >= 8 && nt < 16); }
__device__ __forceinline__ int tile_index(int nt) { return nt < 4 ? nt + 8 : (nt < 8 ? nt - 4 : (nt < 16 ? nt - 8 : nt - 12)); }

__global__ void __cluster_dims__(2, 1, 1) __launch_bounds__(384, 1)
fused_kernel(const __grid_constant__ Params prm) {
    extern __shared__ __align__(1024) uint8_t smem_raw[];
    const uint32_t base = (smem_u32(smem_raw) + 1023) & ~1023u;
    const uint32_t bars = base + BAR_OFF;
    auto full1 = [&](int s) { return bars + s * 8; };
    auto empty1 = [&](int s) { return bars + 32 + s * 8; };
    auto full2 = [&](int s) { return bars + 64 + s * 8; };
    auto empty2 = [&](int s) { return bars + 128 + s * 8; };
    const uint32_t sig_bar = bars + 192, fold_bar = bars + 200, x_bar = bars + 208, dep_bar = bars + 216;
    auto stage2 = [&](int q) { return base + q * G2_STAGE_BYTES; };
    const uint32_t aux = base + AUX_OFF;

    const int warp = __shfl_sync(0xffffffffu, threadIdx.x >> 5, 0);
    const int lane = threadIdx.x & 31;
    const int rank = blockIdx.x & 1;
    const int mblk = ((blockIdx.x >> 1) & 7) * 2 + rank;
    const int nslot = blockIdx.x >> 4;

    if (blockIdx.x >= NGEMM) {
        if (threadIdx.x == 0) { TRACE_GT(0); TRACE(1); }
        attention(&prm.qk, (base + 2 * ATT_SLOT - 1) & ~(2u * ATT_SLOT - 1), prm.zero, blockIdx.x - NGEMM, warp, lane);
    } else if (warp >= 8) {
        unsigned* const flags = g_flags + mblk * 32;
        if (warp == 8) {
            if (lane == 0) {
                TRACE_GT(0); TRACE(1);
                prefetch_map(&prm.x); prefetch_map(nslot < 4 ? &prm.wqkv : (rank ? &prm.wu : &prm.wg));
                for (int s = 0; s < G1_STAGES; s++) { mbar_init(full1(s), 1); mbar_init(empty1(s), 4); }
                for (int s = 0; s < G2_STAGES; s++) { mbar_init(full2(s), 1); mbar_init(empty2(s), 4); }
                mbar_init(sig_bar, 8); mbar_init(fold_bar, 2); mbar_init(x_bar, 1);
                for (int s = 0; s < 4; s++) mbar_init(dep_bar + s * 8, 1);
                asm volatile("fence.mbarrier_init.release.cluster;" ::: "memory");
            }
            __syncwarp();
        }
        asm volatile("barrier.cluster.arrive.relaxed.aligned;" ::: "memory");
        if (warp == 8 && lane == 0) {
            asm volatile("fence.proxy.async.shared::cta;" ::: "memory");
            for (int s = 0; s < G1_STAGES; s++) {
                mbar_expect_tx(full1(s), G1_STAGE_BYTES);
                tma_2d(base + s * G1_STAGE_BYTES, &prm.x, full1(s), s * 64, mblk * 128, policy(P_X));
            }
            TRACE(15);
        }
        asm volatile("setmaxnreg.dec.sync.aligned.u32 %0;" :: "n"(AUX_REGS));
        asm volatile("barrier.cluster.wait.acquire.aligned;" ::: "memory");

        if (warp == 8) {
            if (lane == 0) {
                TRACE(2);
                auto load_b1 = [&](int s, int nt, int k) {
                    const uint32_t dst = base + s * G1_STAGE_BYTES + A_BYTES + rank * 16384;
                    if (tile_is_qkv(nt)) tma_3d_mc(dst, &prm.wqkv, full1(s), k * 64, tile_index(nt) * 4 + rank * 2, policy(P_W1));
                    else tma_3d_mc(dst, rank ? &prm.wu : &prm.wg, full1(s), k * 64, tile_index(nt) * 2, policy(P_W1));
                };
                for (int s = 0; s < G1_STAGES; s++) load_b1(s, nslot, s);
                prefetch_map(&prm.xn); prefetch_map(&prm.wqkv); prefetch_map(rank ? &prm.wu : &prm.wg);
                prefetch_map(&prm.a2); prefetch_map(&prm.wo); prefetch_map(&prm.wd); prefetch_map(&prm.out);
                uint32_t ph = 0;
                for (int it = G1_STAGES; it < G1_TILES * G1_KSTEPS; it++) {
                    const int s = it & 3, k = it & 15;
                    if (it == G1_KSTEPS) { TRACE(14); mbar_wait(dep_bar, 0); TRACE(3); }
                    mbar_wait(empty1(s), ph);
                    mbar_expect_tx(full1(s), G1_STAGE_BYTES);
                    tma_2d(base + s * G1_STAGE_BYTES, it < G1_KSTEPS ? &prm.x : &prm.xn, full1(s), k * 64, mblk * 128,
                           policy(it < G1_KSTEPS ? P_X : (P_XN4 && it >= (G1_TILES - 1) * G1_KSTEPS)));
                    load_b1(s, (it >> 4) * 8 + nslot, k);
                    if (s == 3) ph ^= 1;
                }
                mbar_expect_tx(x_bar, 32768);
                tma_2d(aux, &prm.x, x_bar, nslot * 128, mblk * 128, policy(P_X));
                tma_2d(aux + 16384, &prm.x, x_bar, nslot * 128 + 64, mblk * 128, policy(P_X));
                TRACE(4);
                mbar_wait(dep_bar + 8, 0);
                TRACE(5);
                int q = 0; uint32_t ph2 = 1;
                for (int u = 0; u < G2_KSTEPS; u++) {
                    if (u == G2_LATE || u == G2_DSTEPS) {
                        TRACE(u == G2_LATE ? 6 : 32);
                        mbar_wait(dep_bar + (u == G2_LATE ? 16 : 24), 0);
                        TRACE(u == G2_LATE ? 7 : 33);
                    }
                    if (u < G2_STAGES) {
                        if (u == 0) mbar_wait(empty1(0), ph);
                        if (u == 1) mbar_wait(empty1(1), ph);
                        if (u == 3) mbar_wait(empty1(2), ph);
                        if (u == 4) mbar_wait(empty1(3), ph);
                    } else {
                        mbar_wait(empty2(q), ph2);
                    }
                    const uint32_t sa = stage2(q);
                    const bool down = u < G2_DSTEPS;
                    const int k = down ? u : u - G2_DSTEPS;
                    mbar_expect_tx(full2(q), G2_STAGE_BYTES);
                    tma_3d(sa, &prm.a2, full2(q), (down ? DM : 0) + k * 64, 0, mblk * 64, policy(P_A2));
                    tma_5d_mc(sa + A_BYTES + rank * 8192, down ? &prm.wd : &prm.wo, full2(q), nslot * 128 + rank * 64, k * 2, policy(P_W2));
                    if (++q == G2_STAGES) { q = 0; ph2 ^= 1; }
                }
                TRACE(8);
            }
        } else if (warp == 9) {
            if (lane == 0) {
                mbar_wait(sig_bar, 0);
                TRACE(11);
                flag_add(flags + F_LN * 512);
                for (int t = 0; t < G1_TILES; t++) {
                    mbar_wait(sig_bar, (t + 1) & 1);
                    const int nt = t * 8 + nslot;
                    flag_add(tile_is_qkv(nt) ? g_flags + F_QKV * 512 + (nt & 3) * 32
                                             : flags + (t < G1_TILES - 1 ? F_EARLY : F_LATE) * 512);
                }
            }
        } else {
            const int w = warp - 10;
            const int ld = nslot < 4 ? NQKV : DF;
            const __nv_bfloat16* wp = nslot < 4 ? prm.pwqkv + 2 * DM + nslot * 256 + lane * 8
                                                : (lane < 16 ? prm.pwg : prm.pwu) + (nslot - 4) * 128 + (lane & 15) * 8;
            wp += (size_t)(mblk * 64 + w * 32) * ld;
            const unsigned epoch = __ldcg(g_epoch + blockIdx.x * 16 + w) + 1;
            float cs[8];
#pragma unroll
            for (int d = 0; d < 8; d++) cs[d] = 0.f;
            mbar_wait(full1(0), 0);
#pragma unroll 1
            for (int i = 0; i < 4; i++) {
                uint4 v[8];
#pragma unroll
                for (int j = 0; j < 8; j++) v[j] = ldg_stream(wp + (size_t)(i * 8 + j) * ld, policy(P_W1));
#pragma unroll
                for (int j = 0; j < 8; j++) {
                    float f[8];
                    unpack8(v[j], f);
#pragma unroll
                    for (int d = 0; d < 8; d++) cs[d] += f[d];
                }
            }
            float4* cp = reinterpret_cast<float4*>(g_colsum + (mblk * 2 + w) * 2048 + nslot * 256 + lane * 8);
            cp[0] = make_float4(cs[0], cs[1], cs[2], cs[3]);
            cp[1] = make_float4(cs[4], cs[5], cs[6], cs[7]);
            __syncwarp();
            if (lane == 0) {
                if (w == 0) TRACE(34);
                flag_add(g_flags + F_CS * 512 + nslot * 32);
                flag_wait(g_flags + F_CS * 512 + nslot * 32, epoch * CNT_CS);
            }
            __syncwarp();
            const float4* gp = reinterpret_cast<const float4*>(g_colsum + nslot * 256 + w * 128) + lane;
            float4 c = make_float4(0.f, 0.f, 0.f, 0.f);
#pragma unroll 8
            for (int m = 0; m < 32; m++) {
                const float4 a = __ldcg(gp + m * 512);
                c.x += a.x; c.y += a.y; c.z += a.z; c.w += a.w;
            }
            const uint32_t ca = aux + (w * 8 + (lane >> 2)) * 64 + (lane & 1) * 32 + (lane & 2) * 4;
            sts64f(ca, c.x, c.y);
            sts64f(ca + 16, c.z, c.w);
            if (lane == 0) {
                flag_wait(flags + F_LN * 512, epoch * CNT_LN);
                if (w == 0) { fence_proxy_async(); mbar_arrive(dep_bar); }
            }
            __syncwarp();
            sts128(aux + 1024 + w * 512 + lane * 16, __ldcg(reinterpret_cast<const uint4*>(g_stats + mblk * 128 + w * 64) + lane));
            __syncwarp();
            if (lane == 0) {
                mbar_arrive(fold_bar);
                g_epoch[blockIdx.x * 16 + w] = epoch;
                if (w == 0) {
                    TRACE(35);
                    flag_wait(flags + F_EARLY * 512, epoch * CNT_EARLY);
                    fence_proxy_async(); mbar_arrive(dep_bar + 8);
                    flag_wait(flags + F_LATE * 512, epoch * CNT_LATE);
                    fence_proxy_async(); mbar_arrive(dep_bar + 16);
                    flag_wait(g_flags + F_O * 512, epoch * CNT_O);
                    fence_proxy_async(); mbar_arrive(dep_bar + 24);
                }
            }
        }
    } else {
        asm volatile("barrier.cluster.arrive.relaxed.aligned;" ::: "memory");
        asm volatile("setmaxnreg.inc.sync.aligned.u32 %0;" :: "n"(CONSUMER_REGS));
        const int wg = __shfl_sync(0xffffffffu, threadIdx.x >> 7, 0);
        const int cw = threadIdx.x >> 5;
        const int tid = threadIdx.x & 127;
        float acc[128];
        uint32_t pk[64];
#pragma unroll
        for (int i = 0; i < 64; i++) asm volatile("mov.b32 %0, 0;" : "=r"(pk[i]));
#pragma unroll
        for (int i = 0; i < 128; i++) asm volatile("mov.b32 %0, 0;" : "=f"(acc[i]));
        asm volatile("barrier.cluster.wait.acquire.aligned;" ::: "memory");

        const int orow = ((lane >> 2) & 1) * (SEQ / 2) + mblk * 64 + cw * 8 + (lane >> 3);
        __nv_bfloat16* optr = nullptr;
        auto release = [&](uint32_t bar) { if (tid < 2) mbar_arrive_cluster(bar, tid); };
        auto chunk_geglu = [&](int j) {
            const int c = j >> 1, h = j & 1;
            uint4 v;
            v.x = geglu2(pk[8 * c + h], pk[32 + 8 * c + h]);
            v.y = geglu2(pk[8 * c + 2 + h], pk[32 + 8 * c + 2 + h]);
            v.z = geglu2(pk[8 * c + 4 + h], pk[32 + 8 * c + 4 + h]);
            v.w = geglu2(pk[8 * c + 6 + h], pk[32 + 8 * c + 6 + h]);
            *reinterpret_cast<uint4*>(optr + h * 4 * K2 + c * 32) = v;
        };
        auto chunk_qkv = [&](int c) {
            *reinterpret_cast<uint4*>(optr + c * 32) = make_uint4(pk[8 * c], pk[8 * c + 2], pk[8 * c + 4], pk[8 * c + 6]);
            *reinterpret_cast<uint4*>(optr + 4 * NQKV + c * 32) = make_uint4(pk[8 * c + 1], pk[8 * c + 3], pk[8 * c + 5], pk[8 * c + 7]);
        };
        auto signal_stores = [&]() { __syncwarp(); if (lane == 0) mbar_arrive(sig_bar); };

        auto chunk_ln = [&](int k) {
            const int row = mblk * 128 + nslot * 16 + cw * 2;
            if (k == 0) {
                const uint4* xp = reinterpret_cast<const uint4*>(prm.px + (size_t)row * DM) + lane;
#pragma unroll
                for (int i = 0; i < 8; i++) {
                    const uint4 v = ldg_stream(xp + i * 32, policy(P_X));
                    pk[4 * i] = v.x; pk[4 * i + 1] = v.y; pk[4 * i + 2] = v.z; pk[4 * i + 3] = v.w;
                }
            } else if (k == 3) {
                float a = row_sum(pk), b = row_sum(pk + 16);
                warp_sum2(a, b);
                pk[32] = __float_as_uint(a * (1.f / DM)); pk[33] = __float_as_uint(b * (1.f / DM));
            } else if (k == 4) {
                pk[34] = __float_as_uint(row_sq(pk, __uint_as_float(pk[32])));
            } else if (k == 5) {
                float a = __uint_as_float(pk[34]), b = row_sq(pk + 16, __uint_as_float(pk[33]));
                warp_sum2(a, b);
                pk[34] = __float_as_uint(a); pk[35] = __float_as_uint(b);
            } else if (k == 6) {
                row_store(pk, __uint_as_float(pk[32]), row_inv(__uint_as_float(pk[34])), row, lane);
            } else if (k == 7) {
                row_store(pk + 16, __uint_as_float(pk[33]), row_inv(__uint_as_float(pk[35])), row + 1, lane);
                signal_stores();
            }
        };

        int pending = 0;
#pragma unroll 1
        for (int t = 0; t < G1_TILES; t++) {
#pragma unroll
            for (int k = 0; k < G1_KSTEPS; k++) {
                const int s = k & 3;
                mbar_wait(full1(s), (k >> 2) & 1);
                if (t == 0 && k == 0 && threadIdx.x == 0) TRACE(12);
                if (wg == 1 && k == G1_KSTEPS - G1_SKEW) asm volatile("bar.sync 1, 256;" ::: "memory");
                const uint64_t da = desc_a(base + s * G1_STAGE_BYTES + wg * 8192);
                const uint64_t db = desc_b(base + s * G1_STAGE_BYTES + A_BYTES);
                wg_fence();
#pragma unroll
                for (int kk = 0; kk < 4; kk++) wgmma_n256(acc, da + kk * 2, db + kk * 128, (k | kk) != 0);
                wg_commit();
                if (wg == 0 && k == G1_KSTEPS - 1) asm volatile("bar.arrive 1, 256;" ::: "memory");
                if (k <= 7 && pending == 0) chunk_ln(k);
                if (k >= 1 && k <= 8) {
                    if (pending == 2) chunk_geglu(k - 1);
                    else if (pending == 1) chunk_qkv(k - 1);
                    if (k == 8 && pending) signal_stores();
                }
                wg_wait<1>();
                if (k > 0) release(empty1((k - 1) & 3));
            }
            if (t == 0) mbar_wait(fold_bar, 0);
            wg_wait<0>();
            fence_regs(acc);
            release(empty1(3));
            if (t == 0) {
                const uint32_t sp = aux + 1024 + (cw * 16 + (lane >> 2)) * 8;
                const float2 sa = lds64f(sp), sb = lds64f(sp + 64);
#pragma unroll
                for (int j = 0; j < 16; j++) {
                    const uint4 c = lds128(aux + j * 64 + (lane & 3) * 16);
                    const float c0 = __uint_as_float(c.x), c1 = __uint_as_float(c.y);
                    const float c2 = __uint_as_float(c.z), c3 = __uint_as_float(c.w);
                    const float* a = acc + 8 * j;
                    pk[4 * j] = pack_bf16(fmaf(sa.x, c0, a[0]) * sa.y, fmaf(sa.x, c1, a[1]) * sa.y);
                    pk[4 * j + 1] = pack_bf16(fmaf(sb.x, c0, a[2]) * sb.y, fmaf(sb.x, c1, a[3]) * sb.y);
                    pk[4 * j + 2] = pack_bf16(fmaf(sa.x, c2, a[4]) * sa.y, fmaf(sa.x, c3, a[5]) * sa.y);
                    pk[4 * j + 3] = pack_bf16(fmaf(sb.x, c2, a[6]) * sb.y, fmaf(sb.x, c3, a[7]) * sb.y);
                }
            } else {
#pragma unroll
                for (int i = 0; i < 64; i++) pk[i] = pack_bf16(acc[2 * i], acc[2 * i + 1]);
            }
            const int nt = t * 8 + nslot;
            pending = tile_is_qkv(nt) ? 1 : 2;
            optr = pending == 1 ? g_qkv + (size_t)orow * NQKV + tile_index(nt) * 256 + (lane & 3) * 8
                                : g_a2 + (size_t)orow * K2 + DM + tile_index(nt) * 128 + (lane & 3) * 8;
            if (tid == 0) TRACE(16 + wg * 8 + t);
        }

        float accd[64], accs[64];
#pragma unroll
        for (int i = 0; i < 64; i++) accd[i] = 0.f;
#pragma unroll
        for (int u = 0; u < 9; u++) {
            const int q = u % G2_STAGES;
            mbar_wait(full2(q), (u / G2_STAGES) & 1);
            const uint64_t da = desc_a(stage2(q) + wg * 8192), db = desc_b(stage2(q) + A_BYTES);
            wg_fence();
#pragma unroll
            for (int kk = 0; kk < 4; kk++) wgmma_n128(accd, da + kk * 2, db + kk * 128, (u | kk) != 0);
            wg_commit();
            if (u >= 1) { chunk_geglu(u - 1); if (u == 8) signal_stores(); }
            wg_wait<1>();
            if (u > 0) release(empty2((u - 1) % G2_STAGES));
        }
        {
            int q = 9 % G2_STAGES, qp = 8 % G2_STAGES; uint32_t ph = (9 / G2_STAGES) & 1;
#pragma unroll 1
            for (int u = 9; u < G2_DSTEPS; u++) {
                mbar_wait(full2(q), ph);
                const uint64_t da = desc_a(stage2(q) + wg * 8192), db = desc_b(stage2(q) + A_BYTES);
                wg_fence();
#pragma unroll
                for (int kk = 0; kk < 4; kk++) wgmma_n128(accd, da + kk * 2, db + kk * 128, 1);
                wg_commit();
                wg_wait<1>();
                release(empty2(qp));
                qp = q;
                if (++q == G2_STAGES) { q = 0; ph ^= 1; }
            }
        }
        if (tid == 0) TRACE(16 + wg * 8 + 5);
#pragma unroll
        for (int i = 0; i < 64; i++) accs[i] = 0.f;
        uint32_t gk[32], xr[32];
        const uint32_t xs = aux + cw * 2048;
        const uint32_t xrow = xs + ((lane & 7) + ((lane >> 3) & 1) * 8) * 128;
        auto xaddr = [&](int j) { return xrow + (j >> 2) * 16384 + (((((j & 3) * 2) + (lane >> 4)) ^ (lane & 7)) << 4); };
#pragma unroll
        for (int u = G2_DSTEPS; u < G2_KSTEPS; u++) {
            const int q = u % G2_STAGES, v = u - G2_DSTEPS;
            mbar_wait(full2(q), (u / G2_STAGES) & 1);
            if (G2_SKEW > 0 && wg == 1 && u == G2_KSTEPS - G2_SKEW) asm volatile("bar.sync 1, 256;" ::: "memory");
            const uint64_t da = desc_a(stage2(q) + wg * 8192), db = desc_b(stage2(q) + A_BYTES);
            wg_fence();
#pragma unroll
            for (int kk = 0; kk < 4; kk++) wgmma_n128(accs, da + kk * 2, db + kk * 128, (v | kk) != 0);
            wg_commit();
            if (G2_SKEW > 0 && wg == 0 && u == G2_KSTEPS - 1) asm volatile("bar.arrive 1, 256;" ::: "memory");
            if (v >= 1 && v <= 8) {
#pragma unroll
                for (int i = 4 * (v - 1); i < 4 * v; i++) {
                    const uint32_t d2 = pack_bf16(accd[2 * i], accd[2 * i + 1]);
                    gk[i] = pack_bf16(silu(bf_lo(d2)), silu(bf_hi(d2)));
                }
            }
            if (v == 9) mbar_wait(x_bar, 0);
            if (v >= 9 && v <= 12) {
#pragma unroll
                for (int j = 2 * (v - 9); j < 2 * (v - 8); j++)
                    asm volatile("ldmatrix.sync.aligned.m8n8.x4.shared.b16 {%0,%1,%2,%3}, [%4];"
                                 : "=r"(xr[4 * j]), "=r"(xr[4 * j + 1]), "=r"(xr[4 * j + 2]), "=r"(xr[4 * j + 3])
                                 : "r"(xaddr(j)) : "memory");
            }
            wg_wait<1>();
            if (v == 0) fence_regs(accd);
            if (u - 1 + G2_STAGES < G2_KSTEPS) release(empty2((u - 1) % G2_STAGES));
        }
        wg_wait<0>();
        fence_regs(accs);
        if (tid == 0) TRACE(16 + wg * 8 + 6);
#pragma unroll
        for (int j = 0; j < 8; j++) {
            uint32_t r[4];
#pragma unroll
            for (int i = 0; i < 4; i++) {
                const int e = j * 4 + i;
                r[i] = add_bf16x2(xr[e], mul_bf16x2(pack_bf16(accs[2 * e], accs[2 * e + 1]), gk[e]));
            }
            asm volatile("stmatrix.sync.aligned.m8n8.x4.shared.b16 [%0], {%1,%2,%3,%4};"
                         :: "r"(xaddr(j)), "r"(r[0]), "r"(r[1]), "r"(r[2]), "r"(r[3]) : "memory");
            if (j == 3 || j == 7) {
                asm volatile("fence.proxy.async.shared::cta;" ::: "memory");
                __syncwarp();
                if (lane == 0) {
                    tma_store_2d(&prm.out, xs + (j >> 2) * 16384, nslot * 128 + (j >> 2) * 64, mblk * 128 + cw * 16);
                    asm volatile("cp.async.bulk.commit_group;" ::: "memory");
                }
            }
        }
        if (lane == 0) asm volatile("cp.async.bulk.wait_group.read 0;" ::: "memory");
        if (tid == 0) { TRACE(16 + wg * 8 + 7); if (wg == 1) TRACE_GT(13); }
    }
}

typedef CUresult (*EncodeFn)(CUtensorMap*, CUtensorMapDataType, cuuint32_t, void*, const cuuint64_t*, const cuuint64_t*,
                             const cuuint32_t*, const cuuint32_t*, CUtensorMapInterleave, CUtensorMapSwizzle,
                             CUtensorMapL2promotion, CUtensorMapFloatOOBfill);

void encode(EncodeFn fn, CUtensorMap* m, const void* ptr, int rank, const cuuint64_t* dims, const cuuint64_t* strides,
            const cuuint32_t* box) {
    const cuuint32_t es[5] = {1, 1, 1, 1, 1};
    fn(m, CU_TENSOR_MAP_DATA_TYPE_BFLOAT16, rank, const_cast<void*>(ptr), dims, strides, box, es,
       CU_TENSOR_MAP_INTERLEAVE_NONE, CU_TENSOR_MAP_SWIZZLE_128B, CU_TENSOR_MAP_L2_PROMOTION_L2_128B,
       CU_TENSOR_MAP_FLOAT_OOB_FILL_NONE);
}
void encode_2d(EncodeFn fn, CUtensorMap* m, const void* ptr, int cols, int box_rows) {
    const cuuint64_t dims[2] = {(cuuint64_t)cols, SEQ}, strides[1] = {(cuuint64_t)cols * 2};
    const cuuint32_t box[2] = {64, (cuuint32_t)box_rows};
    encode(fn, m, ptr, 2, dims, strides, box);
}
void encode_w1(EncodeFn fn, CUtensorMap* m, const void* ptr, int cols) {
    const cuuint64_t dims[3] = {64, DM, (cuuint64_t)cols / 64}, strides[2] = {(cuuint64_t)cols * 2, 128};
    const cuuint32_t box[3] = {64, 64, 2};
    encode(fn, m, ptr, 3, dims, strides, box);
}
void encode_qk(EncodeFn fn, CUtensorMap* m, const void* ptr) {
    const cuuint64_t dims[3] = {DM, SEQ, 3}, strides[2] = {NQKV * 2, DM * 2};
    const cuuint32_t box[3] = {64, 16, 2};
    encode(fn, m, ptr, 3, dims, strides, box);
}
void encode_a2(EncodeFn fn, CUtensorMap* m, const void* ptr) {
    const cuuint64_t dims[3] = {K2, 2, SEQ / 2}, strides[2] = {(cuuint64_t)SEQ * K2, K2 * 2};
    const cuuint32_t box[3] = {64, 2, 64};
    encode(fn, m, ptr, 3, dims, strides, box);
}
void encode_w2(EncodeFn fn, CUtensorMap* m, const void* ptr, int rows) {
    const cuuint64_t rb = DM * 2;
    const cuuint64_t dims[5] = {DM, 2, 4, 4, (cuuint64_t)rows / 32}, strides[4] = {rb, 8 * rb, 2 * rb, 32 * rb};
    const cuuint32_t box[5] = {64, 2, 4, 4, 2};
    encode(fn, m, ptr, 5, dims, strides, box);
}

}

extern "C" void kernel_launch(void* const* d_in, const int* in_sizes, int n_in, void* d_out, int out_size) {
    (void)in_sizes; (void)n_in; (void)out_size;
    static EncodeFn fn = nullptr;
    static void *p_xn = nullptr, *p_qkv = nullptr, *p_a2 = nullptr;
    if (!fn) {
        cudaDriverEntryPointQueryResult st;
        cudaGetDriverEntryPoint("cuTensorMapEncodeTiled", (void**)&fn, cudaEnableDefault, &st);
        cudaGetSymbolAddress(&p_xn, g_xn);
        cudaGetSymbolAddress(&p_qkv, g_qkv);
        cudaGetSymbolAddress(&p_a2, g_a2);
        cudaFuncSetAttribute(fused_kernel, cudaFuncAttributeMaxDynamicSharedMemorySize, SMEM_BYTES);
    }
    Params prm;
    encode_2d(fn, &prm.x, d_in[0], DM, 128);
    encode_2d(fn, &prm.xn, p_xn, DM, 128);
    encode_w1(fn, &prm.wqkv, d_in[1], NQKV);
    encode_w1(fn, &prm.wg, d_in[4], DF);
    encode_w1(fn, &prm.wu, d_in[5], DF);
    encode_qk(fn, &prm.qk, p_qkv);
    encode_2d(fn, &prm.v, p_qkv, NQKV, 16);
    encode_2d(fn, &prm.o, p_a2, K2, 16);
    encode_a2(fn, &prm.a2, p_a2);
    encode_w2(fn, &prm.wo, d_in[2], DM);
    encode_w2(fn, &prm.wd, d_in[6], DF);
    encode_2d(fn, &prm.out, d_out, DM, 16);
    prm.px = (const __nv_bfloat16*)d_in[0];
    prm.pwqkv = (const __nv_bfloat16*)d_in[1];
    prm.pwg = (const __nv_bfloat16*)d_in[4];
    prm.pwu = (const __nv_bfloat16*)d_in[5];
    prm.zero = 0;
    fused_kernel<<<NCTA, 384, SMEM_BYTES>>>(prm);
}
```

```cpp
#include <cuda_runtime.h>
#include <cuda_bf16.h>
#include <cuda.h>
#include <stdint.h>

#define P_W1 1
#define P_X 1
#define P_XN4 1
#define P_W2 1
#define P_A2 1
#define P_QKV 1

namespace {

constexpr int SEQ = 2048, DM = 1024, DF = 3584, K2 = DM + DF, NQKV = 3 * DM;
constexpr int NGEMM = 128, NCTA = 132;
constexpr int W_STAGES = 4, W_STAGE_BYTES = 49152, KSTEPS = 16, W_TILES = 4;
constexpr int N_STAGES = 6, N_STAGE_BYTES = 32768;
constexpr int U_D = 16, U_LATE = 48, U_S = 72, U_END = 88;
constexpr int A_BYTES = 16384;
constexpr int AUX_OFF = W_STAGES * W_STAGE_BYTES;
constexpr int BAR_OFF = AUX_OFF + 32768;
constexpr int SMEM_BYTES = BAR_OFF + 1024 + 512;
constexpr int W_SKEW = 2, S_SKEW = 2;
constexpr int CONSUMER_REGS = 224, AUX_REGS = 56;
constexpr int ATT_SLOT = 8192;

enum { F_LN = 0, F_QKV = 1, F_EARLY = 2, F_LATE = 3, F_O = 4, F_CS = 5 };
constexpr unsigned CNT_LN = 8, CNT_QKV = 128, CNT_EARLY = 16, CNT_LATE = 16, CNT_O = 48, CNT_CS = 16;

__device__ __align__(1024) __nv_bfloat16 g_xn[SEQ * DM];
__device__ __align__(1024) __nv_bfloat16 g_qkv[SEQ * NQKV];
__device__ __align__(1024) __nv_bfloat16 g_a2[SEQ * K2];
__device__ __align__(128) float2 g_stats[SEQ];
__device__ __align__(128) float g_colsum[16 * DM];
__device__ __align__(128) unsigned g_flags[6 * 16 * 32];
__device__ __align__(128) unsigned g_epoch[NCTA * 16];

#define TRACE(slot) do {} while (0)
#define TRACE_GT(slot) do {} while (0)

__device__ __forceinline__ uint32_t smem_u32(const void* p) { return (uint32_t)__cvta_generic_to_shared(p); }
__device__ __forceinline__ void mbar_init(uint32_t bar, uint32_t cnt) {
    asm volatile("mbarrier.init.shared::cta.b64 [%0], %1;" :: "r"(bar), "r"(cnt) : "memory");
}
__device__ __forceinline__ void mbar_expect_tx(uint32_t bar, uint32_t bytes) {
    asm volatile("mbarrier.arrive.expect_tx.shared::cta.b64 _, [%0], %1;" :: "r"(bar), "r"(bytes) : "memory");
}
__device__ __forceinline__ void mbar_arrive(uint32_t bar) {
    asm volatile("mbarrier.arrive.shared::cta.b64 _, [%0];" :: "r"(bar) : "memory");
}
__device__ __forceinline__ void mbar_arrive_cluster(uint32_t bar, uint32_t cta) {
    asm volatile("{\n.reg .b32 ra;\nmapa.shared::cluster.u32 ra, %0, %1;\nmbarrier.arrive.shared::cluster.b64 _, [ra];\n}"
                 :: "r"(bar), "r"(cta) : "memory");
}
__device__ __forceinline__ bool mbar_try_wait(uint32_t bar, uint32_t parity) {
    uint32_t ok;
    asm volatile("{\n.reg .pred p;\nmbarrier.try_wait.parity.shared::cta.b64 p, [%1], %2;\nselp.u32 %0, 1, 0, p;\n}"
                 : "=r"(ok) : "r"(bar), "r"(parity) : "memory");
    return ok;
}
__device__ __forceinline__ void mbar_wait(uint32_t bar, uint32_t parity) {
    int spins = 0;
    while (!mbar_try_wait(bar, parity)) { if (++spins > (1 << 17)) break; }
}
__device__ __forceinline__ void flag_wait(const unsigned* p, unsigned target) {
    for (int spins = 0; spins < (1 << 19); spins++) {
        unsigned v;
        asm volatile("ld.acquire.gpu.global.u32 %0, [%1];" : "=r"(v) : "l"(p) : "memory");
        if ((int)(v - target) >= 0) break;
        __nanosleep(64);
    }
}
__device__ __forceinline__ void flag_add(unsigned* p) {
    asm volatile("red.release.gpu.global.add.u32 [%0], 1;" :: "l"(p) : "memory");
}
__device__ __forceinline__ bool elect_one() {
    uint32_t ok;
    asm volatile("{\n.reg .pred p;\nelect.sync _|p, 0xffffffff;\nselp.u32 %0, 1, 0, p;\n}" : "=r"(ok));
    return ok;
}
__device__ __forceinline__ void fence_proxy_async() { asm volatile("fence.proxy.async;" ::: "memory"); }
__device__ __forceinline__ uint4 lds128(uint32_t addr) {
    uint4 v;
    asm volatile("ld.shared.v4.u32 {%0,%1,%2,%3}, [%4];" : "=r"(v.x), "=r"(v.y), "=r"(v.z), "=r"(v.w) : "r"(addr) : "memory");
    return v;
}
__device__ __forceinline__ float2 lds64f(uint32_t addr) {
    float2 v;
    asm volatile("ld.shared.v2.f32 {%0,%1}, [%2];" : "=f"(v.x), "=f"(v.y) : "r"(addr) : "memory");
    return v;
}
__device__ __forceinline__ void sts128(uint32_t addr, uint4 v) {
    asm volatile("st.shared.v4.u32 [%0], {%1,%2,%3,%4};" :: "r"(addr), "r"(v.x), "r"(v.y), "r"(v.z), "r"(v.w) : "memory");
}
__device__ __forceinline__ void sts64f(uint32_t addr, float a, float b) {
    asm volatile("st.shared.v2.f32 [%0], {%1,%2};" :: "r"(addr), "f"(a), "f"(b) : "memory");
}

__device__ __forceinline__ uint64_t policy(bool stream) {
    uint64_t p;
    if (stream) asm("createpolicy.fractional.L2::evict_first.b64 %0, 1.0;" : "=l"(p));
    else asm("createpolicy.fractional.L2::evict_normal.b64 %0, 1.0;" : "=l"(p));
    return p;
}
__device__ __forceinline__ void tma_2d(uint32_t dst, const CUtensorMap* m, uint32_t bar, int c0, int c1, uint64_t pol) {
    asm volatile("cp.async.bulk.tensor.2d.shared::cluster.global.mbarrier::complete_tx::bytes.L2::cache_hint"
                 " [%0], [%1, {%3, %4}], [%2], %5;"
                 :: "r"(dst), "l"(m), "r"(bar), "r"(c0), "r"(c1), "l"(pol) : "memory");
}
__device__ __forceinline__ void tma_3d(uint32_t dst, const CUtensorMap* m, uint32_t bar, int c0, int c1, int c2, uint64_t pol) {
    asm volatile("cp.async.bulk.tensor.3d.shared::cluster.global.mbarrier::complete_tx::bytes.L2::cache_hint"
                 " [%0], [%1, {%3, %4, %5}], [%2], %6;"
                 :: "r"(dst), "l"(m), "r"(bar), "r"(c0), "r"(c1), "r"(c2), "l"(pol) : "memory");
}
__device__ __forceinline__ void tma_3d_mc(uint32_t dst, const CUtensorMap* m, uint32_t bar, int c1, int c2, uint64_t pol) {
    asm volatile("cp.async.bulk.tensor.3d.shared::cluster.global.mbarrier::complete_tx::bytes.multicast::cluster.L2::cache_hint"
                 " [%0], [%1, {%3, %4, %5}], [%2], %6, %7;"
                 :: "r"(dst), "l"(m), "r"(bar), "r"(0), "r"(c1), "r"(c2), "h"((uint16_t)3), "l"(pol) : "memory");
}
__device__ __forceinline__ void tma_5d_mc(uint32_t dst, const CUtensorMap* m, uint32_t bar, int c0, int c4, uint64_t pol) {
    asm volatile("cp.async.bulk.tensor.5d.shared::cluster.global.mbarrier::complete_tx::bytes.multicast::cluster.L2::cache_hint"
                 " [%0], [%1, {%3, %4, %4, %4, %5}], [%2], %6, %7;"
                 :: "r"(dst), "l"(m), "r"(bar), "r"(c0), "r"(0), "r"(c4), "h"((uint16_t)3), "l"(pol) : "memory");
}
__device__ __forceinline__ void tma_store_2d(const CUtensorMap* m, uint32_t src, int c0, int c1) {
    asm volatile("cp.async.bulk.tensor.2d.global.shared::cta.bulk_group [%0, {%2, %3}], [%1];"
                 :: "l"(m), "r"(src), "r"(c0), "r"(c1) : "memory");
}
__device__ __forceinline__ uint4 ldg_stream(const void* p, uint64_t pol) {
    uint4 v;
    asm volatile("ld.global.nc.L1::no_allocate.L2::cache_hint.v4.u32 {%0,%1,%2,%3}, [%4], %5;"
                 : "=r"(v.x), "=r"(v.y), "=r"(v.z), "=r"(v.w) : "l"(p), "l"(pol));
    return v;
}
__device__ __forceinline__ void prefetch_map(const CUtensorMap* m) {
    asm volatile("prefetch.tensormap [%0];" :: "l"(m) : "memory");
}
__device__ __forceinline__ void wg_fence() { asm volatile("wgmma.fence.sync.aligned;" ::: "memory"); }
__device__ __forceinline__ void wg_commit() { asm volatile("wgmma.commit_group.sync.aligned;" ::: "memory"); }
template <int N> __device__ __forceinline__ void wg_wait() { asm volatile("wgmma.wait_group.sync.aligned %0;" :: "n"(N) : "memory"); }

__device__ __forceinline__ uint64_t desc_a(uint32_t addr) {
    return (uint64_t)((addr & 0x3FFFF) >> 4) | (1ull << 16) | (64ull << 32) | (1ull << 62);
}
__device__ __forceinline__ uint64_t desc_b(uint32_t addr) {
    return (uint64_t)((addr & 0x3FFFF) >> 4) | (512ull << 16) | (64ull << 32) | (1ull << 62);
}

#define R8(d, o) "+f"(d[o]), "+f"(d[o+1]), "+f"(d[o+2]), "+f"(d[o+3]), "+f"(d[o+4]), "+f"(d[o+5]), "+f"(d[o+6]), "+f"(d[o+7])
#define R32(d, o) R8(d, o), R8(d, o+8), R8(d, o+16), R8(d, o+24)
#define R64(d, o) R32(d, o), R32(d, o+32)

__device__ __forceinline__ void wgmma_n256(float (&d)[128], uint64_t da, uint64_t db, int scale_d) {
    asm volatile("{\n.reg .pred p;\nsetp.ne.b32 p, %130, 0;\n"
        "wgmma.mma_async.sync.aligned.m64n256k16.f32.bf16.bf16 "
        "{%0,%1,%2,%3,%4,%5,%6,%7,%8,%9,%10,%11,%12,%13,%14,%15,%16,%17,%18,%19,%20,%21,%22,%23,%24,%25,%26,%27,%28,%29,%30,%31,"
        "%32,%33,%34,%35,%36,%37,%38,%39,%40,%41,%42,%43,%44,%45,%46,%47,%48,%49,%50,%51,%52,%53,%54,%55,%56,%57,%58,%59,%60,%61,%62,%63,"
        "%64,%65,%66,%67,%68,%69,%70,%71,%72,%73,%74,%75,%76,%77,%78,%79,%80,%81,%82,%83,%84,%85,%86,%87,%88,%89,%90,%91,%92,%93,%94,%95,"
        "%96,%97,%98,%99,%100,%101,%102,%103,%104,%105,%106,%107,%108,%109,%110,%111,%112,%113,%114,%115,%116,%117,%118,%119,%120,%121,%122,%123,%124,%125,%126,%127},"
        " %128, %129, p, 1, 1, 0, 1;\n}"
        : R64(d, 0), R64(d, 64) : "l"(da), "l"(db), "r"(scale_d));
}
__device__ __forceinline__ void wgmma_n128(float (&d)[64], uint64_t da, uint64_t db, int scale_d) {
    asm volatile("{\n.reg .pred p;\nsetp.ne.b32 p, %66, 0;\n"
        "wgmma.mma_async.sync.aligned.m64n128k16.f32.bf16.bf16 "
        "{%0,%1,%2,%3,%4,%5,%6,%7,%8,%9,%10,%11,%12,%13,%14,%15,%16,%17,%18,%19,%20,%21,%22,%23,%24,%25,%26,%27,%28,%29,%30,%31,"
        "%32,%33,%34,%35,%36,%37,%38,%39,%40,%41,%42,%43,%44,%45,%46,%47,%48,%49,%50,%51,%52,%53,%54,%55,%56,%57,%58,%59,%60,%61,%62,%63},"
        " %64, %65, p, 1, 1, 0, 1;\n}"
        : R64(d, 0) : "l"(da), "l"(db), "r"(scale_d));
}

__device__ __forceinline__ uint32_t pack_bf16(float lo, float hi) {
    uint32_t r; asm("cvt.rn.bf16x2.f32 %0, %1, %2;" : "=r"(r) : "f"(hi), "f"(lo)); return r;
}
__device__ __forceinline__ float bf_lo(uint32_t v) { return __uint_as_float(v << 16); }
__device__ __forceinline__ float bf_hi(uint32_t v) { return __uint_as_float(v & 0xffff0000u); }
__device__ __forceinline__ float round_bf16(float v) { return bf_lo(pack_bf16(v, 0.f)); }
__device__ __forceinline__ uint32_t mul_bf16x2(uint32_t a, uint32_t b) {
    uint32_t r; asm("mul.rn.bf16x2 %0, %1, %2;" : "=r"(r) : "r"(a), "r"(b)); return r;
}
__device__ __forceinline__ uint32_t add_bf16x2(uint32_t a, uint32_t b) {
    uint32_t r; asm("add.rn.bf16x2 %0, %1, %2;" : "=r"(r) : "r"(a), "r"(b)); return r;
}
__device__ __forceinline__ uint32_t sub_bf16x2(uint32_t a, uint32_t b) {
    uint32_t r; asm("sub.rn.bf16x2 %0, %1, %2;" : "=r"(r) : "r"(a), "r"(b)); return r;
}
__device__ __forceinline__ float tanh_fast(float x) { float r; asm("tanh.approx.f32 %0, %1;" : "=f"(r) : "f"(x)); return r; }
__device__ __forceinline__ float gelu_tanh(float g) {
    float t = fmaf(g * g, 0.044715f * 0.7978845608f, 0.7978845608f) * g;
    float hg = 0.5f * g;
    return fmaf(hg, tanh_fast(t), hg);
}
__device__ __forceinline__ uint32_t geglu2(uint32_t g2, uint32_t u2) {
    return mul_bf16x2(pack_bf16(gelu_tanh(bf_lo(g2)), gelu_tanh(bf_hi(g2))), u2);
}
__device__ __forceinline__ float silu(float d) {
    float hd = 0.5f * d;
    return fmaf(hd, tanh_fast(hd), hd);
}
__device__ __forceinline__ float ex2_fast(float x) { float r; asm("ex2.approx.ftz.f32 %0, %1;" : "=f"(r) : "f"(x)); return r; }
__device__ __forceinline__ void unpack8(uint4 v, float (&f)[8]) {
    f[0] = bf_lo(v.x); f[1] = bf_hi(v.x); f[2] = bf_lo(v.y); f[3] = bf_hi(v.y);
    f[4] = bf_lo(v.z); f[5] = bf_hi(v.z); f[6] = bf_lo(v.w); f[7] = bf_hi(v.w);
}
template <int N> __device__ __forceinline__ void fence_regs(float (&d)[N]) {
#pragma unroll
    for (int i = 0; i < N; i++) asm volatile("" : "+f"(d[i]) :: "memory");
}

__device__ __forceinline__ float rcp_fast(float x) { float r; asm("rcp.approx.ftz.f32 %0, %1;" : "=f"(r) : "f"(x)); return r; }
__device__ __forceinline__ uint32_t max_bf16x2(uint32_t a, uint32_t b) {
    uint32_t r; asm("max.bf16x2 %0, %1, %2;" : "=r"(r) : "r"(a), "r"(b)); return r;
}
__device__ __forceinline__ uint4 ldsm4(uint32_t addr) {
    uint4 v;
    asm volatile("ldmatrix.sync.aligned.m8n8.x4.shared.b16 {%0,%1,%2,%3}, [%4];"
                 : "=r"(v.x), "=r"(v.y), "=r"(v.z), "=r"(v.w) : "r"(addr) : "memory");
    return v;
}
__device__ __forceinline__ uint4 ldsm4_t(uint32_t addr) {
    uint4 v;
    asm volatile("ldmatrix.sync.aligned.m8n8.x4.trans.shared.b16 {%0,%1,%2,%3}, [%4];"
                 : "=r"(v.x), "=r"(v.y), "=r"(v.z), "=r"(v.w) : "r"(addr) : "memory");
    return v;
}
__device__ __forceinline__ void mma_16816(float (&c)[4], uint32_t a0, uint32_t a1, uint32_t a2, uint32_t a3, uint32_t b0, uint32_t b1) {
    asm("mma.sync.aligned.m16n8k16.row.col.f32.bf16.bf16.f32 {%0,%1,%2,%3}, {%4,%5,%6,%7}, {%8,%9}, {%0,%1,%2,%3};"
        : "+f"(c[0]), "+f"(c[1]), "+f"(c[2]), "+f"(c[3]) : "r"(a0), "r"(a1), "r"(a2), "r"(a3), "r"(b0), "r"(b1));
}
__device__ __forceinline__ void mma_1688(float (&c)[4], uint32_t a0, uint32_t a1, uint32_t b0) {
    asm("mma.sync.aligned.m16n8k8.row.col.f32.bf16.bf16.f32 {%0,%1,%2,%3}, {%4,%5}, {%6}, {%0,%1,%2,%3};"
        : "+f"(c[0]), "+f"(c[1]), "+f"(c[2]), "+f"(c[3]) : "r"(a0), "r"(a1), "r"(b0));
}
__device__ __forceinline__ void qk_tile(float (&c)[4], const uint4& q0, const uint4& q1, const uint4& k, float init) {
    c[0] = c[1] = c[2] = c[3] = init;
    mma_16816(c, q0.x, q0.y, q0.z, q0.w, k.x, k.y);
    mma_16816(c, q1.x, q1.y, q1.z, q1.w, k.z, k.w);
}
__device__ __forceinline__ uint32_t scaled_logits(bool first, float a0, float a1, float b0, float b1) {
    uint32_t p, r;
    asm("{\n.reg .pred p;\nsetp.ne.u32 p, %1, 0;\n@p cvt.rn.bf16x2.f32 %0, %3, %2;\n@!p cvt.rn.bf16x2.f32 %0, %5, %4;\n}"
        : "=r"(p) : "r"((uint32_t)first), "f"(a0), "f"(a1), "f"(b0), "f"(b1));
    asm("fma.rn.bf16x2 %0, %1, %2, %3;" : "=r"(r) : "r"(p), "r"(0x3e353e35u), "r"(mul_bf16x2(p, 0x379e379eu)));
    return r;
}
template <typename T> __device__ __forceinline__ T uniform(T v) { return __shfl_sync(0xffffffffu, v, 0); }

__device__ __forceinline__ void attention(const CUtensorMap* maps, uint32_t base, uint32_t zero, int grp, int warp, int lane) {
    constexpr float LOG2E = 1.4426950408889634f;
    const int g = lane >> 2, t = lane & 3;
    const bool up0 = 2 * t > g, up1 = 2 * t + 1 > g;
    const uint32_t keep = (up0 ? 0x0000ffffu : 0u) | (up1 ? 0xffff0000u : 0u);
    const uint32_t buf = base + warp * 2 * ATT_SLOT, bar = base + AUX_OFF + warp * 16;
    const uint32_t qoff = (lane & 15) * 128 + (((lane >> 4) ^ (lane & 7)) << 4);
    const uint32_t koff = 2048 + (lane & 7) * 128 + (((lane >> 3) ^ (lane & 7)) << 4);
    const int col = uniform((grp * 4 + warp / 3) * 64), first = uniform(warp % 3 * 43 * 16), last = min(first + 43 * 16, SEQ);
    const CUtensorMap* const mqk = reinterpret_cast<const CUtensorMap*>(uniform(reinterpret_cast<uint64_t>(maps)));
    const CUtensorMap *const mv = mqk + 1, *const mo = mqk + 2;
    const uint64_t pol = policy(P_QKV);
    uint4 kp[2], vp[2];
    uint32_t l0[2], l1[2], m[2];
    float s[2][3][4];
    auto scores = [&](uint32_t st, int row) {
        const float before = (row & 1023) == 0 ? -5.656854e9f : 0.f;
#pragma unroll
        for (int h = 0; h < 2; h++) {
            const uint4 q0 = ldsm4(st + (qoff ^ (h * 64))), q1 = ldsm4(st + (qoff ^ (h * 64 + 32)));
            const uint4 k0 = ldsm4(st + (koff ^ (h * 64))), k1 = ldsm4(st + 1024 + (koff ^ (h * 64)));
            qk_tile(s[h][0], q0, q1, kp[h], before);
            qk_tile(s[h][1], q0, q1, k0, 0.f);
            qk_tile(s[h][2], q0, q1, k1, 0.f);
            kp[h] = k1;
        }
    };
    auto logits = [&]() {
#pragma unroll
        for (int h = 0; h < 2; h++) {
            l0[h] = scaled_logits(up0, s[h][0][0], s[h][1][2], s[h][1][0], s[h][2][2]);
            l1[h] = scaled_logits(up1, s[h][0][1], s[h][1][3], s[h][1][1], s[h][2][3]);
            m[h] = max_bf16x2(l0[h], l1[h]);
            m[h] = max_bf16x2(m[h], __shfl_xor_sync(0xffffffffu, m[h], 1));
        }
    };
    auto row_max = [&]() {
#pragma unroll
        for (int h = 0; h < 2; h++) m[h] = max_bf16x2(m[h], __shfl_xor_sync(0xffffffffu, m[h], 2));
    };
    auto exchange = [&](uint32_t st, uint32_t b, int row, int store, int load) {
        asm volatile("{\n.reg .pred e, p, q;\n"
            "fence.proxy.async.shared::cta;\n"
            "bar.warp.sync 0xffffffff;\n"
            "elect.sync _|e, 0xffffffff;\n"
            "setp.ne.and.b32 p, %10, 0, e;\n"
            "setp.ne.and.b32 q, %11, 0, e;\n"
            "@q mbarrier.arrive.expect_tx.shared::cta.b64 _, [%2], 6144;\n"
            "@q cp.async.bulk.tensor.3d.shared::cluster.global.mbarrier::complete_tx::bytes.L2::cache_hint [%0], [%3, {%6, %7, %12}], [%2], %14;\n"
            "@q cp.async.bulk.tensor.2d.shared::cluster.global.mbarrier::complete_tx::bytes.L2::cache_hint [%0 + 4096], [%4, {%13, %8}], [%2], %14;\n"
            "@e cp.async.bulk.wait_group.read 0;\n"
            "@p cp.async.bulk.tensor.2d.global.shared::cta.bulk_group [%5, {%6, %9}], [%1 + 6144];\n"
            "@e cp.async.bulk.commit_group;\n"
            "bar.warp.sync 0xffffffff;\n}"
            :: "r"(st), "r"(st ^ ATT_SLOT), "r"(b), "l"(mqk), "l"(mv), "l"(mo), "r"(col), "r"(row + 48), "r"(row + 32),
               "r"(row - 16), "r"(store), "r"(load), "r"(0), "r"(col + 2 * DM), "l"(pol) : "memory");
    };
    if (elect_one()) {
        mbar_init(bar, 1); mbar_init(bar + 8, 1);
        prefetch_map(mqk); prefetch_map(mv); prefetch_map(mo);
        const unsigned epoch = __ldcg(g_epoch + blockIdx.x * 16 + warp) + 1;
        flag_wait(g_flags + F_QKV * 512, epoch * CNT_QKV);
        fence_proxy_async();
        mbar_expect_tx(bar + 8, 8192);
        tma_3d(buf + ATT_SLOT, mqk, bar + 8, col, first, 0, pol);
        tma_2d(buf + ATT_SLOT + 4096, mv, bar + 8, col + 2 * DM, first - 16, policy(false));
        tma_2d(buf + ATT_SLOT + 6144, mv, bar + 8, col + DM, first - 16, policy(false));
        mbar_expect_tx(bar, 6144);
        tma_3d(buf, mqk, bar, col, first + 16, 0, pol);
        tma_2d(buf + 4096, mv, bar, col + 2 * DM, first, pol);
        g_epoch[blockIdx.x * 16 + warp] = epoch;
        if (warp == 0) TRACE(9);
    }
    __syncwarp();
    mbar_wait(bar + 8, 0);
#pragma unroll
    for (int h = 0; h < 2; h++) {
        kp[h] = ldsm4(buf + ATT_SLOT + 5120 + (koff ^ (h * 64)));
        vp[h] = ldsm4_t(buf + ATT_SLOT + 3072 + (koff ^ (h * 64)));
    }
    scores(buf + ATT_SLOT, first);
    exchange(buf + ATT_SLOT, bar + 8, first - 16, 0, 1);
    logits();
    row_max();
    uint32_t st = buf, b = bar, cnt = 1;
    bool ready = mbar_try_wait(b, 0);
#pragma unroll 1
    for (int row = first; row < last; row += 16) {
        uint32_t pa[2], pb[2];
        if (!ready) mbar_wait(b, (cnt >> 1) & 1);
        uint4 v[2][2];
#pragma unroll
        for (int h = 0; h < 2; h++) {
            const float ma = -LOG2E * bf_lo(m[h]), mb = -LOG2E * bf_hi(m[h]);
            const float a0 = ex2_fast(fmaf(bf_lo(l0[h]), LOG2E, ma)), a1 = ex2_fast(fmaf(bf_lo(l1[h]), LOG2E, ma));
            const float b0 = ex2_fast(fmaf(bf_hi(l0[h]), LOG2E, mb)), b1 = ex2_fast(fmaf(bf_hi(l1[h]), LOG2E, mb));
            float sum[4] = {0.f, 0.f, 0.f, 0.f};
            mma_1688(sum, pack_bf16(a0, a1), pack_bf16(b0, b1), 0x3f803f80u);
            const float ra = rcp_fast(sum[0]), rb = rcp_fast(sum[2]);
            pa[h] = pack_bf16(a0 * ra, a1 * ra);
            pb[h] = pack_bf16(b0 * rb, b1 * rb);
        }
        scores(st, row + 16);
#pragma unroll
        for (int h = 0; h < 2; h++) {
            v[h][0] = ldsm4_t(st + 4096 + (qoff ^ (h * 64)));
            v[h][1] = ldsm4_t(st + 4096 + (qoff ^ (h * 64 + 32)));
        }
        exchange(st, b, row, row > first, row + 32 < last);
        logits();
        float o[2][4][4];
#pragma unroll
        for (int h = 0; h < 2; h++) {
            const uint32_t prev[4] = {vp[h].x, vp[h].y, vp[h].z, vp[h].w};
            const uint32_t own[8] = {v[h][0].x, v[h][0].y, v[h][0].z, v[h][0].w, v[h][1].x, v[h][1].y, v[h][1].z, v[h][1].w};
            const uint32_t a0 = pa[h] & keep, a1 = pa[h] & ~keep, a2 = pb[h] & keep, a3 = pb[h] & ~keep;
            const uint32_t z0 = pa[h] & zero, z1 = pb[h] & zero;
#pragma unroll
            for (int j = 0; j < 4; j++) {
                o[h][j][0] = o[h][j][1] = o[h][j][2] = o[h][j][3] = 0.f;
                mma_1688(o[h][j], a0, z0, prev[j]);
                mma_16816(o[h][j], a1, a2, z1, a3, own[2 * j], own[2 * j + 1]);
            }
            vp[h] = make_uint4(own[1], own[3], own[5], own[7]);
        }
        row_max();
        b ^= 8; cnt++;
        ready = mbar_try_wait(b, (cnt >> 1) & 1);
#pragma unroll
        for (int h = 0; h < 2; h++) {
#pragma unroll
            for (int d = 0; d < 2; d++)
                asm volatile("stmatrix.sync.aligned.m8n8.x4.shared.b16 [%0], {%1,%2,%3,%4};"
                             :: "r"(st + 6144 + (qoff ^ (h * 64 + d * 32))),
                                "r"(pack_bf16(o[h][2 * d][0], o[h][2 * d][1])), "r"(pack_bf16(o[h][2 * d][2], o[h][2 * d][3])),
                                "r"(pack_bf16(o[h][2 * d + 1][0], o[h][2 * d + 1][1])),
                                "r"(pack_bf16(o[h][2 * d + 1][2], o[h][2 * d + 1][3])) : "memory");
        }
        st ^= ATT_SLOT;
    }
    exchange(st, b, last, 1, 0);
    if (elect_one()) {
        asm volatile("cp.async.bulk.wait_group 0;" ::: "memory");
        fence_proxy_async();
        flag_add(g_flags + F_O * 512);
        if (warp == 0) TRACE(10);
    }
}

__device__ __forceinline__ void warp_sum2(float& a, float& b) {
#pragma unroll
    for (int o = 16; o > 0; o >>= 1) {
        a += __shfl_xor_sync(0xffffffffu, a, o);
        b += __shfl_xor_sync(0xffffffffu, b, o);
    }
}
__device__ __forceinline__ float row_sum(const uint32_t* w) {
    float a = 0.f, b = 0.f;
#pragma unroll
    for (int i = 0; i < 16; i++) { a += bf_lo(w[i]); b += bf_hi(w[i]); }
    return a + b;
}
__device__ __forceinline__ float row_sq(const uint32_t* w, float mean) {
    float a = 0.f, b = 0.f;
#pragma unroll
    for (int i = 0; i < 16; i++) {
        const float lo = bf_lo(w[i]) - mean, hi = bf_hi(w[i]) - mean;
        a = fmaf(lo, lo, a); b = fmaf(hi, hi, b);
    }
    return a + b;
}
__device__ __forceinline__ float row_inv(float sq) {
    return 1.f / round_bf16(sqrtf(round_bf16(round_bf16(sq * (1.f / DM)) + 1e-5f)));
}
__device__ __forceinline__ void row_store(const uint32_t* w, float mean, float inv, __nv_bfloat16* dst) {
    const uint32_t m2 = pack_bf16(mean, mean);
#pragma unroll
    for (int i = 0; i < 2; i++) {
        uint32_t o[4];
#pragma unroll
        for (int j = 0; j < 4; j++) {
            const uint32_t c = sub_bf16x2(w[i * 4 + j], m2);
            o[j] = pack_bf16(bf_lo(c) * inv, bf_hi(c) * inv);
        }
        *reinterpret_cast<uint4*>(dst + i * 256) = make_uint4(o[0], o[1], o[2], o[3]);
    }
}

struct Params {
    CUtensorMap x, xn, wv, wqk, wg, wu, wg1, wu1, qk, v, o, a2, wo, wd, out;
    const __nv_bfloat16 *px, *pwqkv;
    uint32_t zero;
};

__global__ void __cluster_dims__(2, 1, 1) __launch_bounds__(384, 1)
fused_kernel(const __grid_constant__ Params prm) {
    extern __shared__ __align__(1024) uint8_t smem_raw[];
    const uint32_t base = (smem_u32(smem_raw) + 1023) & ~1023u;
    const uint32_t bars = base + BAR_OFF;
    auto full0 = [&](int s) { return bars + s * 8; };
    auto empty0 = [&](int s) { return bars + 48 + s * 8; };
    auto full1 = [&](int s) { return bars + 96 + s * 8; };
    auto empty1 = [&](int s) { return bars + 128 + s * 8; };
    auto full2 = [&](int s) { return bars + 160 + s * 8; };
    auto empty2 = [&](int s) { return bars + 208 + s * 8; };
    const uint32_t sig_bar = bars + 256, fold_bar = bars + 264, x_bar = bars + 272, dep_bar = bars + 280;
    auto wide = [&](int s) { return base + s * W_STAGE_BYTES; };
    auto narrow = [&](int q) { return base + q * N_STAGE_BYTES; };
    const uint32_t aux = base + AUX_OFF;

    const int warp = __shfl_sync(0xffffffffu, threadIdx.x >> 5, 0);
    const int lane = threadIdx.x & 31;
    const int rank = blockIdx.x & 1;
    const int mblk = ((blockIdx.x >> 1) & 7) * 2 + rank;
    const int nslot = blockIdx.x >> 4;

    if (blockIdx.x >= NGEMM) {
        if (threadIdx.x == 0) { TRACE_GT(0); TRACE(1); }
        attention(&prm.qk, (base + 2 * ATT_SLOT - 1) & ~(2u * ATT_SLOT - 1), prm.zero, blockIdx.x - NGEMM, warp, lane);
    } else if (warp >= 8) {
        unsigned* const flags = g_flags + mblk * 32;
        if (warp == 8) {
            if (lane == 0) { TRACE_GT(0); TRACE(1); prefetch_map(&prm.x); prefetch_map(&prm.wv); }
            mbar_init(bars + lane * 8, 0xfc0f0fc0u >> lane & 1 ? 4 : 1);
            if (lane < 7) mbar_init(sig_bar + lane * 8, lane == 0 ? 8 : (lane == 1 ? 2 : 1));
            asm volatile("fence.mbarrier_init.release.cluster;" ::: "memory");
            asm volatile("fence.proxy.async.shared::cta;" ::: "memory");
            __syncwarp();
        }
        asm volatile("barrier.cluster.arrive.relaxed.aligned;" ::: "memory");
        if (warp == 8 && lane == 0) {
            for (int j = 0; j < N_STAGES; j++) {
                const int q = (j + 2) % N_STAGES;
                mbar_expect_tx(full0(q), N_STAGE_BYTES);
                tma_2d(narrow(q), &prm.x, full0(q), j * 64, mblk * 128, policy(P_X));
            }
            TRACE(15);
        }
        asm volatile("setmaxnreg.dec.sync.aligned.u32 %0;" :: "n"(AUX_REGS));
        asm volatile("barrier.cluster.wait.acquire.aligned;" ::: "memory");

        if (warp == 8) {
            if (lane == 0) {
                TRACE(2);
                for (int j = 0; j < KSTEPS; j++) {
                    const int q = (j + 2) % N_STAGES;
                    if (j >= N_STAGES) {
                        mbar_wait(empty0(q), j >= 2 * N_STAGES);
                        mbar_expect_tx(full0(q), N_STAGE_BYTES);
                        tma_2d(narrow(q), &prm.x, full0(q), j * 64, mblk * 128, policy(P_X));
                    }
                    tma_3d_mc(narrow(q) + A_BYTES + rank * 8192, &prm.wv, full0(q), j * 64, 32 + nslot * 2 + rank, policy(P_W1));
                    if (j == N_STAGES - 1) {
                        prefetch_map(&prm.xn); prefetch_map(&prm.wqk); prefetch_map(rank ? &prm.wu : &prm.wg);
                        prefetch_map(rank ? &prm.wu1 : &prm.wg1);
                        prefetch_map(&prm.a2); prefetch_map(&prm.wo); prefetch_map(&prm.wd); prefetch_map(&prm.out);
                    }
                }
                TRACE(14); mbar_wait(dep_bar, 0); TRACE(3);
                uint32_t ph = 1;
                for (int it = 0; it < W_TILES * KSTEPS; it++) {
                    const int s = it & 3, k = it & 15;
                    if (it < W_STAGES) {
                        if (!(it & 1)) mbar_wait(empty0(it + it / 2), it == 0);
                        mbar_wait(empty0(it + it / 2 + 1), it == 0);
                    } else {
                        mbar_wait(empty1(s), ph);
                    }
                    mbar_expect_tx(full1(s), W_STAGE_BYTES);
                    tma_2d(wide(s), &prm.xn, full1(s), k * 64, mblk * 128, policy(false));
                    const uint32_t dst = wide(s) + A_BYTES + rank * 16384;
                    if (it < KSTEPS) tma_3d_mc(dst, &prm.wqk, full1(s), k * 64, nslot * 4 + rank * 2, policy(P_W1));
                    else tma_3d_mc(dst, rank ? &prm.wu : &prm.wg, full1(s), k * 64, ((it >> 4) * 8 - 8 + nslot) * 2, policy(P_W1));
                    if (s == 3) ph ^= 1;
                }
                TRACE(4);
                int q = 0; uint32_t ph2 = 1;
                for (int u = 0; u < U_END; u++) {
                    if (u == U_D || u == U_LATE || u == U_S) {
                        TRACE(u == U_D ? 36 : (u == U_LATE ? 6 : 32));
                        mbar_wait(dep_bar + (u == U_D ? 8 : (u == U_LATE ? 16 : 24)), 0);
                        TRACE(u == U_D ? 5 : (u == U_LATE ? 7 : 33));
                    }
                    if (u < N_STAGES) {
                        if (u == 0) mbar_wait(empty1(0), ph);
                        if (u == 1) mbar_wait(empty1(1), ph);
                        if (u == 3) mbar_wait(empty1(2), ph);
                        if (u == 4) mbar_wait(empty1(3), ph);
                    } else {
                        mbar_wait(empty2(q), ph2);
                    }
                    const uint32_t sa = narrow(q), sb = sa + A_BYTES + rank * 8192;
                    mbar_expect_tx(full2(q), N_STAGE_BYTES);
                    if (u < U_D) {
                        tma_2d(sa, &prm.xn, full2(q), u * 64, mblk * 128, policy(P_XN4));
                        tma_3d_mc(sb, rank ? &prm.wu1 : &prm.wg1, full2(q), u * 64, 48 + nslot, policy(P_W1));
                    } else {
                        const bool down = u < U_S;
                        const int k = down ? u - U_D : u - U_S;
                        tma_3d(sa, &prm.a2, full2(q), (down ? DM : 0) + k * 64, 0, mblk * 64, policy(P_A2));
                        tma_5d_mc(sb, down ? &prm.wd : &prm.wo, full2(q), nslot * 128 + rank * 64, k * 2, policy(P_W2));
                    }
                    if (u == N_STAGES - 1) {
                        mbar_expect_tx(x_bar, 32768);
                        tma_2d(aux, &prm.x, x_bar, nslot * 128, mblk * 128, policy(P_X));
                        tma_2d(aux + 16384, &prm.x, x_bar, nslot * 128 + 64, mblk * 128, policy(P_X));
                    }
                    if (++q == N_STAGES) { q = 0; ph2 ^= 1; }
                }
                TRACE(8);
            }
        } else if (warp == 9) {
            if (lane == 0) {
                for (int t = 0; t < 6; t++) {
                    mbar_wait(sig_bar, t & 1);
                    if (t < 2) TRACE(t ? 37 : 11);
                    flag_add(t == 1 ? g_flags + F_QKV * 512 : flags + (t == 0 ? F_LN : (t < 4 ? F_EARLY : F_LATE)) * 512);
                }
            }
        } else if (warp == 10) {
            const unsigned epoch = __ldcg(g_epoch + blockIdx.x * 16) + 1;
            if (lane == 0) {
                flag_wait(flags + F_LN * 512, epoch * CNT_LN);
                fence_proxy_async(); mbar_arrive(dep_bar);
            }
            __syncwarp();
            const uint4* sp = reinterpret_cast<const uint4*>(g_stats + mblk * 128) + lane;
            const uint4 s0 = __ldcg(sp), s1 = __ldcg(sp + 32);
            sts128(aux + 512 + lane * 16, s0);
            sts128(aux + 1024 + lane * 16, s1);
            __syncwarp();
            if (lane == 0) {
                mbar_arrive(fold_bar);
                g_epoch[blockIdx.x * 16] = epoch;
                flag_wait(flags + F_EARLY * 512, epoch * CNT_EARLY);
                fence_proxy_async(); mbar_arrive(dep_bar + 8);
                flag_wait(flags + F_LATE * 512, epoch * CNT_LATE);
                fence_proxy_async(); mbar_arrive(dep_bar + 16);
                flag_wait(g_flags + F_O * 512, epoch * CNT_O);
                fence_proxy_async(); mbar_arrive(dep_bar + 24);
            }
        } else {
            const __nv_bfloat16* wp = prm.pwqkv + (size_t)(mblk * 64 + (lane >> 4)) * NQKV + 2 * DM + nslot * 128 + (lane & 15) * 8;
            const unsigned epoch = __ldcg(g_epoch + blockIdx.x * 16 + 1) + 1;
            float cs[8];
#pragma unroll
            for (int d = 0; d < 8; d++) cs[d] = 0.f;
            mbar_wait(full0(2), 0);
#pragma unroll 1
            for (int i = 0; i < 4; i++) {
                uint4 v[8];
#pragma unroll
                for (int j = 0; j < 8; j++) v[j] = ldg_stream(wp + (size_t)(i * 16 + j * 2) * NQKV, policy(P_W1));
#pragma unroll
                for (int j = 0; j < 8; j++) {
                    float f[8];
                    unpack8(v[j], f);
#pragma unroll
                    for (int d = 0; d < 8; d++) cs[d] += f[d];
                }
            }
#pragma unroll
            for (int d = 0; d < 8; d++) cs[d] += __shfl_xor_sync(0xffffffffu, cs[d], 16);
            *reinterpret_cast<float4*>(g_colsum + mblk * DM + nslot * 128 + (lane & 15) * 8 + (lane >> 4) * 4) =
                lane < 16 ? make_float4(cs[0], cs[1], cs[2], cs[3]) : make_float4(cs[4], cs[5], cs[6], cs[7]);
            __syncwarp();
            if (lane == 0) {
                TRACE(34);
                flag_add(g_flags + F_CS * 512 + nslot * 32);
                flag_wait(g_flags + F_CS * 512 + nslot * 32, epoch * CNT_CS);
            }
            __syncwarp();
            const float4* gp = reinterpret_cast<const float4*>(g_colsum + nslot * 128) + lane;
            float4 c = make_float4(0.f, 0.f, 0.f, 0.f);
#pragma unroll 8
            for (int m = 0; m < 16; m++) {
                const float4 a = __ldcg(gp + m * (DM / 4));
                c.x += a.x; c.y += a.y; c.z += a.z; c.w += a.w;
            }
            const uint32_t ca = aux + (lane >> 2) * 64 + (lane & 1) * 32 + (lane & 2) * 4;
            sts64f(ca, c.x, c.y);
            sts64f(ca + 16, c.z, c.w);
            __syncwarp();
            if (lane == 0) {
                mbar_arrive(fold_bar);
                g_epoch[blockIdx.x * 16 + 1] = epoch;
                TRACE(35);
            }
        }
    } else {
        asm volatile("barrier.cluster.arrive.relaxed.aligned;" ::: "memory");
        const int cw = threadIdx.x >> 5;
        const int tid = threadIdx.x & 127;
        const int lrow = mblk * 128 + nslot * 16 + cw * 2;
        uint32_t xw[32];
        {
            const uint4* xp = reinterpret_cast<const uint4*>(prm.px + (size_t)lrow * DM) + lane;
#pragma unroll
            for (int i = 0; i < 8; i++) {
                const uint4 v = ldg_stream(xp + i * 32, policy(P_X));
                xw[4 * i] = v.x; xw[4 * i + 1] = v.y; xw[4 * i + 2] = v.z; xw[4 * i + 3] = v.w;
            }
        }
        asm volatile("setmaxnreg.inc.sync.aligned.u32 %0;" :: "n"(CONSUMER_REGS));
        const int wg = __shfl_sync(0xffffffffu, threadIdx.x >> 7, 0);
        float mean0 = row_sum(xw), mean1 = row_sum(xw + 16);
        if (threadIdx.x == 0) TRACE(38);
        warp_sum2(mean0, mean1);
        mean0 *= 1.f / DM; mean1 *= 1.f / DM;
        float inv0 = row_sq(xw, mean0), inv1 = row_sq(xw + 16, mean1);
        warp_sum2(inv0, inv1);
        inv0 = row_inv(inv0); inv1 = row_inv(inv1);
        if (lane == 0) *reinterpret_cast<float4*>(g_stats + lrow) = make_float4(-round_bf16(mean0), inv0, -round_bf16(mean1), inv1);
        if (threadIdx.x == 0) TRACE(39);
        asm volatile("barrier.cluster.wait.acquire.aligned;" ::: "memory");

        auto release = [&](uint32_t bar) { if (tid < 2) mbar_arrive_cluster(bar, tid); };
        auto signal_stores = [&]() { __syncwarp(); if (lane == 0) mbar_arrive(sig_bar); };
        auto mma_narrow = [&](float (&d)[64], int q, bool accumulate) {
            asm volatile("" : "+r"(q));
            const uint64_t da = desc_a(narrow(q) + wg * 8192), db = desc_b(narrow(q) + A_BYTES);
            wg_fence();
#pragma unroll
            for (int kk = 0; kk < 4; kk++) wgmma_n128(d, da + kk * 2, db + kk * 128, accumulate || kk != 0);
            wg_commit();
        };

        uint32_t pk[64];
        {
            float accv[64];
#pragma unroll
            for (int i = 0; i < 64; i++) accv[i] = 0.f;
#pragma unroll
            for (int j = 0; j < 4; j++) {
                mbar_wait(full0(j + 2), 0);
                if (j == 0 && threadIdx.x == 0) TRACE(12);
                mma_narrow(accv, j + 2, j != 0);
                row_store(xw + j * 8, j < 2 ? mean0 : mean1, j < 2 ? inv0 : inv1, g_xn + (size_t)lrow * DM + j * 512 + lane * 8);
                if (j == 3) signal_stores();
                wg_wait<1>();
                if (j > 0) release(empty0(j + 1));
            }
            int q = 0, qp = N_STAGES - 1;
#pragma unroll 1
            for (int j = 4; j < KSTEPS; j++) {
                mbar_wait(full0(q), j >= N_STAGES && j < 2 * N_STAGES);
                mma_narrow(accv, q, true);
                wg_wait<1>();
                release(empty0(qp));
                qp = q;
                if (++q == N_STAGES) q = 0;
            }
            wg_wait<0>();
            fence_regs(accv);
            release(empty0(N_STAGES - 1));
#pragma unroll
            for (int i = 0; i < 64; i++) pk[i] = __float_as_uint(accv[i]);
        }
        if (tid == 0) TRACE(16 + wg * 8);

        const int orow = ((lane >> 2) & 1) * (SEQ / 2) + mblk * 64 + cw * 8 + (lane >> 3);
        __nv_bfloat16* optr = g_qkv + (size_t)orow * NQKV + 2 * DM + nslot * 128 + (lane & 3) * 8;
        auto chunk_v = [&](int c) {
            const uint32_t sp = aux + 512 + (cw * 16 + (lane >> 2)) * 8;
            const float2 sa = lds64f(sp), sb = lds64f(sp + 64);
            uint32_t r[8];
#pragma unroll
            for (int j = 0; j < 2; j++) {
                const uint4 cs = lds128(aux + (c * 2 + j) * 64 + (lane & 3) * 16);
                const float c0 = __uint_as_float(cs.x), c1 = __uint_as_float(cs.y);
                const float c2 = __uint_as_float(cs.z), c3 = __uint_as_float(cs.w);
                const uint32_t* a = pk + 16 * c + 8 * j;
                r[2 * j] = pack_bf16(fmaf(sa.x, c0, __uint_as_float(a[0])) * sa.y, fmaf(sa.x, c1, __uint_as_float(a[1])) * sa.y);
                r[4 + 2 * j] = pack_bf16(fmaf(sb.x, c0, __uint_as_float(a[2])) * sb.y, fmaf(sb.x, c1, __uint_as_float(a[3])) * sb.y);
                r[2 * j + 1] = pack_bf16(fmaf(sa.x, c2, __uint_as_float(a[4])) * sa.y, fmaf(sa.x, c3, __uint_as_float(a[5])) * sa.y);
                r[5 + 2 * j] = pack_bf16(fmaf(sb.x, c2, __uint_as_float(a[6])) * sb.y, fmaf(sb.x, c3, __uint_as_float(a[7])) * sb.y);
            }
            *reinterpret_cast<uint4*>(optr + c * 32) = make_uint4(r[0], r[1], r[2], r[3]);
            *reinterpret_cast<uint4*>(optr + 4 * NQKV + c * 32) = make_uint4(r[4], r[5], r[6], r[7]);
        };
        auto chunk_qk = [&](int c) {
            *reinterpret_cast<uint4*>(optr + c * 32) = make_uint4(pk[8 * c], pk[8 * c + 2], pk[8 * c + 4], pk[8 * c + 6]);
            *reinterpret_cast<uint4*>(optr + 4 * NQKV + c * 32) = make_uint4(pk[8 * c + 1], pk[8 * c + 3], pk[8 * c + 5], pk[8 * c + 7]);
        };
        auto chunk_geglu = [&](int j) {
            const int c = j >> 1, h = j & 1;
            uint4 v;
            v.x = geglu2(pk[8 * c + h], pk[32 + 8 * c + h]);
            v.y = geglu2(pk[8 * c + 2 + h], pk[32 + 8 * c + 2 + h]);
            v.z = geglu2(pk[8 * c + 4 + h], pk[32 + 8 * c + 4 + h]);
            v.w = geglu2(pk[8 * c + 6 + h], pk[32 + 8 * c + 6 + h]);
            *reinterpret_cast<uint4*>(optr + h * 4 * K2 + c * 32) = v;
        };

        {
            float acc[128];
#pragma unroll
            for (int i = 0; i < 128; i++) asm volatile("mov.b32 %0, 0;" : "=f"(acc[i]));
#pragma unroll 1
            for (int t = 0; t < W_TILES; t++) {
#pragma unroll
                for (int k = 0; k < KSTEPS; k++) {
                    const int s = k & 3;
                    mbar_wait(full1(s), (k >> 2) & 1);
                    if (wg == 1 && k == KSTEPS - W_SKEW) asm volatile("bar.sync 1, 256;" ::: "memory");
                    const uint64_t da = desc_a(wide(s) + wg * 8192), db = desc_b(wide(s) + A_BYTES);
                    wg_fence();
#pragma unroll
                    for (int kk = 0; kk < 4; kk++) wgmma_n256(acc, da + kk * 2, db + kk * 128, (k | kk) != 0);
                    wg_commit();
                    if (wg == 0 && k == KSTEPS - 1) asm volatile("bar.arrive 1, 256;" ::: "memory");
                    if (k >= 9 && k <= 12 && t == 0) {
                        if (k == 9) mbar_wait(fold_bar, 0);
                        chunk_v(k - 9);
                    }
                    if (k <= 3 && t == 1) {
                        chunk_qk(2 * k); chunk_qk(2 * k + 1);
                        if (k == 3) signal_stores();
                    }
                    if (k >= 1 && k <= 8 && t >= 2) {
                        chunk_geglu(k - 1);
                        if (k == 8) signal_stores();
                    }
                    wg_wait<1>();
                    if (k > 0) release(empty1((k - 1) & 3));
                }
                wg_wait<0>();
                fence_regs(acc);
                release(empty1(3));
#pragma unroll
                for (int i = 0; i < 64; i++) pk[i] = pack_bf16(acc[2 * i], acc[2 * i + 1]);
                optr = t == 0 ? g_qkv + (size_t)orow * NQKV + nslot * 256 + (lane & 3) * 8
                              : g_a2 + (size_t)orow * K2 + DM + (t * 8 - 8 + nslot) * 128 + (lane & 3) * 8;
                if (tid == 0) TRACE(17 + wg * 8 + t);
            }
        }

        float acch[64], accd[64], accs[64];
#pragma unroll
        for (int i = 0; i < 64; i++) acch[i] = 0.f;
#pragma unroll
        for (int u = 0; u < U_D; u++) {
            mbar_wait(full2(u % N_STAGES), (u / N_STAGES) & 1);
            mma_narrow(acch, u % N_STAGES, u != 0);
            if (u & 1) { chunk_geglu(u >> 1); if (u == U_D - 1) signal_stores(); }
            wg_wait<1>();
            if (u > 0) release(empty2((u - 1) % N_STAGES));
        }
        if (tid == 0) TRACE(40 + wg);
        optr = g_a2 + (size_t)orow * K2 + DM + 3072 + nslot * 64 + (lane & 3) * 8;
#pragma unroll
        for (int i = 0; i < 64; i++) accd[i] = 0.f;
#pragma unroll
        for (int u = U_D; u < U_D + 8; u++) {
            mbar_wait(full2(u % N_STAGES), (u / N_STAGES) & 1);
            mma_narrow(accd, u % N_STAGES, u != U_D);
            if (u & 1) {
                const int c = (u - U_D) >> 2, h = (u - U_D) >> 1 & 1;
                const float* a = acch + 16 * c + 2 * h;
                uint4 v;
                v.x = geglu2(pack_bf16(a[0], a[1]), pack_bf16(a[32], a[33]));
                v.y = geglu2(pack_bf16(a[4], a[5]), pack_bf16(a[36], a[37]));
                v.z = geglu2(pack_bf16(a[8], a[9]), pack_bf16(a[40], a[41]));
                v.w = geglu2(pack_bf16(a[12], a[13]), pack_bf16(a[44], a[45]));
                *reinterpret_cast<uint4*>(optr + h * 4 * K2 + c * 32) = v;
                if (u == U_D + 7) signal_stores();
            }
            wg_wait<1>();
            if (u == U_D) fence_regs(acch);
            release(empty2((u - 1) % N_STAGES));
        }
        {
            int q = (U_D + 8) % N_STAGES, qp = (U_D + 7) % N_STAGES; uint32_t ph = ((U_D + 8) / N_STAGES) & 1;
#pragma unroll 1
            for (int u = U_D + 8; u < U_S; u++) {
                mbar_wait(full2(q), ph);
                mma_narrow(accd, q, true);
                wg_wait<1>();
                release(empty2(qp));
                qp = q;
                if (++q == N_STAGES) { q = 0; ph ^= 1; }
            }
        }
        if (tid == 0) TRACE(16 + wg * 8 + 5);
#pragma unroll
        for (int i = 0; i < 64; i++) accs[i] = 0.f;
        uint32_t gk[32], xr[32];
        const uint32_t xs = aux + cw * 2048;
        const uint32_t xrow = xs + ((lane & 7) + ((lane >> 3) & 1) * 8) * 128;
        auto xaddr = [&](int j) { return xrow + (j >> 2) * 16384 + (((((j & 3) * 2) + (lane >> 4)) ^ (lane & 7)) << 4); };
#pragma unroll
        for (int u = U_S; u < U_END; u++) {
            const int v = u - U_S;
            mbar_wait(full2(u % N_STAGES), (u / N_STAGES) & 1);
            if (S_SKEW > 0 && wg == 1 && u == U_END - S_SKEW) asm volatile("bar.sync 1, 256;" ::: "memory");
            mma_narrow(accs, u % N_STAGES, v != 0);
            if (S_SKEW > 0 && wg == 0 && u == U_END - 1) asm volatile("bar.arrive 1, 256;" ::: "memory");
            if (v >= 1 && v <= 8) {
#pragma unroll
                for (int i = 4 * (v - 1); i < 4 * v; i++) {
                    const uint32_t d2 = pack_bf16(accd[2 * i], accd[2 * i + 1]);
                    gk[i] = pack_bf16(silu(bf_lo(d2)), silu(bf_hi(d2)));
                }
            }
            if (v == 9) mbar_wait(x_bar, 0);
            if (v >= 9 && v <= 12) {
#pragma unroll
                for (int j = 2 * (v - 9); j < 2 * (v - 8); j++)
                    asm volatile("ldmatrix.sync.aligned.m8n8.x4.shared.b16 {%0,%1,%2,%3}, [%4];"
                                 : "=r"(xr[4 * j]), "=r"(xr[4 * j + 1]), "=r"(xr[4 * j + 2]), "=r"(xr[4 * j + 3])
                                 : "r"(xaddr(j)) : "memory");
            }
            wg_wait<1>();
            if (v == 0) fence_regs(accd);
            if (u - 1 + N_STAGES < U_END) release(empty2((u - 1) % N_STAGES));
        }
        wg_wait<0>();
        fence_regs(accs);
        if (tid == 0) TRACE(16 + wg * 8 + 6);
#pragma unroll
        for (int j = 0; j < 8; j++) {
            uint32_t r[4];
#pragma unroll
            for (int i = 0; i < 4; i++) {
                const int e = j * 4 + i;
                r[i] = add_bf16x2(xr[e], mul_bf16x2(pack_bf16(accs[2 * e], accs[2 * e + 1]), gk[e]));
            }
            asm volatile("stmatrix.sync.aligned.m8n8.x4.shared.b16 [%0], {%1,%2,%3,%4};"
                         :: "r"(xaddr(j)), "r"(r[0]), "r"(r[1]), "r"(r[2]), "r"(r[3]) : "memory");
            if (j == 3 || j == 7) {
                asm volatile("fence.proxy.async.shared::cta;" ::: "memory");
                __syncwarp();
                if (lane == 0) {
                    tma_store_2d(&prm.out, xs + (j >> 2) * 16384, nslot * 128 + (j >> 2) * 64, mblk * 128 + cw * 16);
                    asm volatile("cp.async.bulk.commit_group;" ::: "memory");
                }
            }
        }
        if (lane == 0) asm volatile("cp.async.bulk.wait_group.read 0;" ::: "memory");
        if (tid == 0) { TRACE(16 + wg * 8 + 7); if (wg == 1) TRACE_GT(13); }
    }
}

typedef CUresult (*EncodeFn)(CUtensorMap*, CUtensorMapDataType, cuuint32_t, void*, const cuuint64_t*, const cuuint64_t*,
                             const cuuint32_t*, const cuuint32_t*, CUtensorMapInterleave, CUtensorMapSwizzle,
                             CUtensorMapL2promotion, CUtensorMapFloatOOBfill);

void encode(EncodeFn fn, CUtensorMap* m, const void* ptr, int rank, const cuuint64_t* dims, const cuuint64_t* strides,
            const cuuint32_t* box) {
    const cuuint32_t es[5] = {1, 1, 1, 1, 1};
    fn(m, CU_TENSOR_MAP_DATA_TYPE_BFLOAT16, rank, const_cast<void*>(ptr), dims, strides, box, es,
       CU_TENSOR_MAP_INTERLEAVE_NONE, CU_TENSOR_MAP_SWIZZLE_128B, CU_TENSOR_MAP_L2_PROMOTION_L2_128B,
       CU_TENSOR_MAP_FLOAT_OOB_FILL_NONE);
}
void encode_2d(EncodeFn fn, CUtensorMap* m, const void* ptr, int cols, int box_rows) {
    const cuuint64_t dims[2] = {(cuuint64_t)cols, SEQ}, strides[1] = {(cuuint64_t)cols * 2};
    const cuuint32_t box[2] = {64, (cuuint32_t)box_rows};
    encode(fn, m, ptr, 2, dims, strides, box);
}
void encode_w1(EncodeFn fn, CUtensorMap* m, const void* ptr, int cols, int blocks) {
    const cuuint64_t dims[3] = {64, DM, (cuuint64_t)cols / 64}, strides[2] = {(cuuint64_t)cols * 2, 128};
    const cuuint32_t box[3] = {64, 64, (cuuint32_t)blocks};
    encode(fn, m, ptr, 3, dims, strides, box);
}
void encode_qk(EncodeFn fn, CUtensorMap* m, const void* ptr) {
    const cuuint64_t dims[3] = {DM, SEQ, 3}, strides[2] = {NQKV * 2, DM * 2};
    const cuuint32_t box[3] = {64, 16, 2};
    encode(fn, m, ptr, 3, dims, strides, box);
}
void encode_a2(EncodeFn fn, CUtensorMap* m, const void* ptr) {
    const cuuint64_t dims[3] = {K2, 2, SEQ / 2}, strides[2] = {(cuuint64_t)SEQ * K2, K2 * 2};
    const cuuint32_t box[3] = {64, 2, 64};
    encode(fn, m, ptr, 3, dims, strides, box);
}
void encode_w2(EncodeFn fn, CUtensorMap* m, const void* ptr, int rows) {
    const cuuint64_t rb = DM * 2;
    const cuuint64_t dims[5] = {DM, 2, 4, 4, (cuuint64_t)rows / 32}, strides[4] = {rb, 8 * rb, 2 * rb, 32 * rb};
    const cuuint32_t box[5] = {64, 2, 4, 4, 2};
    encode(fn, m, ptr, 5, dims, strides, box);
}

}

extern "C" void kernel_launch(void* const* d_in, const int* in_sizes, int n_in, void* d_out, int out_size) {
    (void)in_sizes; (void)n_in; (void)out_size;
    static EncodeFn fn = nullptr;
    static void *p_xn = nullptr, *p_qkv = nullptr, *p_a2 = nullptr;
    if (!fn) {
        cudaDriverEntryPointQueryResult st;
        cudaGetDriverEntryPoint("cuTensorMapEncodeTiled", (void**)&fn, cudaEnableDefault, &st);
        cudaGetSymbolAddress(&p_xn, g_xn);
        cudaGetSymbolAddress(&p_qkv, g_qkv);
        cudaGetSymbolAddress(&p_a2, g_a2);
        cudaFuncSetAttribute(fused_kernel, cudaFuncAttributeMaxDynamicSharedMemorySize, SMEM_BYTES);
    }
    Params prm;
    encode_2d(fn, &prm.x, d_in[0], DM, 128);
    encode_2d(fn, &prm.xn, p_xn, DM, 128);
    encode_w1(fn, &prm.wv, d_in[1], NQKV, 1);
    encode_w1(fn, &prm.wqk, d_in[1], NQKV, 2);
    encode_w1(fn, &prm.wg, d_in[4], DF, 2);
    encode_w1(fn, &prm.wu, d_in[5], DF, 2);
    encode_w1(fn, &prm.wg1, d_in[4], DF, 1);
    encode_w1(fn, &prm.wu1, d_in[5], DF, 1);
    encode_qk(fn, &prm.qk, p_qkv);
    encode_2d(fn, &prm.v, p_qkv, NQKV, 16);
    encode_2d(fn, &prm.o, p_a2, K2, 16);
    encode_a2(fn, &prm.a2, p_a2);
    encode_w2(fn, &prm.wo, d_in[2], DM);
    encode_w2(fn, &prm.wd, d_in[6], DF);
    encode_2d(fn, &prm.out, d_out, DM, 16);
    prm.px = (const __nv_bfloat16*)d_in[0];
    prm.pwqkv = (const __nv_bfloat16*)d_in[1];
    prm.zero = 0;
    fused_kernel<<<NCTA, 384, SMEM_BYTES>>>(prm);
}
```

```cpp
#include <cuda_runtime.h>
#include <cuda_bf16.h>
#include <cuda.h>
#include <stdint.h>

#define P_W1 1
#define P_X 1
#define P_XN4 1
#define P_W2 1
#define P_A2 1
#define P_QKV 1

namespace {

constexpr int SEQ = 2048, DM = 1024, DF = 3584, K2 = DM + DF, NQKV = 3 * DM;
constexpr int NGEMM = 128, NCTA = 132;
constexpr int W_STAGES = 4, W_STAGE_BYTES = 49152, KSTEPS = 16, W_TILES = 4;
constexpr int N_STAGES = 6, N_STAGE_BYTES = 32768;
constexpr int U_D = 16, U_LATE = 48, U_S = 72, U_END = 88;
constexpr int A_BYTES = 16384;
constexpr int AUX_OFF = W_STAGES * W_STAGE_BYTES;
constexpr int BAR_OFF = AUX_OFF + 32768;
constexpr int SMEM_BYTES = BAR_OFF + 1024 + 512;
constexpr int W_SKEW = 2, S_SKEW = 2;
constexpr int CONSUMER_REGS = 224, AUX_REGS = 56;
constexpr int ATT_SLOT = 8192;

enum { F_LN = 0, F_QKV = 1, F_EARLY = 2, F_LATE = 3, F_O = 4, F_CS = 5 };
constexpr unsigned CNT_LN = 8, CNT_QKV = 128, CNT_EARLY = 16, CNT_LATE = 16, CNT_O = 48, CNT_CS = 16;

__device__ __align__(1024) __nv_bfloat16 g_xn[SEQ * DM];
__device__ __align__(1024) __nv_bfloat16 g_qkv[SEQ * NQKV];
__device__ __align__(1024) __nv_bfloat16 g_a2[SEQ * K2];
__device__ __align__(128) float2 g_stats[SEQ];
__device__ __align__(128) float g_colsum[16 * DM];
__device__ __align__(128) unsigned g_flags[6 * 16 * 32];
__device__ __align__(128) unsigned g_epoch[NCTA * 16];

#define TRACE_T 1
#define TRACE(slot) do {} while (0)
#define TRACE_GT(slot) do {} while (0)

__device__ __forceinline__ uint32_t smem_u32(const void* p) { return (uint32_t)__cvta_generic_to_shared(p); }
__device__ __forceinline__ void mbar_init(uint32_t bar, uint32_t cnt) {
    asm volatile("mbarrier.init.shared::cta.b64 [%0], %1;" :: "r"(bar), "r"(cnt) : "memory");
}
__device__ __forceinline__ void mbar_expect_tx(uint32_t bar, uint32_t bytes) {
    asm volatile("mbarrier.arrive.expect_tx.shared::cta.b64 _, [%0], %1;" :: "r"(bar), "r"(bytes) : "memory");
}
__device__ __forceinline__ void mbar_arrive(uint32_t bar) {
    asm volatile("mbarrier.arrive.shared::cta.b64 _, [%0];" :: "r"(bar) : "memory");
}
__device__ __forceinline__ void mbar_arrive_cluster(uint32_t bar, uint32_t cta) {
    asm volatile("{\n.reg .b32 ra;\nmapa.shared::cluster.u32 ra, %0, %1;\nmbarrier.arrive.shared::cluster.b64 _, [ra];\n}"
                 :: "r"(bar), "r"(cta) : "memory");
}
__device__ __forceinline__ bool mbar_try_wait(uint32_t bar, uint32_t parity) {
    uint32_t ok;
    asm volatile("{\n.reg .pred p;\nmbarrier.try_wait.parity.shared::cta.b64 p, [%1], %2;\nselp.u32 %0, 1, 0, p;\n}"
                 : "=r"(ok) : "r"(bar), "r"(parity) : "memory");
    return ok;
}
__device__ __forceinline__ void mbar_wait(uint32_t bar, uint32_t parity) {
    int spins = 0;
    while (!mbar_try_wait(bar, parity)) { if (++spins > (1 << 17)) break; }
}
__device__ __forceinline__ void flag_wait(const unsigned* p, unsigned target) {
    for (int spins = 0; spins < (1 << 19); spins++) {
        unsigned v;
        asm volatile("ld.acquire.gpu.global.u32 %0, [%1];" : "=r"(v) : "l"(p) : "memory");
        if ((int)(v - target) >= 0) break;
        __nanosleep(64);
    }
}
__device__ __forceinline__ void flag_add(unsigned* p) {
    asm volatile("red.release.gpu.global.add.u32 [%0], 1;" :: "l"(p) : "memory");
}
__device__ __forceinline__ bool elect_one() {
    uint32_t ok;
    asm volatile("{\n.reg .pred p;\nelect.sync _|p, 0xffffffff;\nselp.u32 %0, 1, 0, p;\n}" : "=r"(ok));
    return ok;
}
__device__ __forceinline__ void fence_proxy_async() { asm volatile("fence.proxy.async;" ::: "memory"); }
__device__ __forceinline__ uint4 lds128(uint32_t addr) {
    uint4 v;
    asm volatile("ld.shared.v4.u32 {%0,%1,%2,%3}, [%4];" : "=r"(v.x), "=r"(v.y), "=r"(v.z), "=r"(v.w) : "r"(addr) : "memory");
    return v;
}
__device__ __forceinline__ float2 lds64f(uint32_t addr) {
    float2 v;
    asm volatile("ld.shared.v2.f32 {%0,%1}, [%2];" : "=f"(v.x), "=f"(v.y) : "r"(addr) : "memory");
    return v;
}
__device__ __forceinline__ void sts128(uint32_t addr, uint4 v) {
    asm volatile("st.shared.v4.u32 [%0], {%1,%2,%3,%4};" :: "r"(addr), "r"(v.x), "r"(v.y), "r"(v.z), "r"(v.w) : "memory");
}
__device__ __forceinline__ void sts64f(uint32_t addr, float a, float b) {
    asm volatile("st.shared.v2.f32 [%0], {%1,%2};" :: "r"(addr), "f"(a), "f"(b) : "memory");
}

__device__ __forceinline__ uint64_t policy(bool stream) {
    uint64_t p;
    if (stream) asm("createpolicy.fractional.L2::evict_first.b64 %0, 1.0;" : "=l"(p));
    else asm("createpolicy.fractional.L2::evict_normal.b64 %0, 1.0;" : "=l"(p));
    return p;
}
__device__ __forceinline__ void tma_2d(uint32_t dst, const CUtensorMap* m, uint32_t bar, int c0, int c1, uint64_t pol) {
    asm volatile("cp.async.bulk.tensor.2d.shared::cluster.global.mbarrier::complete_tx::bytes.L2::cache_hint"
                 " [%0], [%1, {%3, %4}], [%2], %5;"
                 :: "r"(dst), "l"(m), "r"(bar), "r"(c0), "r"(c1), "l"(pol) : "memory");
}
__device__ __forceinline__ void tma_3d(uint32_t dst, const CUtensorMap* m, uint32_t bar, int c0, int c1, int c2, uint64_t pol) {
    asm volatile("cp.async.bulk.tensor.3d.shared::cluster.global.mbarrier::complete_tx::bytes.L2::cache_hint"
                 " [%0], [%1, {%3, %4, %5}], [%2], %6;"
                 :: "r"(dst), "l"(m), "r"(bar), "r"(c0), "r"(c1), "r"(c2), "l"(pol) : "memory");
}
__device__ __forceinline__ void tma_3d_mc(uint32_t dst, const CUtensorMap* m, uint32_t bar, int c1, int c2, uint64_t pol) {
    asm volatile("cp.async.bulk.tensor.3d.shared::cluster.global.mbarrier::complete_tx::bytes.multicast::cluster.L2::cache_hint"
                 " [%0], [%1, {%3, %4, %5}], [%2], %6, %7;"
                 :: "r"(dst), "l"(m), "r"(bar), "r"(0), "r"(c1), "r"(c2), "h"((uint16_t)3), "l"(pol) : "memory");
}
__device__ __forceinline__ void tma_5d_mc(uint32_t dst, const CUtensorMap* m, uint32_t bar, int c0, int c4, uint64_t pol) {
    asm volatile("cp.async.bulk.tensor.5d.shared::cluster.global.mbarrier::complete_tx::bytes.multicast::cluster.L2::cache_hint"
                 " [%0], [%1, {%3, %4, %4, %4, %5}], [%2], %6, %7;"
                 :: "r"(dst), "l"(m), "r"(bar), "r"(c0), "r"(0), "r"(c4), "h"((uint16_t)3), "l"(pol) : "memory");
}
__device__ __forceinline__ void tma_store_2d(const CUtensorMap* m, uint32_t src, int c0, int c1) {
    asm volatile("cp.async.bulk.tensor.2d.global.shared::cta.bulk_group [%0, {%2, %3}], [%1];"
                 :: "l"(m), "r"(src), "r"(c0), "r"(c1) : "memory");
}
__device__ __forceinline__ uint4 ldg_stream(const void* p, uint64_t pol) {
    uint4 v;
    asm volatile("ld.global.nc.L1::no_allocate.L2::cache_hint.v4.u32 {%0,%1,%2,%3}, [%4], %5;"
                 : "=r"(v.x), "=r"(v.y), "=r"(v.z), "=r"(v.w) : "l"(p), "l"(pol));
    return v;
}
__device__ __forceinline__ void prefetch_map(const CUtensorMap* m) {
    asm volatile("prefetch.tensormap [%0];" :: "l"(m) : "memory");
}
__device__ __forceinline__ void wg_fence() { asm volatile("wgmma.fence.sync.aligned;" ::: "memory"); }
__device__ __forceinline__ void wg_commit() { asm volatile("wgmma.commit_group.sync.aligned;" ::: "memory"); }
template <int N> __device__ __forceinline__ void wg_wait() { asm volatile("wgmma.wait_group.sync.aligned %0;" :: "n"(N) : "memory"); }

__device__ __forceinline__ uint64_t desc_a(uint32_t addr) {
    return (uint64_t)((addr & 0x3FFFF) >> 4) | (1ull << 16) | (64ull << 32) | (1ull << 62);
}
__device__ __forceinline__ uint64_t desc_b(uint32_t addr) {
    return (uint64_t)((addr & 0x3FFFF) >> 4) | (512ull << 16) | (64ull << 32) | (1ull << 62);
}

#define R8(d, o) "+f"(d[o]), "+f"(d[o+1]), "+f"(d[o+2]), "+f"(d[o+3]), "+f"(d[o+4]), "+f"(d[o+5]), "+f"(d[o+6]), "+f"(d[o+7])
#define R32(d, o) R8(d, o), R8(d, o+8), R8(d, o+16), R8(d, o+24)
#define R64(d, o) R32(d, o), R32(d, o+32)

__device__ __forceinline__ void wgmma_n256(float (&d)[128], uint64_t da, uint64_t db, int scale_d) {
    asm volatile("{\n.reg .pred p;\nsetp.ne.b32 p, %130, 0;\n"
        "wgmma.mma_async.sync.aligned.m64n256k16.f32.bf16.bf16 "
        "{%0,%1,%2,%3,%4,%5,%6,%7,%8,%9,%10,%11,%12,%13,%14,%15,%16,%17,%18,%19,%20,%21,%22,%23,%24,%25,%26,%27,%28,%29,%30,%31,"
        "%32,%33,%34,%35,%36,%37,%38,%39,%40,%41,%42,%43,%44,%45,%46,%47,%48,%49,%50,%51,%52,%53,%54,%55,%56,%57,%58,%59,%60,%61,%62,%63,"
        "%64,%65,%66,%67,%68,%69,%70,%71,%72,%73,%74,%75,%76,%77,%78,%79,%80,%81,%82,%83,%84,%85,%86,%87,%88,%89,%90,%91,%92,%93,%94,%95,"
        "%96,%97,%98,%99,%100,%101,%102,%103,%104,%105,%106,%107,%108,%109,%110,%111,%112,%113,%114,%115,%116,%117,%118,%119,%120,%121,%122,%123,%124,%125,%126,%127},"
        " %128, %129, p, 1, 1, 0, 1;\n}"
        : R64(d, 0), R64(d, 64) : "l"(da), "l"(db), "r"(scale_d));
}
__device__ __forceinline__ void wgmma_n128(float (&d)[64], uint64_t da, uint64_t db, int scale_d) {
    asm volatile("{\n.reg .pred p;\nsetp.ne.b32 p, %66, 0;\n"
        "wgmma.mma_async.sync.aligned.m64n128k16.f32.bf16.bf16 "
        "{%0,%1,%2,%3,%4,%5,%6,%7,%8,%9,%10,%11,%12,%13,%14,%15,%16,%17,%18,%19,%20,%21,%22,%23,%24,%25,%26,%27,%28,%29,%30,%31,"
        "%32,%33,%34,%35,%36,%37,%38,%39,%40,%41,%42,%43,%44,%45,%46,%47,%48,%49,%50,%51,%52,%53,%54,%55,%56,%57,%58,%59,%60,%61,%62,%63},"
        " %64, %65, p, 1, 1, 0, 1;\n}"
        : R64(d, 0) : "l"(da), "l"(db), "r"(scale_d));
}

__device__ __forceinline__ uint32_t pack_bf16(float lo, float hi) {
    uint32_t r; asm("cvt.rn.bf16x2.f32 %0, %1, %2;" : "=r"(r) : "f"(hi), "f"(lo)); return r;
}
__device__ __forceinline__ float bf_lo(uint32_t v) { return __uint_as_float(v << 16); }
__device__ __forceinline__ float bf_hi(uint32_t v) { return __uint_as_float(v & 0xffff0000u); }
__device__ __forceinline__ float round_bf16(float v) { return bf_lo(pack_bf16(v, 0.f)); }
__device__ __forceinline__ uint32_t mul_bf16x2(uint32_t a, uint32_t b) {
    uint32_t r; asm("mul.rn.bf16x2 %0, %1, %2;" : "=r"(r) : "r"(a), "r"(b)); return r;
}
__device__ __forceinline__ uint32_t add_bf16x2(uint32_t a, uint32_t b) {
    uint32_t r; asm("add.rn.bf16x2 %0, %1, %2;" : "=r"(r) : "r"(a), "r"(b)); return r;
}
__device__ __forceinline__ uint32_t sub_bf16x2(uint32_t a, uint32_t b) {
    uint32_t r; asm("sub.rn.bf16x2 %0, %1, %2;" : "=r"(r) : "r"(a), "r"(b)); return r;
}
__device__ __forceinline__ float tanh_fast(float x) { float r; asm("tanh.approx.f32 %0, %1;" : "=f"(r) : "f"(x)); return r; }
__device__ __forceinline__ float gelu_tanh(float g) {
    float t = fmaf(g * g, 0.044715f * 0.7978845608f, 0.7978845608f) * g;
    float hg = 0.5f * g;
    return fmaf(hg, tanh_fast(t), hg);
}
__device__ __forceinline__ uint32_t geglu2(uint32_t g2, uint32_t u2) {
    return mul_bf16x2(pack_bf16(gelu_tanh(bf_lo(g2)), gelu_tanh(bf_hi(g2))), u2);
}
__device__ __forceinline__ float silu(float d) {
    float hd = 0.5f * d;
    return fmaf(hd, tanh_fast(hd), hd);
}
__device__ __forceinline__ float ex2_fast(float x) { float r; asm("ex2.approx.ftz.f32 %0, %1;" : "=f"(r) : "f"(x)); return r; }
__device__ __forceinline__ void unpack8(uint4 v, float (&f)[8]) {
    f[0] = bf_lo(v.x); f[1] = bf_hi(v.x); f[2] = bf_lo(v.y); f[3] = bf_hi(v.y);
    f[4] = bf_lo(v.z); f[5] = bf_hi(v.z); f[6] = bf_lo(v.w); f[7] = bf_hi(v.w);
}
template <int N> __device__ __forceinline__ void fence_regs(float (&d)[N]) {
#pragma unroll
    for (int i = 0; i < N; i++) asm volatile("" : "+f"(d[i]) :: "memory");
}

__device__ __forceinline__ float rcp_fast(float x) { float r; asm("rcp.approx.ftz.f32 %0, %1;" : "=f"(r) : "f"(x)); return r; }
__device__ __forceinline__ uint32_t max_bf16x2(uint32_t a, uint32_t b) {
    uint32_t r; asm("max.bf16x2 %0, %1, %2;" : "=r"(r) : "r"(a), "r"(b)); return r;
}
__device__ __forceinline__ uint4 ldsm4(uint32_t addr) {
    uint4 v;
    asm volatile("ldmatrix.sync.aligned.m8n8.x4.shared.b16 {%0,%1,%2,%3}, [%4];"
                 : "=r"(v.x), "=r"(v.y), "=r"(v.z), "=r"(v.w) : "r"(addr) : "memory");
    return v;
}
__device__ __forceinline__ uint4 ldsm4_t(uint32_t addr) {
    uint4 v;
    asm volatile("ldmatrix.sync.aligned.m8n8.x4.trans.shared.b16 {%0,%1,%2,%3}, [%4];"
                 : "=r"(v.x), "=r"(v.y), "=r"(v.z), "=r"(v.w) : "r"(addr) : "memory");
    return v;
}
__device__ __forceinline__ void mma_16816(float (&c)[4], uint32_t a0, uint32_t a1, uint32_t a2, uint32_t a3, uint32_t b0, uint32_t b1) {
    asm("mma.sync.aligned.m16n8k16.row.col.f32.bf16.bf16.f32 {%0,%1,%2,%3}, {%4,%5,%6,%7}, {%8,%9}, {%0,%1,%2,%3};"
        : "+f"(c[0]), "+f"(c[1]), "+f"(c[2]), "+f"(c[3]) : "r"(a0), "r"(a1), "r"(a2), "r"(a3), "r"(b0), "r"(b1));
}
__device__ __forceinline__ void mma_1688(float (&c)[4], uint32_t a0, uint32_t a1, uint32_t b0) {
    asm("mma.sync.aligned.m16n8k8.row.col.f32.bf16.bf16.f32 {%0,%1,%2,%3}, {%4,%5}, {%6}, {%0,%1,%2,%3};"
        : "+f"(c[0]), "+f"(c[1]), "+f"(c[2]), "+f"(c[3]) : "r"(a0), "r"(a1), "r"(b0));
}
__device__ __forceinline__ void qk_tile(float (&c)[4], const uint4& q0, const uint4& q1, const uint4& k, float init) {
    c[0] = c[1] = c[2] = c[3] = init;
    mma_16816(c, q0.x, q0.y, q0.z, q0.w, k.x, k.y);
    mma_16816(c, q1.x, q1.y, q1.z, q1.w, k.z, k.w);
}
__device__ __forceinline__ uint32_t scaled_logits(bool first, float a0, float a1, float b0, float b1) {
    uint32_t p, r;
    asm("{\n.reg .pred p;\nsetp.ne.u32 p, %1, 0;\n@p cvt.rn.bf16x2.f32 %0, %3, %2;\n@!p cvt.rn.bf16x2.f32 %0, %5, %4;\n}"
        : "=r"(p) : "r"((uint32_t)first), "f"(a0), "f"(a1), "f"(b0), "f"(b1));
    asm("fma.rn.bf16x2 %0, %1, %2, %3;" : "=r"(r) : "r"(p), "r"(0x3e353e35u), "r"(mul_bf16x2(p, 0x379e379eu)));
    return r;
}
template <typename T> __device__ __forceinline__ T uniform(T v) { return __shfl_sync(0xffffffffu, v, 0); }

__device__ __forceinline__ void attention(const CUtensorMap* maps, uint32_t base, uint32_t zero, int grp, int warp, int lane) {
    constexpr float LOG2E = 1.4426950408889634f;
    const int g = lane >> 2, t = lane & 3;
    const bool up0 = 2 * t > g, up1 = 2 * t + 1 > g;
    const uint32_t keep = (up0 ? 0x0000ffffu : 0u) | (up1 ? 0xffff0000u : 0u);
    const uint32_t buf = base + warp * 2 * ATT_SLOT, bar = base + AUX_OFF + warp * 16;
    const uint32_t qoff = (lane & 15) * 128 + (((lane >> 4) ^ (lane & 7)) << 4);
    const uint32_t koff = 2048 + (lane & 7) * 128 + (((lane >> 3) ^ (lane & 7)) << 4);
    const int col = uniform((grp * 4 + warp / 3) * 64), first = uniform(warp % 3 * 43 * 16), last = min(first + 43 * 16, SEQ);
    const CUtensorMap* const mqk = reinterpret_cast<const CUtensorMap*>(uniform(reinterpret_cast<uint64_t>(maps)));
    const CUtensorMap *const mv = mqk + 1, *const mo = mqk + 2;
    const uint64_t pol = policy(P_QKV);
    uint4 kp[2], vp[2];
    uint32_t l0[2], l1[2], m[2];
    float s[2][3][4];
    auto scores = [&](uint32_t st, int row) {
        const float before = (row & 1023) == 0 ? -5.656854e9f : 0.f;
#pragma unroll
        for (int h = 0; h < 2; h++) {
            const uint4 q0 = ldsm4(st + (qoff ^ (h * 64))), q1 = ldsm4(st + (qoff ^ (h * 64 + 32)));
            const uint4 k0 = ldsm4(st + (koff ^ (h * 64))), k1 = ldsm4(st + 1024 + (koff ^ (h * 64)));
            qk_tile(s[h][0], q0, q1, kp[h], before);
            qk_tile(s[h][1], q0, q1, k0, 0.f);
            qk_tile(s[h][2], q0, q1, k1, 0.f);
            kp[h] = k1;
        }
    };
    auto logits = [&]() {
#pragma unroll
        for (int h = 0; h < 2; h++) {
            l0[h] = scaled_logits(up0, s[h][0][0], s[h][1][2], s[h][1][0], s[h][2][2]);
            l1[h] = scaled_logits(up1, s[h][0][1], s[h][1][3], s[h][1][1], s[h][2][3]);
            m[h] = max_bf16x2(l0[h], l1[h]);
            m[h] = max_bf16x2(m[h], __shfl_xor_sync(0xffffffffu, m[h], 1));
        }
    };
    auto row_max = [&]() {
#pragma unroll
        for (int h = 0; h < 2; h++) m[h] = max_bf16x2(m[h], __shfl_xor_sync(0xffffffffu, m[h], 2));
    };
    auto exchange = [&](uint32_t st, uint32_t b, int row, int store, int load) {
        asm volatile("{\n.reg .pred e, p, q;\n"
            "fence.proxy.async.shared::cta;\n"
            "bar.warp.sync 0xffffffff;\n"
            "elect.sync _|e, 0xffffffff;\n"
            "setp.ne.and.b32 p, %10, 0, e;\n"
            "setp.ne.and.b32 q, %11, 0, e;\n"
            "@q mbarrier.arrive.expect_tx.shared::cta.b64 _, [%2], 6144;\n"
            "@q cp.async.bulk.tensor.3d.shared::cluster.global.mbarrier::complete_tx::bytes.L2::cache_hint [%0], [%3, {%6, %7, %12}], [%2], %14;\n"
            "@q cp.async.bulk.tensor.2d.shared::cluster.global.mbarrier::complete_tx::bytes.L2::cache_hint [%0 + 4096], [%4, {%13, %8}], [%2], %14;\n"
            "@e cp.async.bulk.wait_group.read 0;\n"
            "@p cp.async.bulk.tensor.2d.global.shared::cta.bulk_group [%5, {%6, %9}], [%1 + 6144];\n"
            "@e cp.async.bulk.commit_group;\n"
            "bar.warp.sync 0xffffffff;\n}"
            :: "r"(st), "r"(st ^ ATT_SLOT), "r"(b), "l"(mqk), "l"(mv), "l"(mo), "r"(col), "r"(row + 48), "r"(row + 32),
               "r"(row - 16), "r"(store), "r"(load), "r"(0), "r"(col + 2 * DM), "l"(pol) : "memory");
    };
    if (elect_one()) {
        mbar_init(bar, 1); mbar_init(bar + 8, 1);
        prefetch_map(mqk); prefetch_map(mv); prefetch_map(mo);
        const unsigned epoch = __ldcg(g_epoch + blockIdx.x * 16 + warp) + 1;
        flag_wait(g_flags + F_QKV * 512, epoch * CNT_QKV);
        fence_proxy_async();
        mbar_expect_tx(bar + 8, 8192);
        tma_3d(buf + ATT_SLOT, mqk, bar + 8, col, first, 0, pol);
        tma_2d(buf + ATT_SLOT + 4096, mv, bar + 8, col + 2 * DM, first - 16, policy(false));
        tma_2d(buf + ATT_SLOT + 6144, mv, bar + 8, col + DM, first - 16, policy(false));
        mbar_expect_tx(bar, 6144);
        tma_3d(buf, mqk, bar, col, first + 16, 0, pol);
        tma_2d(buf + 4096, mv, bar, col + 2 * DM, first, pol);
        g_epoch[blockIdx.x * 16 + warp] = epoch;
        if (warp == 0) TRACE(9);
    }
    __syncwarp();
    mbar_wait(bar + 8, 0);
#pragma unroll
    for (int h = 0; h < 2; h++) {
        kp[h] = ldsm4(buf + ATT_SLOT + 5120 + (koff ^ (h * 64)));
        vp[h] = ldsm4_t(buf + ATT_SLOT + 3072 + (koff ^ (h * 64)));
    }
    scores(buf + ATT_SLOT, first);
    exchange(buf + ATT_SLOT, bar + 8, first - 16, 0, 1);
    logits();
    row_max();
    uint32_t st = buf, b = bar, cnt = 1;
    bool ready = mbar_try_wait(b, 0);
#pragma unroll 1
    for (int row = first; row < last; row += 16) {
        uint32_t pa[2], pb[2];
        if (!ready) mbar_wait(b, (cnt >> 1) & 1);
        uint4 v[2][2];
#pragma unroll
        for (int h = 0; h < 2; h++) {
            const float ma = -LOG2E * bf_lo(m[h]), mb = -LOG2E * bf_hi(m[h]);
            const float a0 = ex2_fast(fmaf(bf_lo(l0[h]), LOG2E, ma)), a1 = ex2_fast(fmaf(bf_lo(l1[h]), LOG2E, ma));
            const float b0 = ex2_fast(fmaf(bf_hi(l0[h]), LOG2E, mb)), b1 = ex2_fast(fmaf(bf_hi(l1[h]), LOG2E, mb));
            float sum[4] = {0.f, 0.f, 0.f, 0.f};
            mma_1688(sum, pack_bf16(a0, a1), pack_bf16(b0, b1), 0x3f803f80u);
            const float ra = rcp_fast(sum[0]), rb = rcp_fast(sum[2]);
            pa[h] = pack_bf16(a0 * ra, a1 * ra);
            pb[h] = pack_bf16(b0 * rb, b1 * rb);
        }
        scores(st, row + 16);
#pragma unroll
        for (int h = 0; h < 2; h++) {
            v[h][0] = ldsm4_t(st + 4096 + (qoff ^ (h * 64)));
            v[h][1] = ldsm4_t(st + 4096 + (qoff ^ (h * 64 + 32)));
        }
        exchange(st, b, row, row > first, row + 32 < last);
        logits();
        float o[2][4][4];
#pragma unroll
        for (int h = 0; h < 2; h++) {
            const uint32_t prev[4] = {vp[h].x, vp[h].y, vp[h].z, vp[h].w};
            const uint32_t own[8] = {v[h][0].x, v[h][0].y, v[h][0].z, v[h][0].w, v[h][1].x, v[h][1].y, v[h][1].z, v[h][1].w};
            const uint32_t a0 = pa[h] & keep, a1 = pa[h] & ~keep, a2 = pb[h] & keep, a3 = pb[h] & ~keep;
            const uint32_t z0 = pa[h] & zero, z1 = pb[h] & zero;
#pragma unroll
            for (int j = 0; j < 4; j++) {
                o[h][j][0] = o[h][j][1] = o[h][j][2] = o[h][j][3] = 0.f;
                mma_1688(o[h][j], a0, z0, prev[j]);
                mma_16816(o[h][j], a1, a2, z1, a3, own[2 * j], own[2 * j + 1]);
            }
            vp[h] = make_uint4(own[1], own[3], own[5], own[7]);
        }
        row_max();
        b ^= 8; cnt++;
        ready = mbar_try_wait(b, (cnt >> 1) & 1);
#pragma unroll
        for (int h = 0; h < 2; h++) {
#pragma unroll
            for (int d = 0; d < 2; d++)
                asm volatile("stmatrix.sync.aligned.m8n8.x4.shared.b16 [%0], {%1,%2,%3,%4};"
                             :: "r"(st + 6144 + (qoff ^ (h * 64 + d * 32))),
                                "r"(pack_bf16(o[h][2 * d][0], o[h][2 * d][1])), "r"(pack_bf16(o[h][2 * d][2], o[h][2 * d][3])),
                                "r"(pack_bf16(o[h][2 * d + 1][0], o[h][2 * d + 1][1])),
                                "r"(pack_bf16(o[h][2 * d + 1][2], o[h][2 * d + 1][3])) : "memory");
        }
        st ^= ATT_SLOT;
    }
    exchange(st, b, last, 1, 0);
    if (elect_one()) {
        asm volatile("cp.async.bulk.wait_group 0;" ::: "memory");
        fence_proxy_async();
        flag_add(g_flags + F_O * 512);
        if (warp == 0) TRACE(10);
    }
}

__device__ __forceinline__ void warp_sum2(float& a, float& b) {
#pragma unroll
    for (int o = 16; o > 0; o >>= 1) {
        a += __shfl_xor_sync(0xffffffffu, a, o);
        b += __shfl_xor_sync(0xffffffffu, b, o);
    }
}
__device__ __forceinline__ float row_sum(const uint32_t* w) {
    float a = 0.f, b = 0.f;
#pragma unroll
    for (int i = 0; i < 16; i++) { a += bf_lo(w[i]); b += bf_hi(w[i]); }
    return a + b;
}
__device__ __forceinline__ float row_sq(const uint32_t* w, float mean) {
    float a = 0.f, b = 0.f;
#pragma unroll
    for (int i = 0; i < 16; i++) {
        const float lo = bf_lo(w[i]) - mean, hi = bf_hi(w[i]) - mean;
        a = fmaf(lo, lo, a); b = fmaf(hi, hi, b);
    }
    return a + b;
}
__device__ __forceinline__ float row_inv(float sq) {
    return 1.f / round_bf16(sqrtf(round_bf16(round_bf16(sq * (1.f / DM)) + 1e-5f)));
}
__device__ __forceinline__ void row_store(const uint32_t* w, float mean, float inv, __nv_bfloat16* dst) {
    const uint32_t m2 = pack_bf16(mean, mean);
#pragma unroll
    for (int i = 0; i < 2; i++) {
        uint32_t o[4];
#pragma unroll
        for (int j = 0; j < 4; j++) {
            const uint32_t c = sub_bf16x2(w[i * 4 + j], m2);
            o[j] = pack_bf16(bf_lo(c) * inv, bf_hi(c) * inv);
        }
        *reinterpret_cast<uint4*>(dst + i * 256) = make_uint4(o[0], o[1], o[2], o[3]);
    }
}

struct Params {
    CUtensorMap x, xn, wv, wqk, wg, wu, wg1, wu1, qk, v, o, a2, wo, wd, out;
    const __nv_bfloat16* px;
    uint32_t zero;
};

__global__ void __cluster_dims__(2, 1, 1) __launch_bounds__(384, 1)
fused_kernel(const __grid_constant__ Params prm) {
    extern __shared__ __align__(1024) uint8_t smem_raw[];
    const uint32_t base = (smem_u32(smem_raw) + 1023) & ~1023u;
    const uint32_t bars = base + BAR_OFF;
    auto full0 = [&](int s) { return bars + s * 8; };
    auto empty0 = [&](int s) { return bars + 48 + s * 8; };
    auto full1 = [&](int s) { return bars + 96 + s * 8; };
    auto empty1 = [&](int s) { return bars + 128 + s * 8; };
    auto full2 = [&](int s) { return bars + 160 + s * 8; };
    auto empty2 = [&](int s) { return bars + 208 + s * 8; };
    const uint32_t sig_bar = bars + 256, fold_bar = bars + 264, x_bar = bars + 272, cs_bar = bars + 280, dep_bar = bars + 288;
    auto wide = [&](int s) { return base + s * W_STAGE_BYTES; };
    auto narrow = [&](int q) { return base + q * N_STAGE_BYTES; };
    const uint32_t aux = base + AUX_OFF;

    const int warp = __shfl_sync(0xffffffffu, threadIdx.x >> 5, 0);
    const int lane = threadIdx.x & 31;
    const int rank = blockIdx.x & 1;
    const int mblk = ((blockIdx.x >> 1) & 7) * 2 + rank;
    const int nslot = blockIdx.x >> 4;

    if (blockIdx.x >= NGEMM) {
        if (threadIdx.x == 0) { TRACE_GT(0); TRACE(1); }
        attention(&prm.qk, (base + 2 * ATT_SLOT - 1) & ~(2u * ATT_SLOT - 1), prm.zero, blockIdx.x - NGEMM, warp, lane);
    } else if (warp >= 8) {
        unsigned* const flags = g_flags + mblk * 32;
        if (elect_one()) {
            if (warp == 8) {
                TRACE_GT(0); TRACE(1);
                prefetch_map(&prm.x); prefetch_map(&prm.wv);
                for (int s = 0; s < N_STAGES; s++) mbar_init(full0(s), 1);
            } else if (warp == 9) {
                for (int s = 0; s < N_STAGES; s++) { mbar_init(empty0(s), 4); mbar_init(empty2(s), 4); }
            } else if (warp == 10) {
                for (int s = 0; s < W_STAGES; s++) { mbar_init(full1(s), 1); mbar_init(empty1(s), 4); mbar_init(dep_bar + s * 8, 1); }
            } else {
                for (int s = 0; s < N_STAGES; s++) mbar_init(full2(s), 1);
                mbar_init(sig_bar, 8); mbar_init(fold_bar, 2); mbar_init(x_bar, 1); mbar_init(cs_bar, 1);
                prefetch_map(&prm.wqk);
            }
            asm volatile("fence.mbarrier_init.release.cluster;" ::: "memory");
        }
        __syncwarp();
        asm volatile("barrier.cluster.arrive.relaxed.aligned;" ::: "memory");
        if (warp == 8 && lane == 0) {
            for (int j = 0; j < N_STAGES; j++) {
                const int q = (j + 2) % N_STAGES;
                mbar_expect_tx(full0(q), N_STAGE_BYTES);
                tma_2d(narrow(q), &prm.x, full0(q), j * 64, mblk * 128, policy(P_X));
            }
            TRACE(15);
        }
        asm volatile("setmaxnreg.dec.sync.aligned.u32 %0;" :: "n"(AUX_REGS));
        asm volatile("barrier.cluster.wait.acquire.aligned;" ::: "memory");

        if (warp == 8) {
            if (lane == 0) {
                TRACE(2);
                for (int j = 0; j < KSTEPS; j++) {
                    const int q = (j + 2) % N_STAGES;
                    if (j >= N_STAGES) {
                        mbar_wait(empty0(q), j >= 2 * N_STAGES);
                        mbar_expect_tx(full0(q), N_STAGE_BYTES);
                        tma_2d(narrow(q), &prm.x, full0(q), j * 64, mblk * 128, policy(P_X));
                    }
                    tma_3d_mc(narrow(q) + A_BYTES + rank * 8192, &prm.wv, full0(q), j * 64, 32 + nslot * 2 + rank, policy(P_W1));
                    if (j == N_STAGES - 1) {
                        prefetch_map(&prm.xn); prefetch_map(rank ? &prm.wu : &prm.wg);
                        prefetch_map(rank ? &prm.wu1 : &prm.wg1);
                        prefetch_map(&prm.a2); prefetch_map(&prm.wo); prefetch_map(&prm.wd); prefetch_map(&prm.out);
                    }
                }
                TRACE(14); mbar_wait(dep_bar, 0); TRACE(3);
                uint32_t ph = 1;
                for (int it = 0; it < W_TILES * KSTEPS; it++) {
                    const int s = it & 3, k = it & 15;
                    if (it < W_STAGES) {
                        if (!(it & 1)) mbar_wait(empty0(it + it / 2), it == 0);
                        mbar_wait(empty0(it + it / 2 + 1), it == 0);
                    } else {
                        mbar_wait(empty1(s), ph);
                    }
                    mbar_expect_tx(full1(s), W_STAGE_BYTES);
                    tma_2d(wide(s), &prm.xn, full1(s), k * 64, mblk * 128, policy(false));
                    const uint32_t dst = wide(s) + A_BYTES + rank * 16384;
                    if (it < KSTEPS) tma_3d_mc(dst, &prm.wqk, full1(s), k * 64, nslot * 4 + rank * 2, policy(P_W1));
                    else tma_3d_mc(dst, rank ? &prm.wu : &prm.wg, full1(s), k * 64, ((it >> 4) * 8 - 8 + nslot) * 2, policy(P_W1));
                    if (s == 3) ph ^= 1;
                }
                TRACE(4);
                int q = 0; uint32_t ph2 = 1;
                for (int u = 0; u < U_END; u++) {
                    if (u == U_D || u == U_LATE || u == U_S) {
                        TRACE(u == U_D ? 36 : (u == U_LATE ? 6 : 32));
                        mbar_wait(dep_bar + (u == U_D ? 8 : (u == U_LATE ? 16 : 24)), 0);
                        TRACE(u == U_D ? 5 : (u == U_LATE ? 7 : 33));
                    }
                    if (u < N_STAGES) {
                        if (u == 0) mbar_wait(empty1(0), ph);
                        if (u == 1) mbar_wait(empty1(1), ph);
                        if (u == 3) mbar_wait(empty1(2), ph);
                        if (u == 4) mbar_wait(empty1(3), ph);
                    } else {
                        mbar_wait(empty2(q), ph2);
                    }
                    const uint32_t sa = narrow(q), sb = sa + A_BYTES + rank * 8192;
                    mbar_expect_tx(full2(q), N_STAGE_BYTES);
                    if (u < U_D) {
                        tma_2d(sa, &prm.xn, full2(q), u * 64, mblk * 128, policy(P_XN4));
                        tma_3d_mc(sb, rank ? &prm.wu1 : &prm.wg1, full2(q), u * 64, 48 + nslot, policy(P_W1));
                    } else {
                        const bool down = u < U_S;
                        const int k = down ? u - U_D : u - U_S;
                        tma_3d(sa, &prm.a2, full2(q), (down ? DM : 0) + k * 64, 0, mblk * 64, policy(P_A2));
                        tma_5d_mc(sb, down ? &prm.wd : &prm.wo, full2(q), nslot * 128 + rank * 64, k * 2, policy(P_W2));
                    }
                    if (u == N_STAGES - 1) {
                        mbar_expect_tx(x_bar, 32768);
                        tma_2d(aux, &prm.x, x_bar, nslot * 128, mblk * 128, policy(P_X));
                        tma_2d(aux + 16384, &prm.x, x_bar, nslot * 128 + 64, mblk * 128, policy(P_X));
                    }
                    if (++q == N_STAGES) { q = 0; ph2 ^= 1; }
                }
                TRACE(8);
            }
        } else if (warp == 9) {
            if (lane == 0) {
                for (int t = 0; t < 6; t++) {
                    mbar_wait(sig_bar, t & 1);
                    if (t < 2) TRACE(t ? 37 : 11);
                    flag_add(t == 1 ? g_flags + F_QKV * 512 : flags + (t == 0 ? F_LN : (t < 4 ? F_EARLY : F_LATE)) * 512);
                    if (t < 2) TRACE(t ? 43 : 42);
                }
            }
        } else if (warp == 10) {
            const unsigned epoch = __ldcg(g_epoch + blockIdx.x * 16) + 1;
            if (lane == 0) {
                flag_wait(flags + F_LN * 512, epoch * CNT_LN);
                fence_proxy_async(); mbar_arrive(dep_bar);
            }
            __syncwarp();
            const uint4* sp = reinterpret_cast<const uint4*>(g_stats + mblk * 128) + lane;
            const uint4 s0 = __ldcg(sp), s1 = __ldcg(sp + 32);
            sts128(aux + 512 + lane * 16, s0);
            sts128(aux + 1024 + lane * 16, s1);
            __syncwarp();
            if (lane == 0) {
                mbar_arrive(fold_bar);
                g_epoch[blockIdx.x * 16] = epoch;
                flag_wait(flags + F_EARLY * 512, epoch * CNT_EARLY);
                fence_proxy_async(); mbar_arrive(dep_bar + 8);
                flag_wait(flags + F_LATE * 512, epoch * CNT_LATE);
                fence_proxy_async(); mbar_arrive(dep_bar + 16);
                flag_wait(g_flags + F_O * 512, epoch * CNT_O);
                fence_proxy_async(); mbar_arrive(dep_bar + 24);
            }
        } else {
            const unsigned epoch = __ldcg(g_epoch + blockIdx.x * 16 + 1) + 1;
            if (elect_one()) {
                mbar_expect_tx(cs_bar, 16384);
                tma_3d(aux + 16384, &prm.wqk, cs_bar, 0, mblk * 64, 32 + nslot * 2, policy(P_W1));
            }
            float cs[8];
#pragma unroll
            for (int d = 0; d < 8; d++) cs[d] = 0.f;
            mbar_wait(cs_bar, 0);
            const uint32_t wa = aux + 16384 + (lane & 8) * 1024 + (lane >> 4) * 128 + (((lane & 7) ^ (lane >> 4)) << 4);
#pragma unroll 1
            for (int i = 0; i < 8; i++) {
#pragma unroll
                for (int j = 0; j < 4; j++) {
                    float f[8];
                    unpack8(lds128((wa ^ (j * 32)) + i * 1024 + j * 256), f);
#pragma unroll
                    for (int d = 0; d < 8; d++) cs[d] += f[d];
                }
            }
#pragma unroll
            for (int d = 0; d < 8; d++) cs[d] += __shfl_xor_sync(0xffffffffu, cs[d], 16);
            *reinterpret_cast<float4*>(g_colsum + mblk * DM + nslot * 128 + (lane & 15) * 8 + (lane >> 4) * 4) =
                lane < 16 ? make_float4(cs[0], cs[1], cs[2], cs[3]) : make_float4(cs[4], cs[5], cs[6], cs[7]);
            __syncwarp();
            if (lane == 0) {
                TRACE(34);
                flag_add(g_flags + F_CS * 512 + nslot * 32);
                flag_wait(g_flags + F_CS * 512 + nslot * 32, epoch * CNT_CS);
            }
            __syncwarp();
            const float4* gp = reinterpret_cast<const float4*>(g_colsum + nslot * 128) + lane;
            float4 c = make_float4(0.f, 0.f, 0.f, 0.f);
#pragma unroll 8
            for (int m = 0; m < 16; m++) {
                const float4 a = __ldcg(gp + m * (DM / 4));
                c.x += a.x; c.y += a.y; c.z += a.z; c.w += a.w;
            }
            const uint32_t ca = aux + (lane >> 2) * 64 + (lane & 1) * 32 + (lane & 2) * 4;
            sts64f(ca, c.x, c.y);
            sts64f(ca + 16, c.z, c.w);
            __syncwarp();
            if (lane == 0) {
                mbar_arrive(fold_bar);
                g_epoch[blockIdx.x * 16 + 1] = epoch;
                TRACE(35);
            }
        }
    } else {
        asm volatile("barrier.cluster.arrive.relaxed.aligned;" ::: "memory");
        const int cw = threadIdx.x >> 5;
        const int tid = threadIdx.x & 127;
        const int lrow = mblk * 128 + nslot * 16 + cw * 2;
        uint32_t xw[32];
        {
            const uint4* xp = reinterpret_cast<const uint4*>(prm.px + (size_t)lrow * DM) + lane;
#pragma unroll
            for (int i = 0; i < 8; i++) {
                const uint4 v = ldg_stream(xp + i * 32, policy(P_X));
                xw[4 * i] = v.x; xw[4 * i + 1] = v.y; xw[4 * i + 2] = v.z; xw[4 * i + 3] = v.w;
            }
        }
        asm volatile("setmaxnreg.inc.sync.aligned.u32 %0;" :: "n"(CONSUMER_REGS));
        const int wg = __shfl_sync(0xffffffffu, threadIdx.x >> 7, 0);
        float mean0 = row_sum(xw), mean1 = row_sum(xw + 16);
        if (threadIdx.x == 0) TRACE(38);
        warp_sum2(mean0, mean1);
        mean0 *= 1.f / DM; mean1 *= 1.f / DM;
        float inv0 = row_sq(xw, mean0), inv1 = row_sq(xw + 16, mean1);
        warp_sum2(inv0, inv1);
        inv0 = row_inv(inv0); inv1 = row_inv(inv1);
        if (lane == 0) *reinterpret_cast<float4*>(g_stats + lrow) = make_float4(-round_bf16(mean0), inv0, -round_bf16(mean1), inv1);
        if (threadIdx.x == 0) TRACE(39);
        asm volatile("barrier.cluster.wait.acquire.aligned;" ::: "memory");

        auto release = [&](uint32_t bar) { if (tid < 2) mbar_arrive_cluster(bar, tid); };
        auto signal_stores = [&]() { __syncwarp(); if (lane == 0) mbar_arrive(sig_bar); };
        auto mma_narrow = [&](float (&d)[64], int q, bool accumulate) {
            asm volatile("" : "+r"(q));
            const uint64_t da = desc_a(narrow(q) + wg * 8192), db = desc_b(narrow(q) + A_BYTES);
            wg_fence();
#pragma unroll
            for (int kk = 0; kk < 4; kk++) wgmma_n128(d, da + kk * 2, db + kk * 128, accumulate || kk != 0);
            wg_commit();
        };

        uint32_t pk[64];
        {
            float accv[64];
#pragma unroll
            for (int i = 0; i < 64; i++) accv[i] = 0.f;
#pragma unroll
            for (int j = 0; j < 4; j++) {
                mbar_wait(full0(j + 2), 0);
                if (j == 0 && threadIdx.x == 0) TRACE(12);
                mma_narrow(accv, j + 2, j != 0);
                row_store(xw + j * 8, j < 2 ? mean0 : mean1, j < 2 ? inv0 : inv1, g_xn + (size_t)lrow * DM + j * 512 + lane * 8);
                if (j == 3) signal_stores();
                wg_wait<1>();
                if (j > 0) release(empty0(j + 1));
            }
            int q = 0, qp = N_STAGES - 1;
#pragma unroll 1
            for (int j = 4; j < KSTEPS; j++) {
                mbar_wait(full0(q), j >= N_STAGES && j < 2 * N_STAGES);
                mma_narrow(accv, q, true);
                wg_wait<1>();
                release(empty0(qp));
                qp = q;
                if (++q == N_STAGES) q = 0;
            }
            wg_wait<0>();
            fence_regs(accv);
            release(empty0(N_STAGES - 1));
#pragma unroll
            for (int i = 0; i < 64; i++) pk[i] = __float_as_uint(accv[i]);
        }
        if (tid == 0) TRACE(16 + wg * 8);

        const int orow = ((lane >> 2) & 1) * (SEQ / 2) + mblk * 64 + cw * 8 + (lane >> 3);
        __nv_bfloat16* optr = g_qkv + (size_t)orow * NQKV + 2 * DM + nslot * 128 + (lane & 3) * 8;
        auto chunk_v = [&](int c) {
            const uint32_t sp = aux + 512 + (cw * 16 + (lane >> 2)) * 8;
            const float2 sa = lds64f(sp), sb = lds64f(sp + 64);
            uint32_t r[8];
#pragma unroll
            for (int j = 0; j < 2; j++) {
                const uint4 cs = lds128(aux + (c * 2 + j) * 64 + (lane & 3) * 16);
                const float c0 = __uint_as_float(cs.x), c1 = __uint_as_float(cs.y);
                const float c2 = __uint_as_float(cs.z), c3 = __uint_as_float(cs.w);
                const uint32_t* a = pk + 16 * c + 8 * j;
                r[2 * j] = pack_bf16(fmaf(sa.x, c0, __uint_as_float(a[0])) * sa.y, fmaf(sa.x, c1, __uint_as_float(a[1])) * sa.y);
                r[4 + 2 * j] = pack_bf16(fmaf(sb.x, c0, __uint_as_float(a[2])) * sb.y, fmaf(sb.x, c1, __uint_as_float(a[3])) * sb.y);
                r[2 * j + 1] = pack_bf16(fmaf(sa.x, c2, __uint_as_float(a[4])) * sa.y, fmaf(sa.x, c3, __uint_as_float(a[5])) * sa.y);
                r[5 + 2 * j] = pack_bf16(fmaf(sb.x, c2, __uint_as_float(a[6])) * sb.y, fmaf(sb.x, c3, __uint_as_float(a[7])) * sb.y);
            }
            *reinterpret_cast<uint4*>(optr + c * 32) = make_uint4(r[0], r[1], r[2], r[3]);
            *reinterpret_cast<uint4*>(optr + 4 * NQKV + c * 32) = make_uint4(r[4], r[5], r[6], r[7]);
        };
        auto chunk_qk = [&](int c) {
            *reinterpret_cast<uint4*>(optr + c * 32) = make_uint4(pk[8 * c], pk[8 * c + 2], pk[8 * c + 4], pk[8 * c + 6]);
            *reinterpret_cast<uint4*>(optr + 4 * NQKV + c * 32) = make_uint4(pk[8 * c + 1], pk[8 * c + 3], pk[8 * c + 5], pk[8 * c + 7]);
        };
        auto chunk_geglu = [&](int j) {
            const int c = j >> 1, h = j & 1;
            uint4 v;
            v.x = geglu2(pk[8 * c + h], pk[32 + 8 * c + h]);
            v.y = geglu2(pk[8 * c + 2 + h], pk[32 + 8 * c + 2 + h]);
            v.z = geglu2(pk[8 * c + 4 + h], pk[32 + 8 * c + 4 + h]);
            v.w = geglu2(pk[8 * c + 6 + h], pk[32 + 8 * c + 6 + h]);
            *reinterpret_cast<uint4*>(optr + h * 4 * K2 + c * 32) = v;
        };

        {
            float acc[128];
#pragma unroll
            for (int i = 0; i < 128; i++) asm volatile("mov.b32 %0, 0;" : "=f"(acc[i]));
#pragma unroll 1
            for (int t = 0; t < W_TILES; t++) {
#pragma unroll
                for (int k = 0; k < KSTEPS; k++) {
                    const int s = k & 3;
                    mbar_wait(full1(s), (k >> 2) & 1);
                    if (t == TRACE_T && threadIdx.x == 0) TRACE(44 + k);
                    if (wg == 1 && k == KSTEPS - W_SKEW) asm volatile("bar.sync 1, 256;" ::: "memory");
                    const uint64_t da = desc_a(wide(s) + wg * 8192), db = desc_b(wide(s) + A_BYTES);
                    wg_fence();
#pragma unroll
                    for (int kk = 0; kk < 4; kk++) wgmma_n256(acc, da + kk * 2, db + kk * 128, (k | kk) != 0);
                    wg_commit();
                    if (wg == 0 && k == KSTEPS - 1) asm volatile("bar.arrive 1, 256;" ::: "memory");
                    if (k >= 9 && k <= 12 && t == 0) {
                        if (k == 9) mbar_wait(fold_bar, 0);
                        chunk_v(k - 9);
                    }
                    if (k <= 3 && t == 1) {
                        chunk_qk(2 * k); chunk_qk(2 * k + 1);
                        if (k == 3) signal_stores();
                    }
                    if (k >= 1 && k <= 8 && t >= 2) {
                        chunk_geglu(k - 1);
                        if (k == 8) signal_stores();
                    }
                    wg_wait<1>();
                    if (k > 0) release(empty1((k - 1) & 3));
                }
                wg_wait<0>();
                fence_regs(acc);
                release(empty1(3));
#pragma unroll
                for (int i = 0; i < 64; i++) pk[i] = pack_bf16(acc[2 * i], acc[2 * i + 1]);
                optr = t == 0 ? g_qkv + (size_t)orow * NQKV + nslot * 256 + (lane & 3) * 8
                              : g_a2 + (size_t)orow * K2 + DM + (t * 8 - 8 + nslot) * 128 + (lane & 3) * 8;
                if (tid == 0) TRACE(17 + wg * 8 + t);
            }
        }

        float acch[64], accd[64], accs[64];
#pragma unroll
        for (int i = 0; i < 64; i++) acch[i] = 0.f;
#pragma unroll
        for (int u = 0; u < U_D; u++) {
            mbar_wait(full2(u % N_STAGES), (u / N_STAGES) & 1);
            mma_narrow(acch, u % N_STAGES, u != 0);
            if (u & 1) { chunk_geglu(u >> 1); if (u == U_D - 1) signal_stores(); }
            wg_wait<1>();
            if (u > 0) release(empty2((u - 1) % N_STAGES));
        }
        if (tid == 0) TRACE(40 + wg);
        optr = g_a2 + (size_t)orow * K2 + DM + 3072 + nslot * 64 + (lane & 3) * 8;
#pragma unroll
        for (int i = 0; i < 64; i++) accd[i] = 0.f;
#pragma unroll
        for (int u = U_D; u < U_D + 8; u++) {
            mbar_wait(full2(u % N_STAGES), (u / N_STAGES) & 1);
            mma_narrow(accd, u % N_STAGES, u != U_D);
            if (u & 1) {
                const int c = (u - U_D) >> 2, h = (u - U_D) >> 1 & 1;
                const float* a = acch + 16 * c + 2 * h;
                uint4 v;
                v.x = geglu2(pack_bf16(a[0], a[1]), pack_bf16(a[32], a[33]));
                v.y = geglu2(pack_bf16(a[4], a[5]), pack_bf16(a[36], a[37]));
                v.z = geglu2(pack_bf16(a[8], a[9]), pack_bf16(a[40], a[41]));
                v.w = geglu2(pack_bf16(a[12], a[13]), pack_bf16(a[44], a[45]));
                *reinterpret_cast<uint4*>(optr + h * 4 * K2 + c * 32) = v;
                if (u == U_D + 7) signal_stores();
            }
            wg_wait<1>();
            if (u == U_D) fence_regs(acch);
            release(empty2((u - 1) % N_STAGES));
        }
        {
            int q = (U_D + 8) % N_STAGES, qp = (U_D + 7) % N_STAGES; uint32_t ph = ((U_D + 8) / N_STAGES) & 1;
#pragma unroll 1
            for (int u = U_D + 8; u < U_S; u++) {
                mbar_wait(full2(q), ph);
                mma_narrow(accd, q, true);
                wg_wait<1>();
                release(empty2(qp));
                qp = q;
                if (++q == N_STAGES) { q = 0; ph ^= 1; }
            }
        }
        if (tid == 0) TRACE(16 + wg * 8 + 5);
#pragma unroll
        for (int i = 0; i < 64; i++) accs[i] = 0.f;
        uint32_t gk[32], xr[32];
        const uint32_t xs = aux + cw * 2048;
        const uint32_t xrow = xs + ((lane & 7) + ((lane >> 3) & 1) * 8) * 128;
        auto xaddr = [&](int j) { return xrow + (j >> 2) * 16384 + (((((j & 3) * 2) + (lane >> 4)) ^ (lane & 7)) << 4); };
#pragma unroll
        for (int u = U_S; u < U_END; u++) {
            const int v = u - U_S;
            mbar_wait(full2(u % N_STAGES), (u / N_STAGES) & 1);
            if (S_SKEW > 0 && wg == 1 && u == U_END - S_SKEW) asm volatile("bar.sync 1, 256;" ::: "memory");
            mma_narrow(accs, u % N_STAGES, v != 0);
            if (S_SKEW > 0 && wg == 0 && u == U_END - 1) asm volatile("bar.arrive 1, 256;" ::: "memory");
            if (v >= 1 && v <= 8) {
#pragma unroll
                for (int i = 4 * (v - 1); i < 4 * v; i++) {
                    const uint32_t d2 = pack_bf16(accd[2 * i], accd[2 * i + 1]);
                    gk[i] = pack_bf16(silu(bf_lo(d2)), silu(bf_hi(d2)));
                }
            }
            if (v == 9) mbar_wait(x_bar, 0);
            if (v >= 9 && v <= 12) {
#pragma unroll
                for (int j = 2 * (v - 9); j < 2 * (v - 8); j++)
                    asm volatile("ldmatrix.sync.aligned.m8n8.x4.shared.b16 {%0,%1,%2,%3}, [%4];"
                                 : "=r"(xr[4 * j]), "=r"(xr[4 * j + 1]), "=r"(xr[4 * j + 2]), "=r"(xr[4 * j + 3])
                                 : "r"(xaddr(j)) : "memory");
            }
            wg_wait<1>();
            if (v == 0) fence_regs(accd);
            if (u - 1 + N_STAGES < U_END) release(empty2((u - 1) % N_STAGES));
        }
        wg_wait<0>();
        fence_regs(accs);
        if (tid == 0) TRACE(16 + wg * 8 + 6);
#pragma unroll
        for (int j = 0; j < 8; j++) {
            uint32_t r[4];
#pragma unroll
            for (int i = 0; i < 4; i++) {
                const int e = j * 4 + i;
                r[i] = add_bf16x2(xr[e], mul_bf16x2(pack_bf16(accs[2 * e], accs[2 * e + 1]), gk[e]));
            }
            asm volatile("stmatrix.sync.aligned.m8n8.x4.shared.b16 [%0], {%1,%2,%3,%4};"
                         :: "r"(xaddr(j)), "r"(r[0]), "r"(r[1]), "r"(r[2]), "r"(r[3]) : "memory");
            if (j == 3 || j == 7) {
                asm volatile("fence.proxy.async.shared::cta;" ::: "memory");
                __syncwarp();
                if (lane == 0) {
                    tma_store_2d(&prm.out, xs + (j >> 2) * 16384, nslot * 128 + (j >> 2) * 64, mblk * 128 + cw * 16);
                    asm volatile("cp.async.bulk.commit_group;" ::: "memory");
                }
            }
        }
        if (lane == 0) asm volatile("cp.async.bulk.wait_group.read 0;" ::: "memory");
        if (tid == 0) { TRACE(16 + wg * 8 + 7); if (wg == 1) TRACE_GT(13); }
    }
}

typedef CUresult (*EncodeFn)(CUtensorMap*, CUtensorMapDataType, cuuint32_t, void*, const cuuint64_t*, const cuuint64_t*,
                             const cuuint32_t*, const cuuint32_t*, CUtensorMapInterleave, CUtensorMapSwizzle,
                             CUtensorMapL2promotion, CUtensorMapFloatOOBfill);

void encode(EncodeFn fn, CUtensorMap* m, const void* ptr, int rank, const cuuint64_t* dims, const cuuint64_t* strides,
            const cuuint32_t* box) {
    const cuuint32_t es[5] = {1, 1, 1, 1, 1};
    fn(m, CU_TENSOR_MAP_DATA_TYPE_BFLOAT16, rank, const_cast<void*>(ptr), dims, strides, box, es,
       CU_TENSOR_MAP_INTERLEAVE_NONE, CU_TENSOR_MAP_SWIZZLE_128B, CU_TENSOR_MAP_L2_PROMOTION_L2_128B,
       CU_TENSOR_MAP_FLOAT_OOB_FILL_NONE);
}
void encode_2d(EncodeFn fn, CUtensorMap* m, const void* ptr, int cols, int box_rows) {
    const cuuint64_t dims[2] = {(cuuint64_t)cols, SEQ}, strides[1] = {(cuuint64_t)cols * 2};
    const cuuint32_t box[2] = {64, (cuuint32_t)box_rows};
    encode(fn, m, ptr, 2, dims, strides, box);
}
void encode_w1(EncodeFn fn, CUtensorMap* m, const void* ptr, int cols, int blocks) {
    const cuuint64_t dims[3] = {64, DM, (cuuint64_t)cols / 64}, strides[2] = {(cuuint64_t)cols * 2, 128};
    const cuuint32_t box[3] = {64, 64, (cuuint32_t)blocks};
    encode(fn, m, ptr, 3, dims, strides, box);
}
void encode_qk(EncodeFn fn, CUtensorMap* m, const void* ptr) {
    const cuuint64_t dims[3] = {DM, SEQ, 3}, strides[2] = {NQKV * 2, DM * 2};
    const cuuint32_t box[3] = {64, 16, 2};
    encode(fn, m, ptr, 3, dims, strides, box);
}
void encode_a2(EncodeFn fn, CUtensorMap* m, const void* ptr) {
    const cuuint64_t dims[3] = {K2, 2, SEQ / 2}, strides[2] = {(cuuint64_t)SEQ * K2, K2 * 2};
    const cuuint32_t box[3] = {64, 2, 64};
    encode(fn, m, ptr, 3, dims, strides, box);
}
void encode_w2(EncodeFn fn, CUtensorMap* m, const void* ptr, int rows) {
    const cuuint64_t rb = DM * 2;
    const cuuint64_t dims[5] = {DM, 2, 4, 4, (cuuint64_t)rows / 32}, strides[4] = {rb, 8 * rb, 2 * rb, 32 * rb};
    const cuuint32_t box[5] = {64, 2, 4, 4, 2};
    encode(fn, m, ptr, 5, dims, strides, box);
}

}

extern "C" void kernel_launch(void* const* d_in, const int* in_sizes, int n_in, void* d_out, int out_size) {
    (void)in_sizes; (void)n_in; (void)out_size;
    static EncodeFn fn = nullptr;
    static void *p_xn = nullptr, *p_qkv = nullptr, *p_a2 = nullptr;
    if (!fn) {
        cudaDriverEntryPointQueryResult st;
        cudaGetDriverEntryPoint("cuTensorMapEncodeTiled", (void**)&fn, cudaEnableDefault, &st);
        cudaGetSymbolAddress(&p_xn, g_xn);
        cudaGetSymbolAddress(&p_qkv, g_qkv);
        cudaGetSymbolAddress(&p_a2, g_a2);
        cudaFuncSetAttribute(fused_kernel, cudaFuncAttributeMaxDynamicSharedMemorySize, SMEM_BYTES);
    }
    Params prm;
    encode_2d(fn, &prm.x, d_in[0], DM, 128);
    encode_2d(fn, &prm.xn, p_xn, DM, 128);
    encode_w1(fn, &prm.wv, d_in[1], NQKV, 1);
    encode_w1(fn, &prm.wqk, d_in[1], NQKV, 2);
    encode_w1(fn, &prm.wg, d_in[4], DF, 2);
    encode_w1(fn, &prm.wu, d_in[5], DF, 2);
    encode_w1(fn, &prm.wg1, d_in[4], DF, 1);
    encode_w1(fn, &prm.wu1, d_in[5], DF, 1);
    encode_qk(fn, &prm.qk, p_qkv);
    encode_2d(fn, &prm.v, p_qkv, NQKV, 16);
    encode_2d(fn, &prm.o, p_a2, K2, 16);
    encode_a2(fn, &prm.a2, p_a2);
    encode_w2(fn, &prm.wo, d_in[2], DM);
    encode_w2(fn, &prm.wd, d_in[6], DF);
    encode_2d(fn, &prm.out, d_out, DM, 16);
    prm.px = (const __nv_bfloat16*)d_in[0];
    prm.zero = 0;
    fused_kernel<<<NCTA, 384, SMEM_BYTES>>>(prm);
}
```

```cpp
#include <cuda_runtime.h>
#include <cuda_bf16.h>
#include <cuda.h>
#include <stdint.h>

#define P_W1 1
#define P_X 1
#define P_XN4 1
#define P_W2 1
#define P_A2 1
#define P_QKV 1

namespace {

constexpr int SEQ = 2048, DM = 1024, DF = 3584, K2 = DM + DF, NQKV = 3 * DM;
constexpr int NGEMM = 128, NCTA = 132;
constexpr int W_STAGES = 4, W_STAGE_BYTES = 49152, KSTEPS = 16, W_TILES = 4;
constexpr int N_STAGES = 6, N_STAGE_BYTES = 32768;
constexpr int U_D = 16, U_LATE = 48, U_S = 72, U_END = 88;
constexpr int A_BYTES = 16384;
constexpr int AUX_OFF = W_STAGES * W_STAGE_BYTES;
constexpr int BAR_OFF = AUX_OFF + 32768;
constexpr int SMEM_BYTES = BAR_OFF + 2304;
constexpr int W_SKEW = 2, S_SKEW = 2;
constexpr int CONSUMER_REGS = 224, AUX_REGS = 56;
constexpr int ATT_SLOT = 8192;

constexpr unsigned QK_FIRST = 0x1ce3;

enum { F_LN = 0, F_QKV = 1, F_EARLY = 2, F_LATE = 3, F_O = 4, F_CS = 5 };
constexpr unsigned CNT_LN = 8, CNT_QKV = 64, CNT_EARLY = 16, CNT_LATE = 16, CNT_O = 48, CNT_CS = 16;

__device__ __align__(1024) __nv_bfloat16 g_xn[SEQ * DM];
__device__ __align__(1024) __nv_bfloat16 g_qkv[SEQ * NQKV];
__device__ __align__(1024) __nv_bfloat16 g_a2[SEQ * K2];
__device__ __align__(128) float2 g_stats[SEQ];
__device__ __align__(128) float g_colsum[16 * DM];
__device__ __align__(128) unsigned g_flags[6 * 16 * 32];
__device__ __align__(128) unsigned g_epoch[NCTA * 16];

#define TRACE_T 1
#define TRACE(slot) do {} while (0)
#define TRACE_GT(slot) do {} while (0)

__device__ __forceinline__ uint32_t smem_u32(const void* p) { return (uint32_t)__cvta_generic_to_shared(p); }
__device__ __forceinline__ void mbar_init(uint32_t bar, uint32_t cnt) {
    asm volatile("mbarrier.init.shared::cta.b64 [%0], %1;" :: "r"(bar), "r"(cnt) : "memory");
}
__device__ __forceinline__ void mbar_expect_tx(uint32_t bar, uint32_t bytes) {
    asm volatile("mbarrier.arrive.expect_tx.shared::cta.b64 _, [%0], %1;" :: "r"(bar), "r"(bytes) : "memory");
}
__device__ __forceinline__ void mbar_arrive(uint32_t bar) {
    asm volatile("mbarrier.arrive.shared::cta.b64 _, [%0];" :: "r"(bar) : "memory");
}
__device__ __forceinline__ void mbar_arrive_cluster(uint32_t bar, uint32_t cta) {
    asm volatile("{\n.reg .b32 ra;\nmapa.shared::cluster.u32 ra, %0, %1;\nmbarrier.arrive.shared::cluster.b64 _, [ra];\n}"
                 :: "r"(bar), "r"(cta) : "memory");
}
__device__ __forceinline__ bool mbar_try_wait(uint32_t bar, uint32_t parity) {
    uint32_t ok;
    asm volatile("{\n.reg .pred p;\nmbarrier.try_wait.parity.shared::cta.b64 p, [%1], %2;\nselp.u32 %0, 1, 0, p;\n}"
                 : "=r"(ok) : "r"(bar), "r"(parity) : "memory");
    return ok;
}
__device__ __forceinline__ void mbar_wait(uint32_t bar, uint32_t parity) {
    int spins = 0;
    while (!mbar_try_wait(bar, parity)) { if (++spins > (1 << 17)) break; }
}
__device__ __forceinline__ void flag_wait(const unsigned* p, unsigned target) {
    for (int spins = 0; spins < (1 << 19); spins++) {
        unsigned v;
        asm volatile("ld.acquire.gpu.global.u32 %0, [%1];" : "=r"(v) : "l"(p) : "memory");
        if ((int)(v - target) >= 0) break;
        __nanosleep(64);
    }
}
__device__ __forceinline__ void flag_add(unsigned* p) {
    asm volatile("red.release.gpu.global.add.u32 [%0], 1;" :: "l"(p) : "memory");
}
__device__ __forceinline__ bool elect_one() {
    uint32_t ok;
    asm volatile("{\n.reg .pred p;\nelect.sync _|p, 0xffffffff;\nselp.u32 %0, 1, 0, p;\n}" : "=r"(ok));
    return ok;
}
__device__ __forceinline__ void fence_proxy_async() { asm volatile("fence.proxy.async;" ::: "memory"); }
__device__ __forceinline__ uint4 lds128(uint32_t addr) {
    uint4 v;
    asm volatile("ld.shared.v4.u32 {%0,%1,%2,%3}, [%4];" : "=r"(v.x), "=r"(v.y), "=r"(v.z), "=r"(v.w) : "r"(addr) : "memory");
    return v;
}
__device__ __forceinline__ float2 lds64f(uint32_t addr) {
    float2 v;
    asm volatile("ld.shared.v2.f32 {%0,%1}, [%2];" : "=f"(v.x), "=f"(v.y) : "r"(addr) : "memory");
    return v;
}
__device__ __forceinline__ void sts128(uint32_t addr, uint4 v) {
    asm volatile("st.shared.v4.u32 [%0], {%1,%2,%3,%4};" :: "r"(addr), "r"(v.x), "r"(v.y), "r"(v.z), "r"(v.w) : "memory");
}
__device__ __forceinline__ void sts64f(uint32_t addr, float a, float b) {
    asm volatile("st.shared.v2.f32 [%0], {%1,%2};" :: "r"(addr), "f"(a), "f"(b) : "memory");
}

__device__ __forceinline__ uint64_t policy(bool stream) {
    uint64_t p;
    if (stream) asm("createpolicy.fractional.L2::evict_first.b64 %0, 1.0;" : "=l"(p));
    else asm("createpolicy.fractional.L2::evict_normal.b64 %0, 1.0;" : "=l"(p));
    return p;
}
__device__ __forceinline__ void tma_2d(uint32_t dst, const CUtensorMap* m, uint32_t bar, int c0, int c1, uint64_t pol) {
    asm volatile("cp.async.bulk.tensor.2d.shared::cluster.global.mbarrier::complete_tx::bytes.L2::cache_hint"
                 " [%0], [%1, {%3, %4}], [%2], %5;"
                 :: "r"(dst), "l"(m), "r"(bar), "r"(c0), "r"(c1), "l"(pol) : "memory");
}
__device__ __forceinline__ void tma_3d(uint32_t dst, const CUtensorMap* m, uint32_t bar, int c0, int c1, int c2, uint64_t pol) {
    asm volatile("cp.async.bulk.tensor.3d.shared::cluster.global.mbarrier::complete_tx::bytes.L2::cache_hint"
                 " [%0], [%1, {%3, %4, %5}], [%2], %6;"
                 :: "r"(dst), "l"(m), "r"(bar), "r"(c0), "r"(c1), "r"(c2), "l"(pol) : "memory");
}
__device__ __forceinline__ void tma_3d_mc(uint32_t dst, const CUtensorMap* m, uint32_t bar, int c1, int c2, uint64_t pol) {
    asm volatile("cp.async.bulk.tensor.3d.shared::cluster.global.mbarrier::complete_tx::bytes.multicast::cluster.L2::cache_hint"
                 " [%0], [%1, {%3, %4, %5}], [%2], %6, %7;"
                 :: "r"(dst), "l"(m), "r"(bar), "r"(0), "r"(c1), "r"(c2), "h"((uint16_t)3), "l"(pol) : "memory");
}
__device__ __forceinline__ void tma_5d_mc(uint32_t dst, const CUtensorMap* m, uint32_t bar, int c0, int c4, uint64_t pol) {
    asm volatile("cp.async.bulk.tensor.5d.shared::cluster.global.mbarrier::complete_tx::bytes.multicast::cluster.L2::cache_hint"
                 " [%0], [%1, {%3, %4, %4, %4, %5}], [%2], %6, %7;"
                 :: "r"(dst), "l"(m), "r"(bar), "r"(c0), "r"(0), "r"(c4), "h"((uint16_t)3), "l"(pol) : "memory");
}
__device__ __forceinline__ void tma_store_2d(const CUtensorMap* m, uint32_t src, int c0, int c1) {
    asm volatile("cp.async.bulk.tensor.2d.global.shared::cta.bulk_group [%0, {%2, %3}], [%1];"
                 :: "l"(m), "r"(src), "r"(c0), "r"(c1) : "memory");
}
__device__ __forceinline__ void bulk_load(uint32_t dst, const void* src, uint32_t bytes, uint32_t bar) {
    asm volatile("cp.async.bulk.shared::cluster.global.mbarrier::complete_tx::bytes [%0], [%1], %2, [%3];"
                 :: "r"(dst), "l"(src), "r"(bytes), "r"(bar) : "memory");
}
__device__ __forceinline__ void bulk_store(void* dst, uint32_t src, uint32_t bytes) {
    asm volatile("cp.async.bulk.global.shared::cta.bulk_group [%0], [%1], %2;" :: "l"(dst), "r"(src), "r"(bytes) : "memory");
}
__device__ __forceinline__ void prefetch_3d(const CUtensorMap* m, int c1, int c2, uint64_t pol) {
    asm volatile("cp.async.bulk.prefetch.tensor.3d.L2.global.L2::cache_hint [%0, {%1, %2, %3}], %4;"
                 :: "l"(m), "r"(0), "r"(c1), "r"(c2), "l"(pol) : "memory");
}
__device__ __forceinline__ void prefetch_map(const CUtensorMap* m) {
    asm volatile("prefetch.tensormap [%0];" :: "l"(m) : "memory");
}
__device__ __forceinline__ void wg_fence() { asm volatile("wgmma.fence.sync.aligned;" ::: "memory"); }
__device__ __forceinline__ void wg_commit() { asm volatile("wgmma.commit_group.sync.aligned;" ::: "memory"); }
template <int N> __device__ __forceinline__ void wg_wait() { asm volatile("wgmma.wait_group.sync.aligned %0;" :: "n"(N) : "memory"); }

__device__ __forceinline__ uint64_t desc_a(uint32_t addr) {
    return (uint64_t)((addr & 0x3FFFF) >> 4) | (1ull << 16) | (64ull << 32) | (1ull << 62);
}
__device__ __forceinline__ uint64_t desc_b(uint32_t addr) {
    return (uint64_t)((addr & 0x3FFFF) >> 4) | (512ull << 16) | (64ull << 32) | (1ull << 62);
}

#define R8(d, o) "+f"(d[o]), "+f"(d[o+1]), "+f"(d[o+2]), "+f"(d[o+3]), "+f"(d[o+4]), "+f"(d[o+5]), "+f"(d[o+6]), "+f"(d[o+7])
#define R32(d, o) R8(d, o), R8(d, o+8), R8(d, o+16), R8(d, o+24)
#define R64(d, o) R32(d, o), R32(d, o+32)

__device__ __forceinline__ void wgmma_n256(float (&d)[128], uint64_t da, uint64_t db, int scale_d) {
    asm volatile("{\n.reg .pred p;\nsetp.ne.b32 p, %130, 0;\n"
        "wgmma.mma_async.sync.aligned.m64n256k16.f32.bf16.bf16 "
        "{%0,%1,%2,%3,%4,%5,%6,%7,%8,%9,%10,%11,%12,%13,%14,%15,%16,%17,%18,%19,%20,%21,%22,%23,%24,%25,%26,%27,%28,%29,%30,%31,"
        "%32,%33,%34,%35,%36,%37,%38,%39,%40,%41,%42,%43,%44,%45,%46,%47,%48,%49,%50,%51,%52,%53,%54,%55,%56,%57,%58,%59,%60,%61,%62,%63,"
        "%64,%65,%66,%67,%68,%69,%70,%71,%72,%73,%74,%75,%76,%77,%78,%79,%80,%81,%82,%83,%84,%85,%86,%87,%88,%89,%90,%91,%92,%93,%94,%95,"
        "%96,%97,%98,%99,%100,%101,%102,%103,%104,%105,%106,%107,%108,%109,%110,%111,%112,%113,%114,%115,%116,%117,%118,%119,%120,%121,%122,%123,%124,%125,%126,%127},"
        " %128, %129, p, 1, 1, 0, 1;\n}"
        : R64(d, 0), R64(d, 64) : "l"(da), "l"(db), "r"(scale_d));
}
__device__ __forceinline__ void wgmma_n128(float (&d)[64], uint64_t da, uint64_t db, int scale_d) {
    asm volatile("{\n.reg .pred p;\nsetp.ne.b32 p, %66, 0;\n"
        "wgmma.mma_async.sync.aligned.m64n128k16.f32.bf16.bf16 "
        "{%0,%1,%2,%3,%4,%5,%6,%7,%8,%9,%10,%11,%12,%13,%14,%15,%16,%17,%18,%19,%20,%21,%22,%23,%24,%25,%26,%27,%28,%29,%30,%31,"
        "%32,%33,%34,%35,%36,%37,%38,%39,%40,%41,%42,%43,%44,%45,%46,%47,%48,%49,%50,%51,%52,%53,%54,%55,%56,%57,%58,%59,%60,%61,%62,%63},"
        " %64, %65, p, 1, 1, 0, 1;\n}"
        : R64(d, 0) : "l"(da), "l"(db), "r"(scale_d));
}

__device__ __forceinline__ uint32_t pack_bf16(float lo, float hi) {
    uint32_t r; asm("cvt.rn.bf16x2.f32 %0, %1, %2;" : "=r"(r) : "f"(hi), "f"(lo)); return r;
}
__device__ __forceinline__ float bf_lo(uint32_t v) { return __uint_as_float(v << 16); }
__device__ __forceinline__ float bf_hi(uint32_t v) { return __uint_as_float(v & 0xffff0000u); }
__device__ __forceinline__ float round_bf16(float v) { return bf_lo(pack_bf16(v, 0.f)); }
__device__ __forceinline__ uint32_t mul_bf16x2(uint32_t a, uint32_t b) {
    uint32_t r; asm("mul.rn.bf16x2 %0, %1, %2;" : "=r"(r) : "r"(a), "r"(b)); return r;
}
__device__ __forceinline__ uint32_t add_bf16x2(uint32_t a, uint32_t b) {
    uint32_t r; asm("add.rn.bf16x2 %0, %1, %2;" : "=r"(r) : "r"(a), "r"(b)); return r;
}
__device__ __forceinline__ uint32_t sub_bf16x2(uint32_t a, uint32_t b) {
    uint32_t r; asm("sub.rn.bf16x2 %0, %1, %2;" : "=r"(r) : "r"(a), "r"(b)); return r;
}
__device__ __forceinline__ float tanh_fast(float x) { float r; asm("tanh.approx.f32 %0, %1;" : "=f"(r) : "f"(x)); return r; }
__device__ __forceinline__ float gelu_tanh(float g) {
    float t = fmaf(g * g, 0.044715f * 0.7978845608f, 0.7978845608f) * g;
    float hg = 0.5f * g;
    return fmaf(hg, tanh_fast(t), hg);
}
__device__ __forceinline__ uint32_t geglu2(uint32_t g2, uint32_t u2) {
    return mul_bf16x2(pack_bf16(gelu_tanh(bf_lo(g2)), gelu_tanh(bf_hi(g2))), u2);
}
__device__ __forceinline__ float silu(float d) {
    float hd = 0.5f * d;
    return fmaf(hd, tanh_fast(hd), hd);
}
__device__ __forceinline__ float ex2_fast(float x) { float r; asm("ex2.approx.ftz.f32 %0, %1;" : "=f"(r) : "f"(x)); return r; }
__device__ __forceinline__ void unpack8(uint4 v, float (&f)[8]) {
    f[0] = bf_lo(v.x); f[1] = bf_hi(v.x); f[2] = bf_lo(v.y); f[3] = bf_hi(v.y);
    f[4] = bf_lo(v.z); f[5] = bf_hi(v.z); f[6] = bf_lo(v.w); f[7] = bf_hi(v.w);
}
template <int N> __device__ __forceinline__ void fence_regs(float (&d)[N]) {
#pragma unroll
    for (int i = 0; i < N; i++) asm volatile("" : "+f"(d[i]) :: "memory");
}

__device__ __forceinline__ float rcp_fast(float x) { float r; asm("rcp.approx.ftz.f32 %0, %1;" : "=f"(r) : "f"(x)); return r; }
__device__ __forceinline__ uint32_t max_bf16x2(uint32_t a, uint32_t b) {
    uint32_t r; asm("max.bf16x2 %0, %1, %2;" : "=r"(r) : "r"(a), "r"(b)); return r;
}
__device__ __forceinline__ uint4 ldsm4(uint32_t addr) {
    uint4 v;
    asm volatile("ldmatrix.sync.aligned.m8n8.x4.shared.b16 {%0,%1,%2,%3}, [%4];"
                 : "=r"(v.x), "=r"(v.y), "=r"(v.z), "=r"(v.w) : "r"(addr) : "memory");
    return v;
}
__device__ __forceinline__ uint4 ldsm4_t(uint32_t addr) {
    uint4 v;
    asm volatile("ldmatrix.sync.aligned.m8n8.x4.trans.shared.b16 {%0,%1,%2,%3}, [%4];"
                 : "=r"(v.x), "=r"(v.y), "=r"(v.z), "=r"(v.w) : "r"(addr) : "memory");
    return v;
}
__device__ __forceinline__ void mma_16816(float (&c)[4], uint32_t a0, uint32_t a1, uint32_t a2, uint32_t a3, uint32_t b0, uint32_t b1) {
    asm("mma.sync.aligned.m16n8k16.row.col.f32.bf16.bf16.f32 {%0,%1,%2,%3}, {%4,%5,%6,%7}, {%8,%9}, {%0,%1,%2,%3};"
        : "+f"(c[0]), "+f"(c[1]), "+f"(c[2]), "+f"(c[3]) : "r"(a0), "r"(a1), "r"(a2), "r"(a3), "r"(b0), "r"(b1));
}
__device__ __forceinline__ void mma_1688(float (&c)[4], uint32_t a0, uint32_t a1, uint32_t b0) {
    asm("mma.sync.aligned.m16n8k8.row.col.f32.bf16.bf16.f32 {%0,%1,%2,%3}, {%4,%5}, {%6}, {%0,%1,%2,%3};"
        : "+f"(c[0]), "+f"(c[1]), "+f"(c[2]), "+f"(c[3]) : "r"(a0), "r"(a1), "r"(b0));
}
__device__ __forceinline__ void qk_tile(float (&c)[4], const uint4& q0, const uint4& q1, const uint4& k, float init) {
    c[0] = c[1] = c[2] = c[3] = init;
    mma_16816(c, q0.x, q0.y, q0.z, q0.w, k.x, k.y);
    mma_16816(c, q1.x, q1.y, q1.z, q1.w, k.z, k.w);
}
__device__ __forceinline__ uint32_t scaled_logits(bool first, float a0, float a1, float b0, float b1) {
    uint32_t p, r;
    asm("{\n.reg .pred p;\nsetp.ne.u32 p, %1, 0;\n@p cvt.rn.bf16x2.f32 %0, %3, %2;\n@!p cvt.rn.bf16x2.f32 %0, %5, %4;\n}"
        : "=r"(p) : "r"((uint32_t)first), "f"(a0), "f"(a1), "f"(b0), "f"(b1));
    asm("fma.rn.bf16x2 %0, %1, %2, %3;" : "=r"(r) : "r"(p), "r"(0x3e353e35u), "r"(mul_bf16x2(p, 0x379e379eu)));
    return r;
}
template <typename T> __device__ __forceinline__ T uniform(T v) { return __shfl_sync(0xffffffffu, v, 0); }

__device__ __forceinline__ void attention(const CUtensorMap* maps, uint32_t base, uint32_t zero, int grp, int warp, int lane) {
    constexpr float LOG2E = 1.4426950408889634f;
    const int g = lane >> 2, t = lane & 3;
    const bool up0 = 2 * t > g, up1 = 2 * t + 1 > g;
    const uint32_t keep = (up0 ? 0x0000ffffu : 0u) | (up1 ? 0xffff0000u : 0u);
    const uint32_t buf = base + warp * 2 * ATT_SLOT, bar = base + AUX_OFF + warp * 16;
    const uint32_t qoff = (lane & 15) * 128 + (((lane >> 4) ^ (lane & 7)) << 4);
    const uint32_t koff = 2048 + (lane & 7) * 128 + (((lane >> 3) ^ (lane & 7)) << 4);
    const int col = uniform((grp * 4 + warp / 3) * 64), first = uniform(warp % 3 * 43 * 16), last = min(first + 43 * 16, SEQ);
    const CUtensorMap* const mqk = reinterpret_cast<const CUtensorMap*>(uniform(reinterpret_cast<uint64_t>(maps)));
    const CUtensorMap *const mv = mqk + 1, *const mo = mqk + 2;
    const uint64_t pol = policy(P_QKV);
    uint4 kp[2], vp[2];
    uint32_t l0[2], l1[2], m[2];
    float s[2][3][4];
    auto scores = [&](uint32_t st, int row) {
        const float before = (row & 1023) == 0 ? -5.656854e9f : 0.f;
#pragma unroll
        for (int h = 0; h < 2; h++) {
            const uint4 q0 = ldsm4(st + (qoff ^ (h * 64))), q1 = ldsm4(st + (qoff ^ (h * 64 + 32)));
            const uint4 k0 = ldsm4(st + (koff ^ (h * 64))), k1 = ldsm4(st + 1024 + (koff ^ (h * 64)));
            qk_tile(s[h][0], q0, q1, kp[h], before);
            qk_tile(s[h][1], q0, q1, k0, 0.f);
            qk_tile(s[h][2], q0, q1, k1, 0.f);
            kp[h] = k1;
        }
    };
    auto logits = [&]() {
#pragma unroll
        for (int h = 0; h < 2; h++) {
            l0[h] = scaled_logits(up0, s[h][0][0], s[h][1][2], s[h][1][0], s[h][2][2]);
            l1[h] = scaled_logits(up1, s[h][0][1], s[h][1][3], s[h][1][1], s[h][2][3]);
            m[h] = max_bf16x2(l0[h], l1[h]);
            m[h] = max_bf16x2(m[h], __shfl_xor_sync(0xffffffffu, m[h], 1));
        }
    };
    auto row_max = [&]() {
#pragma unroll
        for (int h = 0; h < 2; h++) m[h] = max_bf16x2(m[h], __shfl_xor_sync(0xffffffffu, m[h], 2));
    };
    auto exchange = [&](uint32_t st, uint32_t b, int row, int store, int load) {
        asm volatile("{\n.reg .pred e, p, q;\n"
            "fence.proxy.async.shared::cta;\n"
            "bar.warp.sync 0xffffffff;\n"
            "elect.sync _|e, 0xffffffff;\n"
            "setp.ne.and.b32 p, %10, 0, e;\n"
            "setp.ne.and.b32 q, %11, 0, e;\n"
            "@q mbarrier.arrive.expect_tx.shared::cta.b64 _, [%2], 6144;\n"
            "@q cp.async.bulk.tensor.3d.shared::cluster.global.mbarrier::complete_tx::bytes.L2::cache_hint [%0], [%3, {%6, %7, %12}], [%2], %14;\n"
            "@q cp.async.bulk.tensor.2d.shared::cluster.global.mbarrier::complete_tx::bytes.L2::cache_hint [%0 + 4096], [%4, {%13, %8}], [%2], %14;\n"
            "@e cp.async.bulk.wait_group.read 0;\n"
            "@p cp.async.bulk.tensor.2d.global.shared::cta.bulk_group [%5, {%6, %9}], [%1 + 6144];\n"
            "@e cp.async.bulk.commit_group;\n"
            "bar.warp.sync 0xffffffff;\n}"
            :: "r"(st), "r"(st ^ ATT_SLOT), "r"(b), "l"(mqk), "l"(mv), "l"(mo), "r"(col), "r"(row + 48), "r"(row + 32),
               "r"(row - 16), "r"(store), "r"(load), "r"(0), "r"(col + 2 * DM), "l"(pol) : "memory");
    };
    const unsigned epoch = __ldcg(g_epoch + blockIdx.x * 16 + warp) + 1;
    __syncwarp();
    if (elect_one()) {
        mbar_init(bar, 1); mbar_init(bar + 8, 1);
        prefetch_map(mqk); prefetch_map(mv); prefetch_map(mo);
        flag_wait(g_flags + F_QKV * 512, epoch * CNT_QKV);
        fence_proxy_async();
        mbar_expect_tx(bar + 8, 8192);
        tma_3d(buf + ATT_SLOT, mqk, bar + 8, col, first, 0, pol);
        tma_2d(buf + ATT_SLOT + 4096, mv, bar + 8, col + 2 * DM, first - 16, policy(false));
        tma_2d(buf + ATT_SLOT + 6144, mv, bar + 8, col + DM, first - 16, policy(false));
        mbar_expect_tx(bar, 6144);
        tma_3d(buf, mqk, bar, col, first + 16, 0, pol);
        tma_2d(buf + 4096, mv, bar, col + 2 * DM, first, pol);
        g_epoch[blockIdx.x * 16 + warp] = epoch;
        if (warp == 0) TRACE(9);
    }
    __syncwarp();
    mbar_wait(bar + 8, 0);
#pragma unroll
    for (int h = 0; h < 2; h++) {
        kp[h] = ldsm4(buf + ATT_SLOT + 5120 + (koff ^ (h * 64)));
        vp[h] = ldsm4_t(buf + ATT_SLOT + 3072 + (koff ^ (h * 64)));
    }
    scores(buf + ATT_SLOT, first);
    exchange(buf + ATT_SLOT, bar + 8, first - 16, 0, 1);
    logits();
    row_max();
    uint32_t st = buf, b = bar, cnt = 1;
    bool ready = mbar_try_wait(b, 0);
#pragma unroll 1
    for (int row = first; row < last; row += 16) {
        uint32_t pa[2], pb[2];
        if (!ready) mbar_wait(b, (cnt >> 1) & 1);
        uint4 v[2][2];
#pragma unroll
        for (int h = 0; h < 2; h++) {
            const float ma = -LOG2E * bf_lo(m[h]), mb = -LOG2E * bf_hi(m[h]);
            const float a0 = ex2_fast(fmaf(bf_lo(l0[h]), LOG2E, ma)), a1 = ex2_fast(fmaf(bf_lo(l1[h]), LOG2E, ma));
            const float b0 = ex2_fast(fmaf(bf_hi(l0[h]), LOG2E, mb)), b1 = ex2_fast(fmaf(bf_hi(l1[h]), LOG2E, mb));
            float sum[4] = {0.f, 0.f, 0.f, 0.f};
            mma_1688(sum, pack_bf16(a0, a1), pack_bf16(b0, b1), 0x3f803f80u);
            const float ra = rcp_fast(sum[0]), rb = rcp_fast(sum[2]);
            pa[h] = pack_bf16(a0 * ra, a1 * ra);
            pb[h] = pack_bf16(b0 * rb, b1 * rb);
        }
        scores(st, row + 16);
#pragma unroll
        for (int h = 0; h < 2; h++) {
            v[h][0] = ldsm4_t(st + 4096 + (qoff ^ (h * 64)));
            v[h][1] = ldsm4_t(st + 4096 + (qoff ^ (h * 64 + 32)));
        }
        if (row == first + 80) {
            flag_wait(g_flags + F_QKV * 512 + 32, epoch * CNT_QKV);
            fence_proxy_async();
        }
        exchange(st, b, row, row > first, row + 32 < last);
        logits();
        float o[2][4][4];
#pragma unroll
        for (int h = 0; h < 2; h++) {
            const uint32_t prev[4] = {vp[h].x, vp[h].y, vp[h].z, vp[h].w};
            const uint32_t own[8] = {v[h][0].x, v[h][0].y, v[h][0].z, v[h][0].w, v[h][1].x, v[h][1].y, v[h][1].z, v[h][1].w};
            const uint32_t a0 = pa[h] & keep, a1 = pa[h] & ~keep, a2 = pb[h] & keep, a3 = pb[h] & ~keep;
            const uint32_t z0 = pa[h] & zero, z1 = pb[h] & zero;
#pragma unroll
            for (int j = 0; j < 4; j++) {
                o[h][j][0] = o[h][j][1] = o[h][j][2] = o[h][j][3] = 0.f;
                mma_1688(o[h][j], a0, z0, prev[j]);
                mma_16816(o[h][j], a1, a2, z1, a3, own[2 * j], own[2 * j + 1]);
            }
            vp[h] = make_uint4(own[1], own[3], own[5], own[7]);
        }
        row_max();
        b ^= 8; cnt++;
        ready = mbar_try_wait(b, (cnt >> 1) & 1);
#pragma unroll
        for (int h = 0; h < 2; h++) {
#pragma unroll
            for (int d = 0; d < 2; d++)
                asm volatile("stmatrix.sync.aligned.m8n8.x4.shared.b16 [%0], {%1,%2,%3,%4};"
                             :: "r"(st + 6144 + (qoff ^ (h * 64 + d * 32))),
                                "r"(pack_bf16(o[h][2 * d][0], o[h][2 * d][1])), "r"(pack_bf16(o[h][2 * d][2], o[h][2 * d][3])),
                                "r"(pack_bf16(o[h][2 * d + 1][0], o[h][2 * d + 1][1])),
                                "r"(pack_bf16(o[h][2 * d + 1][2], o[h][2 * d + 1][3])) : "memory");
        }
        st ^= ATT_SLOT;
    }
    exchange(st, b, last, 1, 0);
    if (elect_one()) {
        asm volatile("cp.async.bulk.wait_group 0;" ::: "memory");
        fence_proxy_async();
        flag_add(g_flags + F_O * 512);
        if (warp == 0) TRACE(10);
    }
}

__device__ __forceinline__ void warp_sum2(float& a, float& b) {
#pragma unroll
    for (int o = 16; o > 0; o >>= 1) {
        a += __shfl_xor_sync(0xffffffffu, a, o);
        b += __shfl_xor_sync(0xffffffffu, b, o);
    }
}
__device__ __forceinline__ float row_sum(const uint32_t* w) {
    float a = 0.f, b = 0.f;
#pragma unroll
    for (int i = 0; i < 16; i++) { a += bf_lo(w[i]); b += bf_hi(w[i]); }
    return a + b;
}
__device__ __forceinline__ float row_sq(const uint32_t* w, float mean) {
    float a = 0.f, b = 0.f;
#pragma unroll
    for (int i = 0; i < 16; i++) {
        const float lo = bf_lo(w[i]) - mean, hi = bf_hi(w[i]) - mean;
        a = fmaf(lo, lo, a); b = fmaf(hi, hi, b);
    }
    return a + b;
}
__device__ __forceinline__ float row_inv(float sq) {
    return 1.f / round_bf16(sqrtf(round_bf16(round_bf16(sq * (1.f / DM)) + 1e-5f)));
}
__device__ __forceinline__ void row_store(const uint32_t* w, float mean, float inv, uint32_t dst) {
    const uint32_t m2 = pack_bf16(mean, mean);
#pragma unroll
    for (int i = 0; i < 4; i++) {
        uint32_t o[4];
#pragma unroll
        for (int j = 0; j < 4; j++) {
            const uint32_t c = sub_bf16x2(w[i * 4 + j], m2);
            o[j] = pack_bf16(bf_lo(c) * inv, bf_hi(c) * inv);
        }
        sts128(dst + i * 512, make_uint4(o[0], o[1], o[2], o[3]));
    }
}

struct Params {
    CUtensorMap x, xn, wv, wqk, wg, wu, wg1, wu1, qk, v, o, a2, wo, wd, out;
    const __nv_bfloat16* px;
    uint32_t zero;
};

__global__ void __cluster_dims__(2, 1, 1) __launch_bounds__(384, 1)
fused_kernel(const __grid_constant__ Params prm) {
    extern __shared__ __align__(1024) uint8_t smem_raw[];
    const uint32_t base = smem_u32(smem_raw);
    const uint32_t bars = base + BAR_OFF;
    auto full0 = [&](int s) { return bars + s * 8; };
    auto empty0 = [&](int s) { return bars + 48 + s * 8; };
    auto full1 = [&](int s) { return bars + 96 + s * 8; };
    auto empty1 = [&](int s) { return bars + 128 + s * 8; };
    auto full2 = [&](int s) { return bars + 160 + s * 8; };
    auto empty2 = [&](int s) { return bars + 208 + s * 8; };
    const uint32_t sig_bar = bars + 256, fold_bar = bars + 264, x_bar = bars + 272, cs_bar = bars + 280, ln_bar = bars + 288;
    const uint32_t dep_bar = bars + 296, colsum = bars + 512, stats = bars + 1024, own_stats = bars + 2048, last_epoch = bars + 2176;
    auto wide = [&](int s) { return base + s * W_STAGE_BYTES; };
    auto narrow = [&](int q) { return base + q * N_STAGE_BYTES; };
    const uint32_t aux = base + AUX_OFF;

    const int warp = __shfl_sync(0xffffffffu, threadIdx.x >> 5, 0);
    const int lane = threadIdx.x & 31;
    const int rank = blockIdx.x & 1;
    const int mblk = ((blockIdx.x >> 1) & 7) * 2 + rank;
    const int nslot = blockIdx.x >> 4;
    const int lrow = mblk * 128 + nslot * 16;

    if (blockIdx.x >= NGEMM) {
        if (threadIdx.x == 0) { TRACE_GT(0); TRACE(1); }
        attention(&prm.qk, (base + 2 * ATT_SLOT - 1) & ~(2u * ATT_SLOT - 1), prm.zero, blockIdx.x - NGEMM, warp, lane);
    } else if (warp >= 8) {
        unsigned* const flags = g_flags + mblk * 32;
        if (elect_one()) {
            if (warp == 8) {
                TRACE_GT(0); TRACE(1);
                prefetch_map(&prm.x); prefetch_map(&prm.wv);
                for (int s = 0; s < N_STAGES; s++) mbar_init(full0(s), 1);
                mbar_init(ln_bar, 1);
            } else if (warp == 9) {
                for (int s = 0; s < N_STAGES; s++) { mbar_init(empty0(s), 4); mbar_init(empty2(s), 4); }
            } else if (warp == 10) {
                for (int s = 0; s < W_STAGES; s++) { mbar_init(full1(s), 1); mbar_init(empty1(s), 4); mbar_init(dep_bar + s * 8, 1); }
            } else {
                for (int s = 0; s < N_STAGES; s++) mbar_init(full2(s), 1);
                mbar_init(sig_bar, 8); mbar_init(fold_bar, 2); mbar_init(x_bar, 1); mbar_init(cs_bar, 1);
                prefetch_map(&prm.wqk);
            }
            asm volatile("fence.mbarrier_init.release.cluster;" ::: "memory");
        }
        __syncwarp();
        asm volatile("barrier.cluster.arrive.relaxed.aligned;" ::: "memory");
        if (warp == 8 && lane == 0) {
            mbar_expect_tx(ln_bar, 32768 + 16);
            bulk_load(aux, prm.px + (size_t)lrow * DM, 32768, ln_bar);
            bulk_load(last_epoch, g_epoch + blockIdx.x * 16, 16, ln_bar);
            for (int j = 0; j < N_STAGES; j++) {
                const int q = (j + 2) % N_STAGES;
                mbar_expect_tx(full0(q), N_STAGE_BYTES);
                if (j < 2) prefetch_3d(&prm.wv, j * 64, 32 + nslot * 2 + rank, policy(P_W1));
                tma_2d(narrow(q), &prm.x, full0(q), j * 64, mblk * 128, policy(P_X));
            }
            TRACE(15);
        }
        asm volatile("setmaxnreg.dec.sync.aligned.u32 %0;" :: "n"(AUX_REGS));
        asm volatile("barrier.cluster.wait.acquire.aligned;" ::: "memory");

        if (warp == 8) {
            if (lane == 0) {
                TRACE(2);
                for (int j = 0; j < KSTEPS; j++) {
                    const int q = (j + 2) % N_STAGES;
                    if (j >= N_STAGES) {
                        mbar_wait(empty0(q), j >= 2 * N_STAGES);
                        mbar_expect_tx(full0(q), N_STAGE_BYTES);
                        tma_2d(narrow(q), &prm.x, full0(q), j * 64, mblk * 128, policy(P_X));
                    }
                    tma_3d_mc(narrow(q) + A_BYTES + rank * 8192, &prm.wv, full0(q), j * 64, 32 + nslot * 2 + rank, policy(P_W1));
                    if (j == N_STAGES - 1) {
                        prefetch_map(&prm.xn); prefetch_map(rank ? &prm.wu : &prm.wg);
                        prefetch_map(rank ? &prm.wu1 : &prm.wg1);
                        prefetch_map(&prm.a2); prefetch_map(&prm.wo); prefetch_map(&prm.wd); prefetch_map(&prm.out);
                    }
                }
                uint32_t ph = 1;
                for (int it = 0; it < W_TILES * KSTEPS; it++) {
                    const int s = it & 3, k = it & 15;
                    if (it < W_STAGES) {
                        if (!(it & 1)) mbar_wait(empty0(it + it / 2), it == 0);
                        mbar_wait(empty0(it + it / 2 + 1), it == 0);
                    } else {
                        mbar_wait(empty1(s), ph);
                    }
                    mbar_expect_tx(full1(s), W_STAGE_BYTES);
                    const uint32_t dst = wide(s) + A_BYTES + rank * 16384;
                    if (it < KSTEPS) tma_3d_mc(dst, &prm.wqk, full1(s), k * 64, nslot * 4 + rank * 2, policy(P_W1));
                    else tma_3d_mc(dst, rank ? &prm.wu : &prm.wg, full1(s), k * 64, ((it >> 4) * 8 - 8 + nslot) * 2, policy(P_W1));
                    if (it == 1) {
                        TRACE(14); mbar_wait(dep_bar, 0); TRACE(3);
                        tma_2d(wide(0), &prm.xn, full1(0), 0, mblk * 128, policy(false));
                    }
                    if (it != 0) tma_2d(wide(s), &prm.xn, full1(s), k * 64, mblk * 128, policy(false));
                    if (s == 3) ph ^= 1;
                }
                TRACE(4);
                int q = 0; uint32_t ph2 = 1;
                for (int u = 0; u < U_END; u++) {
                    if (u == U_D || u == U_LATE || u == U_S) {
                        TRACE(u == U_D ? 36 : (u == U_LATE ? 6 : 32));
                        mbar_wait(dep_bar + (u == U_D ? 8 : (u == U_LATE ? 16 : 24)), 0);
                        TRACE(u == U_D ? 5 : (u == U_LATE ? 7 : 33));
                    }
                    if (u < N_STAGES) {
                        if (u == 0) mbar_wait(empty1(0), ph);
                        if (u == 1) mbar_wait(empty1(1), ph);
                        if (u == 3) mbar_wait(empty1(2), ph);
                        if (u == 4) mbar_wait(empty1(3), ph);
                    } else {
                        mbar_wait(empty2(q), ph2);
                    }
                    const uint32_t sa = narrow(q), sb = sa + A_BYTES + rank * 8192;
                    mbar_expect_tx(full2(q), N_STAGE_BYTES);
                    if (u < U_D) {
                        tma_2d(sa, &prm.xn, full2(q), u * 64, mblk * 128, policy(P_XN4));
                        tma_3d_mc(sb, rank ? &prm.wu1 : &prm.wg1, full2(q), u * 64, 48 + nslot, policy(P_W1));
                    } else {
                        const bool down = u < U_S;
                        const int k = down ? u - U_D : u - U_S;
                        tma_3d(sa, &prm.a2, full2(q), (down ? DM : 0) + k * 64, 0, mblk * 64, policy(P_A2));
                        tma_5d_mc(sb, down ? &prm.wd : &prm.wo, full2(q), nslot * 128 + rank * 64, k * 2, policy(P_W2));
                    }
                    if (u == N_STAGES - 1) {
                        mbar_expect_tx(x_bar, 32768);
                        tma_2d(aux, &prm.x, x_bar, nslot * 128, mblk * 128, policy(P_X));
                        tma_2d(aux + 16384, &prm.x, x_bar, nslot * 128 + 64, mblk * 128, policy(P_X));
                    }
                    if (++q == N_STAGES) { q = 0; ph2 ^= 1; }
                }
                TRACE(8);
            }
        } else if (warp == 9) {
            if (lane == 0) {
                mbar_wait(sig_bar, 0);
                TRACE(11);
                bulk_store(g_xn + (size_t)lrow * DM, aux, 32768);
                bulk_store(g_stats + lrow, own_stats, 128);
                asm volatile("cp.async.bulk.commit_group;\ncp.async.bulk.wait_group.read 0;" ::: "memory");
                mbar_expect_tx(cs_bar, 16384);
                tma_3d(aux, &prm.wqk, cs_bar, 0, mblk * 64, 32 + nslot * 2, policy(P_W1));
                asm volatile("cp.async.bulk.wait_group 0;" ::: "memory");
                fence_proxy_async();
                flag_add(flags + F_LN * 512);
                TRACE(42);
                for (int t = 1; t < 6; t++) {
                    mbar_wait(sig_bar, t & 1);
                    if (t == 1) TRACE(37);
                    flag_add(t == 1 ? g_flags + F_QKV * 512 + (QK_FIRST >> mblk & 1 ? 0 : 32) : flags + (t < 4 ? F_EARLY : F_LATE) * 512);
                    if (t == 1) TRACE(43);
                }
            }
        } else if (warp == 10) {
            if (lane == 0) {
                mbar_wait(sig_bar, 0);
                const unsigned epoch = lds128(last_epoch).x + 1;
                flag_wait(flags + F_LN * 512, epoch * CNT_LN);
                fence_proxy_async(); mbar_arrive(dep_bar);
                mbar_expect_tx(fold_bar, 1024);
                bulk_load(stats, g_stats + mblk * 128, 1024, fold_bar);
                g_epoch[blockIdx.x * 16] = epoch;
                flag_wait(flags + F_EARLY * 512, epoch * CNT_EARLY);
                fence_proxy_async(); mbar_arrive(dep_bar + 8);
                flag_wait(flags + F_LATE * 512, epoch * CNT_LATE);
                fence_proxy_async(); mbar_arrive(dep_bar + 16);
                flag_wait(g_flags + F_O * 512, epoch * CNT_O);
                fence_proxy_async(); mbar_arrive(dep_bar + 24);
            }
        } else {
            float cs[8];
#pragma unroll
            for (int d = 0; d < 8; d++) cs[d] = 0.f;
            mbar_wait(cs_bar, 0);
            const uint32_t wa = aux + (lane & 8) * 1024 + (lane >> 4) * 128 + (((lane & 7) ^ (lane >> 4)) << 4);
#pragma unroll 1
            for (int i = 0; i < 8; i++) {
#pragma unroll
                for (int j = 0; j < 4; j++) {
                    float f[8];
                    unpack8(lds128((wa ^ (j * 32)) + i * 1024 + j * 256), f);
#pragma unroll
                    for (int d = 0; d < 8; d++) cs[d] += f[d];
                }
            }
#pragma unroll
            for (int d = 0; d < 8; d++) cs[d] += __shfl_xor_sync(0xffffffffu, cs[d], 16);
            *reinterpret_cast<float4*>(g_colsum + mblk * DM + nslot * 128 + (lane & 15) * 8 + (lane >> 4) * 4) =
                lane < 16 ? make_float4(cs[0], cs[1], cs[2], cs[3]) : make_float4(cs[4], cs[5], cs[6], cs[7]);
            __syncwarp();
            if (lane == 0) {
                TRACE(34);
                flag_add(g_flags + F_CS * 512 + nslot * 32);
                flag_wait(g_flags + F_CS * 512 + nslot * 32, (lds128(last_epoch).x + 1) * CNT_CS);
            }
            __syncwarp();
            const float4* gp = reinterpret_cast<const float4*>(g_colsum + nslot * 128) + lane;
            float4 c = make_float4(0.f, 0.f, 0.f, 0.f);
#pragma unroll 8
            for (int m = 0; m < 16; m++) {
                const float4 a = __ldcg(gp + m * (DM / 4));
                c.x += a.x; c.y += a.y; c.z += a.z; c.w += a.w;
            }
            const uint32_t ca = colsum + (lane >> 2) * 64 + (lane & 1) * 32 + (lane & 2) * 4;
            sts64f(ca, c.x, c.y);
            sts64f(ca + 16, c.z, c.w);
            __syncwarp();
            if (lane == 0) {
                mbar_arrive(fold_bar);
                TRACE(35);
            }
        }
    } else {
        asm volatile("barrier.cluster.arrive.relaxed.aligned;" ::: "memory");
        const int cw = threadIdx.x >> 5;
        const int tid = threadIdx.x & 127;
        asm volatile("setmaxnreg.inc.sync.aligned.u32 %0;" :: "n"(CONSUMER_REGS));
        const int wg = __shfl_sync(0xffffffffu, threadIdx.x >> 7, 0);
        asm volatile("barrier.cluster.wait.acquire.aligned;" ::: "memory");

        auto release = [&](uint32_t bar) { if (tid < 2) mbar_arrive_cluster(bar, tid); };
        auto signal_stores = [&]() { __syncwarp(); if (lane == 0) mbar_arrive(sig_bar); };
        auto mma_narrow = [&](float (&d)[64], int q, bool accumulate) {
            asm volatile("" : "+r"(q));
            const uint64_t da = desc_a(narrow(q) + wg * 8192), db = desc_b(narrow(q) + A_BYTES);
            wg_fence();
#pragma unroll
            for (int kk = 0; kk < 4; kk++) wgmma_n128(d, da + kk * 2, db + kk * 128, accumulate || kk != 0);
            wg_commit();
        };

        uint32_t pk[64];
        {
            const uint32_t xa = aux + cw * 4096 + lane * 16;
            uint32_t xw[32];
            mbar_wait(ln_bar, 0);
            if (threadIdx.x == 0) TRACE(38);
#pragma unroll
            for (int i = 0; i < 8; i++) {
                const uint4 v = lds128(xa + i * 512);
                xw[4 * i] = v.x; xw[4 * i + 1] = v.y; xw[4 * i + 2] = v.z; xw[4 * i + 3] = v.w;
            }
            float mean0 = row_sum(xw), mean1 = row_sum(xw + 16), inv0, inv1;
            warp_sum2(mean0, mean1);
            mean0 *= 1.f / DM; mean1 *= 1.f / DM;
            float accv[64];
#pragma unroll
            for (int i = 0; i < 64; i++) accv[i] = 0.f;
#pragma unroll
            for (int j = 0; j < 4; j++) {
                if (j == 0 && threadIdx.x == 0) TRACE(39);
                mbar_wait(full0(j + 2), 0);
                if (j == 0 && threadIdx.x == 0) TRACE(12);
                mma_narrow(accv, j + 2, j != 0);
                if (j == 0) {
                    inv0 = row_sq(xw, mean0); inv1 = row_sq(xw + 16, mean1);
                    warp_sum2(inv0, inv1);
                }
                if (j == 1) {
                    inv0 = row_inv(inv0); inv1 = row_inv(inv1);
                    row_store(xw, mean0, inv0, xa);
                }
                if (j == 2) {
                    row_store(xw + 16, mean1, inv1, xa + 2048);
                    if (lane == 0) sts128(own_stats + cw * 16, make_uint4(__float_as_uint(-round_bf16(mean0)), __float_as_uint(inv0),
                                                                          __float_as_uint(-round_bf16(mean1)), __float_as_uint(inv1)));
                    asm volatile("fence.proxy.async.shared::cta;" ::: "memory");
                    signal_stores();
                }
                wg_wait<1>();
                if (j > 0) release(empty0(j + 1));
            }
            int q = 0, qp = N_STAGES - 1;
#pragma unroll 1
            for (int j = 4; j < KSTEPS; j++) {
                mbar_wait(full0(q), j >= N_STAGES && j < 2 * N_STAGES);
                mma_narrow(accv, q, true);
                wg_wait<1>();
                release(empty0(qp));
                qp = q;
                if (++q == N_STAGES) q = 0;
            }
            wg_wait<0>();
            fence_regs(accv);
            release(empty0(N_STAGES - 1));
#pragma unroll
            for (int i = 0; i < 64; i++) pk[i] = __float_as_uint(accv[i]);
        }
        if (tid == 0) TRACE(16 + wg * 8);

        const int orow = ((lane >> 2) & 1) * (SEQ / 2) + mblk * 64 + cw * 8 + (lane >> 3);
        __nv_bfloat16* optr = g_qkv + (size_t)orow * NQKV + 2 * DM + nslot * 128 + (lane & 3) * 8;
        auto chunk_v = [&](int c) {
            const uint32_t sp = stats + (cw * 16 + (lane >> 2)) * 8;
            const float2 sa = lds64f(sp), sb = lds64f(sp + 64);
            uint32_t r[8];
#pragma unroll
            for (int j = 0; j < 2; j++) {
                const uint4 cs = lds128(colsum + (c * 2 + j) * 64 + (lane & 3) * 16);
                const float c0 = __uint_as_float(cs.x), c1 = __uint_as_float(cs.y);
                const float c2 = __uint_as_float(cs.z), c3 = __uint_as_float(cs.w);
                const uint32_t* a = pk + 16 * c + 8 * j;
                r[2 * j] = pack_bf16(fmaf(sa.x, c0, __uint_as_float(a[0])) * sa.y, fmaf(sa.x, c1, __uint_as_float(a[1])) * sa.y);
                r[4 + 2 * j] = pack_bf16(fmaf(sb.x, c0, __uint_as_float(a[2])) * sb.y, fmaf(sb.x, c1, __uint_as_float(a[3])) * sb.y);
                r[2 * j + 1] = pack_bf16(fmaf(sa.x, c2, __uint_as_float(a[4])) * sa.y, fmaf(sa.x, c3, __uint_as_float(a[5])) * sa.y);
                r[5 + 2 * j] = pack_bf16(fmaf(sb.x, c2, __uint_as_float(a[6])) * sb.y, fmaf(sb.x, c3, __uint_as_float(a[7])) * sb.y);
            }
            *reinterpret_cast<uint4*>(optr + c * 32) = make_uint4(r[0], r[1], r[2], r[3]);
            *reinterpret_cast<uint4*>(optr + 4 * NQKV + c * 32) = make_uint4(r[4], r[5], r[6], r[7]);
        };
        auto chunk_qk = [&](int c) {
            *reinterpret_cast<uint4*>(optr + c * 32) = make_uint4(pk[8 * c], pk[8 * c + 2], pk[8 * c + 4], pk[8 * c + 6]);
            *reinterpret_cast<uint4*>(optr + 4 * NQKV + c * 32) = make_uint4(pk[8 * c + 1], pk[8 * c + 3], pk[8 * c + 5], pk[8 * c + 7]);
        };
        auto chunk_geglu = [&](int j) {
            const int c = j >> 1, h = j & 1;
            uint4 v;
            v.x = geglu2(pk[8 * c + h], pk[32 + 8 * c + h]);
            v.y = geglu2(pk[8 * c + 2 + h], pk[32 + 8 * c + 2 + h]);
            v.z = geglu2(pk[8 * c + 4 + h], pk[32 + 8 * c + 4 + h]);
            v.w = geglu2(pk[8 * c + 6 + h], pk[32 + 8 * c + 6 + h]);
            *reinterpret_cast<uint4*>(optr + h * 4 * K2 + c * 32) = v;
        };

        {
            float acc[128];
#pragma unroll
            for (int i = 0; i < 128; i++) asm volatile("mov.b32 %0, 0;" : "=f"(acc[i]));
#pragma unroll 1
            for (int t = 0; t < W_TILES; t++) {
#pragma unroll
                for (int k = 0; k < KSTEPS; k++) {
                    const int s = k & 3;
                    mbar_wait(full1(s), (k >> 2) & 1);
                    if (t == TRACE_T && threadIdx.x == 0) TRACE(44 + k);
                    if (wg == 1 && k == KSTEPS - W_SKEW) asm volatile("bar.sync 1, 256;" ::: "memory");
                    const uint64_t da = desc_a(wide(s) + wg * 8192), db = desc_b(wide(s) + A_BYTES);
                    wg_fence();
#pragma unroll
                    for (int kk = 0; kk < 4; kk++) wgmma_n256(acc, da + kk * 2, db + kk * 128, (k | kk) != 0);
                    wg_commit();
                    if (wg == 0 && k == KSTEPS - 1) asm volatile("bar.arrive 1, 256;" ::: "memory");
                    if (k >= 9 && k <= 12 && t == 0) {
                        if (k == 9) mbar_wait(fold_bar, 0);
                        chunk_v(k - 9);
                    }
                    if (k < 8 && t == 1 && (QK_FIRST >> mblk & 1) != k >> 2) {
                        chunk_qk(2 * s); chunk_qk(2 * s + 1);
                        if (s == 3) signal_stores();
                    }
                    if (k >= 1 && k <= 8 && t >= 2) {
                        chunk_geglu(k - 1);
                        if (k == 8) signal_stores();
                    }
                    wg_wait<1>();
                    if (k > 0) release(empty1((k - 1) & 3));
                }
                wg_wait<0>();
                fence_regs(acc);
                release(empty1(3));
#pragma unroll
                for (int i = 0; i < 64; i++) pk[i] = pack_bf16(acc[2 * i], acc[2 * i + 1]);
                optr = t == 0 ? g_qkv + (size_t)orow * NQKV + nslot * 256 + (lane & 3) * 8
                              : g_a2 + (size_t)orow * K2 + DM + (t * 8 - 8 + nslot) * 128 + (lane & 3) * 8;
                if (tid == 0) TRACE(17 + wg * 8 + t);
            }
        }

        float acch[64], accd[64], accs[64];
#pragma unroll
        for (int i = 0; i < 64; i++) acch[i] = 0.f;
#pragma unroll
        for (int u = 0; u < U_D; u++) {
            mbar_wait(full2(u % N_STAGES), (u / N_STAGES) & 1);
            mma_narrow(acch, u % N_STAGES, u != 0);
            if (u & 1) { chunk_geglu(u >> 1); if (u == U_D - 1) signal_stores(); }
            wg_wait<1>();
            if (u > 0) release(empty2((u - 1) % N_STAGES));
        }
        if (tid == 0) TRACE(40 + wg);
        optr = g_a2 + (size_t)orow * K2 + DM + 3072 + nslot * 64 + (lane & 3) * 8;
#pragma unroll
        for (int i = 0; i < 64; i++) accd[i] = 0.f;
#pragma unroll
        for (int u = U_D; u < U_D + 8; u++) {
            mbar_wait(full2(u % N_STAGES), (u / N_STAGES) & 1);
            mma_narrow(accd, u % N_STAGES, u != U_D);
            if (u & 1) {
                const int c = (u - U_D) >> 2, h = (u - U_D) >> 1 & 1;
                const float* a = acch + 16 * c + 2 * h;
                uint4 v;
                v.x = geglu2(pack_bf16(a[0], a[1]), pack_bf16(a[32], a[33]));
                v.y = geglu2(pack_bf16(a[4], a[5]), pack_bf16(a[36], a[37]));
                v.z = geglu2(pack_bf16(a[8], a[9]), pack_bf16(a[40], a[41]));
                v.w = geglu2(pack_bf16(a[12], a[13]), pack_bf16(a[44], a[45]));
                *reinterpret_cast<uint4*>(optr + h * 4 * K2 + c * 32) = v;
                if (u == U_D + 7) signal_stores();
            }
            wg_wait<1>();
            if (u == U_D) fence_regs(acch);
            release(empty2((u - 1) % N_STAGES));
        }
        {
            int q = (U_D + 8) % N_STAGES, qp = (U_D + 7) % N_STAGES; uint32_t ph = ((U_D + 8) / N_STAGES) & 1;
#pragma unroll 1
            for (int u = U_D + 8; u < U_S; u++) {
                mbar_wait(full2(q), ph);
                mma_narrow(accd, q, true);
                wg_wait<1>();
                release(empty2(qp));
                qp = q;
                if (++q == N_STAGES) { q = 0; ph ^= 1; }
            }
        }
        if (tid == 0) TRACE(16 + wg * 8 + 5);
#pragma unroll
        for (int i = 0; i < 64; i++) accs[i] = 0.f;
        uint32_t gk[32], xr[32];
        const uint32_t xs = aux + cw * 2048;
        const uint32_t xrow = xs + ((lane & 7) + ((lane >> 3) & 1) * 8) * 128;
        auto xaddr = [&](int j) { return xrow + (j >> 2) * 16384 + (((((j & 3) * 2) + (lane >> 4)) ^ (lane & 7)) << 4); };
#pragma unroll
        for (int u = U_S; u < U_END; u++) {
            const int v = u - U_S;
            mbar_wait(full2(u % N_STAGES), (u / N_STAGES) & 1);
            if (S_SKEW > 0 && wg == 1 && u == U_END - S_SKEW) asm volatile("bar.sync 1, 256;" ::: "memory");
            mma_narrow(accs, u % N_STAGES, v != 0);
            if (S_SKEW > 0 && wg == 0 && u == U_END - 1) asm volatile("bar.arrive 1, 256;" ::: "memory");
            if (v >= 1 && v <= 8) {
#pragma unroll
                for (int i = 4 * (v - 1); i < 4 * v; i++) {
                    const uint32_t d2 = pack_bf16(accd[2 * i], accd[2 * i + 1]);
                    gk[i] = pack_bf16(silu(bf_lo(d2)), silu(bf_hi(d2)));
                }
            }
            if (v == 9) mbar_wait(x_bar, 0);
            if (v >= 9 && v <= 12) {
#pragma unroll
                for (int j = 2 * (v - 9); j < 2 * (v - 8); j++)
                    asm volatile("ldmatrix.sync.aligned.m8n8.x4.shared.b16 {%0,%1,%2,%3}, [%4];"
                                 : "=r"(xr[4 * j]), "=r"(xr[4 * j + 1]), "=r"(xr[4 * j + 2]), "=r"(xr[4 * j + 3])
                                 : "r"(xaddr(j)) : "memory");
            }
            wg_wait<1>();
            if (v == 0) fence_regs(accd);
            if (u - 1 + N_STAGES < U_END) release(empty2((u - 1) % N_STAGES));
        }
        wg_wait<0>();
        fence_regs(accs);
        if (tid == 0) TRACE(16 + wg * 8 + 6);
#pragma unroll
        for (int j = 0; j < 8; j++) {
            uint32_t r[4];
#pragma unroll
            for (int i = 0; i < 4; i++) {
                const int e = j * 4 + i;
                r[i] = add_bf16x2(xr[e], mul_bf16x2(pack_bf16(accs[2 * e], accs[2 * e + 1]), gk[e]));
            }
            asm volatile("stmatrix.sync.aligned.m8n8.x4.shared.b16 [%0], {%1,%2,%3,%4};"
                         :: "r"(xaddr(j)), "r"(r[0]), "r"(r[1]), "r"(r[2]), "r"(r[3]) : "memory");
            if (j == 3 || j == 7) {
                asm volatile("fence.proxy.async.shared::cta;" ::: "memory");
                __syncwarp();
                if (lane == 0) {
                    tma_store_2d(&prm.out, xs + (j >> 2) * 16384, nslot * 128 + (j >> 2) * 64, mblk * 128 + cw * 16);
                    asm volatile("cp.async.bulk.commit_group;" ::: "memory");
                }
            }
        }
        if (lane == 0) asm volatile("cp.async.bulk.wait_group.read 0;" ::: "memory");
        if (tid == 0) { TRACE(16 + wg * 8 + 7); if (wg == 1) TRACE_GT(13); }
    }
}

typedef CUresult (*EncodeFn)(CUtensorMap*, CUtensorMapDataType, cuuint32_t, void*, const cuuint64_t*, const cuuint64_t*,
                             const cuuint32_t*, const cuuint32_t*, CUtensorMapInterleave, CUtensorMapSwizzle,
                             CUtensorMapL2promotion, CUtensorMapFloatOOBfill);

void encode(EncodeFn fn, CUtensorMap* m, const void* ptr, int rank, const cuuint64_t* dims, const cuuint64_t* strides,
            const cuuint32_t* box) {
    const cuuint32_t es[5] = {1, 1, 1, 1, 1};
    fn(m, CU_TENSOR_MAP_DATA_TYPE_BFLOAT16, rank, const_cast<void*>(ptr), dims, strides, box, es,
       CU_TENSOR_MAP_INTERLEAVE_NONE, CU_TENSOR_MAP_SWIZZLE_128B, CU_TENSOR_MAP_L2_PROMOTION_L2_128B,
       CU_TENSOR_MAP_FLOAT_OOB_FILL_NONE);
}
void encode_2d(EncodeFn fn, CUtensorMap* m, const void* ptr, int cols, int box_rows) {
    const cuuint64_t dims[2] = {(cuuint64_t)cols, SEQ}, strides[1] = {(cuuint64_t)cols * 2};
    const cuuint32_t box[2] = {64, (cuuint32_t)box_rows};
    encode(fn, m, ptr, 2, dims, strides, box);
}
void encode_w1(EncodeFn fn, CUtensorMap* m, const void* ptr, int cols, int blocks) {
    const cuuint64_t dims[3] = {64, DM, (cuuint64_t)cols / 64}, strides[2] = {(cuuint64_t)cols * 2, 128};
    const cuuint32_t box[3] = {64, 64, (cuuint32_t)blocks};
    encode(fn, m, ptr, 3, dims, strides, box);
}
void encode_qk(EncodeFn fn, CUtensorMap* m, const void* ptr) {
    const cuuint64_t dims[3] = {DM, SEQ, 3}, strides[2] = {NQKV * 2, DM * 2};
    const cuuint32_t box[3] = {64, 16, 2};
    encode(fn, m, ptr, 3, dims, strides, box);
}
void encode_a2(EncodeFn fn, CUtensorMap* m, const void* ptr) {
    const cuuint64_t dims[3] = {K2, 2, SEQ / 2}, strides[2] = {(cuuint64_t)SEQ * K2, K2 * 2};
    const cuuint32_t box[3] = {64, 2, 64};
    encode(fn, m, ptr, 3, dims, strides, box);
}
void encode_w2(EncodeFn fn, CUtensorMap* m, const void* ptr, int rows) {
    const cuuint64_t rb = DM * 2;
    const cuuint64_t dims[5] = {DM, 2, 4, 4, (cuuint64_t)rows / 32}, strides[4] = {rb, 8 * rb, 2 * rb, 32 * rb};
    const cuuint32_t box[5] = {64, 2, 4, 4, 2};
    encode(fn, m, ptr, 5, dims, strides, box);
}

}

extern "C" void kernel_launch(void* const* d_in, const int* in_sizes, int n_in, void* d_out, int out_size) {
    (void)in_sizes; (void)n_in; (void)out_size;
    static EncodeFn fn = nullptr;
    static void *p_xn = nullptr, *p_qkv = nullptr, *p_a2 = nullptr;
    if (!fn) {
        cudaDriverEntryPointQueryResult st;
        cudaGetDriverEntryPoint("cuTensorMapEncodeTiled", (void**)&fn, cudaEnableDefault, &st);
        cudaGetSymbolAddress(&p_xn, g_xn);
        cudaGetSymbolAddress(&p_qkv, g_qkv);
        cudaGetSymbolAddress(&p_a2, g_a2);
        cudaFuncSetAttribute(fused_kernel, cudaFuncAttributeMaxDynamicSharedMemorySize, SMEM_BYTES);
    }
    Params prm;
    encode_2d(fn, &prm.x, d_in[0], DM, 128);
    encode_2d(fn, &prm.xn, p_xn, DM, 128);
    encode_w1(fn, &prm.wv, d_in[1], NQKV, 1);
    encode_w1(fn, &prm.wqk, d_in[1], NQKV, 2);
    encode_w1(fn, &prm.wg, d_in[4], DF, 2);
    encode_w1(fn, &prm.wu, d_in[5], DF, 2);
    encode_w1(fn, &prm.wg1, d_in[4], DF, 1);
    encode_w1(fn, &prm.wu1, d_in[5], DF, 1);
    encode_qk(fn, &prm.qk, p_qkv);
    encode_2d(fn, &prm.v, p_qkv, NQKV, 16);
    encode_2d(fn, &prm.o, p_a2, K2, 16);
    encode_a2(fn, &prm.a2, p_a2);
    encode_w2(fn, &prm.wo, d_in[2], DM);
    encode_w2(fn, &prm.wd, d_in[6], DF);
    encode_2d(fn, &prm.out, d_out, DM, 16);
    prm.px = (const __nv_bfloat16*)d_in[0];
    prm.zero = 0;
    fused_kernel<<<NCTA, 384, SMEM_BYTES>>>(prm);
}
```

```cpp
#include <cuda_runtime.h>
#include <cuda_bf16.h>
#include <cuda.h>
#include <stdint.h>

#define P_W1 1
#define P_X 1
#define P_XN4 1
#define P_W2 1
#define P_A2 1
#define P_QKV 1

namespace {

constexpr int SEQ = 2048, DM = 1024, DF = 3584, K2 = DM + DF, NQKV = 3 * DM;
constexpr int NGEMM = 128, NCTA = 132;
constexpr int G1_STAGES = 4, G1_STAGE_BYTES = 49152, G1_KSTEPS = 16, G1_TILES = 5;
constexpr int G2_STAGES = 6, G2_STAGE_BYTES = 32768, G2_KSTEPS = 72, G2_LATE = 40, G2_DSTEPS = 56, G2_LAST = 68;
constexpr int A_BYTES = 16384;
constexpr int AUX_OFF = G1_STAGES * G1_STAGE_BYTES;
constexpr int BAR_OFF = AUX_OFF + 32768;
constexpr int SMEM_BYTES = BAR_OFF + 2560;
constexpr int G1_SKEW = 2, G2_SKEW = 2;
constexpr int CONSUMER_REGS = 224, AUX_REGS = 56;
constexpr int ATT_SLOT = 8192;

enum { F_LN = 0, F_QKV = 1, F_EARLY = 2, F_LATE = 3, F_O = 4, F_CS = 5 };
constexpr unsigned CNT_LN = 8, CNT_QKV = 32, CNT_EARLY = 20, CNT_LATE = 8, CNT_O = 48, CNT_CS = 16;

__device__ __align__(1024) __nv_bfloat16 g_xn[SEQ * DM];
__device__ __align__(1024) __nv_bfloat16 g_qkv[SEQ * NQKV];
__device__ __align__(1024) __nv_bfloat16 g_a2[SEQ * K2];
__device__ __align__(128) float2 g_stats[SEQ];
__device__ __align__(128) float g_colsum[16 * 2048];
__device__ __align__(128) unsigned g_flags[6 * 16 * 32];
__device__ __align__(128) unsigned g_epoch[NCTA * 16];

#define TRACE_T 2
#define TRACE(slot) do {} while (0)
#define TRACE_GT(slot) do {} while (0)

__device__ __forceinline__ uint32_t smem_u32(const void* p) { return (uint32_t)__cvta_generic_to_shared(p); }
__device__ __forceinline__ void mbar_init(uint32_t bar, uint32_t cnt) {
    asm volatile("mbarrier.init.shared::cta.b64 [%0], %1;" :: "r"(bar), "r"(cnt) : "memory");
}
__device__ __forceinline__ void mbar_expect_tx(uint32_t bar, uint32_t bytes) {
    asm volatile("mbarrier.arrive.expect_tx.shared::cta.b64 _, [%0], %1;" :: "r"(bar), "r"(bytes) : "memory");
}
__device__ __forceinline__ void mbar_arrive(uint32_t bar) {
    asm volatile("mbarrier.arrive.shared::cta.b64 _, [%0];" :: "r"(bar) : "memory");
}
__device__ __forceinline__ void mbar_arrive_cluster(uint32_t bar, uint32_t cta) {
    asm volatile("{\n.reg .b32 ra;\nmapa.shared::cluster.u32 ra, %0, %1;\nmbarrier.arrive.shared::cluster.b64 _, [ra];\n}"
                 :: "r"(bar), "r"(cta) : "memory");
}
__device__ __forceinline__ bool mbar_try_wait(uint32_t bar, uint32_t parity) {
    uint32_t ok;
    asm volatile("{\n.reg .pred p;\nmbarrier.try_wait.parity.shared::cta.b64 p, [%1], %2;\nselp.u32 %0, 1, 0, p;\n}"
                 : "=r"(ok) : "r"(bar), "r"(parity) : "memory");
    return ok;
}
__device__ __forceinline__ void mbar_wait(uint32_t bar, uint32_t parity) {
    int spins = 0;
    while (!mbar_try_wait(bar, parity)) { if (++spins > (1 << 17)) break; }
}
__device__ __forceinline__ void flag_wait(const unsigned* p, unsigned target) {
    for (int spins = 0; spins < (1 << 19); spins++) {
        unsigned v;
        asm volatile("ld.acquire.gpu.global.u32 %0, [%1];" : "=r"(v) : "l"(p) : "memory");
        if ((int)(v - target) >= 0) break;
        __nanosleep(64);
    }
}
__device__ __forceinline__ void flag_add(unsigned* p) {
    asm volatile("red.release.gpu.global.add.u32 [%0], 1;" :: "l"(p) : "memory");
}
__device__ __forceinline__ bool elect_one() {
    uint32_t ok;
    asm volatile("{\n.reg .pred p;\nelect.sync _|p, 0xffffffff;\nselp.u32 %0, 1, 0, p;\n}" : "=r"(ok));
    return ok;
}
__device__ __forceinline__ void fence_proxy_async() { asm volatile("fence.proxy.async;" ::: "memory"); }
__device__ __forceinline__ uint4 lds128(uint32_t addr) {
    uint4 v;
    asm volatile("ld.shared.v4.u32 {%0,%1,%2,%3}, [%4];" : "=r"(v.x), "=r"(v.y), "=r"(v.z), "=r"(v.w) : "r"(addr) : "memory");
    return v;
}
__device__ __forceinline__ float2 lds64f(uint32_t addr) {
    float2 v;
    asm volatile("ld.shared.v2.f32 {%0,%1}, [%2];" : "=f"(v.x), "=f"(v.y) : "r"(addr) : "memory");
    return v;
}
__device__ __forceinline__ void sts128(uint32_t addr, uint4 v) {
    asm volatile("st.shared.v4.u32 [%0], {%1,%2,%3,%4};" :: "r"(addr), "r"(v.x), "r"(v.y), "r"(v.z), "r"(v.w) : "memory");
}
__device__ __forceinline__ void sts64f(uint32_t addr, float a, float b) {
    asm volatile("st.shared.v2.f32 [%0], {%1,%2};" :: "r"(addr), "f"(a), "f"(b) : "memory");
}

__device__ __forceinline__ uint64_t policy(bool stream) {
    uint64_t p;
    if (stream) asm("createpolicy.fractional.L2::evict_first.b64 %0, 1.0;" : "=l"(p));
    else asm("createpolicy.fractional.L2::evict_normal.b64 %0, 1.0;" : "=l"(p));
    return p;
}
__device__ __forceinline__ void tma_2d(uint32_t dst, const CUtensorMap* m, uint32_t bar, int c0, int c1, uint64_t pol) {
    asm volatile("cp.async.bulk.tensor.2d.shared::cluster.global.mbarrier::complete_tx::bytes.L2::cache_hint"
                 " [%0], [%1, {%3, %4}], [%2], %5;"
                 :: "r"(dst), "l"(m), "r"(bar), "r"(c0), "r"(c1), "l"(pol) : "memory");
}
__device__ __forceinline__ void tma_3d(uint32_t dst, const CUtensorMap* m, uint32_t bar, int c0, int c1, int c2, uint64_t pol) {
    asm volatile("cp.async.bulk.tensor.3d.shared::cluster.global.mbarrier::complete_tx::bytes.L2::cache_hint"
                 " [%0], [%1, {%3, %4, %5}], [%2], %6;"
                 :: "r"(dst), "l"(m), "r"(bar), "r"(c0), "r"(c1), "r"(c2), "l"(pol) : "memory");
}
__device__ __forceinline__ void tma_3d_mc(uint32_t dst, const CUtensorMap* m, uint32_t bar, int c1, int c2, uint64_t pol) {
    asm volatile("cp.async.bulk.tensor.3d.shared::cluster.global.mbarrier::complete_tx::bytes.multicast::cluster.L2::cache_hint"
                 " [%0], [%1, {%3, %4, %5}], [%2], %6, %7;"
                 :: "r"(dst), "l"(m), "r"(bar), "r"(0), "r"(c1), "r"(c2), "h"((uint16_t)3), "l"(pol) : "memory");
}
__device__ __forceinline__ void tma_5d_mc(uint32_t dst, const CUtensorMap* m, uint32_t bar, int c0, int c4, uint64_t pol) {
    asm volatile("cp.async.bulk.tensor.5d.shared::cluster.global.mbarrier::complete_tx::bytes.multicast::cluster.L2::cache_hint"
                 " [%0], [%1, {%3, %4, %4, %4, %5}], [%2], %6, %7;"
                 :: "r"(dst), "l"(m), "r"(bar), "r"(c0), "r"(0), "r"(c4), "h"((uint16_t)3), "l"(pol) : "memory");
}
__device__ __forceinline__ void tma_store_2d(const CUtensorMap* m, uint32_t src, int c0, int c1) {
    asm volatile("cp.async.bulk.tensor.2d.global.shared::cta.bulk_group [%0, {%2, %3}], [%1];"
                 :: "l"(m), "r"(src), "r"(c0), "r"(c1) : "memory");
}
__device__ __forceinline__ uint4 ldg_stream(const void* p, uint64_t pol) {
    uint4 v;
    asm volatile("ld.global.nc.L1::no_allocate.L2::cache_hint.v4.u32 {%0,%1,%2,%3}, [%4], %5;"
                 : "=r"(v.x), "=r"(v.y), "=r"(v.z), "=r"(v.w) : "l"(p), "l"(pol));
    return v;
}
__device__ __forceinline__ void bulk_load(uint32_t dst, const void* src, uint32_t bytes, uint32_t bar) {
    asm volatile("cp.async.bulk.shared::cluster.global.mbarrier::complete_tx::bytes [%0], [%1], %2, [%3];"
                 :: "r"(dst), "l"(src), "r"(bytes), "r"(bar) : "memory");
}
__device__ __forceinline__ void prefetch_3d(const CUtensorMap* m, int c1, int c2, uint64_t pol) {
    asm volatile("cp.async.bulk.prefetch.tensor.3d.L2.global.L2::cache_hint [%0, {%1, %2, %3}], %4;"
                 :: "l"(m), "r"(0), "r"(c1), "r"(c2), "l"(pol) : "memory");
}
__device__ __forceinline__ void prefetch_map(const CUtensorMap* m) {
    asm volatile("prefetch.tensormap [%0];" :: "l"(m) : "memory");
}
__device__ __forceinline__ void wg_fence() { asm volatile("wgmma.fence.sync.aligned;" ::: "memory"); }
__device__ __forceinline__ void wg_commit() { asm volatile("wgmma.commit_group.sync.aligned;" ::: "memory"); }
template <int N> __device__ __forceinline__ void wg_wait() { asm volatile("wgmma.wait_group.sync.aligned %0;" :: "n"(N) : "memory"); }

__device__ __forceinline__ uint64_t desc_a(uint32_t addr) {
    return (uint64_t)((addr & 0x3FFFF) >> 4) | (1ull << 16) | (64ull << 32) | (1ull << 62);
}
__device__ __forceinline__ uint64_t desc_b(uint32_t addr) {
    return (uint64_t)((addr & 0x3FFFF) >> 4) | (512ull << 16) | (64ull << 32) | (1ull << 62);
}

#define R8(d, o) "+f"(d[o]), "+f"(d[o+1]), "+f"(d[o+2]), "+f"(d[o+3]), "+f"(d[o+4]), "+f"(d[o+5]), "+f"(d[o+6]), "+f"(d[o+7])
#define R32(d, o) R8(d, o), R8(d, o+8), R8(d, o+16), R8(d, o+24)
#define R64(d, o) R32(d, o), R32(d, o+32)

__device__ __forceinline__ void wgmma_n256(float (&d)[128], uint64_t da, uint64_t db, int scale_d) {
    asm volatile("{\n.reg .pred p;\nsetp.ne.b32 p, %130, 0;\n"
        "wgmma.mma_async.sync.aligned.m64n256k16.f32.bf16.bf16 "
        "{%0,%1,%2,%3,%4,%5,%6,%7,%8,%9,%10,%11,%12,%13,%14,%15,%16,%17,%18,%19,%20,%21,%22,%23,%24,%25,%26,%27,%28,%29,%30,%31,"
        "%32,%33,%34,%35,%36,%37,%38,%39,%40,%41,%42,%43,%44,%45,%46,%47,%48,%49,%50,%51,%52,%53,%54,%55,%56,%57,%58,%59,%60,%61,%62,%63,"
        "%64,%65,%66,%67,%68,%69,%70,%71,%72,%73,%74,%75,%76,%77,%78,%79,%80,%81,%82,%83,%84,%85,%86,%87,%88,%89,%90,%91,%92,%93,%94,%95,"
        "%96,%97,%98,%99,%100,%101,%102,%103,%104,%105,%106,%107,%108,%109,%110,%111,%112,%113,%114,%115,%116,%117,%118,%119,%120,%121,%122,%123,%124,%125,%126,%127},"
        " %128, %129, p, 1, 1, 0, 1;\n}"
        : R64(d, 0), R64(d, 64) : "l"(da), "l"(db), "r"(scale_d));
}
__device__ __forceinline__ void wgmma_n128(float (&d)[64], uint64_t da, uint64_t db, int scale_d) {
    asm volatile("{\n.reg .pred p;\nsetp.ne.b32 p, %66, 0;\n"
        "wgmma.mma_async.sync.aligned.m64n128k16.f32.bf16.bf16 "
        "{%0,%1,%2,%3,%4,%5,%6,%7,%8,%9,%10,%11,%12,%13,%14,%15,%16,%17,%18,%19,%20,%21,%22,%23,%24,%25,%26,%27,%28,%29,%30,%31,"
        "%32,%33,%34,%35,%36,%37,%38,%39,%40,%41,%42,%43,%44,%45,%46,%47,%48,%49,%50,%51,%52,%53,%54,%55,%56,%57,%58,%59,%60,%61,%62,%63},"
        " %64, %65, p, 1, 1, 0, 1;\n}"
        : R64(d, 0) : "l"(da), "l"(db), "r"(scale_d));
}

__device__ __forceinline__ uint32_t pack_bf16(float lo, float hi) {
    uint32_t r; asm("cvt.rn.bf16x2.f32 %0, %1, %2;" : "=r"(r) : "f"(hi), "f"(lo)); return r;
}
__device__ __forceinline__ float bf_lo(uint32_t v) { return __uint_as_float(v << 16); }
__device__ __forceinline__ float bf_hi(uint32_t v) { return __uint_as_float(v & 0xffff0000u); }
__device__ __forceinline__ float round_bf16(float v) { return bf_lo(pack_bf16(v, 0.f)); }
__device__ __forceinline__ uint32_t mul_bf16x2(uint32_t a, uint32_t b) {
    uint32_t r; asm("mul.rn.bf16x2 %0, %1, %2;" : "=r"(r) : "r"(a), "r"(b)); return r;
}
__device__ __forceinline__ uint32_t add_bf16x2(uint32_t a, uint32_t b) {
    uint32_t r; asm("add.rn.bf16x2 %0, %1, %2;" : "=r"(r) : "r"(a), "r"(b)); return r;
}
__device__ __forceinline__ uint32_t sub_bf16x2(uint32_t a, uint32_t b) {
    uint32_t r; asm("sub.rn.bf16x2 %0, %1, %2;" : "=r"(r) : "r"(a), "r"(b)); return r;
}
__device__ __forceinline__ float tanh_fast(float x) { float r; asm("tanh.approx.f32 %0, %1;" : "=f"(r) : "f"(x)); return r; }
__device__ __forceinline__ float gelu_tanh(float g) {
    float t = fmaf(g * g, 0.044715f * 0.7978845608f, 0.7978845608f) * g;
    float hg = 0.5f * g;
    return fmaf(hg, tanh_fast(t), hg);
}
__device__ __forceinline__ uint32_t geglu2(uint32_t g2, uint32_t u2) {
    return mul_bf16x2(pack_bf16(gelu_tanh(bf_lo(g2)), gelu_tanh(bf_hi(g2))), u2);
}
__device__ __forceinline__ float silu(float d) {
    float hd = 0.5f * d;
    return fmaf(hd, tanh_fast(hd), hd);
}
__device__ __forceinline__ float ex2_fast(float x) { float r; asm("ex2.approx.ftz.f32 %0, %1;" : "=f"(r) : "f"(x)); return r; }
__device__ __forceinline__ void unpack8(uint4 v, float (&f)[8]) {
    f[0] = bf_lo(v.x); f[1] = bf_hi(v.x); f[2] = bf_lo(v.y); f[3] = bf_hi(v.y);
    f[4] = bf_lo(v.z); f[5] = bf_hi(v.z); f[6] = bf_lo(v.w); f[7] = bf_hi(v.w);
}
template <int N> __device__ __forceinline__ void fence_regs(float (&d)[N]) {
#pragma unroll
    for (int i = 0; i < N; i++) asm volatile("" : "+f"(d[i]) :: "memory");
}

__device__ __forceinline__ float rcp_fast(float x) { float r; asm("rcp.approx.ftz.f32 %0, %1;" : "=f"(r) : "f"(x)); return r; }
__device__ __forceinline__ uint32_t max_bf16x2(uint32_t a, uint32_t b) {
    uint32_t r; asm("max.bf16x2 %0, %1, %2;" : "=r"(r) : "r"(a), "r"(b)); return r;
}
__device__ __forceinline__ uint4 ldsm4(uint32_t addr) {
    uint4 v;
    asm volatile("ldmatrix.sync.aligned.m8n8.x4.shared.b16 {%0,%1,%2,%3}, [%4];"
                 : "=r"(v.x), "=r"(v.y), "=r"(v.z), "=r"(v.w) : "r"(addr) : "memory");
    return v;
}
__device__ __forceinline__ uint4 ldsm4_t(uint32_t addr) {
    uint4 v;
    asm volatile("ldmatrix.sync.aligned.m8n8.x4.trans.shared.b16 {%0,%1,%2,%3}, [%4];"
                 : "=r"(v.x), "=r"(v.y), "=r"(v.z), "=r"(v.w) : "r"(addr) : "memory");
    return v;
}
__device__ __forceinline__ void mma_16816(float (&c)[4], uint32_t a0, uint32_t a1, uint32_t a2, uint32_t a3, uint32_t b0, uint32_t b1) {
    asm("mma.sync.aligned.m16n8k16.row.col.f32.bf16.bf16.f32 {%0,%1,%2,%3}, {%4,%5,%6,%7}, {%8,%9}, {%0,%1,%2,%3};"
        : "+f"(c[0]), "+f"(c[1]), "+f"(c[2]), "+f"(c[3]) : "r"(a0), "r"(a1), "r"(a2), "r"(a3), "r"(b0), "r"(b1));
}
__device__ __forceinline__ void mma_1688(float (&c)[4], uint32_t a0, uint32_t a1, uint32_t b0) {
    asm("mma.sync.aligned.m16n8k8.row.col.f32.bf16.bf16.f32 {%0,%1,%2,%3}, {%4,%5}, {%6}, {%0,%1,%2,%3};"
        : "+f"(c[0]), "+f"(c[1]), "+f"(c[2]), "+f"(c[3]) : "r"(a0), "r"(a1), "r"(b0));
}
__device__ __forceinline__ void qk_tile(float (&c)[4], const uint4& q0, const uint4& q1, const uint4& k, float init) {
    c[0] = c[1] = c[2] = c[3] = init;
    mma_16816(c, q0.x, q0.y, q0.z, q0.w, k.x, k.y);
    mma_16816(c, q1.x, q1.y, q1.z, q1.w, k.z, k.w);
}
__device__ __forceinline__ uint32_t scaled_logits(bool first, float a0, float a1, float b0, float b1) {
    uint32_t p, r;
    asm("{\n.reg .pred p;\nsetp.ne.u32 p, %1, 0;\n@p cvt.rn.bf16x2.f32 %0, %3, %2;\n@!p cvt.rn.bf16x2.f32 %0, %5, %4;\n}"
        : "=r"(p) : "r"((uint32_t)first), "f"(a0), "f"(a1), "f"(b0), "f"(b1));
    asm("fma.rn.bf16x2 %0, %1, %2, %3;" : "=r"(r) : "r"(p), "r"(0x3e353e35u), "r"(mul_bf16x2(p, 0x379e379eu)));
    return r;
}
template <typename T> __device__ __forceinline__ T uniform(T v) { return __shfl_sync(0xffffffffu, v, 0); }

__device__ __forceinline__ void attention(const CUtensorMap* maps, uint32_t base, uint32_t zero, int grp, int warp, int lane) {
    constexpr float LOG2E = 1.4426950408889634f;
    const int g = lane >> 2, t = lane & 3;
    const bool up0 = 2 * t > g, up1 = 2 * t + 1 > g;
    const uint32_t keep = (up0 ? 0x0000ffffu : 0u) | (up1 ? 0xffff0000u : 0u);
    const uint32_t buf = base + warp * 2 * ATT_SLOT, bar = base + AUX_OFF + warp * 16;
    const uint32_t qoff = (lane & 15) * 128 + (((lane >> 4) ^ (lane & 7)) << 4);
    const uint32_t koff = 2048 + (lane & 7) * 128 + (((lane >> 3) ^ (lane & 7)) << 4);
    const uint32_t rest_bar = base + AUX_OFF + 192;
    const int col = uniform(grp * 256), first = uniform((warp / 3 * 32 + warp % 3 * 11) * 16);
    const CUtensorMap* const mqk = reinterpret_cast<const CUtensorMap*>(uniform(reinterpret_cast<uint64_t>(maps)));
    const CUtensorMap *const mv = mqk + 1, *const mo = mqk + 2;
    const uint64_t pol = policy(P_QKV);
    uint4 kp[2], vp[2];
    uint32_t l0[2], l1[2], m[2];
    float s[2][3][4];
    auto scores = [&](uint32_t st, int row) {
        const float before = (row & 1023) == 0 ? -5.656854e9f : 0.f;
#pragma unroll
        for (int h = 0; h < 2; h++) {
            const uint4 q0 = ldsm4(st + (qoff ^ (h * 64))), q1 = ldsm4(st + (qoff ^ (h * 64 + 32)));
            const uint4 k0 = ldsm4(st + (koff ^ (h * 64))), k1 = ldsm4(st + 1024 + (koff ^ (h * 64)));
            qk_tile(s[h][0], q0, q1, kp[h], before);
            qk_tile(s[h][1], q0, q1, k0, 0.f);
            qk_tile(s[h][2], q0, q1, k1, 0.f);
            kp[h] = k1;
        }
    };
    auto logits = [&]() {
#pragma unroll
        for (int h = 0; h < 2; h++) {
            l0[h] = scaled_logits(up0, s[h][0][0], s[h][1][2], s[h][1][0], s[h][2][2]);
            l1[h] = scaled_logits(up1, s[h][0][1], s[h][1][3], s[h][1][1], s[h][2][3]);
            m[h] = max_bf16x2(l0[h], l1[h]);
            m[h] = max_bf16x2(m[h], __shfl_xor_sync(0xffffffffu, m[h], 1));
        }
    };
    auto row_max = [&]() {
#pragma unroll
        for (int h = 0; h < 2; h++) m[h] = max_bf16x2(m[h], __shfl_xor_sync(0xffffffffu, m[h], 2));
    };
    auto next = [](uint32_t p) {
        return (0x80200400u >> (p >> 4 & 31) & 1) > (p >> 15 & 1) ? p + (64 << 16) + 0x8000 : (p + 16) & ~0x8800u;
    };
    auto exchange = [&](uint32_t st, uint32_t b, uint32_t po, uint32_t pv, uint32_t pq) {
        asm volatile("{\n.reg .pred e, p, q;\n"
            "fence.proxy.async.shared::cta;\n"
            "bar.warp.sync 0xffffffff;\n"
            "elect.sync _|e, 0xffffffff;\n"
            "setp.eq.and.b32 p, %12, 0, e;\n"
            "setp.lt.and.s32 q, %8, %13, e;\n"
            "@q mbarrier.arrive.expect_tx.shared::cta.b64 _, [%2], 6144;\n"
            "@q cp.async.bulk.tensor.3d.shared::cluster.global.mbarrier::complete_tx::bytes.L2::cache_hint [%0], [%3, {%6, %7, %14}], [%2], %15;\n"
            "@q cp.async.bulk.tensor.2d.shared::cluster.global.mbarrier::complete_tx::bytes.L2::cache_hint [%0 + 4096], [%4, {%8, %9}], [%2], %15;\n"
            "@e cp.async.bulk.wait_group.read 0;\n"
            "@p cp.async.bulk.tensor.2d.global.shared::cta.bulk_group [%5, {%10, %11}], [%1 + 6144];\n"
            "@e cp.async.bulk.commit_group;\n"
            "bar.warp.sync 0xffffffff;\n}"
            :: "r"(st), "r"(st ^ ATT_SLOT), "r"(b), "l"(mqk), "l"(mv), "l"(mo), "r"(pq >> 16), "r"(pq & 2047),
               "r"((pv >> 16) + 2 * DM), "r"(pv & 2047), "r"(po >> 16), "r"(po & 2047), "r"(po & 0x8000),
               "r"(col + 256 + 2 * DM), "r"(0), "l"(pol) : "memory");
    };
    unsigned epoch = 0;
    if (elect_one()) {
        mbar_init(bar, 1); mbar_init(bar + 8, 1);
        prefetch_map(mqk); prefetch_map(mv); prefetch_map(mo);
        if (warp == 2) {
            mbar_init(rest_bar, 1);
            epoch = __ldcg(g_epoch + blockIdx.x * 16) + 1;
            g_epoch[blockIdx.x * 16] = epoch;
            flag_wait(g_flags + F_QKV * 512 + grp * 32, epoch * CNT_QKV);
            TRACE(60);
        }
        fence_proxy_async();
    }
    __syncthreads();
    if (elect_one()) {
        mbar_expect_tx(bar + 8, 8192);
        tma_3d(buf + ATT_SLOT, mqk, bar + 8, col, first, 0, pol);
        tma_2d(buf + ATT_SLOT + 4096, mv, bar + 8, col + 2 * DM, first - 16, policy(false));
        tma_2d(buf + ATT_SLOT + 6144, mv, bar + 8, col + DM, first - 16, policy(false));
        mbar_expect_tx(bar, 6144);
        tma_3d(buf, mqk, bar, col, first + 16, 0, pol);
        tma_2d(buf + 4096, mv, bar, col + 2 * DM, first, pol);
        if (warp == 0) TRACE(9);
    }
    __syncwarp();
    mbar_wait(bar + 8, 0);
#pragma unroll
    for (int h = 0; h < 2; h++) {
        kp[h] = ldsm4(buf + ATT_SLOT + 5120 + (koff ^ (h * 64)));
        vp[h] = ldsm4_t(buf + ATT_SLOT + 3072 + (koff ^ (h * 64)));
    }
    scores(buf + ATT_SLOT, first);
    uint32_t pm = 0x8000, p0 = col << 16 | first, p1 = p0 + 16, p2 = p0 + 32, p3 = p0 + 48;
    exchange(buf + ATT_SLOT, bar + 8, pm, p1, p2);
    logits();
    row_max();
    uint32_t st = buf, b = bar, cnt = 1;
    bool ready = mbar_try_wait(b, 0);
#pragma unroll 1
    while (p0 >> 16 < col + 256) {
        uint32_t pa[2], pb[2];
        if (!ready) mbar_wait(b, (cnt >> 1) & 1);
        uint4 v[2][2];
#pragma unroll
        for (int h = 0; h < 2; h++) {
            const float ma = -LOG2E * bf_lo(m[h]), mb = -LOG2E * bf_hi(m[h]);
            const float a0 = ex2_fast(fmaf(bf_lo(l0[h]), LOG2E, ma)), a1 = ex2_fast(fmaf(bf_lo(l1[h]), LOG2E, ma));
            const float b0 = ex2_fast(fmaf(bf_hi(l0[h]), LOG2E, mb)), b1 = ex2_fast(fmaf(bf_hi(l1[h]), LOG2E, mb));
            float sum[4] = {0.f, 0.f, 0.f, 0.f};
            mma_1688(sum, pack_bf16(a0, a1), pack_bf16(b0, b1), 0x3f803f80u);
            const float ra = rcp_fast(sum[0]), rb = rcp_fast(sum[2]);
            pa[h] = pack_bf16(a0 * ra, a1 * ra);
            pb[h] = pack_bf16(b0 * rb, b1 * rb);
        }
        scores(st, p1);
#pragma unroll
        for (int h = 0; h < 2; h++) {
            v[h][0] = ldsm4_t(st + 4096 + (qoff ^ (h * 64)));
            v[h][1] = ldsm4_t(st + 4096 + (qoff ^ (h * 64 + 32)));
        }
        if (cnt == 6 && warp == 2 && elect_one()) {
            flag_wait(g_flags + F_QKV * 512 + 128 + grp * 32, epoch * CNT_QKV);
            fence_proxy_async();
            mbar_arrive(rest_bar);
        }
        if (cnt == 8) mbar_wait(rest_bar, 0);
        if (cnt == 37 && elect_one()) {
            asm volatile("cp.async.bulk.wait_group 1;" ::: "memory");
            fence_proxy_async();
            flag_add(g_flags + F_O * 512);
        }
        exchange(st, b, pm, p2, p3);
        pm = p0; p0 = p1; p1 = p2; p2 = p3; p3 = next(p3);
        logits();
        float o[2][4][4];
#pragma unroll
        for (int h = 0; h < 2; h++) {
            const uint32_t prev[4] = {vp[h].x, vp[h].y, vp[h].z, vp[h].w};
            const uint32_t own[8] = {v[h][0].x, v[h][0].y, v[h][0].z, v[h][0].w, v[h][1].x, v[h][1].y, v[h][1].z, v[h][1].w};
            const uint32_t a0 = pa[h] & keep, a1 = pa[h] & ~keep, a2 = pb[h] & keep, a3 = pb[h] & ~keep;
            const uint32_t z0 = pa[h] & zero, z1 = pb[h] & zero;
#pragma unroll
            for (int j = 0; j < 4; j++) {
                o[h][j][0] = o[h][j][1] = o[h][j][2] = o[h][j][3] = 0.f;
                mma_1688(o[h][j], a0, z0, prev[j]);
                mma_16816(o[h][j], a1, a2, z1, a3, own[2 * j], own[2 * j + 1]);
            }
            vp[h] = make_uint4(own[1], own[3], own[5], own[7]);
        }
        row_max();
        b ^= 8; cnt++;
        ready = mbar_try_wait(b, (cnt >> 1) & 1);
#pragma unroll
        for (int h = 0; h < 2; h++) {
#pragma unroll
            for (int d = 0; d < 2; d++)
                asm volatile("stmatrix.sync.aligned.m8n8.x4.shared.b16 [%0], {%1,%2,%3,%4};"
                             :: "r"(st + 6144 + (qoff ^ (h * 64 + d * 32))),
                                "r"(pack_bf16(o[h][2 * d][0], o[h][2 * d][1])), "r"(pack_bf16(o[h][2 * d][2], o[h][2 * d][3])),
                                "r"(pack_bf16(o[h][2 * d + 1][0], o[h][2 * d + 1][1])),
                                "r"(pack_bf16(o[h][2 * d + 1][2], o[h][2 * d + 1][3])) : "memory");
        }
        st ^= ATT_SLOT;
    }
    exchange(st, b, pm, p0, p0);
    if (elect_one()) {
        asm volatile("cp.async.bulk.wait_group 0;" ::: "memory");
        fence_proxy_async();
        flag_add(g_flags + F_O * 512 + 32);
        if (warp == 0) TRACE(10);
    }
}

__device__ __forceinline__ void warp_sum2(float& a, float& b) {
#pragma unroll
    for (int o = 16; o > 0; o >>= 1) {
        a += __shfl_xor_sync(0xffffffffu, a, o);
        b += __shfl_xor_sync(0xffffffffu, b, o);
    }
}
__device__ __forceinline__ float row_sum(const uint32_t* w) {
    float a = 0.f, b = 0.f;
#pragma unroll
    for (int i = 0; i < 16; i++) { a += bf_lo(w[i]); b += bf_hi(w[i]); }
    return a + b;
}
__device__ __forceinline__ float row_sq(const uint32_t* w, float mean) {
    float a = 0.f, b = 0.f;
#pragma unroll
    for (int i = 0; i < 16; i++) {
        const float lo = bf_lo(w[i]) - mean, hi = bf_hi(w[i]) - mean;
        a = fmaf(lo, lo, a); b = fmaf(hi, hi, b);
    }
    return a + b;
}
__device__ __forceinline__ float row_inv(float sq) {
    return 1.f / round_bf16(sqrtf(round_bf16(round_bf16(sq * (1.f / DM)) + 1e-5f)));
}
__device__ __forceinline__ void row_store(const uint32_t* w, float mean, float inv, int row, int lane) {
    const uint32_t m2 = pack_bf16(mean, mean);
    __nv_bfloat16* dst = g_xn + (size_t)row * DM + lane * 8;
#pragma unroll
    for (int i = 0; i < 4; i++) {
        uint32_t o[4];
#pragma unroll
        for (int j = 0; j < 4; j++) {
            const uint32_t c = sub_bf16x2(w[i * 4 + j], m2);
            o[j] = pack_bf16(bf_lo(c) * inv, bf_hi(c) * inv);
        }
        *reinterpret_cast<uint4*>(dst + i * 256) = make_uint4(o[0], o[1], o[2], o[3]);
    }
    if (lane == 0) g_stats[row] = make_float2(-bf_lo(m2), inv);
}

struct Params {
    CUtensorMap x, xn, wqkv, wg, wu, qk, v, o, a2, wo, wd, out;
    const __nv_bfloat16* px;
    uint32_t zero;
};

__device__ __forceinline__ bool tile_is_qkv(int nt) { return nt < 4 || (nt >= 8 && nt < 16); }
__device__ __forceinline__ int tile_index(int nt) { return nt < 4 ? nt + 8 : (nt < 8 ? nt - 4 : (nt < 16 ? nt - 8 : nt - 12)); }

__global__ void __cluster_dims__(2, 1, 1) __launch_bounds__(384, 1)
fused_kernel(const __grid_constant__ Params prm) {
    extern __shared__ __align__(1024) uint8_t smem_raw[];
    const uint32_t base = smem_u32(smem_raw) & ~1023u;
    const uint32_t bars = base + BAR_OFF;
    auto full1 = [&](int s) { return bars + s * 8; };
    auto empty1 = [&](int s) { return bars + 32 + s * 8; };
    auto full2 = [&](int s) { return bars + 64 + s * 8; };
    auto empty2 = [&](int s) { return bars + 128 + s * 8; };
    const uint32_t sig_bar = bars + 192, dep_bar = bars + 256, cs_bar = bars + 304, fold_bar = bars + 320, x_bar = bars + 328;
    const uint32_t colsum = bars + 512, stats = bars + 1536;
    auto stage2 = [&](int q) { return base + q * G2_STAGE_BYTES; };
    const uint32_t aux = base + AUX_OFF;

    const int warp = __shfl_sync(0xffffffffu, threadIdx.x >> 5, 0);
    const int lane = threadIdx.x & 31;
    const int rank = blockIdx.x & 1;
    const int mblk = ((blockIdx.x >> 1) & 7) * 2 + rank;
    const int nslot = blockIdx.x >> 4;

    if (blockIdx.x >= NGEMM) {
        if (threadIdx.x == 0) { TRACE_GT(0); TRACE(1); }
        attention(&prm.qk, (base + 2 * ATT_SLOT - 1) & ~(2u * ATT_SLOT - 1), prm.zero, blockIdx.x - NGEMM, warp, lane);
    } else if (warp >= 8) {
        unsigned* const flags = g_flags + mblk * 32;
        const CUtensorMap* const w0 = nslot < 4 ? &prm.wqkv : (rank ? &prm.wu : &prm.wg);
        if (elect_one()) {
            if (warp == 8) {
                TRACE_GT(0); TRACE(1);
                prefetch_map(&prm.x); prefetch_map(w0);
                for (int s = 0; s < G1_STAGES; s++) { mbar_init(full1(s), 1); mbar_init(empty1(s), 4); }
            } else if (warp == 9) {
                for (int s = 0; s < G2_STAGES; s++) { mbar_init(full2(s), 1); mbar_init(empty2(s), 4); }
            } else if (warp == 10) {
                for (int s = 0; s < 7; s++) mbar_init(sig_bar + s * 8, 8);
                mbar_init(fold_bar, 3); mbar_init(x_bar, 1);
            } else {
                for (int s = 0; s < 8; s++) mbar_init(dep_bar + s * 8, 1);
            }
            asm volatile("fence.mbarrier_init.release.cluster;" ::: "memory");
        }
        __syncwarp();
        asm volatile("barrier.cluster.arrive.relaxed.aligned;" ::: "memory");
        if (warp == 8 && lane == 0) {
            for (int s = 0; s < G1_STAGES; s++) {
                mbar_expect_tx(full1(s), G1_STAGE_BYTES);
                tma_2d(base + s * G1_STAGE_BYTES, &prm.x, full1(s), s * 64, mblk * 128, policy(P_X));
            }
            TRACE(15);
        }
        asm volatile("setmaxnreg.dec.sync.aligned.u32 %0;" :: "n"(AUX_REGS));
        asm volatile("barrier.cluster.wait.acquire.aligned;" ::: "memory");

        if (warp == 8) {
            if (lane == 0) {
                TRACE(2);
                auto load_b1 = [&](int s, int nt, int k) {
                    const uint32_t dst = base + s * G1_STAGE_BYTES + A_BYTES + rank * 16384;
                    if (tile_is_qkv(nt)) tma_3d_mc(dst, &prm.wqkv, full1(s), k * 64, tile_index(nt) * 4 + rank * 2, policy(P_W1));
                    else tma_3d_mc(dst, rank ? &prm.wu : &prm.wg, full1(s), k * 64, tile_index(nt) * 2, policy(P_W1));
                };
                for (int s = 0; s < G1_STAGES; s++) load_b1(s, nslot, s);
                prefetch_map(&prm.xn); prefetch_map(&prm.wqkv); prefetch_map(rank ? &prm.wu : &prm.wg);
                prefetch_map(&prm.a2); prefetch_map(&prm.wo); prefetch_map(&prm.wd); prefetch_map(&prm.out);
                uint32_t ph = 0;
                for (int it = G1_STAGES; it < G1_TILES * G1_KSTEPS; it++) {
                    const int s = it & 3, k = it & 15;
                    if (it == G1_KSTEPS) { TRACE(14); mbar_wait(dep_bar, 0); TRACE(3); }
                    mbar_wait(empty1(s), ph);
                    mbar_expect_tx(full1(s), G1_STAGE_BYTES);
                    tma_2d(base + s * G1_STAGE_BYTES, it < G1_KSTEPS ? &prm.x : &prm.xn, full1(s), k * 64, mblk * 128,
                           policy(it < G1_KSTEPS ? P_X : (P_XN4 && it >= (G1_TILES - 1) * G1_KSTEPS)));
                    load_b1(s, (it >> 4) * 8 + nslot, k);
                    if (s == 3) ph ^= 1;
                }
                mbar_expect_tx(x_bar, 32768);
                tma_2d(aux, &prm.x, x_bar, nslot * 128, mblk * 128, policy(P_X));
                tma_2d(aux + 16384, &prm.x, x_bar, nslot * 128 + 64, mblk * 128, policy(P_X));
                TRACE(4);
                mbar_wait(dep_bar + 8, 0);
                TRACE(5);
                int q = 0; uint32_t ph2 = 1;
                for (int u = 0; u < G2_KSTEPS; u++) {
                    if (u == G2_LATE || u == G2_DSTEPS || u == G2_LAST) {
                        TRACE(u == G2_LATE ? 6 : (u == G2_DSTEPS ? 32 : 40));
                        mbar_wait(dep_bar + (u == G2_LATE ? 16 : (u == G2_DSTEPS ? 24 : 32)), 0);
                        TRACE(u == G2_LATE ? 7 : (u == G2_DSTEPS ? 33 : 41));
                    }
                    if (u < G2_STAGES) {
                        if (u == 0) mbar_wait(empty1(0), ph);
                        if (u == 1) mbar_wait(empty1(1), ph);
                        if (u == 3) mbar_wait(empty1(2), ph);
                        if (u == 4) mbar_wait(empty1(3), ph);
                    } else {
                        mbar_wait(empty2(q), ph2);
                    }
                    const uint32_t sa = stage2(q);
                    const bool down = u < G2_DSTEPS;
                    const int k = down ? u : (u - G2_DSTEPS) % 4 * 4 + (u - G2_DSTEPS) / 4;
                    mbar_expect_tx(full2(q), G2_STAGE_BYTES);
                    tma_3d(sa, &prm.a2, full2(q), (down ? DM : 0) + k * 64, 0, mblk * 64, policy(P_A2));
                    tma_5d_mc(sa + A_BYTES + rank * 8192, down ? &prm.wd : &prm.wo, full2(q), nslot * 128 + rank * 64, k * 2, policy(P_W2));
                    if (++q == G2_STAGES) { q = 0; ph2 ^= 1; }
                }
                TRACE(8);
            }
        } else if (warp == 9) {
            if (lane == 0) {
                const unsigned epoch = __ldcg(g_epoch + blockIdx.x * 16 + 2) + 1;
                mbar_wait(sig_bar, 0);
                TRACE(11);
                flag_add(flags + F_LN * 512);
                TRACE(42);
                flag_wait(flags + F_LN * 512, epoch * CNT_LN);
                fence_proxy_async();
                mbar_arrive(dep_bar);
                mbar_expect_tx(fold_bar, 1024);
                bulk_load(stats, g_stats + mblk * 128, 1024, fold_bar);
                g_epoch[blockIdx.x * 16 + 2] = epoch;
                for (int p = nslot < 4 ? 2 : 1; p < 7; p++) {
                    mbar_wait(sig_bar + p * 8, 0);
                    if (p == 2) TRACE(37);
                    flag_add(p == 2 || p == 3 ? g_flags + F_QKV * 512 + (p * 4 - 8 + (nslot & 3)) * 32
                                              : flags + (p < 6 ? F_EARLY : F_LATE) * 512);
                    if (p == 2) TRACE(43);
                }
            }
        } else {
            const int w = warp - 10;
            const unsigned epoch = __ldcg(g_epoch + blockIdx.x * 16 + w) + 1;
            unsigned* const cs_flag = g_flags + F_CS * 512 + (nslot * 2 + w) * 32;
            mbar_wait(full1(0), 0);
            if (elect_one()) {
                mbar_expect_tx(cs_bar + w * 8, 16384);
                tma_3d(aux + w * 16384, nslot < 4 ? &prm.wqkv : (w ? &prm.wu : &prm.wg), cs_bar + w * 8, 0, mblk * 64,
                       nslot < 4 ? 32 + nslot * 4 + w * 2 : nslot * 2 - 8, policy(P_W1));
            }
            float cs[8];
#pragma unroll
            for (int d = 0; d < 8; d++) cs[d] = 0.f;
            mbar_wait(cs_bar + w * 8, 0);
            const uint32_t wa = aux + w * 16384 + (lane & 8) * 1024 + (lane >> 4) * 128 + (((lane & 7) ^ (lane >> 4)) << 4);
#pragma unroll 1
            for (int i = 0; i < 8; i++) {
#pragma unroll
                for (int j = 0; j < 4; j++) {
                    float f[8];
                    unpack8(lds128((wa ^ (j * 32)) + i * 1024 + j * 256), f);
#pragma unroll
                    for (int d = 0; d < 8; d++) cs[d] += f[d];
                }
            }
#pragma unroll
            for (int d = 0; d < 8; d++) cs[d] += __shfl_xor_sync(0xffffffffu, cs[d], 16);
            *reinterpret_cast<float4*>(g_colsum + mblk * 2048 + nslot * 256 + w * 128 + (lane & 15) * 8 + (lane >> 4) * 4) =
                lane < 16 ? make_float4(cs[0], cs[1], cs[2], cs[3]) : make_float4(cs[4], cs[5], cs[6], cs[7]);
            __syncwarp();
            if (lane == 0) {
                if (w == 0) TRACE(34);
                flag_add(cs_flag);
                flag_wait(cs_flag, epoch * CNT_CS);
            }
            __syncwarp();
            const float4* gp = reinterpret_cast<const float4*>(g_colsum + nslot * 256 + w * 128) + lane;
            float4 c = make_float4(0.f, 0.f, 0.f, 0.f);
#pragma unroll 8
            for (int m = 0; m < 16; m++) {
                const float4 a = __ldcg(gp + m * 512);
                c.x += a.x; c.y += a.y; c.z += a.z; c.w += a.w;
            }
            const uint32_t ca = colsum + (w * 8 + (lane >> 2)) * 64 + (lane & 1) * 32 + (lane & 2) * 4;
            sts64f(ca, c.x, c.y);
            sts64f(ca + 16, c.z, c.w);
            __syncwarp();
            if (lane == 0) {
                mbar_arrive(fold_bar);
                g_epoch[blockIdx.x * 16 + w] = epoch;
                if (w == 0) {
                    TRACE(35);
                    flag_wait(flags + F_EARLY * 512, epoch * CNT_EARLY);
                    fence_proxy_async(); mbar_arrive(dep_bar + 8);
                    flag_wait(flags + F_LATE * 512, epoch * CNT_LATE);
                    fence_proxy_async(); mbar_arrive(dep_bar + 16);
                    flag_wait(g_flags + F_O * 512, epoch * CNT_O);
                    fence_proxy_async(); mbar_arrive(dep_bar + 24);
                    flag_wait(g_flags + F_O * 512 + 32, epoch * CNT_O);
                    fence_proxy_async(); mbar_arrive(dep_bar + 32);
                }
            }
        }
    } else {
        asm volatile("barrier.cluster.arrive.relaxed.aligned;" ::: "memory");
        asm volatile("setmaxnreg.inc.sync.aligned.u32 %0;" :: "n"(CONSUMER_REGS));
        const int wg = __shfl_sync(0xffffffffu, threadIdx.x >> 7, 0);
        const int cw = threadIdx.x >> 5;
        const int tid = threadIdx.x & 127;
        float acc[128];
        uint32_t pk[64];
#pragma unroll
        for (int i = 0; i < 64; i++) asm volatile("mov.b32 %0, 0;" : "=r"(pk[i]));
#pragma unroll
        for (int i = 0; i < 128; i++) asm volatile("mov.b32 %0, 0;" : "=f"(acc[i]));
        asm volatile("barrier.cluster.wait.acquire.aligned;" ::: "memory");

        const int orow = ((lane >> 2) & 1) * (SEQ / 2) + mblk * 64 + cw * 8 + (lane >> 3);
        __nv_bfloat16* optr = nullptr;
        auto release = [&](uint32_t bar) { if (tid < 2) mbar_arrive_cluster(bar, tid); };
        auto chunk_geglu = [&](int j) {
            const int c = j >> 1, h = j & 1;
            uint4 v;
            v.x = geglu2(pk[8 * c + h], pk[32 + 8 * c + h]);
            v.y = geglu2(pk[8 * c + 2 + h], pk[32 + 8 * c + 2 + h]);
            v.z = geglu2(pk[8 * c + 4 + h], pk[32 + 8 * c + 4 + h]);
            v.w = geglu2(pk[8 * c + 6 + h], pk[32 + 8 * c + 6 + h]);
            *reinterpret_cast<uint4*>(optr + h * 4 * K2 + c * 32) = v;
        };
        auto chunk_qkv = [&](int c) {
            *reinterpret_cast<uint4*>(optr + c * 32) = make_uint4(pk[8 * c], pk[8 * c + 2], pk[8 * c + 4], pk[8 * c + 6]);
            *reinterpret_cast<uint4*>(optr + 4 * NQKV + c * 32) = make_uint4(pk[8 * c + 1], pk[8 * c + 3], pk[8 * c + 5], pk[8 * c + 7]);
        };
        auto signal_stores = [&](int p) { __syncwarp(); if (lane == 0) mbar_arrive(sig_bar + p * 8); };

        auto chunk_ln = [&](int k) {
            const int row = mblk * 128 + nslot * 16 + cw * 2;
            if (k == 0) {
                const uint4* xp = reinterpret_cast<const uint4*>(prm.px + (size_t)row * DM) + lane;
#pragma unroll
                for (int i = 0; i < 8; i++) {
                    const uint4 v = ldg_stream(xp + i * 32, policy(P_X));
                    pk[4 * i] = v.x; pk[4 * i + 1] = v.y; pk[4 * i + 2] = v.z; pk[4 * i + 3] = v.w;
                }
            } else if (k == 2) {
                float a = row_sum(pk), b = row_sum(pk + 16);
                warp_sum2(a, b);
                pk[32] = __float_as_uint(a * (1.f / DM)); pk[33] = __float_as_uint(b * (1.f / DM));
            } else if (k == 3) {
                float a = row_sq(pk, __uint_as_float(pk[32])), b = row_sq(pk + 16, __uint_as_float(pk[33]));
                warp_sum2(a, b);
                pk[34] = __float_as_uint(a); pk[35] = __float_as_uint(b);
            } else if (k == 4) {
                row_store(pk, __uint_as_float(pk[32]), row_inv(__uint_as_float(pk[34])), row, lane);
            } else if (k == 5) {
                row_store(pk + 16, __uint_as_float(pk[33]), row_inv(__uint_as_float(pk[35])), row + 1, lane);
                signal_stores(0);
            }
        };

        bool gated = false;
#pragma unroll 1
        for (int t = 0; t < G1_TILES; t++) {
#pragma unroll
            for (int k = 0; k < G1_KSTEPS; k++) {
                const int s = k & 3;
                mbar_wait(full1(s), (k >> 2) & 1);
                if (t == 0 && k == 0 && threadIdx.x == 0) TRACE(12);
                if (t == TRACE_T && threadIdx.x == 0) TRACE(44 + k);
                if (wg == 1 && k == G1_KSTEPS - G1_SKEW) asm volatile("bar.sync 1, 256;" ::: "memory");
                const uint64_t da = desc_a(base + s * G1_STAGE_BYTES + wg * 8192);
                const uint64_t db = desc_b(base + s * G1_STAGE_BYTES + A_BYTES);
                wg_fence();
#pragma unroll
                for (int kk = 0; kk < 4; kk++) wgmma_n256(acc, da + kk * 2, db + kk * 128, (k | kk) != 0);
                wg_commit();
                if (wg == 0 && k == G1_KSTEPS - 1) asm volatile("bar.arrive 1, 256;" ::: "memory");
                if (k <= 5 && t == 0) chunk_ln(k);
                if (k >= 1 && k <= 8 && gated) {
                    chunk_geglu(k - 1);
                    if (k == 8) signal_stores(t == 1 ? 1 : t + 1);
                }
                if (t != 0 && !gated) {
                    if (k == 0) { chunk_qkv(0); chunk_qkv(1); }
                    if (k >= 4 && k <= 9) chunk_qkv(k - 2);
                    if ((k == 0 || k == 9) && t == 2) signal_stores(k ? 3 : 2);
                }
                wg_wait<1>();
                if (k > 0) release(empty1((k - 1) & 3));
            }
            if (t == 0) mbar_wait(fold_bar, 0);
            wg_wait<0>();
            fence_regs(acc);
            release(empty1(3));
            if (t == 0) {
                const uint32_t sp = stats + (cw * 16 + (lane >> 2)) * 8;
                const float2 sa = lds64f(sp), sb = lds64f(sp + 64);
#pragma unroll
                for (int j = 0; j < 16; j++) {
                    const uint4 c = lds128(colsum + j * 64 + (lane & 3) * 16);
                    const float c0 = __uint_as_float(c.x), c1 = __uint_as_float(c.y);
                    const float c2 = __uint_as_float(c.z), c3 = __uint_as_float(c.w);
                    const float* a = acc + 8 * j;
                    pk[4 * j] = pack_bf16(fmaf(sa.x, c0, a[0]) * sa.y, fmaf(sa.x, c1, a[1]) * sa.y);
                    pk[4 * j + 1] = pack_bf16(fmaf(sb.x, c0, a[2]) * sb.y, fmaf(sb.x, c1, a[3]) * sb.y);
                    pk[4 * j + 2] = pack_bf16(fmaf(sa.x, c2, a[4]) * sa.y, fmaf(sa.x, c3, a[5]) * sa.y);
                    pk[4 * j + 3] = pack_bf16(fmaf(sb.x, c2, a[6]) * sb.y, fmaf(sb.x, c3, a[7]) * sb.y);
                }
            } else {
#pragma unroll
                for (int i = 0; i < 64; i++) pk[i] = pack_bf16(acc[2 * i], acc[2 * i + 1]);
            }
            const int nt = t * 8 + nslot;
            gated = !tile_is_qkv(nt);
            optr = !gated ? g_qkv + (size_t)orow * NQKV + tile_index(nt) * 256 + (lane & 3) * 8
                                : g_a2 + (size_t)orow * K2 + DM + tile_index(nt) * 128 + (lane & 3) * 8;
            if (tid == 0) TRACE(16 + wg * 8 + t);
        }

        float accd[64], accs[64];
#pragma unroll
        for (int i = 0; i < 64; i++) accd[i] = 0.f;
#pragma unroll
        for (int u = 0; u < 9; u++) {
            const int q = u % G2_STAGES;
            mbar_wait(full2(q), (u / G2_STAGES) & 1);
            const uint64_t da = desc_a(stage2(q) + wg * 8192), db = desc_b(stage2(q) + A_BYTES);
            wg_fence();
#pragma unroll
            for (int kk = 0; kk < 4; kk++) wgmma_n128(accd, da + kk * 2, db + kk * 128, (u | kk) != 0);
            wg_commit();
            if (u >= 1) { chunk_geglu(u - 1); if (u == 8) signal_stores(6); }
            wg_wait<1>();
            if (u > 0) release(empty2((u - 1) % G2_STAGES));
        }
        {
            int q = 9 % G2_STAGES, qp = 8 % G2_STAGES; uint32_t ph = (9 / G2_STAGES) & 1;
#pragma unroll 1
            for (int u = 9; u < G2_DSTEPS; u++) {
                mbar_wait(full2(q), ph);
                const uint64_t da = desc_a(stage2(q) + wg * 8192), db = desc_b(stage2(q) + A_BYTES);
                wg_fence();
#pragma unroll
                for (int kk = 0; kk < 4; kk++) wgmma_n128(accd, da + kk * 2, db + kk * 128, 1);
                wg_commit();
                wg_wait<1>();
                release(empty2(qp));
                qp = q;
                if (++q == G2_STAGES) { q = 0; ph ^= 1; }
            }
        }
        if (tid == 0) TRACE(16 + wg * 8 + 5);
#pragma unroll
        for (int i = 0; i < 64; i++) accs[i] = 0.f;
        uint32_t gk[32], xr[32];
        const uint32_t xs = aux + cw * 2048;
        const uint32_t xrow = xs + ((lane & 7) + ((lane >> 3) & 1) * 8) * 128;
        auto xaddr = [&](int j) { return xrow + (j >> 2) * 16384 + (((((j & 3) * 2) + (lane >> 4)) ^ (lane & 7)) << 4); };
#pragma unroll
        for (int u = G2_DSTEPS; u < G2_KSTEPS; u++) {
            const int q = u % G2_STAGES, v = u - G2_DSTEPS;
            mbar_wait(full2(q), (u / G2_STAGES) & 1);
            if (G2_SKEW > 0 && wg == 1 && u == G2_KSTEPS - G2_SKEW) asm volatile("bar.sync 1, 256;" ::: "memory");
            const uint64_t da = desc_a(stage2(q) + wg * 8192), db = desc_b(stage2(q) + A_BYTES);
            wg_fence();
#pragma unroll
            for (int kk = 0; kk < 4; kk++) wgmma_n128(accs, da + kk * 2, db + kk * 128, (v | kk) != 0);
            wg_commit();
            if (G2_SKEW > 0 && wg == 0 && u == G2_KSTEPS - 1) asm volatile("bar.arrive 1, 256;" ::: "memory");
            if (v >= 1 && v <= 8) {
#pragma unroll
                for (int i = 4 * (v - 1); i < 4 * v; i++) {
                    const uint32_t d2 = pack_bf16(accd[2 * i], accd[2 * i + 1]);
                    gk[i] = pack_bf16(silu(bf_lo(d2)), silu(bf_hi(d2)));
                }
            }
            if (v == 9) mbar_wait(x_bar, 0);
            if (v >= 9 && v <= 12) {
#pragma unroll
                for (int j = 2 * (v - 9); j < 2 * (v - 8); j++)
                    asm volatile("ldmatrix.sync.aligned.m8n8.x4.shared.b16 {%0,%1,%2,%3}, [%4];"
                                 : "=r"(xr[4 * j]), "=r"(xr[4 * j + 1]), "=r"(xr[4 * j + 2]), "=r"(xr[4 * j + 3])
                                 : "r"(xaddr(j)) : "memory");
            }
            wg_wait<1>();
            if (v == 0) fence_regs(accd);
            if (u - 1 + G2_STAGES < G2_KSTEPS) release(empty2((u - 1) % G2_STAGES));
        }
        wg_wait<0>();
        fence_regs(accs);
        if (tid == 0) TRACE(16 + wg * 8 + 6);
#pragma unroll
        for (int j = 0; j < 8; j++) {
            uint32_t r[4];
#pragma unroll
            for (int i = 0; i < 4; i++) {
                const int e = j * 4 + i;
                r[i] = add_bf16x2(xr[e], mul_bf16x2(pack_bf16(accs[2 * e], accs[2 * e + 1]), gk[e]));
            }
            asm volatile("stmatrix.sync.aligned.m8n8.x4.shared.b16 [%0], {%1,%2,%3,%4};"
                         :: "r"(xaddr(j)), "r"(r[0]), "r"(r[1]), "r"(r[2]), "r"(r[3]) : "memory");
            if (j == 3 || j == 7) {
                asm volatile("fence.proxy.async.shared::cta;" ::: "memory");
                __syncwarp();
                if (lane == 0) {
                    tma_store_2d(&prm.out, xs + (j >> 2) * 16384, nslot * 128 + (j >> 2) * 64, mblk * 128 + cw * 16);
                    asm volatile("cp.async.bulk.commit_group;" ::: "memory");
                }
            }
        }
        if (lane == 0) asm volatile("cp.async.bulk.wait_group.read 0;" ::: "memory");
        if (tid == 0) { TRACE(16 + wg * 8 + 7); if (wg == 1) TRACE_GT(13); }
    }
}

typedef CUresult (*EncodeFn)(CUtensorMap*, CUtensorMapDataType, cuuint32_t, void*, const cuuint64_t*, const cuuint64_t*,
                             const cuuint32_t*, const cuuint32_t*, CUtensorMapInterleave, CUtensorMapSwizzle,
                             CUtensorMapL2promotion, CUtensorMapFloatOOBfill);

void encode(EncodeFn fn, CUtensorMap* m, const void* ptr, int rank, const cuuint64_t* dims, const cuuint64_t* strides,
            const cuuint32_t* box) {
    const cuuint32_t es[5] = {1, 1, 1, 1, 1};
    fn(m, CU_TENSOR_MAP_DATA_TYPE_BFLOAT16, rank, const_cast<void*>(ptr), dims, strides, box, es,
       CU_TENSOR_MAP_INTERLEAVE_NONE, CU_TENSOR_MAP_SWIZZLE_128B, CU_TENSOR_MAP_L2_PROMOTION_L2_128B,
       CU_TENSOR_MAP_FLOAT_OOB_FILL_NONE);
}
void encode_2d(EncodeFn fn, CUtensorMap* m, const void* ptr, int cols, int box_rows) {
    const cuuint64_t dims[2] = {(cuuint64_t)cols, SEQ}, strides[1] = {(cuuint64_t)cols * 2};
    const cuuint32_t box[2] = {64, (cuuint32_t)box_rows};
    encode(fn, m, ptr, 2, dims, strides, box);
}
void encode_w1(EncodeFn fn, CUtensorMap* m, const void* ptr, int cols) {
    const cuuint64_t dims[3] = {64, DM, (cuuint64_t)cols / 64}, strides[2] = {(cuuint64_t)cols * 2, 128};
    const cuuint32_t box[3] = {64, 64, 2};
    encode(fn, m, ptr, 3, dims, strides, box);
}
void encode_qk(EncodeFn fn, CUtensorMap* m, const void* ptr) {
    const cuuint64_t dims[3] = {DM, SEQ, 3}, strides[2] = {NQKV * 2, DM * 2};
    const cuuint32_t box[3] = {64, 16, 2};
    encode(fn, m, ptr, 3, dims, strides, box);
}
void encode_a2(EncodeFn fn, CUtensorMap* m, const void* ptr) {
    const cuuint64_t dims[3] = {K2, 2, SEQ / 2}, strides[2] = {(cuuint64_t)SEQ * K2, K2 * 2};
    const cuuint32_t box[3] = {64, 2, 64};
    encode(fn, m, ptr, 3, dims, strides, box);
}
void encode_w2(EncodeFn fn, CUtensorMap* m, const void* ptr, int rows) {
    const cuuint64_t rb = DM * 2;
    const cuuint64_t dims[5] = {DM, 2, 4, 4, (cuuint64_t)rows / 32}, strides[4] = {rb, 8 * rb, 2 * rb, 32 * rb};
    const cuuint32_t box[5] = {64, 2, 4, 4, 2};
    encode(fn, m, ptr, 5, dims, strides, box);
}

}

extern "C" void kernel_launch(void* const* d_in, const int* in_sizes, int n_in, void* d_out, int out_size) {
    (void)in_sizes; (void)n_in; (void)out_size;
    static EncodeFn fn = nullptr;
    static void *p_xn = nullptr, *p_qkv = nullptr, *p_a2 = nullptr;
    if (!fn) {
        cudaDriverEntryPointQueryResult st;
        cudaGetDriverEntryPoint("cuTensorMapEncodeTiled", (void**)&fn, cudaEnableDefault, &st);
        cudaGetSymbolAddress(&p_xn, g_xn);
        cudaGetSymbolAddress(&p_qkv, g_qkv);
        cudaGetSymbolAddress(&p_a2, g_a2);
        cudaFuncSetAttribute(fused_kernel, cudaFuncAttributeMaxDynamicSharedMemorySize, SMEM_BYTES);
    }
    Params prm;
    encode_2d(fn, &prm.x, d_in[0], DM, 128);
    encode_2d(fn, &prm.xn, p_xn, DM, 128);
    encode_w1(fn, &prm.wqkv, d_in[1], NQKV);
    encode_w1(fn, &prm.wg, d_in[4], DF);
    encode_w1(fn, &prm.wu, d_in[5], DF);
    encode_qk(fn, &prm.qk, p_qkv);
    encode_2d(fn, &prm.v, p_qkv, NQKV, 16);
    encode_2d(fn, &prm.o, p_a2, K2, 16);
    encode_a2(fn, &prm.a2, p_a2);
    encode_w2(fn, &prm.wo, d_in[2], DM);
    encode_w2(fn, &prm.wd, d_in[6], DF);
    encode_2d(fn, &prm.out, d_out, DM, 16);
    prm.px = (const __nv_bfloat16*)d_in[0];
    prm.zero = 0;
    fused_kernel<<<NCTA, 384, SMEM_BYTES>>>(prm);
}
```

```cpp
#include <cuda_runtime.h>
#include <cuda_bf16.h>
#include <cuda.h>
#include <stdint.h>
#include <type_traits>

#define P_W1 1
#define P_X 1
#define P_XN4 1
#define P_W2 1
#define P_A2 1
#define P_QKV 1

namespace {

constexpr int SEQ = 2048, DM = 1024, DF = 3584, K2 = DM + DF, NQKV = 3 * DM;
constexpr int NGEMM = 128, NCTA = 132;
constexpr int G1_STAGES = 4, G1_STAGE_BYTES = 49152, G1_KSTEPS = 16, G1_TILES = 5;
constexpr int G2_STAGES = 6, G2_STAGE_BYTES = 32768, G2_KSTEPS = 72, G2_LATE = 40, G2_DSTEPS = 56, G2_LAST = 68;
constexpr int A_BYTES = 16384;
constexpr int AUX_OFF = G1_STAGES * G1_STAGE_BYTES;
constexpr int BAR_OFF = AUX_OFF + 32768;
constexpr int SMEM_BYTES = BAR_OFF + 2560;
constexpr int G1_SKEW = 2, G2_SKEW = 2;
constexpr int CONSUMER_REGS = 224, AUX_REGS = 56;
constexpr int ATT_SLOT = 8192;

enum { F_LN = 0, F_QKV = 1, F_EARLY = 2, F_LATE = 3, F_O = 4, F_CS = 5 };
constexpr unsigned CNT_LN = 8, CNT_QKV = 32, CNT_EARLY = 20, CNT_LATE = 8, CNT_O = 48, CNT_CS = 16;

__device__ __align__(1024) __nv_bfloat16 g_xn[SEQ * DM];
__device__ __align__(1024) __nv_bfloat16 g_qkv[SEQ * NQKV];
__device__ __align__(1024) __nv_bfloat16 g_a2[SEQ * K2];
__device__ __align__(128) float2 g_stats[SEQ];
__device__ __align__(128) float g_colsum[16 * 2048];
__device__ __align__(128) unsigned g_flags[6 * 16 * 32];
__device__ __align__(128) unsigned g_epoch[NCTA * 16];

#define TRACE_T 2
#define TRACE(slot) do {} while (0)
#define TRACE_GT(slot) do {} while (0)

__device__ __forceinline__ uint32_t smem_u32(const void* p) { return (uint32_t)__cvta_generic_to_shared(p); }
__device__ __forceinline__ void mbar_init(uint32_t bar, uint32_t cnt) {
    asm volatile("mbarrier.init.shared::cta.b64 [%0], %1;" :: "r"(bar), "r"(cnt) : "memory");
}
__device__ __forceinline__ void mbar_expect_tx(uint32_t bar, uint32_t bytes) {
    asm volatile("mbarrier.arrive.expect_tx.shared::cta.b64 _, [%0], %1;" :: "r"(bar), "r"(bytes) : "memory");
}
__device__ __forceinline__ void mbar_arrive(uint32_t bar) {
    asm volatile("mbarrier.arrive.shared::cta.b64 _, [%0];" :: "r"(bar) : "memory");
}
__device__ __forceinline__ void mbar_arrive_cluster(uint32_t bar, uint32_t cta) {
    asm volatile("{\n.reg .b32 ra;\nmapa.shared::cluster.u32 ra, %0, %1;\nmbarrier.arrive.shared::cluster.b64 _, [ra];\n}"
                 :: "r"(bar), "r"(cta) : "memory");
}
__device__ __forceinline__ bool mbar_try_wait(uint32_t bar, uint32_t parity) {
    uint32_t ok;
    asm volatile("{\n.reg .pred p;\nmbarrier.try_wait.parity.shared::cta.b64 p, [%1], %2;\nselp.u32 %0, 1, 0, p;\n}"
                 : "=r"(ok) : "r"(bar), "r"(parity) : "memory");
    return ok;
}
__device__ __forceinline__ void mbar_wait(uint32_t bar, uint32_t parity) {
#pragma unroll 1
    for (int spins = 0; !mbar_try_wait(bar, parity) && spins < (1 << 17); spins++) {}
}
template <bool WARP = false> __device__ __forceinline__ void flag_wait(const unsigned* p, unsigned target) {
#pragma unroll 1
    for (int spins = 0; spins < (1 << 19); spins++) {
        unsigned v;
        asm volatile("ld.acquire.gpu.global.u32 %0, [%1];" : "=r"(v) : "l"(p) : "memory");
        if (WARP ? __all_sync(0xffffffffu, (int)(v - target) >= 0) : (int)(v - target) >= 0) break;
        __nanosleep(64);
    }
}
__device__ __forceinline__ void flag_add(unsigned* p) {
    asm volatile("red.release.gpu.global.add.u32 [%0], 1;" :: "l"(p) : "memory");
}
__device__ __forceinline__ bool elect_one() {
    uint32_t ok;
    asm volatile("{\n.reg .pred p;\nelect.sync _|p, 0xffffffff;\nselp.u32 %0, 1, 0, p;\n}" : "=r"(ok));
    return ok;
}
__device__ __forceinline__ void fence_proxy_async() { asm volatile("fence.proxy.async;" ::: "memory"); }
__device__ __forceinline__ uint4 lds128(uint32_t addr) {
    uint4 v;
    asm volatile("ld.shared.v4.u32 {%0,%1,%2,%3}, [%4];" : "=r"(v.x), "=r"(v.y), "=r"(v.z), "=r"(v.w) : "r"(addr) : "memory");
    return v;
}
__device__ __forceinline__ float2 lds64f(uint32_t addr) {
    float2 v;
    asm volatile("ld.shared.v2.f32 {%0,%1}, [%2];" : "=f"(v.x), "=f"(v.y) : "r"(addr) : "memory");
    return v;
}
__device__ __forceinline__ void sts128(uint32_t addr, uint4 v) {
    asm volatile("st.shared.v4.u32 [%0], {%1,%2,%3,%4};" :: "r"(addr), "r"(v.x), "r"(v.y), "r"(v.z), "r"(v.w) : "memory");
}
__device__ __forceinline__ void sts64f(uint32_t addr, float a, float b) {
    asm volatile("st.shared.v2.f32 [%0], {%1,%2};" :: "r"(addr), "f"(a), "f"(b) : "memory");
}

__device__ __forceinline__ uint64_t policy(bool stream) {
    uint64_t p;
    if (stream) asm("createpolicy.fractional.L2::evict_first.b64 %0, 1.0;" : "=l"(p));
    else asm("createpolicy.fractional.L2::evict_normal.b64 %0, 1.0;" : "=l"(p));
    return p;
}
__device__ __forceinline__ void tma_2d(uint32_t dst, const CUtensorMap* m, uint32_t bar, int c0, int c1, uint64_t pol) {
    asm volatile("cp.async.bulk.tensor.2d.shared::cluster.global.mbarrier::complete_tx::bytes.L2::cache_hint"
                 " [%0], [%1, {%3, %4}], [%2], %5;"
                 :: "r"(dst), "l"(m), "r"(bar), "r"(c0), "r"(c1), "l"(pol) : "memory");
}
__device__ __forceinline__ void tma_3d(uint32_t dst, const CUtensorMap* m, uint32_t bar, int c0, int c1, int c2, uint64_t pol) {
    asm volatile("cp.async.bulk.tensor.3d.shared::cluster.global.mbarrier::complete_tx::bytes.L2::cache_hint"
                 " [%0], [%1, {%3, %4, %5}], [%2], %6;"
                 :: "r"(dst), "l"(m), "r"(bar), "r"(c0), "r"(c1), "r"(c2), "l"(pol) : "memory");
}
__device__ __forceinline__ void tma_3d_mc(uint32_t dst, const CUtensorMap* m, uint32_t bar, int c1, int c2, uint64_t pol) {
    asm volatile("cp.async.bulk.tensor.3d.shared::cluster.global.mbarrier::complete_tx::bytes.multicast::cluster.L2::cache_hint"
                 " [%0], [%1, {%3, %4, %5}], [%2], %6, %7;"
                 :: "r"(dst), "l"(m), "r"(bar), "r"(0), "r"(c1), "r"(c2), "h"((uint16_t)3), "l"(pol) : "memory");
}
__device__ __forceinline__ void tma_5d_mc(uint32_t dst, const CUtensorMap* m, uint32_t bar, int c0, int c4, uint64_t pol) {
    asm volatile("cp.async.bulk.tensor.5d.shared::cluster.global.mbarrier::complete_tx::bytes.multicast::cluster.L2::cache_hint"
                 " [%0], [%1, {%3, %4, %4, %4, %5}], [%2], %6, %7;"
                 :: "r"(dst), "l"(m), "r"(bar), "r"(c0), "r"(0), "r"(c4), "h"((uint16_t)3), "l"(pol) : "memory");
}
__device__ __forceinline__ void tma_store_2d(const CUtensorMap* m, uint32_t src, int c0, int c1) {
    asm volatile("cp.async.bulk.tensor.2d.global.shared::cta.bulk_group [%0, {%2, %3}], [%1];"
                 :: "l"(m), "r"(src), "r"(c0), "r"(c1) : "memory");
}
__device__ __forceinline__ uint4 ldg_stream(const void* p, uint64_t pol) {
    uint4 v;
    asm volatile("ld.global.nc.L1::no_allocate.L2::cache_hint.v4.u32 {%0,%1,%2,%3}, [%4], %5;"
                 : "=r"(v.x), "=r"(v.y), "=r"(v.z), "=r"(v.w) : "l"(p), "l"(pol));
    return v;
}
__device__ __forceinline__ void bulk_load(uint32_t dst, const void* src, uint32_t bytes, uint32_t bar) {
    asm volatile("cp.async.bulk.shared::cluster.global.mbarrier::complete_tx::bytes [%0], [%1], %2, [%3];"
                 :: "r"(dst), "l"(src), "r"(bytes), "r"(bar) : "memory");
}
__device__ __forceinline__ void prefetch_3d(const CUtensorMap* m, int c1, int c2, uint64_t pol) {
    asm volatile("cp.async.bulk.prefetch.tensor.3d.L2.global.L2::cache_hint [%0, {%1, %2, %3}], %4;"
                 :: "l"(m), "r"(0), "r"(c1), "r"(c2), "l"(pol) : "memory");
}
__device__ __forceinline__ void prefetch_map(const CUtensorMap* m) {
    asm volatile("prefetch.tensormap [%0];" :: "l"(m) : "memory");
}
__device__ __forceinline__ void wg_fence() { asm volatile("wgmma.fence.sync.aligned;" ::: "memory"); }
__device__ __forceinline__ void wg_commit() { asm volatile("wgmma.commit_group.sync.aligned;" ::: "memory"); }
template <int N> __device__ __forceinline__ void wg_wait() { asm volatile("wgmma.wait_group.sync.aligned %0;" :: "n"(N) : "memory"); }

__device__ __forceinline__ uint64_t desc_a(uint32_t addr) {
    return (uint64_t)((addr & 0x3FFFF) >> 4) | (1ull << 16) | (64ull << 32) | (1ull << 62);
}
__device__ __forceinline__ uint64_t desc_b(uint32_t addr) {
    return (uint64_t)((addr & 0x3FFFF) >> 4) | (512ull << 16) | (64ull << 32) | (1ull << 62);
}

#define R8(d, o) "+f"(d[o]), "+f"(d[o+1]), "+f"(d[o+2]), "+f"(d[o+3]), "+f"(d[o+4]), "+f"(d[o+5]), "+f"(d[o+6]), "+f"(d[o+7])
#define R32(d, o) R8(d, o), R8(d, o+8), R8(d, o+16), R8(d, o+24)
#define R64(d, o) R32(d, o), R32(d, o+32)

__device__ __forceinline__ void wgmma_n256(float (&d)[128], uint64_t da, uint64_t db, int scale_d) {
    asm volatile("{\n.reg .pred p;\nsetp.ne.b32 p, %130, 0;\n"
        "wgmma.mma_async.sync.aligned.m64n256k16.f32.bf16.bf16 "
        "{%0,%1,%2,%3,%4,%5,%6,%7,%8,%9,%10,%11,%12,%13,%14,%15,%16,%17,%18,%19,%20,%21,%22,%23,%24,%25,%26,%27,%28,%29,%30,%31,"
        "%32,%33,%34,%35,%36,%37,%38,%39,%40,%41,%42,%43,%44,%45,%46,%47,%48,%49,%50,%51,%52,%53,%54,%55,%56,%57,%58,%59,%60,%61,%62,%63,"
        "%64,%65,%66,%67,%68,%69,%70,%71,%72,%73,%74,%75,%76,%77,%78,%79,%80,%81,%82,%83,%84,%85,%86,%87,%88,%89,%90,%91,%92,%93,%94,%95,"
        "%96,%97,%98,%99,%100,%101,%102,%103,%104,%105,%106,%107,%108,%109,%110,%111,%112,%113,%114,%115,%116,%117,%118,%119,%120,%121,%122,%123,%124,%125,%126,%127},"
        " %128, %129, p, 1, 1, 0, 1;\n}"
        : R64(d, 0), R64(d, 64) : "l"(da), "l"(db), "r"(scale_d));
}
__device__ __forceinline__ void wgmma_n128(float (&d)[64], uint64_t da, uint64_t db, int scale_d) {
    asm volatile("{\n.reg .pred p;\nsetp.ne.b32 p, %66, 0;\n"
        "wgmma.mma_async.sync.aligned.m64n128k16.f32.bf16.bf16 "
        "{%0,%1,%2,%3,%4,%5,%6,%7,%8,%9,%10,%11,%12,%13,%14,%15,%16,%17,%18,%19,%20,%21,%22,%23,%24,%25,%26,%27,%28,%29,%30,%31,"
        "%32,%33,%34,%35,%36,%37,%38,%39,%40,%41,%42,%43,%44,%45,%46,%47,%48,%49,%50,%51,%52,%53,%54,%55,%56,%57,%58,%59,%60,%61,%62,%63},"
        " %64, %65, p, 1, 1, 0, 1;\n}"
        : R64(d, 0) : "l"(da), "l"(db), "r"(scale_d));
}

__device__ __forceinline__ uint32_t pack_bf16(float lo, float hi) {
    uint32_t r; asm("cvt.rn.bf16x2.f32 %0, %1, %2;" : "=r"(r) : "f"(hi), "f"(lo)); return r;
}
__device__ __forceinline__ float bf_lo(uint32_t v) { return __uint_as_float(v << 16); }
__device__ __forceinline__ float bf_hi(uint32_t v) { return __uint_as_float(v & 0xffff0000u); }
__device__ __forceinline__ float round_bf16(float v) { return bf_lo(pack_bf16(v, 0.f)); }
__device__ __forceinline__ uint32_t mul_bf16x2(uint32_t a, uint32_t b) {
    uint32_t r; asm("mul.rn.bf16x2 %0, %1, %2;" : "=r"(r) : "r"(a), "r"(b)); return r;
}
__device__ __forceinline__ uint32_t add_bf16x2(uint32_t a, uint32_t b) {
    uint32_t r; asm("add.rn.bf16x2 %0, %1, %2;" : "=r"(r) : "r"(a), "r"(b)); return r;
}
__device__ __forceinline__ uint32_t sub_bf16x2(uint32_t a, uint32_t b) {
    uint32_t r; asm("sub.rn.bf16x2 %0, %1, %2;" : "=r"(r) : "r"(a), "r"(b)); return r;
}
__device__ __forceinline__ float tanh_fast(float x) { float r; asm("tanh.approx.f32 %0, %1;" : "=f"(r) : "f"(x)); return r; }
__device__ __forceinline__ float gelu_tanh(float g) {
    float t = fmaf(g * g, 0.044715f * 0.7978845608f, 0.7978845608f) * g;
    float hg = 0.5f * g;
    return fmaf(hg, tanh_fast(t), hg);
}
__device__ __forceinline__ uint32_t geglu2(uint32_t g2, uint32_t u2) {
    return mul_bf16x2(pack_bf16(gelu_tanh(bf_lo(g2)), gelu_tanh(bf_hi(g2))), u2);
}
__device__ __forceinline__ float silu(float d) {
    float hd = 0.5f * d;
    return fmaf(hd, tanh_fast(hd), hd);
}
__device__ __forceinline__ float ex2_fast(float x) { float r; asm("ex2.approx.ftz.f32 %0, %1;" : "=f"(r) : "f"(x)); return r; }
__device__ __forceinline__ void unpack8(uint4 v, float (&f)[8]) {
    f[0] = bf_lo(v.x); f[1] = bf_hi(v.x); f[2] = bf_lo(v.y); f[3] = bf_hi(v.y);
    f[4] = bf_lo(v.z); f[5] = bf_hi(v.z); f[6] = bf_lo(v.w); f[7] = bf_hi(v.w);
}
template <int N> __device__ __forceinline__ void fence_regs(float (&d)[N]) {
#pragma unroll
    for (int i = 0; i < N; i++) asm volatile("" : "+f"(d[i]) :: "memory");
}

__device__ __forceinline__ float rcp_fast(float x) { float r; asm("rcp.approx.ftz.f32 %0, %1;" : "=f"(r) : "f"(x)); return r; }
__device__ __forceinline__ uint32_t max_bf16x2(uint32_t a, uint32_t b) {
    uint32_t r; asm("max.bf16x2 %0, %1, %2;" : "=r"(r) : "r"(a), "r"(b)); return r;
}
__device__ __forceinline__ uint4 ldsm4(uint32_t addr) {
    uint4 v;
    asm volatile("ldmatrix.sync.aligned.m8n8.x4.shared.b16 {%0,%1,%2,%3}, [%4];"
                 : "=r"(v.x), "=r"(v.y), "=r"(v.z), "=r"(v.w) : "r"(addr) : "memory");
    return v;
}
__device__ __forceinline__ uint4 ldsm4_t(uint32_t addr) {
    uint4 v;
    asm volatile("ldmatrix.sync.aligned.m8n8.x4.trans.shared.b16 {%0,%1,%2,%3}, [%4];"
                 : "=r"(v.x), "=r"(v.y), "=r"(v.z), "=r"(v.w) : "r"(addr) : "memory");
    return v;
}
__device__ __forceinline__ void mma_16816(float (&c)[4], uint32_t a0, uint32_t a1, uint32_t a2, uint32_t a3, uint32_t b0, uint32_t b1) {
    asm("mma.sync.aligned.m16n8k16.row.col.f32.bf16.bf16.f32 {%0,%1,%2,%3}, {%4,%5,%6,%7}, {%8,%9}, {%0,%1,%2,%3};"
        : "+f"(c[0]), "+f"(c[1]), "+f"(c[2]), "+f"(c[3]) : "r"(a0), "r"(a1), "r"(a2), "r"(a3), "r"(b0), "r"(b1));
}
__device__ __forceinline__ void mma_1688(float (&c)[4], uint32_t a0, uint32_t a1, uint32_t b0) {
    asm("mma.sync.aligned.m16n8k8.row.col.f32.bf16.bf16.f32 {%0,%1,%2,%3}, {%4,%5}, {%6}, {%0,%1,%2,%3};"
        : "+f"(c[0]), "+f"(c[1]), "+f"(c[2]), "+f"(c[3]) : "r"(a0), "r"(a1), "r"(b0));
}
__device__ __forceinline__ void qk_tile(float (&c)[4], const uint4& q0, const uint4& q1, const uint4& k, float init) {
    c[0] = c[1] = c[2] = c[3] = init;
    mma_16816(c, q0.x, q0.y, q0.z, q0.w, k.x, k.y);
    mma_16816(c, q1.x, q1.y, q1.z, q1.w, k.z, k.w);
}
__device__ __forceinline__ uint32_t scaled_logits(bool first, float a0, float a1, float b0, float b1) {
    uint32_t p, r;
    asm("{\n.reg .pred p;\nsetp.ne.u32 p, %1, 0;\n@p cvt.rn.bf16x2.f32 %0, %3, %2;\n@!p cvt.rn.bf16x2.f32 %0, %5, %4;\n}"
        : "=r"(p) : "r"((uint32_t)first), "f"(a0), "f"(a1), "f"(b0), "f"(b1));
    asm("fma.rn.bf16x2 %0, %1, %2, %3;" : "=r"(r) : "r"(p), "r"(0x3e353e35u), "r"(mul_bf16x2(p, 0x379e379eu)));
    return r;
}
template <typename T> __device__ __forceinline__ T uniform(T v) { return __shfl_sync(0xffffffffu, v, 0); }

__device__ __forceinline__ void attention(const CUtensorMap* maps, uint32_t base, uint32_t zero, int grp, int warp, int lane) {
    constexpr float LOG2E = 1.4426950408889634f;
    const int g = lane >> 2, t = lane & 3;
    const bool up0 = 2 * t > g, up1 = 2 * t + 1 > g;
    const uint32_t keep = (up0 ? 0x0000ffffu : 0u) | (up1 ? 0xffff0000u : 0u);
    const uint32_t buf = base + warp * 2 * ATT_SLOT, bar = base + AUX_OFF + warp * 16;
    const uint32_t qoff = (lane & 15) * 128 + (((lane >> 4) ^ (lane & 7)) << 4);
    const uint32_t koff = 2048 + (lane & 7) * 128 + (((lane >> 3) ^ (lane & 7)) << 4);
    const uint32_t rest_bar = base + AUX_OFF + 192;
    const int col = uniform(grp * 256), first = uniform((warp / 3 * 32 + warp % 3 * 11) * 16);
    const CUtensorMap* const mqk = reinterpret_cast<const CUtensorMap*>(uniform(reinterpret_cast<uint64_t>(maps)));
    const CUtensorMap *const mv = mqk + 1, *const mo = mqk + 2;
    const uint64_t pol = policy(P_QKV);
    uint4 kp[2], vp[2];
    uint32_t l0[2], l1[2], m[2];
    float s[2][3][4];
    auto scores = [&](uint32_t st, int row) {
        const float before = (row & 1023) == 0 ? -5.656854e9f : 0.f;
#pragma unroll
        for (int h = 0; h < 2; h++) {
            const uint4 q0 = ldsm4(st + (qoff ^ (h * 64))), q1 = ldsm4(st + (qoff ^ (h * 64 + 32)));
            const uint4 k0 = ldsm4(st + (koff ^ (h * 64))), k1 = ldsm4(st + 1024 + (koff ^ (h * 64)));
            qk_tile(s[h][0], q0, q1, kp[h], before);
            qk_tile(s[h][1], q0, q1, k0, 0.f);
            qk_tile(s[h][2], q0, q1, k1, 0.f);
            kp[h] = k1;
        }
    };
    auto logits = [&]() {
#pragma unroll
        for (int h = 0; h < 2; h++) {
            l0[h] = scaled_logits(up0, s[h][0][0], s[h][1][2], s[h][1][0], s[h][2][2]);
            l1[h] = scaled_logits(up1, s[h][0][1], s[h][1][3], s[h][1][1], s[h][2][3]);
            m[h] = max_bf16x2(l0[h], l1[h]);
            m[h] = max_bf16x2(m[h], __shfl_xor_sync(0xffffffffu, m[h], 1));
        }
    };
    auto row_max = [&]() {
#pragma unroll
        for (int h = 0; h < 2; h++) m[h] = max_bf16x2(m[h], __shfl_xor_sync(0xffffffffu, m[h], 2));
    };
    auto next = [](uint32_t p) {
        return (0x80200400u >> (p >> 4 & 31) & 1) > (p >> 15 & 1) ? p + (64 << 16) + 0x8000 : (p + 16) & ~0x8800u;
    };
    auto exchange = [&](uint32_t st, uint32_t b, uint32_t po, uint32_t pv, uint32_t pq) {
        asm volatile("{\n.reg .pred e, p, q;\n"
            "fence.proxy.async.shared::cta;\n"
            "bar.warp.sync 0xffffffff;\n"
            "elect.sync _|e, 0xffffffff;\n"
            "setp.eq.and.b32 p, %12, 0, e;\n"
            "setp.lt.and.s32 q, %8, %13, e;\n"
            "@q mbarrier.arrive.expect_tx.shared::cta.b64 _, [%2], 6144;\n"
            "@q cp.async.bulk.tensor.3d.shared::cluster.global.mbarrier::complete_tx::bytes.L2::cache_hint [%0], [%3, {%6, %7, %14}], [%2], %15;\n"
            "@q cp.async.bulk.tensor.2d.shared::cluster.global.mbarrier::complete_tx::bytes.L2::cache_hint [%0 + 4096], [%4, {%8, %9}], [%2], %15;\n"
            "@e cp.async.bulk.wait_group.read 0;\n"
            "@p cp.async.bulk.tensor.2d.global.shared::cta.bulk_group [%5, {%10, %11}], [%1 + 6144];\n"
            "@e cp.async.bulk.commit_group;\n"
            "bar.warp.sync 0xffffffff;\n}"
            :: "r"(st), "r"(st ^ ATT_SLOT), "r"(b), "l"(mqk), "l"(mv), "l"(mo), "r"(pq >> 16), "r"(pq & 2047),
               "r"((pv >> 16) + 2 * DM), "r"(pv & 2047), "r"(po >> 16), "r"(po & 2047), "r"(po & 0x8000),
               "r"(col + 256 + 2 * DM), "r"(0), "l"(pol) : "memory");
    };
    auto publish = [](auto pending, unsigned* flag) {
        asm volatile("{\n.reg .pred e;\n"
            "elect.sync _|e, 0xffffffff;\n"
            "cp.async.bulk.wait_group %1;\n"
            "fence.proxy.async;\n"
            "fence.acq_rel.gpu;\n"
            "@e red.relaxed.gpu.global.add.u32 [%0], 1;\n}" :: "l"(flag), "n"(pending.value) : "memory");
    };
    const unsigned epoch = __ldcg(g_epoch + blockIdx.x * 16) + 1;
    if (elect_one()) {
        mbar_init(bar, 1); mbar_init(bar + 8, 1);
        if (warp == 2) mbar_init(rest_bar, 32);
        prefetch_map(mqk); prefetch_map(mv); prefetch_map(mo);
    }
    __syncthreads();
    if (elect_one()) {
        g_epoch[blockIdx.x * 16] = epoch;
        flag_wait(g_flags + F_QKV * 512 + grp * 32, epoch * CNT_QKV);
        fence_proxy_async();
        mbar_expect_tx(bar + 8, 8192);
        tma_3d(buf + ATT_SLOT, mqk, bar + 8, col, first, 0, pol);
        tma_2d(buf + ATT_SLOT + 4096, mv, bar + 8, col + 2 * DM, first - 16, policy(false));
        tma_2d(buf + ATT_SLOT + 6144, mv, bar + 8, col + DM, first - 16, policy(false));
        mbar_expect_tx(bar, 6144);
        tma_3d(buf, mqk, bar, col, first + 16, 0, pol);
        tma_2d(buf + 4096, mv, bar, col + 2 * DM, first, pol);
        if (warp == 0) TRACE(9);
    }
    __syncwarp();
    mbar_wait(bar + 8, 0);
#pragma unroll
    for (int h = 0; h < 2; h++) {
        kp[h] = ldsm4(buf + ATT_SLOT + 5120 + (koff ^ (h * 64)));
        vp[h] = ldsm4_t(buf + ATT_SLOT + 3072 + (koff ^ (h * 64)));
    }
    scores(buf + ATT_SLOT, first);
    uint32_t pm = 0x8000, p0 = col << 16 | first, p1 = p0 + 16, p2 = p0 + 32, p3 = p0 + 48;
    exchange(buf + ATT_SLOT, bar + 8, pm, p1, p2);
    logits();
    row_max();
    uint32_t st = buf, b = bar, cnt = 1;
    const uint32_t relay = warp == 2 ? 6 : 0;
    bool ready = mbar_try_wait(b, 0);
#pragma unroll 1
    while (p0 >> 16 < col + 256) {
        uint32_t pa[2], pb[2];
        if (!ready) mbar_wait(b, (cnt >> 1) & 1);
        uint4 v[2][2];
#pragma unroll
        for (int h = 0; h < 2; h++) {
            const float ma = -LOG2E * bf_lo(m[h]), mb = -LOG2E * bf_hi(m[h]);
            const float a0 = ex2_fast(fmaf(bf_lo(l0[h]), LOG2E, ma)), a1 = ex2_fast(fmaf(bf_lo(l1[h]), LOG2E, ma));
            const float b0 = ex2_fast(fmaf(bf_hi(l0[h]), LOG2E, mb)), b1 = ex2_fast(fmaf(bf_hi(l1[h]), LOG2E, mb));
            float sum[4] = {0.f, 0.f, 0.f, 0.f};
            mma_1688(sum, pack_bf16(a0, a1), pack_bf16(b0, b1), 0x3f803f80u);
            const float ra = rcp_fast(sum[0]), rb = rcp_fast(sum[2]);
            pa[h] = pack_bf16(a0 * ra, a1 * ra);
            pb[h] = pack_bf16(b0 * rb, b1 * rb);
        }
        scores(st, p1);
#pragma unroll
        for (int h = 0; h < 2; h++) {
            v[h][0] = ldsm4_t(st + 4096 + (qoff ^ (h * 64)));
            v[h][1] = ldsm4_t(st + 4096 + (qoff ^ (h * 64 + 32)));
        }
        if (cnt == relay) {
            flag_wait<true>(g_flags + F_QKV * 512 + 128 + grp * 32, epoch * CNT_QKV);
            fence_proxy_async();
            mbar_arrive(rest_bar);
        }
        if (cnt == 8) {
#pragma unroll 1
            for (int spins = 0; !__all_sync(0xffffffffu, mbar_try_wait(rest_bar, 0)) && spins < (1 << 17); spins++) {}
        }
        if (cnt == 37) publish(std::integral_constant<int, 1>(), g_flags + F_O * 512);
        exchange(st, b, pm, p2, p3);
        pm = p0; p0 = p1; p1 = p2; p2 = p3; p3 = next(p3);
        logits();
        float o[2][4][4];
#pragma unroll
        for (int h = 0; h < 2; h++) {
            const uint32_t prev[4] = {vp[h].x, vp[h].y, vp[h].z, vp[h].w};
            const uint32_t own[8] = {v[h][0].x, v[h][0].y, v[h][0].z, v[h][0].w, v[h][1].x, v[h][1].y, v[h][1].z, v[h][1].w};
            const uint32_t a0 = pa[h] & keep, a1 = pa[h] & ~keep, a2 = pb[h] & keep, a3 = pb[h] & ~keep;
            const uint32_t z0 = pa[h] & zero, z1 = pb[h] & zero;
#pragma unroll
            for (int j = 0; j < 4; j++) {
                o[h][j][0] = o[h][j][1] = o[h][j][2] = o[h][j][3] = 0.f;
                mma_1688(o[h][j], a0, z0, prev[j]);
                mma_16816(o[h][j], a1, a2, z1, a3, own[2 * j], own[2 * j + 1]);
            }
            vp[h] = make_uint4(own[1], own[3], own[5], own[7]);
        }
        row_max();
        b ^= 8; cnt++;
        ready = mbar_try_wait(b, (cnt >> 1) & 1);
#pragma unroll
        for (int h = 0; h < 2; h++) {
#pragma unroll
            for (int d = 0; d < 2; d++)
                asm volatile("stmatrix.sync.aligned.m8n8.x4.shared.b16 [%0], {%1,%2,%3,%4};"
                             :: "r"(st + 6144 + (qoff ^ (h * 64 + d * 32))),
                                "r"(pack_bf16(o[h][2 * d][0], o[h][2 * d][1])), "r"(pack_bf16(o[h][2 * d][2], o[h][2 * d][3])),
                                "r"(pack_bf16(o[h][2 * d + 1][0], o[h][2 * d + 1][1])),
                                "r"(pack_bf16(o[h][2 * d + 1][2], o[h][2 * d + 1][3])) : "memory");
        }
        st ^= ATT_SLOT;
    }
    exchange(st, b, pm, p0, p0);
    publish(std::integral_constant<int, 0>(), g_flags + F_O * 512 + 32);
    if (threadIdx.x == 0) TRACE(10);
}

__device__ __forceinline__ void warp_sum2(float& a, float& b) {
#pragma unroll
    for (int o = 16; o > 0; o >>= 1) {
        a += __shfl_xor_sync(0xffffffffu, a, o);
        b += __shfl_xor_sync(0xffffffffu, b, o);
    }
}
__device__ __forceinline__ float row_sum(const uint32_t* w) {
    float a = 0.f, b = 0.f;
#pragma unroll
    for (int i = 0; i < 16; i++) { a += bf_lo(w[i]); b += bf_hi(w[i]); }
    return a + b;
}
__device__ __forceinline__ float row_sq(const uint32_t* w, float mean) {
    float a = 0.f, b = 0.f;
#pragma unroll
    for (int i = 0; i < 16; i++) {
        const float lo = bf_lo(w[i]) - mean, hi = bf_hi(w[i]) - mean;
        a = fmaf(lo, lo, a); b = fmaf(hi, hi, b);
    }
    return a + b;
}
__device__ __forceinline__ float row_inv(float sq) {
    return 1.f / round_bf16(sqrtf(round_bf16(round_bf16(sq * (1.f / DM)) + 1e-5f)));
}
__device__ __forceinline__ void row_store(const uint32_t* w, float mean, float inv, int row, int lane) {
    const uint32_t m2 = pack_bf16(mean, mean);
    __nv_bfloat16* dst = g_xn + (size_t)row * DM + lane * 8;
#pragma unroll
    for (int i = 0; i < 4; i++) {
        uint32_t o[4];
#pragma unroll
        for (int j = 0; j < 4; j++) {
            const uint32_t c = sub_bf16x2(w[i * 4 + j], m2);
            o[j] = pack_bf16(bf_lo(c) * inv, bf_hi(c) * inv);
        }
        *reinterpret_cast<uint4*>(dst + i * 256) = make_uint4(o[0], o[1], o[2], o[3]);
    }
    if (lane == 0) g_stats[row] = make_float2(-bf_lo(m2), inv);
}

struct Params {
    CUtensorMap x, xn, wqkv, wg, wu, qk, v, o, a2, wo, wd, out;
    const __nv_bfloat16* px;
    uint32_t zero;
};

__device__ __forceinline__ bool tile_is_qkv(int nt) { return nt < 4 || (nt >= 8 && nt < 16); }
__device__ __forceinline__ int tile_index(int nt) { return nt < 4 ? nt + 8 : (nt < 8 ? nt - 4 : (nt < 16 ? nt - 8 : nt - 12)); }

__global__ void __cluster_dims__(2, 1, 1) __launch_bounds__(384, 1)
fused_kernel(const __grid_constant__ Params prm) {
    extern __shared__ __align__(1024) uint8_t smem_raw[];
    const uint32_t base = smem_u32(smem_raw) & ~1023u;
    const uint32_t bars = base + BAR_OFF;
    auto full1 = [&](int s) { return bars + s * 8; };
    auto empty1 = [&](int s) { return bars + 32 + s * 8; };
    auto full2 = [&](int s) { return bars + 64 + s * 8; };
    auto empty2 = [&](int s) { return bars + 128 + s * 8; };
    const uint32_t sig_bar = bars + 192, dep_bar = bars + 256, cs_bar = bars + 304, fold_bar = bars + 320, x_bar = bars + 328;
    const uint32_t colsum = bars + 512, stats = bars + 1536;
    auto stage2 = [&](int q) { return base + q * G2_STAGE_BYTES; };
    const uint32_t aux = base + AUX_OFF;

    const int warp = __shfl_sync(0xffffffffu, threadIdx.x >> 5, 0);
    const int lane = threadIdx.x & 31;
    const int rank = blockIdx.x & 1;
    const int mblk = ((blockIdx.x >> 1) & 7) * 2 + rank;
    const int nslot = blockIdx.x >> 4;

    if (blockIdx.x >= NGEMM) {
        if (threadIdx.x == 0) { TRACE_GT(0); TRACE(1); }
        attention(&prm.qk, (base + 2 * ATT_SLOT - 1) & ~(2u * ATT_SLOT - 1), prm.zero, blockIdx.x - NGEMM, warp, lane);
    } else if (warp >= 8) {
        unsigned* const flags = g_flags + mblk * 32;
        const CUtensorMap* const w0 = nslot < 4 ? &prm.wqkv : (rank ? &prm.wu : &prm.wg);
        if (elect_one()) {
            if (warp == 8) {
                TRACE_GT(0); TRACE(1);
                prefetch_map(&prm.x); prefetch_map(w0);
                for (int s = 0; s < G1_STAGES; s++) { mbar_init(full1(s), 1); mbar_init(empty1(s), 4); }
            } else if (warp == 9) {
                for (int s = 0; s < G2_STAGES; s++) { mbar_init(full2(s), 1); mbar_init(empty2(s), 4); }
            } else if (warp == 10) {
                for (int s = 0; s < 7; s++) mbar_init(sig_bar + s * 8, 8);
                mbar_init(fold_bar, 3); mbar_init(x_bar, 1);
            } else {
                for (int s = 0; s < 8; s++) mbar_init(dep_bar + s * 8, 1);
            }
            asm volatile("fence.mbarrier_init.release.cluster;" ::: "memory");
        }
        __syncwarp();
        asm volatile("barrier.cluster.arrive.relaxed.aligned;" ::: "memory");
        if (warp == 8 && lane == 0) {
            for (int s = 0; s < G1_STAGES; s++) {
                mbar_expect_tx(full1(s), G1_STAGE_BYTES);
                tma_2d(base + s * G1_STAGE_BYTES, &prm.x, full1(s), s * 64, mblk * 128, policy(P_X));
            }
            TRACE(15);
        }
        asm volatile("setmaxnreg.dec.sync.aligned.u32 %0;" :: "n"(AUX_REGS));
        asm volatile("barrier.cluster.wait.acquire.aligned;" ::: "memory");

        if (warp == 8) {
            if (lane == 0) {
                TRACE(2);
                auto load_b1 = [&](int s, int nt, int k) {
                    const uint32_t dst = base + s * G1_STAGE_BYTES + A_BYTES + rank * 16384;
                    if (tile_is_qkv(nt)) tma_3d_mc(dst, &prm.wqkv, full1(s), k * 64, tile_index(nt) * 4 + rank * 2, policy(P_W1));
                    else tma_3d_mc(dst, rank ? &prm.wu : &prm.wg, full1(s), k * 64, tile_index(nt) * 2, policy(P_W1));
                };
                for (int s = 0; s < G1_STAGES; s++) load_b1(s, nslot, s);
                prefetch_map(&prm.xn); prefetch_map(&prm.wqkv); prefetch_map(rank ? &prm.wu : &prm.wg);
                prefetch_map(&prm.a2); prefetch_map(&prm.wo); prefetch_map(&prm.wd); prefetch_map(&prm.out);
                uint32_t ph = 0;
                for (int it = G1_STAGES; it < G1_TILES * G1_KSTEPS; it++) {
                    const int s = it & 3, k = it & 15;
                    if (it == G1_KSTEPS) { TRACE(14); mbar_wait(dep_bar, 0); TRACE(3); }
                    mbar_wait(empty1(s), ph);
                    mbar_expect_tx(full1(s), G1_STAGE_BYTES);
                    tma_2d(base + s * G1_STAGE_BYTES, it < G1_KSTEPS ? &prm.x : &prm.xn, full1(s), k * 64, mblk * 128,
                           policy(it < G1_KSTEPS ? P_X : (P_XN4 && it >= (G1_TILES - 1) * G1_KSTEPS)));
                    load_b1(s, (it >> 4) * 8 + nslot, k);
                    if (s == 3) ph ^= 1;
                }
                mbar_expect_tx(x_bar, 32768);
                tma_2d(aux, &prm.x, x_bar, nslot * 128, mblk * 128, policy(P_X));
                tma_2d(aux + 16384, &prm.x, x_bar, nslot * 128 + 64, mblk * 128, policy(P_X));
                TRACE(4);
                mbar_wait(dep_bar + 8, 0);
                TRACE(5);
                int q = 0; uint32_t ph2 = 1;
                for (int u = 0; u < G2_KSTEPS; u++) {
                    if (u == G2_LATE || u == G2_DSTEPS || u == G2_LAST) {
                        TRACE(u == G2_LATE ? 6 : (u == G2_DSTEPS ? 32 : 40));
                        mbar_wait(dep_bar + (u == G2_LATE ? 16 : (u == G2_DSTEPS ? 24 : 32)), 0);
                        TRACE(u == G2_LATE ? 7 : (u == G2_DSTEPS ? 33 : 41));
                    }
                    if (u < G2_STAGES) {
                        if (u == 0) mbar_wait(empty1(0), ph);
                        if (u == 1) mbar_wait(empty1(1), ph);
                        if (u == 3) mbar_wait(empty1(2), ph);
                        if (u == 4) mbar_wait(empty1(3), ph);
                    } else {
                        mbar_wait(empty2(q), ph2);
                    }
                    const uint32_t sa = stage2(q);
                    const bool down = u < G2_DSTEPS;
                    const int k = down ? u : (u - G2_DSTEPS) % 4 * 4 + (u - G2_DSTEPS) / 4;
                    mbar_expect_tx(full2(q), G2_STAGE_BYTES);
                    tma_3d(sa, &prm.a2, full2(q), (down ? DM : 0) + k * 64, 0, mblk * 64, policy(P_A2));
                    tma_5d_mc(sa + A_BYTES + rank * 8192, down ? &prm.wd : &prm.wo, full2(q), nslot * 128 + rank * 64, k * 2, policy(P_W2));
                    if (++q == G2_STAGES) { q = 0; ph2 ^= 1; }
                }
                TRACE(8);
            }
        } else if (warp == 9) {
            if (lane == 0) {
                const unsigned epoch = __ldcg(g_epoch + blockIdx.x * 16 + 2) + 1;
                mbar_wait(sig_bar, 0);
                TRACE(11);
                flag_add(flags + F_LN * 512);
                TRACE(42);
                flag_wait(flags + F_LN * 512, epoch * CNT_LN);
                fence_proxy_async();
                mbar_arrive(dep_bar);
                mbar_expect_tx(fold_bar, 1024);
                bulk_load(stats, g_stats + mblk * 128, 1024, fold_bar);
                g_epoch[blockIdx.x * 16 + 2] = epoch;
                for (int p = nslot < 4 ? 2 : 1; p < 7; p++) {
                    mbar_wait(sig_bar + p * 8, 0);
                    if (p == 2) TRACE(37);
                    flag_add(p == 2 || p == 3 ? g_flags + F_QKV * 512 + (p * 4 - 8 + (nslot & 3)) * 32
                                              : flags + (p < 6 ? F_EARLY : F_LATE) * 512);
                    if (p == 2) TRACE(43);
                }
            }
        } else {
            const int w = warp - 10;
            const unsigned epoch = __ldcg(g_epoch + blockIdx.x * 16 + w) + 1;
            unsigned* const cs_flag = g_flags + F_CS * 512 + (nslot * 2 + w) * 32;
            mbar_wait(full1(0), 0);
            if (elect_one()) {
                mbar_expect_tx(cs_bar + w * 8, 16384);
                tma_3d(aux + w * 16384, nslot < 4 ? &prm.wqkv : (w ? &prm.wu : &prm.wg), cs_bar + w * 8, 0, mblk * 64,
                       nslot < 4 ? 32 + nslot * 4 + w * 2 : nslot * 2 - 8, policy(P_W1));
            }
            float cs[8];
#pragma unroll
            for (int d = 0; d < 8; d++) cs[d] = 0.f;
            mbar_wait(cs_bar + w * 8, 0);
            const uint32_t wa = aux + w * 16384 + (lane & 8) * 1024 + (lane >> 4) * 128 + (((lane & 7) ^ (lane >> 4)) << 4);
#pragma unroll 1
            for (int i = 0; i < 8; i++) {
#pragma unroll
                for (int j = 0; j < 4; j++) {
                    float f[8];
                    unpack8(lds128((wa ^ (j * 32)) + i * 1024 + j * 256), f);
#pragma unroll
                    for (int d = 0; d < 8; d++) cs[d] += f[d];
                }
            }
#pragma unroll
            for (int d = 0; d < 8; d++) cs[d] += __shfl_xor_sync(0xffffffffu, cs[d], 16);
            *reinterpret_cast<float4*>(g_colsum + mblk * 2048 + nslot * 256 + w * 128 + (lane & 15) * 8 + (lane >> 4) * 4) =
                lane < 16 ? make_float4(cs[0], cs[1], cs[2], cs[3]) : make_float4(cs[4], cs[5], cs[6], cs[7]);
            __syncwarp();
            if (lane == 0) {
                if (w == 0) TRACE(34);
                flag_add(cs_flag);
                flag_wait(cs_flag, epoch * CNT_CS);
            }
            __syncwarp();
            const float4* gp = reinterpret_cast<const float4*>(g_colsum + nslot * 256 + w * 128) + lane;
            float4 c = make_float4(0.f, 0.f, 0.f, 0.f);
#pragma unroll 8
            for (int m = 0; m < 16; m++) {
                const float4 a = __ldcg(gp + m * 512);
                c.x += a.x; c.y += a.y; c.z += a.z; c.w += a.w;
            }
            const uint32_t ca = colsum + (w * 8 + (lane >> 2)) * 64 + (lane & 1) * 32 + (lane & 2) * 4;
            sts64f(ca, c.x, c.y);
            sts64f(ca + 16, c.z, c.w);
            __syncwarp();
            if (lane == 0) {
                mbar_arrive(fold_bar);
                g_epoch[blockIdx.x * 16 + w] = epoch;
                if (w == 0) {
                    TRACE(35);
                    flag_wait(flags + F_EARLY * 512, epoch * CNT_EARLY);
                    fence_proxy_async(); mbar_arrive(dep_bar + 8);
                    flag_wait(flags + F_LATE * 512, epoch * CNT_LATE);
                    fence_proxy_async(); mbar_arrive(dep_bar + 16);
                    flag_wait(g_flags + F_O * 512, epoch * CNT_O);
                    fence_proxy_async(); mbar_arrive(dep_bar + 24);
                    flag_wait(g_flags + F_O * 512 + 32, epoch * CNT_O);
                    fence_proxy_async(); mbar_arrive(dep_bar + 32);
                }
            }
        }
    } else {
        asm volatile("barrier.cluster.arrive.relaxed.aligned;" ::: "memory");
        asm volatile("setmaxnreg.inc.sync.aligned.u32 %0;" :: "n"(CONSUMER_REGS));
        const int wg = __shfl_sync(0xffffffffu, threadIdx.x >> 7, 0);
        const int cw = threadIdx.x >> 5;
        const int tid = threadIdx.x & 127;
        float acc[128];
        uint32_t pk[64];
#pragma unroll
        for (int i = 0; i < 64; i++) asm volatile("mov.b32 %0, 0;" : "=r"(pk[i]));
#pragma unroll
        for (int i = 0; i < 128; i++) asm volatile("mov.b32 %0, 0;" : "=f"(acc[i]));
        asm volatile("barrier.cluster.wait.acquire.aligned;" ::: "memory");

        const int orow = ((lane >> 2) & 1) * (SEQ / 2) + mblk * 64 + cw * 8 + (lane >> 3);
        __nv_bfloat16* optr = nullptr;
        auto release = [&](uint32_t bar) { if (tid < 2) mbar_arrive_cluster(bar, tid); };
        auto chunk_geglu = [&](int j) {
            const int c = j >> 1, h = j & 1;
            uint4 v;
            v.x = geglu2(pk[8 * c + h], pk[32 + 8 * c + h]);
            v.y = geglu2(pk[8 * c + 2 + h], pk[32 + 8 * c + 2 + h]);
            v.z = geglu2(pk[8 * c + 4 + h], pk[32 + 8 * c + 4 + h]);
            v.w = geglu2(pk[8 * c + 6 + h], pk[32 + 8 * c + 6 + h]);
            *reinterpret_cast<uint4*>(optr + h * 4 * K2 + c * 32) = v;
        };
        auto chunk_qkv = [&](int c) {
            *reinterpret_cast<uint4*>(optr + c * 32) = make_uint4(pk[8 * c], pk[8 * c + 2], pk[8 * c + 4], pk[8 * c + 6]);
            *reinterpret_cast<uint4*>(optr + 4 * NQKV + c * 32) = make_uint4(pk[8 * c + 1], pk[8 * c + 3], pk[8 * c + 5], pk[8 * c + 7]);
        };
        auto signal_stores = [&](int p) { __syncwarp(); if (lane == 0) mbar_arrive(sig_bar + p * 8); };

        auto chunk_ln = [&](int k) {
            const int row = mblk * 128 + nslot * 16 + cw * 2;
            if (k == 0) {
                const uint4* xp = reinterpret_cast<const uint4*>(prm.px + (size_t)row * DM) + lane;
#pragma unroll
                for (int i = 0; i < 8; i++) {
                    const uint4 v = ldg_stream(xp + i * 32, policy(P_X));
                    pk[4 * i] = v.x; pk[4 * i + 1] = v.y; pk[4 * i + 2] = v.z; pk[4 * i + 3] = v.w;
                }
            } else if (k == 2) {
                float a = row_sum(pk), b = row_sum(pk + 16);
                warp_sum2(a, b);
                pk[32] = __float_as_uint(a * (1.f / DM)); pk[33] = __float_as_uint(b * (1.f / DM));
            } else if (k == 3) {
                float a = row_sq(pk, __uint_as_float(pk[32])), b = row_sq(pk + 16, __uint_as_float(pk[33]));
                warp_sum2(a, b);
                pk[34] = __float_as_uint(a); pk[35] = __float_as_uint(b);
            } else if (k == 4) {
                row_store(pk, __uint_as_float(pk[32]), row_inv(__uint_as_float(pk[34])), row, lane);
            } else if (k == 5) {
                row_store(pk + 16, __uint_as_float(pk[33]), row_inv(__uint_as_float(pk[35])), row + 1, lane);
                signal_stores(0);
            }
        };

        bool gated = false;
#pragma unroll 1
        for (int t = 0; t < G1_TILES; t++) {
#pragma unroll
            for (int k = 0; k < G1_KSTEPS; k++) {
                const int s = k & 3;
                mbar_wait(full1(s), (k >> 2) & 1);
                if (t == 0 && k == 0 && threadIdx.x == 0) TRACE(12);
                if (t == TRACE_T && threadIdx.x == 0) TRACE(44 + k);
                if (wg == 1 && k == G1_KSTEPS - G1_SKEW) asm volatile("bar.sync 1, 256;" ::: "memory");
                const uint64_t da = desc_a(base + s * G1_STAGE_BYTES + wg * 8192);
                const uint64_t db = desc_b(base + s * G1_STAGE_BYTES + A_BYTES);
                wg_fence();
#pragma unroll
                for (int kk = 0; kk < 4; kk++) wgmma_n256(acc, da + kk * 2, db + kk * 128, (k | kk) != 0);
                wg_commit();
                if (wg == 0 && k == G1_KSTEPS - 1) asm volatile("bar.arrive 1, 256;" ::: "memory");
                if (k <= 5 && t == 0) chunk_ln(k);
                if (k >= 1 && k <= 8 && gated) {
                    chunk_geglu(k - 1);
                    if (k == 8) signal_stores(t == 1 ? 1 : t + 1);
                }
                if (t != 0 && !gated) {
                    if (k == 0) { chunk_qkv(0); chunk_qkv(1); }
                    if (k >= 4 && k <= 9) chunk_qkv(k - 2);
                    if ((k == 0 || k == 9) && t == 2) signal_stores(k ? 3 : 2);
                }
                wg_wait<1>();
                if (k > 0) release(empty1((k - 1) & 3));
            }
            if (t == 0) mbar_wait(fold_bar, 0);
            wg_wait<0>();
            fence_regs(acc);
            release(empty1(3));
            if (t == 0) {
                const uint32_t sp = stats + (cw * 16 + (lane >> 2)) * 8;
                const float2 sa = lds64f(sp), sb = lds64f(sp + 64);
#pragma unroll
                for (int j = 0; j < 16; j++) {
                    const uint4 c = lds128(colsum + j * 64 + (lane & 3) * 16);
                    const float c0 = __uint_as_float(c.x), c1 = __uint_as_float(c.y);
                    const float c2 = __uint_as_float(c.z), c3 = __uint_as_float(c.w);
                    const float* a = acc + 8 * j;
                    pk[4 * j] = pack_bf16(fmaf(sa.x, c0, a[0]) * sa.y, fmaf(sa.x, c1, a[1]) * sa.y);
                    pk[4 * j + 1] = pack_bf16(fmaf(sb.x, c0, a[2]) * sb.y, fmaf(sb.x, c1, a[3]) * sb.y);
                    pk[4 * j + 2] = pack_bf16(fmaf(sa.x, c2, a[4]) * sa.y, fmaf(sa.x, c3, a[5]) * sa.y);
                    pk[4 * j + 3] = pack_bf16(fmaf(sb.x, c2, a[6]) * sb.y, fmaf(sb.x, c3, a[7]) * sb.y);
                }
            } else {
#pragma unroll
                for (int i = 0; i < 64; i++) pk[i] = pack_bf16(acc[2 * i], acc[2 * i + 1]);
            }
            const int nt = t * 8 + nslot;
            gated = !tile_is_qkv(nt);
            optr = !gated ? g_qkv + (size_t)orow * NQKV + tile_index(nt) * 256 + (lane & 3) * 8
                                : g_a2 + (size_t)orow * K2 + DM + tile_index(nt) * 128 + (lane & 3) * 8;
            if (tid == 0) TRACE(16 + wg * 8 + t);
        }

        float accd[64], accs[64];
#pragma unroll
        for (int i = 0; i < 64; i++) accd[i] = 0.f;
#pragma unroll
        for (int u = 0; u < 9; u++) {
            const int q = u % G2_STAGES;
            mbar_wait(full2(q), (u / G2_STAGES) & 1);
            const uint64_t da = desc_a(stage2(q) + wg * 8192), db = desc_b(stage2(q) + A_BYTES);
            wg_fence();
#pragma unroll
            for (int kk = 0; kk < 4; kk++) wgmma_n128(accd, da + kk * 2, db + kk * 128, (u | kk) != 0);
            wg_commit();
            if (u >= 1) { chunk_geglu(u - 1); if (u == 8) signal_stores(6); }
            wg_wait<1>();
            if (u > 0) release(empty2((u - 1) % G2_STAGES));
        }
        {
            int q = 9 % G2_STAGES, qp = 8 % G2_STAGES; uint32_t ph = (9 / G2_STAGES) & 1;
#pragma unroll 1
            for (int u = 9; u < G2_DSTEPS; u++) {
                mbar_wait(full2(q), ph);
                const uint64_t da = desc_a(stage2(q) + wg * 8192), db = desc_b(stage2(q) + A_BYTES);
                wg_fence();
#pragma unroll
                for (int kk = 0; kk < 4; kk++) wgmma_n128(accd, da + kk * 2, db + kk * 128, 1);
                wg_commit();
                wg_wait<1>();
                release(empty2(qp));
                qp = q;
                if (++q == G2_STAGES) { q = 0; ph ^= 1; }
            }
        }
        if (tid == 0) TRACE(16 + wg * 8 + 5);
#pragma unroll
        for (int i = 0; i < 64; i++) accs[i] = 0.f;
        uint32_t gk[32], xr[32];
        const uint32_t xs = aux + cw * 2048;
        const uint32_t xrow = xs + ((lane & 7) + ((lane >> 3) & 1) * 8) * 128;
        auto xaddr = [&](int j) { return xrow + (j >> 2) * 16384 + (((((j & 3) * 2) + (lane >> 4)) ^ (lane & 7)) << 4); };
#pragma unroll
        for (int u = G2_DSTEPS; u < G2_KSTEPS; u++) {
            const int q = u % G2_STAGES, v = u - G2_DSTEPS;
            mbar_wait(full2(q), (u / G2_STAGES) & 1);
            if (G2_SKEW > 0 && wg == 1 && u == G2_KSTEPS - G2_SKEW) asm volatile("bar.sync 1, 256;" ::: "memory");
            const uint64_t da = desc_a(stage2(q) + wg * 8192), db = desc_b(stage2(q) + A_BYTES);
            wg_fence();
#pragma unroll
            for (int kk = 0; kk < 4; kk++) wgmma_n128(accs, da + kk * 2, db + kk * 128, (v | kk) != 0);
            wg_commit();
            if (G2_SKEW > 0 && wg == 0 && u == G2_KSTEPS - 1) asm volatile("bar.arrive 1, 256;" ::: "memory");
            if (v >= 1 && v <= 8) {
#pragma unroll
                for (int i = 4 * (v - 1); i < 4 * v; i++) {
                    const uint32_t d2 = pack_bf16(accd[2 * i], accd[2 * i + 1]);
                    gk[i] = pack_bf16(silu(bf_lo(d2)), silu(bf_hi(d2)));
                }
            }
            if (v == 9) mbar_wait(x_bar, 0);
            if (v >= 9 && v <= 12) {
#pragma unroll
                for (int j = 2 * (v - 9); j < 2 * (v - 8); j++)
                    asm volatile("ldmatrix.sync.aligned.m8n8.x4.shared.b16 {%0,%1,%2,%3}, [%4];"
                                 : "=r"(xr[4 * j]), "=r"(xr[4 * j + 1]), "=r"(xr[4 * j + 2]), "=r"(xr[4 * j + 3])
                                 : "r"(xaddr(j)) : "memory");
            }
            wg_wait<1>();
            if (v == 0) fence_regs(accd);
            if (u - 1 + G2_STAGES < G2_KSTEPS) release(empty2((u - 1) % G2_STAGES));
        }
        wg_wait<0>();
        fence_regs(accs);
        if (tid == 0) TRACE(16 + wg * 8 + 6);
#pragma unroll
        for (int j = 0; j < 8; j++) {
            uint32_t r[4];
#pragma unroll
            for (int i = 0; i < 4; i++) {
                const int e = j * 4 + i;
                r[i] = add_bf16x2(xr[e], mul_bf16x2(pack_bf16(accs[2 * e], accs[2 * e + 1]), gk[e]));
            }
            asm volatile("stmatrix.sync.aligned.m8n8.x4.shared.b16 [%0], {%1,%2,%3,%4};"
                         :: "r"(xaddr(j)), "r"(r[0]), "r"(r[1]), "r"(r[2]), "r"(r[3]) : "memory");
            if (j == 3 || j == 7) {
                asm volatile("fence.proxy.async.shared::cta;" ::: "memory");
                __syncwarp();
                if (lane == 0) {
                    tma_store_2d(&prm.out, xs + (j >> 2) * 16384, nslot * 128 + (j >> 2) * 64, mblk * 128 + cw * 16);
                    asm volatile("cp.async.bulk.commit_group;" ::: "memory");
                }
            }
        }
        if (lane == 0) asm volatile("cp.async.bulk.wait_group.read 0;" ::: "memory");
        if (tid == 0) { TRACE(16 + wg * 8 + 7); if (wg == 1) TRACE_GT(13); }
    }
}

typedef CUresult (*EncodeFn)(CUtensorMap*, CUtensorMapDataType, cuuint32_t, void*, const cuuint64_t*, const cuuint64_t*,
                             const cuuint32_t*, const cuuint32_t*, CUtensorMapInterleave, CUtensorMapSwizzle,
                             CUtensorMapL2promotion, CUtensorMapFloatOOBfill);

void encode(EncodeFn fn, CUtensorMap* m, const void* ptr, int rank, const cuuint64_t* dims, const cuuint64_t* strides,
            const cuuint32_t* box) {
    const cuuint32_t es[5] = {1, 1, 1, 1, 1};
    fn(m, CU_TENSOR_MAP_DATA_TYPE_BFLOAT16, rank, const_cast<void*>(ptr), dims, strides, box, es,
       CU_TENSOR_MAP_INTERLEAVE_NONE, CU_TENSOR_MAP_SWIZZLE_128B, CU_TENSOR_MAP_L2_PROMOTION_L2_128B,
       CU_TENSOR_MAP_FLOAT_OOB_FILL_NONE);
}
void encode_2d(EncodeFn fn, CUtensorMap* m, const void* ptr, int cols, int box_rows) {
    const cuuint64_t dims[2] = {(cuuint64_t)cols, SEQ}, strides[1] = {(cuuint64_t)cols * 2};
    const cuuint32_t box[2] = {64, (cuuint32_t)box_rows};
    encode(fn, m, ptr, 2, dims, strides, box);
}
void encode_w1(EncodeFn fn, CUtensorMap* m, const void* ptr, int cols) {
    const cuuint64_t dims[3] = {64, DM, (cuuint64_t)cols / 64}, strides[2] = {(cuuint64_t)cols * 2, 128};
    const cuuint32_t box[3] = {64, 64, 2};
    encode(fn, m, ptr, 3, dims, strides, box);
}
void encode_qk(EncodeFn fn, CUtensorMap* m, const void* ptr) {
    const cuuint64_t dims[3] = {DM, SEQ, 3}, strides[2] = {NQKV * 2, DM * 2};
    const cuuint32_t box[3] = {64, 16, 2};
    encode(fn, m, ptr, 3, dims, strides, box);
}
void encode_a2(EncodeFn fn, CUtensorMap* m, const void* ptr) {
    const cuuint64_t dims[3] = {K2, 2, SEQ / 2}, strides[2] = {(cuuint64_t)SEQ * K2, K2 * 2};
    const cuuint32_t box[3] = {64, 2, 64};
    encode(fn, m, ptr, 3, dims, strides, box);
}
void encode_w2(EncodeFn fn, CUtensorMap* m, const void* ptr, int rows) {
    const cuuint64_t rb = DM * 2;
    const cuuint64_t dims[5] = {DM, 2, 4, 4, (cuuint64_t)rows / 32}, strides[4] = {rb, 8 * rb, 2 * rb, 32 * rb};
    const cuuint32_t box[5] = {64, 2, 4, 4, 2};
    encode(fn, m, ptr, 5, dims, strides, box);
}

}

extern "C" void kernel_launch(void* const* d_in, const int* in_sizes, int n_in, void* d_out, int out_size) {
    (void)in_sizes; (void)n_in; (void)out_size;
    static EncodeFn fn = nullptr;
    static void *p_xn = nullptr, *p_qkv = nullptr, *p_a2 = nullptr;
    if (!fn) {
        cudaDriverEntryPointQueryResult st;
        cudaGetDriverEntryPoint("cuTensorMapEncodeTiled", (void**)&fn, cudaEnableDefault, &st);
        cudaGetSymbolAddress(&p_xn, g_xn);
        cudaGetSymbolAddress(&p_qkv, g_qkv);
        cudaGetSymbolAddress(&p_a2, g_a2);
        cudaFuncSetAttribute(fused_kernel, cudaFuncAttributeMaxDynamicSharedMemorySize, SMEM_BYTES);
    }
    Params prm;
    encode_2d(fn, &prm.x, d_in[0], DM, 128);
    encode_2d(fn, &prm.xn, p_xn, DM, 128);
    encode_w1(fn, &prm.wqkv, d_in[1], NQKV);
    encode_w1(fn, &prm.wg, d_in[4], DF);
    encode_w1(fn, &prm.wu, d_in[5], DF);
    encode_qk(fn, &prm.qk, p_qkv);
    encode_2d(fn, &prm.v, p_qkv, NQKV, 16);
    encode_2d(fn, &prm.o, p_a2, K2, 16);
    encode_a2(fn, &prm.a2, p_a2);
    encode_w2(fn, &prm.wo, d_in[2], DM);
    encode_w2(fn, &prm.wd, d_in[6], DF);
    encode_2d(fn, &prm.out, d_out, DM, 16);
    prm.px = (const __nv_bfloat16*)d_in[0];
    prm.zero = 0;
    fused_kernel<<<NCTA, 384, SMEM_BYTES>>>(prm);
}
```

```cpp
#include <cuda_runtime.h>
#include <cuda_bf16.h>
#include <cuda.h>
#include <stdint.h>
#include <type_traits>

#define P_W1 1
#define P_X 1
#define P_XN4 1
#define P_W2 1
#define P_A2 1
#define P_QKV 1

namespace {

constexpr int SEQ = 2048, DM = 1024, DF = 3584, K2 = DM + DF, NQKV = 3 * DM;
constexpr int NGEMM = 128, NCTA = 132;
constexpr int G1_STAGES = 4, G1_STAGE_BYTES = 49152, G1_KSTEPS = 16, G1_TILES = 5;
constexpr int G2_STAGES = 6, G2_STAGE_BYTES = 32768, G2_KSTEPS = 72, G2_LATE = 40, G2_DSTEPS = 56, G2_LAST = 68;
constexpr int A_BYTES = 16384;
constexpr int AUX_OFF = G1_STAGES * G1_STAGE_BYTES;
constexpr int BAR_OFF = AUX_OFF + 32768;
constexpr int SMEM_BYTES = BAR_OFF + 2560;
constexpr int G1_SKEW = 2, G2_SKEW = 2, LN_STEP = 3;
constexpr int CONSUMER_REGS = 224, AUX_REGS = 56;
constexpr int ATT_SLOT = 8192;

enum { F_LN = 0, F_QKV = 1, F_EARLY = 2, F_LATE = 3, F_O = 4, F_CS = 5 };
constexpr unsigned CNT_LN = 8, CNT_QKV = 32, CNT_EARLY = 20, CNT_LATE = 8, CNT_O = 4, CNT_CS = 16;

__device__ __align__(1024) __nv_bfloat16 g_xn[SEQ * DM];
__device__ __align__(1024) __nv_bfloat16 g_qkv[SEQ * NQKV];
__device__ __align__(1024) __nv_bfloat16 g_a2[SEQ * K2];
__device__ __align__(128) float2 g_stats[SEQ];
__device__ __align__(128) float g_colsum[16 * 2048];
__device__ __align__(128) unsigned g_flags[6 * 16 * 32];
__device__ __align__(128) unsigned g_epoch[NCTA * 16];

#define TRACE_T -1
#define TRACE(slot) do {} while (0)
#define TRACE_GT(slot) do {} while (0)

__device__ __forceinline__ uint32_t smem_u32(const void* p) { return (uint32_t)__cvta_generic_to_shared(p); }
__device__ __forceinline__ void mbar_init(uint32_t bar, uint32_t cnt) {
    asm volatile("mbarrier.init.shared::cta.b64 [%0], %1;" :: "r"(bar), "r"(cnt) : "memory");
}
__device__ __forceinline__ void mbar_expect_tx(uint32_t bar, uint32_t bytes) {
    asm volatile("mbarrier.arrive.expect_tx.shared::cta.b64 _, [%0], %1;" :: "r"(bar), "r"(bytes) : "memory");
}
__device__ __forceinline__ void mbar_arrive(uint32_t bar) {
    asm volatile("mbarrier.arrive.shared::cta.b64 _, [%0];" :: "r"(bar) : "memory");
}
__device__ __forceinline__ void mbar_arrive_cluster(uint32_t bar, uint32_t cta) {
    asm volatile("{\n.reg .b32 ra;\nmapa.shared::cluster.u32 ra, %0, %1;\nmbarrier.arrive.shared::cluster.b64 _, [ra];\n}"
                 :: "r"(bar), "r"(cta) : "memory");
}
__device__ __forceinline__ bool mbar_try_wait(uint32_t bar, uint32_t parity) {
    uint32_t ok;
    asm volatile("{\n.reg .pred p;\nmbarrier.try_wait.parity.shared::cta.b64 p, [%1], %2;\nselp.u32 %0, 1, 0, p;\n}"
                 : "=r"(ok) : "r"(bar), "r"(parity) : "memory");
    return ok;
}
__device__ __forceinline__ void mbar_wait(uint32_t bar, uint32_t parity) {
#pragma unroll 1
    for (int spins = 0; !mbar_try_wait(bar, parity) && spins < (1 << 17); spins++) {}
}
template <bool WARP = false> __device__ __forceinline__ void flag_wait(const unsigned* p, unsigned target) {
#pragma unroll 1
    for (int spins = 0; spins < (1 << 19); spins++) {
        unsigned v;
        asm volatile("ld.acquire.gpu.global.u32 %0, [%1];" : "=r"(v) : "l"(p) : "memory");
        if (WARP ? __all_sync(0xffffffffu, (int)(v - target) >= 0) : (int)(v - target) >= 0) break;
        __nanosleep(64);
    }
}
__device__ __forceinline__ void flag_add(unsigned* p) {
    asm volatile("red.release.gpu.global.add.u32 [%0], 1;" :: "l"(p) : "memory");
}
__device__ __forceinline__ bool elect_one() {
    uint32_t ok;
    asm volatile("{\n.reg .pred p;\nelect.sync _|p, 0xffffffff;\nselp.u32 %0, 1, 0, p;\n}" : "=r"(ok));
    return ok;
}
__device__ __forceinline__ void fence_proxy_async() { asm volatile("fence.proxy.async.global;" ::: "memory"); }
__device__ __forceinline__ uint4 lds128(uint32_t addr) {
    uint4 v;
    asm volatile("ld.shared.v4.u32 {%0,%1,%2,%3}, [%4];" : "=r"(v.x), "=r"(v.y), "=r"(v.z), "=r"(v.w) : "r"(addr) : "memory");
    return v;
}
__device__ __forceinline__ float2 lds64f(uint32_t addr) {
    float2 v;
    asm volatile("ld.shared.v2.f32 {%0,%1}, [%2];" : "=f"(v.x), "=f"(v.y) : "r"(addr) : "memory");
    return v;
}
__device__ __forceinline__ void sts128(uint32_t addr, uint4 v) {
    asm volatile("st.shared.v4.u32 [%0], {%1,%2,%3,%4};" :: "r"(addr), "r"(v.x), "r"(v.y), "r"(v.z), "r"(v.w) : "memory");
}
__device__ __forceinline__ void sts64f(uint32_t addr, float a, float b) {
    asm volatile("st.shared.v2.f32 [%0], {%1,%2};" :: "r"(addr), "f"(a), "f"(b) : "memory");
}

__device__ __forceinline__ uint64_t policy(bool stream) {
    uint64_t p;
    if (stream) asm("createpolicy.fractional.L2::evict_first.b64 %0, 1.0;" : "=l"(p));
    else asm("createpolicy.fractional.L2::evict_normal.b64 %0, 1.0;" : "=l"(p));
    return p;
}
__device__ __forceinline__ void tma_2d(uint32_t dst, const CUtensorMap* m, uint32_t bar, int c0, int c1, uint64_t pol) {
    asm volatile("cp.async.bulk.tensor.2d.shared::cluster.global.mbarrier::complete_tx::bytes.L2::cache_hint"
                 " [%0], [%1, {%3, %4}], [%2], %5;"
                 :: "r"(dst), "l"(m), "r"(bar), "r"(c0), "r"(c1), "l"(pol) : "memory");
}
__device__ __forceinline__ void tma_3d(uint32_t dst, const CUtensorMap* m, uint32_t bar, int c0, int c1, int c2, uint64_t pol) {
    asm volatile("cp.async.bulk.tensor.3d.shared::cluster.global.mbarrier::complete_tx::bytes.L2::cache_hint"
                 " [%0], [%1, {%3, %4, %5}], [%2], %6;"
                 :: "r"(dst), "l"(m), "r"(bar), "r"(c0), "r"(c1), "r"(c2), "l"(pol) : "memory");
}
__device__ __forceinline__ void tma_3d_mc(uint32_t dst, const CUtensorMap* m, uint32_t bar, int c1, int c2, uint64_t pol) {
    asm volatile("cp.async.bulk.tensor.3d.shared::cluster.global.mbarrier::complete_tx::bytes.multicast::cluster.L2::cache_hint"
                 " [%0], [%1, {%3, %4, %5}], [%2], %6, %7;"
                 :: "r"(dst), "l"(m), "r"(bar), "r"(0), "r"(c1), "r"(c2), "h"((uint16_t)3), "l"(pol) : "memory");
}
__device__ __forceinline__ void tma_5d_mc(uint32_t dst, const CUtensorMap* m, uint32_t bar, int c0, int c4, uint64_t pol) {
    asm volatile("cp.async.bulk.tensor.5d.shared::cluster.global.mbarrier::complete_tx::bytes.multicast::cluster.L2::cache_hint"
                 " [%0], [%1, {%3, %4, %4, %4, %5}], [%2], %6, %7;"
                 :: "r"(dst), "l"(m), "r"(bar), "r"(c0), "r"(0), "r"(c4), "h"((uint16_t)3), "l"(pol) : "memory");
}
__device__ __forceinline__ void tma_store_2d(const CUtensorMap* m, uint32_t src, int c0, int c1) {
    asm volatile("cp.async.bulk.tensor.2d.global.shared::cta.bulk_group [%0, {%2, %3}], [%1];"
                 :: "l"(m), "r"(src), "r"(c0), "r"(c1) : "memory");
}
__device__ __forceinline__ uint4 ldg_stream(const void* p, uint64_t pol) {
    uint4 v;
    asm volatile("ld.global.nc.L1::no_allocate.L2::cache_hint.v4.u32 {%0,%1,%2,%3}, [%4], %5;"
                 : "=r"(v.x), "=r"(v.y), "=r"(v.z), "=r"(v.w) : "l"(p), "l"(pol));
    return v;
}
__device__ __forceinline__ void bulk_load(uint32_t dst, const void* src, uint32_t bytes, uint32_t bar) {
    asm volatile("cp.async.bulk.shared::cluster.global.mbarrier::complete_tx::bytes [%0], [%1], %2, [%3];"
                 :: "r"(dst), "l"(src), "r"(bytes), "r"(bar) : "memory");
}
__device__ __forceinline__ void prefetch_3d(const CUtensorMap* m, int c1, int c2, uint64_t pol) {
    asm volatile("cp.async.bulk.prefetch.tensor.3d.L2.global.L2::cache_hint [%0, {%1, %2, %3}], %4;"
                 :: "l"(m), "r"(0), "r"(c1), "r"(c2), "l"(pol) : "memory");
}
__device__ __forceinline__ void prefetch_map(const CUtensorMap* m) {
    asm volatile("prefetch.tensormap [%0];" :: "l"(m) : "memory");
}
__device__ __forceinline__ void wg_fence() { asm volatile("wgmma.fence.sync.aligned;" ::: "memory"); }
__device__ __forceinline__ void wg_commit() { asm volatile("wgmma.commit_group.sync.aligned;" ::: "memory"); }
template <int N> __device__ __forceinline__ void wg_wait() { asm volatile("wgmma.wait_group.sync.aligned %0;" :: "n"(N) : "memory"); }

__device__ __forceinline__ uint64_t desc_a(uint32_t addr) {
    return (uint64_t)((addr & 0x3FFFF) >> 4) | (1ull << 16) | (64ull << 32) | (1ull << 62);
}
__device__ __forceinline__ uint64_t desc_b(uint32_t addr) {
    return (uint64_t)((addr & 0x3FFFF) >> 4) | (512ull << 16) | (64ull << 32) | (1ull << 62);
}

#define R8(d, o) "+f"(d[o]), "+f"(d[o+1]), "+f"(d[o+2]), "+f"(d[o+3]), "+f"(d[o+4]), "+f"(d[o+5]), "+f"(d[o+6]), "+f"(d[o+7])
#define R32(d, o) R8(d, o), R8(d, o+8), R8(d, o+16), R8(d, o+24)
#define R64(d, o) R32(d, o), R32(d, o+32)

__device__ __forceinline__ void wgmma_n256(float (&d)[128], uint64_t da, uint64_t db, int scale_d) {
    asm volatile("{\n.reg .pred p;\nsetp.ne.b32 p, %130, 0;\n"
        "wgmma.mma_async.sync.aligned.m64n256k16.f32.bf16.bf16 "
        "{%0,%1,%2,%3,%4,%5,%6,%7,%8,%9,%10,%11,%12,%13,%14,%15,%16,%17,%18,%19,%20,%21,%22,%23,%24,%25,%26,%27,%28,%29,%30,%31,"
        "%32,%33,%34,%35,%36,%37,%38,%39,%40,%41,%42,%43,%44,%45,%46,%47,%48,%49,%50,%51,%52,%53,%54,%55,%56,%57,%58,%59,%60,%61,%62,%63,"
        "%64,%65,%66,%67,%68,%69,%70,%71,%72,%73,%74,%75,%76,%77,%78,%79,%80,%81,%82,%83,%84,%85,%86,%87,%88,%89,%90,%91,%92,%93,%94,%95,"
        "%96,%97,%98,%99,%100,%101,%102,%103,%104,%105,%106,%107,%108,%109,%110,%111,%112,%113,%114,%115,%116,%117,%118,%119,%120,%121,%122,%123,%124,%125,%126,%127},"
        " %128, %129, p, 1, 1, 0, 1;\n}"
        : R64(d, 0), R64(d, 64) : "l"(da), "l"(db), "r"(scale_d));
}
__device__ __forceinline__ void wgmma_n128(float (&d)[64], uint64_t da, uint64_t db, int scale_d) {
    asm volatile("{\n.reg .pred p;\nsetp.ne.b32 p, %66, 0;\n"
        "wgmma.mma_async.sync.aligned.m64n128k16.f32.bf16.bf16 "
        "{%0,%1,%2,%3,%4,%5,%6,%7,%8,%9,%10,%11,%12,%13,%14,%15,%16,%17,%18,%19,%20,%21,%22,%23,%24,%25,%26,%27,%28,%29,%30,%31,"
        "%32,%33,%34,%35,%36,%37,%38,%39,%40,%41,%42,%43,%44,%45,%46,%47,%48,%49,%50,%51,%52,%53,%54,%55,%56,%57,%58,%59,%60,%61,%62,%63},"
        " %64, %65, p, 1, 1, 0, 1;\n}"
        : R64(d, 0) : "l"(da), "l"(db), "r"(scale_d));
}

__device__ __forceinline__ uint32_t pack_bf16(float lo, float hi) {
    uint32_t r; asm("cvt.rn.bf16x2.f32 %0, %1, %2;" : "=r"(r) : "f"(hi), "f"(lo)); return r;
}
__device__ __forceinline__ float bf_lo(uint32_t v) { return __uint_as_float(v << 16); }
__device__ __forceinline__ float bf_hi(uint32_t v) { return __uint_as_float(v & 0xffff0000u); }
__device__ __forceinline__ float round_bf16(float v) { return bf_lo(pack_bf16(v, 0.f)); }
__device__ __forceinline__ uint32_t mul_bf16x2(uint32_t a, uint32_t b) {
    uint32_t r; asm("mul.rn.bf16x2 %0, %1, %2;" : "=r"(r) : "r"(a), "r"(b)); return r;
}
__device__ __forceinline__ uint32_t add_bf16x2(uint32_t a, uint32_t b) {
    uint32_t r; asm("add.rn.bf16x2 %0, %1, %2;" : "=r"(r) : "r"(a), "r"(b)); return r;
}
__device__ __forceinline__ uint32_t sub_bf16x2(uint32_t a, uint32_t b) {
    uint32_t r; asm("sub.rn.bf16x2 %0, %1, %2;" : "=r"(r) : "r"(a), "r"(b)); return r;
}
__device__ __forceinline__ uint32_t mul2_bf16x2(uint32_t a, uint32_t hi, uint32_t lo) {
    uint32_t r; asm("fma.rn.bf16x2 %0, %1, %2, %3;" : "=r"(r) : "r"(a), "r"(hi), "r"(mul_bf16x2(a, lo))); return r;
}
__device__ __forceinline__ float tanh_fast(float x) { float r; asm("tanh.approx.f32 %0, %1;" : "=f"(r) : "f"(x)); return r; }
__device__ __forceinline__ float gelu_tanh(float g) {
    float t = fmaf(g * g, 0.044715f * 0.7978845608f, 0.7978845608f) * g;
    float hg = 0.5f * g;
    return fmaf(hg, tanh_fast(t), hg);
}
__device__ __forceinline__ uint32_t geglu2(uint32_t g2, uint32_t u2) {
    return mul_bf16x2(pack_bf16(gelu_tanh(bf_lo(g2)), gelu_tanh(bf_hi(g2))), u2);
}
__device__ __forceinline__ float silu(float d) {
    float hd = 0.5f * d;
    return fmaf(hd, tanh_fast(hd), hd);
}
__device__ __forceinline__ float ex2_fast(float x) { float r; asm("ex2.approx.ftz.f32 %0, %1;" : "=f"(r) : "f"(x)); return r; }
__device__ __forceinline__ void unpack8(uint4 v, float (&f)[8]) {
    f[0] = bf_lo(v.x); f[1] = bf_hi(v.x); f[2] = bf_lo(v.y); f[3] = bf_hi(v.y);
    f[4] = bf_lo(v.z); f[5] = bf_hi(v.z); f[6] = bf_lo(v.w); f[7] = bf_hi(v.w);
}
template <int N> __device__ __forceinline__ void fence_regs(float (&d)[N]) {
#pragma unroll
    for (int i = 0; i < N; i++) asm volatile("" : "+f"(d[i]) :: "memory");
}

__device__ __forceinline__ float rcp_fast(float x) { float r; asm("rcp.approx.ftz.f32 %0, %1;" : "=f"(r) : "f"(x)); return r; }
__device__ __forceinline__ uint32_t max_bf16x2(uint32_t a, uint32_t b) {
    uint32_t r; asm("max.bf16x2 %0, %1, %2;" : "=r"(r) : "r"(a), "r"(b)); return r;
}
__device__ __forceinline__ uint4 ldsm4(uint32_t addr) {
    uint4 v;
    asm volatile("ldmatrix.sync.aligned.m8n8.x4.shared.b16 {%0,%1,%2,%3}, [%4];"
                 : "=r"(v.x), "=r"(v.y), "=r"(v.z), "=r"(v.w) : "r"(addr) : "memory");
    return v;
}
__device__ __forceinline__ uint4 ldsm4_t(uint32_t addr) {
    uint4 v;
    asm volatile("ldmatrix.sync.aligned.m8n8.x4.trans.shared.b16 {%0,%1,%2,%3}, [%4];"
                 : "=r"(v.x), "=r"(v.y), "=r"(v.z), "=r"(v.w) : "r"(addr) : "memory");
    return v;
}
__device__ __forceinline__ void mma_16816(float (&c)[4], uint32_t a0, uint32_t a1, uint32_t a2, uint32_t a3, uint32_t b0, uint32_t b1) {
    asm("mma.sync.aligned.m16n8k16.row.col.f32.bf16.bf16.f32 {%0,%1,%2,%3}, {%4,%5,%6,%7}, {%8,%9}, {%0,%1,%2,%3};"
        : "+f"(c[0]), "+f"(c[1]), "+f"(c[2]), "+f"(c[3]) : "r"(a0), "r"(a1), "r"(a2), "r"(a3), "r"(b0), "r"(b1));
}
__device__ __forceinline__ void mma_1688(float (&c)[4], uint32_t a0, uint32_t a1, uint32_t b0) {
    asm("mma.sync.aligned.m16n8k8.row.col.f32.bf16.bf16.f32 {%0,%1,%2,%3}, {%4,%5}, {%6}, {%0,%1,%2,%3};"
        : "+f"(c[0]), "+f"(c[1]), "+f"(c[2]), "+f"(c[3]) : "r"(a0), "r"(a1), "r"(b0));
}
__device__ __forceinline__ void qk_tile(float (&c)[4], const uint4& q0, const uint4& q1, const uint4& k, float init) {
    c[0] = c[1] = c[2] = c[3] = init;
    mma_16816(c, q0.x, q0.y, q0.z, q0.w, k.x, k.y);
    mma_16816(c, q1.x, q1.y, q1.z, q1.w, k.z, k.w);
}
__device__ __forceinline__ uint32_t scaled_logits(bool first, float a0, float a1, float b0, float b1) {
    return mul2_bf16x2(pack_bf16(first ? a0 : b0, first ? a1 : b1), 0x3e353e35u, 0x379e379eu);
}
template <typename T> __device__ __forceinline__ T uniform(T v) { return __shfl_sync(0xffffffffu, v, 0); }

__device__ __forceinline__ void attention(const CUtensorMap* maps, uint32_t base, uint32_t zero, int grp, int warp, int lane) {
    constexpr float LOG2E = 1.4426950408889634f;
    const int g = lane >> 2, t = lane & 3;
    const bool up0 = 2 * t > g, up1 = 2 * t + 1 > g;
    const uint32_t keep = (up0 ? 0x0000ffffu : 0u) | (up1 ? 0xffff0000u : 0u);
    const uint32_t buf = base + warp * 2 * ATT_SLOT, bar = base + AUX_OFF + warp * 16;
    const uint32_t qoff = (lane & 15) * 128 + (((lane >> 4) ^ (lane & 7)) << 4);
    const uint32_t koff = 2048 + (lane & 7) * 128 + (((lane >> 3) ^ (lane & 7)) << 4);
    const uint32_t rest_bar = base + AUX_OFF + 192;
    const int col = uniform(grp * 256), first = uniform((warp / 3 * 32 + warp % 3 * 11) * 16);
    const CUtensorMap* const mqk = reinterpret_cast<const CUtensorMap*>(uniform(reinterpret_cast<uint64_t>(maps)));
    const CUtensorMap *const mv = mqk + 1, *const mo = mqk + 2;
    const uint64_t pol = policy(P_QKV);
    uint4 kp[2], vp[2];
    uint32_t l0[2], l1[2], m[2];
    float s[2][3][4];
    auto scores = [&](uint32_t st, int row) {
        const float before = (row & 1023) == 0 ? -5.656854e9f : 0.f;
#pragma unroll
        for (int h = 0; h < 2; h++) {
            const uint4 q0 = ldsm4(st + (qoff ^ (h * 64))), q1 = ldsm4(st + (qoff ^ (h * 64 + 32)));
            const uint4 k0 = ldsm4(st + (koff ^ (h * 64))), k1 = ldsm4(st + 1024 + (koff ^ (h * 64)));
            qk_tile(s[h][0], q0, q1, kp[h], before);
            qk_tile(s[h][1], q0, q1, k0, 0.f);
            qk_tile(s[h][2], q0, q1, k1, 0.f);
            kp[h] = k1;
        }
    };
    auto logits = [&]() {
#pragma unroll
        for (int h = 0; h < 2; h++) {
            l0[h] = scaled_logits(up0, s[h][0][0], s[h][1][2], s[h][1][0], s[h][2][2]);
            l1[h] = scaled_logits(up1, s[h][0][1], s[h][1][3], s[h][1][1], s[h][2][3]);
            m[h] = max_bf16x2(l0[h], l1[h]);
            m[h] = max_bf16x2(m[h], __shfl_xor_sync(0xffffffffu, m[h], 1));
        }
    };
    auto row_max = [&]() {
#pragma unroll
        for (int h = 0; h < 2; h++) m[h] = max_bf16x2(m[h], __shfl_xor_sync(0xffffffffu, m[h], 2));
    };
    auto next = [](uint32_t p) {
        return (0x80200400u >> (p >> 4 & 31) & 1) > (p >> 15 & 1) ? p + (64 << 16) + 0x8000 : (p + 16) & ~0x8800u;
    };
    auto exchange = [&](uint32_t st, uint32_t b, uint32_t po, uint32_t pv, uint32_t pq) {
        asm volatile("{\n.reg .pred e, p, q;\n"
            "fence.proxy.async.shared::cta;\n"
            "bar.warp.sync 0xffffffff;\n"
            "elect.sync _|e, 0xffffffff;\n"
            "setp.eq.and.b32 p, %12, 0, e;\n"
            "setp.lt.and.s32 q, %8, %13, e;\n"
            "@q mbarrier.arrive.expect_tx.shared::cta.b64 _, [%2], 6144;\n"
            "@q cp.async.bulk.tensor.3d.shared::cluster.global.mbarrier::complete_tx::bytes.L2::cache_hint [%0], [%3, {%6, %7, %14}], [%2], %15;\n"
            "@q cp.async.bulk.tensor.2d.shared::cluster.global.mbarrier::complete_tx::bytes.L2::cache_hint [%0 + 4096], [%4, {%8, %9}], [%2], %15;\n"
            "@e cp.async.bulk.wait_group.read 0;\n"
            "@p cp.async.bulk.tensor.2d.global.shared::cta.bulk_group [%5, {%10, %11}], [%1 + 6144];\n"
            "@e cp.async.bulk.commit_group;\n"
            "bar.warp.sync 0xffffffff;\n}"
            :: "r"(st), "r"(st ^ ATT_SLOT), "r"(b), "l"(mqk), "l"(mv), "l"(mo), "r"(pq >> 16), "r"(pq & 2047),
               "r"((pv >> 16) + 2 * DM), "r"(pv & 2047), "r"(po >> 16), "r"(po & 2047), "r"(po & 0x8000),
               "r"(col + 256 + 2 * DM), "r"(0), "l"(pol) : "memory");
    };
    auto publish = [&](auto pending, int part) {
        asm volatile("{\n.reg .pred e;\n.reg .u32 n;\n"
            "elect.sync _|e, 0xffffffff;\n"
            "cp.async.bulk.wait_group %2;\n"
            "@e atom.acq_rel.cta.shared.add.u32 n, [%1], 1;\n"
            "setp.eq.and.u32 e, n, 11, e;\n"
            "@e red.release.gpu.global.add.u32 [%0], 1;\n}"
            :: "l"(g_flags + F_O * 512 + part * 32), "r"(rest_bar + 8 + part * 4), "n"(pending.value) : "memory");
    };
    const unsigned epoch = __ldcg(g_epoch + blockIdx.x * 16) + 1;
    if (elect_one()) {
        mbar_init(bar, 1); mbar_init(bar + 8, 1);
        if (warp == 2) { mbar_init(rest_bar, 32); sts64f(rest_bar + 8, 0.f, 0.f); }
        asm volatile("fence.mbarrier_init.release.cluster;" ::: "memory");
        prefetch_map(mqk); prefetch_map(mv); prefetch_map(mo);
    }
    __syncthreads();
    if (elect_one()) {
        g_epoch[blockIdx.x * 16] = epoch;
        flag_wait(g_flags + F_QKV * 512 + grp * 32, epoch * CNT_QKV);
        fence_proxy_async();
        mbar_expect_tx(bar + 8, 8192);
        tma_3d(buf + ATT_SLOT, mqk, bar + 8, col, first, 0, pol);
        tma_2d(buf + ATT_SLOT + 4096, mv, bar + 8, col + 2 * DM, first - 16, policy(false));
        tma_2d(buf + ATT_SLOT + 6144, mv, bar + 8, col + DM, first - 16, policy(false));
        mbar_expect_tx(bar, 6144);
        tma_3d(buf, mqk, bar, col, first + 16, 0, pol);
        tma_2d(buf + 4096, mv, bar, col + 2 * DM, first, pol);
        if (warp == 0) TRACE(9);
    }
    __syncwarp();
    mbar_wait(bar + 8, 0);
#pragma unroll
    for (int h = 0; h < 2; h++) {
        kp[h] = ldsm4(buf + ATT_SLOT + 5120 + (koff ^ (h * 64)));
        vp[h] = ldsm4_t(buf + ATT_SLOT + 3072 + (koff ^ (h * 64)));
    }
    scores(buf + ATT_SLOT, first);
    uint32_t pm = 0x8000, p0 = col << 16 | first, p1 = p0 + 16, p2 = p0 + 32, p3 = p0 + 48;
    exchange(buf + ATT_SLOT, bar + 8, pm, p1, p2);
    logits();
    row_max();
    uint32_t st = buf, b = bar, cnt = 1;
    const uint32_t relay = warp == 2 ? 6 : 0;
    bool ready = mbar_try_wait(b, 0);
#pragma unroll 1
    while (p0 >> 16 < col + 256) {
        uint32_t pa[2], pb[2];
        if (!ready) mbar_wait(b, (cnt >> 1) & 1);
        uint4 v[2][2];
#pragma unroll
        for (int h = 0; h < 2; h++) {
            const float ma = -LOG2E * bf_lo(m[h]), mb = -LOG2E * bf_hi(m[h]);
            const float a0 = ex2_fast(fmaf(bf_lo(l0[h]), LOG2E, ma)), a1 = ex2_fast(fmaf(bf_lo(l1[h]), LOG2E, ma));
            const float b0 = ex2_fast(fmaf(bf_hi(l0[h]), LOG2E, mb)), b1 = ex2_fast(fmaf(bf_hi(l1[h]), LOG2E, mb));
            float sum[4] = {0.f, 0.f, 0.f, 0.f};
            mma_1688(sum, pack_bf16(a0, a1), pack_bf16(b0, b1), 0x3f803f80u);
            const float ra = rcp_fast(sum[0]), rb = rcp_fast(sum[2]);
            pa[h] = pack_bf16(a0 * ra, a1 * ra);
            pb[h] = pack_bf16(b0 * rb, b1 * rb);
        }
        scores(st, p1);
#pragma unroll
        for (int h = 0; h < 2; h++) {
            v[h][0] = ldsm4_t(st + 4096 + (qoff ^ (h * 64)));
            v[h][1] = ldsm4_t(st + 4096 + (qoff ^ (h * 64 + 32)));
        }
        if (cnt == relay) {
            flag_wait<true>(g_flags + F_QKV * 512 + 128 + grp * 32, epoch * CNT_QKV);
            fence_proxy_async();
            mbar_arrive(rest_bar);
        }
        if (cnt == 8) {
#pragma unroll 1
            for (int spins = 0; !__all_sync(0xffffffffu, mbar_try_wait(rest_bar, 0)) && spins < (1 << 17); spins++) {}
        }
        if (cnt == 37) publish(std::integral_constant<int, 1>(), 0);
        exchange(st, b, pm, p2, p3);
        pm = p0; p0 = p1; p1 = p2; p2 = p3; p3 = next(p3);
        logits();
        float o[2][4][4];
#pragma unroll
        for (int h = 0; h < 2; h++) {
            const uint32_t prev[4] = {vp[h].x, vp[h].y, vp[h].z, vp[h].w};
            const uint32_t own[8] = {v[h][0].x, v[h][0].y, v[h][0].z, v[h][0].w, v[h][1].x, v[h][1].y, v[h][1].z, v[h][1].w};
            const uint32_t a0 = pa[h] & keep, a1 = pa[h] & ~keep, a2 = pb[h] & keep, a3 = pb[h] & ~keep;
            const uint32_t z0 = pa[h] & zero, z1 = pb[h] & zero;
#pragma unroll
            for (int j = 0; j < 4; j++) {
                o[h][j][0] = o[h][j][1] = o[h][j][2] = o[h][j][3] = 0.f;
                mma_1688(o[h][j], a0, z0, prev[j]);
                mma_16816(o[h][j], a1, a2, z1, a3, own[2 * j], own[2 * j + 1]);
            }
            vp[h] = make_uint4(own[1], own[3], own[5], own[7]);
        }
        row_max();
        b ^= 8; cnt++;
        ready = mbar_try_wait(b, (cnt >> 1) & 1);
#pragma unroll
        for (int h = 0; h < 2; h++) {
#pragma unroll
            for (int d = 0; d < 2; d++)
                asm volatile("stmatrix.sync.aligned.m8n8.x4.shared.b16 [%0], {%1,%2,%3,%4};"
                             :: "r"(st + 6144 + (qoff ^ (h * 64 + d * 32))),
                                "r"(pack_bf16(o[h][2 * d][0], o[h][2 * d][1])), "r"(pack_bf16(o[h][2 * d][2], o[h][2 * d][3])),
                                "r"(pack_bf16(o[h][2 * d + 1][0], o[h][2 * d + 1][1])),
                                "r"(pack_bf16(o[h][2 * d + 1][2], o[h][2 * d + 1][3])) : "memory");
        }
        st ^= ATT_SLOT;
    }
    exchange(st, b, pm, p0, p0);
    publish(std::integral_constant<int, 0>(), 1);
    if (threadIdx.x == 0) TRACE(10);
}

struct Params {
    CUtensorMap x, xn, wqkv, wg, wu, qk, v, o, a2, wo, wd, out;
    const __nv_bfloat16* px;
    uint32_t zero;
};

__device__ __forceinline__ bool tile_is_qkv(int nt) { return nt < 4 || (nt >= 8 && nt < 16); }
__device__ __forceinline__ int tile_index(int nt) { return nt < 4 ? nt + 8 : (nt < 8 ? nt - 4 : (nt < 16 ? nt - 8 : nt - 12)); }

__global__ void __cluster_dims__(2, 1, 1) __launch_bounds__(384, 1)
fused_kernel(const __grid_constant__ Params prm) {
    extern __shared__ __align__(1024) uint8_t smem_raw[];
    const uint32_t base = smem_u32(smem_raw) & ~1023u;
    const uint32_t bars = base + BAR_OFF;
    auto full1 = [&](int s) { return bars + s * 8; };
    auto empty1 = [&](int s) { return bars + 32 + s * 8; };
    auto full2 = [&](int s) { return bars + 64 + s * 8; };
    auto empty2 = [&](int s) { return bars + 128 + s * 8; };
    const uint32_t sig_bar = bars + 192, dep_bar = bars + 256, cs_bar = bars + 304, fold_bar = bars + 320, x_bar = bars + 328;
    const uint32_t colsum = bars + 512, stats = bars + 1536;
    auto stage2 = [&](int q) { return base + q * G2_STAGE_BYTES; };
    const uint32_t aux = base + AUX_OFF;

    const int warp = __shfl_sync(0xffffffffu, threadIdx.x >> 5, 0);
    const int lane = threadIdx.x & 31;
    const int rank = blockIdx.x & 1;
    const int mblk = ((blockIdx.x >> 1) & 7) * 2 + rank;
    const int nslot = blockIdx.x >> 4;

    if (blockIdx.x >= NGEMM) {
        if (threadIdx.x == 0) { TRACE_GT(0); TRACE(1); }
        attention(&prm.qk, (base + 2 * ATT_SLOT - 1) & ~(2u * ATT_SLOT - 1), prm.zero, blockIdx.x - NGEMM, warp, lane);
    } else if (warp >= 8) {
        unsigned* const flags = g_flags + mblk * 32;
        const CUtensorMap* const w0 = nslot < 4 ? &prm.wqkv : (rank ? &prm.wu : &prm.wg);
        if (elect_one()) {
            if (warp == 8) {
                TRACE_GT(0); TRACE(1);
                prefetch_map(&prm.x); prefetch_map(w0);
                for (int s = 0; s < G1_STAGES; s++) { mbar_init(full1(s), 1); mbar_init(empty1(s), 4); }
            } else if (warp == 9) {
                for (int s = 0; s < G2_STAGES; s++) { mbar_init(full2(s), 1); mbar_init(empty2(s), 4); }
            } else if (warp == 10) {
                for (int s = 0; s < 7; s++) mbar_init(sig_bar + s * 8, 8);
                mbar_init(fold_bar, 3); mbar_init(x_bar, 1);
            } else {
                for (int s = 0; s < 8; s++) mbar_init(dep_bar + s * 8, 1);
            }
            asm volatile("fence.mbarrier_init.release.cluster;" ::: "memory");
        }
        __syncwarp();
        asm volatile("barrier.cluster.arrive.relaxed.aligned;" ::: "memory");
        if (warp == 8 && lane == 0) {
            mbar_expect_tx(full1(0), G1_STAGE_BYTES);
            tma_2d(base, &prm.x, full1(0), 0, mblk * 128, policy(P_X));
            prefetch_3d(w0, 0, nslot < 4 ? 32 + nslot * 4 + rank * 2 : nslot * 2 - 8, policy(P_W1));
            TRACE(15);
        }
        asm volatile("setmaxnreg.dec.sync.aligned.u32 %0;" :: "n"(AUX_REGS));
        asm volatile("barrier.cluster.wait.acquire.aligned;" ::: "memory");

        if (warp == 8) {
            if (lane == 0) {
                TRACE(2);
                auto load_b1 = [&](int s, int nt, int k) {
                    const uint32_t dst = base + s * G1_STAGE_BYTES + A_BYTES + rank * 16384;
                    if (tile_is_qkv(nt)) tma_3d_mc(dst, &prm.wqkv, full1(s), k * 64, tile_index(nt) * 4 + rank * 2, policy(P_W1));
                    else tma_3d_mc(dst, rank ? &prm.wu : &prm.wg, full1(s), k * 64, tile_index(nt) * 2, policy(P_W1));
                };
                load_b1(0, nslot, 0);
                uint32_t ph = 1;
                for (int it = 1; it < G1_TILES * G1_KSTEPS; it++) {
                    const int s = it & 3, k = it & 15;
                    if (it == G1_STAGES) {
                        prefetch_map(&prm.xn); prefetch_map(&prm.wqkv); prefetch_map(&prm.wu); prefetch_map(&prm.wg);
                        prefetch_map(&prm.a2); prefetch_map(&prm.wo); prefetch_map(&prm.wd); prefetch_map(&prm.out);
                    }
                    if (it == G1_KSTEPS) { TRACE(14); mbar_wait(dep_bar, 0); TRACE(3); }
                    mbar_wait(empty1(s), ph);
                    mbar_expect_tx(full1(s), G1_STAGE_BYTES);
                    tma_2d(base + s * G1_STAGE_BYTES, it < G1_KSTEPS ? &prm.x : &prm.xn, full1(s), k * 64, mblk * 128,
                           policy(it < G1_KSTEPS ? P_X : (P_XN4 && it >= (G1_TILES - 1) * G1_KSTEPS)));
                    load_b1(s, (it >> 4) * 8 + nslot, k);
                    if (s == 3) ph ^= 1;
                }
                mbar_expect_tx(x_bar, 32768);
                tma_2d(aux, &prm.x, x_bar, nslot * 128, mblk * 128, policy(P_X));
                tma_2d(aux + 16384, &prm.x, x_bar, nslot * 128 + 64, mblk * 128, policy(P_X));
                TRACE(4);
                mbar_wait(dep_bar + 8, 0);
                TRACE(5);
                int q = 0; uint32_t ph2 = 1;
                for (int u = 0; u < G2_KSTEPS; u++) {
                    if (u == G2_LATE || u == G2_DSTEPS || u == G2_LAST) {
                        TRACE(u == G2_LATE ? 6 : (u == G2_DSTEPS ? 32 : 40));
                        mbar_wait(dep_bar + (u == G2_LATE ? 16 : (u == G2_DSTEPS ? 24 : 32)), 0);
                        TRACE(u == G2_LATE ? 7 : (u == G2_DSTEPS ? 33 : 41));
                    }
                    if (u < G2_STAGES) {
                        if (u == 0) mbar_wait(empty1(0), ph);
                        if (u == 1) mbar_wait(empty1(1), ph);
                        if (u == 3) mbar_wait(empty1(2), ph);
                        if (u == 4) mbar_wait(empty1(3), ph);
                    } else {
                        mbar_wait(empty2(q), ph2);
                    }
                    const uint32_t sa = stage2(q);
                    const bool down = u < G2_DSTEPS;
                    const int k = down ? u : (u - G2_DSTEPS) % 4 * 4 + (u - G2_DSTEPS) / 4;
                    mbar_expect_tx(full2(q), G2_STAGE_BYTES);
                    tma_3d(sa, &prm.a2, full2(q), (down ? DM : 0) + k * 64, 0, mblk * 64, policy(P_A2));
                    tma_5d_mc(sa + A_BYTES + rank * 8192, down ? &prm.wd : &prm.wo, full2(q), nslot * 128 + rank * 64, k * 2, policy(P_W2));
                    if (++q == G2_STAGES) { q = 0; ph2 ^= 1; }
                }
                TRACE(8);
            }
        } else if (warp == 9) {
            if (lane == 0) {
                const unsigned epoch = __ldcg(g_epoch + blockIdx.x * 16 + 2) + 1;
                mbar_wait(sig_bar, 0);
                TRACE(11);
                flag_add(flags + F_LN * 512);
                TRACE(42);
                flag_wait(flags + F_LN * 512, epoch * CNT_LN);
                fence_proxy_async();
                mbar_arrive(dep_bar);
                mbar_expect_tx(fold_bar, 1024);
                bulk_load(stats, g_stats + mblk * 128, 1024, fold_bar);
                g_epoch[blockIdx.x * 16 + 2] = epoch;
                for (int p = nslot < 4 ? 2 : 1; p < 7; p++) {
                    mbar_wait(sig_bar + p * 8, 0);
                    if (p == 2) TRACE(37);
                    flag_add(p == 2 || p == 3 ? g_flags + F_QKV * 512 + (p * 4 - 8 + (nslot & 3)) * 32
                                              : flags + (p < 6 ? F_EARLY : F_LATE) * 512);
                    if (p == 2) TRACE(43);
                }
            }
        } else {
            const int w = warp - 10;
            const unsigned epoch = __ldcg(g_epoch + blockIdx.x * 16 + w) + 1;
            unsigned* const cs_flag = g_flags + F_CS * 512 + (nslot * 2 + w) * 32;
            mbar_wait(empty1(1), 0);
            if (elect_one()) {
                mbar_expect_tx(cs_bar + w * 8, 16384);
                tma_3d(aux + w * 16384, nslot < 4 ? &prm.wqkv : (w ? &prm.wu : &prm.wg), cs_bar + w * 8, 0, mblk * 64,
                       nslot < 4 ? 32 + nslot * 4 + w * 2 : nslot * 2 - 8, policy(P_W1));
            }
            float cs[8];
#pragma unroll
            for (int d = 0; d < 8; d++) cs[d] = 0.f;
            mbar_wait(cs_bar + w * 8, 0);
            const uint32_t wa = aux + w * 16384 + (lane & 8) * 1024 + (lane >> 4) * 128 + (((lane & 7) ^ (lane >> 4)) << 4);
#pragma unroll 1
            for (int i = 0; i < 8; i++) {
#pragma unroll
                for (int j = 0; j < 4; j++) {
                    float f[8];
                    unpack8(lds128((wa ^ (j * 32)) + i * 1024 + j * 256), f);
#pragma unroll
                    for (int d = 0; d < 8; d++) cs[d] += f[d];
                }
            }
#pragma unroll
            for (int d = 0; d < 8; d++) cs[d] += __shfl_xor_sync(0xffffffffu, cs[d], 16);
            *reinterpret_cast<float4*>(g_colsum + mblk * 2048 + nslot * 256 + w * 128 + (lane & 15) * 8 + (lane >> 4) * 4) =
                lane < 16 ? make_float4(cs[0], cs[1], cs[2], cs[3]) : make_float4(cs[4], cs[5], cs[6], cs[7]);
            __syncwarp();
            if (lane == 0) {
                if (w == 0) TRACE(34);
                flag_add(cs_flag);
                flag_wait(cs_flag, epoch * CNT_CS);
            }
            __syncwarp();
            const float4* gp = reinterpret_cast<const float4*>(g_colsum + nslot * 256 + w * 128) + lane;
            float4 c = make_float4(0.f, 0.f, 0.f, 0.f);
#pragma unroll 8
            for (int m = 0; m < 16; m++) {
                const float4 a = __ldcg(gp + m * 512);
                c.x += a.x; c.y += a.y; c.z += a.z; c.w += a.w;
            }
            const uint32_t ca = colsum + (w * 8 + (lane >> 2)) * 64 + (lane & 1) * 32 + (lane & 2) * 4;
            sts64f(ca, c.x, c.y);
            sts64f(ca + 16, c.z, c.w);
            __syncwarp();
            if (lane == 0) {
                mbar_arrive(fold_bar);
                g_epoch[blockIdx.x * 16 + w] = epoch;
                if (w == 0) {
                    TRACE(35);
                    flag_wait(flags + F_EARLY * 512, epoch * CNT_EARLY);
                    fence_proxy_async(); mbar_arrive(dep_bar + 8);
                    flag_wait(flags + F_LATE * 512, epoch * CNT_LATE);
                    fence_proxy_async(); mbar_arrive(dep_bar + 16);
                    flag_wait(g_flags + F_O * 512, epoch * CNT_O);
                    fence_proxy_async(); mbar_arrive(dep_bar + 24);
                    flag_wait(g_flags + F_O * 512 + 32, epoch * CNT_O);
                    fence_proxy_async(); mbar_arrive(dep_bar + 32);
                }
            }
        }
    } else {
        asm volatile("barrier.cluster.arrive.relaxed.aligned;" ::: "memory");
        asm volatile("setmaxnreg.inc.sync.aligned.u32 %0;" :: "n"(CONSUMER_REGS));
        const int wg = __shfl_sync(0xffffffffu, threadIdx.x >> 7, 0);
        const int cw = threadIdx.x >> 5;
        const int tid = threadIdx.x & 127;
        float acc[128];
        uint32_t pk[64];
#pragma unroll
        for (int i = 0; i < 64; i++) asm volatile("mov.b32 %0, 0;" : "=r"(pk[i]));
#pragma unroll
        for (int i = 0; i < 128; i++) asm volatile("mov.b32 %0, 0;" : "=f"(acc[i]));
        asm volatile("barrier.cluster.wait.acquire.aligned;" ::: "memory");

        const int orow = ((lane >> 2) & 1) * (SEQ / 2) + mblk * 64 + cw * 8 + (lane >> 3);
        __nv_bfloat16* optr = nullptr;
        auto release = [&](uint32_t bar) { if (tid < 2) mbar_arrive_cluster(bar, tid); };
        auto chunk_geglu = [&](int j) {
            const int c = j >> 1, h = j & 1;
            uint4 v;
            v.x = geglu2(pk[8 * c + h], pk[32 + 8 * c + h]);
            v.y = geglu2(pk[8 * c + 2 + h], pk[32 + 8 * c + 2 + h]);
            v.z = geglu2(pk[8 * c + 4 + h], pk[32 + 8 * c + 4 + h]);
            v.w = geglu2(pk[8 * c + 6 + h], pk[32 + 8 * c + 6 + h]);
            *reinterpret_cast<uint4*>(optr + h * 4 * K2 + c * 32) = v;
        };
        auto chunk_qkv = [&](int c) {
            *reinterpret_cast<uint4*>(optr + c * 32) = make_uint4(pk[8 * c], pk[8 * c + 2], pk[8 * c + 4], pk[8 * c + 6]);
            *reinterpret_cast<uint4*>(optr + 4 * NQKV + c * 32) = make_uint4(pk[8 * c + 1], pk[8 * c + 3], pk[8 * c + 5], pk[8 * c + 7]);
        };
        auto signal_stores = [&](int p) { __syncwarp(); if (lane == 0) mbar_arrive(sig_bar + p * 8); };

        auto chunk_ln = [&](int k) {
            const int row = mblk * 128 + nslot * 16 + cw * 2;
            float* const mo = reinterpret_cast<float*>(pk + 32);
            if (k == 0) {
                const uint4* xp = reinterpret_cast<const uint4*>(prm.px + (size_t)row * DM) + lane;
#pragma unroll
                for (int i = 0; i < 8; i++) {
                    const uint4 v = ldg_stream(xp + i * 32, policy(P_X));
                    pk[4 * i] = v.x; pk[4 * i + 1] = v.y; pk[4 * i + 2] = v.z; pk[4 * i + 3] = v.w;
                }
            } else if (k >= LN_STEP && k < LN_STEP + 3) {
                if (k == LN_STEP) {
                    mo[0] = bf_lo(uniform(pk[0])); mo[1] = bf_lo(uniform(pk[16]));
                    mo[2] = mo[3] = mo[4] = mo[5] = 0.f;
                }
#pragma unroll
                for (int i = (k - LN_STEP) * 11; i < (k - LN_STEP) * 11 + 11 && i < 32; i++) {
                    const int r = i & 1;
                    const uint32_t w = pk[r * 16 + i / 2];
                    const float lo = bf_lo(w) - mo[r], hi = bf_hi(w) - mo[r];
                    mo[2 + r] += lo + hi;
                    mo[4 + r] = fmaf(hi, hi, fmaf(lo, lo, mo[4 + r]));
                }
            } else if (k == LN_STEP + 3) {
                const bool second = lane & 16;
                float m1 = (second ? mo[3] : mo[2]) + __shfl_xor_sync(0xffffffffu, second ? mo[2] : mo[3], 16);
                float m2 = (second ? mo[5] : mo[4]) + __shfl_xor_sync(0xffffffffu, second ? mo[4] : mo[5], 16);
#pragma unroll
                for (int o = 8; o > 0; o >>= 1) {
                    m1 += __shfl_xor_sync(0xffffffffu, m1, o);
                    m2 += __shfl_xor_sync(0xffffffffu, m2, o);
                }
                m1 *= 1.f / DM;
                const float var = fmaxf(fmaf(-m1, m1, m2 * (1.f / DM)), 0.f);
                const float mean = round_bf16((second ? mo[1] : mo[0]) + m1);
                const float inv = 1.f / round_bf16(sqrtf(round_bf16(round_bf16(var) + 1e-5f)));
                if ((lane & 15) == 0) g_stats[row + second] = make_float2(-mean, inv);
                pk[32] = __float_as_uint(mean);
                pk[33] = pack_bf16(inv - round_bf16(inv), inv);
            } else if (k == LN_STEP + 4) {
#pragma unroll
                for (int r = 0; r < 2; r++) {
                    const uint32_t mean = __byte_perm(__shfl_sync(0xffffffffu, pk[32], r * 16), 0, 0x3232);
                    const uint32_t inv = __shfl_sync(0xffffffffu, pk[33], r * 16);
                    const uint32_t ih = __byte_perm(inv, 0, 0x3232), il = __byte_perm(inv, 0, 0x1010);
#pragma unroll
                    for (int i = 0; i < 4; i++) {
                        uint32_t o[4];
#pragma unroll
                        for (int j = 0; j < 4; j++) o[j] = mul2_bf16x2(sub_bf16x2(pk[r * 16 + i * 4 + j], mean), ih, il);
                        *reinterpret_cast<uint4*>(g_xn + (size_t)(row + r) * DM + i * 256 + lane * 8) = make_uint4(o[0], o[1], o[2], o[3]);
                    }
                }
                signal_stores(0);
            } else if (k == G1_KSTEPS - 1) {
                mbar_wait(fold_bar, 0);
#pragma unroll
                for (int j = 0; j < 16; j++) {
                    const uint4 c = lds128(colsum + j * 64 + (lane & 3) * 16);
                    pk[4 * j] = c.x; pk[4 * j + 1] = c.y; pk[4 * j + 2] = c.z; pk[4 * j + 3] = c.w;
                }
            }
        };

        bool gated = false;
#pragma unroll 1
        for (int t = 0; t < G1_TILES; t++) {
#pragma unroll
            for (int k = 0; k < G1_KSTEPS; k++) {
                const int s = k & 3;
                mbar_wait(full1(s), (k >> 2) & 1);
                if (t == 0 && k == 0 && threadIdx.x == 0) TRACE(12);
                if (TRACE_T >= 0 && t == TRACE_T && threadIdx.x == 0) TRACE(44 + k);
                if (wg == 1 && k == G1_KSTEPS - G1_SKEW) asm volatile("bar.sync 1, 256;" ::: "memory");
                const uint64_t da = desc_a(base + s * G1_STAGE_BYTES + wg * 8192);
                const uint64_t db = desc_b(base + s * G1_STAGE_BYTES + A_BYTES);
                wg_fence();
#pragma unroll
                for (int kk = 0; kk < 4; kk++) wgmma_n256(acc, da + kk * 2, db + kk * 128, (k | kk) != 0);
                wg_commit();
                if (wg == 0 && k == G1_KSTEPS - 1) asm volatile("bar.arrive 1, 256;" ::: "memory");
                if (t == 0) chunk_ln(k);
                if (k >= 1 && k <= 8 && gated) {
                    chunk_geglu(k - 1);
                    if (k == 8) signal_stores(t == 1 ? 1 : t + 1);
                }
                if (t != 0 && !gated) {
                    if (k == 0) { chunk_qkv(0); chunk_qkv(1); }
                    if (k >= 4 && k <= 9) chunk_qkv(k - 2);
                    if ((k == 0 || k == 9) && t == 2) signal_stores(k ? 3 : 2);
                }
                wg_wait<1>();
                if (k > 0) release(empty1((k - 1) & 3));
            }
            wg_wait<0>();
            fence_regs(acc);
            release(empty1(3));
            if (t == 0) {
                const uint32_t sp = stats + (cw * 16 + (lane >> 2)) * 8;
                const float2 sa = lds64f(sp), sb = lds64f(sp + 64);
#pragma unroll
                for (int j = 0; j < 16; j++) {
                    const float c0 = __uint_as_float(pk[4 * j]), c1 = __uint_as_float(pk[4 * j + 1]);
                    const float c2 = __uint_as_float(pk[4 * j + 2]), c3 = __uint_as_float(pk[4 * j + 3]);
                    const float* a = acc + 8 * j;
                    pk[4 * j] = pack_bf16(fmaf(sa.x, c0, a[0]) * sa.y, fmaf(sa.x, c1, a[1]) * sa.y);
                    pk[4 * j + 1] = pack_bf16(fmaf(sb.x, c0, a[2]) * sb.y, fmaf(sb.x, c1, a[3]) * sb.y);
                    pk[4 * j + 2] = pack_bf16(fmaf(sa.x, c2, a[4]) * sa.y, fmaf(sa.x, c3, a[5]) * sa.y);
                    pk[4 * j + 3] = pack_bf16(fmaf(sb.x, c2, a[6]) * sb.y, fmaf(sb.x, c3, a[7]) * sb.y);
                }
            } else {
#pragma unroll
                for (int i = 0; i < 64; i++) pk[i] = pack_bf16(acc[2 * i], acc[2 * i + 1]);
            }
            const int nt = t * 8 + nslot;
            gated = !tile_is_qkv(nt);
            optr = !gated ? g_qkv + (size_t)orow * NQKV + tile_index(nt) * 256 + (lane & 3) * 8
                                : g_a2 + (size_t)orow * K2 + DM + tile_index(nt) * 128 + (lane & 3) * 8;
            if (tid == 0) TRACE(16 + wg * 8 + t);
        }

        float accd[64], accs[64];
#pragma unroll
        for (int i = 0; i < 64; i++) accd[i] = 0.f;
#pragma unroll
        for (int u = 0; u < 9; u++) {
            const int q = u % G2_STAGES;
            mbar_wait(full2(q), (u / G2_STAGES) & 1);
            const uint64_t da = desc_a(stage2(q) + wg * 8192), db = desc_b(stage2(q) + A_BYTES);
            wg_fence();
#pragma unroll
            for (int kk = 0; kk < 4; kk++) wgmma_n128(accd, da + kk * 2, db + kk * 128, (u | kk) != 0);
            wg_commit();
            if (u >= 1) { chunk_geglu(u - 1); if (u == 8) signal_stores(6); }
            wg_wait<1>();
            if (u > 0) release(empty2((u - 1) % G2_STAGES));
        }
        {
            int q = 9 % G2_STAGES, qp = 8 % G2_STAGES; uint32_t ph = (9 / G2_STAGES) & 1;
#pragma unroll 1
            for (int u = 9; u < G2_DSTEPS; u++) {
                mbar_wait(full2(q), ph);
                const uint64_t da = desc_a(stage2(q) + wg * 8192), db = desc_b(stage2(q) + A_BYTES);
                wg_fence();
#pragma unroll
                for (int kk = 0; kk < 4; kk++) wgmma_n128(accd, da + kk * 2, db + kk * 128, 1);
                wg_commit();
                wg_wait<1>();
                release(empty2(qp));
                qp = q;
                if (++q == G2_STAGES) { q = 0; ph ^= 1; }
            }
        }
        if (tid == 0) TRACE(16 + wg * 8 + 5);
#pragma unroll
        for (int i = 0; i < 64; i++) accs[i] = 0.f;
        uint32_t gk[32], xr[32];
        const uint32_t xs = aux + cw * 2048;
        const uint32_t xrow = xs + ((lane & 7) + ((lane >> 3) & 1) * 8) * 128;
        auto xaddr = [&](int j) { return xrow + (j >> 2) * 16384 + (((((j & 3) * 2) + (lane >> 4)) ^ (lane & 7)) << 4); };
#pragma unroll
        for (int u = G2_DSTEPS; u < G2_KSTEPS; u++) {
            const int q = u % G2_STAGES, v = u - G2_DSTEPS;
            mbar_wait(full2(q), (u / G2_STAGES) & 1);
            if (G2_SKEW > 0 && wg == 1 && u == G2_KSTEPS - G2_SKEW) asm volatile("bar.sync 1, 256;" ::: "memory");
            const uint64_t da = desc_a(stage2(q) + wg * 8192), db = desc_b(stage2(q) + A_BYTES);
            wg_fence();
#pragma unroll
            for (int kk = 0; kk < 4; kk++) wgmma_n128(accs, da + kk * 2, db + kk * 128, (v | kk) != 0);
            wg_commit();
            if (G2_SKEW > 0 && wg == 0 && u == G2_KSTEPS - 1) asm volatile("bar.arrive 1, 256;" ::: "memory");
            if (v >= 1 && v <= 8) {
#pragma unroll
                for (int i = 4 * (v - 1); i < 4 * v; i++) {
                    const uint32_t d2 = pack_bf16(accd[2 * i], accd[2 * i + 1]);
                    gk[i] = pack_bf16(silu(bf_lo(d2)), silu(bf_hi(d2)));
                }
            }
            if (v == 9) mbar_wait(x_bar, 0);
            if (v >= 9 && v <= 12) {
#pragma unroll
                for (int j = 2 * (v - 9); j < 2 * (v - 8); j++)
                    asm volatile("ldmatrix.sync.aligned.m8n8.x4.shared.b16 {%0,%1,%2,%3}, [%4];"
                                 : "=r"(xr[4 * j]), "=r"(xr[4 * j + 1]), "=r"(xr[4 * j + 2]), "=r"(xr[4 * j + 3])
                                 : "r"(xaddr(j)) : "memory");
            }
            wg_wait<1>();
            if (v == 0) fence_regs(accd);
            if (u - 1 + G2_STAGES < G2_KSTEPS) release(empty2((u - 1) % G2_STAGES));
        }
        wg_wait<0>();
        fence_regs(accs);
        if (tid == 0) TRACE(16 + wg * 8 + 6);
#pragma unroll
        for (int j = 0; j < 8; j++) {
            uint32_t r[4];
#pragma unroll
            for (int i = 0; i < 4; i++) {
                const int e = j * 4 + i;
                r[i] = add_bf16x2(xr[e], mul_bf16x2(pack_bf16(accs[2 * e], accs[2 * e + 1]), gk[e]));
            }
            asm volatile("stmatrix.sync.aligned.m8n8.x4.shared.b16 [%0], {%1,%2,%3,%4};"
                         :: "r"(xaddr(j)), "r"(r[0]), "r"(r[1]), "r"(r[2]), "r"(r[3]) : "memory");
            if (j == 3 || j == 7) {
                asm volatile("fence.proxy.async.shared::cta;" ::: "memory");
                __syncwarp();
                if (lane == 0) {
                    tma_store_2d(&prm.out, xs + (j >> 2) * 16384, nslot * 128 + (j >> 2) * 64, mblk * 128 + cw * 16);
                    asm volatile("cp.async.bulk.commit_group;" ::: "memory");
                }
            }
        }
        if (lane == 0) asm volatile("cp.async.bulk.wait_group.read 0;" ::: "memory");
        if (tid == 0) { TRACE(16 + wg * 8 + 7); if (wg == 1) TRACE_GT(13); }
    }
}

typedef CUresult (*EncodeFn)(CUtensorMap*, CUtensorMapDataType, cuuint32_t, void*, const cuuint64_t*, const cuuint64_t*,
                             const cuuint32_t*, const cuuint32_t*, CUtensorMapInterleave, CUtensorMapSwizzle,
                             CUtensorMapL2promotion, CUtensorMapFloatOOBfill);

void encode(EncodeFn fn, CUtensorMap* m, const void* ptr, int rank, const cuuint64_t* dims, const cuuint64_t* strides,
            const cuuint32_t* box) {
    const cuuint32_t es[5] = {1, 1, 1, 1, 1};
    fn(m, CU_TENSOR_MAP_DATA_TYPE_BFLOAT16, rank, const_cast<void*>(ptr), dims, strides, box, es,
       CU_TENSOR_MAP_INTERLEAVE_NONE, CU_TENSOR_MAP_SWIZZLE_128B, CU_TENSOR_MAP_L2_PROMOTION_L2_128B,
       CU_TENSOR_MAP_FLOAT_OOB_FILL_NONE);
}
void encode_2d(EncodeFn fn, CUtensorMap* m, const void* ptr, int cols, int box_rows) {
    const cuuint64_t dims[2] = {(cuuint64_t)cols, SEQ}, strides[1] = {(cuuint64_t)cols * 2};
    const cuuint32_t box[2] = {64, (cuuint32_t)box_rows};
    encode(fn, m, ptr, 2, dims, strides, box);
}
void encode_w1(EncodeFn fn, CUtensorMap* m, const void* ptr, int cols) {
    const cuuint64_t dims[3] = {64, DM, (cuuint64_t)cols / 64}, strides[2] = {(cuuint64_t)cols * 2, 128};
    const cuuint32_t box[3] = {64, 64, 2};
    encode(fn, m, ptr, 3, dims, strides, box);
}
void encode_qk(EncodeFn fn, CUtensorMap* m, const void* ptr) {
    const cuuint64_t dims[3] = {DM, SEQ, 3}, strides[2] = {NQKV * 2, DM * 2};
    const cuuint32_t box[3] = {64, 16, 2};
    encode(fn, m, ptr, 3, dims, strides, box);
}
void encode_a2(EncodeFn fn, CUtensorMap* m, const void* ptr) {
    const cuuint64_t dims[3] = {K2, 2, SEQ / 2}, strides[2] = {(cuuint64_t)SEQ * K2, K2 * 2};
    const cuuint32_t box[3] = {64, 2, 64};
    encode(fn, m, ptr, 3, dims, strides, box);
}
void encode_w2(EncodeFn fn, CUtensorMap* m, const void* ptr, int rows) {
    const cuuint64_t rb = DM * 2;
    const cuuint64_t dims[5] = {DM, 2, 4, 4, (cuuint64_t)rows / 32}, strides[4] = {rb, 8 * rb, 2 * rb, 32 * rb};
    const cuuint32_t box[5] = {64, 2, 4, 4, 2};
    encode(fn, m, ptr, 5, dims, strides, box);
}

}

extern "C" void kernel_launch(void* const* d_in, const int* in_sizes, int n_in, void* d_out, int out_size) {
    (void)in_sizes; (void)n_in; (void)out_size;
    static EncodeFn fn = nullptr;
    static void *p_xn = nullptr, *p_qkv = nullptr, *p_a2 = nullptr;
    if (!fn) {
        cudaDriverEntryPointQueryResult st;
        cudaGetDriverEntryPoint("cuTensorMapEncodeTiled", (void**)&fn, cudaEnableDefault, &st);
        cudaGetSymbolAddress(&p_xn, g_xn);
        cudaGetSymbolAddress(&p_qkv, g_qkv);
        cudaGetSymbolAddress(&p_a2, g_a2);
        cudaFuncSetAttribute(fused_kernel, cudaFuncAttributeMaxDynamicSharedMemorySize, SMEM_BYTES);
    }
    Params prm;
    encode_2d(fn, &prm.x, d_in[0], DM, 128);
    encode_2d(fn, &prm.xn, p_xn, DM, 128);
    encode_w1(fn, &prm.wqkv, d_in[1], NQKV);
    encode_w1(fn, &prm.wg, d_in[4], DF);
    encode_w1(fn, &prm.wu, d_in[5], DF);
    encode_qk(fn, &prm.qk, p_qkv);
    encode_2d(fn, &prm.v, p_qkv, NQKV, 16);
    encode_2d(fn, &prm.o, p_a2, K2, 16);
    encode_a2(fn, &prm.a2, p_a2);
    encode_w2(fn, &prm.wo, d_in[2], DM);
    encode_w2(fn, &prm.wd, d_in[6], DF);
    encode_2d(fn, &prm.out, d_out, DM, 16);
    prm.px = (const __nv_bfloat16*)d_in[0];
    prm.zero = 0;
    fused_kernel<<<NCTA, 384, SMEM_BYTES>>>(prm);
}
```

```cpp
#include <cuda_runtime.h>
#include <cuda_bf16.h>
#include <cuda.h>
#include <stdint.h>
#include <type_traits>

#define P_W1 1
#define P_X 1
#define P_XN4 1
#define P_W2 1
#define P_A2 1
#define P_QKV 1

#define LN_STEP 3
#define FOLD_STEP 14
#define CS_AT empty1(0)
#define PF_X 1
#define PF_W 8

namespace {

constexpr int SEQ = 2048, DM = 1024, DF = 3584, K2 = DM + DF, NQKV = 3 * DM;
constexpr int NGEMM = 128, NCTA = 132;
constexpr int G1_STAGES = 4, G1_STAGE_BYTES = 49152, G1_KSTEPS = 16, G1_TILES = 5;
constexpr int G2_STAGES = 6, G2_STAGE_BYTES = 32768, G2_KSTEPS = 72, G2_LATE = 40, G2_DSTEPS = 56, G2_LAST = 68;
constexpr int A_BYTES = 16384;
constexpr int AUX_OFF = G1_STAGES * G1_STAGE_BYTES;
constexpr int BAR_OFF = AUX_OFF + 32768;
constexpr int SMEM_BYTES = BAR_OFF + 2560;
constexpr int G1_SKEW = 2, G2_SKEW = 2;
constexpr int CONSUMER_REGS = 224, AUX_REGS = 56;
constexpr int ATT_SLOT = 8192;

enum { F_LN = 0, F_QKV = 1, F_EARLY = 2, F_LATE = 3, F_O = 4, F_CS = 5 };
constexpr unsigned CNT_LN = 8, CNT_QKV = 32, CNT_EARLY = 20, CNT_LATE = 8, CNT_O = 4, CNT_CS = 16;

__device__ __align__(1024) __nv_bfloat16 g_xn[SEQ * DM];
__device__ __align__(1024) __nv_bfloat16 g_qkv[SEQ * NQKV];
__device__ __align__(1024) __nv_bfloat16 g_a2[SEQ * K2];
__device__ __align__(128) float2 g_stats[SEQ];
__device__ __align__(128) float g_colsum[16 * 2048];
__device__ __align__(128) unsigned g_flags[6 * 16 * 32];
__device__ __align__(128) unsigned g_epoch[NCTA * 16];

#define TRACE_T -1
#define TRACE(slot) do {} while (0)
#define TRACE_GT(slot) do {} while (0)

__device__ __forceinline__ uint32_t smem_u32(const void* p) { return (uint32_t)__cvta_generic_to_shared(p); }
__device__ __forceinline__ void mbar_init(uint32_t bar, uint32_t cnt) {
    asm volatile("mbarrier.init.shared::cta.b64 [%0], %1;" :: "r"(bar), "r"(cnt) : "memory");
}
__device__ __forceinline__ void mbar_expect_tx(uint32_t bar, uint32_t bytes) {
    asm volatile("mbarrier.arrive.expect_tx.shared::cta.b64 _, [%0], %1;" :: "r"(bar), "r"(bytes) : "memory");
}
__device__ __forceinline__ void mbar_arrive(uint32_t bar) {
    asm volatile("mbarrier.arrive.shared::cta.b64 _, [%0];" :: "r"(bar) : "memory");
}
__device__ __forceinline__ void mbar_arrive_cluster(uint32_t bar, uint32_t cta) {
    asm volatile("{\n.reg .b32 ra;\nmapa.shared::cluster.u32 ra, %0, %1;\nmbarrier.arrive.shared::cluster.b64 _, [ra];\n}"
                 :: "r"(bar), "r"(cta) : "memory");
}
__device__ __forceinline__ bool mbar_try_wait(uint32_t bar, uint32_t parity) {
    uint32_t ok;
    asm volatile("{\n.reg .pred p;\nmbarrier.try_wait.parity.shared::cta.b64 p, [%1], %2;\nselp.u32 %0, 1, 0, p;\n}"
                 : "=r"(ok) : "r"(bar), "r"(parity) : "memory");
    return ok;
}
__device__ __forceinline__ bool mbar_test(uint32_t bar, uint32_t parity) {
    uint32_t ok;
    asm volatile("{\n.reg .pred p;\nmbarrier.test_wait.parity.shared::cta.b64 p, [%1], %2;\nselp.u32 %0, 1, 0, p;\n}"
                 : "=r"(ok) : "r"(bar), "r"(parity) : "memory");
    return ok;
}
__device__ __forceinline__ void mbar_wait(uint32_t bar, uint32_t parity) {
#pragma unroll 1
    for (int spins = 0; !mbar_try_wait(bar, parity) && spins < (1 << 17); spins++) {}
}
template <bool WARP = false> __device__ __forceinline__ void flag_wait(const unsigned* p, unsigned target) {
#pragma unroll 1
    for (int spins = 0; spins < (1 << 19); spins++) {
        unsigned v;
        asm volatile("ld.acquire.gpu.global.u32 %0, [%1];" : "=r"(v) : "l"(p) : "memory");
        if (WARP ? __all_sync(0xffffffffu, (int)(v - target) >= 0) : (int)(v - target) >= 0) break;
        __nanosleep(64);
    }
}
__device__ __forceinline__ void flag_add(unsigned* p) {
    asm volatile("red.release.gpu.global.add.u32 [%0], 1;" :: "l"(p) : "memory");
}
__device__ __forceinline__ bool elect_one() {
    uint32_t ok;
    asm volatile("{\n.reg .pred p;\nelect.sync _|p, 0xffffffff;\nselp.u32 %0, 1, 0, p;\n}" : "=r"(ok));
    return ok;
}
__device__ __forceinline__ void fence_proxy_async() { asm volatile("fence.proxy.async.global;" ::: "memory"); }
__device__ __forceinline__ uint4 lds128(uint32_t addr) {
    uint4 v;
    asm volatile("ld.shared.v4.u32 {%0,%1,%2,%3}, [%4];" : "=r"(v.x), "=r"(v.y), "=r"(v.z), "=r"(v.w) : "r"(addr) : "memory");
    return v;
}
__device__ __forceinline__ float2 lds64f(uint32_t addr) {
    float2 v;
    asm volatile("ld.shared.v2.f32 {%0,%1}, [%2];" : "=f"(v.x), "=f"(v.y) : "r"(addr) : "memory");
    return v;
}
__device__ __forceinline__ void sts128(uint32_t addr, uint4 v) {
    asm volatile("st.shared.v4.u32 [%0], {%1,%2,%3,%4};" :: "r"(addr), "r"(v.x), "r"(v.y), "r"(v.z), "r"(v.w) : "memory");
}
__device__ __forceinline__ void sts64f(uint32_t addr, float a, float b) {
    asm volatile("st.shared.v2.f32 [%0], {%1,%2};" :: "r"(addr), "f"(a), "f"(b) : "memory");
}

__device__ __forceinline__ uint64_t policy(bool stream) {
    uint64_t p;
    if (stream) asm("createpolicy.fractional.L2::evict_first.b64 %0, 1.0;" : "=l"(p));
    else asm("createpolicy.fractional.L2::evict_normal.b64 %0, 1.0;" : "=l"(p));
    return p;
}
__device__ __forceinline__ void tma_2d(uint32_t dst, const CUtensorMap* m, uint32_t bar, int c0, int c1, uint64_t pol) {
    asm volatile("cp.async.bulk.tensor.2d.shared::cluster.global.mbarrier::complete_tx::bytes.L2::cache_hint"
                 " [%0], [%1, {%3, %4}], [%2], %5;"
                 :: "r"(dst), "l"(m), "r"(bar), "r"(c0), "r"(c1), "l"(pol) : "memory");
}
__device__ __forceinline__ void tma_3d(uint32_t dst, const CUtensorMap* m, uint32_t bar, int c0, int c1, int c2, uint64_t pol) {
    asm volatile("cp.async.bulk.tensor.3d.shared::cluster.global.mbarrier::complete_tx::bytes.L2::cache_hint"
                 " [%0], [%1, {%3, %4, %5}], [%2], %6;"
                 :: "r"(dst), "l"(m), "r"(bar), "r"(c0), "r"(c1), "r"(c2), "l"(pol) : "memory");
}
__device__ __forceinline__ void tma_3d_mc(uint32_t dst, const CUtensorMap* m, uint32_t bar, int c1, int c2, uint64_t pol) {
    asm volatile("cp.async.bulk.tensor.3d.shared::cluster.global.mbarrier::complete_tx::bytes.multicast::cluster.L2::cache_hint"
                 " [%0], [%1, {%3, %4, %5}], [%2], %6, %7;"
                 :: "r"(dst), "l"(m), "r"(bar), "r"(0), "r"(c1), "r"(c2), "h"((uint16_t)3), "l"(pol) : "memory");
}
__device__ __forceinline__ void tma_5d_mc(uint32_t dst, const CUtensorMap* m, uint32_t bar, int c0, int c4, uint64_t pol) {
    asm volatile("cp.async.bulk.tensor.5d.shared::cluster.global.mbarrier::complete_tx::bytes.multicast::cluster.L2::cache_hint"
                 " [%0], [%1, {%3, %4, %4, %4, %5}], [%2], %6, %7;"
                 :: "r"(dst), "l"(m), "r"(bar), "r"(c0), "r"(0), "r"(c4), "h"((uint16_t)3), "l"(pol) : "memory");
}
__device__ __forceinline__ void tma_store_2d(const CUtensorMap* m, uint32_t src, int c0, int c1) {
    asm volatile("cp.async.bulk.tensor.2d.global.shared::cta.bulk_group [%0, {%2, %3}], [%1];"
                 :: "l"(m), "r"(src), "r"(c0), "r"(c1) : "memory");
}
__device__ __forceinline__ uint4 ldg_stream(const void* p, uint64_t pol) {
    uint4 v;
    asm volatile("ld.global.nc.L1::no_allocate.L2::cache_hint.v4.u32 {%0,%1,%2,%3}, [%4], %5;"
                 : "=r"(v.x), "=r"(v.y), "=r"(v.z), "=r"(v.w) : "l"(p), "l"(pol));
    return v;
}
__device__ __forceinline__ void bulk_load(uint32_t dst, const void* src, uint32_t bytes, uint32_t bar) {
    asm volatile("cp.async.bulk.shared::cluster.global.mbarrier::complete_tx::bytes [%0], [%1], %2, [%3];"
                 :: "r"(dst), "l"(src), "r"(bytes), "r"(bar) : "memory");
}
__device__ __forceinline__ void prefetch_3d(const CUtensorMap* m, int c1, int c2, uint64_t pol) {
    asm volatile("cp.async.bulk.prefetch.tensor.3d.L2.global.L2::cache_hint [%0, {%1, %2, %3}], %4;"
                 :: "l"(m), "r"(0), "r"(c1), "r"(c2), "l"(pol) : "memory");
}
__device__ __forceinline__ void prefetch_map(const CUtensorMap* m) {
    asm volatile("prefetch.tensormap [%0];" :: "l"(m) : "memory");
}
__device__ __forceinline__ void wg_fence() { asm volatile("wgmma.fence.sync.aligned;" ::: "memory"); }
__device__ __forceinline__ void wg_commit() { asm volatile("wgmma.commit_group.sync.aligned;" ::: "memory"); }
template <int N> __device__ __forceinline__ void wg_wait() { asm volatile("wgmma.wait_group.sync.aligned %0;" :: "n"(N) : "memory"); }

__device__ __forceinline__ uint64_t desc_a(uint32_t addr) {
    return (uint64_t)((addr & 0x3FFFF) >> 4) | (1ull << 16) | (64ull << 32) | (1ull << 62);
}
__device__ __forceinline__ uint64_t desc_b(uint32_t addr) {
    return (uint64_t)((addr & 0x3FFFF) >> 4) | (512ull << 16) | (64ull << 32) | (1ull << 62);
}

#define R8(d, o) "+f"(d[o]), "+f"(d[o+1]), "+f"(d[o+2]), "+f"(d[o+3]), "+f"(d[o+4]), "+f"(d[o+5]), "+f"(d[o+6]), "+f"(d[o+7])
#define R32(d, o) R8(d, o), R8(d, o+8), R8(d, o+16), R8(d, o+24)
#define R64(d, o) R32(d, o), R32(d, o+32)

__device__ __forceinline__ void wgmma_n256(float (&d)[128], uint64_t da, uint64_t db, int scale_d) {
    asm volatile("{\n.reg .pred p;\nsetp.ne.b32 p, %130, 0;\n"
        "wgmma.mma_async.sync.aligned.m64n256k16.f32.bf16.bf16 "
        "{%0,%1,%2,%3,%4,%5,%6,%7,%8,%9,%10,%11,%12,%13,%14,%15,%16,%17,%18,%19,%20,%21,%22,%23,%24,%25,%26,%27,%28,%29,%30,%31,"
        "%32,%33,%34,%35,%36,%37,%38,%39,%40,%41,%42,%43,%44,%45,%46,%47,%48,%49,%50,%51,%52,%53,%54,%55,%56,%57,%58,%59,%60,%61,%62,%63,"
        "%64,%65,%66,%67,%68,%69,%70,%71,%72,%73,%74,%75,%76,%77,%78,%79,%80,%81,%82,%83,%84,%85,%86,%87,%88,%89,%90,%91,%92,%93,%94,%95,"
        "%96,%97,%98,%99,%100,%101,%102,%103,%104,%105,%106,%107,%108,%109,%110,%111,%112,%113,%114,%115,%116,%117,%118,%119,%120,%121,%122,%123,%124,%125,%126,%127},"
        " %128, %129, p, 1, 1, 0, 1;\n}"
        : R64(d, 0), R64(d, 64) : "l"(da), "l"(db), "r"(scale_d));
}
__device__ __forceinline__ void wgmma_n128(float (&d)[64], uint64_t da, uint64_t db, int scale_d) {
    asm volatile("{\n.reg .pred p;\nsetp.ne.b32 p, %66, 0;\n"
        "wgmma.mma_async.sync.aligned.m64n128k16.f32.bf16.bf16 "
        "{%0,%1,%2,%3,%4,%5,%6,%7,%8,%9,%10,%11,%12,%13,%14,%15,%16,%17,%18,%19,%20,%21,%22,%23,%24,%25,%26,%27,%28,%29,%30,%31,"
        "%32,%33,%34,%35,%36,%37,%38,%39,%40,%41,%42,%43,%44,%45,%46,%47,%48,%49,%50,%51,%52,%53,%54,%55,%56,%57,%58,%59,%60,%61,%62,%63},"
        " %64, %65, p, 1, 1, 0, 1;\n}"
        : R64(d, 0) : "l"(da), "l"(db), "r"(scale_d));
}

__device__ __forceinline__ uint32_t pack_bf16(float lo, float hi) {
    uint32_t r; asm("cvt.rn.bf16x2.f32 %0, %1, %2;" : "=r"(r) : "f"(hi), "f"(lo)); return r;
}
__device__ __forceinline__ float bf_lo(uint32_t v) { return __uint_as_float(v << 16); }
__device__ __forceinline__ float bf_hi(uint32_t v) { return __uint_as_float(v & 0xffff0000u); }
__device__ __forceinline__ float round_bf16(float v) { return bf_lo(pack_bf16(v, 0.f)); }
__device__ __forceinline__ uint32_t mul_bf16x2(uint32_t a, uint32_t b) {
    uint32_t r; asm("mul.rn.bf16x2 %0, %1, %2;" : "=r"(r) : "r"(a), "r"(b)); return r;
}
__device__ __forceinline__ uint32_t add_bf16x2(uint32_t a, uint32_t b) {
    uint32_t r; asm("add.rn.bf16x2 %0, %1, %2;" : "=r"(r) : "r"(a), "r"(b)); return r;
}
__device__ __forceinline__ uint32_t sub_bf16x2(uint32_t a, uint32_t b) {
    uint32_t r; asm("sub.rn.bf16x2 %0, %1, %2;" : "=r"(r) : "r"(a), "r"(b)); return r;
}
__device__ __forceinline__ uint32_t mul2_bf16x2(uint32_t a, uint32_t hi, uint32_t lo) {
    uint32_t r; asm("fma.rn.bf16x2 %0, %1, %2, %3;" : "=r"(r) : "r"(a), "r"(hi), "r"(mul_bf16x2(a, lo))); return r;
}
__device__ __forceinline__ float tanh_fast(float x) { float r; asm("tanh.approx.f32 %0, %1;" : "=f"(r) : "f"(x)); return r; }
__device__ __forceinline__ float gelu_tanh(float g) {
    float t = fmaf(g * g, 0.044715f * 0.7978845608f, 0.7978845608f) * g;
    float hg = 0.5f * g;
    return fmaf(hg, tanh_fast(t), hg);
}
__device__ __forceinline__ uint32_t geglu2(uint32_t g2, uint32_t u2) {
    return mul_bf16x2(pack_bf16(gelu_tanh(bf_lo(g2)), gelu_tanh(bf_hi(g2))), u2);
}
__device__ __forceinline__ float silu(float d) {
    float hd = 0.5f * d;
    return fmaf(hd, tanh_fast(hd), hd);
}
__device__ __forceinline__ float ex2_fast(float x) { float r; asm("ex2.approx.ftz.f32 %0, %1;" : "=f"(r) : "f"(x)); return r; }
__device__ __forceinline__ void unpack8(uint4 v, float (&f)[8]) {
    f[0] = bf_lo(v.x); f[1] = bf_hi(v.x); f[2] = bf_lo(v.y); f[3] = bf_hi(v.y);
    f[4] = bf_lo(v.z); f[5] = bf_hi(v.z); f[6] = bf_lo(v.w); f[7] = bf_hi(v.w);
}
template <int N> __device__ __forceinline__ void fence_regs(float (&d)[N]) {
#pragma unroll
    for (int i = 0; i < N; i++) asm volatile("" : "+f"(d[i]) :: "memory");
}

__device__ __forceinline__ float rcp_fast(float x) { float r; asm("rcp.approx.ftz.f32 %0, %1;" : "=f"(r) : "f"(x)); return r; }
__device__ __forceinline__ uint32_t max_bf16x2(uint32_t a, uint32_t b) {
    uint32_t r; asm("max.bf16x2 %0, %1, %2;" : "=r"(r) : "r"(a), "r"(b)); return r;
}
__device__ __forceinline__ uint4 ldsm4(uint32_t addr) {
    uint4 v;
    asm volatile("ldmatrix.sync.aligned.m8n8.x4.shared.b16 {%0,%1,%2,%3}, [%4];"
                 : "=r"(v.x), "=r"(v.y), "=r"(v.z), "=r"(v.w) : "r"(addr) : "memory");
    return v;
}
__device__ __forceinline__ uint4 ldsm4_t(uint32_t addr) {
    uint4 v;
    asm volatile("ldmatrix.sync.aligned.m8n8.x4.trans.shared.b16 {%0,%1,%2,%3}, [%4];"
                 : "=r"(v.x), "=r"(v.y), "=r"(v.z), "=r"(v.w) : "r"(addr) : "memory");
    return v;
}
__device__ __forceinline__ void mma_16816(float (&c)[4], uint32_t a0, uint32_t a1, uint32_t a2, uint32_t a3, uint32_t b0, uint32_t b1) {
    asm("mma.sync.aligned.m16n8k16.row.col.f32.bf16.bf16.f32 {%0,%1,%2,%3}, {%4,%5,%6,%7}, {%8,%9}, {%0,%1,%2,%3};"
        : "+f"(c[0]), "+f"(c[1]), "+f"(c[2]), "+f"(c[3]) : "r"(a0), "r"(a1), "r"(a2), "r"(a3), "r"(b0), "r"(b1));
}
__device__ __forceinline__ void mma_1688(float (&c)[4], uint32_t a0, uint32_t a1, uint32_t b0) {
    asm("mma.sync.aligned.m16n8k8.row.col.f32.bf16.bf16.f32 {%0,%1,%2,%3}, {%4,%5}, {%6}, {%0,%1,%2,%3};"
        : "+f"(c[0]), "+f"(c[1]), "+f"(c[2]), "+f"(c[3]) : "r"(a0), "r"(a1), "r"(b0));
}
__device__ __forceinline__ void qk_tile(float (&c)[4], const uint4& q0, const uint4& q1, const uint4& k, float init) {
    c[0] = c[1] = c[2] = c[3] = init;
    mma_16816(c, q0.x, q0.y, q0.z, q0.w, k.x, k.y);
    mma_16816(c, q1.x, q1.y, q1.z, q1.w, k.z, k.w);
}
__device__ __forceinline__ uint32_t scaled_logits(bool first, float a0, float a1, float b0, float b1) {
    return mul2_bf16x2(pack_bf16(first ? a0 : b0, first ? a1 : b1), 0x3e353e35u, 0x379e379eu);
}
template <typename T> __device__ __forceinline__ T uniform(T v) { return __shfl_sync(0xffffffffu, v, 0); }

__device__ __forceinline__ void attention(const CUtensorMap* maps, uint32_t base, uint32_t zero, int grp, int warp, int lane) {
    constexpr float LOG2E = 1.4426950408889634f;
    const int g = lane >> 2, t = lane & 3;
    const bool up0 = 2 * t > g, up1 = 2 * t + 1 > g;
    const uint32_t keep = (up0 ? 0x0000ffffu : 0u) | (up1 ? 0xffff0000u : 0u);
    const uint32_t buf = base + warp * 2 * ATT_SLOT, bar = base + AUX_OFF + warp * 16;
    const uint32_t qoff = (lane & 15) * 128 + (((lane >> 4) ^ (lane & 7)) << 4);
    const uint32_t koff = 2048 + (lane & 7) * 128 + (((lane >> 3) ^ (lane & 7)) << 4);
    const uint32_t rest_bar = base + AUX_OFF + 192;
    const int col = uniform(grp * 256), first = uniform((warp / 3 * 32 + warp % 3 * 11) * 16);
    const CUtensorMap* const mqk = reinterpret_cast<const CUtensorMap*>(uniform(reinterpret_cast<uint64_t>(maps)));
    const CUtensorMap *const mv = mqk + 1, *const mo = mqk + 2;
    const uint64_t pol = policy(P_QKV);
    uint4 kp[2], vp[2];
    uint32_t l0[2], l1[2], m[2];
    float s[2][3][4];
    auto scores = [&](uint32_t st, int row) {
        const float before = (row & 1023) == 0 ? -5.656854e9f : 0.f;
#pragma unroll
        for (int h = 0; h < 2; h++) {
            const uint4 q0 = ldsm4(st + (qoff ^ (h * 64))), q1 = ldsm4(st + (qoff ^ (h * 64 + 32)));
            const uint4 k0 = ldsm4(st + (koff ^ (h * 64))), k1 = ldsm4(st + 1024 + (koff ^ (h * 64)));
            qk_tile(s[h][0], q0, q1, kp[h], before);
            qk_tile(s[h][1], q0, q1, k0, 0.f);
            qk_tile(s[h][2], q0, q1, k1, 0.f);
            kp[h] = k1;
        }
    };
    auto logits = [&]() {
#pragma unroll
        for (int h = 0; h < 2; h++) {
            l0[h] = scaled_logits(up0, s[h][0][0], s[h][1][2], s[h][1][0], s[h][2][2]);
            l1[h] = scaled_logits(up1, s[h][0][1], s[h][1][3], s[h][1][1], s[h][2][3]);
            m[h] = max_bf16x2(l0[h], l1[h]);
            m[h] = max_bf16x2(m[h], __shfl_xor_sync(0xffffffffu, m[h], 1));
        }
    };
    auto row_max = [&]() {
#pragma unroll
        for (int h = 0; h < 2; h++) m[h] = max_bf16x2(m[h], __shfl_xor_sync(0xffffffffu, m[h], 2));
    };
    auto next = [](uint32_t p) {
        return (0x80200400u >> (p >> 4 & 31) & 1) > (p >> 15 & 1) ? p + (64 << 16) + 0x8000 : (p + 16) & ~0x8800u;
    };
    auto exchange = [&](uint32_t st, uint32_t b, uint32_t po, uint32_t pv, uint32_t pq) {
        asm volatile("{\n.reg .pred e, p, q;\n"
            "fence.proxy.async.shared::cta;\n"
            "bar.warp.sync 0xffffffff;\n"
            "elect.sync _|e, 0xffffffff;\n"
            "setp.eq.and.b32 p, %12, 0, e;\n"
            "setp.lt.and.s32 q, %8, %13, e;\n"
            "@q mbarrier.arrive.expect_tx.shared::cta.b64 _, [%2], 6144;\n"
            "@q cp.async.bulk.tensor.3d.shared::cluster.global.mbarrier::complete_tx::bytes.L2::cache_hint [%0], [%3, {%6, %7, %14}], [%2], %15;\n"
            "@q cp.async.bulk.tensor.2d.shared::cluster.global.mbarrier::complete_tx::bytes.L2::cache_hint [%0 + 4096], [%4, {%8, %9}], [%2], %15;\n"
            "@e cp.async.bulk.wait_group.read 0;\n"
            "@p cp.async.bulk.tensor.2d.global.shared::cta.bulk_group [%5, {%10, %11}], [%1 + 6144];\n"
            "@e cp.async.bulk.commit_group;\n"
            "bar.warp.sync 0xffffffff;\n}"
            :: "r"(st), "r"(st ^ ATT_SLOT), "r"(b), "l"(mqk), "l"(mv), "l"(mo), "r"(pq >> 16), "r"(pq & 2047),
               "r"((pv >> 16) + 2 * DM), "r"(pv & 2047), "r"(po >> 16), "r"(po & 2047), "r"(po & 0x8000),
               "r"(col + 256 + 2 * DM), "r"(0), "l"(pol) : "memory");
    };
    auto publish = [&](auto pending, int part) {
        asm volatile("{\n.reg .pred e;\n.reg .u32 n;\n"
            "elect.sync _|e, 0xffffffff;\n"
            "cp.async.bulk.wait_group %2;\n"
            "@e atom.acq_rel.cta.shared.add.u32 n, [%1], 1;\n"
            "setp.eq.and.u32 e, n, 11, e;\n"
            "@e red.release.gpu.global.add.u32 [%0], 1;\n}"
            :: "l"(g_flags + F_O * 512 + part * 32), "r"(rest_bar + 8 + part * 4), "n"(pending.value) : "memory");
    };
    const unsigned epoch = __ldcg(g_epoch + blockIdx.x * 16) + 1;
    if (elect_one()) {
        mbar_init(bar, 1); mbar_init(bar + 8, 1);
        if (warp == 2) { mbar_init(rest_bar, 32); sts64f(rest_bar + 8, 0.f, 0.f); }
        asm volatile("fence.mbarrier_init.release.cluster;" ::: "memory");
        prefetch_map(mqk); prefetch_map(mv); prefetch_map(mo);
    }
    __syncthreads();
    if (elect_one()) {
        g_epoch[blockIdx.x * 16] = epoch;
        flag_wait(g_flags + F_QKV * 512 + grp * 32, epoch * CNT_QKV);
        fence_proxy_async();
        mbar_expect_tx(bar + 8, 8192);
        tma_3d(buf + ATT_SLOT, mqk, bar + 8, col, first, 0, pol);
        tma_2d(buf + ATT_SLOT + 4096, mv, bar + 8, col + 2 * DM, first - 16, policy(false));
        tma_2d(buf + ATT_SLOT + 6144, mv, bar + 8, col + DM, first - 16, policy(false));
        mbar_expect_tx(bar, 6144);
        tma_3d(buf, mqk, bar, col, first + 16, 0, pol);
        tma_2d(buf + 4096, mv, bar, col + 2 * DM, first, pol);
        if (warp == 0) TRACE(9);
    }
    __syncwarp();
    mbar_wait(bar + 8, 0);
#pragma unroll
    for (int h = 0; h < 2; h++) {
        kp[h] = ldsm4(buf + ATT_SLOT + 5120 + (koff ^ (h * 64)));
        vp[h] = ldsm4_t(buf + ATT_SLOT + 3072 + (koff ^ (h * 64)));
    }
    scores(buf + ATT_SLOT, first);
    uint32_t pm = 0x8000, p0 = col << 16 | first, p1 = p0 + 16, p2 = p0 + 32, p3 = p0 + 48;
    exchange(buf + ATT_SLOT, bar + 8, pm, p1, p2);
    logits();
    row_max();
    uint32_t st = buf, b = bar, cnt = 1;
    const uint32_t relay = warp == 2 ? 7 : 0;
    bool ready = false;
#pragma unroll 1
    while (p0 >> 16 < col + 256) {
        uint32_t pa[2], pb[2];
        if (!ready) mbar_wait(b, (cnt >> 1) & 1);
        uint4 v[2][2];
#pragma unroll
        for (int h = 0; h < 2; h++) {
            const float ma = -LOG2E * bf_lo(m[h]), mb = -LOG2E * bf_hi(m[h]);
            const float a0 = ex2_fast(fmaf(bf_lo(l0[h]), LOG2E, ma)), a1 = ex2_fast(fmaf(bf_lo(l1[h]), LOG2E, ma));
            const float b0 = ex2_fast(fmaf(bf_hi(l0[h]), LOG2E, mb)), b1 = ex2_fast(fmaf(bf_hi(l1[h]), LOG2E, mb));
            float sum[4] = {0.f, 0.f, 0.f, 0.f};
            mma_1688(sum, pack_bf16(a0, a1), pack_bf16(b0, b1), 0x3f803f80u);
            const float ra = rcp_fast(sum[0]), rb = rcp_fast(sum[2]);
            pa[h] = pack_bf16(a0 * ra, a1 * ra);
            pb[h] = pack_bf16(b0 * rb, b1 * rb);
        }
        scores(st, p1);
#pragma unroll
        for (int h = 0; h < 2; h++) {
            v[h][0] = ldsm4_t(st + 4096 + (qoff ^ (h * 64)));
            v[h][1] = ldsm4_t(st + 4096 + (qoff ^ (h * 64 + 32)));
        }
        if (cnt == relay) {
            flag_wait<true>(g_flags + F_QKV * 512 + 128 + grp * 32, epoch * CNT_QKV);
            fence_proxy_async();
            mbar_arrive(rest_bar);
        }
        if (cnt == 8) {
#pragma unroll 1
            for (int spins = 0; !__all_sync(0xffffffffu, mbar_try_wait(rest_bar, 0)) && spins < (1 << 17); spins++) {}
        }
        if (cnt == 37) publish(std::integral_constant<int, 1>(), 0);
        exchange(st, b, pm, p2, p3);
        pm = p0; p0 = p1; p1 = p2; p2 = p3; p3 = next(p3);
        logits();
        float o[2][4][4];
#pragma unroll
        for (int h = 0; h < 2; h++) {
            const uint32_t prev[4] = {vp[h].x, vp[h].y, vp[h].z, vp[h].w};
            const uint32_t own[8] = {v[h][0].x, v[h][0].y, v[h][0].z, v[h][0].w, v[h][1].x, v[h][1].y, v[h][1].z, v[h][1].w};
            const uint32_t a0 = pa[h] & keep, a1 = pa[h] & ~keep, a2 = pb[h] & keep, a3 = pb[h] & ~keep;
            const uint32_t z0 = pa[h] & zero, z1 = pb[h] & zero;
#pragma unroll
            for (int j = 0; j < 4; j++) {
                o[h][j][0] = o[h][j][1] = o[h][j][2] = o[h][j][3] = 0.f;
                mma_1688(o[h][j], a0, z0, prev[j]);
                mma_16816(o[h][j], a1, a2, z1, a3, own[2 * j], own[2 * j + 1]);
            }
            vp[h] = make_uint4(own[1], own[3], own[5], own[7]);
        }
        row_max();
        b ^= 8; cnt++;
        ready = mbar_test(b, (cnt >> 1) & 1);
#pragma unroll
        for (int h = 0; h < 2; h++) {
#pragma unroll
            for (int d = 0; d < 2; d++)
                asm volatile("stmatrix.sync.aligned.m8n8.x4.shared.b16 [%0], {%1,%2,%3,%4};"
                             :: "r"(st + 6144 + (qoff ^ (h * 64 + d * 32))),
                                "r"(pack_bf16(o[h][2 * d][0], o[h][2 * d][1])), "r"(pack_bf16(o[h][2 * d][2], o[h][2 * d][3])),
                                "r"(pack_bf16(o[h][2 * d + 1][0], o[h][2 * d + 1][1])),
                                "r"(pack_bf16(o[h][2 * d + 1][2], o[h][2 * d + 1][3])) : "memory");
        }
        st ^= ATT_SLOT;
    }
    exchange(st, b, pm, p0, p0);
    publish(std::integral_constant<int, 0>(), 1);
    if (threadIdx.x == 0) TRACE(10);
}

struct Params {
    CUtensorMap x, xn, wqkv, wg, wu, qk, v, o, a2, wo, wd, out;
    const __nv_bfloat16* px;
    uint32_t zero;
};

__device__ __forceinline__ bool tile_is_qkv(int nt) { return nt < 4 || (nt >= 8 && nt < 16); }
__device__ __forceinline__ int tile_index(int nt) { return nt < 4 ? nt + 8 : (nt < 8 ? nt - 4 : (nt < 16 ? nt - 8 : nt - 12)); }

__global__ void __cluster_dims__(2, 1, 1) __launch_bounds__(384, 1)
fused_kernel(const __grid_constant__ Params prm) {
    extern __shared__ __align__(1024) uint8_t smem_raw[];
    const uint32_t base = smem_u32(smem_raw) & ~1023u;
    const uint32_t bars = base + BAR_OFF;
    auto full1 = [&](int s) { return bars + s * 8; };
    auto empty1 = [&](int s) { return bars + 32 + s * 8; };
    auto full2 = [&](int s) { return bars + 64 + s * 8; };
    auto empty2 = [&](int s) { return bars + 128 + s * 8; };
    const uint32_t sig_bar = bars + 192, dep_bar = bars + 256, cs_bar = bars + 304, fold_bar = bars + 320, x_bar = bars + 336;
    const uint32_t colsum = bars + 512, stats = bars + 1536;
    auto stage2 = [&](int q) { return base + q * G2_STAGE_BYTES; };
    const uint32_t aux = base + AUX_OFF;

    const int warp = __shfl_sync(0xffffffffu, threadIdx.x >> 5, 0);
    const int lane = threadIdx.x & 31;
    const int rank = blockIdx.x & 1;
    const int mblk = ((blockIdx.x >> 1) & 7) * 2 + rank;
    const int nslot = blockIdx.x >> 4;

    if (blockIdx.x >= NGEMM) {
        if (threadIdx.x == 0) { TRACE_GT(0); TRACE(1); }
        attention(&prm.qk, (base + 2 * ATT_SLOT - 1) & ~(2u * ATT_SLOT - 1), prm.zero, blockIdx.x - NGEMM, warp, lane);
    } else if (warp >= 8) {
        unsigned* const flags = g_flags + mblk * 32;
        const CUtensorMap* const w0 = nslot < 4 ? &prm.wqkv : (rank ? &prm.wu : &prm.wg);
        const int w0_col = nslot < 4 ? 32 + nslot * 4 + rank * 2 : nslot * 2 - 8;
        if (elect_one()) {
            if (warp == 8) {
                TRACE_GT(0); TRACE(1);
                prefetch_map(&prm.x); prefetch_map(w0);
                for (int s = 0; s < G1_STAGES; s++) { mbar_init(full1(s), 1); mbar_init(empty1(s), 4); }
            } else if (warp == 9) {
                for (int s = 0; s < G2_STAGES; s++) { mbar_init(full2(s), 1); mbar_init(empty2(s), 4); }
            } else if (warp == 10) {
                for (int s = 0; s < 7; s++) mbar_init(sig_bar + s * 8, 8);
                mbar_init(fold_bar, 2); mbar_init(fold_bar + 8, 1); mbar_init(x_bar, 1);
            } else {
                for (int s = 0; s < 8; s++) mbar_init(dep_bar + s * 8, 1);
            }
            asm volatile("fence.mbarrier_init.release.cluster;" ::: "memory");
        }
        __syncwarp();
        asm volatile("barrier.cluster.arrive.relaxed.aligned;" ::: "memory");
        if (warp == 8 && lane == 0) {
            mbar_expect_tx(full1(0), G1_STAGE_BYTES);
            tma_2d(base, &prm.x, full1(0), 0, mblk * 128, policy(P_X));
            prefetch_3d(w0, 0, w0_col, policy(P_W1));
            TRACE(15);
        }
        asm volatile("setmaxnreg.dec.sync.aligned.u32 %0;" :: "n"(AUX_REGS));
        asm volatile("barrier.cluster.wait.acquire.aligned;" ::: "memory");

        if (warp == 8) {
            if (lane == 0) {
                TRACE(2);
                auto load_b1 = [&](int s, int nt, int k) {
                    const uint32_t dst = base + s * G1_STAGE_BYTES + A_BYTES + rank * 16384;
                    if (tile_is_qkv(nt)) tma_3d_mc(dst, &prm.wqkv, full1(s), k * 64, tile_index(nt) * 4 + rank * 2, policy(P_W1));
                    else tma_3d_mc(dst, rank ? &prm.wu : &prm.wg, full1(s), k * 64, tile_index(nt) * 2, policy(P_W1));
                };
                load_b1(0, nslot, 0);
                uint32_t ph = 1;
                for (int it = 1; it < G1_TILES * G1_KSTEPS; it++) {
                    const int s = it & 3, k = it & 15;
                    if (it == G1_STAGES) {
                        if (PF_X) asm volatile("cp.async.bulk.prefetch.L2.global.L2::cache_hint [%0], 32768, %1;"
                                     :: "l"(prm.px + (size_t)(mblk * 128 + nslot * 16) * DM), "l"(policy(P_X)) : "memory");
                        if (mblk / 2 + 4 < PF_W) prefetch_3d(w0, (mblk / 2 + 4) * 64, w0_col, policy(P_W1));
                        prefetch_map(&prm.xn); prefetch_map(&prm.wqkv); prefetch_map(&prm.wu); prefetch_map(&prm.wg);
                        prefetch_map(&prm.a2); prefetch_map(&prm.wo); prefetch_map(&prm.wd); prefetch_map(&prm.out);
                    }
                    if (it == G1_KSTEPS) { TRACE(14); mbar_wait(dep_bar, 0); TRACE(3); }
                    mbar_wait(empty1(s), ph);
                    mbar_expect_tx(full1(s), G1_STAGE_BYTES);
                    tma_2d(base + s * G1_STAGE_BYTES, it < G1_KSTEPS ? &prm.x : &prm.xn, full1(s), k * 64, mblk * 128,
                           policy(it < G1_KSTEPS ? P_X : (P_XN4 && it >= (G1_TILES - 1) * G1_KSTEPS)));
                    load_b1(s, (it >> 4) * 8 + nslot, k);
                    if (s == 3) ph ^= 1;
                }
                mbar_expect_tx(x_bar, 32768);
                tma_2d(aux, &prm.x, x_bar, nslot * 128, mblk * 128, policy(P_X));
                tma_2d(aux + 16384, &prm.x, x_bar, nslot * 128 + 64, mblk * 128, policy(P_X));
                TRACE(4);
                mbar_wait(dep_bar + 8, 0);
                TRACE(5);
                int q = 0; uint32_t ph2 = 1;
                for (int u = 0; u < G2_KSTEPS; u++) {
                    if (u == G2_LATE || u == G2_DSTEPS || u == G2_LAST) {
                        TRACE(u == G2_LATE ? 6 : (u == G2_DSTEPS ? 32 : 40));
                        mbar_wait(dep_bar + (u == G2_LATE ? 16 : (u == G2_DSTEPS ? 24 : 32)), 0);
                        TRACE(u == G2_LATE ? 7 : (u == G2_DSTEPS ? 33 : 41));
                    }
                    if (u < G2_STAGES) {
                        if (u == 0) mbar_wait(empty1(0), ph);
                        if (u == 1) mbar_wait(empty1(1), ph);
                        if (u == 3) mbar_wait(empty1(2), ph);
                        if (u == 4) mbar_wait(empty1(3), ph);
                    } else {
                        mbar_wait(empty2(q), ph2);
                    }
                    const uint32_t sa = stage2(q);
                    const bool down = u < G2_DSTEPS;
                    const int k = down ? u : (u - G2_DSTEPS) % 4 * 4 + (u - G2_DSTEPS) / 4;
                    mbar_expect_tx(full2(q), G2_STAGE_BYTES);
                    tma_3d(sa, &prm.a2, full2(q), (down ? DM : 0) + k * 64, 0, mblk * 64, policy(P_A2));
                    tma_5d_mc(sa + A_BYTES + rank * 8192, down ? &prm.wd : &prm.wo, full2(q), nslot * 128 + rank * 64, k * 2, policy(P_W2));
                    if (++q == G2_STAGES) { q = 0; ph2 ^= 1; }
                }
                TRACE(8);
            }
        } else if (warp == 9) {
            if (lane == 0) {
                const unsigned epoch = __ldcg(g_epoch + blockIdx.x * 16 + 2) + 1;
                mbar_wait(sig_bar, 0);
                TRACE(11);
                flag_add(flags + F_LN * 512);
                TRACE(42);
                flag_wait(flags + F_LN * 512, epoch * CNT_LN);
                fence_proxy_async();
                mbar_arrive(dep_bar);
                mbar_expect_tx(fold_bar + 8, 1024);
                bulk_load(stats, g_stats + mblk * 128, 1024, fold_bar + 8);
                g_epoch[blockIdx.x * 16 + 2] = epoch;
                for (int p = nslot < 4 ? 2 : 1; p < 7; p++) {
                    mbar_wait(sig_bar + p * 8, 0);
                    if (p == 2) TRACE(37);
                    flag_add(p == 2 || p == 3 ? g_flags + F_QKV * 512 + (p * 4 - 8 + (nslot & 3)) * 32
                                              : flags + (p < 6 ? F_EARLY : F_LATE) * 512);
                    if (p == 2) TRACE(43);
                }
            }
        } else {
            const int w = warp - 10;
            const unsigned epoch = __ldcg(g_epoch + blockIdx.x * 16 + w) + 1;
            unsigned* const cs_flag = g_flags + F_CS * 512 + (nslot * 2 + w) * 32;
            mbar_wait(CS_AT, 0);
            if (elect_one()) {
                mbar_expect_tx(cs_bar + w * 8, 16384);
                tma_3d(aux + w * 16384, nslot < 4 ? &prm.wqkv : (w ? &prm.wu : &prm.wg), cs_bar + w * 8, 0, mblk * 64,
                       nslot < 4 ? 32 + nslot * 4 + w * 2 : nslot * 2 - 8, policy(P_W1));
            }
            float cs[8];
#pragma unroll
            for (int d = 0; d < 8; d++) cs[d] = 0.f;
            mbar_wait(cs_bar + w * 8, 0);
            const uint32_t wa = aux + w * 16384 + (lane & 8) * 1024 + (lane >> 4) * 128 + (((lane & 7) ^ (lane >> 4)) << 4);
#pragma unroll 1
            for (int i = 0; i < 8; i++) {
#pragma unroll
                for (int j = 0; j < 4; j++) {
                    float f[8];
                    unpack8(lds128((wa ^ (j * 32)) + i * 1024 + j * 256), f);
#pragma unroll
                    for (int d = 0; d < 8; d++) cs[d] += f[d];
                }
            }
#pragma unroll
            for (int d = 0; d < 8; d++) cs[d] += __shfl_xor_sync(0xffffffffu, cs[d], 16);
            *reinterpret_cast<float4*>(g_colsum + (nslot * 2 + w) * 2048 + mblk * 128 + (lane & 15) * 8 + (lane >> 4) * 4) =
                lane < 16 ? make_float4(cs[0], cs[1], cs[2], cs[3]) : make_float4(cs[4], cs[5], cs[6], cs[7]);
            __syncwarp();
            if (lane == 0) {
                if (w == 0) TRACE(34);
                flag_add(cs_flag);
                flag_wait(cs_flag, epoch * CNT_CS);
                fence_proxy_async();
                mbar_expect_tx(cs_bar + w * 8, 8192);
                bulk_load(aux + w * 16384, g_colsum + (nslot * 2 + w) * 2048, 8192, cs_bar + w * 8);
            }
            mbar_wait(cs_bar + w * 8, 1);
            float4 c = make_float4(0.f, 0.f, 0.f, 0.f);
#pragma unroll 8
            for (int m = 0; m < 16; m++) {
                const uint4 a = lds128(aux + w * 16384 + m * 512 + lane * 16);
                c.x += __uint_as_float(a.x); c.y += __uint_as_float(a.y); c.z += __uint_as_float(a.z); c.w += __uint_as_float(a.w);
            }
            const uint32_t ca = colsum + (w * 8 + (lane >> 2)) * 64 + (lane & 1) * 32 + (lane & 2) * 4;
            sts64f(ca, c.x, c.y);
            sts64f(ca + 16, c.z, c.w);
            __syncwarp();
            if (lane == 0) {
                mbar_arrive(fold_bar);
                g_epoch[blockIdx.x * 16 + w] = epoch;
                if (w == 0) {
                    TRACE(35);
                    flag_wait(flags + F_EARLY * 512, epoch * CNT_EARLY);
                    fence_proxy_async(); mbar_arrive(dep_bar + 8);
                    flag_wait(flags + F_LATE * 512, epoch * CNT_LATE);
                    fence_proxy_async(); mbar_arrive(dep_bar + 16);
                    flag_wait(g_flags + F_O * 512, epoch * CNT_O);
                    fence_proxy_async(); mbar_arrive(dep_bar + 24);
                    flag_wait(g_flags + F_O * 512 + 32, epoch * CNT_O);
                    fence_proxy_async(); mbar_arrive(dep_bar + 32);
                }
            }
        }
    } else {
        asm volatile("barrier.cluster.arrive.relaxed.aligned;" ::: "memory");
        asm volatile("setmaxnreg.inc.sync.aligned.u32 %0;" :: "n"(CONSUMER_REGS));
        const int wg = __shfl_sync(0xffffffffu, threadIdx.x >> 7, 0);
        const int cw = threadIdx.x >> 5;
        const int tid = threadIdx.x & 127;
        float acc[128];
        uint32_t pk[64];
#pragma unroll
        for (int i = 0; i < 64; i++) asm volatile("mov.b32 %0, 0;" : "=r"(pk[i]));
#pragma unroll
        for (int i = 0; i < 128; i++) asm volatile("mov.b32 %0, 0;" : "=f"(acc[i]));
        asm volatile("barrier.cluster.wait.acquire.aligned;" ::: "memory");

        const int orow = ((lane >> 2) & 1) * (SEQ / 2) + mblk * 64 + cw * 8 + (lane >> 3);
        __nv_bfloat16* optr = nullptr;
        auto release = [&](uint32_t bar) { if (tid < 2) mbar_arrive_cluster(bar, tid); };
        auto chunk_geglu = [&](int j) {
            const int c = j >> 1, h = j & 1;
            uint4 v;
            v.x = geglu2(pk[8 * c + h], pk[32 + 8 * c + h]);
            v.y = geglu2(pk[8 * c + 2 + h], pk[32 + 8 * c + 2 + h]);
            v.z = geglu2(pk[8 * c + 4 + h], pk[32 + 8 * c + 4 + h]);
            v.w = geglu2(pk[8 * c + 6 + h], pk[32 + 8 * c + 6 + h]);
            *reinterpret_cast<uint4*>(optr + h * 4 * K2 + c * 32) = v;
        };
        auto chunk_qkv = [&](int c) {
            *reinterpret_cast<uint4*>(optr + c * 32) = make_uint4(pk[8 * c], pk[8 * c + 2], pk[8 * c + 4], pk[8 * c + 6]);
            *reinterpret_cast<uint4*>(optr + 4 * NQKV + c * 32) = make_uint4(pk[8 * c + 1], pk[8 * c + 3], pk[8 * c + 5], pk[8 * c + 7]);
        };
        auto signal_stores = [&](int p) { __syncwarp(); if (lane == 0) mbar_arrive(sig_bar + p * 8); };

        auto chunk_ln = [&](int k) {
            const int row = mblk * 128 + nslot * 16 + cw * 2;
            float* const mo = reinterpret_cast<float*>(pk + 32);
            if (k == 0) {
                const uint4* xp = reinterpret_cast<const uint4*>(prm.px + (size_t)row * DM) + lane;
#pragma unroll
                for (int i = 0; i < 8; i++) {
                    const uint4 v = ldg_stream(xp + i * 32, policy(P_X));
                    pk[4 * i] = v.x; pk[4 * i + 1] = v.y; pk[4 * i + 2] = v.z; pk[4 * i + 3] = v.w;
                }
            } else if (k >= LN_STEP && k < LN_STEP + 3) {
                if (k == LN_STEP) {
                    mo[0] = bf_lo(uniform(pk[0])); mo[1] = bf_lo(uniform(pk[16]));
                    mo[2] = mo[3] = mo[4] = mo[5] = 0.f;
                }
#pragma unroll
                for (int i = (k - LN_STEP) * 11; i < (k - LN_STEP) * 11 + 11 && i < 32; i++) {
                    const int r = i & 1;
                    const uint32_t w = pk[r * 16 + i / 2];
                    const float lo = bf_lo(w) - mo[r], hi = bf_hi(w) - mo[r];
                    mo[2 + r] += lo + hi;
                    mo[4 + r] = fmaf(hi, hi, fmaf(lo, lo, mo[4 + r]));
                }
            } else if (k == LN_STEP + 3) {
                const bool second = lane & 16;
                float m1 = (second ? mo[3] : mo[2]) + __shfl_xor_sync(0xffffffffu, second ? mo[2] : mo[3], 16);
                float m2 = (second ? mo[5] : mo[4]) + __shfl_xor_sync(0xffffffffu, second ? mo[4] : mo[5], 16);
#pragma unroll
                for (int o = 8; o > 0; o >>= 1) {
                    m1 += __shfl_xor_sync(0xffffffffu, m1, o);
                    m2 += __shfl_xor_sync(0xffffffffu, m2, o);
                }
                m1 *= 1.f / DM;
                const float var = fmaxf(fmaf(-m1, m1, m2 * (1.f / DM)), 0.f);
                const float mean = round_bf16((second ? mo[1] : mo[0]) + m1);
                const float inv = 1.f / round_bf16(sqrtf(round_bf16(round_bf16(var) + 1e-5f)));
                if ((lane & 15) == 0) g_stats[row + second] = make_float2(-mean, inv);
                const uint32_t split = pack_bf16(inv - round_bf16(inv), inv);
#pragma unroll
                for (int r = 0; r < 2; r++) {
                    const uint32_t f = __shfl_sync(0xffffffffu, split, r * 16);
                    pk[32 + 3 * r] = __byte_perm(__shfl_sync(0xffffffffu, __float_as_uint(mean), r * 16), 0, 0x3232);
                    pk[33 + 3 * r] = __byte_perm(f, 0, 0x3232);
                    pk[34 + 3 * r] = __byte_perm(f, 0, 0x1010);
                }
            } else if (k >= LN_STEP + 4 && k < LN_STEP + 7) {
#pragma unroll
                for (int i = (k - LN_STEP - 4) * 3; i < (k - LN_STEP - 3) * 3 && i < 8; i++) {
                    const uint32_t* n = pk + 32 + i / 4 * 3;
                    uint32_t o[4];
#pragma unroll
                    for (int j = 0; j < 4; j++) o[j] = mul2_bf16x2(sub_bf16x2(pk[i * 4 + j], n[0]), n[1], n[2]);
                    *reinterpret_cast<uint4*>(g_xn + (size_t)row * DM + i * 256 + lane * 8) = make_uint4(o[0], o[1], o[2], o[3]);
                }
                if (k == LN_STEP + 6) signal_stores(0);
            } else if (k == FOLD_STEP) {
                mbar_wait(fold_bar, 0);
#pragma unroll
                for (int j = 0; j < 16; j++) {
                    const uint4 c = lds128(colsum + j * 64 + (lane & 3) * 16);
                    pk[4 * j] = c.x; pk[4 * j + 1] = c.y; pk[4 * j + 2] = c.z; pk[4 * j + 3] = c.w;
                }
            }
        };

        bool gated = false;
#pragma unroll 1
        for (int t = 0; t < G1_TILES; t++) {
#pragma unroll
            for (int k = 0; k < G1_KSTEPS; k++) {
                const int s = k & 3;
                mbar_wait(full1(s), (k >> 2) & 1);
                if (t == 0 && k == 0 && threadIdx.x == 0) TRACE(12);
                if (TRACE_T >= 0 && t == TRACE_T && threadIdx.x == 0) TRACE(44 + k);
                if (wg == 1 && k == G1_KSTEPS - G1_SKEW) asm volatile("bar.sync 1, 256;" ::: "memory");
                const uint64_t da = desc_a(base + s * G1_STAGE_BYTES + wg * 8192);
                const uint64_t db = desc_b(base + s * G1_STAGE_BYTES + A_BYTES);
                wg_fence();
#pragma unroll
                for (int kk = 0; kk < 4; kk++) wgmma_n256(acc, da + kk * 2, db + kk * 128, (k | kk) != 0);
                wg_commit();
                if (wg == 0 && k == G1_KSTEPS - 1) asm volatile("bar.arrive 1, 256;" ::: "memory");
                if (t == 0) chunk_ln(k);
                if (k >= 1 && k <= 8 && gated) {
                    chunk_geglu(k - 1);
                    if (k == 8) signal_stores(t == 1 ? 1 : t + 1);
                }
                if (t != 0 && !gated) {
                    if (k == 0) { chunk_qkv(0); chunk_qkv(1); }
                    if (k >= 6 && k <= 11) chunk_qkv(k - 4);
                    if ((k == 0 || k == 11) && t == 2) signal_stores(k ? 3 : 2);
                }
                wg_wait<1>();
                if (k > 0) release(empty1((k - 1) & 3));
            }
            wg_wait<0>();
            fence_regs(acc);
            release(empty1(3));
            if (t == 0) {
                mbar_wait(fold_bar + 8, 0);
                const uint32_t sp = stats + (cw * 16 + (lane >> 2)) * 8;
                const float2 sa = lds64f(sp), sb = lds64f(sp + 64);
#pragma unroll
                for (int j = 0; j < 16; j++) {
                    const float c0 = __uint_as_float(pk[4 * j]), c1 = __uint_as_float(pk[4 * j + 1]);
                    const float c2 = __uint_as_float(pk[4 * j + 2]), c3 = __uint_as_float(pk[4 * j + 3]);
                    const float* a = acc + 8 * j;
                    pk[4 * j] = pack_bf16(fmaf(sa.x, c0, a[0]) * sa.y, fmaf(sa.x, c1, a[1]) * sa.y);
                    pk[4 * j + 1] = pack_bf16(fmaf(sb.x, c0, a[2]) * sb.y, fmaf(sb.x, c1, a[3]) * sb.y);
                    pk[4 * j + 2] = pack_bf16(fmaf(sa.x, c2, a[4]) * sa.y, fmaf(sa.x, c3, a[5]) * sa.y);
                    pk[4 * j + 3] = pack_bf16(fmaf(sb.x, c2, a[6]) * sb.y, fmaf(sb.x, c3, a[7]) * sb.y);
                }
            } else {
#pragma unroll
                for (int i = 0; i < 64; i++) pk[i] = pack_bf16(acc[2 * i], acc[2 * i + 1]);
            }
            const int nt = t * 8 + nslot;
            gated = !tile_is_qkv(nt);
            optr = !gated ? g_qkv + (size_t)orow * NQKV + tile_index(nt) * 256 + (lane & 3) * 8
                                : g_a2 + (size_t)orow * K2 + DM + tile_index(nt) * 128 + (lane & 3) * 8;
            if (tid == 0) TRACE(16 + wg * 8 + t);
        }

        float accd[64], accs[64];
#pragma unroll
        for (int i = 0; i < 64; i++) accd[i] = 0.f;
#pragma unroll
        for (int u = 0; u < 9; u++) {
            const int q = u % G2_STAGES;
            mbar_wait(full2(q), (u / G2_STAGES) & 1);
            const uint64_t da = desc_a(stage2(q) + wg * 8192), db = desc_b(stage2(q) + A_BYTES);
            wg_fence();
#pragma unroll
            for (int kk = 0; kk < 4; kk++) wgmma_n128(accd, da + kk * 2, db + kk * 128, (u | kk) != 0);
            wg_commit();
            if (u >= 1) { chunk_geglu(u - 1); if (u == 8) signal_stores(6); }
            wg_wait<1>();
            if (u > 0) release(empty2((u - 1) % G2_STAGES));
        }
        {
            int q = 9 % G2_STAGES, qp = 8 % G2_STAGES; uint32_t ph = (9 / G2_STAGES) & 1;
#pragma unroll 1
            for (int u = 9; u < G2_DSTEPS; u++) {
                mbar_wait(full2(q), ph);
                const uint64_t da = desc_a(stage2(q) + wg * 8192), db = desc_b(stage2(q) + A_BYTES);
                wg_fence();
#pragma unroll
                for (int kk = 0; kk < 4; kk++) wgmma_n128(accd, da + kk * 2, db + kk * 128, 1);
                wg_commit();
                wg_wait<1>();
                release(empty2(qp));
                qp = q;
                if (++q == G2_STAGES) { q = 0; ph ^= 1; }
            }
        }
        if (tid == 0) TRACE(16 + wg * 8 + 5);
#pragma unroll
        for (int i = 0; i < 64; i++) accs[i] = 0.f;
        uint32_t gk[32], xr[32];
        const uint32_t xs = aux + cw * 2048;
        const uint32_t xrow = xs + ((lane & 7) + ((lane >> 3) & 1) * 8) * 128;
        auto xaddr = [&](int j) { return xrow + (j >> 2) * 16384 + (((((j & 3) * 2) + (lane >> 4)) ^ (lane & 7)) << 4); };
#pragma unroll
        for (int u = G2_DSTEPS; u < G2_KSTEPS; u++) {
            const int q = u % G2_STAGES, v = u - G2_DSTEPS;
            mbar_wait(full2(q), (u / G2_STAGES) & 1);
            if (G2_SKEW > 0 && wg == 1 && u == G2_KSTEPS - G2_SKEW) asm volatile("bar.sync 1, 256;" ::: "memory");
            const uint64_t da = desc_a(stage2(q) + wg * 8192), db = desc_b(stage2(q) + A_BYTES);
            wg_fence();
#pragma unroll
            for (int kk = 0; kk < 4; kk++) wgmma_n128(accs, da + kk * 2, db + kk * 128, (v | kk) != 0);
            wg_commit();
            if (G2_SKEW > 0 && wg == 0 && u == G2_KSTEPS - 1) asm volatile("bar.arrive 1, 256;" ::: "memory");
            if (v >= 1 && v <= 8) {
#pragma unroll
                for (int i = 4 * (v - 1); i < 4 * v; i++) {
                    const uint32_t d2 = pack_bf16(accd[2 * i], accd[2 * i + 1]);
                    gk[i] = pack_bf16(silu(bf_lo(d2)), silu(bf_hi(d2)));
                }
            }
            if (v == 9) mbar_wait(x_bar, 0);
            if (v >= 9 && v <= 12) {
#pragma unroll
                for (int j = 2 * (v - 9); j < 2 * (v - 8); j++)
                    asm volatile("ldmatrix.sync.aligned.m8n8.x4.shared.b16 {%0,%1,%2,%3}, [%4];"
                                 : "=r"(xr[4 * j]), "=r"(xr[4 * j + 1]), "=r"(xr[4 * j + 2]), "=r"(xr[4 * j + 3])
                                 : "r"(xaddr(j)) : "memory");
            }
            wg_wait<1>();
            if (v == 0) fence_regs(accd);
            if (u - 1 + G2_STAGES < G2_KSTEPS) release(empty2((u - 1) % G2_STAGES));
        }
        wg_wait<0>();
        fence_regs(accs);
        if (tid == 0) TRACE(16 + wg * 8 + 6);
#pragma unroll
        for (int j = 0; j < 8; j++) {
            uint32_t r[4];
#pragma unroll
            for (int i = 0; i < 4; i++) {
                const int e = j * 4 + i;
                r[i] = add_bf16x2(xr[e], mul_bf16x2(pack_bf16(accs[2 * e], accs[2 * e + 1]), gk[e]));
            }
            asm volatile("stmatrix.sync.aligned.m8n8.x4.shared.b16 [%0], {%1,%2,%3,%4};"
                         :: "r"(xaddr(j)), "r"(r[0]), "r"(r[1]), "r"(r[2]), "r"(r[3]) : "memory");
            if (j == 3 || j == 7) {
                asm volatile("fence.proxy.async.shared::cta;" ::: "memory");
                __syncwarp();
                if (lane == 0) {
                    tma_store_2d(&prm.out, xs + (j >> 2) * 16384, nslot * 128 + (j >> 2) * 64, mblk * 128 + cw * 16);
                    asm volatile("cp.async.bulk.commit_group;" ::: "memory");
                }
            }
        }
        if (lane == 0) asm volatile("cp.async.bulk.wait_group.read 0;" ::: "memory");
        if (tid == 0) { TRACE(16 + wg * 8 + 7); if (wg == 1) TRACE_GT(13); }
    }
}

typedef CUresult (*EncodeFn)(CUtensorMap*, CUtensorMapDataType, cuuint32_t, void*, const cuuint64_t*, const cuuint64_t*,
                             const cuuint32_t*, const cuuint32_t*, CUtensorMapInterleave, CUtensorMapSwizzle,
                             CUtensorMapL2promotion, CUtensorMapFloatOOBfill);

void encode(EncodeFn fn, CUtensorMap* m, const void* ptr, int rank, const cuuint64_t* dims, const cuuint64_t* strides,
            const cuuint32_t* box) {
    const cuuint32_t es[5] = {1, 1, 1, 1, 1};
    fn(m, CU_TENSOR_MAP_DATA_TYPE_BFLOAT16, rank, const_cast<void*>(ptr), dims, strides, box, es,
       CU_TENSOR_MAP_INTERLEAVE_NONE, CU_TENSOR_MAP_SWIZZLE_128B, CU_TENSOR_MAP_L2_PROMOTION_L2_128B,
       CU_TENSOR_MAP_FLOAT_OOB_FILL_NONE);
}
void encode_2d(EncodeFn fn, CUtensorMap* m, const void* ptr, int cols, int box_rows) {
    const cuuint64_t dims[2] = {(cuuint64_t)cols, SEQ}, strides[1] = {(cuuint64_t)cols * 2};
    const cuuint32_t box[2] = {64, (cuuint32_t)box_rows};
    encode(fn, m, ptr, 2, dims, strides, box);
}
void encode_w1(EncodeFn fn, CUtensorMap* m, const void* ptr, int cols) {
    const cuuint64_t dims[3] = {64, DM, (cuuint64_t)cols / 64}, strides[2] = {(cuuint64_t)cols * 2, 128};
    const cuuint32_t box[3] = {64, 64, 2};
    encode(fn, m, ptr, 3, dims, strides, box);
}
void encode_qk(EncodeFn fn, CUtensorMap* m, const void* ptr) {
    const cuuint64_t dims[3] = {DM, SEQ, 3}, strides[2] = {NQKV * 2, DM * 2};
    const cuuint32_t box[3] = {64, 16, 2};
    encode(fn, m, ptr, 3, dims, strides, box);
}
void encode_a2(EncodeFn fn, CUtensorMap* m, const void* ptr) {
    const cuuint64_t dims[3] = {K2, 2, SEQ / 2}, strides[2] = {(cuuint64_t)SEQ * K2, K2 * 2};
    const cuuint32_t box[3] = {64, 2, 64};
    encode(fn, m, ptr, 3, dims, strides, box);
}
void encode_w2(EncodeFn fn, CUtensorMap* m, const void* ptr, int rows) {
    const cuuint64_t rb = DM * 2;
    const cuuint64_t dims[5] = {DM, 2, 4, 4, (cuuint64_t)rows / 32}, strides[4] = {rb, 8 * rb, 2 * rb, 32 * rb};
    const cuuint32_t box[5] = {64, 2, 4, 4, 2};
    encode(fn, m, ptr, 5, dims, strides, box);
}

}

extern "C" void kernel_launch(void* const* d_in, const int* in_sizes, int n_in, void* d_out, int out_size) {
    (void)in_sizes; (void)n_in; (void)out_size;
    static EncodeFn fn = nullptr;
    static void *p_xn = nullptr, *p_qkv = nullptr, *p_a2 = nullptr;
    if (!fn) {
        cudaDriverEntryPointQueryResult st;
        cudaGetDriverEntryPoint("cuTensorMapEncodeTiled", (void**)&fn, cudaEnableDefault, &st);
        cudaGetSymbolAddress(&p_xn, g_xn);
        cudaGetSymbolAddress(&p_qkv, g_qkv);
        cudaGetSymbolAddress(&p_a2, g_a2);
        cudaFuncSetAttribute(fused_kernel, cudaFuncAttributeMaxDynamicSharedMemorySize, SMEM_BYTES);
    }
    Params prm;
    encode_2d(fn, &prm.x, d_in[0], DM, 128);
    encode_2d(fn, &prm.xn, p_xn, DM, 128);
    encode_w1(fn, &prm.wqkv, d_in[1], NQKV);
    encode_w1(fn, &prm.wg, d_in[4], DF);
    encode_w1(fn, &prm.wu, d_in[5], DF);
    encode_qk(fn, &prm.qk, p_qkv);
    encode_2d(fn, &prm.v, p_qkv, NQKV, 16);
    encode_2d(fn, &prm.o, p_a2, K2, 16);
    encode_a2(fn, &prm.a2, p_a2);
    encode_w2(fn, &prm.wo, d_in[2], DM);
    encode_w2(fn, &prm.wd, d_in[6], DF);
    encode_2d(fn, &prm.out, d_out, DM, 16);
    prm.px = (const __nv_bfloat16*)d_in[0];
    prm.zero = 0;
    fused_kernel<<<NCTA, 384, SMEM_BYTES>>>(prm);
}
```

```cpp
#include <cuda_runtime.h>
#include <cuda_bf16.h>
#include <cuda.h>
#include <stdint.h>
#include <type_traits>

#define P_W1 1
#define P_X 1
#define P_XN4 1
#define P_W2 1
#define P_A2 1
#define P_QKV 1

#define ORD1 1
#define ORD2 1
#define LN_STEP 3
#define FOLD_STEP 14
#define CS_AT empty1(1)
#define PF_X 0
#define PF_W 0

namespace {

constexpr int SEQ = 2048, DM = 1024, DF = 3584, K2 = DM + DF, NQKV = 3 * DM;
constexpr int NGEMM = 128, NCTA = 132;
constexpr int G1_STAGES = 4, G1_STAGE_BYTES = 49152, G1_KSTEPS = 16, G1_TILES = 5;
constexpr int G2_STAGES = 6, G2_STAGE_BYTES = 32768, G2_KSTEPS = 72, G2_LATE = 40, G2_DSTEPS = 56, G2_LAST = 68;
constexpr int A_BYTES = 16384;
constexpr int AUX_OFF = G1_STAGES * G1_STAGE_BYTES;
constexpr int BAR_OFF = AUX_OFF + 32768;
constexpr int SMEM_BYTES = BAR_OFF + 2560;
constexpr int G1_SKEW = 2, G2_SKEW = 2;
constexpr int CONSUMER_REGS = 224, AUX_REGS = 56;
constexpr int ATT_SLOT = 8192;

enum { F_LN = 0, F_QKV = 1, F_EARLY = 2, F_LATE = 3, F_O = 4, F_CS = 5 };
constexpr unsigned CNT_LN = 8, CNT_QKV = 32, CNT_EARLY = 20, CNT_LATE = 8, CNT_O = 4, CNT_CS = 16;

__device__ __align__(1024) __nv_bfloat16 g_xn[SEQ * DM];
__device__ __align__(1024) __nv_bfloat16 g_qkv[SEQ * NQKV];
__device__ __align__(1024) __nv_bfloat16 g_a2[SEQ * K2];
__device__ __align__(128) float2 g_stats[SEQ];
__device__ __align__(128) float g_colsum[16 * 2048];
__device__ __align__(128) unsigned g_flags[6 * 16 * 32];
__device__ __align__(128) unsigned g_epoch[NCTA * 16];

#define TRACE_T -1
#define TRACE(slot) do {} while (0)
#define TRACE_GT(slot) do {} while (0)

__device__ __forceinline__ uint32_t smem_u32(const void* p) { return (uint32_t)__cvta_generic_to_shared(p); }
__device__ __forceinline__ void mbar_init(uint32_t bar, uint32_t cnt) {
    asm volatile("mbarrier.init.shared::cta.b64 [%0], %1;" :: "r"(bar), "r"(cnt) : "memory");
}
__device__ __forceinline__ void mbar_expect_tx(uint32_t bar, uint32_t bytes) {
    asm volatile("mbarrier.arrive.expect_tx.shared::cta.b64 _, [%0], %1;" :: "r"(bar), "r"(bytes) : "memory");
}
__device__ __forceinline__ void mbar_arrive(uint32_t bar) {
    asm volatile("mbarrier.arrive.shared::cta.b64 _, [%0];" :: "r"(bar) : "memory");
}
__device__ __forceinline__ void mbar_arrive_cluster(uint32_t bar, uint32_t cta) {
    asm volatile("{\n.reg .b32 ra;\nmapa.shared::cluster.u32 ra, %0, %1;\nmbarrier.arrive.shared::cluster.b64 _, [ra];\n}"
                 :: "r"(bar), "r"(cta) : "memory");
}
__device__ __forceinline__ bool mbar_try_wait(uint32_t bar, uint32_t parity) {
    uint32_t ok;
    asm volatile("{\n.reg .pred p;\nmbarrier.try_wait.parity.shared::cta.b64 p, [%1], %2;\nselp.u32 %0, 1, 0, p;\n}"
                 : "=r"(ok) : "r"(bar), "r"(parity) : "memory");
    return ok;
}
__device__ __forceinline__ bool mbar_test(uint32_t bar, uint32_t parity) {
    uint32_t ok;
    asm volatile("{\n.reg .pred p;\nmbarrier.test_wait.parity.shared::cta.b64 p, [%1], %2;\nselp.u32 %0, 1, 0, p;\n}"
                 : "=r"(ok) : "r"(bar), "r"(parity) : "memory");
    return ok;
}
__device__ __forceinline__ void mbar_wait(uint32_t bar, uint32_t parity) {
#pragma unroll 1
    for (int spins = 0; !mbar_try_wait(bar, parity) && spins < (1 << 17); spins++) {}
}
template <bool WARP = false> __device__ __forceinline__ void flag_wait(const unsigned* p, unsigned target) {
#pragma unroll 1
    for (int spins = 0; spins < (1 << 19); spins++) {
        unsigned v;
        asm volatile("ld.acquire.gpu.global.u32 %0, [%1];" : "=r"(v) : "l"(p) : "memory");
        if (WARP ? __all_sync(0xffffffffu, (int)(v - target) >= 0) : (int)(v - target) >= 0) break;
        __nanosleep(64);
    }
}
__device__ __forceinline__ void flag_add(unsigned* p) {
    asm volatile("red.release.gpu.global.add.u32 [%0], 1;" :: "l"(p) : "memory");
}
__device__ __forceinline__ bool elect_one() {
    uint32_t ok;
    asm volatile("{\n.reg .pred p;\nelect.sync _|p, 0xffffffff;\nselp.u32 %0, 1, 0, p;\n}" : "=r"(ok));
    return ok;
}
__device__ __forceinline__ void fence_proxy_async() { asm volatile("fence.proxy.async.global;" ::: "memory"); }
__device__ __forceinline__ uint4 lds128(uint32_t addr) {
    uint4 v;
    asm volatile("ld.shared.v4.u32 {%0,%1,%2,%3}, [%4];" : "=r"(v.x), "=r"(v.y), "=r"(v.z), "=r"(v.w) : "r"(addr) : "memory");
    return v;
}
__device__ __forceinline__ float2 lds64f(uint32_t addr) {
    float2 v;
    asm volatile("ld.shared.v2.f32 {%0,%1}, [%2];" : "=f"(v.x), "=f"(v.y) : "r"(addr) : "memory");
    return v;
}
__device__ __forceinline__ void sts128(uint32_t addr, uint4 v) {
    asm volatile("st.shared.v4.u32 [%0], {%1,%2,%3,%4};" :: "r"(addr), "r"(v.x), "r"(v.y), "r"(v.z), "r"(v.w) : "memory");
}
__device__ __forceinline__ void sts64f(uint32_t addr, float a, float b) {
    asm volatile("st.shared.v2.f32 [%0], {%1,%2};" :: "r"(addr), "f"(a), "f"(b) : "memory");
}

__device__ __forceinline__ uint64_t policy(bool stream) {
    uint64_t p;
    if (stream) asm("createpolicy.fractional.L2::evict_first.b64 %0, 1.0;" : "=l"(p));
    else asm("createpolicy.fractional.L2::evict_normal.b64 %0, 1.0;" : "=l"(p));
    return p;
}
__device__ __forceinline__ void tma_2d(uint32_t dst, const CUtensorMap* m, uint32_t bar, int c0, int c1, uint64_t pol) {
    asm volatile("cp.async.bulk.tensor.2d.shared::cluster.global.mbarrier::complete_tx::bytes.L2::cache_hint"
                 " [%0], [%1, {%3, %4}], [%2], %5;"
                 :: "r"(dst), "l"(m), "r"(bar), "r"(c0), "r"(c1), "l"(pol) : "memory");
}
__device__ __forceinline__ void tma_3d(uint32_t dst, const CUtensorMap* m, uint32_t bar, int c0, int c1, int c2, uint64_t pol) {
    asm volatile("cp.async.bulk.tensor.3d.shared::cluster.global.mbarrier::complete_tx::bytes.L2::cache_hint"
                 " [%0], [%1, {%3, %4, %5}], [%2], %6;"
                 :: "r"(dst), "l"(m), "r"(bar), "r"(c0), "r"(c1), "r"(c2), "l"(pol) : "memory");
}
__device__ __forceinline__ void tma_3d_mc(uint32_t dst, const CUtensorMap* m, uint32_t bar, int c1, int c2, uint64_t pol) {
    asm volatile("cp.async.bulk.tensor.3d.shared::cluster.global.mbarrier::complete_tx::bytes.multicast::cluster.L2::cache_hint"
                 " [%0], [%1, {%3, %4, %5}], [%2], %6, %7;"
                 :: "r"(dst), "l"(m), "r"(bar), "r"(0), "r"(c1), "r"(c2), "h"((uint16_t)3), "l"(pol) : "memory");
}
__device__ __forceinline__ void tma_5d_mc(uint32_t dst, const CUtensorMap* m, uint32_t bar, int c0, int c4, uint64_t pol) {
    asm volatile("cp.async.bulk.tensor.5d.shared::cluster.global.mbarrier::complete_tx::bytes.multicast::cluster.L2::cache_hint"
                 " [%0], [%1, {%3, %4, %4, %4, %5}], [%2], %6, %7;"
                 :: "r"(dst), "l"(m), "r"(bar), "r"(c0), "r"(0), "r"(c4), "h"((uint16_t)3), "l"(pol) : "memory");
}
__device__ __forceinline__ void tma_store_2d(const CUtensorMap* m, uint32_t src, int c0, int c1) {
    asm volatile("cp.async.bulk.tensor.2d.global.shared::cta.bulk_group [%0, {%2, %3}], [%1];"
                 :: "l"(m), "r"(src), "r"(c0), "r"(c1) : "memory");
}
__device__ __forceinline__ uint4 ldg_stream(const void* p, uint64_t pol) {
    uint4 v;
    asm volatile("ld.global.nc.L1::no_allocate.L2::cache_hint.v4.u32 {%0,%1,%2,%3}, [%4], %5;"
                 : "=r"(v.x), "=r"(v.y), "=r"(v.z), "=r"(v.w) : "l"(p), "l"(pol));
    return v;
}
__device__ __forceinline__ void bulk_load(uint32_t dst, const void* src, uint32_t bytes, uint32_t bar) {
    asm volatile("cp.async.bulk.shared::cluster.global.mbarrier::complete_tx::bytes [%0], [%1], %2, [%3];"
                 :: "r"(dst), "l"(src), "r"(bytes), "r"(bar) : "memory");
}
__device__ __forceinline__ void prefetch_3d(const CUtensorMap* m, int c1, int c2, uint64_t pol) {
    asm volatile("cp.async.bulk.prefetch.tensor.3d.L2.global.L2::cache_hint [%0, {%1, %2, %3}], %4;"
                 :: "l"(m), "r"(0), "r"(c1), "r"(c2), "l"(pol) : "memory");
}
__device__ __forceinline__ void prefetch_map(const CUtensorMap* m) {
    asm volatile("prefetch.tensormap [%0];" :: "l"(m) : "memory");
}
__device__ __forceinline__ void wg_fence() { asm volatile("wgmma.fence.sync.aligned;" ::: "memory"); }
__device__ __forceinline__ void wg_commit() { asm volatile("wgmma.commit_group.sync.aligned;" ::: "memory"); }
template <int N> __device__ __forceinline__ void wg_wait() { asm volatile("wgmma.wait_group.sync.aligned %0;" :: "n"(N) : "memory"); }

__device__ __forceinline__ uint64_t desc_a(uint32_t addr) {
    return (uint64_t)((addr & 0x3FFFF) >> 4) | (1ull << 16) | (64ull << 32) | (1ull << 62);
}
__device__ __forceinline__ uint64_t desc_b(uint32_t addr) {
    return (uint64_t)((addr & 0x3FFFF) >> 4) | (512ull << 16) | (64ull << 32) | (1ull << 62);
}

#define R8(d, o) "+f"(d[o]), "+f"(d[o+1]), "+f"(d[o+2]), "+f"(d[o+3]), "+f"(d[o+4]), "+f"(d[o+5]), "+f"(d[o+6]), "+f"(d[o+7])
#define R32(d, o) R8(d, o), R8(d, o+8), R8(d, o+16), R8(d, o+24)
#define R64(d, o) R32(d, o), R32(d, o+32)

__device__ __forceinline__ void wgmma_n256(float (&d)[128], uint64_t da, uint64_t db, int scale_d) {
    asm volatile("{\n.reg .pred p;\nsetp.ne.b32 p, %130, 0;\n"
        "wgmma.mma_async.sync.aligned.m64n256k16.f32.bf16.bf16 "
        "{%0,%1,%2,%3,%4,%5,%6,%7,%8,%9,%10,%11,%12,%13,%14,%15,%16,%17,%18,%19,%20,%21,%22,%23,%24,%25,%26,%27,%28,%29,%30,%31,"
        "%32,%33,%34,%35,%36,%37,%38,%39,%40,%41,%42,%43,%44,%45,%46,%47,%48,%49,%50,%51,%52,%53,%54,%55,%56,%57,%58,%59,%60,%61,%62,%63,"
        "%64,%65,%66,%67,%68,%69,%70,%71,%72,%73,%74,%75,%76,%77,%78,%79,%80,%81,%82,%83,%84,%85,%86,%87,%88,%89,%90,%91,%92,%93,%94,%95,"
        "%96,%97,%98,%99,%100,%101,%102,%103,%104,%105,%106,%107,%108,%109,%110,%111,%112,%113,%114,%115,%116,%117,%118,%119,%120,%121,%122,%123,%124,%125,%126,%127},"
        " %128, %129, p, 1, 1, 0, 1;\n}"
        : R64(d, 0), R64(d, 64) : "l"(da), "l"(db), "r"(scale_d));
}
__device__ __forceinline__ void wgmma_n128(float (&d)[64], uint64_t da, uint64_t db, int scale_d) {
    asm volatile("{\n.reg .pred p;\nsetp.ne.b32 p, %66, 0;\n"
        "wgmma.mma_async.sync.aligned.m64n128k16.f32.bf16.bf16 "
        "{%0,%1,%2,%3,%4,%5,%6,%7,%8,%9,%10,%11,%12,%13,%14,%15,%16,%17,%18,%19,%20,%21,%22,%23,%24,%25,%26,%27,%28,%29,%30,%31,"
        "%32,%33,%34,%35,%36,%37,%38,%39,%40,%41,%42,%43,%44,%45,%46,%47,%48,%49,%50,%51,%52,%53,%54,%55,%56,%57,%58,%59,%60,%61,%62,%63},"
        " %64, %65, p, 1, 1, 0, 1;\n}"
        : R64(d, 0) : "l"(da), "l"(db), "r"(scale_d));
}

__device__ __forceinline__ uint32_t pack_bf16(float lo, float hi) {
    uint32_t r; asm("cvt.rn.bf16x2.f32 %0, %1, %2;" : "=r"(r) : "f"(hi), "f"(lo)); return r;
}
__device__ __forceinline__ float bf_lo(uint32_t v) { return __uint_as_float(v << 16); }
__device__ __forceinline__ float bf_hi(uint32_t v) { return __uint_as_float(v & 0xffff0000u); }
__device__ __forceinline__ float round_bf16(float v) { return bf_lo(pack_bf16(v, 0.f)); }
__device__ __forceinline__ uint32_t mul_bf16x2(uint32_t a, uint32_t b) {
    uint32_t r; asm("mul.rn.bf16x2 %0, %1, %2;" : "=r"(r) : "r"(a), "r"(b)); return r;
}
__device__ __forceinline__ uint32_t add_bf16x2(uint32_t a, uint32_t b) {
    uint32_t r; asm("add.rn.bf16x2 %0, %1, %2;" : "=r"(r) : "r"(a), "r"(b)); return r;
}
__device__ __forceinline__ uint32_t sub_bf16x2(uint32_t a, uint32_t b) {
    uint32_t r; asm("sub.rn.bf16x2 %0, %1, %2;" : "=r"(r) : "r"(a), "r"(b)); return r;
}
__device__ __forceinline__ uint32_t mul2_bf16x2(uint32_t a, uint32_t hi, uint32_t lo) {
    uint32_t r; asm("fma.rn.bf16x2 %0, %1, %2, %3;" : "=r"(r) : "r"(a), "r"(hi), "r"(mul_bf16x2(a, lo))); return r;
}
__device__ __forceinline__ float tanh_fast(float x) { float r; asm("tanh.approx.f32 %0, %1;" : "=f"(r) : "f"(x)); return r; }
__device__ __forceinline__ float gelu_tanh(float g) {
    float t = fmaf(g * g, 0.044715f * 0.7978845608f, 0.7978845608f) * g;
    float hg = 0.5f * g;
    return fmaf(hg, tanh_fast(t), hg);
}
__device__ __forceinline__ uint32_t geglu2(uint32_t g2, uint32_t u2) {
    return mul_bf16x2(pack_bf16(gelu_tanh(bf_lo(g2)), gelu_tanh(bf_hi(g2))), u2);
}
__device__ __forceinline__ float silu(float d) {
    float hd = 0.5f * d;
    return fmaf(hd, tanh_fast(hd), hd);
}
__device__ __forceinline__ float ex2_fast(float x) { float r; asm("ex2.approx.ftz.f32 %0, %1;" : "=f"(r) : "f"(x)); return r; }
__device__ __forceinline__ void unpack8(uint4 v, float (&f)[8]) {
    f[0] = bf_lo(v.x); f[1] = bf_hi(v.x); f[2] = bf_lo(v.y); f[3] = bf_hi(v.y);
    f[4] = bf_lo(v.z); f[5] = bf_hi(v.z); f[6] = bf_lo(v.w); f[7] = bf_hi(v.w);
}
template <int N> __device__ __forceinline__ void fence_regs(float (&d)[N]) {
#pragma unroll
    for (int i = 0; i < N; i++) asm volatile("" : "+f"(d[i]) :: "memory");
}

__device__ __forceinline__ float rcp_fast(float x) { float r; asm("rcp.approx.ftz.f32 %0, %1;" : "=f"(r) : "f"(x)); return r; }
__device__ __forceinline__ uint32_t max_bf16x2(uint32_t a, uint32_t b) {
    uint32_t r; asm("max.bf16x2 %0, %1, %2;" : "=r"(r) : "r"(a), "r"(b)); return r;
}
__device__ __forceinline__ uint4 ldsm4(uint32_t addr) {
    uint4 v;
    asm volatile("ldmatrix.sync.aligned.m8n8.x4.shared.b16 {%0,%1,%2,%3}, [%4];"
                 : "=r"(v.x), "=r"(v.y), "=r"(v.z), "=r"(v.w) : "r"(addr) : "memory");
    return v;
}
__device__ __forceinline__ uint4 ldsm4_t(uint32_t addr) {
    uint4 v;
    asm volatile("ldmatrix.sync.aligned.m8n8.x4.trans.shared.b16 {%0,%1,%2,%3}, [%4];"
                 : "=r"(v.x), "=r"(v.y), "=r"(v.z), "=r"(v.w) : "r"(addr) : "memory");
    return v;
}
__device__ __forceinline__ void mma_16816(float (&c)[4], uint32_t a0, uint32_t a1, uint32_t a2, uint32_t a3, uint32_t b0, uint32_t b1) {
    asm("mma.sync.aligned.m16n8k16.row.col.f32.bf16.bf16.f32 {%0,%1,%2,%3}, {%4,%5,%6,%7}, {%8,%9}, {%0,%1,%2,%3};"
        : "+f"(c[0]), "+f"(c[1]), "+f"(c[2]), "+f"(c[3]) : "r"(a0), "r"(a1), "r"(a2), "r"(a3), "r"(b0), "r"(b1));
}
__device__ __forceinline__ void mma_1688(float (&c)[4], uint32_t a0, uint32_t a1, uint32_t b0) {
    asm("mma.sync.aligned.m16n8k8.row.col.f32.bf16.bf16.f32 {%0,%1,%2,%3}, {%4,%5}, {%6}, {%0,%1,%2,%3};"
        : "+f"(c[0]), "+f"(c[1]), "+f"(c[2]), "+f"(c[3]) : "r"(a0), "r"(a1), "r"(b0));
}
__device__ __forceinline__ void qk_tile(float (&c)[4], const uint4& q0, const uint4& q1, const uint4& k, float init) {
    c[0] = c[1] = c[2] = c[3] = init;
    mma_16816(c, q0.x, q0.y, q0.z, q0.w, k.x, k.y);
    mma_16816(c, q1.x, q1.y, q1.z, q1.w, k.z, k.w);
}
__device__ __forceinline__ uint32_t scaled_logits(bool first, float a0, float a1, float b0, float b1) {
    return mul2_bf16x2(pack_bf16(first ? a0 : b0, first ? a1 : b1), 0x3e353e35u, 0x379e379eu);
}
template <typename T> __device__ __forceinline__ T uniform(T v) { return __shfl_sync(0xffffffffu, v, 0); }

__device__ __forceinline__ void attention(const CUtensorMap* maps, uint32_t base, uint32_t zero, int grp, int warp, int lane) {
    constexpr float LOG2E = 1.4426950408889634f;
    const int g = lane >> 2, t = lane & 3;
    const bool up0 = 2 * t > g, up1 = 2 * t + 1 > g;
    const uint32_t keep = (up0 ? 0x0000ffffu : 0u) | (up1 ? 0xffff0000u : 0u);
    const uint32_t buf = base + warp * 2 * ATT_SLOT, bar = base + AUX_OFF + warp * 16;
    const uint32_t qoff = (lane & 15) * 128 + (((lane >> 4) ^ (lane & 7)) << 4);
    const uint32_t koff = 2048 + (lane & 7) * 128 + (((lane >> 3) ^ (lane & 7)) << 4);
    const uint32_t rest_bar = base + AUX_OFF + 192;
    const int col = uniform(grp * 256), first = uniform((warp / 3 * 32 + warp % 3 * 11) * 16);
    const CUtensorMap* const mqk = reinterpret_cast<const CUtensorMap*>(uniform(reinterpret_cast<uint64_t>(maps)));
    const CUtensorMap *const mv = mqk + 1, *const mo = mqk + 2;
    const uint64_t pol = policy(P_QKV);
    uint4 kp[2], vp[2];
    uint32_t l0[2], l1[2], m[2];
    float s[2][3][4];
    auto scores = [&](uint32_t st, int row) {
        const float before = (row & 1023) == 0 ? -5.656854e9f : 0.f;
#pragma unroll
        for (int h = 0; h < 2; h++) {
            const uint4 q0 = ldsm4(st + (qoff ^ (h * 64))), q1 = ldsm4(st + (qoff ^ (h * 64 + 32)));
            const uint4 k0 = ldsm4(st + (koff ^ (h * 64))), k1 = ldsm4(st + 1024 + (koff ^ (h * 64)));
            qk_tile(s[h][0], q0, q1, kp[h], before);
            qk_tile(s[h][1], q0, q1, k0, 0.f);
            qk_tile(s[h][2], q0, q1, k1, 0.f);
            kp[h] = k1;
        }
    };
    auto logits = [&]() {
#pragma unroll
        for (int h = 0; h < 2; h++) {
            l0[h] = scaled_logits(up0, s[h][0][0], s[h][1][2], s[h][1][0], s[h][2][2]);
            l1[h] = scaled_logits(up1, s[h][0][1], s[h][1][3], s[h][1][1], s[h][2][3]);
            m[h] = max_bf16x2(l0[h], l1[h]);
            m[h] = max_bf16x2(m[h], __shfl_xor_sync(0xffffffffu, m[h], 1));
        }
    };
    auto row_max = [&]() {
#pragma unroll
        for (int h = 0; h < 2; h++) m[h] = max_bf16x2(m[h], __shfl_xor_sync(0xffffffffu, m[h], 2));
    };
    auto next = [](uint32_t p) {
        return (0x80200400u >> (p >> 4 & 31) & 1) > (p >> 15 & 1) ? p + (64 << 16) + 0x8000 : (p + 16) & ~0x8800u;
    };
    auto exchange = [&](uint32_t st, uint32_t b, uint32_t po, uint32_t pv, uint32_t pq) {
        asm volatile("{\n.reg .pred e, p, q;\n"
            "fence.proxy.async.shared::cta;\n"
            "bar.warp.sync 0xffffffff;\n"
            "elect.sync _|e, 0xffffffff;\n"
            "setp.eq.and.b32 p, %12, 0, e;\n"
            "setp.lt.and.s32 q, %8, %13, e;\n"
            "@q mbarrier.arrive.expect_tx.shared::cta.b64 _, [%2], 6144;\n"
            "@q cp.async.bulk.tensor.3d.shared::cluster.global.mbarrier::complete_tx::bytes.L2::cache_hint [%0], [%3, {%6, %7, %14}], [%2], %15;\n"
            "@q cp.async.bulk.tensor.2d.shared::cluster.global.mbarrier::complete_tx::bytes.L2::cache_hint [%0 + 4096], [%4, {%8, %9}], [%2], %15;\n"
            "@e cp.async.bulk.wait_group.read 0;\n"
            "@p cp.async.bulk.tensor.2d.global.shared::cta.bulk_group [%5, {%10, %11}], [%1 + 6144];\n"
            "@e cp.async.bulk.commit_group;\n"
            "bar.warp.sync 0xffffffff;\n}"
            :: "r"(st), "r"(st ^ ATT_SLOT), "r"(b), "l"(mqk), "l"(mv), "l"(mo), "r"(pq >> 16), "r"(pq & 2047),
               "r"((pv >> 16) + 2 * DM), "r"(pv & 2047), "r"(po >> 16), "r"(po & 2047), "r"(po & 0x8000),
               "r"(col + 256 + 2 * DM), "r"(0), "l"(pol) : "memory");
    };
    auto publish = [&](auto pending, int part) {
        asm volatile("{\n.reg .pred e;\n.reg .u32 n;\n"
            "elect.sync _|e, 0xffffffff;\n"
            "cp.async.bulk.wait_group %2;\n"
            "@e atom.acq_rel.cta.shared.add.u32 n, [%1], 1;\n"
            "setp.eq.and.u32 e, n, 11, e;\n"
            "@e red.release.gpu.global.add.u32 [%0], 1;\n}"
            :: "l"(g_flags + F_O * 512 + part * 32), "r"(rest_bar + 8 + part * 4), "n"(pending.value) : "memory");
    };
    const unsigned epoch = __ldcg(g_epoch + blockIdx.x * 16) + 1;
    if (elect_one()) {
        mbar_init(bar, 1); mbar_init(bar + 8, 1);
        if (warp == 2) { mbar_init(rest_bar, 32); sts64f(rest_bar + 8, 0.f, 0.f); }
        asm volatile("fence.mbarrier_init.release.cluster;" ::: "memory");
        prefetch_map(mqk); prefetch_map(mv); prefetch_map(mo);
    }
    __syncthreads();
    if (elect_one()) {
        g_epoch[blockIdx.x * 16] = epoch;
        flag_wait(g_flags + F_QKV * 512 + grp * 32, epoch * CNT_QKV);
        fence_proxy_async();
        mbar_expect_tx(bar + 8, 8192);
        tma_3d(buf + ATT_SLOT, mqk, bar + 8, col, first, 0, pol);
        tma_2d(buf + ATT_SLOT + 4096, mv, bar + 8, col + 2 * DM, first - 16, policy(false));
        tma_2d(buf + ATT_SLOT + 6144, mv, bar + 8, col + DM, first - 16, policy(false));
        mbar_expect_tx(bar, 6144);
        tma_3d(buf, mqk, bar, col, first + 16, 0, pol);
        tma_2d(buf + 4096, mv, bar, col + 2 * DM, first, pol);
        if (warp == 0) TRACE(9);
    }
    __syncwarp();
    mbar_wait(bar + 8, 0);
#pragma unroll
    for (int h = 0; h < 2; h++) {
        kp[h] = ldsm4(buf + ATT_SLOT + 5120 + (koff ^ (h * 64)));
        vp[h] = ldsm4_t(buf + ATT_SLOT + 3072 + (koff ^ (h * 64)));
    }
    scores(buf + ATT_SLOT, first);
    uint32_t pm = 0x8000, p0 = col << 16 | first, p1 = p0 + 16, p2 = p0 + 32, p3 = p0 + 48;
    exchange(buf + ATT_SLOT, bar + 8, pm, p1, p2);
    logits();
    row_max();
    uint32_t st = buf, b = bar, cnt = 1;
    const uint32_t relay = warp == 2 ? 7 : 0;
    bool ready = false;
#pragma unroll 1
    while (p0 >> 16 < col + 256) {
        uint32_t pa[2], pb[2];
        if (!ready) mbar_wait(b, (cnt >> 1) & 1);
        uint4 v[2][2];
#pragma unroll
        for (int h = 0; h < 2; h++) {
            const float ma = -LOG2E * bf_lo(m[h]), mb = -LOG2E * bf_hi(m[h]);
            const float a0 = ex2_fast(fmaf(bf_lo(l0[h]), LOG2E, ma)), a1 = ex2_fast(fmaf(bf_lo(l1[h]), LOG2E, ma));
            const float b0 = ex2_fast(fmaf(bf_hi(l0[h]), LOG2E, mb)), b1 = ex2_fast(fmaf(bf_hi(l1[h]), LOG2E, mb));
            float sum[4] = {0.f, 0.f, 0.f, 0.f};
            mma_1688(sum, pack_bf16(a0, a1), pack_bf16(b0, b1), 0x3f803f80u);
            const float ra = rcp_fast(sum[0]), rb = rcp_fast(sum[2]);
            pa[h] = pack_bf16(a0 * ra, a1 * ra);
            pb[h] = pack_bf16(b0 * rb, b1 * rb);
        }
        scores(st, p1);
#pragma unroll
        for (int h = 0; h < 2; h++) {
            v[h][0] = ldsm4_t(st + 4096 + (qoff ^ (h * 64)));
            v[h][1] = ldsm4_t(st + 4096 + (qoff ^ (h * 64 + 32)));
        }
        if (cnt == relay) {
            flag_wait<true>(g_flags + F_QKV * 512 + 128 + grp * 32, epoch * CNT_QKV);
            fence_proxy_async();
            mbar_arrive(rest_bar);
        }
        if (cnt == 8) {
#pragma unroll 1
            for (int spins = 0; !__all_sync(0xffffffffu, mbar_try_wait(rest_bar, 0)) && spins < (1 << 17); spins++) {}
        }
        if (cnt == 37) publish(std::integral_constant<int, 1>(), 0);
        exchange(st, b, pm, p2, p3);
        pm = p0; p0 = p1; p1 = p2; p2 = p3; p3 = next(p3);
        logits();
        float o[2][4][4];
#pragma unroll
        for (int h = 0; h < 2; h++) {
            const uint32_t prev[4] = {vp[h].x, vp[h].y, vp[h].z, vp[h].w};
            const uint32_t own[8] = {v[h][0].x, v[h][0].y, v[h][0].z, v[h][0].w, v[h][1].x, v[h][1].y, v[h][1].z, v[h][1].w};
            const uint32_t a0 = pa[h] & keep, a1 = pa[h] & ~keep, a2 = pb[h] & keep, a3 = pb[h] & ~keep;
            const uint32_t z0 = pa[h] & zero, z1 = pb[h] & zero;
#pragma unroll
            for (int j = 0; j < 4; j++) {
                o[h][j][0] = o[h][j][1] = o[h][j][2] = o[h][j][3] = 0.f;
                mma_1688(o[h][j], a0, z0, prev[j]);
                mma_16816(o[h][j], a1, a2, z1, a3, own[2 * j], own[2 * j + 1]);
            }
            vp[h] = make_uint4(own[1], own[3], own[5], own[7]);
        }
        row_max();
        b ^= 8; cnt++;
        ready = mbar_test(b, (cnt >> 1) & 1);
#pragma unroll
        for (int h = 0; h < 2; h++) {
#pragma unroll
            for (int d = 0; d < 2; d++)
                asm volatile("stmatrix.sync.aligned.m8n8.x4.shared.b16 [%0], {%1,%2,%3,%4};"
                             :: "r"(st + 6144 + (qoff ^ (h * 64 + d * 32))),
                                "r"(pack_bf16(o[h][2 * d][0], o[h][2 * d][1])), "r"(pack_bf16(o[h][2 * d][2], o[h][2 * d][3])),
                                "r"(pack_bf16(o[h][2 * d + 1][0], o[h][2 * d + 1][1])),
                                "r"(pack_bf16(o[h][2 * d + 1][2], o[h][2 * d + 1][3])) : "memory");
        }
        st ^= ATT_SLOT;
    }
    exchange(st, b, pm, p0, p0);
    publish(std::integral_constant<int, 0>(), 1);
    if (threadIdx.x == 0) TRACE(10);
}

struct Params {
    CUtensorMap x, xn, wqkv, wg, wu, qk, v, o, a2, wo, wd, out;
    const __nv_bfloat16* px;
    uint32_t zero;
};

__device__ __forceinline__ bool tile_is_qkv(int nt) { return nt < 4 || (nt >= 8 && nt < 16); }
__device__ __forceinline__ int tile_index(int nt) { return nt < 4 ? nt + 8 : (nt < 8 ? nt - 4 : (nt < 16 ? nt - 8 : nt - 12)); }

__global__ void __cluster_dims__(2, 1, 1) __launch_bounds__(384, 1)
fused_kernel(const __grid_constant__ Params prm) {
    extern __shared__ __align__(1024) uint8_t smem_raw[];
    const uint32_t base = smem_u32(smem_raw) & ~1023u;
    const uint32_t bars = base + BAR_OFF;
    auto full1 = [&](int s) { return bars + s * 8; };
    auto empty1 = [&](int s) { return bars + 32 + s * 8; };
    auto full2 = [&](int s) { return bars + 64 + s * 8; };
    auto empty2 = [&](int s) { return bars + 128 + s * 8; };
    const uint32_t sig_bar = bars + 192, dep_bar = bars + 256, cs_bar = bars + 304, fold_bar = bars + 320, x_bar = bars + 336;
    const uint32_t colsum = bars + 512, stats = bars + 1536;
    auto stage2 = [&](int q) { return base + q * G2_STAGE_BYTES; };
    const uint32_t aux = base + AUX_OFF;

    const int warp = __shfl_sync(0xffffffffu, threadIdx.x >> 5, 0);
    const int lane = threadIdx.x & 31;
    const int rank = blockIdx.x & 1;
    const int mblk = ((blockIdx.x >> 1) & 7) * 2 + rank;
    const int nslot = blockIdx.x >> 4;

    if (blockIdx.x >= NGEMM) {
        if (threadIdx.x == 0) { TRACE_GT(0); TRACE(1); }
        attention(&prm.qk, (base + 2 * ATT_SLOT - 1) & ~(2u * ATT_SLOT - 1), prm.zero, blockIdx.x - NGEMM, warp, lane);
    } else if (warp >= 8) {
        unsigned* const flags = g_flags + mblk * 32;
        const CUtensorMap* const w0 = nslot < 4 ? &prm.wqkv : (rank ? &prm.wu : &prm.wg);
        const int w0_col = nslot < 4 ? 32 + nslot * 4 + rank * 2 : nslot * 2 - 8;
        if (elect_one()) {
            if (warp == 8) {
                TRACE_GT(0); TRACE(1);
                prefetch_map(&prm.x); prefetch_map(w0);
                for (int s = 0; s < G1_STAGES; s++) { mbar_init(full1(s), 1); mbar_init(empty1(s), 4); }
            } else if (warp == 9) {
                for (int s = 0; s < G2_STAGES; s++) { mbar_init(full2(s), 1); mbar_init(empty2(s), 4); }
            } else if (warp == 10) {
                for (int s = 0; s < 7; s++) mbar_init(sig_bar + s * 8, 8);
                mbar_init(fold_bar, 2); mbar_init(fold_bar + 8, 1); mbar_init(x_bar, 1);
            } else {
                for (int s = 0; s < 8; s++) mbar_init(dep_bar + s * 8, 1);
            }
            asm volatile("fence.mbarrier_init.release.cluster;" ::: "memory");
        }
        __syncwarp();
        asm volatile("barrier.cluster.arrive.relaxed.aligned;" ::: "memory");
        if (warp == 8 && lane == 0) {
            mbar_expect_tx(full1(0), G1_STAGE_BYTES);
            tma_2d(base, &prm.x, full1(0), 0, mblk * 128, policy(P_X));
            prefetch_3d(w0, 0, w0_col, policy(P_W1));
            TRACE(15);
        }
        asm volatile("setmaxnreg.dec.sync.aligned.u32 %0;" :: "n"(AUX_REGS));
        asm volatile("barrier.cluster.wait.acquire.aligned;" ::: "memory");

        if (warp == 8) {
            if (lane == 0) {
                TRACE(2);
                auto load_b1 = [&](int s, int nt, int k) {
                    const uint32_t dst = base + s * G1_STAGE_BYTES + A_BYTES + rank * 16384;
                    if (tile_is_qkv(nt)) tma_3d_mc(dst, &prm.wqkv, full1(s), k * 64, tile_index(nt) * 4 + rank * 2, policy(P_W1));
                    else tma_3d_mc(dst, rank ? &prm.wu : &prm.wg, full1(s), k * 64, tile_index(nt) * 2, policy(P_W1));
                };
                load_b1(0, nslot, 0);
                uint32_t ph = 1;
                for (int it = 1; it < G1_TILES * G1_KSTEPS; it++) {
                    const int s = it & 3, k = it & 15;
                    if (it == G1_STAGES) {
                        if (PF_X) asm volatile("cp.async.bulk.prefetch.L2.global.L2::cache_hint [%0], 32768, %1;"
                                     :: "l"(prm.px + (size_t)(mblk * 128 + nslot * 16) * DM), "l"(policy(P_X)) : "memory");
                        if (mblk / 2 + 4 < PF_W) prefetch_3d(w0, (mblk / 2 + 4) * 64, w0_col, policy(P_W1));
                        prefetch_map(&prm.xn); prefetch_map(&prm.wqkv); prefetch_map(&prm.wu); prefetch_map(&prm.wg);
                        prefetch_map(&prm.a2); prefetch_map(&prm.wo); prefetch_map(&prm.wd); prefetch_map(&prm.out);
                    }
                    if (it == G1_KSTEPS) { TRACE(14); mbar_wait(dep_bar, 0); TRACE(3); }
                    mbar_wait(empty1(s), ph);
                    mbar_expect_tx(full1(s), G1_STAGE_BYTES);
                    tma_2d(base + s * G1_STAGE_BYTES, it < G1_KSTEPS ? &prm.x : &prm.xn, full1(s), k * 64, mblk * 128,
                           policy(it < G1_KSTEPS ? P_X : (P_XN4 && it >= (G1_TILES - 1) * G1_KSTEPS)));
                    load_b1(s, (it >> 4) * 8 + nslot, k);
                    if (s == 3) ph ^= 1;
                }
                mbar_expect_tx(x_bar, 32768);
                tma_2d(aux, &prm.x, x_bar, nslot * 128, mblk * 128, policy(P_X));
                tma_2d(aux + 16384, &prm.x, x_bar, nslot * 128 + 64, mblk * 128, policy(P_X));
                TRACE(4);
                mbar_wait(dep_bar + 8, 0);
                TRACE(5);
                int q = 0; uint32_t ph2 = 1;
                for (int u = 0; u < G2_KSTEPS; u++) {
                    if (u == G2_LATE || u == G2_DSTEPS || u == G2_LAST) {
                        TRACE(u == G2_LATE ? 6 : (u == G2_DSTEPS ? 32 : 40));
                        mbar_wait(dep_bar + (u == G2_LATE ? 16 : (u == G2_DSTEPS ? 24 : 32)), 0);
                        TRACE(u == G2_LATE ? 7 : (u == G2_DSTEPS ? 33 : 41));
                    }
                    if (u < G2_STAGES) {
                        if (u == 0) mbar_wait(empty1(0), ph);
                        if (u == 1) mbar_wait(empty1(1), ph);
                        if (u == 3) mbar_wait(empty1(2), ph);
                        if (u == 4) mbar_wait(empty1(3), ph);
                    } else {
                        mbar_wait(empty2(q), ph2);
                    }
                    const uint32_t sa = stage2(q);
                    const bool down = u < G2_DSTEPS;
                    const int k = down ? u : (u - G2_DSTEPS) % 4 * 4 + (u - G2_DSTEPS) / 4;
                    mbar_expect_tx(full2(q), G2_STAGE_BYTES);
                    tma_3d(sa, &prm.a2, full2(q), (down ? DM : 0) + k * 64, 0, mblk * 64, policy(P_A2));
                    tma_5d_mc(sa + A_BYTES + rank * 8192, down ? &prm.wd : &prm.wo, full2(q), nslot * 128 + rank * 64, k * 2, policy(P_W2));
                    if (++q == G2_STAGES) { q = 0; ph2 ^= 1; }
                }
                TRACE(8);
            }
        } else if (warp == 9) {
            if (lane == 0) {
                const unsigned epoch = __ldcg(g_epoch + blockIdx.x * 16 + 2) + 1;
                mbar_wait(sig_bar, 0);
                TRACE(11);
                flag_add(flags + F_LN * 512);
                TRACE(42);
                flag_wait(flags + F_LN * 512, epoch * CNT_LN);
                fence_proxy_async();
                mbar_arrive(dep_bar);
                mbar_expect_tx(fold_bar + 8, 1024);
                bulk_load(stats, g_stats + mblk * 128, 1024, fold_bar + 8);
                g_epoch[blockIdx.x * 16 + 2] = epoch;
                for (int p = nslot < 4 ? 2 : 1; p < 7; p++) {
                    mbar_wait(sig_bar + p * 8, 0);
                    if (p == 2) TRACE(37);
                    flag_add(p == 2 || p == 3 ? g_flags + F_QKV * 512 + (p * 4 - 8 + (nslot & 3)) * 32
                                              : flags + (p < 6 ? F_EARLY : F_LATE) * 512);
                    if (p == 2) TRACE(43);
                }
            }
        } else {
            const int w = warp - 10;
            const unsigned epoch = __ldcg(g_epoch + blockIdx.x * 16 + w) + 1;
            unsigned* const cs_flag = g_flags + F_CS * 512 + (nslot * 2 + w) * 32;
            mbar_wait(CS_AT, 0);
            if (elect_one()) {
                mbar_expect_tx(cs_bar + w * 8, 16384);
                tma_3d(aux + w * 16384, nslot < 4 ? &prm.wqkv : (w ? &prm.wu : &prm.wg), cs_bar + w * 8, 0, mblk * 64,
                       nslot < 4 ? 32 + nslot * 4 + w * 2 : nslot * 2 - 8, policy(P_W1));
            }
            float cs[8];
#pragma unroll
            for (int d = 0; d < 8; d++) cs[d] = 0.f;
            mbar_wait(cs_bar + w * 8, 0);
            const uint32_t wa = aux + w * 16384 + (lane & 8) * 1024 + (lane >> 4) * 128 + (((lane & 7) ^ (lane >> 4)) << 4);
#pragma unroll 1
            for (int i = 0; i < 8; i++) {
#pragma unroll
                for (int j = 0; j < 4; j++) {
                    float f[8];
                    unpack8(lds128((wa ^ (j * 32)) + i * 1024 + j * 256), f);
#pragma unroll
                    for (int d = 0; d < 8; d++) cs[d] += f[d];
                }
            }
#pragma unroll
            for (int d = 0; d < 8; d++) cs[d] += __shfl_xor_sync(0xffffffffu, cs[d], 16);
            *reinterpret_cast<float4*>(g_colsum + (nslot * 2 + w) * 2048 + mblk * 128 + (lane & 15) * 8 + (lane >> 4) * 4) =
                lane < 16 ? make_float4(cs[0], cs[1], cs[2], cs[3]) : make_float4(cs[4], cs[5], cs[6], cs[7]);
            __syncwarp();
            if (lane == 0) {
                if (w == 0) TRACE(34);
                flag_add(cs_flag);
                flag_wait(cs_flag, epoch * CNT_CS);
                fence_proxy_async();
                mbar_expect_tx(cs_bar + w * 8, 8192);
                bulk_load(aux + w * 16384, g_colsum + (nslot * 2 + w) * 2048, 8192, cs_bar + w * 8);
            }
            mbar_wait(cs_bar + w * 8, 1);
            float4 c = make_float4(0.f, 0.f, 0.f, 0.f);
#pragma unroll 8
            for (int m = 0; m < 16; m++) {
                const uint4 a = lds128(aux + w * 16384 + m * 512 + lane * 16);
                c.x += __uint_as_float(a.x); c.y += __uint_as_float(a.y); c.z += __uint_as_float(a.z); c.w += __uint_as_float(a.w);
            }
            const uint32_t ca = colsum + (w * 8 + (lane >> 2)) * 64 + (lane & 1) * 32 + (lane & 2) * 4;
            sts64f(ca, c.x, c.y);
            sts64f(ca + 16, c.z, c.w);
            __syncwarp();
            if (lane == 0) {
                mbar_arrive(fold_bar);
                g_epoch[blockIdx.x * 16 + w] = epoch;
                if (w == 0) {
                    TRACE(35);
                    flag_wait(flags + F_EARLY * 512, epoch * CNT_EARLY);
                    fence_proxy_async(); mbar_arrive(dep_bar + 8);
                    flag_wait(flags + F_LATE * 512, epoch * CNT_LATE);
                    fence_proxy_async(); mbar_arrive(dep_bar + 16);
                    flag_wait(g_flags + F_O * 512, epoch * CNT_O);
                    fence_proxy_async(); mbar_arrive(dep_bar + 24);
                    flag_wait(g_flags + F_O * 512 + 32, epoch * CNT_O);
                    fence_proxy_async(); mbar_arrive(dep_bar + 32);
                }
            }
        }
    } else {
        asm volatile("barrier.cluster.arrive.relaxed.aligned;" ::: "memory");
        asm volatile("setmaxnreg.inc.sync.aligned.u32 %0;" :: "n"(CONSUMER_REGS));
        const int wg = __shfl_sync(0xffffffffu, threadIdx.x >> 7, 0);
        const int cw = threadIdx.x >> 5;
        const int tid = threadIdx.x & 127;
        float acc[128];
        uint32_t pk[64];
#pragma unroll
        for (int i = 0; i < 64; i++) asm volatile("mov.b32 %0, 0;" : "=r"(pk[i]));
#pragma unroll
        for (int i = 0; i < 128; i++) asm volatile("mov.b32 %0, 0;" : "=f"(acc[i]));
        asm volatile("barrier.cluster.wait.acquire.aligned;" ::: "memory");

        const int orow = ((lane >> 2) & 1) * (SEQ / 2) + mblk * 64 + cw * 8 + (lane >> 3);
        __nv_bfloat16* optr = nullptr;
        auto release = [&](uint32_t bar) { if (tid < 2) mbar_arrive_cluster(bar, tid); };
        auto chunk_geglu = [&](int j) {
            const int c = j >> 1, h = j & 1;
            uint4 v;
            v.x = geglu2(pk[8 * c + h], pk[32 + 8 * c + h]);
            v.y = geglu2(pk[8 * c + 2 + h], pk[32 + 8 * c + 2 + h]);
            v.z = geglu2(pk[8 * c + 4 + h], pk[32 + 8 * c + 4 + h]);
            v.w = geglu2(pk[8 * c + 6 + h], pk[32 + 8 * c + 6 + h]);
            *reinterpret_cast<uint4*>(optr + h * 4 * K2 + c * 32) = v;
        };
        auto chunk_qkv = [&](int c) {
            *reinterpret_cast<uint4*>(optr + c * 32) = make_uint4(pk[8 * c], pk[8 * c + 2], pk[8 * c + 4], pk[8 * c + 6]);
            *reinterpret_cast<uint4*>(optr + 4 * NQKV + c * 32) = make_uint4(pk[8 * c + 1], pk[8 * c + 3], pk[8 * c + 5], pk[8 * c + 7]);
        };
        auto signal_stores = [&](int p) { __syncwarp(); if (lane == 0) mbar_arrive(sig_bar + p * 8); };

        auto chunk_ln = [&](int k) {
            const int row = mblk * 128 + nslot * 16 + cw * 2;
            float* const mo = reinterpret_cast<float*>(pk + 32);
            if (k == 0) {
                const uint4* xp = reinterpret_cast<const uint4*>(prm.px + (size_t)row * DM) + lane;
#pragma unroll
                for (int i = 0; i < 8; i++) {
                    const uint4 v = ldg_stream(xp + i * 32, policy(P_X));
                    pk[4 * i] = v.x; pk[4 * i + 1] = v.y; pk[4 * i + 2] = v.z; pk[4 * i + 3] = v.w;
                }
            } else if (k >= LN_STEP && k < LN_STEP + 3) {
                if (k == LN_STEP) {
                    mo[0] = bf_lo(uniform(pk[0])); mo[1] = bf_lo(uniform(pk[16]));
                    mo[2] = mo[3] = mo[4] = mo[5] = 0.f;
                }
#pragma unroll
                for (int i = (k - LN_STEP) * 11; i < (k - LN_STEP) * 11 + 11 && i < 32; i++) {
                    const int r = i & 1;
                    const uint32_t w = pk[r * 16 + i / 2];
                    const float lo = bf_lo(w) - mo[r], hi = bf_hi(w) - mo[r];
                    mo[2 + r] += lo + hi;
                    mo[4 + r] = fmaf(hi, hi, fmaf(lo, lo, mo[4 + r]));
                }
            } else if (k == LN_STEP + 3) {
                const bool second = lane & 16;
                float m1 = (second ? mo[3] : mo[2]) + __shfl_xor_sync(0xffffffffu, second ? mo[2] : mo[3], 16);
                float m2 = (second ? mo[5] : mo[4]) + __shfl_xor_sync(0xffffffffu, second ? mo[4] : mo[5], 16);
#pragma unroll
                for (int o = 8; o > 0; o >>= 1) {
                    m1 += __shfl_xor_sync(0xffffffffu, m1, o);
                    m2 += __shfl_xor_sync(0xffffffffu, m2, o);
                }
                m1 *= 1.f / DM;
                const float var = fmaxf(fmaf(-m1, m1, m2 * (1.f / DM)), 0.f);
                const float mean = round_bf16((second ? mo[1] : mo[0]) + m1);
                const float inv = 1.f / round_bf16(sqrtf(round_bf16(round_bf16(var) + 1e-5f)));
                if ((lane & 15) == 0) g_stats[row + second] = make_float2(-mean, inv);
                const uint32_t split = pack_bf16(inv - round_bf16(inv), inv);
#pragma unroll
                for (int r = 0; r < 2; r++) {
                    const uint32_t f = __shfl_sync(0xffffffffu, split, r * 16);
                    pk[32 + 3 * r] = __byte_perm(__shfl_sync(0xffffffffu, __float_as_uint(mean), r * 16), 0, 0x3232);
                    pk[33 + 3 * r] = __byte_perm(f, 0, 0x3232);
                    pk[34 + 3 * r] = __byte_perm(f, 0, 0x1010);
                }
            } else if (k >= LN_STEP + 4 && k < LN_STEP + 7) {
#pragma unroll
                for (int i = (k - LN_STEP - 4) * 3; i < (k - LN_STEP - 3) * 3 && i < 8; i++) {
                    const uint32_t* n = pk + 32 + i / 4 * 3;
                    uint32_t o[4];
#pragma unroll
                    for (int j = 0; j < 4; j++) o[j] = mul2_bf16x2(sub_bf16x2(pk[i * 4 + j], n[0]), n[1], n[2]);
                    *reinterpret_cast<uint4*>(g_xn + (size_t)row * DM + i * 256 + lane * 8) = make_uint4(o[0], o[1], o[2], o[3]);
                }
                if (k == LN_STEP + 6) signal_stores(0);
            } else if (k == FOLD_STEP) {
                mbar_wait(fold_bar, 0);
#pragma unroll
                for (int j = 0; j < 16; j++) {
                    const uint4 c = lds128(colsum + j * 64 + (lane & 3) * 16);
                    pk[4 * j] = c.x; pk[4 * j + 1] = c.y; pk[4 * j + 2] = c.z; pk[4 * j + 3] = c.w;
                }
            }
        };

        bool gated = false;
#pragma unroll 1
        for (int t = 0; t < G1_TILES; t++) {
#pragma unroll
            for (int k = 0; k < G1_KSTEPS; k++) {
                const int s = k & 3;
                mbar_wait(full1(s), (k >> 2) & 1);
                if (t == 0 && k == 0 && threadIdx.x == 0) TRACE(12);
                if (TRACE_T >= 0 && t == TRACE_T && threadIdx.x == 0) TRACE(44 + k);
                if (wg == 1 && k == G1_KSTEPS - G1_SKEW) asm volatile("bar.sync 1, 256;" ::: "memory");
                const uint64_t da = desc_a(base + s * G1_STAGE_BYTES + wg * 8192);
                const uint64_t db = desc_b(base + s * G1_STAGE_BYTES + A_BYTES);
                wg_fence();
#pragma unroll
                for (int kk = 0; kk < 4; kk++) wgmma_n256(acc, da + kk * 2, db + kk * 128, (k | kk) != 0);
                wg_commit();
                if (wg == 0 && k == G1_KSTEPS - 1) asm volatile("bar.arrive 1, 256;" ::: "memory");
                if (ORD1) { wg_wait<1>(); if (k > 0) release(empty1((k - 1) & 3)); }
                if (t == 0) chunk_ln(k);
                if (k >= 1 && k <= 8 && gated) {
                    chunk_geglu(k - 1);
                    if (k == 8) signal_stores(t == 1 ? 1 : t + 1);
                }
                if (t != 0 && !gated) {
                    if (k == 0) { chunk_qkv(0); chunk_qkv(1); }
                    if (k >= 6 && k <= 11) chunk_qkv(k - 4);
                    if ((k == 0 || k == 11) && t == 2) signal_stores(k ? 3 : 2);
                }
                if (!ORD1) { wg_wait<1>(); if (k > 0) release(empty1((k - 1) & 3)); }
            }
            wg_wait<0>();
            fence_regs(acc);
            release(empty1(3));
            if (t == 0) {
                mbar_wait(fold_bar + 8, 0);
                const uint32_t sp = stats + (cw * 16 + (lane >> 2)) * 8;
                const float2 sa = lds64f(sp), sb = lds64f(sp + 64);
#pragma unroll
                for (int j = 0; j < 16; j++) {
                    const float c0 = __uint_as_float(pk[4 * j]), c1 = __uint_as_float(pk[4 * j + 1]);
                    const float c2 = __uint_as_float(pk[4 * j + 2]), c3 = __uint_as_float(pk[4 * j + 3]);
                    const float* a = acc + 8 * j;
                    pk[4 * j] = pack_bf16(fmaf(sa.x, c0, a[0]) * sa.y, fmaf(sa.x, c1, a[1]) * sa.y);
                    pk[4 * j + 1] = pack_bf16(fmaf(sb.x, c0, a[2]) * sb.y, fmaf(sb.x, c1, a[3]) * sb.y);
                    pk[4 * j + 2] = pack_bf16(fmaf(sa.x, c2, a[4]) * sa.y, fmaf(sa.x, c3, a[5]) * sa.y);
                    pk[4 * j + 3] = pack_bf16(fmaf(sb.x, c2, a[6]) * sb.y, fmaf(sb.x, c3, a[7]) * sb.y);
                }
            } else {
#pragma unroll
                for (int i = 0; i < 64; i++) pk[i] = pack_bf16(acc[2 * i], acc[2 * i + 1]);
            }
            const int nt = t * 8 + nslot;
            gated = !tile_is_qkv(nt);
            optr = !gated ? g_qkv + (size_t)orow * NQKV + tile_index(nt) * 256 + (lane & 3) * 8
                                : g_a2 + (size_t)orow * K2 + DM + tile_index(nt) * 128 + (lane & 3) * 8;
            if (tid == 0) TRACE(16 + wg * 8 + t);
        }

        float accd[64], accs[64];
#pragma unroll
        for (int i = 0; i < 64; i++) accd[i] = 0.f;
#pragma unroll
        for (int u = 0; u < 9; u++) {
            const int q = u % G2_STAGES;
            mbar_wait(full2(q), (u / G2_STAGES) & 1);
            const uint64_t da = desc_a(stage2(q) + wg * 8192), db = desc_b(stage2(q) + A_BYTES);
            wg_fence();
#pragma unroll
            for (int kk = 0; kk < 4; kk++) wgmma_n128(accd, da + kk * 2, db + kk * 128, (u | kk) != 0);
            wg_commit();
            if (ORD2) { wg_wait<1>(); if (u > 0) release(empty2((u - 1) % G2_STAGES)); }
            if (u >= 1) { chunk_geglu(u - 1); if (u == 8) signal_stores(6); }
            if (!ORD2) { wg_wait<1>(); if (u > 0) release(empty2((u - 1) % G2_STAGES)); }
        }
        {
            int q = 9 % G2_STAGES, qp = 8 % G2_STAGES; uint32_t ph = (9 / G2_STAGES) & 1;
#pragma unroll 1
            for (int u = 9; u < G2_DSTEPS; u++) {
                mbar_wait(full2(q), ph);
                const uint64_t da = desc_a(stage2(q) + wg * 8192), db = desc_b(stage2(q) + A_BYTES);
                wg_fence();
#pragma unroll
                for (int kk = 0; kk < 4; kk++) wgmma_n128(accd, da + kk * 2, db + kk * 128, 1);
                wg_commit();
                wg_wait<1>();
                release(empty2(qp));
                qp = q;
                if (++q == G2_STAGES) { q = 0; ph ^= 1; }
            }
        }
        if (tid == 0) TRACE(16 + wg * 8 + 5);
#pragma unroll
        for (int i = 0; i < 64; i++) accs[i] = 0.f;
        uint32_t gk[32], xr[32];
        const uint32_t xs = aux + cw * 2048;
        const uint32_t xrow = xs + ((lane & 7) + ((lane >> 3) & 1) * 8) * 128;
        auto xaddr = [&](int j) { return xrow + (j >> 2) * 16384 + (((((j & 3) * 2) + (lane >> 4)) ^ (lane & 7)) << 4); };
#pragma unroll
        for (int u = G2_DSTEPS; u < G2_KSTEPS; u++) {
            const int q = u % G2_STAGES, v = u - G2_DSTEPS;
            mbar_wait(full2(q), (u / G2_STAGES) & 1);
            if (G2_SKEW > 0 && wg == 1 && u == G2_KSTEPS - G2_SKEW) asm volatile("bar.sync 1, 256;" ::: "memory");
            const uint64_t da = desc_a(stage2(q) + wg * 8192), db = desc_b(stage2(q) + A_BYTES);
            wg_fence();
#pragma unroll
            for (int kk = 0; kk < 4; kk++) wgmma_n128(accs, da + kk * 2, db + kk * 128, (v | kk) != 0);
            wg_commit();
            if (G2_SKEW > 0 && wg == 0 && u == G2_KSTEPS - 1) asm volatile("bar.arrive 1, 256;" ::: "memory");
            if (v >= 1 && v <= 8) {
#pragma unroll
                for (int i = 4 * (v - 1); i < 4 * v; i++) {
                    const uint32_t d2 = pack_bf16(accd[2 * i], accd[2 * i + 1]);
                    gk[i] = pack_bf16(silu(bf_lo(d2)), silu(bf_hi(d2)));
                }
            }
            if (v == 9) mbar_wait(x_bar, 0);
            if (v >= 9 && v <= 12) {
#pragma unroll
                for (int j = 2 * (v - 9); j < 2 * (v - 8); j++)
                    asm volatile("ldmatrix.sync.aligned.m8n8.x4.shared.b16 {%0,%1,%2,%3}, [%4];"
                                 : "=r"(xr[4 * j]), "=r"(xr[4 * j + 1]), "=r"(xr[4 * j + 2]), "=r"(xr[4 * j + 3])
                                 : "r"(xaddr(j)) : "memory");
            }
            wg_wait<1>();
            if (v == 0) fence_regs(accd);
            if (u - 1 + G2_STAGES < G2_KSTEPS) release(empty2((u - 1) % G2_STAGES));
        }
        wg_wait<0>();
        fence_regs(accs);
        if (tid == 0) TRACE(16 + wg * 8 + 6);
#pragma unroll
        for (int j = 0; j < 8; j++) {
            uint32_t r[4];
#pragma unroll
            for (int i = 0; i < 4; i++) {
                const int e = j * 4 + i;
                r[i] = add_bf16x2(xr[e], mul_bf16x2(pack_bf16(accs[2 * e], accs[2 * e + 1]), gk[e]));
            }
            asm volatile("stmatrix.sync.aligned.m8n8.x4.shared.b16 [%0], {%1,%2,%3,%4};"
                         :: "r"(xaddr(j)), "r"(r[0]), "r"(r[1]), "r"(r[2]), "r"(r[3]) : "memory");
            if (j == 3 || j == 7) {
                asm volatile("fence.proxy.async.shared::cta;" ::: "memory");
                __syncwarp();
                if (lane == 0) {
                    tma_store_2d(&prm.out, xs + (j >> 2) * 16384, nslot * 128 + (j >> 2) * 64, mblk * 128 + cw * 16);
                    asm volatile("cp.async.bulk.commit_group;" ::: "memory");
                }
            }
        }
        if (lane == 0) asm volatile("cp.async.bulk.wait_group.read 0;" ::: "memory");
        if (tid == 0) { TRACE(16 + wg * 8 + 7); if (wg == 1) TRACE_GT(13); }
    }
}

typedef CUresult (*EncodeFn)(CUtensorMap*, CUtensorMapDataType, cuuint32_t, void*, const cuuint64_t*, const cuuint64_t*,
                             const cuuint32_t*, const cuuint32_t*, CUtensorMapInterleave, CUtensorMapSwizzle,
                             CUtensorMapL2promotion, CUtensorMapFloatOOBfill);

void encode(EncodeFn fn, CUtensorMap* m, const void* ptr, int rank, const cuuint64_t* dims, const cuuint64_t* strides,
            const cuuint32_t* box) {
    const cuuint32_t es[5] = {1, 1, 1, 1, 1};
    fn(m, CU_TENSOR_MAP_DATA_TYPE_BFLOAT16, rank, const_cast<void*>(ptr), dims, strides, box, es,
       CU_TENSOR_MAP_INTERLEAVE_NONE, CU_TENSOR_MAP_SWIZZLE_128B, CU_TENSOR_MAP_L2_PROMOTION_L2_128B,
       CU_TENSOR_MAP_FLOAT_OOB_FILL_NONE);
}
void encode_2d(EncodeFn fn, CUtensorMap* m, const void* ptr, int cols, int box_rows) {
    const cuuint64_t dims[2] = {(cuuint64_t)cols, SEQ}, strides[1] = {(cuuint64_t)cols * 2};
    const cuuint32_t box[2] = {64, (cuuint32_t)box_rows};
    encode(fn, m, ptr, 2, dims, strides, box);
}
void encode_w1(EncodeFn fn, CUtensorMap* m, const void* ptr, int cols) {
    const cuuint64_t dims[3] = {64, DM, (cuuint64_t)cols / 64}, strides[2] = {(cuuint64_t)cols * 2, 128};
    const cuuint32_t box[3] = {64, 64, 2};
    encode(fn, m, ptr, 3, dims, strides, box);
}
void encode_qk(EncodeFn fn, CUtensorMap* m, const void* ptr) {
    const cuuint64_t dims[3] = {DM, SEQ, 3}, strides[2] = {NQKV * 2, DM * 2};
    const cuuint32_t box[3] = {64, 16, 2};
    encode(fn, m, ptr, 3, dims, strides, box);
}
void encode_a2(EncodeFn fn, CUtensorMap* m, const void* ptr) {
    const cuuint64_t dims[3] = {K2, 2, SEQ / 2}, strides[2] = {(cuuint64_t)SEQ * K2, K2 * 2};
    const cuuint32_t box[3] = {64, 2, 64};
    encode(fn, m, ptr, 3, dims, strides, box);
}
void encode_w2(EncodeFn fn, CUtensorMap* m, const void* ptr, int rows) {
    const cuuint64_t rb = DM * 2;
    const cuuint64_t dims[5] = {DM, 2, 4, 4, (cuuint64_t)rows / 32}, strides[4] = {rb, 8 * rb, 2 * rb, 32 * rb};
    const cuuint32_t box[5] = {64, 2, 4, 4, 2};
    encode(fn, m, ptr, 5, dims, strides, box);
}

}

extern "C" void kernel_launch(void* const* d_in, const int* in_sizes, int n_in, void* d_out, int out_size) {
    (void)in_sizes; (void)n_in; (void)out_size;
    static EncodeFn fn = nullptr;
    static void *p_xn = nullptr, *p_qkv = nullptr, *p_a2 = nullptr;
    if (!fn) {
        cudaDriverEntryPointQueryResult st;
        cudaGetDriverEntryPoint("cuTensorMapEncodeTiled", (void**)&fn, cudaEnableDefault, &st);
        cudaGetSymbolAddress(&p_xn, g_xn);
        cudaGetSymbolAddress(&p_qkv, g_qkv);
        cudaGetSymbolAddress(&p_a2, g_a2);
        cudaFuncSetAttribute(fused_kernel, cudaFuncAttributeMaxDynamicSharedMemorySize, SMEM_BYTES);
    }
    Params prm;
    encode_2d(fn, &prm.x, d_in[0], DM, 128);
    encode_2d(fn, &prm.xn, p_xn, DM, 128);
    encode_w1(fn, &prm.wqkv, d_in[1], NQKV);
    encode_w1(fn, &prm.wg, d_in[4], DF);
    encode_w1(fn, &prm.wu, d_in[5], DF);
    encode_qk(fn, &prm.qk, p_qkv);
    encode_2d(fn, &prm.v, p_qkv, NQKV, 16);
    encode_2d(fn, &prm.o, p_a2, K2, 16);
    encode_a2(fn, &prm.a2, p_a2);
    encode_w2(fn, &prm.wo, d_in[2], DM);
    encode_w2(fn, &prm.wd, d_in[6], DF);
    encode_2d(fn, &prm.out, d_out, DM, 16);
    prm.px = (const __nv_bfloat16*)d_in[0];
    prm.zero = 0;
    fused_kernel<<<NCTA, 384, SMEM_BYTES>>>(prm);
}
```

```cpp
#include <cuda_runtime.h>
#include <cuda_bf16.h>
#include <cuda.h>
#include <stdint.h>
#include <type_traits>

#define XF32 1
#define SEND_AT 2
#define RECV_AT 6
#define X_AT 92

namespace {

constexpr int SEQ = 2048, DM = 1024, DF = 3584, K2 = DM + DF, NQKV = 3 * DM;
constexpr int NGEMM = 128, NCTA = 132;
constexpr int G1_STAGES = 4, G1_STAGE_BYTES = 49152, G1_KSTEPS = 16, G1_TILES = 5;
constexpr int D_KSTEPS = 28, D_LATE = 20, D_FIRST = G1_TILES * G1_KSTEPS;
constexpr int G2_STAGES = XF32 ? 4 : 5, G2_STAGE_BYTES = 32768, G2_KSTEPS = 16, G2_LAST = 12;
constexpr int LN_STEP = 3, FOLD_STEP = 14;
constexpr int A_BYTES = 16384;
constexpr int AUX_OFF = G1_STAGES * G1_STAGE_BYTES;
constexpr int BAR_OFF = AUX_OFF + 32768;
constexpr int SMEM_BYTES = BAR_OFF + 2560;
constexpr int G1_SKEW = 2, G2_SKEW = 2;
constexpr int CONSUMER_REGS = 224, AUX_REGS = 56;
constexpr int ATT_SLOT = 8192;

enum { F_LN = 0, F_QKV = 1, F_EARLY = 2, F_LATE = 3, F_O = 4, F_CS = 5 };
constexpr unsigned CNT_LN = 8, CNT_QKV = 32, CNT_EARLY = 20, CNT_LATE = 8, CNT_O = 4, CNT_CS = 16;

__device__ __align__(1024) __nv_bfloat16 g_xn[SEQ * DM];
__device__ __align__(1024) __nv_bfloat16 g_qkv[SEQ * NQKV];
__device__ __align__(1024) __nv_bfloat16 g_a2[SEQ * K2];
__device__ __align__(128) float2 g_stats[SEQ];
__device__ __align__(128) float g_colsum[16 * 2048];
__device__ __align__(128) unsigned g_flags[6 * 16 * 32];
__device__ __align__(128) unsigned g_epoch[NCTA * 16];

#define TRACE_T -1
#define TRACE(slot) do {} while (0)
#define TRACE_GT(slot) do {} while (0)

__device__ __forceinline__ uint32_t smem_u32(const void* p) { return (uint32_t)__cvta_generic_to_shared(p); }
__device__ __forceinline__ void mbar_init(uint32_t bar, uint32_t cnt) {
    asm volatile("mbarrier.init.shared::cta.b64 [%0], %1;" :: "r"(bar), "r"(cnt) : "memory");
}
__device__ __forceinline__ void mbar_expect_tx(uint32_t bar, uint32_t bytes) {
    asm volatile("mbarrier.arrive.expect_tx.shared::cta.b64 _, [%0], %1;" :: "r"(bar), "r"(bytes) : "memory");
}
__device__ __forceinline__ void mbar_arrive(uint32_t bar) {
    asm volatile("mbarrier.arrive.shared::cta.b64 _, [%0];" :: "r"(bar) : "memory");
}
__device__ __forceinline__ void mbar_arrive_cluster(uint32_t bar, uint32_t cta) {
    asm volatile("{\n.reg .b32 ra;\nmapa.shared::cluster.u32 ra, %0, %1;\nmbarrier.arrive.shared::cluster.b64 _, [ra];\n}"
                 :: "r"(bar), "r"(cta) : "memory");
}
__device__ __forceinline__ bool mbar_try_wait(uint32_t bar, uint32_t parity) {
    uint32_t ok;
    asm volatile("{\n.reg .pred p;\nmbarrier.try_wait.parity.shared::cta.b64 p, [%1], %2;\nselp.u32 %0, 1, 0, p;\n}"
                 : "=r"(ok) : "r"(bar), "r"(parity) : "memory");
    return ok;
}
__device__ __forceinline__ bool mbar_test(uint32_t bar, uint32_t parity) {
    uint32_t ok;
    asm volatile("{\n.reg .pred p;\nmbarrier.test_wait.parity.shared::cta.b64 p, [%1], %2;\nselp.u32 %0, 1, 0, p;\n}"
                 : "=r"(ok) : "r"(bar), "r"(parity) : "memory");
    return ok;
}
__device__ __forceinline__ void mbar_wait(uint32_t bar, uint32_t parity) {
#pragma unroll 1
    for (int spins = 0; !mbar_try_wait(bar, parity) && spins < (1 << 17); spins++) {}
}
__device__ __forceinline__ void mbar_wait_cluster(uint32_t bar) {
    uint32_t ok = 0;
#pragma unroll 1
    for (int spins = 0; !ok && spins < (1 << 17); spins++)
        asm volatile("{\n.reg .pred p;\nmbarrier.try_wait.parity.acquire.cluster.shared::cta.b64 p, [%1], 0;\nselp.u32 %0, 1, 0, p;\n}"
                     : "=r"(ok) : "r"(bar) : "memory");
}
template <bool WARP = false> __device__ __forceinline__ void flag_wait(const unsigned* p, unsigned target) {
#pragma unroll 1
    for (int spins = 0; spins < (1 << 19); spins++) {
        unsigned v;
        asm volatile("ld.acquire.gpu.global.u32 %0, [%1];" : "=r"(v) : "l"(p) : "memory");
        if (WARP ? __all_sync(0xffffffffu, (int)(v - target) >= 0) : (int)(v - target) >= 0) break;
        __nanosleep(64);
    }
}
__device__ __forceinline__ void flag_add(unsigned* p) {
    asm volatile("red.release.gpu.global.add.u32 [%0], 1;" :: "l"(p) : "memory");
}
__device__ __forceinline__ bool elect_one() {
    uint32_t ok;
    asm volatile("{\n.reg .pred p;\nelect.sync _|p, 0xffffffff;\nselp.u32 %0, 1, 0, p;\n}" : "=r"(ok));
    return ok;
}
__device__ __forceinline__ void fence_proxy_async() { asm volatile("fence.proxy.async.global;" ::: "memory"); }
__device__ __forceinline__ uint4 lds128(uint32_t addr) {
    uint4 v;
    asm volatile("ld.shared.v4.u32 {%0,%1,%2,%3}, [%4];" : "=r"(v.x), "=r"(v.y), "=r"(v.z), "=r"(v.w) : "r"(addr) : "memory");
    return v;
}
__device__ __forceinline__ float2 lds64f(uint32_t addr) {
    float2 v;
    asm volatile("ld.shared.v2.f32 {%0,%1}, [%2];" : "=f"(v.x), "=f"(v.y) : "r"(addr) : "memory");
    return v;
}
__device__ __forceinline__ void sts128(uint32_t addr, uint4 v) {
    asm volatile("st.shared.v4.u32 [%0], {%1,%2,%3,%4};" :: "r"(addr), "r"(v.x), "r"(v.y), "r"(v.z), "r"(v.w) : "memory");
}
__device__ __forceinline__ void sts64f(uint32_t addr, float a, float b) {
    asm volatile("st.shared.v2.f32 [%0], {%1,%2};" :: "r"(addr), "f"(a), "f"(b) : "memory");
}

__device__ __forceinline__ uint64_t policy(bool stream) {
    uint64_t p;
    if (stream) asm("createpolicy.fractional.L2::evict_first.b64 %0, 1.0;" : "=l"(p));
    else asm("createpolicy.fractional.L2::evict_normal.b64 %0, 1.0;" : "=l"(p));
    return p;
}
__device__ __forceinline__ void tma_2d(uint32_t dst, const CUtensorMap* m, uint32_t bar, int c0, int c1, uint64_t pol) {
    asm volatile("cp.async.bulk.tensor.2d.shared::cluster.global.mbarrier::complete_tx::bytes.L2::cache_hint"
                 " [%0], [%1, {%3, %4}], [%2], %5;"
                 :: "r"(dst), "l"(m), "r"(bar), "r"(c0), "r"(c1), "l"(pol) : "memory");
}
__device__ __forceinline__ void tma_3d(uint32_t dst, const CUtensorMap* m, uint32_t bar, int c0, int c1, int c2, uint64_t pol) {
    asm volatile("cp.async.bulk.tensor.3d.shared::cluster.global.mbarrier::complete_tx::bytes.L2::cache_hint"
                 " [%0], [%1, {%3, %4, %5}], [%2], %6;"
                 :: "r"(dst), "l"(m), "r"(bar), "r"(c0), "r"(c1), "r"(c2), "l"(pol) : "memory");
}
__device__ __forceinline__ void tma_3d_mc(uint32_t dst, const CUtensorMap* m, uint32_t bar, int c0, int c1, int c2, uint64_t pol) {
    asm volatile("cp.async.bulk.tensor.3d.shared::cluster.global.mbarrier::complete_tx::bytes.multicast::cluster.L2::cache_hint"
                 " [%0], [%1, {%3, %4, %5}], [%2], %6, %7;"
                 :: "r"(dst), "l"(m), "r"(bar), "r"(c0), "r"(c1), "r"(c2), "h"((uint16_t)3), "l"(pol) : "memory");
}
__device__ __forceinline__ void tma_5d(uint32_t dst, const CUtensorMap* m, uint32_t bar, int c0, int c4, uint64_t pol) {
    asm volatile("cp.async.bulk.tensor.5d.shared::cluster.global.mbarrier::complete_tx::bytes.L2::cache_hint"
                 " [%0], [%1, {%3, %4, %4, %4, %5}], [%2], %6;"
                 :: "r"(dst), "l"(m), "r"(bar), "r"(c0), "r"(0), "r"(c4), "l"(pol) : "memory");
}
__device__ __forceinline__ uint32_t map_cluster(uint32_t addr, uint32_t cta) {
    uint32_t r; asm("mapa.shared::cluster.u32 %0, %1, %2;" : "=r"(r) : "r"(addr), "r"(cta)); return r;
}
__device__ __forceinline__ void st_async(uint32_t dst, uint32_t a, uint32_t b, uint32_t c, uint32_t d, uint32_t bar) {
    asm volatile("st.async.weak.shared::cluster.mbarrier::complete_tx::bytes.v4.b32 [%0], {%1,%2,%3,%4}, [%5];"
                 :: "r"(dst), "r"(a), "r"(b), "r"(c), "r"(d), "r"(bar) : "memory");
}
__device__ __forceinline__ void tma_store_2d(const CUtensorMap* m, uint32_t src, int c0, int c1) {
    asm volatile("cp.async.bulk.tensor.2d.global.shared::cta.bulk_group [%0, {%2, %3}], [%1];"
                 :: "l"(m), "r"(src), "r"(c0), "r"(c1) : "memory");
}
__device__ __forceinline__ uint4 ldg_stream(const void* p, uint64_t pol) {
    uint4 v;
    asm volatile("ld.global.nc.L1::no_allocate.L2::cache_hint.v4.u32 {%0,%1,%2,%3}, [%4], %5;"
                 : "=r"(v.x), "=r"(v.y), "=r"(v.z), "=r"(v.w) : "l"(p), "l"(pol));
    return v;
}
__device__ __forceinline__ void bulk_load(uint32_t dst, const void* src, uint32_t bytes, uint32_t bar) {
    asm volatile("cp.async.bulk.shared::cluster.global.mbarrier::complete_tx::bytes [%0], [%1], %2, [%3];"
                 :: "r"(dst), "l"(src), "r"(bytes), "r"(bar) : "memory");
}
__device__ __forceinline__ void prefetch_3d(const CUtensorMap* m, int c1, int c2, uint64_t pol) {
    asm volatile("cp.async.bulk.prefetch.tensor.3d.L2.global.L2::cache_hint [%0, {%1, %2, %3}], %4;"
                 :: "l"(m), "r"(0), "r"(c1), "r"(c2), "l"(pol) : "memory");
}
__device__ __forceinline__ void prefetch_map(const CUtensorMap* m) {
    asm volatile("prefetch.tensormap [%0];" :: "l"(m) : "memory");
}
__device__ __forceinline__ void wg_fence() { asm volatile("wgmma.fence.sync.aligned;" ::: "memory"); }
__device__ __forceinline__ void wg_commit() { asm volatile("wgmma.commit_group.sync.aligned;" ::: "memory"); }
template <int N> __device__ __forceinline__ void wg_wait() { asm volatile("wgmma.wait_group.sync.aligned %0;" :: "n"(N) : "memory"); }

__device__ __forceinline__ uint64_t desc_a(uint32_t addr) {
    return (uint64_t)((addr & 0x3FFFF) >> 4) | (1ull << 16) | (64ull << 32) | (1ull << 62);
}
__device__ __forceinline__ uint64_t desc_b(uint32_t addr) {
    return (uint64_t)((addr & 0x3FFFF) >> 4) | (512ull << 16) | (64ull << 32) | (1ull << 62);
}

#define R8(d, o) "+f"(d[o]), "+f"(d[o+1]), "+f"(d[o+2]), "+f"(d[o+3]), "+f"(d[o+4]), "+f"(d[o+5]), "+f"(d[o+6]), "+f"(d[o+7])
#define R32(d, o) R8(d, o), R8(d, o+8), R8(d, o+16), R8(d, o+24)
#define R64(d, o) R32(d, o), R32(d, o+32)

__device__ __forceinline__ void wgmma_n256(float (&d)[128], uint64_t da, uint64_t db, int scale_d) {
    asm volatile("{\n.reg .pred p;\nsetp.ne.b32 p, %130, 0;\n"
        "wgmma.mma_async.sync.aligned.m64n256k16.f32.bf16.bf16 "
        "{%0,%1,%2,%3,%4,%5,%6,%7,%8,%9,%10,%11,%12,%13,%14,%15,%16,%17,%18,%19,%20,%21,%22,%23,%24,%25,%26,%27,%28,%29,%30,%31,"
        "%32,%33,%34,%35,%36,%37,%38,%39,%40,%41,%42,%43,%44,%45,%46,%47,%48,%49,%50,%51,%52,%53,%54,%55,%56,%57,%58,%59,%60,%61,%62,%63,"
        "%64,%65,%66,%67,%68,%69,%70,%71,%72,%73,%74,%75,%76,%77,%78,%79,%80,%81,%82,%83,%84,%85,%86,%87,%88,%89,%90,%91,%92,%93,%94,%95,"
        "%96,%97,%98,%99,%100,%101,%102,%103,%104,%105,%106,%107,%108,%109,%110,%111,%112,%113,%114,%115,%116,%117,%118,%119,%120,%121,%122,%123,%124,%125,%126,%127},"
        " %128, %129, p, 1, 1, 0, 1;\n}"
        : R64(d, 0), R64(d, 64) : "l"(da), "l"(db), "r"(scale_d));
}
__device__ __forceinline__ void wgmma_n128(float (&d)[64], uint64_t da, uint64_t db, int scale_d) {
    asm volatile("{\n.reg .pred p;\nsetp.ne.b32 p, %66, 0;\n"
        "wgmma.mma_async.sync.aligned.m64n128k16.f32.bf16.bf16 "
        "{%0,%1,%2,%3,%4,%5,%6,%7,%8,%9,%10,%11,%12,%13,%14,%15,%16,%17,%18,%19,%20,%21,%22,%23,%24,%25,%26,%27,%28,%29,%30,%31,"
        "%32,%33,%34,%35,%36,%37,%38,%39,%40,%41,%42,%43,%44,%45,%46,%47,%48,%49,%50,%51,%52,%53,%54,%55,%56,%57,%58,%59,%60,%61,%62,%63},"
        " %64, %65, p, 1, 1, 0, 1;\n}"
        : R64(d, 0) : "l"(da), "l"(db), "r"(scale_d));
}

__device__ __forceinline__ uint32_t pack_bf16(float lo, float hi) {
    uint32_t r; asm("cvt.rn.bf16x2.f32 %0, %1, %2;" : "=r"(r) : "f"(hi), "f"(lo)); return r;
}
__device__ __forceinline__ float bf_lo(uint32_t v) { return __uint_as_float(v << 16); }
__device__ __forceinline__ float bf_hi(uint32_t v) { return __uint_as_float(v & 0xffff0000u); }
__device__ __forceinline__ float round_bf16(float v) { return bf_lo(pack_bf16(v, 0.f)); }
__device__ __forceinline__ uint32_t mul_bf16x2(uint32_t a, uint32_t b) {
    uint32_t r; asm("mul.rn.bf16x2 %0, %1, %2;" : "=r"(r) : "r"(a), "r"(b)); return r;
}
__device__ __forceinline__ uint32_t add_bf16x2(uint32_t a, uint32_t b) {
    uint32_t r; asm("add.rn.bf16x2 %0, %1, %2;" : "=r"(r) : "r"(a), "r"(b)); return r;
}
__device__ __forceinline__ uint32_t sub_bf16x2(uint32_t a, uint32_t b) {
    uint32_t r; asm("sub.rn.bf16x2 %0, %1, %2;" : "=r"(r) : "r"(a), "r"(b)); return r;
}
__device__ __forceinline__ uint32_t mul2_bf16x2(uint32_t a, uint32_t hi, uint32_t lo) {
    uint32_t r; asm("fma.rn.bf16x2 %0, %1, %2, %3;" : "=r"(r) : "r"(a), "r"(hi), "r"(mul_bf16x2(a, lo))); return r;
}
__device__ __forceinline__ float tanh_fast(float x) { float r; asm("tanh.approx.f32 %0, %1;" : "=f"(r) : "f"(x)); return r; }
__device__ __forceinline__ float gelu_tanh(float g) {
    float t = fmaf(g * g, 0.044715f * 0.7978845608f, 0.7978845608f) * g;
    float hg = 0.5f * g;
    return fmaf(hg, tanh_fast(t), hg);
}
__device__ __forceinline__ uint32_t geglu2(uint32_t g2, uint32_t u2) {
    return mul_bf16x2(pack_bf16(gelu_tanh(bf_lo(g2)), gelu_tanh(bf_hi(g2))), u2);
}
__device__ __forceinline__ float silu(float d) {
    float hd = 0.5f * d;
    return fmaf(hd, tanh_fast(hd), hd);
}
__device__ __forceinline__ float ex2_fast(float x) { float r; asm("ex2.approx.ftz.f32 %0, %1;" : "=f"(r) : "f"(x)); return r; }
__device__ __forceinline__ void unpack8(uint4 v, float (&f)[8]) {
    f[0] = bf_lo(v.x); f[1] = bf_hi(v.x); f[2] = bf_lo(v.y); f[3] = bf_hi(v.y);
    f[4] = bf_lo(v.z); f[5] = bf_hi(v.z); f[6] = bf_lo(v.w); f[7] = bf_hi(v.w);
}
template <int N> __device__ __forceinline__ void fence_regs(float (&d)[N]) {
#pragma unroll
    for (int i = 0; i < N; i++) asm volatile("" : "+f"(d[i]) :: "memory");
}

__device__ __forceinline__ float rcp_fast(float x) { float r; asm("rcp.approx.ftz.f32 %0, %1;" : "=f"(r) : "f"(x)); return r; }
__device__ __forceinline__ uint32_t max_bf16x2(uint32_t a, uint32_t b) {
    uint32_t r; asm("max.bf16x2 %0, %1, %2;" : "=r"(r) : "r"(a), "r"(b)); return r;
}
__device__ __forceinline__ uint4 ldsm4(uint32_t addr) {
    uint4 v;
    asm volatile("ldmatrix.sync.aligned.m8n8.x4.shared.b16 {%0,%1,%2,%3}, [%4];"
                 : "=r"(v.x), "=r"(v.y), "=r"(v.z), "=r"(v.w) : "r"(addr) : "memory");
    return v;
}
__device__ __forceinline__ uint4 ldsm4_t(uint32_t addr) {
    uint4 v;
    asm volatile("ldmatrix.sync.aligned.m8n8.x4.trans.shared.b16 {%0,%1,%2,%3}, [%4];"
                 : "=r"(v.x), "=r"(v.y), "=r"(v.z), "=r"(v.w) : "r"(addr) : "memory");
    return v;
}
__device__ __forceinline__ void mma_16816(float (&c)[4], uint32_t a0, uint32_t a1, uint32_t a2, uint32_t a3, uint32_t b0, uint32_t b1) {
    asm("mma.sync.aligned.m16n8k16.row.col.f32.bf16.bf16.f32 {%0,%1,%2,%3}, {%4,%5,%6,%7}, {%8,%9}, {%0,%1,%2,%3};"
        : "+f"(c[0]), "+f"(c[1]), "+f"(c[2]), "+f"(c[3]) : "r"(a0), "r"(a1), "r"(a2), "r"(a3), "r"(b0), "r"(b1));
}
__device__ __forceinline__ void mma_1688(float (&c)[4], uint32_t a0, uint32_t a1, uint32_t b0) {
    asm("mma.sync.aligned.m16n8k8.row.col.f32.bf16.bf16.f32 {%0,%1,%2,%3}, {%4,%5}, {%6}, {%0,%1,%2,%3};"
        : "+f"(c[0]), "+f"(c[1]), "+f"(c[2]), "+f"(c[3]) : "r"(a0), "r"(a1), "r"(b0));
}
__device__ __forceinline__ void qk_tile(float (&c)[4], const uint4& q0, const uint4& q1, const uint4& k, float init) {
    c[0] = c[1] = c[2] = c[3] = init;
    mma_16816(c, q0.x, q0.y, q0.z, q0.w, k.x, k.y);
    mma_16816(c, q1.x, q1.y, q1.z, q1.w, k.z, k.w);
}
__device__ __forceinline__ uint32_t scaled_logits(bool first, float a0, float a1, float b0, float b1) {
    return mul2_bf16x2(pack_bf16(first ? a0 : b0, first ? a1 : b1), 0x3e353e35u, 0x379e379eu);
}
template <typename T> __device__ __forceinline__ T uniform(T v) { return __shfl_sync(0xffffffffu, v, 0); }

__device__ __forceinline__ void attention(const CUtensorMap* maps, uint32_t base, uint32_t zero, int grp, int warp, int lane) {
    constexpr float LOG2E = 1.4426950408889634f;
    const int g = lane >> 2, t = lane & 3;
    const bool up0 = 2 * t > g, up1 = 2 * t + 1 > g;
    const uint32_t keep = (up0 ? 0x0000ffffu : 0u) | (up1 ? 0xffff0000u : 0u);
    const uint32_t buf = base + warp * 2 * ATT_SLOT, bar = base + AUX_OFF + warp * 16;
    const uint32_t qoff = (lane & 15) * 128 + (((lane >> 4) ^ (lane & 7)) << 4);
    const uint32_t koff = 2048 + (lane & 7) * 128 + (((lane >> 3) ^ (lane & 7)) << 4);
    const uint32_t rest_bar = base + AUX_OFF + 192;
    const int col = uniform(grp * 256), first = uniform((warp / 3 * 32 + warp % 3 * 11) * 16);
    const CUtensorMap* const mqk = reinterpret_cast<const CUtensorMap*>(uniform(reinterpret_cast<uint64_t>(maps)));
    const CUtensorMap *const mv = mqk + 1, *const mo = mqk + 2;
    const uint64_t pol = policy(true);
    uint4 kp[2], vp[2];
    uint32_t l0[2], l1[2], m[2];
    float s[2][3][4];
    auto scores = [&](uint32_t st, int row) {
        const float before = (row & 1023) == 0 ? -5.656854e9f : 0.f;
#pragma unroll
        for (int h = 0; h < 2; h++) {
            const uint4 q0 = ldsm4(st + (qoff ^ (h * 64))), q1 = ldsm4(st + (qoff ^ (h * 64 + 32)));
            const uint4 k0 = ldsm4(st + (koff ^ (h * 64))), k1 = ldsm4(st + 1024 + (koff ^ (h * 64)));
            qk_tile(s[h][0], q0, q1, kp[h], before);
            qk_tile(s[h][1], q0, q1, k0, 0.f);
            qk_tile(s[h][2], q0, q1, k1, 0.f);
            kp[h] = k1;
        }
    };
    auto logits = [&]() {
#pragma unroll
        for (int h = 0; h < 2; h++) {
            l0[h] = scaled_logits(up0, s[h][0][0], s[h][1][2], s[h][1][0], s[h][2][2]);
            l1[h] = scaled_logits(up1, s[h][0][1], s[h][1][3], s[h][1][1], s[h][2][3]);
            m[h] = max_bf16x2(l0[h], l1[h]);
            m[h] = max_bf16x2(m[h], __shfl_xor_sync(0xffffffffu, m[h], 1));
        }
    };
    auto row_max = [&]() {
#pragma unroll
        for (int h = 0; h < 2; h++) m[h] = max_bf16x2(m[h], __shfl_xor_sync(0xffffffffu, m[h], 2));
    };
    auto next = [](uint32_t p) {
        return (0x80200400u >> (p >> 4 & 31) & 1) > (p >> 15 & 1) ? p + (64 << 16) + 0x8000 : (p + 16) & ~0x8800u;
    };
    auto exchange = [&](uint32_t st, uint32_t b, uint32_t po, uint32_t pv, uint32_t pq) {
        asm volatile("{\n.reg .pred e, p, q;\n"
            "fence.proxy.async.shared::cta;\n"
            "bar.warp.sync 0xffffffff;\n"
            "elect.sync _|e, 0xffffffff;\n"
            "setp.eq.and.b32 p, %12, 0, e;\n"
            "setp.lt.and.s32 q, %8, %13, e;\n"
            "@q mbarrier.arrive.expect_tx.shared::cta.b64 _, [%2], 6144;\n"
            "@q cp.async.bulk.tensor.3d.shared::cluster.global.mbarrier::complete_tx::bytes.L2::cache_hint [%0], [%3, {%6, %7, %14}], [%2], %15;\n"
            "@q cp.async.bulk.tensor.2d.shared::cluster.global.mbarrier::complete_tx::bytes.L2::cache_hint [%0 + 4096], [%4, {%8, %9}], [%2], %15;\n"
            "@e cp.async.bulk.wait_group.read 0;\n"
            "@p cp.async.bulk.tensor.2d.global.shared::cta.bulk_group [%5, {%10, %11}], [%1 + 6144];\n"
            "@e cp.async.bulk.commit_group;\n"
            "bar.warp.sync 0xffffffff;\n}"
            :: "r"(st), "r"(st ^ ATT_SLOT), "r"(b), "l"(mqk), "l"(mv), "l"(mo), "r"(pq >> 16), "r"(pq & 2047),
               "r"((pv >> 16) + 2 * DM), "r"(pv & 2047), "r"(po >> 16), "r"(po & 2047), "r"(po & 0x8000),
               "r"(col + 256 + 2 * DM), "r"(0), "l"(pol) : "memory");
    };
    auto publish = [&](auto pending, int part) {
        asm volatile("{\n.reg .pred e;\n.reg .u32 n;\n"
            "elect.sync _|e, 0xffffffff;\n"
            "cp.async.bulk.wait_group %2;\n"
            "@e atom.acq_rel.cta.shared.add.u32 n, [%1], 1;\n"
            "setp.eq.and.u32 e, n, 11, e;\n"
            "@e red.release.gpu.global.add.u32 [%0], 1;\n}"
            :: "l"(g_flags + F_O * 512 + part * 32), "r"(rest_bar + 8 + part * 4), "n"(pending.value) : "memory");
    };
    const unsigned epoch = __ldcg(g_epoch + blockIdx.x * 16) + 1;
    if (elect_one()) {
        mbar_init(bar, 1); mbar_init(bar + 8, 1);
        if (warp == 2) { mbar_init(rest_bar, 32); sts64f(rest_bar + 8, 0.f, 0.f); }
        asm volatile("fence.mbarrier_init.release.cluster;" ::: "memory");
        prefetch_map(mqk); prefetch_map(mv); prefetch_map(mo);
    }
    __syncthreads();
    if (elect_one()) {
        g_epoch[blockIdx.x * 16] = epoch;
        flag_wait(g_flags + F_QKV * 512 + grp * 32, epoch * CNT_QKV);
        fence_proxy_async();
        mbar_expect_tx(bar + 8, 8192);
        tma_3d(buf + ATT_SLOT, mqk, bar + 8, col, first, 0, pol);
        tma_2d(buf + ATT_SLOT + 4096, mv, bar + 8, col + 2 * DM, first - 16, policy(false));
        tma_2d(buf + ATT_SLOT + 6144, mv, bar + 8, col + DM, first - 16, policy(false));
        mbar_expect_tx(bar, 6144);
        tma_3d(buf, mqk, bar, col, first + 16, 0, pol);
        tma_2d(buf + 4096, mv, bar, col + 2 * DM, first, pol);
        if (warp == 0) TRACE(9);
    }
    __syncwarp();
    mbar_wait(bar + 8, 0);
#pragma unroll
    for (int h = 0; h < 2; h++) {
        kp[h] = ldsm4(buf + ATT_SLOT + 5120 + (koff ^ (h * 64)));
        vp[h] = ldsm4_t(buf + ATT_SLOT + 3072 + (koff ^ (h * 64)));
    }
    scores(buf + ATT_SLOT, first);
    uint32_t pm = 0x8000, p0 = col << 16 | first, p1 = p0 + 16, p2 = p0 + 32, p3 = p0 + 48;
    exchange(buf + ATT_SLOT, bar + 8, pm, p1, p2);
    logits();
    row_max();
    uint32_t st = buf, b = bar, cnt = 1;
    const uint32_t relay = warp == 2 ? 7 : 0;
    bool ready = false;
#pragma unroll 1
    while (p0 >> 16 < col + 256) {
        uint32_t pa[2], pb[2];
        if (!ready) mbar_wait(b, (cnt >> 1) & 1);
        uint4 v[2][2];
#pragma unroll
        for (int h = 0; h < 2; h++) {
            const float ma = -LOG2E * bf_lo(m[h]), mb = -LOG2E * bf_hi(m[h]);
            const float a0 = ex2_fast(fmaf(bf_lo(l0[h]), LOG2E, ma)), a1 = ex2_fast(fmaf(bf_lo(l1[h]), LOG2E, ma));
            const float b0 = ex2_fast(fmaf(bf_hi(l0[h]), LOG2E, mb)), b1 = ex2_fast(fmaf(bf_hi(l1[h]), LOG2E, mb));
            float sum[4] = {0.f, 0.f, 0.f, 0.f};
            mma_1688(sum, pack_bf16(a0, a1), pack_bf16(b0, b1), 0x3f803f80u);
            const float ra = rcp_fast(sum[0]), rb = rcp_fast(sum[2]);
            pa[h] = pack_bf16(a0 * ra, a1 * ra);
            pb[h] = pack_bf16(b0 * rb, b1 * rb);
        }
        scores(st, p1);
#pragma unroll
        for (int h = 0; h < 2; h++) {
            v[h][0] = ldsm4_t(st + 4096 + (qoff ^ (h * 64)));
            v[h][1] = ldsm4_t(st + 4096 + (qoff ^ (h * 64 + 32)));
        }
        if (cnt == relay) {
            flag_wait<true>(g_flags + F_QKV * 512 + 128 + grp * 32, epoch * CNT_QKV);
            fence_proxy_async();
            mbar_arrive(rest_bar);
        }
        if (cnt == 8) {
#pragma unroll 1
            for (int spins = 0; !__all_sync(0xffffffffu, mbar_try_wait(rest_bar, 0)) && spins < (1 << 17); spins++) {}
        }
        if (cnt == 37) publish(std::integral_constant<int, 1>(), 0);
        exchange(st, b, pm, p2, p3);
        pm = p0; p0 = p1; p1 = p2; p2 = p3; p3 = next(p3);
        logits();
        float o[2][4][4];
#pragma unroll
        for (int h = 0; h < 2; h++) {
            const uint32_t prev[4] = {vp[h].x, vp[h].y, vp[h].z, vp[h].w};
            const uint32_t own[8] = {v[h][0].x, v[h][0].y, v[h][0].z, v[h][0].w, v[h][1].x, v[h][1].y, v[h][1].z, v[h][1].w};
            const uint32_t a0 = pa[h] & keep, a1 = pa[h] & ~keep, a2 = pb[h] & keep, a3 = pb[h] & ~keep;
            const uint32_t z0 = pa[h] & zero, z1 = pb[h] & zero;
#pragma unroll
            for (int j = 0; j < 4; j++) {
                o[h][j][0] = o[h][j][1] = o[h][j][2] = o[h][j][3] = 0.f;
                mma_1688(o[h][j], a0, z0, prev[j]);
                mma_16816(o[h][j], a1, a2, z1, a3, own[2 * j], own[2 * j + 1]);
            }
            vp[h] = make_uint4(own[1], own[3], own[5], own[7]);
        }
        row_max();
        b ^= 8; cnt++;
        ready = mbar_test(b, (cnt >> 1) & 1);
#pragma unroll
        for (int h = 0; h < 2; h++) {
#pragma unroll
            for (int d = 0; d < 2; d++)
                asm volatile("stmatrix.sync.aligned.m8n8.x4.shared.b16 [%0], {%1,%2,%3,%4};"
                             :: "r"(st + 6144 + (qoff ^ (h * 64 + d * 32))),
                                "r"(pack_bf16(o[h][2 * d][0], o[h][2 * d][1])), "r"(pack_bf16(o[h][2 * d][2], o[h][2 * d][3])),
                                "r"(pack_bf16(o[h][2 * d + 1][0], o[h][2 * d + 1][1])),
                                "r"(pack_bf16(o[h][2 * d + 1][2], o[h][2 * d + 1][3])) : "memory");
        }
        st ^= ATT_SLOT;
    }
    exchange(st, b, pm, p0, p0);
    publish(std::integral_constant<int, 0>(), 1);
    if (threadIdx.x == 0) TRACE(10);
}

struct Params {
    CUtensorMap x, xn, wqkv, wg, wu, qk, v, o, a2, a2h, wo, wd, out;
    const __nv_bfloat16* px;
    uint32_t zero;
};

__device__ __forceinline__ bool tile_is_qkv(int nt) { return nt < 4 || (nt >= 8 && nt < 16); }
__device__ __forceinline__ int tile_index(int nt) { return nt < 4 ? nt + 8 : (nt < 8 ? nt - 4 : (nt < 16 ? nt - 8 : nt - 12)); }

__global__ void __cluster_dims__(2, 1, 1) __launch_bounds__(384, 1)
fused_kernel(const __grid_constant__ Params prm) {
    extern __shared__ __align__(1024) uint8_t smem_raw[];
    const uint32_t base = smem_u32(smem_raw) & ~1023u;
    const uint32_t bars = base + BAR_OFF;
    auto full1 = [&](int s) { return bars + s * 8; };
    auto empty1 = [&](int s) { return bars + 32 + s * 8; };
    auto full2 = [&](int s) { return bars + 64 + s * 8; };
    auto empty2 = [&](int s) { return bars + 128 + s * 8; };
    const uint32_t sig_bar = bars + 192, dep_bar = bars + 256, cs_bar = bars + 304, fold_bar = bars + 320, x_bar = bars + 336;
    const uint32_t d_bar = bars + 344;
    const uint32_t colsum = bars + 512, stats = bars + 1536;
    auto stage2 = [&](int q) { return base + q * G2_STAGE_BYTES; };
    const uint32_t aux = base + AUX_OFF;

    const int warp = __shfl_sync(0xffffffffu, threadIdx.x >> 5, 0);
    const int lane = threadIdx.x & 31;
    const int rank = blockIdx.x & 1;
    const int mblk = ((blockIdx.x >> 1) & 7) * 2 + rank;
    const int nslot = blockIdx.x >> 4;
    const int mblk2 = (mblk & ~1) | (nslot & 1), col2 = (nslot >> 1) * 256 + rank * 128;

    if (blockIdx.x >= NGEMM) {
        if (threadIdx.x == 0) { TRACE_GT(0); TRACE(1); }
        attention(&prm.qk, (base + 2 * ATT_SLOT - 1) & ~(2u * ATT_SLOT - 1), prm.zero, blockIdx.x - NGEMM, warp, lane);
    } else if (warp >= 8) {
        unsigned* const flags = g_flags + mblk * 32;
        const CUtensorMap* const w0 = nslot < 4 ? &prm.wqkv : (rank ? &prm.wu : &prm.wg);
        const int w0_col = nslot < 4 ? 32 + nslot * 4 + rank * 2 : nslot * 2 - 8;
        if (elect_one()) {
            if (warp == 8) {
                TRACE_GT(0); TRACE(1);
                prefetch_map(&prm.x); prefetch_map(w0);
                for (int s = 0; s < G1_STAGES; s++) { mbar_init(full1(s), 1); mbar_init(empty1(s), 4); }
            } else if (warp == 9) {
                for (int s = 0; s < G2_STAGES; s++) { mbar_init(full2(s), 1); mbar_init(empty2(s), 4); }
                for (int s = 0; s < 2; s++) { mbar_init(d_bar + s * 8, 1); mbar_expect_tx(d_bar + s * 8, XF32 ? 32768 : 16384); }
            } else if (warp == 10) {
                for (int s = 0; s < 7; s++) mbar_init(sig_bar + s * 8, 8);
                mbar_init(fold_bar, 2); mbar_init(fold_bar + 8, 1); mbar_init(x_bar, 1);
            } else {
                for (int s = 0; s < 8; s++) mbar_init(dep_bar + s * 8, 1);
            }
            asm volatile("fence.mbarrier_init.release.cluster;" ::: "memory");
        }
        __syncwarp();
        asm volatile("barrier.cluster.arrive.relaxed.aligned;" ::: "memory");
        if (warp == 8 && lane == 0) {
            mbar_expect_tx(full1(0), G1_STAGE_BYTES);
            tma_2d(base, &prm.x, full1(0), 0, mblk * 128, policy(true));
            prefetch_3d(w0, 0, w0_col, policy(true));
            TRACE(15);
        }
        asm volatile("setmaxnreg.dec.sync.aligned.u32 %0;" :: "n"(AUX_REGS));
        asm volatile("barrier.cluster.wait.acquire.aligned;" ::: "memory");

        if (warp == 8) {
            if (lane == 0) {
                TRACE(2);
                auto load_b1 = [&](int s, int nt, int k) {
                    const uint32_t dst = base + s * G1_STAGE_BYTES + A_BYTES + rank * 16384;
                    if (tile_is_qkv(nt)) tma_3d_mc(dst, &prm.wqkv, full1(s), 0, k * 64, tile_index(nt) * 4 + rank * 2, policy(true));
                    else tma_3d_mc(dst, rank ? &prm.wu : &prm.wg, full1(s), 0, k * 64, tile_index(nt) * 2, policy(true));
                };
                load_b1(0, nslot, 0);
                uint32_t ph = 1;
                for (int it = 1; it < G1_TILES * G1_KSTEPS; it++) {
                    const int s = it & 3, k = it & 15;
                    if (it == G1_STAGES) {
                        prefetch_map(&prm.xn); prefetch_map(&prm.wqkv); prefetch_map(&prm.wu); prefetch_map(&prm.wg);
                        prefetch_map(&prm.a2); prefetch_map(&prm.a2h); prefetch_map(&prm.wo); prefetch_map(&prm.wd); prefetch_map(&prm.out);
                    }
                    if (it == G1_KSTEPS) { TRACE(14); mbar_wait(dep_bar, 0); TRACE(3); }
                    mbar_wait(empty1(s), ph);
                    mbar_expect_tx(full1(s), G1_STAGE_BYTES);
                    tma_2d(base + s * G1_STAGE_BYTES, it < G1_KSTEPS ? &prm.x : &prm.xn, full1(s), k * 64, mblk * 128,
                           policy(it < G1_KSTEPS || it >= (G1_TILES - 1) * G1_KSTEPS));
                    load_b1(s, (it >> 4) * 8 + nslot, k);
                    if (s == 3) ph ^= 1;
                }
                TRACE(4);
                mbar_wait(dep_bar + 8, 0);
                TRACE(5);
                for (int u = 0; u < D_KSTEPS; u++) {
                    const int s = u & 3, k = u < D_LATE ? rank * D_LATE + u : D_LATE + rank * (D_KSTEPS - D_LATE) + u;
                    if (u == D_LATE) { TRACE(6); mbar_wait(dep_bar + 16, 0); TRACE(7); }
                    mbar_wait(empty1(s), ph);
                    mbar_expect_tx(full1(s), G1_STAGE_BYTES);
                    const uint32_t sa = base + s * G1_STAGE_BYTES;
                    tma_3d(sa, &prm.a2, full1(s), DM + k * 64, 0, mblk2 * 64, policy(true));
#pragma unroll
                    for (int j = 0; j < 4; j++) tma_5d(sa + A_BYTES + j * 8192, &prm.wd, full1(s), col2 ^ (j * 64), k * 2, policy(true));
                    if (s == 3) ph ^= 1;
                    if (u == X_AT - D_FIRST) {
                        mbar_expect_tx(x_bar, 32768);
                        tma_2d(aux, &prm.x, x_bar, col2, mblk2 * 128, policy(true));
                        tma_2d(aux + 16384, &prm.x, x_bar, col2 + 64, mblk2 * 128, policy(true));
                    }
                }
                int q = 0; uint32_t ph2 = 1;
                for (int u = 0; u < G2_KSTEPS; u++) {
                    if (u == 0 || u == G2_LAST) {
                        TRACE(u ? 40 : 32);
                        mbar_wait(dep_bar + (u ? 32 : 24), 0);
                        TRACE(u ? 41 : 33);
                    }
                    if (u < G2_STAGES) {
                        if (u == 0) mbar_wait(empty1(0), ph);
                        if (u == 1) mbar_wait(empty1(1), ph);
                        if (u == 3) mbar_wait(empty1(2), ph);
                        if (u == 4) mbar_wait(empty1(3), ph);
                    } else {
                        mbar_wait(empty2(q), ph2);
                    }
                    const uint32_t sa = stage2(q);
                    const int k = u % 4 * 4 + u / 4;
                    mbar_expect_tx(full2(q), G2_STAGE_BYTES);
                    tma_3d_mc(sa + rank * 8192, &prm.a2h, full2(q), k * 64, 0, mblk2 * 64 + rank * 32, policy(true));
                    tma_5d(sa + A_BYTES, &prm.wo, full2(q), col2, k * 2, policy(true));
                    tma_5d(sa + A_BYTES + 8192, &prm.wo, full2(q), col2 + 64, k * 2, policy(true));
                    if (++q == G2_STAGES) { q = 0; ph2 ^= 1; }
                }
                TRACE(8);
            }
        } else if (warp == 9) {
            if (lane == 0) {
                const unsigned epoch = __ldcg(g_epoch + blockIdx.x * 16 + 2) + 1;
                mbar_wait(sig_bar, 0);
                TRACE(11);
                flag_add(flags + F_LN * 512);
                TRACE(42);
                flag_wait(flags + F_LN * 512, epoch * CNT_LN);
                fence_proxy_async();
                mbar_arrive(dep_bar);
                mbar_expect_tx(fold_bar + 8, 1024);
                bulk_load(stats, g_stats + mblk * 128, 1024, fold_bar + 8);
                g_epoch[blockIdx.x * 16 + 2] = epoch;
                for (int p = nslot < 4 ? 2 : 1; p < 7; p++) {
                    mbar_wait(sig_bar + p * 8, 0);
                    if (p == 2) TRACE(37);
                    flag_add(p == 2 || p == 3 ? g_flags + F_QKV * 512 + (p * 4 - 8 + (nslot & 3)) * 32
                                              : flags + (p < 6 ? F_EARLY : F_LATE) * 512);
                    if (p == 2) TRACE(43);
                }
            }
        } else {
            const int w = warp - 10;
            const unsigned epoch = __ldcg(g_epoch + blockIdx.x * 16 + w) + 1;
            unsigned* const cs_flag = g_flags + F_CS * 512 + (nslot * 2 + w) * 32;
            mbar_wait(empty1(1), 0);
            if (elect_one()) {
                mbar_expect_tx(cs_bar + w * 8, 16384);
                tma_3d(aux + w * 16384, nslot < 4 ? &prm.wqkv : (w ? &prm.wu : &prm.wg), cs_bar + w * 8, 0, mblk * 64,
                       nslot < 4 ? 32 + nslot * 4 + w * 2 : nslot * 2 - 8, policy(true));
            }
            float cs[8];
#pragma unroll
            for (int d = 0; d < 8; d++) cs[d] = 0.f;
            mbar_wait(cs_bar + w * 8, 0);
            const uint32_t wa = aux + w * 16384 + (lane & 8) * 1024 + (lane >> 4) * 128 + (((lane & 7) ^ (lane >> 4)) << 4);
#pragma unroll 1
            for (int i = 0; i < 8; i++) {
#pragma unroll
                for (int j = 0; j < 4; j++) {
                    float f[8];
                    unpack8(lds128((wa ^ (j * 32)) + i * 1024 + j * 256), f);
#pragma unroll
                    for (int d = 0; d < 8; d++) cs[d] += f[d];
                }
            }
#pragma unroll
            for (int d = 0; d < 8; d++) cs[d] += __shfl_xor_sync(0xffffffffu, cs[d], 16);
            *reinterpret_cast<float4*>(g_colsum + (nslot * 2 + w) * 2048 + mblk * 128 + (lane & 15) * 8 + (lane >> 4) * 4) =
                lane < 16 ? make_float4(cs[0], cs[1], cs[2], cs[3]) : make_float4(cs[4], cs[5], cs[6], cs[7]);
            __syncwarp();
            if (lane == 0) {
                if (w == 0) TRACE(34);
                flag_add(cs_flag);
                flag_wait(cs_flag, epoch * CNT_CS);
                fence_proxy_async();
                mbar_expect_tx(cs_bar + w * 8, 8192);
                bulk_load(aux + w * 16384, g_colsum + (nslot * 2 + w) * 2048, 8192, cs_bar + w * 8);
            }
            mbar_wait(cs_bar + w * 8, 1);
            float4 c = make_float4(0.f, 0.f, 0.f, 0.f);
#pragma unroll 8
            for (int m = 0; m < 16; m++) {
                const uint4 a = lds128(aux + w * 16384 + m * 512 + lane * 16);
                c.x += __uint_as_float(a.x); c.y += __uint_as_float(a.y); c.z += __uint_as_float(a.z); c.w += __uint_as_float(a.w);
            }
            const uint32_t ca = colsum + (w * 8 + (lane >> 2)) * 64 + (lane & 1) * 32 + (lane & 2) * 4;
            sts64f(ca, c.x, c.y);
            sts64f(ca + 16, c.z, c.w);
            __syncwarp();
            if (lane == 0) {
                mbar_arrive(fold_bar);
                g_epoch[blockIdx.x * 16 + w] = epoch;
                if (w == 0) {
                    TRACE(35);
                    flag_wait(g_flags + F_EARLY * 512 + mblk2 * 32, epoch * CNT_EARLY);
                    fence_proxy_async(); mbar_arrive(dep_bar + 8);
                    flag_wait(g_flags + F_LATE * 512 + mblk2 * 32, epoch * CNT_LATE);
                    fence_proxy_async(); mbar_arrive(dep_bar + 16);
                    flag_wait(g_flags + F_O * 512, epoch * CNT_O);
                    fence_proxy_async(); mbar_arrive(dep_bar + 24);
                    flag_wait(g_flags + F_O * 512 + 32, epoch * CNT_O);
                    fence_proxy_async(); mbar_arrive(dep_bar + 32);
                }
            }
        }
    } else {
        asm volatile("barrier.cluster.arrive.relaxed.aligned;" ::: "memory");
        asm volatile("setmaxnreg.inc.sync.aligned.u32 %0;" :: "n"(CONSUMER_REGS));
        const int wg = __shfl_sync(0xffffffffu, threadIdx.x >> 7, 0);
        const int cw = threadIdx.x >> 5;
        const int tid = threadIdx.x & 127;
        float acc[128];
        uint32_t pk[64];
#pragma unroll
        for (int i = 0; i < 64; i++) asm volatile("mov.b32 %0, 0;" : "=r"(pk[i]));
#pragma unroll
        for (int i = 0; i < 128; i++) asm volatile("mov.b32 %0, 0;" : "=f"(acc[i]));
        asm volatile("barrier.cluster.wait.acquire.aligned;" ::: "memory");

        const int orow = ((lane >> 2) & 1) * (SEQ / 2) + mblk * 64 + cw * 8 + (lane >> 3);
        __nv_bfloat16* optr = nullptr;
        auto release = [&](uint32_t bar) { if (tid < 2) mbar_arrive_cluster(bar, tid); };
        auto chunk_geglu = [&](int j) {
            const int c = j >> 1, h = j & 1;
            uint4 v;
            v.x = geglu2(pk[8 * c + h], pk[32 + 8 * c + h]);
            v.y = geglu2(pk[8 * c + 2 + h], pk[32 + 8 * c + 2 + h]);
            v.z = geglu2(pk[8 * c + 4 + h], pk[32 + 8 * c + 4 + h]);
            v.w = geglu2(pk[8 * c + 6 + h], pk[32 + 8 * c + 6 + h]);
            *reinterpret_cast<uint4*>(optr + h * 4 * K2 + c * 32) = v;
        };
        auto chunk_qkv = [&](int c) {
            *reinterpret_cast<uint4*>(optr + c * 32) = make_uint4(pk[8 * c], pk[8 * c + 2], pk[8 * c + 4], pk[8 * c + 6]);
            *reinterpret_cast<uint4*>(optr + 4 * NQKV + c * 32) = make_uint4(pk[8 * c + 1], pk[8 * c + 3], pk[8 * c + 5], pk[8 * c + 7]);
        };
        auto signal_stores = [&](int p) { __syncwarp(); if (lane == 0) mbar_arrive(sig_bar + p * 8); };

        auto chunk_ln = [&](int k) {
            const int row = mblk * 128 + nslot * 16 + cw * 2;
            float* const mo = reinterpret_cast<float*>(pk + 32);
            if (k == 0) {
                const uint4* xp = reinterpret_cast<const uint4*>(prm.px + (size_t)row * DM) + lane;
#pragma unroll
                for (int i = 0; i < 8; i++) {
                    const uint4 v = ldg_stream(xp + i * 32, policy(true));
                    pk[4 * i] = v.x; pk[4 * i + 1] = v.y; pk[4 * i + 2] = v.z; pk[4 * i + 3] = v.w;
                }
            } else if (k >= LN_STEP && k < LN_STEP + 3) {
                if (k == LN_STEP) {
                    mo[0] = bf_lo(uniform(pk[0])); mo[1] = bf_lo(uniform(pk[16]));
                    mo[2] = mo[3] = mo[4] = mo[5] = 0.f;
                }
#pragma unroll
                for (int i = (k - LN_STEP) * 11; i < (k - LN_STEP) * 11 + 11 && i < 32; i++) {
                    const int r = i & 1;
                    const uint32_t w = pk[r * 16 + i / 2];
                    const float lo = bf_lo(w) - mo[r], hi = bf_hi(w) - mo[r];
                    mo[2 + r] += lo + hi;
                    mo[4 + r] = fmaf(hi, hi, fmaf(lo, lo, mo[4 + r]));
                }
            } else if (k == LN_STEP + 3) {
                const bool second = lane & 16;
                float m1 = (second ? mo[3] : mo[2]) + __shfl_xor_sync(0xffffffffu, second ? mo[2] : mo[3], 16);
                float m2 = (second ? mo[5] : mo[4]) + __shfl_xor_sync(0xffffffffu, second ? mo[4] : mo[5], 16);
#pragma unroll
                for (int o = 8; o > 0; o >>= 1) {
                    m1 += __shfl_xor_sync(0xffffffffu, m1, o);
                    m2 += __shfl_xor_sync(0xffffffffu, m2, o);
                }
                m1 *= 1.f / DM;
                const float var = fmaxf(fmaf(-m1, m1, m2 * (1.f / DM)), 0.f);
                const float mean = round_bf16((second ? mo[1] : mo[0]) + m1);
                const float inv = 1.f / round_bf16(sqrtf(round_bf16(round_bf16(var) + 1e-5f)));
                if ((lane & 15) == 0) g_stats[row + second] = make_float2(-mean, inv);
                const uint32_t split = pack_bf16(inv - round_bf16(inv), inv);
#pragma unroll
                for (int r = 0; r < 2; r++) {
                    const uint32_t f = __shfl_sync(0xffffffffu, split, r * 16);
                    pk[32 + 3 * r] = __byte_perm(__shfl_sync(0xffffffffu, __float_as_uint(mean), r * 16), 0, 0x3232);
                    pk[33 + 3 * r] = __byte_perm(f, 0, 0x3232);
                    pk[34 + 3 * r] = __byte_perm(f, 0, 0x1010);
                }
            } else if (k >= LN_STEP + 4 && k < LN_STEP + 7) {
#pragma unroll
                for (int i = (k - LN_STEP - 4) * 3; i < (k - LN_STEP - 3) * 3 && i < 8; i++) {
                    const uint32_t* n = pk + 32 + i / 4 * 3;
                    uint32_t o[4];
#pragma unroll
                    for (int j = 0; j < 4; j++) o[j] = mul2_bf16x2(sub_bf16x2(pk[i * 4 + j], n[0]), n[1], n[2]);
                    *reinterpret_cast<uint4*>(g_xn + (size_t)row * DM + i * 256 + lane * 8) = make_uint4(o[0], o[1], o[2], o[3]);
                }
                if (k == LN_STEP + 6) signal_stores(0);
            } else if (k == FOLD_STEP) {
                mbar_wait(fold_bar, 0);
#pragma unroll
                for (int j = 0; j < 16; j++) {
                    const uint4 c = lds128(colsum + j * 64 + (lane & 3) * 16);
                    pk[4 * j] = c.x; pk[4 * j + 1] = c.y; pk[4 * j + 2] = c.z; pk[4 * j + 3] = c.w;
                }
            }
        };

        bool gated = false;
#pragma unroll 1
        for (int t = 0;; t++) {
#pragma unroll
            for (int k = 0; k < G1_KSTEPS; k++) {
                const int s = k & 3;
                mbar_wait(full1(s), (k >> 2) & 1);
                if (t == 0 && k == 0 && threadIdx.x == 0) TRACE(12);
                if (TRACE_T >= 0 && t == TRACE_T && threadIdx.x == 0) TRACE(44 + k);
                if (wg == 1 && k == G1_KSTEPS - G1_SKEW && t < G1_TILES) asm volatile("bar.sync 1, 256;" ::: "memory");
                const uint64_t da = desc_a(base + s * G1_STAGE_BYTES + wg * 8192);
                const uint64_t db = desc_b(base + s * G1_STAGE_BYTES + A_BYTES);
                wg_fence();
#pragma unroll
                for (int kk = 0; kk < 4; kk++) wgmma_n256(acc, da + kk * 2, db + kk * 128, (k | kk) != 0);
                wg_commit();
                if (wg == 0 && k == G1_KSTEPS - 1 && t < G1_TILES) asm volatile("bar.arrive 1, 256;" ::: "memory");
                wg_wait<1>();
                if (k > 0) release(empty1((k - 1) & 3));
                if (t == 0) chunk_ln(k);
                if (k >= 1 && k <= 8 && gated) {
                    chunk_geglu(k - 1);
                    if (k == 8) signal_stores(t == 1 ? 1 : t + 1);
                }
                if (t != 0 && !gated) {
                    if (k == 0) { chunk_qkv(0); chunk_qkv(1); }
                    if (k >= 6 && k <= 11) chunk_qkv(k - 4);
                    if ((k == 0 || k == 11) && t == 2) signal_stores(k ? 3 : 2);
                }
            }
            if (t == G1_TILES) break;
            wg_wait<0>();
            fence_regs(acc);
            release(empty1(3));
            if (t == 0) {
                mbar_wait(fold_bar + 8, 0);
                const uint32_t sp = stats + (cw * 16 + (lane >> 2)) * 8;
                const float2 sa = lds64f(sp), sb = lds64f(sp + 64);
#pragma unroll
                for (int j = 0; j < 16; j++) {
                    const float c0 = __uint_as_float(pk[4 * j]), c1 = __uint_as_float(pk[4 * j + 1]);
                    const float c2 = __uint_as_float(pk[4 * j + 2]), c3 = __uint_as_float(pk[4 * j + 3]);
                    const float* a = acc + 8 * j;
                    pk[4 * j] = pack_bf16(fmaf(sa.x, c0, a[0]) * sa.y, fmaf(sa.x, c1, a[1]) * sa.y);
                    pk[4 * j + 1] = pack_bf16(fmaf(sb.x, c0, a[2]) * sb.y, fmaf(sb.x, c1, a[3]) * sb.y);
                    pk[4 * j + 2] = pack_bf16(fmaf(sa.x, c2, a[4]) * sa.y, fmaf(sa.x, c3, a[5]) * sa.y);
                    pk[4 * j + 3] = pack_bf16(fmaf(sb.x, c2, a[6]) * sb.y, fmaf(sb.x, c3, a[7]) * sb.y);
                }
            } else {
#pragma unroll
                for (int i = 0; i < 64; i++) pk[i] = pack_bf16(acc[2 * i], acc[2 * i + 1]);
            }
            const int nt = t * 8 + nslot;
            gated = !tile_is_qkv(nt);
            optr = !gated ? g_qkv + (size_t)orow * NQKV + tile_index(nt) * 256 + (lane & 3) * 8
                                : g_a2 + (size_t)orow * K2 + DM + tile_index(nt) * 128 + (lane & 3) * 8;
            if (tid == 0) TRACE(16 + wg * 8 + t);
        }

#pragma unroll 1
        for (int k4 = G1_KSTEPS / 4; k4 < D_KSTEPS / 4; k4++) {
#pragma unroll
            for (int s = 0; s < 4; s++) {
                mbar_wait(full1(s), k4 & 1);
                const uint64_t da = desc_a(base + s * G1_STAGE_BYTES + wg * 8192);
                const uint64_t db = desc_b(base + s * G1_STAGE_BYTES + A_BYTES);
                wg_fence();
#pragma unroll
                for (int kk = 0; kk < 4; kk++) wgmma_n256(acc, da + kk * 2, db + kk * 128, 1);
                wg_commit();
                wg_wait<1>();
                release(empty1((s - 1) & 3));
            }
        }
        float accs[64];
        if (tid == 0) TRACE(16 + wg * 8 + 5);
#pragma unroll
        for (int i = 0; i < 64; i++) accs[i] = 0.f;
        uint32_t gk[32], xr[32];
        const uint32_t swap = stage2(G2_STAGES) + threadIdx.x * 16;
        const uint32_t xs = aux + cw * 2048;
        const uint32_t xrow = xs + ((lane & 7) + ((lane >> 3) & 1) * 8) * 128;
        auto xaddr = [&](int j) { return xrow + (j >> 2) * 16384 + (((((j & 3) * 2) + (lane >> 4)) ^ (lane & 7)) << 4); };
#pragma unroll
        for (int u = 0; u < G2_KSTEPS; u++) {
            const int q = u % G2_STAGES, v = u;
            mbar_wait(full2(q), (u / G2_STAGES) & 1);
            if (G2_SKEW > 0 && wg == 1 && u == G2_KSTEPS - G2_SKEW) asm volatile("bar.sync 1, 256;" ::: "memory");
            const uint64_t da = desc_a(stage2(q) + wg * 8192), db = desc_b(stage2(q) + A_BYTES);
            wg_fence();
#pragma unroll
            for (int kk = 0; kk < 4; kk++) wgmma_n128(accs, da + kk * 2, db + kk * 128, (v | kk) != 0);
            wg_commit();
            if (G2_SKEW > 0 && wg == 0 && u == G2_KSTEPS - 1) asm volatile("bar.arrive 1, 256;" ::: "memory");
            wg_wait<1>();
            if (v == 0) { fence_regs(acc); release(empty1(3)); }
            else if (u - 1 + G2_STAGES < G2_KSTEPS) release(empty2((u - 1) % G2_STAGES));
            if (v == SEND_AT) mbar_wait(empty1(3), (D_KSTEPS / 4 - 1) & 1);
            if (v >= SEND_AT && v < SEND_AT + 4) {
                const uint32_t dst = map_cluster(swap, rank ^ 1), bar = map_cluster(d_bar + wg * 8, rank ^ 1);
                const float* a = acc + 64 + (v - SEND_AT) * 16;
#pragma unroll
                for (int j = 0; j < (XF32 ? 4 : 2); j++) {
                    if (XF32) st_async(dst + ((v - SEND_AT) * 4 + j) * 4096, __float_as_uint(a[4 * j]), __float_as_uint(a[4 * j + 1]),
                                       __float_as_uint(a[4 * j + 2]), __float_as_uint(a[4 * j + 3]), bar);
                    else st_async(dst + ((v - SEND_AT) * 2 + j) * 4096, pack_bf16(a[8 * j], a[8 * j + 1]), pack_bf16(a[8 * j + 2], a[8 * j + 3]),
                                  pack_bf16(a[8 * j + 4], a[8 * j + 5]), pack_bf16(a[8 * j + 6], a[8 * j + 7]), bar);
                }
            }
            if (v == RECV_AT) mbar_wait_cluster(d_bar + wg * 8);
            if (v >= RECV_AT && v < RECV_AT + 8) {
                const int c = v - RECV_AT;
                float f[8];
                if (XF32) {
                    const uint4 a = lds128(swap + c * 8192), b = lds128(swap + c * 8192 + 4096);
                    f[0] = __uint_as_float(a.x); f[1] = __uint_as_float(a.y); f[2] = __uint_as_float(a.z); f[3] = __uint_as_float(a.w);
                    f[4] = __uint_as_float(b.x); f[5] = __uint_as_float(b.y); f[6] = __uint_as_float(b.z); f[7] = __uint_as_float(b.w);
                } else {
                    unpack8(lds128(swap + c * 4096), f);
                }
#pragma unroll
                for (int i = 0; i < 4; i++) {
                    const uint32_t d2 = pack_bf16(acc[8 * c + 2 * i] + f[2 * i], acc[8 * c + 2 * i + 1] + f[2 * i + 1]);
                    gk[4 * c + i] = pack_bf16(silu(bf_lo(d2)), silu(bf_hi(d2)));
                }
            }
            if (v == 10) mbar_wait(x_bar, 0);
            if (v >= 10 && v <= 13) {
#pragma unroll
                for (int j = 2 * (v - 10); j < 2 * (v - 9); j++)
                    asm volatile("ldmatrix.sync.aligned.m8n8.x4.shared.b16 {%0,%1,%2,%3}, [%4];"
                                 : "=r"(xr[4 * j]), "=r"(xr[4 * j + 1]), "=r"(xr[4 * j + 2]), "=r"(xr[4 * j + 3])
                                 : "r"(xaddr(j)) : "memory");
            }
        }
        wg_wait<0>();
        fence_regs(accs);
        if (tid == 0) TRACE(16 + wg * 8 + 6);
#pragma unroll
        for (int j = 0; j < 8; j++) {
            uint32_t r[4];
#pragma unroll
            for (int i = 0; i < 4; i++) {
                const int e = j * 4 + i;
                r[i] = add_bf16x2(xr[e], mul_bf16x2(pack_bf16(accs[2 * e], accs[2 * e + 1]), gk[e]));
            }
            asm volatile("stmatrix.sync.aligned.m8n8.x4.shared.b16 [%0], {%1,%2,%3,%4};"
                         :: "r"(xaddr(j)), "r"(r[0]), "r"(r[1]), "r"(r[2]), "r"(r[3]) : "memory");
            if (j == 3 || j == 7) {
                asm volatile("fence.proxy.async.shared::cta;" ::: "memory");
                __syncwarp();
                if (lane == 0) {
                    tma_store_2d(&prm.out, xs + (j >> 2) * 16384, col2 + (j >> 2) * 64, mblk2 * 128 + cw * 16);
                    asm volatile("cp.async.bulk.commit_group;" ::: "memory");
                }
            }
        }
        if (lane == 0) asm volatile("cp.async.bulk.wait_group.read 0;" ::: "memory");
        if (tid == 0) { TRACE(16 + wg * 8 + 7); if (wg == 1) TRACE_GT(13); }
    }
}

typedef CUresult (*EncodeFn)(CUtensorMap*, CUtensorMapDataType, cuuint32_t, void*, const cuuint64_t*, const cuuint64_t*,
                             const cuuint32_t*, const cuuint32_t*, CUtensorMapInterleave, CUtensorMapSwizzle,
                             CUtensorMapL2promotion, CUtensorMapFloatOOBfill);

void encode(EncodeFn fn, CUtensorMap* m, const void* ptr, int rank, const cuuint64_t* dims, const cuuint64_t* strides,
            const cuuint32_t* box) {
    const cuuint32_t es[5] = {1, 1, 1, 1, 1};
    fn(m, CU_TENSOR_MAP_DATA_TYPE_BFLOAT16, rank, const_cast<void*>(ptr), dims, strides, box, es,
       CU_TENSOR_MAP_INTERLEAVE_NONE, CU_TENSOR_MAP_SWIZZLE_128B, CU_TENSOR_MAP_L2_PROMOTION_L2_128B,
       CU_TENSOR_MAP_FLOAT_OOB_FILL_NONE);
}
void encode_2d(EncodeFn fn, CUtensorMap* m, const void* ptr, int cols, int box_rows) {
    const cuuint64_t dims[2] = {(cuuint64_t)cols, SEQ}, strides[1] = {(cuuint64_t)cols * 2};
    const cuuint32_t box[2] = {64, (cuuint32_t)box_rows};
    encode(fn, m, ptr, 2, dims, strides, box);
}
void encode_w1(EncodeFn fn, CUtensorMap* m, const void* ptr, int cols) {
    const cuuint64_t dims[3] = {64, DM, (cuuint64_t)cols / 64}, strides[2] = {(cuuint64_t)cols * 2, 128};
    const cuuint32_t box[3] = {64, 64, 2};
    encode(fn, m, ptr, 3, dims, strides, box);
}
void encode_qk(EncodeFn fn, CUtensorMap* m, const void* ptr) {
    const cuuint64_t dims[3] = {DM, SEQ, 3}, strides[2] = {NQKV * 2, DM * 2};
    const cuuint32_t box[3] = {64, 16, 2};
    encode(fn, m, ptr, 3, dims, strides, box);
}
void encode_a2(EncodeFn fn, CUtensorMap* m, const void* ptr, int rows) {
    const cuuint64_t dims[3] = {K2, 2, SEQ / 2}, strides[2] = {(cuuint64_t)SEQ * K2, K2 * 2};
    const cuuint32_t box[3] = {64, 2, (cuuint32_t)rows / 2};
    encode(fn, m, ptr, 3, dims, strides, box);
}
void encode_w2(EncodeFn fn, CUtensorMap* m, const void* ptr, int rows) {
    const cuuint64_t rb = DM * 2;
    const cuuint64_t dims[5] = {DM, 2, 4, 4, (cuuint64_t)rows / 32}, strides[4] = {rb, 8 * rb, 2 * rb, 32 * rb};
    const cuuint32_t box[5] = {64, 2, 4, 4, 2};
    encode(fn, m, ptr, 5, dims, strides, box);
}

}

extern "C" void kernel_launch(void* const* d_in, const int* in_sizes, int n_in, void* d_out, int out_size) {
    (void)in_sizes; (void)n_in; (void)out_size;
    static EncodeFn fn = nullptr;
    static void *p_xn = nullptr, *p_qkv = nullptr, *p_a2 = nullptr;
    if (!fn) {
        cudaDriverEntryPointQueryResult st;
        cudaGetDriverEntryPoint("cuTensorMapEncodeTiled", (void**)&fn, cudaEnableDefault, &st);
        cudaGetSymbolAddress(&p_xn, g_xn);
        cudaGetSymbolAddress(&p_qkv, g_qkv);
        cudaGetSymbolAddress(&p_a2, g_a2);
        cudaFuncSetAttribute(fused_kernel, cudaFuncAttributeMaxDynamicSharedMemorySize, SMEM_BYTES);
    }
    Params prm;
    encode_2d(fn, &prm.x, d_in[0], DM, 128);
    encode_2d(fn, &prm.xn, p_xn, DM, 128);
    encode_w1(fn, &prm.wqkv, d_in[1], NQKV);
    encode_w1(fn, &prm.wg, d_in[4], DF);
    encode_w1(fn, &prm.wu, d_in[5], DF);
    encode_qk(fn, &prm.qk, p_qkv);
    encode_2d(fn, &prm.v, p_qkv, NQKV, 16);
    encode_2d(fn, &prm.o, p_a2, K2, 16);
    encode_a2(fn, &prm.a2, p_a2, 128);
    encode_a2(fn, &prm.a2h, p_a2, 64);
    encode_w2(fn, &prm.wo, d_in[2], DM);
    encode_w2(fn, &prm.wd, d_in[6], DF);
    encode_2d(fn, &prm.out, d_out, DM, 16);
    prm.px = (const __nv_bfloat16*)d_in[0];
    prm.zero = 0;
    fused_kernel<<<NCTA, 384, SMEM_BYTES>>>(prm);
}
```

```cpp
#include <cuda_runtime.h>
#include <cuda_bf16.h>
#include <cuda.h>
#include <stdint.h>
#include <type_traits>

namespace {

constexpr int SEQ = 2048, DM = 1024, DF = 3584, K2 = DM + DF, NQKV = 3 * DM;
constexpr int NGEMM = 128, NCTA = 132;
constexpr int G1_STAGES = 4, G1_STAGE_BYTES = 49152, G1_KSTEPS = 16, G1_TILES = 5;
constexpr int G2_STAGES = 6, G2_STAGE_BYTES = 32768, G2_KSTEPS = 72, G2_LATE = 40, G2_DSTEPS = 56, G2_LAST = 68;
constexpr int LN_STEP = 3, FOLD_STEP = 14;
constexpr int A_BYTES = 16384;
constexpr int AUX_OFF = G1_STAGES * G1_STAGE_BYTES;
constexpr int BAR_OFF = AUX_OFF + 32768;
constexpr int SMEM_BYTES = BAR_OFF + 2560;
constexpr int G1_SKEW = 2, G2_SKEW = 2;
constexpr int CONSUMER_REGS = 224, AUX_REGS = 56;
constexpr int ATT_SLOT = 8192;

enum { F_LN = 0, F_QKV = 1, F_EARLY = 2, F_LATE = 3, F_O = 4, F_CS = 5 };
constexpr unsigned CNT_LN = 8, CNT_QKV = 32, CNT_EARLY = 20, CNT_LATE = 8, CNT_O = 4, CNT_CS = 16;

__device__ __align__(1024) __nv_bfloat16 g_xn[SEQ * DM];
__device__ __align__(1024) __nv_bfloat16 g_qkv[SEQ * NQKV];
__device__ __align__(1024) __nv_bfloat16 g_a2[SEQ * K2];
__device__ __align__(128) float2 g_stats[SEQ];
__device__ __align__(128) float g_colsum[16 * 2048];
__device__ __align__(128) unsigned g_flags[6 * 16 * 32];
__device__ __align__(128) unsigned g_epoch[NCTA * 16];

#define TRACE_T -1
#define TRACE(slot) do {} while (0)
#define TRACE_GT(slot) do {} while (0)

__device__ __forceinline__ uint32_t smem_u32(const void* p) { return (uint32_t)__cvta_generic_to_shared(p); }
__device__ __forceinline__ void mbar_init(uint32_t bar, uint32_t cnt) {
    asm volatile("mbarrier.init.shared::cta.b64 [%0], %1;" :: "r"(bar), "r"(cnt) : "memory");
}
__device__ __forceinline__ void mbar_expect_tx(uint32_t bar, uint32_t bytes) {
    asm volatile("mbarrier.arrive.expect_tx.shared::cta.b64 _, [%0], %1;" :: "r"(bar), "r"(bytes) : "memory");
}
__device__ __forceinline__ void mbar_arrive(uint32_t bar) {
    asm volatile("mbarrier.arrive.shared::cta.b64 _, [%0];" :: "r"(bar) : "memory");
}
__device__ __forceinline__ void mbar_arrive_cluster(uint32_t bar, uint32_t cta) {
    asm volatile("{\n.reg .b32 ra;\nmapa.shared::cluster.u32 ra, %0, %1;\nmbarrier.arrive.shared::cluster.b64 _, [ra];\n}"
                 :: "r"(bar), "r"(cta) : "memory");
}
__device__ __forceinline__ bool mbar_try_wait(uint32_t bar, uint32_t parity) {
    uint32_t ok;
    asm volatile("{\n.reg .pred p;\nmbarrier.try_wait.parity.shared::cta.b64 p, [%1], %2;\nselp.u32 %0, 1, 0, p;\n}"
                 : "=r"(ok) : "r"(bar), "r"(parity) : "memory");
    return ok;
}
__device__ __forceinline__ bool mbar_test(uint32_t bar, uint32_t parity) {
    uint32_t ok;
    asm volatile("{\n.reg .pred p;\nmbarrier.test_wait.parity.shared::cta.b64 p, [%1], %2;\nselp.u32 %0, 1, 0, p;\n}"
                 : "=r"(ok) : "r"(bar), "r"(parity) : "memory");
    return ok;
}
__device__ __forceinline__ void mbar_wait(uint32_t bar, uint32_t parity) {
#pragma unroll 1
    for (int spins = 0; !mbar_try_wait(bar, parity) && spins < (1 << 17); spins++) {}
}
template <bool WARP = false> __device__ __forceinline__ void flag_wait(const unsigned* p, unsigned target) {
#pragma unroll 1
    for (int spins = 0; spins < (1 << 19); spins++) {
        unsigned v;
        asm volatile("ld.acquire.gpu.global.u32 %0, [%1];" : "=r"(v) : "l"(p) : "memory");
        if (WARP ? __all_sync(0xffffffffu, (int)(v - target) >= 0) : (int)(v - target) >= 0) break;
        __nanosleep(64);
    }
}
__device__ __forceinline__ void mbar_wait_warp(uint32_t bar, uint32_t parity) {
#pragma unroll 1
    for (int spins = 0; !__all_sync(0xffffffffu, mbar_try_wait(bar, parity)) && spins < (1 << 17); spins++) {}
}
__device__ __forceinline__ void flag_add(unsigned* p) {
    asm volatile("red.release.gpu.global.add.u32 [%0], 1;" :: "l"(p) : "memory");
}
__device__ __forceinline__ bool elect_one() {
    uint32_t ok;
    asm volatile("{\n.reg .pred p;\nelect.sync _|p, 0xffffffff;\nselp.u32 %0, 1, 0, p;\n}" : "=r"(ok));
    return ok;
}
__device__ __forceinline__ void fence_proxy_async() { asm volatile("fence.proxy.async.global;" ::: "memory"); }
__device__ __forceinline__ uint4 lds128(uint32_t addr) {
    uint4 v;
    asm volatile("ld.shared.v4.u32 {%0,%1,%2,%3}, [%4];" : "=r"(v.x), "=r"(v.y), "=r"(v.z), "=r"(v.w) : "r"(addr) : "memory");
    return v;
}
__device__ __forceinline__ float2 lds64f(uint32_t addr) {
    float2 v;
    asm volatile("ld.shared.v2.f32 {%0,%1}, [%2];" : "=f"(v.x), "=f"(v.y) : "r"(addr) : "memory");
    return v;
}
__device__ __forceinline__ void sts128(uint32_t addr, uint4 v) {
    asm volatile("st.shared.v4.u32 [%0], {%1,%2,%3,%4};" :: "r"(addr), "r"(v.x), "r"(v.y), "r"(v.z), "r"(v.w) : "memory");
}
__device__ __forceinline__ void sts64f(uint32_t addr, float a, float b) {
    asm volatile("st.shared.v2.f32 [%0], {%1,%2};" :: "r"(addr), "f"(a), "f"(b) : "memory");
}

__device__ __forceinline__ uint64_t stream_policy() {
    uint64_t p;
    asm("createpolicy.fractional.L2::evict_first.b64 %0, 1.0;" : "=l"(p));
    return p;
}
__device__ __forceinline__ void tma_2d(uint32_t dst, const CUtensorMap* m, uint32_t bar, int c0, int c1, uint64_t pol) {
    asm volatile("cp.async.bulk.tensor.2d.shared::cluster.global.mbarrier::complete_tx::bytes.L2::cache_hint"
                 " [%0], [%1, {%3, %4}], [%2], %5;"
                 :: "r"(dst), "l"(m), "r"(bar), "r"(c0), "r"(c1), "l"(pol) : "memory");
}
__device__ __forceinline__ void tma_3d(uint32_t dst, const CUtensorMap* m, uint32_t bar, int c0, int c1, int c2, uint64_t pol) {
    asm volatile("cp.async.bulk.tensor.3d.shared::cluster.global.mbarrier::complete_tx::bytes.L2::cache_hint"
                 " [%0], [%1, {%3, %4, %5}], [%2], %6;"
                 :: "r"(dst), "l"(m), "r"(bar), "r"(c0), "r"(c1), "r"(c2), "l"(pol) : "memory");
}
__device__ __forceinline__ void tma_3d_mc(uint32_t dst, const CUtensorMap* m, uint32_t bar, int c1, int c2, uint64_t pol) {
    asm volatile("cp.async.bulk.tensor.3d.shared::cluster.global.mbarrier::complete_tx::bytes.multicast::cluster.L2::cache_hint"
                 " [%0], [%1, {%3, %4, %5}], [%2], %6, %7;"
                 :: "r"(dst), "l"(m), "r"(bar), "r"(0), "r"(c1), "r"(c2), "h"((uint16_t)3), "l"(pol) : "memory");
}
__device__ __forceinline__ void load_stage1(uint32_t dst, uint32_t dst_b, uint32_t bar, const CUtensorMap* ma, const CUtensorMap* mb,
                                            int k, int row, int col, int keep_a, uint64_t pol) {
    asm volatile("{\n.reg .pred e, p, q;\nelect.sync _|e, 0xffffffff;\nsetp.ne.and.b32 p|q, %8, 0, e;\n"
        "@p cp.async.bulk.tensor.2d.shared::cluster.global.mbarrier::complete_tx::bytes [%0], [%3, {%5, %6}], [%2];\n"
        "@q cp.async.bulk.tensor.2d.shared::cluster.global.mbarrier::complete_tx::bytes.L2::cache_hint [%0], [%3, {%5, %6}], [%2], %9;\n"
        "@e cp.async.bulk.tensor.3d.shared::cluster.global.mbarrier::complete_tx::bytes.multicast::cluster.L2::cache_hint"
        " [%1], [%4, {%10, %5, %7}], [%2], %11, %9;\n"
        "@e mbarrier.arrive.expect_tx.shared::cta.b64 _, [%2], %12;\n}"
        :: "r"(dst), "r"(dst_b), "r"(bar), "l"(ma), "l"(mb), "r"(k), "r"(row), "r"(col), "r"(keep_a), "l"(pol), "r"(0),
           "h"((uint16_t)3), "n"(G1_STAGE_BYTES) : "memory");
}
__device__ __forceinline__ void load_stage2(uint32_t dst, uint32_t dst_b, uint32_t bar, const CUtensorMap* ma, const CUtensorMap* mb,
                                            int ka, int row, int col, int kb, uint64_t pol) {
    asm volatile("{\n.reg .pred e;\nelect.sync _|e, 0xffffffff;\n"
        "@e cp.async.bulk.tensor.3d.shared::cluster.global.mbarrier::complete_tx::bytes.L2::cache_hint [%0], [%3, {%5, %10, %6}], [%2], %9;\n"
        "@e cp.async.bulk.tensor.5d.shared::cluster.global.mbarrier::complete_tx::bytes.multicast::cluster.L2::cache_hint"
        " [%1], [%4, {%7, %10, %10, %10, %8}], [%2], %11, %9;\n"
        "@e mbarrier.arrive.expect_tx.shared::cta.b64 _, [%2], %12;\n}"
        :: "r"(dst), "r"(dst_b), "r"(bar), "l"(ma), "l"(mb), "r"(ka), "r"(row), "r"(col), "r"(kb), "l"(pol), "r"(0),
           "h"((uint16_t)3), "n"(G2_STAGE_BYTES) : "memory");
}
__device__ __forceinline__ void tma_store_2d(const CUtensorMap* m, uint32_t src, int c0, int c1) {
    asm volatile("cp.async.bulk.tensor.2d.global.shared::cta.bulk_group [%0, {%2, %3}], [%1];"
                 :: "l"(m), "r"(src), "r"(c0), "r"(c1) : "memory");
}
__device__ __forceinline__ uint4 ldg_stream(const void* p, uint64_t pol) {
    uint4 v;
    asm volatile("ld.global.nc.L1::no_allocate.L2::cache_hint.v4.u32 {%0,%1,%2,%3}, [%4], %5;"
                 : "=r"(v.x), "=r"(v.y), "=r"(v.z), "=r"(v.w) : "l"(p), "l"(pol));
    return v;
}
__device__ __forceinline__ void bulk_load(uint32_t dst, const void* src, uint32_t bytes, uint32_t bar) {
    asm volatile("cp.async.bulk.shared::cluster.global.mbarrier::complete_tx::bytes [%0], [%1], %2, [%3];"
                 :: "r"(dst), "l"(src), "r"(bytes), "r"(bar) : "memory");
}
__device__ __forceinline__ void prefetch_3d(const CUtensorMap* m, int c1, int c2, uint64_t pol) {
    asm volatile("cp.async.bulk.prefetch.tensor.3d.L2.global.L2::cache_hint [%0, {%1, %2, %3}], %4;"
                 :: "l"(m), "r"(0), "r"(c1), "r"(c2), "l"(pol) : "memory");
}
__device__ __forceinline__ void prefetch_map(const CUtensorMap* m) {
    asm volatile("prefetch.tensormap [%0];" :: "l"(m) : "memory");
}
__device__ __forceinline__ void wg_fence() { asm volatile("wgmma.fence.sync.aligned;" ::: "memory"); }
__device__ __forceinline__ void wg_commit() { asm volatile("wgmma.commit_group.sync.aligned;" ::: "memory"); }
template <int N> __device__ __forceinline__ void wg_wait() { asm volatile("wgmma.wait_group.sync.aligned %0;" :: "n"(N) : "memory"); }

__device__ __forceinline__ uint64_t desc_a(uint32_t addr) {
    return (uint64_t)((addr & 0x3FFFF) >> 4) | (1ull << 16) | (64ull << 32) | (1ull << 62);
}
__device__ __forceinline__ uint64_t desc_b(uint32_t addr) {
    return (uint64_t)((addr & 0x3FFFF) >> 4) | (512ull << 16) | (64ull << 32) | (1ull << 62);
}

#define R8(d, o) "+f"(d[o]), "+f"(d[o+1]), "+f"(d[o+2]), "+f"(d[o+3]), "+f"(d[o+4]), "+f"(d[o+5]), "+f"(d[o+6]), "+f"(d[o+7])
#define R32(d, o) R8(d, o), R8(d, o+8), R8(d, o+16), R8(d, o+24)
#define R64(d, o) R32(d, o), R32(d, o+32)

__device__ __forceinline__ void wgmma_n256(float (&d)[128], uint64_t da, uint64_t db, int scale_d) {
    asm volatile("{\n.reg .pred p;\nsetp.ne.b32 p, %130, 0;\n"
        "wgmma.mma_async.sync.aligned.m64n256k16.f32.bf16.bf16 "
        "{%0,%1,%2,%3,%4,%5,%6,%7,%8,%9,%10,%11,%12,%13,%14,%15,%16,%17,%18,%19,%20,%21,%22,%23,%24,%25,%26,%27,%28,%29,%30,%31,"
        "%32,%33,%34,%35,%36,%37,%38,%39,%40,%41,%42,%43,%44,%45,%46,%47,%48,%49,%50,%51,%52,%53,%54,%55,%56,%57,%58,%59,%60,%61,%62,%63,"
        "%64,%65,%66,%67,%68,%69,%70,%71,%72,%73,%74,%75,%76,%77,%78,%79,%80,%81,%82,%83,%84,%85,%86,%87,%88,%89,%90,%91,%92,%93,%94,%95,"
        "%96,%97,%98,%99,%100,%101,%102,%103,%104,%105,%106,%107,%108,%109,%110,%111,%112,%113,%114,%115,%116,%117,%118,%119,%120,%121,%122,%123,%124,%125,%126,%127},"
        " %128, %129, p, 1, 1, 0, 1;\n}"
        : R64(d, 0), R64(d, 64) : "l"(da), "l"(db), "r"(scale_d));
}
__device__ __forceinline__ void wgmma_n128(float (&d)[64], uint64_t da, uint64_t db, int scale_d) {
    asm volatile("{\n.reg .pred p;\nsetp.ne.b32 p, %66, 0;\n"
        "wgmma.mma_async.sync.aligned.m64n128k16.f32.bf16.bf16 "
        "{%0,%1,%2,%3,%4,%5,%6,%7,%8,%9,%10,%11,%12,%13,%14,%15,%16,%17,%18,%19,%20,%21,%22,%23,%24,%25,%26,%27,%28,%29,%30,%31,"
        "%32,%33,%34,%35,%36,%37,%38,%39,%40,%41,%42,%43,%44,%45,%46,%47,%48,%49,%50,%51,%52,%53,%54,%55,%56,%57,%58,%59,%60,%61,%62,%63},"
        " %64, %65, p, 1, 1, 0, 1;\n}"
        : R64(d, 0) : "l"(da), "l"(db), "r"(scale_d));
}

__device__ __forceinline__ uint32_t pack_bf16(float lo, float hi) {
    uint32_t r; asm("cvt.rn.bf16x2.f32 %0, %1, %2;" : "=r"(r) : "f"(hi), "f"(lo)); return r;
}
__device__ __forceinline__ float bf_lo(uint32_t v) { return __uint_as_float(v << 16); }
__device__ __forceinline__ float bf_hi(uint32_t v) { return __uint_as_float(v & 0xffff0000u); }
__device__ __forceinline__ float round_bf16(float v) { return bf_lo(pack_bf16(v, 0.f)); }
__device__ __forceinline__ uint32_t mul_bf16x2(uint32_t a, uint32_t b) {
    uint32_t r; asm("mul.rn.bf16x2 %0, %1, %2;" : "=r"(r) : "r"(a), "r"(b)); return r;
}
__device__ __forceinline__ uint32_t add_bf16x2(uint32_t a, uint32_t b) {
    uint32_t r; asm("add.rn.bf16x2 %0, %1, %2;" : "=r"(r) : "r"(a), "r"(b)); return r;
}
__device__ __forceinline__ uint32_t sub_bf16x2(uint32_t a, uint32_t b) {
    uint32_t r; asm("sub.rn.bf16x2 %0, %1, %2;" : "=r"(r) : "r"(a), "r"(b)); return r;
}
__device__ __forceinline__ uint32_t mul2_bf16x2(uint32_t a, uint32_t hi, uint32_t lo) {
    uint32_t r; asm("fma.rn.bf16x2 %0, %1, %2, %3;" : "=r"(r) : "r"(a), "r"(hi), "r"(mul_bf16x2(a, lo))); return r;
}
__device__ __forceinline__ float tanh_fast(float x) { float r; asm("tanh.approx.f32 %0, %1;" : "=f"(r) : "f"(x)); return r; }
__device__ __forceinline__ float gelu_tanh(float g) {
    float t = fmaf(g * g, 0.044715f * 0.7978845608f, 0.7978845608f) * g;
    float hg = 0.5f * g;
    return fmaf(hg, tanh_fast(t), hg);
}
__device__ __forceinline__ uint32_t geglu2(uint32_t g2, uint32_t u2) {
    return mul_bf16x2(pack_bf16(gelu_tanh(bf_lo(g2)), gelu_tanh(bf_hi(g2))), u2);
}
__device__ __forceinline__ float silu(float d) {
    float hd = 0.5f * d;
    return fmaf(hd, tanh_fast(hd), hd);
}
__device__ __forceinline__ float ex2_fast(float x) { float r; asm("ex2.approx.ftz.f32 %0, %1;" : "=f"(r) : "f"(x)); return r; }
__device__ __forceinline__ void unpack8(uint4 v, float (&f)[8]) {
    f[0] = bf_lo(v.x); f[1] = bf_hi(v.x); f[2] = bf_lo(v.y); f[3] = bf_hi(v.y);
    f[4] = bf_lo(v.z); f[5] = bf_hi(v.z); f[6] = bf_lo(v.w); f[7] = bf_hi(v.w);
}
template <int N> __device__ __forceinline__ void fence_regs(float (&d)[N]) {
#pragma unroll
    for (int i = 0; i < N; i++) asm volatile("" : "+f"(d[i]) :: "memory");
}

__device__ __forceinline__ float rcp_fast(float x) { float r; asm("rcp.approx.ftz.f32 %0, %1;" : "=f"(r) : "f"(x)); return r; }
__device__ __forceinline__ uint32_t max_bf16x2(uint32_t a, uint32_t b) {
    uint32_t r; asm("max.bf16x2 %0, %1, %2;" : "=r"(r) : "r"(a), "r"(b)); return r;
}
__device__ __forceinline__ uint4 ldsm4(uint32_t addr) {
    uint4 v;
    asm volatile("ldmatrix.sync.aligned.m8n8.x4.shared.b16 {%0,%1,%2,%3}, [%4];"
                 : "=r"(v.x), "=r"(v.y), "=r"(v.z), "=r"(v.w) : "r"(addr) : "memory");
    return v;
}
__device__ __forceinline__ uint4 ldsm4_t(uint32_t addr) {
    uint4 v;
    asm volatile("ldmatrix.sync.aligned.m8n8.x4.trans.shared.b16 {%0,%1,%2,%3}, [%4];"
                 : "=r"(v.x), "=r"(v.y), "=r"(v.z), "=r"(v.w) : "r"(addr) : "memory");
    return v;
}
__device__ __forceinline__ void mma_16816(float (&c)[4], uint32_t a0, uint32_t a1, uint32_t a2, uint32_t a3, uint32_t b0, uint32_t b1) {
    asm("mma.sync.aligned.m16n8k16.row.col.f32.bf16.bf16.f32 {%0,%1,%2,%3}, {%4,%5,%6,%7}, {%8,%9}, {%0,%1,%2,%3};"
        : "+f"(c[0]), "+f"(c[1]), "+f"(c[2]), "+f"(c[3]) : "r"(a0), "r"(a1), "r"(a2), "r"(a3), "r"(b0), "r"(b1));
}
__device__ __forceinline__ void mma_1688(float (&c)[4], uint32_t a0, uint32_t a1, uint32_t b0) {
    asm("mma.sync.aligned.m16n8k8.row.col.f32.bf16.bf16.f32 {%0,%1,%2,%3}, {%4,%5}, {%6}, {%0,%1,%2,%3};"
        : "+f"(c[0]), "+f"(c[1]), "+f"(c[2]), "+f"(c[3]) : "r"(a0), "r"(a1), "r"(b0));
}
__device__ __forceinline__ void qk_tile(float (&c)[4], const uint4& q0, const uint4& q1, const uint4& k, float init) {
    c[0] = c[1] = c[2] = c[3] = init;
    mma_16816(c, q0.x, q0.y, q0.z, q0.w, k.x, k.y);
    mma_16816(c, q1.x, q1.y, q1.z, q1.w, k.z, k.w);
}
__device__ __forceinline__ uint32_t scaled_logits(bool first, float a0, float a1, float b0, float b1) {
    return mul2_bf16x2(pack_bf16(first ? a0 : b0, first ? a1 : b1), 0x3e353e35u, 0x379e379eu);
}
template <typename T> __device__ __forceinline__ T uniform(T v) { return __shfl_sync(0xffffffffu, v, 0); }

__device__ __forceinline__ void attention(const CUtensorMap* maps, uint32_t base, uint32_t zero, int grp, int warp, int lane) {
    constexpr float LOG2E = 1.4426950408889634f;
    const int g = lane >> 2, t = lane & 3;
    const bool up0 = 2 * t > g, up1 = 2 * t + 1 > g;
    const uint32_t keep = (up0 ? 0x0000ffffu : 0u) | (up1 ? 0xffff0000u : 0u);
    const uint32_t buf = base + warp * 2 * ATT_SLOT, bar = base + AUX_OFF + warp * 16;
    const uint32_t qoff = (lane & 15) * 128 + (((lane >> 4) ^ (lane & 7)) << 4);
    const uint32_t koff = 2048 + (lane & 7) * 128 + (((lane >> 3) ^ (lane & 7)) << 4);
    const uint32_t rest_bar = base + AUX_OFF + 192;
    const int col = uniform(grp * 256), first = uniform((warp / 3 * 32 + warp % 3 * 11) * 16);
    const CUtensorMap* const mqk = reinterpret_cast<const CUtensorMap*>(uniform(reinterpret_cast<uint64_t>(maps)));
    const CUtensorMap *const mv = mqk + 1, *const mo = mqk + 2;
    const uint64_t pol = stream_policy();
    uint4 kp[2], vp[2];
    uint32_t l0[2], l1[2], m[2];
    float s[2][3][4];
    auto scores = [&](uint32_t st, int row) {
        const float before = (row & 1023) == 0 ? -5.656854e9f : 0.f;
#pragma unroll
        for (int h = 0; h < 2; h++) {
            const uint4 q0 = ldsm4(st + (qoff ^ (h * 64))), q1 = ldsm4(st + (qoff ^ (h * 64 + 32)));
            const uint4 k0 = ldsm4(st + (koff ^ (h * 64))), k1 = ldsm4(st + 1024 + (koff ^ (h * 64)));
            qk_tile(s[h][0], q0, q1, kp[h], before);
            qk_tile(s[h][1], q0, q1, k0, 0.f);
            qk_tile(s[h][2], q0, q1, k1, 0.f);
            kp[h] = k1;
        }
    };
    auto logits = [&]() {
#pragma unroll
        for (int h = 0; h < 2; h++) {
            l0[h] = scaled_logits(up0, s[h][0][0], s[h][1][2], s[h][1][0], s[h][2][2]);
            l1[h] = scaled_logits(up1, s[h][0][1], s[h][1][3], s[h][1][1], s[h][2][3]);
            m[h] = max_bf16x2(l0[h], l1[h]);
            m[h] = max_bf16x2(m[h], __shfl_xor_sync(0xffffffffu, m[h], 1));
        }
    };
    auto row_max = [&]() {
#pragma unroll
        for (int h = 0; h < 2; h++) m[h] = max_bf16x2(m[h], __shfl_xor_sync(0xffffffffu, m[h], 2));
    };
    auto next = [](uint32_t p) {
        return (0x80200400u >> (p >> 4 & 31) & 1) > (p >> 15 & 1) ? p + (64 << 16) + 0x8000 : (p + 16) & ~0x8800u;
    };
    auto exchange = [&](uint32_t st, uint32_t b, uint32_t po, uint32_t pv, uint32_t pq) {
        asm volatile("{\n.reg .pred e, p, q;\n"
            "fence.proxy.async.shared::cta;\n"
            "bar.warp.sync 0xffffffff;\n"
            "elect.sync _|e, 0xffffffff;\n"
            "setp.eq.and.b32 p, %12, 0, e;\n"
            "setp.lt.and.s32 q, %8, %13, e;\n"
            "@q mbarrier.arrive.expect_tx.shared::cta.b64 _, [%2], 6144;\n"
            "@q cp.async.bulk.tensor.3d.shared::cluster.global.mbarrier::complete_tx::bytes.L2::cache_hint [%0], [%3, {%6, %7, %14}], [%2], %15;\n"
            "@q cp.async.bulk.tensor.2d.shared::cluster.global.mbarrier::complete_tx::bytes.L2::cache_hint [%0 + 4096], [%4, {%8, %9}], [%2], %15;\n"
            "@e cp.async.bulk.wait_group.read 0;\n"
            "@p cp.async.bulk.tensor.2d.global.shared::cta.bulk_group [%5, {%10, %11}], [%1 + 6144];\n"
            "@e cp.async.bulk.commit_group;\n"
            "bar.warp.sync 0xffffffff;\n}"
            :: "r"(st), "r"(st ^ ATT_SLOT), "r"(b), "l"(mqk), "l"(mv), "l"(mo), "r"(pq >> 16), "r"(pq & 2047),
               "r"((pv >> 16) + 2 * DM), "r"(pv & 2047), "r"(po >> 16), "r"(po & 2047), "r"(po & 0x8000),
               "r"(col + 256 + 2 * DM), "r"(0), "l"(pol) : "memory");
    };
    auto publish = [&](auto pending, int part) {
        asm volatile("{\n.reg .pred e;\n.reg .u32 n;\n"
            "elect.sync _|e, 0xffffffff;\n"
            "cp.async.bulk.wait_group %2;\n"
            "@e atom.acq_rel.cta.shared.add.u32 n, [%1], 1;\n"
            "setp.eq.and.u32 e, n, 11, e;\n"
            "@e red.release.gpu.global.add.u32 [%0], 1;\n}"
            :: "l"(g_flags + F_O * 512 + part * 32), "r"(rest_bar + 8 + part * 4), "n"(pending.value) : "memory");
    };
    const unsigned epoch = __ldcg(g_epoch + blockIdx.x * 16) + 1;
    if (elect_one()) {
        mbar_init(bar, 1); mbar_init(bar + 8, 1);
        if (warp == 2) { mbar_init(rest_bar, 32); sts64f(rest_bar + 8, 0.f, 0.f); }
        asm volatile("fence.mbarrier_init.release.cluster;" ::: "memory");
        prefetch_map(mqk); prefetch_map(mv); prefetch_map(mo);
    }
    __syncthreads();
    if (elect_one()) {
        g_epoch[blockIdx.x * 16] = epoch;
        flag_wait(g_flags + F_QKV * 512 + grp * 32, epoch * CNT_QKV);
        fence_proxy_async();
        mbar_expect_tx(bar + 8, 8192);
        tma_3d(buf + ATT_SLOT, mqk, bar + 8, col, first, 0, pol);
        tma_2d(buf + ATT_SLOT + 4096, mv, bar + 8, col + 2 * DM, first - 16, pol);
        tma_2d(buf + ATT_SLOT + 6144, mv, bar + 8, col + DM, first - 16, pol);
        mbar_expect_tx(bar, 6144);
        tma_3d(buf, mqk, bar, col, first + 16, 0, pol);
        tma_2d(buf + 4096, mv, bar, col + 2 * DM, first, pol);
        if (warp == 0) TRACE(9);
    }
    __syncwarp();
    mbar_wait(bar + 8, 0);
#pragma unroll
    for (int h = 0; h < 2; h++) {
        kp[h] = ldsm4(buf + ATT_SLOT + 5120 + (koff ^ (h * 64)));
        vp[h] = ldsm4_t(buf + ATT_SLOT + 3072 + (koff ^ (h * 64)));
    }
    scores(buf + ATT_SLOT, first);
    uint32_t pm = 0x8000, p0 = col << 16 | first, p1 = p0 + 16, p2 = p0 + 32, p3 = p0 + 48;
    exchange(buf + ATT_SLOT, bar + 8, pm, p1, p2);
    logits();
    row_max();
    uint32_t st = buf, b = bar, cnt = 1;
    const uint32_t relay = warp == 2 ? 7 : 0;
    bool ready = false;
#pragma unroll 1
    while (p0 >> 16 < col + 256) {
        uint32_t pa[2], pb[2];
        if (!ready) mbar_wait(b, (cnt >> 1) & 1);
        uint4 v[2][2];
#pragma unroll
        for (int h = 0; h < 2; h++) {
            const float ma = -LOG2E * bf_lo(m[h]), mb = -LOG2E * bf_hi(m[h]);
            const float a0 = ex2_fast(fmaf(bf_lo(l0[h]), LOG2E, ma)), a1 = ex2_fast(fmaf(bf_lo(l1[h]), LOG2E, ma));
            const float b0 = ex2_fast(fmaf(bf_hi(l0[h]), LOG2E, mb)), b1 = ex2_fast(fmaf(bf_hi(l1[h]), LOG2E, mb));
            float sum[4] = {0.f, 0.f, 0.f, 0.f};
            mma_1688(sum, pack_bf16(a0, a1), pack_bf16(b0, b1), 0x3f803f80u);
            const float ra = rcp_fast(sum[0]), rb = rcp_fast(sum[2]);
            pa[h] = pack_bf16(a0 * ra, a1 * ra);
            pb[h] = pack_bf16(b0 * rb, b1 * rb);
        }
        scores(st, p1);
#pragma unroll
        for (int h = 0; h < 2; h++) {
            v[h][0] = ldsm4_t(st + 4096 + (qoff ^ (h * 64)));
            v[h][1] = ldsm4_t(st + 4096 + (qoff ^ (h * 64 + 32)));
        }
        if (cnt == relay) {
            flag_wait<true>(g_flags + F_QKV * 512 + 128 + grp * 32, epoch * CNT_QKV);
            fence_proxy_async();
            mbar_arrive(rest_bar);
        }
        if (cnt == 8) {
#pragma unroll 1
            for (int spins = 0; !__all_sync(0xffffffffu, mbar_try_wait(rest_bar, 0)) && spins < (1 << 17); spins++) {}
        }
        if (cnt == 37) publish(std::integral_constant<int, 1>(), 0);
        exchange(st, b, pm, p2, p3);
        pm = p0; p0 = p1; p1 = p2; p2 = p3; p3 = next(p3);
        logits();
        float o[2][4][4];
#pragma unroll
        for (int h = 0; h < 2; h++) {
            const uint32_t prev[4] = {vp[h].x, vp[h].y, vp[h].z, vp[h].w};
            const uint32_t own[8] = {v[h][0].x, v[h][0].y, v[h][0].z, v[h][0].w, v[h][1].x, v[h][1].y, v[h][1].z, v[h][1].w};
            const uint32_t a0 = pa[h] & keep, a1 = pa[h] & ~keep, a2 = pb[h] & keep, a3 = pb[h] & ~keep;
            const uint32_t z0 = pa[h] & zero, z1 = pb[h] & zero;
#pragma unroll
            for (int j = 0; j < 4; j++) {
                o[h][j][0] = o[h][j][1] = o[h][j][2] = o[h][j][3] = 0.f;
                mma_1688(o[h][j], a0, z0, prev[j]);
                mma_16816(o[h][j], a1, a2, z1, a3, own[2 * j], own[2 * j + 1]);
            }
            vp[h] = make_uint4(own[1], own[3], own[5], own[7]);
        }
        row_max();
        b ^= 8; cnt++;
        ready = mbar_test(b, (cnt >> 1) & 1);
#pragma unroll
        for (int h = 0; h < 2; h++) {
#pragma unroll
            for (int d = 0; d < 2; d++)
                asm volatile("stmatrix.sync.aligned.m8n8.x4.shared.b16 [%0], {%1,%2,%3,%4};"
                             :: "r"(st + 6144 + (qoff ^ (h * 64 + d * 32))),
                                "r"(pack_bf16(o[h][2 * d][0], o[h][2 * d][1])), "r"(pack_bf16(o[h][2 * d][2], o[h][2 * d][3])),
                                "r"(pack_bf16(o[h][2 * d + 1][0], o[h][2 * d + 1][1])),
                                "r"(pack_bf16(o[h][2 * d + 1][2], o[h][2 * d + 1][3])) : "memory");
        }
        st ^= ATT_SLOT;
    }
    exchange(st, b, pm, p0, p0);
    publish(std::integral_constant<int, 0>(), 1);
    if (threadIdx.x == 0) TRACE(10);
}

struct Params {
    CUtensorMap x, xn, wqkv, wg, wu, qk, v, o, a2, wo, wd, out;
    const __nv_bfloat16* px;
    uint32_t zero;
    uint32_t role[NCTA];
};

__device__ __forceinline__ bool tile_is_qkv(int nt) { return nt < 4 || (nt >= 8 && nt < 16); }
__device__ __forceinline__ int tile_index(int nt) { return nt < 4 ? nt + 8 : (nt < 8 ? nt - 4 : (nt < 16 ? nt - 8 : nt - 12)); }

__global__ void __cluster_dims__(2, 1, 1) __launch_bounds__(384, 1)
fused_kernel(const __grid_constant__ Params prm) {
    extern __shared__ __align__(1024) uint8_t smem_raw[];
    const uint32_t base = smem_u32(smem_raw) & ~1023u;
    const uint32_t bars = base + BAR_OFF;
    auto full1 = [&](int s) { return bars + s * 8; };
    auto empty1 = [&](int s) { return bars + 32 + s * 8; };
    auto full2 = [&](int s) { return bars + 64 + s * 8; };
    auto empty2 = [&](int s) { return bars + 128 + s * 8; };
    const uint32_t sig_bar = bars + 192, dep_bar = bars + 256, cs_bar = bars + 304, fold_bar = bars + 320, x_bar = bars + 336;
    const uint32_t colsum = bars + 512, stats = bars + 1536;
    auto stage2 = [&](int q) { return base + q * G2_STAGE_BYTES; };
    const uint32_t aux = base + AUX_OFF;

    const int warp = __shfl_sync(0xffffffffu, threadIdx.x >> 5, 0);
    const int lane = threadIdx.x & 31;
    const int rank = blockIdx.x & 1;
    const uint32_t role = prm.role[blockIdx.x];
    const int mblk = role & 15, nslot = role >> 4;

    if (blockIdx.x >= NGEMM) {
        if (threadIdx.x == 0) { TRACE_GT(0); TRACE(1); }
        attention(&prm.qk, (base + 2 * ATT_SLOT - 1) & ~(2u * ATT_SLOT - 1), prm.zero, blockIdx.x - NGEMM, warp, lane);
    } else if (warp >= 8) {
        unsigned* const flags = g_flags + mblk * 32;
        const CUtensorMap* const w0 = nslot < 4 ? &prm.wqkv : (rank ? &prm.wu : &prm.wg);
        const int w0_col = nslot < 4 ? 32 + nslot * 4 + rank * 2 : nslot * 2 - 8;
        if (elect_one()) {
            if (warp == 8) {
                TRACE_GT(0); TRACE(1);
                prefetch_map(&prm.x); prefetch_map(w0);
                for (int s = 0; s < G1_STAGES; s++) { mbar_init(full1(s), 1); mbar_init(empty1(s), 4); }
            } else if (warp == 9) {
                for (int s = 0; s < G2_STAGES; s++) { mbar_init(full2(s), 1); mbar_init(empty2(s), 4); }
            } else if (warp == 10) {
                for (int s = 0; s < 7; s++) mbar_init(sig_bar + s * 8, 8);
                mbar_init(fold_bar, 2); mbar_init(fold_bar + 8, 1); mbar_init(x_bar, 1);
            } else {
                for (int s = 0; s < 8; s++) mbar_init(dep_bar + s * 8, 1);
            }
            asm volatile("fence.mbarrier_init.release.cluster;" ::: "memory");
        }
        __syncwarp();
        asm volatile("barrier.cluster.arrive.relaxed.aligned;" ::: "memory");
        if (warp == 8 && lane == 0) {
            mbar_expect_tx(full1(0), G1_STAGE_BYTES);
            tma_2d(base, &prm.x, full1(0), 0, mblk * 128, stream_policy());
            prefetch_3d(w0, 0, w0_col, stream_policy());
            TRACE(15);
        }
        asm volatile("setmaxnreg.dec.sync.aligned.u32 %0;" :: "n"(AUX_REGS));
        asm volatile("barrier.cluster.wait.acquire.aligned;" ::: "memory");

        if (warp == 8) {
            if (elect_one()) { TRACE(2); tma_3d_mc(base + A_BYTES + rank * 16384, w0, full1(0), 0, w0_col, stream_policy()); }
            uint32_t ph = 1;
#pragma unroll 1
            for (int t = 0; t < G1_TILES; t++) {
                const int nt = t * 8 + nslot;
                const CUtensorMap* const mb = tile_is_qkv(nt) ? &prm.wqkv : (rank ? &prm.wu : &prm.wg);
                const int col = tile_is_qkv(nt) ? tile_index(nt) * 4 + rank * 2 : tile_index(nt) * 2;
                if (t == 1) { TRACE(14); mbar_wait_warp(dep_bar, 0); TRACE(3); }
#pragma unroll 1
                for (int k = t == 0; k < G1_KSTEPS; k++) {
                    const int s = k & 3;
                    if (t == 0 && k == G1_STAGES && elect_one()) {
                        prefetch_map(&prm.xn); prefetch_map(&prm.wqkv); prefetch_map(&prm.wu); prefetch_map(&prm.wg);
                        prefetch_map(&prm.a2); prefetch_map(&prm.wo); prefetch_map(&prm.wd); prefetch_map(&prm.out);
                    }
                    mbar_wait_warp(empty1(s), ph);
                    const uint32_t sa = base + s * G1_STAGE_BYTES;
                    load_stage1(sa, sa + A_BYTES + rank * 16384, full1(s), t ? &prm.xn : &prm.x, mb, k * 64, mblk * 128, col,
                                t & 3, stream_policy());
                    if (s == 3) ph ^= 1;
                }
            }
            if (elect_one()) {
                mbar_expect_tx(x_bar, 32768);
                tma_2d(aux, &prm.x, x_bar, nslot * 128, mblk * 128, stream_policy());
                tma_2d(aux + 16384, &prm.x, x_bar, nslot * 128 + 64, mblk * 128, stream_policy());
            }
            TRACE(4);
            mbar_wait_warp(dep_bar + 8, 0);
            TRACE(5);
            int q = 0; uint32_t ph2 = 1;
#pragma unroll 1
            for (int u = 0; u < G2_KSTEPS; u++) {
                if (u == G2_LATE || u == G2_DSTEPS || u == G2_LAST) {
                    TRACE(u == G2_LATE ? 6 : (u == G2_DSTEPS ? 32 : 40));
                    mbar_wait_warp(dep_bar + (u == G2_LATE ? 16 : (u == G2_DSTEPS ? 24 : 32)), 0);
                    TRACE(u == G2_LATE ? 7 : (u == G2_DSTEPS ? 33 : 41));
                }
                const uint32_t sa = stage2(q);
                const bool down = u < G2_DSTEPS;
                const int k = down ? u : (u & 3) * 4 + (u - G2_DSTEPS) / 4;
                mbar_wait_warp(u < G2_STAGES ? empty1((u * 2 + 1) / 3) : empty2(q), u < G2_STAGES ? ph : ph2);
                load_stage2(sa, sa + A_BYTES + rank * 8192, full2(q), &prm.a2, down ? &prm.wd : &prm.wo, (down ? DM : 0) + k * 64,
                            mblk * 64, nslot * 128 + rank * 64, k * 2, stream_policy());
                if (++q == G2_STAGES) { q = 0; ph2 ^= 1; }
            }
            TRACE(8);
        } else if (warp == 9) {
            if (lane == 0) {
                const unsigned epoch = __ldcg(g_epoch + blockIdx.x * 16 + 2) + 1;
                mbar_wait(sig_bar, 0);
                TRACE(11);
                flag_add(flags + F_LN * 512);
                TRACE(42);
                flag_wait(flags + F_LN * 512, epoch * CNT_LN);
                fence_proxy_async();
                mbar_arrive(dep_bar);
                mbar_expect_tx(fold_bar + 8, 1024);
                bulk_load(stats, g_stats + mblk * 128, 1024, fold_bar + 8);
                g_epoch[blockIdx.x * 16 + 2] = epoch;
                for (int p = nslot < 4 ? 2 : 1; p < 7; p++) {
                    mbar_wait(sig_bar + p * 8, 0);
                    if (p == 2) TRACE(37);
                    flag_add(p == 2 || p == 3 ? g_flags + F_QKV * 512 + (p * 4 - 8 + (nslot & 3)) * 32
                                              : flags + (p < 6 ? F_EARLY : F_LATE) * 512);
                    if (p == 2) TRACE(43);
                }
            }
        } else {
            const int w = warp - 10;
            const unsigned epoch = __ldcg(g_epoch + blockIdx.x * 16 + w) + 1;
            unsigned* const cs_flag = g_flags + F_CS * 512 + (nslot * 2 + w) * 32;
            mbar_wait(empty1(1), 0);
            if (elect_one()) {
                mbar_expect_tx(cs_bar + w * 8, 16384);
                tma_3d(aux + w * 16384, nslot < 4 ? &prm.wqkv : (w ? &prm.wu : &prm.wg), cs_bar + w * 8, 0, mblk * 64,
                       nslot < 4 ? 32 + nslot * 4 + w * 2 : nslot * 2 - 8, stream_policy());
            }
            float cs[8];
#pragma unroll
            for (int d = 0; d < 8; d++) cs[d] = 0.f;
            mbar_wait(cs_bar + w * 8, 0);
            const uint32_t wa = aux + w * 16384 + (lane & 8) * 1024 + (lane >> 4) * 128 + (((lane & 7) ^ (lane >> 4)) << 4);
#pragma unroll 1
            for (int i = 0; i < 8; i++) {
#pragma unroll
                for (int j = 0; j < 4; j++) {
                    float f[8];
                    unpack8(lds128((wa ^ (j * 32)) + i * 1024 + j * 256), f);
#pragma unroll
                    for (int d = 0; d < 8; d++) cs[d] += f[d];
                }
            }
#pragma unroll
            for (int d = 0; d < 8; d++) cs[d] += __shfl_xor_sync(0xffffffffu, cs[d], 16);
            *reinterpret_cast<float4*>(g_colsum + (nslot * 2 + w) * 2048 + mblk * 128 + (lane & 15) * 8 + (lane >> 4) * 4) =
                lane < 16 ? make_float4(cs[0], cs[1], cs[2], cs[3]) : make_float4(cs[4], cs[5], cs[6], cs[7]);
            __syncwarp();
            if (lane == 0) {
                if (w == 0) TRACE(34);
                flag_add(cs_flag);
                flag_wait(cs_flag, epoch * CNT_CS);
                fence_proxy_async();
                mbar_expect_tx(cs_bar + w * 8, 8192);
                bulk_load(aux + w * 16384, g_colsum + (nslot * 2 + w) * 2048, 8192, cs_bar + w * 8);
            }
            mbar_wait(cs_bar + w * 8, 1);
            float4 c = make_float4(0.f, 0.f, 0.f, 0.f);
#pragma unroll 8
            for (int m = 0; m < 16; m++) {
                const uint4 a = lds128(aux + w * 16384 + m * 512 + lane * 16);
                c.x += __uint_as_float(a.x); c.y += __uint_as_float(a.y); c.z += __uint_as_float(a.z); c.w += __uint_as_float(a.w);
            }
            const uint32_t ca = colsum + (w * 8 + (lane >> 2)) * 64 + (lane & 1) * 32 + (lane & 2) * 4;
            sts64f(ca, c.x, c.y);
            sts64f(ca + 16, c.z, c.w);
            __syncwarp();
            if (lane == 0) {
                mbar_arrive(fold_bar);
                g_epoch[blockIdx.x * 16 + w] = epoch;
                if (w == 0) {
                    TRACE(35);
                    flag_wait(flags + F_EARLY * 512, epoch * CNT_EARLY);
                    fence_proxy_async(); mbar_arrive(dep_bar + 8);
                    flag_wait(flags + F_LATE * 512, epoch * CNT_LATE);
                    fence_proxy_async(); mbar_arrive(dep_bar + 16);
                    flag_wait(g_flags + F_O * 512, epoch * CNT_O);
                    fence_proxy_async(); mbar_arrive(dep_bar + 24);
                    flag_wait(g_flags + F_O * 512 + 32, epoch * CNT_O);
                    fence_proxy_async(); mbar_arrive(dep_bar + 32);
                }
            }
        }
    } else {
        asm volatile("barrier.cluster.arrive.relaxed.aligned;" ::: "memory");
        asm volatile("setmaxnreg.inc.sync.aligned.u32 %0;" :: "n"(CONSUMER_REGS));
        const int wg = __shfl_sync(0xffffffffu, threadIdx.x >> 7, 0);
        const int cw = threadIdx.x >> 5;
        const int tid = threadIdx.x & 127;
        float acc[128];
        uint32_t pk[64];
#pragma unroll
        for (int i = 0; i < 64; i++) asm volatile("mov.b32 %0, 0;" : "=r"(pk[i]));
#pragma unroll
        for (int i = 0; i < 128; i++) asm volatile("mov.b32 %0, 0;" : "=f"(acc[i]));
        asm volatile("barrier.cluster.wait.acquire.aligned;" ::: "memory");

        const int orow = ((lane >> 2) & 1) * (SEQ / 2) + mblk * 64 + cw * 8 + (lane >> 3);
        __nv_bfloat16* optr = nullptr;
        auto release = [&](uint32_t bar) { if (tid < 2) mbar_arrive_cluster(bar, tid); };
        auto chunk_geglu = [&](int j) {
            const int c = j >> 1, h = j & 1;
            uint4 v;
            v.x = geglu2(pk[8 * c + h], pk[32 + 8 * c + h]);
            v.y = geglu2(pk[8 * c + 2 + h], pk[32 + 8 * c + 2 + h]);
            v.z = geglu2(pk[8 * c + 4 + h], pk[32 + 8 * c + 4 + h]);
            v.w = geglu2(pk[8 * c + 6 + h], pk[32 + 8 * c + 6 + h]);
            *reinterpret_cast<uint4*>(optr + h * 4 * K2 + c * 32) = v;
        };
        auto chunk_qkv = [&](int c) {
            *reinterpret_cast<uint4*>(optr + c * 32) = make_uint4(pk[8 * c], pk[8 * c + 2], pk[8 * c + 4], pk[8 * c + 6]);
            *reinterpret_cast<uint4*>(optr + 4 * NQKV + c * 32) = make_uint4(pk[8 * c + 1], pk[8 * c + 3], pk[8 * c + 5], pk[8 * c + 7]);
        };
        auto signal_stores = [&](int p) { __syncwarp(); if (lane == 0) mbar_arrive(sig_bar + p * 8); };

        auto chunk_ln = [&](int k) {
            const int row = mblk * 128 + nslot * 16 + cw * 2;
            float* const mo = reinterpret_cast<float*>(pk + 32);
            if (k == 0) {
                const uint4* xp = reinterpret_cast<const uint4*>(prm.px + (size_t)row * DM) + lane;
#pragma unroll
                for (int i = 0; i < 8; i++) {
                    const uint4 v = ldg_stream(xp + i * 32, stream_policy());
                    pk[4 * i] = v.x; pk[4 * i + 1] = v.y; pk[4 * i + 2] = v.z; pk[4 * i + 3] = v.w;
                }
            } else if (k >= LN_STEP && k < LN_STEP + 3) {
                if (k == LN_STEP) {
                    mo[0] = bf_lo(uniform(pk[0])); mo[1] = bf_lo(uniform(pk[16]));
                    mo[2] = mo[3] = mo[4] = mo[5] = 0.f;
                }
#pragma unroll
                for (int i = (k - LN_STEP) * 11; i < (k - LN_STEP) * 11 + 11 && i < 32; i++) {
                    const int r = i & 1;
                    const uint32_t w = pk[r * 16 + i / 2];
                    const float lo = bf_lo(w) - mo[r], hi = bf_hi(w) - mo[r];
                    mo[2 + r] += lo + hi;
                    mo[4 + r] = fmaf(hi, hi, fmaf(lo, lo, mo[4 + r]));
                }
            } else if (k == LN_STEP + 3) {
                const bool second = lane & 16;
                float m1 = (second ? mo[3] : mo[2]) + __shfl_xor_sync(0xffffffffu, second ? mo[2] : mo[3], 16);
                float m2 = (second ? mo[5] : mo[4]) + __shfl_xor_sync(0xffffffffu, second ? mo[4] : mo[5], 16);
#pragma unroll
                for (int o = 8; o > 0; o >>= 1) {
                    m1 += __shfl_xor_sync(0xffffffffu, m1, o);
                    m2 += __shfl_xor_sync(0xffffffffu, m2, o);
                }
                m1 *= 1.f / DM;
                const float var = fmaxf(fmaf(-m1, m1, m2 * (1.f / DM)), 0.f);
                const float mean = round_bf16((second ? mo[1] : mo[0]) + m1);
                const float inv = 1.f / round_bf16(sqrtf(round_bf16(round_bf16(var) + 1e-5f)));
                if ((lane & 15) == 0) g_stats[row + second] = make_float2(-mean, inv);
                const uint32_t split = pack_bf16(inv - round_bf16(inv), inv);
#pragma unroll
                for (int r = 0; r < 2; r++) {
                    const uint32_t f = __shfl_sync(0xffffffffu, split, r * 16);
                    pk[32 + 3 * r] = __byte_perm(__shfl_sync(0xffffffffu, __float_as_uint(mean), r * 16), 0, 0x3232);
                    pk[33 + 3 * r] = __byte_perm(f, 0, 0x3232);
                    pk[34 + 3 * r] = __byte_perm(f, 0, 0x1010);
                }
            } else if (k >= LN_STEP + 4 && k < LN_STEP + 7) {
#pragma unroll
                for (int i = (k - LN_STEP - 4) * 3; i < (k - LN_STEP - 3) * 3 && i < 8; i++) {
                    const uint32_t* n = pk + 32 + i / 4 * 3;
                    uint32_t o[4];
#pragma unroll
                    for (int j = 0; j < 4; j++) o[j] = mul2_bf16x2(sub_bf16x2(pk[i * 4 + j], n[0]), n[1], n[2]);
                    *reinterpret_cast<uint4*>(g_xn + (size_t)row * DM + i * 256 + lane * 8) = make_uint4(o[0], o[1], o[2], o[3]);
                }
                if (k == LN_STEP + 6) signal_stores(0);
            } else if (k == FOLD_STEP) {
                mbar_wait(fold_bar, 0);
#pragma unroll
                for (int j = 0; j < 16; j++) {
                    const uint4 c = lds128(colsum + j * 64 + (lane & 3) * 16);
                    pk[4 * j] = c.x; pk[4 * j + 1] = c.y; pk[4 * j + 2] = c.z; pk[4 * j + 3] = c.w;
                }
            }
        };

        bool gated = false;
#pragma unroll 1
        for (int t = 0; t < G1_TILES; t++) {
#pragma unroll
            for (int k = 0; k < G1_KSTEPS; k++) {
                const int s = k & 3;
                mbar_wait(full1(s), (k >> 2) & 1);
                if (t == 0 && k == 0 && threadIdx.x == 0) TRACE(12);
                if (TRACE_T >= 0 && t == TRACE_T && threadIdx.x == 0) TRACE(44 + k);
                if (wg == 1 && k == G1_KSTEPS - G1_SKEW) asm volatile("bar.sync 1, 256;" ::: "memory");
                const uint64_t da = desc_a(base + s * G1_STAGE_BYTES + wg * 8192);
                const uint64_t db = desc_b(base + s * G1_STAGE_BYTES + A_BYTES);
                wg_fence();
#pragma unroll
                for (int kk = 0; kk < 4; kk++) wgmma_n256(acc, da + kk * 2, db + kk * 128, (k | kk) != 0);
                wg_commit();
                if (wg == 0 && k == G1_KSTEPS - 1) asm volatile("bar.arrive 1, 256;" ::: "memory");
                wg_wait<1>();
                if (k > 0) release(empty1((k - 1) & 3));
                if (t == 0) chunk_ln(k);
                if (k >= 1 && k <= 8 && gated) {
                    chunk_geglu(k - 1);
                    if (k == 8) signal_stores(t == 1 ? 1 : t + 1);
                }
                if (t != 0 && !gated) {
                    if (k == 0) { chunk_qkv(0); chunk_qkv(1); }
                    if (k >= 6 && k <= 11) chunk_qkv(k - 4);
                    if ((k == 0 || k == 11) && t == 2) signal_stores(k ? 3 : 2);
                }
            }
            wg_wait<0>();
            fence_regs(acc);
            release(empty1(3));
            if (t == 0) {
                mbar_wait(fold_bar + 8, 0);
                const uint32_t sp = stats + (cw * 16 + (lane >> 2)) * 8;
                const float2 sa = lds64f(sp), sb = lds64f(sp + 64);
#pragma unroll
                for (int j = 0; j < 16; j++) {
                    const float c0 = __uint_as_float(pk[4 * j]), c1 = __uint_as_float(pk[4 * j + 1]);
                    const float c2 = __uint_as_float(pk[4 * j + 2]), c3 = __uint_as_float(pk[4 * j + 3]);
                    const float* a = acc + 8 * j;
                    pk[4 * j] = pack_bf16(fmaf(sa.x, c0, a[0]) * sa.y, fmaf(sa.x, c1, a[1]) * sa.y);
                    pk[4 * j + 1] = pack_bf16(fmaf(sb.x, c0, a[2]) * sb.y, fmaf(sb.x, c1, a[3]) * sb.y);
                    pk[4 * j + 2] = pack_bf16(fmaf(sa.x, c2, a[4]) * sa.y, fmaf(sa.x, c3, a[5]) * sa.y);
                    pk[4 * j + 3] = pack_bf16(fmaf(sb.x, c2, a[6]) * sb.y, fmaf(sb.x, c3, a[7]) * sb.y);
                }
            } else {
#pragma unroll
                for (int i = 0; i < 64; i++) pk[i] = pack_bf16(acc[2 * i], acc[2 * i + 1]);
            }
            const int nt = t * 8 + nslot;
            gated = !tile_is_qkv(nt);
            optr = !gated ? g_qkv + (size_t)orow * NQKV + tile_index(nt) * 256 + (lane & 3) * 8
                                : g_a2 + (size_t)orow * K2 + DM + tile_index(nt) * 128 + (lane & 3) * 8;
            if (tid == 0) TRACE(16 + wg * 8 + t);
        }

        float accd[64], accs[64];
#pragma unroll
        for (int i = 0; i < 64; i++) accd[i] = 0.f;
#pragma unroll
        for (int u = 0; u < 9; u++) {
            const int q = u % G2_STAGES;
            mbar_wait(full2(q), (u / G2_STAGES) & 1);
            const uint64_t da = desc_a(stage2(q) + wg * 8192), db = desc_b(stage2(q) + A_BYTES);
            wg_fence();
#pragma unroll
            for (int kk = 0; kk < 4; kk++) wgmma_n128(accd, da + kk * 2, db + kk * 128, (u | kk) != 0);
            wg_commit();
            wg_wait<1>();
            if (u > 0) release(empty2((u - 1) % G2_STAGES));
            if (u >= 1) { chunk_geglu(u - 1); if (u == 8) signal_stores(6); }
        }
        {
            int q = 9 % G2_STAGES, qp = 8 % G2_STAGES; uint32_t ph = (9 / G2_STAGES) & 1;
#pragma unroll 1
            for (int u = 9; u < G2_DSTEPS; u++) {
                mbar_wait(full2(q), ph);
                const uint64_t da = desc_a(stage2(q) + wg * 8192), db = desc_b(stage2(q) + A_BYTES);
                wg_fence();
#pragma unroll
                for (int kk = 0; kk < 4; kk++) wgmma_n128(accd, da + kk * 2, db + kk * 128, 1);
                wg_commit();
                wg_wait<1>();
                release(empty2(qp));
                qp = q;
                if (++q == G2_STAGES) { q = 0; ph ^= 1; }
            }
        }
        if (tid == 0) TRACE(16 + wg * 8 + 5);
#pragma unroll
        for (int i = 0; i < 64; i++) accs[i] = 0.f;
        uint32_t gk[32], xr[32];
        const uint32_t xs = aux + cw * 2048;
        const uint32_t xrow = xs + ((lane & 7) + ((lane >> 3) & 1) * 8) * 128;
        auto xaddr = [&](int j) { return xrow + (j >> 2) * 16384 + (((((j & 3) * 2) + (lane >> 4)) ^ (lane & 7)) << 4); };
#pragma unroll
        for (int u = G2_DSTEPS; u < G2_KSTEPS; u++) {
            const int q = u % G2_STAGES, v = u - G2_DSTEPS;
            mbar_wait(full2(q), (u / G2_STAGES) & 1);
            if (G2_SKEW > 0 && wg == 1 && u == G2_KSTEPS - G2_SKEW) asm volatile("bar.sync 1, 256;" ::: "memory");
            const uint64_t da = desc_a(stage2(q) + wg * 8192), db = desc_b(stage2(q) + A_BYTES);
            wg_fence();
#pragma unroll
            for (int kk = 0; kk < 4; kk++) wgmma_n128(accs, da + kk * 2, db + kk * 128, (v | kk) != 0);
            wg_commit();
            if (G2_SKEW > 0 && wg == 0 && u == G2_KSTEPS - 1) asm volatile("bar.arrive 1, 256;" ::: "memory");
            if (v >= 1 && v <= 8) {
#pragma unroll
                for (int i = 4 * (v - 1); i < 4 * v; i++) {
                    const uint32_t d2 = pack_bf16(accd[2 * i], accd[2 * i + 1]);
                    gk[i] = pack_bf16(silu(bf_lo(d2)), silu(bf_hi(d2)));
                }
            }
            if (v == 9) mbar_wait(x_bar, 0);
            if (v >= 9 && v <= 12) {
#pragma unroll
                for (int j = 2 * (v - 9); j < 2 * (v - 8); j++)
                    asm volatile("ldmatrix.sync.aligned.m8n8.x4.shared.b16 {%0,%1,%2,%3}, [%4];"
                                 : "=r"(xr[4 * j]), "=r"(xr[4 * j + 1]), "=r"(xr[4 * j + 2]), "=r"(xr[4 * j + 3])
                                 : "r"(xaddr(j)) : "memory");
            }
            wg_wait<1>();
            if (v == 0) fence_regs(accd);
            if (u - 1 + G2_STAGES < G2_KSTEPS) release(empty2((u - 1) % G2_STAGES));
        }
        wg_wait<0>();
        fence_regs(accs);
        if (tid == 0) TRACE(16 + wg * 8 + 6);
#pragma unroll
        for (int j = 0; j < 8; j++) {
            uint32_t r[4];
#pragma unroll
            for (int i = 0; i < 4; i++) {
                const int e = j * 4 + i;
                r[i] = add_bf16x2(xr[e], mul_bf16x2(pack_bf16(accs[2 * e], accs[2 * e + 1]), gk[e]));
            }
            asm volatile("stmatrix.sync.aligned.m8n8.x4.shared.b16 [%0], {%1,%2,%3,%4};"
                         :: "r"(xaddr(j)), "r"(r[0]), "r"(r[1]), "r"(r[2]), "r"(r[3]) : "memory");
            if (j == 3 || j == 7) {
                asm volatile("fence.proxy.async.shared::cta;" ::: "memory");
                __syncwarp();
                if (lane == 0) {
                    tma_store_2d(&prm.out, xs + (j >> 2) * 16384, nslot * 128 + (j >> 2) * 64, mblk * 128 + cw * 16);
                    asm volatile("cp.async.bulk.commit_group;" ::: "memory");
                }
            }
        }
        if (lane == 0) asm volatile("cp.async.bulk.wait_group.read 0;" ::: "memory");
        if (tid == 0) { TRACE(16 + wg * 8 + 7); if (wg == 1) TRACE_GT(13); }
    }
}

typedef CUresult (*EncodeFn)(CUtensorMap*, CUtensorMapDataType, cuuint32_t, void*, const cuuint64_t*, const cuuint64_t*,
                             const cuuint32_t*, const cuuint32_t*, CUtensorMapInterleave, CUtensorMapSwizzle,
                             CUtensorMapL2promotion, CUtensorMapFloatOOBfill);

void encode(EncodeFn fn, CUtensorMap* m, const void* ptr, int rank, const cuuint64_t* dims, const cuuint64_t* strides,
            const cuuint32_t* box) {
    const cuuint32_t es[5] = {1, 1, 1, 1, 1};
    fn(m, CU_TENSOR_MAP_DATA_TYPE_BFLOAT16, rank, const_cast<void*>(ptr), dims, strides, box, es,
       CU_TENSOR_MAP_INTERLEAVE_NONE, CU_TENSOR_MAP_SWIZZLE_128B, CU_TENSOR_MAP_L2_PROMOTION_L2_128B,
       CU_TENSOR_MAP_FLOAT_OOB_FILL_NONE);
}
void encode_2d(EncodeFn fn, CUtensorMap* m, const void* ptr, int cols, int box_rows) {
    const cuuint64_t dims[2] = {(cuuint64_t)cols, SEQ}, strides[1] = {(cuuint64_t)cols * 2};
    const cuuint32_t box[2] = {64, (cuuint32_t)box_rows};
    encode(fn, m, ptr, 2, dims, strides, box);
}
void encode_w1(EncodeFn fn, CUtensorMap* m, const void* ptr, int cols) {
    const cuuint64_t dims[3] = {64, DM, (cuuint64_t)cols / 64}, strides[2] = {(cuuint64_t)cols * 2, 128};
    const cuuint32_t box[3] = {64, 64, 2};
    encode(fn, m, ptr, 3, dims, strides, box);
}
void encode_qk(EncodeFn fn, CUtensorMap* m, const void* ptr) {
    const cuuint64_t dims[3] = {DM, SEQ, 3}, strides[2] = {NQKV * 2, DM * 2};
    const cuuint32_t box[3] = {64, 16, 2};
    encode(fn, m, ptr, 3, dims, strides, box);
}
void encode_a2(EncodeFn fn, CUtensorMap* m, const void* ptr) {
    const cuuint64_t dims[3] = {K2, 2, SEQ / 2}, strides[2] = {(cuuint64_t)SEQ * K2, K2 * 2};
    const cuuint32_t box[3] = {64, 2, 64};
    encode(fn, m, ptr, 3, dims, strides, box);
}
void encode_w2(EncodeFn fn, CUtensorMap* m, const void* ptr, int rows) {
    const cuuint64_t rb = DM * 2;
    const cuuint64_t dims[5] = {DM, 2, 4, 4, (cuuint64_t)rows / 32}, strides[4] = {rb, 8 * rb, 2 * rb, 32 * rb};
    const cuuint32_t box[5] = {64, 2, 4, 4, 2};
    encode(fn, m, ptr, 5, dims, strides, box);
}

}

extern "C" void kernel_launch(void* const* d_in, const int* in_sizes, int n_in, void* d_out, int out_size) {
    (void)in_sizes; (void)n_in; (void)out_size;
    static EncodeFn fn = nullptr;
    static void *p_xn = nullptr, *p_qkv = nullptr, *p_a2 = nullptr;
    if (!fn) {
        cudaDriverEntryPointQueryResult st;
        cudaGetDriverEntryPoint("cuTensorMapEncodeTiled", (void**)&fn, cudaEnableDefault, &st);
        cudaGetSymbolAddress(&p_xn, g_xn);
        cudaGetSymbolAddress(&p_qkv, g_qkv);
        cudaGetSymbolAddress(&p_a2, g_a2);
        cudaFuncSetAttribute(fused_kernel, cudaFuncAttributeMaxDynamicSharedMemorySize, SMEM_BYTES);
    }
    Params prm;
    encode_2d(fn, &prm.x, d_in[0], DM, 128);
    encode_2d(fn, &prm.xn, p_xn, DM, 128);
    encode_w1(fn, &prm.wqkv, d_in[1], NQKV);
    encode_w1(fn, &prm.wg, d_in[4], DF);
    encode_w1(fn, &prm.wu, d_in[5], DF);
    encode_qk(fn, &prm.qk, p_qkv);
    encode_2d(fn, &prm.v, p_qkv, NQKV, 16);
    encode_2d(fn, &prm.o, p_a2, K2, 16);
    encode_a2(fn, &prm.a2, p_a2);
    encode_w2(fn, &prm.wo, d_in[2], DM);
    encode_w2(fn, &prm.wd, d_in[6], DF);
    encode_2d(fn, &prm.out, d_out, DM, 16);
    prm.px = (const __nv_bfloat16*)d_in[0];
    prm.zero = 0;
    for (int b = 0; b < NCTA; b++) {
        const int c = b / 2;
        prm.role[b] = (c < 4 ? 32 + c * 8 : (c < 36 ? c - 4 : 33 + (c - 36) / 7 * 8 + (c - 36) % 7)) * 2 + b % 2;
    }
    fused_kernel<<<NCTA, 384, SMEM_BYTES>>>(prm);
}
```

```cpp
#include <cuda_runtime.h>
#include <cuda_bf16.h>
#include <cuda.h>
#include <stdint.h>
#include <type_traits>

#define LNS 3
#define FS 15
#define CSAT empty1(3)
#define SK0 3

namespace {

constexpr int SEQ = 2048, DM = 1024, DF = 3584, K2 = DM + DF, NQKV = 3 * DM;
constexpr int NGEMM = 128, NCTA = 132;
constexpr int G1_STAGES = 4, G1_STAGE_BYTES = 49152, G1_KSTEPS = 16, G1_TILES = 5;
constexpr int G2_STAGES = 6, G2_STAGE_BYTES = 32768, G2_KSTEPS = 72, G2_LATE = 40, G2_DSTEPS = 56, G2_LAST = 68;
constexpr int LN_STEP = LNS, FOLD_STEP = FS;
constexpr int A_BYTES = 16384;
constexpr int AUX_OFF = G1_STAGES * G1_STAGE_BYTES;
constexpr int BAR_OFF = AUX_OFF + 32768;
constexpr int SMEM_BYTES = BAR_OFF + 2816;
constexpr int G1_SKEW = 2, G2_SKEW = 2;
constexpr int CONSUMER_REGS = 224, AUX_REGS = 56;
constexpr int ATT_SLOT = 8192;

enum { F_LN = 0, F_QKV = 1, F_EARLY = 2, F_LATE = 3, F_O = 4 };
constexpr unsigned CNT_LN = 8, CNT_QKV = 32, CNT_EARLY = 20, CNT_LATE = 8, CNT_O = 4;

__device__ __align__(1024) __nv_bfloat16 g_xn[SEQ * DM];
__device__ __align__(1024) __nv_bfloat16 g_qkv[SEQ * NQKV];
__device__ __align__(1024) __nv_bfloat16 g_a2[SEQ * K2];
__device__ __align__(128) float2 g_stats[SEQ];
__device__ __align__(128) float g_colsum[16 * 1024];
__device__ __align__(128) unsigned g_flags[5 * 16 * 32];
__device__ __align__(128) unsigned g_epoch[NCTA * 16];

#define TRACE(slot) do {} while (0)
#define TRACE_GT(slot) do {} while (0)
#define TRACE_S(slot, v, want) do {} while (0)
#define TRACE_DUMP() do {} while (0)
#define TRACE_CLEAR() do {} while (0)
#define TRACE_STEP(t, k, i) do {} while (0)

__device__ __forceinline__ uint32_t smem_u32(const void* p) { return (uint32_t)__cvta_generic_to_shared(p); }
__device__ __forceinline__ void mbar_init(uint32_t bar, uint32_t cnt) {
    asm volatile("mbarrier.init.shared::cta.b64 [%0], %1;" :: "r"(bar), "r"(cnt) : "memory");
}
__device__ __forceinline__ void mbar_expect_tx(uint32_t bar, uint32_t bytes) {
    asm volatile("mbarrier.arrive.expect_tx.shared::cta.b64 _, [%0], %1;" :: "r"(bar), "r"(bytes) : "memory");
}
__device__ __forceinline__ void mbar_arrive(uint32_t bar) {
    asm volatile("mbarrier.arrive.shared::cta.b64 _, [%0];" :: "r"(bar) : "memory");
}
__device__ __forceinline__ void mbar_arrive_cluster(uint32_t bar, uint32_t cta) {
    asm volatile("{\n.reg .b32 ra;\nmapa.shared::cluster.u32 ra, %0, %1;\nmbarrier.arrive.shared::cluster.b64 _, [ra];\n}"
                 :: "r"(bar), "r"(cta) : "memory");
}
__device__ __forceinline__ bool mbar_try_wait(uint32_t bar, uint32_t parity) {
    uint32_t ok;
    asm volatile("{\n.reg .pred p;\nmbarrier.try_wait.parity.shared::cta.b64 p, [%1], %2;\nselp.u32 %0, 1, 0, p;\n}"
                 : "=r"(ok) : "r"(bar), "r"(parity) : "memory");
    return ok;
}
__device__ __forceinline__ bool mbar_test(uint32_t bar, uint32_t parity) {
    uint32_t ok;
    asm volatile("{\n.reg .pred p;\nmbarrier.test_wait.parity.shared::cta.b64 p, [%1], %2;\nselp.u32 %0, 1, 0, p;\n}"
                 : "=r"(ok) : "r"(bar), "r"(parity) : "memory");
    return ok;
}
__device__ __forceinline__ void mbar_wait(uint32_t bar, uint32_t parity) {
#pragma unroll 1
    for (int spins = 0; !mbar_try_wait(bar, parity) && spins < (1 << 17); spins++) {}
}
template <bool WARP = false> __device__ __forceinline__ void flag_wait(const unsigned* p, unsigned target) {
#pragma unroll 1
    for (int spins = 0; spins < (1 << 19); spins++) {
        unsigned v;
        asm volatile("ld.acquire.gpu.global.u32 %0, [%1];" : "=r"(v) : "l"(p) : "memory");
        if (WARP ? __all_sync(0xffffffffu, (int)(v - target) >= 0) : (int)(v - target) >= 0) break;
        __nanosleep(64);
    }
}
__device__ __forceinline__ void mbar_wait_warp(uint32_t bar, uint32_t parity) {
#pragma unroll 1
    for (int spins = 0; !__all_sync(0xffffffffu, mbar_try_wait(bar, parity)) && spins < (1 << 17); spins++) {}
}
__device__ __forceinline__ void flag_add(unsigned* p) {
    asm volatile("red.release.gpu.global.add.u32 [%0], 1;" :: "l"(p) : "memory");
}
__device__ __forceinline__ bool elect_one() {
    uint32_t ok;
    asm volatile("{\n.reg .pred p;\nelect.sync _|p, 0xffffffff;\nselp.u32 %0, 1, 0, p;\n}" : "=r"(ok));
    return ok;
}
__device__ __forceinline__ void fence_proxy_async() { asm volatile("fence.proxy.async.global;" ::: "memory"); }
__device__ __forceinline__ uint4 lds128(uint32_t addr) {
    uint4 v;
    asm volatile("ld.shared.v4.u32 {%0,%1,%2,%3}, [%4];" : "=r"(v.x), "=r"(v.y), "=r"(v.z), "=r"(v.w) : "r"(addr) : "memory");
    return v;
}
__device__ __forceinline__ float2 lds64f(uint32_t addr) {
    float2 v;
    asm volatile("ld.shared.v2.f32 {%0,%1}, [%2];" : "=f"(v.x), "=f"(v.y) : "r"(addr) : "memory");
    return v;
}
__device__ __forceinline__ void sts128(uint32_t addr, uint4 v) {
    asm volatile("st.shared.v4.u32 [%0], {%1,%2,%3,%4};" :: "r"(addr), "r"(v.x), "r"(v.y), "r"(v.z), "r"(v.w) : "memory");
}
__device__ __forceinline__ void sts64f(uint32_t addr, float a, float b) {
    asm volatile("st.shared.v2.f32 [%0], {%1,%2};" :: "r"(addr), "f"(a), "f"(b) : "memory");
}

__device__ __forceinline__ uint64_t stream_policy() {
    uint64_t p;
    asm("createpolicy.fractional.L2::evict_first.b64 %0, 1.0;" : "=l"(p));
    return p;
}
__device__ __forceinline__ void tma_2d(uint32_t dst, const CUtensorMap* m, uint32_t bar, int c0, int c1, uint64_t pol) {
    asm volatile("cp.async.bulk.tensor.2d.shared::cluster.global.mbarrier::complete_tx::bytes.L2::cache_hint"
                 " [%0], [%1, {%3, %4}], [%2], %5;"
                 :: "r"(dst), "l"(m), "r"(bar), "r"(c0), "r"(c1), "l"(pol) : "memory");
}
__device__ __forceinline__ void tma_3d(uint32_t dst, const CUtensorMap* m, uint32_t bar, int c0, int c1, int c2, uint64_t pol) {
    asm volatile("cp.async.bulk.tensor.3d.shared::cluster.global.mbarrier::complete_tx::bytes.L2::cache_hint"
                 " [%0], [%1, {%3, %4, %5}], [%2], %6;"
                 :: "r"(dst), "l"(m), "r"(bar), "r"(c0), "r"(c1), "r"(c2), "l"(pol) : "memory");
}
__device__ __forceinline__ void tma_3d_mc(uint32_t dst, const CUtensorMap* m, uint32_t bar, int c1, int c2, uint64_t pol) {
    asm volatile("cp.async.bulk.tensor.3d.shared::cluster.global.mbarrier::complete_tx::bytes.multicast::cluster.L2::cache_hint"
                 " [%0], [%1, {%3, %4, %5}], [%2], %6, %7;"
                 :: "r"(dst), "l"(m), "r"(bar), "r"(0), "r"(c1), "r"(c2), "h"((uint16_t)3), "l"(pol) : "memory");
}
__device__ __forceinline__ void load_stage1(uint32_t dst, uint32_t dst_b, uint32_t bar, const CUtensorMap* ma, const CUtensorMap* mb,
                                            int k, int row, int col, int keep_a, uint64_t pol) {
    asm volatile("{\n.reg .pred e, p, q;\nelect.sync _|e, 0xffffffff;\nsetp.ne.and.b32 p|q, %8, 0, e;\n"
        "@p cp.async.bulk.tensor.2d.shared::cluster.global.mbarrier::complete_tx::bytes [%0], [%3, {%5, %6}], [%2];\n"
        "@q cp.async.bulk.tensor.2d.shared::cluster.global.mbarrier::complete_tx::bytes.L2::cache_hint [%0], [%3, {%5, %6}], [%2], %9;\n"
        "@e cp.async.bulk.tensor.3d.shared::cluster.global.mbarrier::complete_tx::bytes.multicast::cluster.L2::cache_hint"
        " [%1], [%4, {%10, %5, %7}], [%2], %11, %9;\n"
        "@e mbarrier.arrive.expect_tx.shared::cta.b64 _, [%2], %12;\n}"
        :: "r"(dst), "r"(dst_b), "r"(bar), "l"(ma), "l"(mb), "r"(k), "r"(row), "r"(col), "r"(keep_a), "l"(pol), "r"(0),
           "h"((uint16_t)3), "n"(G1_STAGE_BYTES) : "memory");
}
__device__ __forceinline__ void load_stage2(uint32_t dst, uint32_t dst_b, uint32_t bar, const CUtensorMap* ma, const CUtensorMap* mb,
                                            int ka, int row, int col, int kb, uint64_t pol) {
    asm volatile("{\n.reg .pred e;\nelect.sync _|e, 0xffffffff;\n"
        "@e cp.async.bulk.tensor.3d.shared::cluster.global.mbarrier::complete_tx::bytes.L2::cache_hint [%0], [%3, {%5, %10, %6}], [%2], %9;\n"
        "@e cp.async.bulk.tensor.5d.shared::cluster.global.mbarrier::complete_tx::bytes.multicast::cluster.L2::cache_hint"
        " [%1], [%4, {%7, %10, %10, %10, %8}], [%2], %11, %9;\n"
        "@e mbarrier.arrive.expect_tx.shared::cta.b64 _, [%2], %12;\n}"
        :: "r"(dst), "r"(dst_b), "r"(bar), "l"(ma), "l"(mb), "r"(ka), "r"(row), "r"(col), "r"(kb), "l"(pol), "r"(0),
           "h"((uint16_t)3), "n"(G2_STAGE_BYTES) : "memory");
}
__device__ __forceinline__ void tma_store_2d(const CUtensorMap* m, uint32_t src, int c0, int c1) {
    asm volatile("cp.async.bulk.tensor.2d.global.shared::cta.bulk_group [%0, {%2, %3}], [%1];"
                 :: "l"(m), "r"(src), "r"(c0), "r"(c1) : "memory");
}
__device__ __forceinline__ uint4 ldg_stream(const void* p, uint64_t pol) {
    uint4 v;
    asm volatile("ld.global.nc.L1::no_allocate.L2::cache_hint.v4.u32 {%0,%1,%2,%3}, [%4], %5;"
                 : "=r"(v.x), "=r"(v.y), "=r"(v.z), "=r"(v.w) : "l"(p), "l"(pol));
    return v;
}
__device__ __forceinline__ void st_tagged(void* p, float a, float b, uint32_t tag) {
    asm volatile("st.relaxed.gpu.global.v2.b32 [%0], {%1,%2};"
                 :: "l"(p), "r"((__float_as_uint(a) & ~3u) | tag), "r"((__float_as_uint(b) & ~3u) | tag) : "memory");
}
__device__ __forceinline__ bool untagged(const uint4& v, uint32_t tag) {
    return ((v.x ^ tag) | (v.y ^ tag) | (v.z ^ tag) | (v.w ^ tag)) & 3;
}
__device__ __forceinline__ uint4 ld_relaxed(const void* p) {
    uint4 v;
    asm volatile("ld.relaxed.gpu.global.v4.b32 {%0,%1,%2,%3}, [%4];" : "=r"(v.x), "=r"(v.y), "=r"(v.z), "=r"(v.w) : "l"(p) : "memory");
    return v;
}
__device__ __forceinline__ void prefetch_3d(const CUtensorMap* m, int c1, int c2, uint64_t pol) {
    asm volatile("cp.async.bulk.prefetch.tensor.3d.L2.global.L2::cache_hint [%0, {%1, %2, %3}], %4;"
                 :: "l"(m), "r"(0), "r"(c1), "r"(c2), "l"(pol) : "memory");
}
__device__ __forceinline__ void prefetch_map(const CUtensorMap* m) {
    asm volatile("prefetch.tensormap [%0];" :: "l"(m) : "memory");
}
template <int N> __device__ __forceinline__ void wg_wait() { asm volatile("wgmma.wait_group.sync.aligned %0;" :: "n"(N) : "memory"); }

__device__ __forceinline__ uint32_t desc_a(uint32_t addr) { return (addr & 0x3FFFF) >> 4 | 1 << 16; }
__device__ __forceinline__ uint32_t desc_b(uint32_t addr) { return (addr & 0x3FFFF) >> 4 | 512 << 16; }

#define R8(d, o) "+f"(d[o]), "+f"(d[o+1]), "+f"(d[o+2]), "+f"(d[o+3]), "+f"(d[o+4]), "+f"(d[o+5]), "+f"(d[o+6]), "+f"(d[o+7])
#define R32(d, o) R8(d, o), R8(d, o+8), R8(d, o+16), R8(d, o+24)
#define R64(d, o) R32(d, o), R32(d, o+32)
#define ACC64 \
    "{%0,%1,%2,%3,%4,%5,%6,%7,%8,%9,%10,%11,%12,%13,%14,%15,%16,%17,%18,%19,%20,%21,%22,%23,%24,%25,%26,%27,%28,%29,%30,%31," \
    "%32,%33,%34,%35,%36,%37,%38,%39,%40,%41,%42,%43,%44,%45,%46,%47,%48,%49,%50,%51,%52,%53,%54,%55,%56,%57,%58,%59,%60,%61,%62,%63}"
#define ACC128 \
    "{%0,%1,%2,%3,%4,%5,%6,%7,%8,%9,%10,%11,%12,%13,%14,%15,%16,%17,%18,%19,%20,%21,%22,%23,%24,%25,%26,%27,%28,%29,%30,%31," \
    "%32,%33,%34,%35,%36,%37,%38,%39,%40,%41,%42,%43,%44,%45,%46,%47,%48,%49,%50,%51,%52,%53,%54,%55,%56,%57,%58,%59,%60,%61,%62,%63," \
    "%64,%65,%66,%67,%68,%69,%70,%71,%72,%73,%74,%75,%76,%77,%78,%79,%80,%81,%82,%83,%84,%85,%86,%87,%88,%89,%90,%91,%92,%93,%94,%95," \
    "%96,%97,%98,%99,%100,%101,%102,%103,%104,%105,%106,%107,%108,%109,%110,%111,%112,%113,%114,%115,%116,%117,%118,%119,%120,%121,%122,%123,%124,%125,%126,%127}"
#define MMA_K16(shape, acc, keep) \
    "mov.b64 da, {la, 0x40000040};\nmov.b64 db, {lb, 0x40000040};\n" \
    "wgmma.mma_async.sync.aligned." shape ".f32.bf16.bf16 " acc ", da, db, " keep ", 1, 1, 0, 1;\n" \
    "add.u32 la, la, 2;\nadd.u32 lb, lb, 128;\n"
#define MMA_STEP(shape, acc, a, b, off, keep) \
    "{\n.reg .pred p, q;\n.reg .b32 la, lb;\n.reg .b64 da, db;\nsetp.ne.b32 p, " keep ", 0;\nsetp.eq.b32 q, 0, 0;\n" \
    "add.u32 la, " a ", " off ";\nadd.u32 lb, " b ", " off ";\nwgmma.fence.sync.aligned;\n" \
    MMA_K16(shape, acc, "p") MMA_K16(shape, acc, "q") MMA_K16(shape, acc, "q") MMA_K16(shape, acc, "q") \
    "wgmma.commit_group.sync.aligned;\n}"

__device__ __forceinline__ void mma_step(float (&d)[128], uint32_t da, uint32_t db, uint32_t off, int keep) {
    asm volatile(MMA_STEP("m64n256k16", ACC128, "%128", "%129", "%130", "%131")
                 : R64(d, 0), R64(d, 64) : "r"(da), "r"(db), "r"(off), "r"(keep) : "memory");
}
__device__ __forceinline__ void mma_step(float (&d)[64], uint32_t da, uint32_t db, uint32_t off, int keep) {
    asm volatile(MMA_STEP("m64n128k16", ACC64, "%64", "%65", "%66", "%67")
                 : R64(d, 0) : "r"(da), "r"(db), "r"(off), "r"(keep) : "memory");
}

__device__ __forceinline__ uint32_t pack_bf16(float lo, float hi) {
    uint32_t r; asm("cvt.rn.bf16x2.f32 %0, %1, %2;" : "=r"(r) : "f"(hi), "f"(lo)); return r;
}
__device__ __forceinline__ float bf_lo(uint32_t v) { return __uint_as_float(v << 16); }
__device__ __forceinline__ float bf_hi(uint32_t v) { return __uint_as_float(v & 0xffff0000u); }
__device__ __forceinline__ float round_bf16(float v) { return bf_lo(pack_bf16(v, 0.f)); }
__device__ __forceinline__ uint32_t mul_bf16x2(uint32_t a, uint32_t b) {
    uint32_t r; asm("mul.rn.bf16x2 %0, %1, %2;" : "=r"(r) : "r"(a), "r"(b)); return r;
}
__device__ __forceinline__ uint32_t add_bf16x2(uint32_t a, uint32_t b) {
    uint32_t r; asm("add.rn.bf16x2 %0, %1, %2;" : "=r"(r) : "r"(a), "r"(b)); return r;
}
__device__ __forceinline__ uint32_t sub_bf16x2(uint32_t a, uint32_t b) {
    uint32_t r; asm("sub.rn.bf16x2 %0, %1, %2;" : "=r"(r) : "r"(a), "r"(b)); return r;
}
__device__ __forceinline__ uint32_t mul2_bf16x2(uint32_t a, uint32_t hi, uint32_t lo) {
    uint32_t r; asm("fma.rn.bf16x2 %0, %1, %2, %3;" : "=r"(r) : "r"(a), "r"(hi), "r"(mul_bf16x2(a, lo))); return r;
}
__device__ __forceinline__ float tanh_fast(float x) { float r; asm("tanh.approx.f32 %0, %1;" : "=f"(r) : "f"(x)); return r; }
__device__ __forceinline__ float gelu_tanh(float g) {
    float t = fmaf(g * g, 0.044715f * 0.7978845608f, 0.7978845608f) * g;
    float hg = 0.5f * g;
    return fmaf(hg, tanh_fast(t), hg);
}
__device__ __forceinline__ uint32_t geglu2(uint32_t g2, uint32_t u2) {
    return mul_bf16x2(pack_bf16(gelu_tanh(bf_lo(g2)), gelu_tanh(bf_hi(g2))), u2);
}
__device__ __forceinline__ float silu(float d) {
    float hd = 0.5f * d;
    return fmaf(hd, tanh_fast(hd), hd);
}
__device__ __forceinline__ float ex2_fast(float x) { float r; asm("ex2.approx.ftz.f32 %0, %1;" : "=f"(r) : "f"(x)); return r; }
__device__ __forceinline__ void unpack8(uint4 v, float (&f)[8]) {
    f[0] = bf_lo(v.x); f[1] = bf_hi(v.x); f[2] = bf_lo(v.y); f[3] = bf_hi(v.y);
    f[4] = bf_lo(v.z); f[5] = bf_hi(v.z); f[6] = bf_lo(v.w); f[7] = bf_hi(v.w);
}
template <int N> __device__ __forceinline__ void fence_regs(float (&d)[N]) {
#pragma unroll
    for (int i = 0; i < N; i++) asm volatile("" : "+f"(d[i]) :: "memory");
}

__device__ __forceinline__ float rcp_fast(float x) { float r; asm("rcp.approx.ftz.f32 %0, %1;" : "=f"(r) : "f"(x)); return r; }
__device__ __forceinline__ float sqrt_fast(float x) { float r; asm("sqrt.approx.ftz.f32 %0, %1;" : "=f"(r) : "f"(x)); return r; }
__device__ __forceinline__ uint32_t max_bf16x2(uint32_t a, uint32_t b) {
    uint32_t r; asm("max.bf16x2 %0, %1, %2;" : "=r"(r) : "r"(a), "r"(b)); return r;
}
__device__ __forceinline__ uint4 ldsm4(uint32_t addr) {
    uint4 v;
    asm volatile("ldmatrix.sync.aligned.m8n8.x4.shared.b16 {%0,%1,%2,%3}, [%4];"
                 : "=r"(v.x), "=r"(v.y), "=r"(v.z), "=r"(v.w) : "r"(addr) : "memory");
    return v;
}
__device__ __forceinline__ uint4 ldsm4_t(uint32_t addr) {
    uint4 v;
    asm volatile("ldmatrix.sync.aligned.m8n8.x4.trans.shared.b16 {%0,%1,%2,%3}, [%4];"
                 : "=r"(v.x), "=r"(v.y), "=r"(v.z), "=r"(v.w) : "r"(addr) : "memory");
    return v;
}
__device__ __forceinline__ void mma_16816(float (&c)[4], uint32_t a0, uint32_t a1, uint32_t a2, uint32_t a3, uint32_t b0, uint32_t b1) {
    asm("mma.sync.aligned.m16n8k16.row.col.f32.bf16.bf16.f32 {%0,%1,%2,%3}, {%4,%5,%6,%7}, {%8,%9}, {%0,%1,%2,%3};"
        : "+f"(c[0]), "+f"(c[1]), "+f"(c[2]), "+f"(c[3]) : "r"(a0), "r"(a1), "r"(a2), "r"(a3), "r"(b0), "r"(b1));
}
__device__ __forceinline__ void mma_1688(float (&c)[4], uint32_t a0, uint32_t a1, uint32_t b0) {
    asm("mma.sync.aligned.m16n8k8.row.col.f32.bf16.bf16.f32 {%0,%1,%2,%3}, {%4,%5}, {%6}, {%0,%1,%2,%3};"
        : "+f"(c[0]), "+f"(c[1]), "+f"(c[2]), "+f"(c[3]) : "r"(a0), "r"(a1), "r"(b0));
}
__device__ __forceinline__ void qk_tile(float (&c)[4], const uint4& q0, const uint4& q1, const uint4& k, float init) {
    c[0] = c[1] = c[2] = c[3] = init;
    mma_16816(c, q0.x, q0.y, q0.z, q0.w, k.x, k.y);
    mma_16816(c, q1.x, q1.y, q1.z, q1.w, k.z, k.w);
}
__device__ __forceinline__ uint32_t scaled_logits(bool first, float a0, float a1, float b0, float b1) {
    return mul2_bf16x2(pack_bf16(first ? a0 : b0, first ? a1 : b1), 0x3e353e35u, 0x379e379eu);
}
template <typename T> __device__ __forceinline__ T uniform(T v) { return __shfl_sync(0xffffffffu, v, 0); }

__device__ __forceinline__ void attention(const CUtensorMap* maps, uint32_t base, uint32_t zero, int grp, int warp, int lane) {
    constexpr float LOG2E = 1.4426950408889634f;
    const int g = lane >> 2, t = lane & 3;
    const bool up0 = 2 * t > g, up1 = 2 * t + 1 > g;
    const uint32_t keep = (up0 ? 0x0000ffffu : 0u) | (up1 ? 0xffff0000u : 0u);
    const uint32_t buf = base + warp * 2 * ATT_SLOT, bar = base + AUX_OFF + warp * 16;
    const uint32_t qoff = (lane & 15) * 128 + (((lane >> 4) ^ (lane & 7)) << 4);
    const uint32_t koff = 2048 + (lane & 7) * 128 + (((lane >> 3) ^ (lane & 7)) << 4);
    const uint32_t rest_bar = base + AUX_OFF + 192;
    const int col = uniform(grp * 256), first = uniform((warp / 3 * 32 + warp % 3 * 11) * 16);
    const CUtensorMap* const mqk = reinterpret_cast<const CUtensorMap*>(uniform(reinterpret_cast<uint64_t>(maps)));
    const CUtensorMap *const mv = mqk + 1, *const mo = mqk + 2;
    const uint64_t pol = stream_policy();
    uint4 kp[2], vp[2];
    uint32_t l0[2], l1[2], m[2];
    float s[2][3][4];
    auto scores = [&](uint32_t st, int row) {
        const float before = (row & 1023) == 0 ? -5.656854e9f : 0.f;
#pragma unroll
        for (int h = 0; h < 2; h++) {
            const uint4 q0 = ldsm4(st + (qoff ^ (h * 64))), q1 = ldsm4(st + (qoff ^ (h * 64 + 32)));
            const uint4 k0 = ldsm4(st + (koff ^ (h * 64))), k1 = ldsm4(st + 1024 + (koff ^ (h * 64)));
            qk_tile(s[h][0], q0, q1, kp[h], before);
            qk_tile(s[h][1], q0, q1, k0, 0.f);
            qk_tile(s[h][2], q0, q1, k1, 0.f);
            kp[h] = k1;
        }
    };
    auto logits = [&]() {
#pragma unroll
        for (int h = 0; h < 2; h++) {
            l0[h] = scaled_logits(up0, s[h][0][0], s[h][1][2], s[h][1][0], s[h][2][2]);
            l1[h] = scaled_logits(up1, s[h][0][1], s[h][1][3], s[h][1][1], s[h][2][3]);
            m[h] = max_bf16x2(l0[h], l1[h]);
            m[h] = max_bf16x2(m[h], __shfl_xor_sync(0xffffffffu, m[h], 1));
        }
    };
    auto row_max = [&]() {
#pragma unroll
        for (int h = 0; h < 2; h++) m[h] = max_bf16x2(m[h], __shfl_xor_sync(0xffffffffu, m[h], 2));
    };
    auto next = [](uint32_t p) {
        return (0x80200400u >> (p >> 4 & 31) & 1) > (p >> 15 & 1) ? p + (64 << 16) + 0x8000 : (p + 16) & ~0x8800u;
    };
    auto exchange = [&](uint32_t st, uint32_t b, uint32_t po, uint32_t pv, uint32_t pq) {
        asm volatile("{\n.reg .pred e, p, q;\n"
            "fence.proxy.async.shared::cta;\n"
            "bar.warp.sync 0xffffffff;\n"
            "elect.sync _|e, 0xffffffff;\n"
            "setp.eq.and.b32 p, %12, 0, e;\n"
            "setp.lt.and.s32 q, %8, %13, e;\n"
            "@q mbarrier.arrive.expect_tx.shared::cta.b64 _, [%2], 6144;\n"
            "@q cp.async.bulk.tensor.3d.shared::cluster.global.mbarrier::complete_tx::bytes.L2::cache_hint [%0], [%3, {%6, %7, %14}], [%2], %15;\n"
            "@q cp.async.bulk.tensor.2d.shared::cluster.global.mbarrier::complete_tx::bytes.L2::cache_hint [%0 + 4096], [%4, {%8, %9}], [%2], %15;\n"
            "@e cp.async.bulk.wait_group.read 0;\n"
            "@p cp.async.bulk.tensor.2d.global.shared::cta.bulk_group [%5, {%10, %11}], [%1 + 6144];\n"
            "@e cp.async.bulk.commit_group;\n"
            "bar.warp.sync 0xffffffff;\n}"
            :: "r"(st), "r"(st ^ ATT_SLOT), "r"(b), "l"(mqk), "l"(mv), "l"(mo), "r"(pq >> 16), "r"(pq & 2047),
               "r"((pv >> 16) + 2 * DM), "r"(pv & 2047), "r"(po >> 16), "r"(po & 2047), "r"(po & 0x8000),
               "r"(col + 256 + 2 * DM), "r"(0), "l"(pol) : "memory");
    };
    auto publish = [&](auto pending, int part) {
        asm volatile("{\n.reg .pred e;\n.reg .u32 n;\n"
            "elect.sync _|e, 0xffffffff;\n"
            "cp.async.bulk.wait_group %2;\n"
            "@e atom.acq_rel.cta.shared.add.u32 n, [%1], 1;\n"
            "setp.eq.and.u32 e, n, 11, e;\n"
            "@e red.release.gpu.global.add.u32 [%0], 1;\n}"
            :: "l"(g_flags + F_O * 512 + part * 32), "r"(rest_bar + 8 + part * 4), "n"(pending.value) : "memory");
    };
    const unsigned epoch = __ldcg(g_epoch + blockIdx.x * 16) + 1;
    if (elect_one()) {
        mbar_init(bar, 1); mbar_init(bar + 8, 1);
        if (warp == 2) { mbar_init(rest_bar, 32); sts64f(rest_bar + 8, 0.f, 0.f); }
        asm volatile("fence.mbarrier_init.release.cluster;" ::: "memory");
        prefetch_map(mqk); prefetch_map(mv); prefetch_map(mo);
    }
    __syncthreads();
    if (elect_one()) {
        g_epoch[blockIdx.x * 16] = epoch;
        flag_wait(g_flags + F_QKV * 512 + grp * 32, epoch * CNT_QKV);
        fence_proxy_async();
        mbar_expect_tx(bar + 8, 8192);
        tma_3d(buf + ATT_SLOT, mqk, bar + 8, col, first, 0, pol);
        tma_2d(buf + ATT_SLOT + 4096, mv, bar + 8, col + 2 * DM, first - 16, pol);
        tma_2d(buf + ATT_SLOT + 6144, mv, bar + 8, col + DM, first - 16, pol);
        mbar_expect_tx(bar, 6144);
        tma_3d(buf, mqk, bar, col, first + 16, 0, pol);
        tma_2d(buf + 4096, mv, bar, col + 2 * DM, first, pol);
        if (warp == 0) TRACE(9);
    }
    __syncwarp();
    mbar_wait(bar + 8, 0);
#pragma unroll
    for (int h = 0; h < 2; h++) {
        kp[h] = ldsm4(buf + ATT_SLOT + 5120 + (koff ^ (h * 64)));
        vp[h] = ldsm4_t(buf + ATT_SLOT + 3072 + (koff ^ (h * 64)));
    }
    scores(buf + ATT_SLOT, first);
    uint32_t pm = 0x8000, p0 = col << 16 | first, p1 = p0 + 16, p2 = p0 + 32, p3 = p0 + 48;
    exchange(buf + ATT_SLOT, bar + 8, pm, p1, p2);
    logits();
    row_max();
    uint32_t st = buf, b = bar, cnt = 1;
    const uint32_t relay = warp == 2 ? 7 : 0;
    bool ready = false;
#pragma unroll 1
    while (p0 >> 16 < col + 256) {
        uint32_t pa[2], pb[2];
        if (!ready) mbar_wait(b, (cnt >> 1) & 1);
        uint4 v[2][2];
#pragma unroll
        for (int h = 0; h < 2; h++) {
            const float ma = -LOG2E * bf_lo(m[h]), mb = -LOG2E * bf_hi(m[h]);
            const float a0 = ex2_fast(fmaf(bf_lo(l0[h]), LOG2E, ma)), a1 = ex2_fast(fmaf(bf_lo(l1[h]), LOG2E, ma));
            const float b0 = ex2_fast(fmaf(bf_hi(l0[h]), LOG2E, mb)), b1 = ex2_fast(fmaf(bf_hi(l1[h]), LOG2E, mb));
            float sum[4] = {0.f, 0.f, 0.f, 0.f};
            mma_1688(sum, pack_bf16(a0, a1), pack_bf16(b0, b1), 0x3f803f80u);
            const float ra = rcp_fast(sum[0]), rb = rcp_fast(sum[2]);
            pa[h] = pack_bf16(a0 * ra, a1 * ra);
            pb[h] = pack_bf16(b0 * rb, b1 * rb);
        }
        scores(st, p1);
#pragma unroll
        for (int h = 0; h < 2; h++) {
            v[h][0] = ldsm4_t(st + 4096 + (qoff ^ (h * 64)));
            v[h][1] = ldsm4_t(st + 4096 + (qoff ^ (h * 64 + 32)));
        }
        if (cnt == relay) {
            flag_wait<true>(g_flags + F_QKV * 512 + 128 + grp * 32, epoch * CNT_QKV);
            fence_proxy_async();
            mbar_arrive(rest_bar);
        }
        if (cnt == 8) {
#pragma unroll 1
            for (int spins = 0; !__all_sync(0xffffffffu, mbar_try_wait(rest_bar, 0)) && spins < (1 << 17); spins++) {}
        }
        if (cnt == 37) publish(std::integral_constant<int, 1>(), 0);
        exchange(st, b, pm, p2, p3);
        pm = p0; p0 = p1; p1 = p2; p2 = p3; p3 = next(p3);
        logits();
        float o[2][4][4];
#pragma unroll
        for (int h = 0; h < 2; h++) {
            const uint32_t prev[4] = {vp[h].x, vp[h].y, vp[h].z, vp[h].w};
            const uint32_t own[8] = {v[h][0].x, v[h][0].y, v[h][0].z, v[h][0].w, v[h][1].x, v[h][1].y, v[h][1].z, v[h][1].w};
            const uint32_t a0 = pa[h] & keep, a1 = pa[h] & ~keep, a2 = pb[h] & keep, a3 = pb[h] & ~keep;
            const uint32_t z0 = pa[h] & zero, z1 = pb[h] & zero;
#pragma unroll
            for (int j = 0; j < 4; j++) {
                o[h][j][0] = o[h][j][1] = o[h][j][2] = o[h][j][3] = 0.f;
                mma_1688(o[h][j], a0, z0, prev[j]);
                mma_16816(o[h][j], a1, a2, z1, a3, own[2 * j], own[2 * j + 1]);
            }
            vp[h] = make_uint4(own[1], own[3], own[5], own[7]);
        }
        row_max();
        b ^= 8; cnt++;
        ready = mbar_test(b, (cnt >> 1) & 1);
#pragma unroll
        for (int h = 0; h < 2; h++) {
#pragma unroll
            for (int d = 0; d < 2; d++)
                asm volatile("stmatrix.sync.aligned.m8n8.x4.shared.b16 [%0], {%1,%2,%3,%4};"
                             :: "r"(st + 6144 + (qoff ^ (h * 64 + d * 32))),
                                "r"(pack_bf16(o[h][2 * d][0], o[h][2 * d][1])), "r"(pack_bf16(o[h][2 * d][2], o[h][2 * d][3])),
                                "r"(pack_bf16(o[h][2 * d + 1][0], o[h][2 * d + 1][1])),
                                "r"(pack_bf16(o[h][2 * d + 1][2], o[h][2 * d + 1][3])) : "memory");
        }
        st ^= ATT_SLOT;
    }
    exchange(st, b, pm, p0, p0);
    publish(std::integral_constant<int, 0>(), 1);
    if (threadIdx.x == 0) TRACE(10);
}

struct Params {
    CUtensorMap x, xn, wqkv, wg, wu, qk, v, o, a2, wo, wd, out;
    const __nv_bfloat16* px;
    uint32_t zero;
    uint32_t role[NCTA];
};

__device__ __forceinline__ bool tile_is_qkv(int nt) { return nt < 4 || (nt >= 8 && nt < 16); }
__device__ __forceinline__ int tile_index(int nt) { return nt < 4 ? nt + 8 : (nt < 8 ? nt - 4 : (nt < 16 ? nt - 8 : nt - 12)); }

__global__ void __cluster_dims__(2, 1, 1) __launch_bounds__(384, 1)
fused_kernel(const __grid_constant__ Params prm) {
    extern __shared__ __align__(1024) uint8_t smem_raw[];
    const uint32_t base = smem_u32(smem_raw) & ~1023u;
    const uint32_t bars = base + BAR_OFF;
    auto full1 = [&](int s) { return bars + s * 8; };
    auto empty1 = [&](int s) { return bars + 32 + s * 8; };
    auto full2 = [&](int s) { return bars + 64 + s * 8; };
    auto empty2 = [&](int s) { return bars + 128 + s * 8; };
    const uint32_t sig_bar = bars + 192, dep_bar = bars + 256, cs_bar = bars + 304, fold_bar = bars + 320, x_bar = bars + 336;
    const uint32_t colsum = bars + 512, stats = bars + 1536;
    auto stage2 = [&](int q) { return base + q * G2_STAGE_BYTES; };
    const uint32_t aux = base + AUX_OFF;

    const int warp = __shfl_sync(0xffffffffu, threadIdx.x >> 5, 0);
    const int lane = threadIdx.x & 31;
    const int rank = blockIdx.x & 1;
    const uint32_t role = prm.role[blockIdx.x];
    const int mblk = role & 15, nslot = role >> 4;

    if (blockIdx.x >= NGEMM) {
        if (threadIdx.x == 0) { TRACE_GT(0); TRACE(1); }
        attention(&prm.qk, (base + 2 * ATT_SLOT - 1) & ~(2u * ATT_SLOT - 1), prm.zero, blockIdx.x - NGEMM, warp, lane);
    } else if (warp >= 8) {
        unsigned* const flags = g_flags + mblk * 32;
        const CUtensorMap* const w0 = nslot < 4 ? &prm.wqkv : (rank ? &prm.wu : &prm.wg);
        const int w0_col = nslot < 4 ? 32 + nslot * 4 + rank * 2 : nslot * 2 - 8;
        if (elect_one()) {
            if (warp == 8) {
                TRACE_GT(0); TRACE(1);
                prefetch_map(&prm.x); prefetch_map(w0);
                for (int s = 0; s < G1_STAGES; s++) { mbar_init(full1(s), 1); mbar_init(empty1(s), 4); }
            } else if (warp == 9) {
                for (int s = 0; s < G2_STAGES; s++) { mbar_init(full2(s), 1); mbar_init(empty2(s), 4); }
            } else if (warp == 10) {
                for (int s = 0; s < 7; s++) mbar_init(sig_bar + s * 8, 8);
                mbar_init(fold_bar, 2); mbar_init(x_bar, 1);
            } else {
                for (int s = 0; s < 8; s++) mbar_init(dep_bar + s * 8, 1);
                TRACE_CLEAR();
            }
            asm volatile("fence.mbarrier_init.release.cluster;" ::: "memory");
        }
        __syncwarp();
        asm volatile("barrier.cluster.arrive.relaxed.aligned;" ::: "memory");
        if (warp == 8 && lane == 0) {
            mbar_expect_tx(full1(0), G1_STAGE_BYTES);
            tma_2d(base, &prm.x, full1(0), 0, mblk * 128, stream_policy());
            prefetch_3d(w0, 0, w0_col, stream_policy());
            TRACE(15);
        }
        asm volatile("setmaxnreg.dec.sync.aligned.u32 %0;" :: "n"(AUX_REGS));
        asm volatile("barrier.cluster.wait.acquire.aligned;" ::: "memory");

        if (warp == 8) {
            if (elect_one()) { TRACE(2); tma_3d_mc(base + A_BYTES + rank * 16384, w0, full1(0), 0, w0_col, stream_policy()); }
            uint32_t ph = 1;
#pragma unroll 1
            for (int t = 0; t < G1_TILES; t++) {
                const int nt = t * 8 + nslot;
                const CUtensorMap* const mb = tile_is_qkv(nt) ? &prm.wqkv : (rank ? &prm.wu : &prm.wg);
                const int col = tile_is_qkv(nt) ? tile_index(nt) * 4 + rank * 2 : tile_index(nt) * 2;
                if (t == 1) { TRACE(14); mbar_wait_warp(dep_bar, 0); TRACE(3); }
#pragma unroll 1
                for (int k = t == 0; k < G1_KSTEPS; k++) {
                    const int s = k & 3;
                    if (t == 0 && k == G1_STAGES && elect_one()) {
                        prefetch_map(&prm.xn); prefetch_map(&prm.wqkv); prefetch_map(&prm.wu); prefetch_map(&prm.wg);
                        prefetch_map(&prm.a2); prefetch_map(&prm.wo); prefetch_map(&prm.wd); prefetch_map(&prm.out);
                    }
                    mbar_wait_warp(empty1(s), ph);
                    const uint32_t sa = base + s * G1_STAGE_BYTES;
                    load_stage1(sa, sa + A_BYTES + rank * 16384, full1(s), t ? &prm.xn : &prm.x, mb, k * 64, mblk * 128, col,
                                t & 3, stream_policy());
                    if (s == 3) ph ^= 1;
                }
            }
            if (elect_one()) {
                mbar_expect_tx(x_bar, 32768);
                tma_2d(aux, &prm.x, x_bar, nslot * 128, mblk * 128, stream_policy());
                tma_2d(aux + 16384, &prm.x, x_bar, nslot * 128 + 64, mblk * 128, stream_policy());
            }
            TRACE(4);
            mbar_wait_warp(dep_bar + 8, 0);
            TRACE(5);
            int q = 0; uint32_t ph2 = 1;
#pragma unroll 1
            for (int u = 0; u < G2_KSTEPS; u++) {
                if (u == G2_LATE || u == G2_DSTEPS || u == G2_LAST) {
                    TRACE(u == G2_LATE ? 6 : (u == G2_DSTEPS ? 32 : 40));
                    mbar_wait_warp(dep_bar + (u == G2_LATE ? 16 : (u == G2_DSTEPS ? 24 : 32)), 0);
                    TRACE(u == G2_LATE ? 7 : (u == G2_DSTEPS ? 33 : 41));
                }
                const uint32_t sa = stage2(q);
                const bool down = u < G2_DSTEPS;
                const int k = down ? u : (u & 3) * 4 + (u - G2_DSTEPS) / 4;
                mbar_wait_warp(u < G2_STAGES ? empty1((u * 2 + 1) / 3) : empty2(q), u < G2_STAGES ? ph : ph2);
                load_stage2(sa, sa + A_BYTES + rank * 8192, full2(q), &prm.a2, down ? &prm.wd : &prm.wo, (down ? DM : 0) + k * 64,
                            mblk * 64, nslot * 128 + rank * 64, k * 2, stream_policy());
                if (++q == G2_STAGES) { q = 0; ph2 ^= 1; }
            }
            TRACE(8);
        } else if (warp == 9) {
            if (lane == 0) {
                const unsigned epoch = __ldcg(g_epoch + blockIdx.x * 16 + 2) + 1;
                mbar_wait(sig_bar, 0);
                TRACE(11);
                flag_add(flags + F_LN * 512);
                TRACE(42);
                flag_wait(flags + F_LN * 512, epoch * CNT_LN);
                fence_proxy_async();
                mbar_arrive(dep_bar);
                g_epoch[blockIdx.x * 16 + 2] = epoch;
                for (int p = nslot < 4 ? 2 : 1; p < 7; p++) {
                    mbar_wait(sig_bar + p * 8, 0);
                    if (p == 2) TRACE(37);
                    flag_add(p == 2 || p == 3 ? g_flags + F_QKV * 512 + (p * 4 - 8 + (nslot & 3)) * 32
                                              : flags + (p < 6 ? F_EARLY : F_LATE) * 512);
                    if (p == 2) TRACE(43);
                }
            }
        } else {
            const int w = warp - 10;
            const unsigned epoch = __ldcg(g_epoch + blockIdx.x * 16 + w) + 1;
            const uint32_t tag = 1 + (epoch & 1);
            mbar_wait(CSAT, 0);
            if (elect_one()) {
                mbar_expect_tx(cs_bar + w * 8, 16384);
                tma_3d(aux + w * 16384, w0, cs_bar + w * 8, 0, ((mblk & ~1) + w) * 64, w0_col, stream_policy());
            }
            float cs[8];
#pragma unroll
            for (int d = 0; d < 8; d++) cs[d] = 0.f;
            const uint32_t wa = aux + w * 8192 + (lane >> 3) * 128 + (((lane & 7) ^ (lane >> 3)) << 4);
            uint4 v[9];
            auto fetch = [&](int h, int i) {
#pragma unroll
                for (int j = 0; j < 4; j++) v[h * 4 + j] = lds128((wa ^ (j & 1) * 64) + h * 16384 + i * 2048 + j * 512);
            };
            auto add = [&](int h) {
#pragma unroll
                for (int j = 0; j < 4; j++) {
                    float f[8];
                    unpack8(v[h * 4 + j], f);
#pragma unroll
                    for (int d = 0; d < 8; d++) cs[d] += f[d];
                }
            };
            mbar_wait(cs_bar, 0);
            fetch(0, 0);
            mbar_wait(cs_bar + 8, 0);
            if (w == 0 && lane == 0) TRACE(36);
#pragma unroll 1
            for (int i = 0; i < 4; i++) {
                fetch(1, i);
                add(0);
                fetch(0, (i + 1) & 3);
                add(1);
            }
#pragma unroll
            for (int d = 0; d < 4; d++)
                cs[d] = (lane & 16 ? cs[d + 4] : cs[d]) + __shfl_xor_sync(0xffffffffu, lane & 16 ? cs[d] : cs[d + 4], 16);
#pragma unroll
            for (int d = 0; d < 2; d++)
                cs[d] = (lane & 8 ? cs[d + 2] : cs[d]) + __shfl_xor_sync(0xffffffffu, lane & 8 ? cs[d] : cs[d + 2], 8);
            st_tagged(g_colsum + (nslot * 2 + rank) * 1024 + (mblk >> 1) * 128 + w * 64 + (lane & 7) * 8 + (lane >> 3) * 2,
                      cs[0], cs[1], tag);
            if (w == 0 && lane == 0) TRACE(34);
#pragma unroll
            for (int m = 0; m < 9; m++) v[m] = make_uint4(0, 0, 0, 0);
#pragma unroll 1
            for (int spins = 0; spins < (1 << 16); spins++) {
                bool missing = false;
#pragma unroll
                for (int m = 0; m < 9; m++) {
                    if (untagged(v[m], tag)) {
                        missing = true;
                        v[m] = m < 8 ? ld_relaxed(g_colsum + (nslot * 2 + w) * 1024 + m * 128 + lane * 4)
                                     : ld_relaxed(g_stats + mblk * 128 + w * 64 + lane * 2);
                    }
                }
                if (!missing) break;
            }
            float4 c = make_float4(0.f, 0.f, 0.f, 0.f);
#pragma unroll
            for (int m = 0; m < 8; m++) {
                c.x += __uint_as_float(v[m].x ^ tag); c.y += __uint_as_float(v[m].y ^ tag);
                c.z += __uint_as_float(v[m].z ^ tag); c.w += __uint_as_float(v[m].w ^ tag);
            }
            sts128(stats + w * 512 + lane * 16, make_uint4(v[8].x ^ tag, v[8].y ^ tag, v[8].z ^ tag, v[8].w ^ tag));
            const uint32_t ca = colsum + (w * 8 + (lane >> 2)) * 64 + (lane & 1) * 32 + (lane & 2) * 4;
            sts64f(ca, c.y, c.x);
            sts64f(ca + 16, c.w, c.z);
            __syncwarp();
            if (lane == 0) {
                mbar_arrive(fold_bar);
                g_epoch[blockIdx.x * 16 + w] = epoch;
                if (w == 0) {
                    TRACE(35);
                    flag_wait(flags + F_EARLY * 512, epoch * CNT_EARLY);
                    fence_proxy_async(); mbar_arrive(dep_bar + 8);
                    flag_wait(flags + F_LATE * 512, epoch * CNT_LATE);
                    fence_proxy_async(); mbar_arrive(dep_bar + 16);
                    flag_wait(g_flags + F_O * 512, epoch * CNT_O);
                    fence_proxy_async(); mbar_arrive(dep_bar + 24);
                    flag_wait(g_flags + F_O * 512 + 32, epoch * CNT_O);
                    fence_proxy_async(); mbar_arrive(dep_bar + 32);
                }
            }
        }
    } else {
        asm volatile("barrier.cluster.arrive.relaxed.aligned;" ::: "memory");
        asm volatile("setmaxnreg.inc.sync.aligned.u32 %0;" :: "n"(CONSUMER_REGS));
        const int wg = __shfl_sync(0xffffffffu, threadIdx.x >> 7, 0);
        const int cw = threadIdx.x >> 5;
        const int tid = threadIdx.x & 127;
        float acc[128];
        uint32_t pk[64];
#pragma unroll
        for (int i = 0; i < 64; i++) asm volatile("mov.b32 %0, 0;" : "=r"(pk[i]));
#pragma unroll
        for (int i = 0; i < 128; i++) asm volatile("mov.b32 %0, 0;" : "=f"(acc[i]));
        asm volatile("barrier.cluster.wait.acquire.aligned;" ::: "memory");

        const int orow = ((lane >> 2) & 1) * (SEQ / 2) + mblk * 64 + cw * 8 + (lane >> 3);
        __nv_bfloat16* optr = g_xn + (mblk * 128 + nslot * 16 + cw * 2) * DM + lane * 8;
        const uint32_t da = desc_a(base + wg * 8192), db = desc_b(base + A_BYTES);
        auto release = [&](uint32_t bar) { if (tid < 2) mbar_arrive_cluster(bar, tid); };
        auto store_pk = [&](__nv_bfloat16* p, int j) {
            *reinterpret_cast<uint4*>(p) = make_uint4(pk[4 * j], pk[4 * j + 1], pk[4 * j + 2], pk[4 * j + 3]);
        };
        auto chunk_geglu = [&](int j) {
#pragma unroll
            for (int i = 4 * j; i < 4 * j + 4; i++) pk[i] = geglu2(pk[i], pk[32 + i]);
            store_pk(optr + (j & 1) * 4 * K2 + (j >> 1) * 32, j);
        };
        auto chunk_qkv = [&](int c) {
            store_pk(optr + c * 32, 2 * c);
            store_pk(optr + 4 * NQKV + c * 32, 2 * c + 1);
        };
        auto signal_stores = [&](int p) { __syncwarp(); if (lane == 0) mbar_arrive(sig_bar + p * 8); };

        auto chunk_ln = [&](int k) {
            float* const mo = reinterpret_cast<float*>(pk + 32);
            if (k == 0) {
                const uint4* xp = reinterpret_cast<const uint4*>(prm.px + (optr - g_xn));
                pk[38] = __ldcg(g_epoch + blockIdx.x * 16 + 2);
#pragma unroll
                for (int i = 0; i < 8; i++) {
                    const uint4 v = ldg_stream(xp + i * 32, stream_policy());
                    pk[4 * i] = v.x; pk[4 * i + 1] = v.y; pk[4 * i + 2] = v.z; pk[4 * i + 3] = v.w;
                }
            } else if (k >= LN_STEP && k < LN_STEP + 3) {
                if (k == LN_STEP) {
                    mo[0] = bf_lo(uniform(pk[0])); mo[1] = bf_lo(uniform(pk[16]));
                    mo[2] = mo[3] = mo[4] = mo[5] = 0.f;
                }
#pragma unroll
                for (int i = (k - LN_STEP) * 11; i < (k - LN_STEP) * 11 + 11 && i < 32; i++) {
                    const int r = i & 1;
                    const uint32_t w = pk[r * 16 + i / 2];
                    const float lo = bf_lo(w) - mo[r], hi = bf_hi(w) - mo[r];
                    mo[2 + r] += lo + hi;
                    mo[4 + r] = fmaf(hi, hi, fmaf(lo, lo, mo[4 + r]));
                }
            } else if (k == LN_STEP + 3) {
                const bool second = lane & 16;
                float m1 = (second ? mo[3] : mo[2]) + __shfl_xor_sync(0xffffffffu, second ? mo[2] : mo[3], 16);
                float m2 = (second ? mo[5] : mo[4]) + __shfl_xor_sync(0xffffffffu, second ? mo[4] : mo[5], 16);
#pragma unroll
                for (int o = 8; o > 0; o >>= 1) {
                    m1 += __shfl_xor_sync(0xffffffffu, m1, o);
                    m2 += __shfl_xor_sync(0xffffffffu, m2, o);
                }
                m1 *= 1.f / DM;
                const float var = fmaxf(fmaf(-m1, m1, m2 * (1.f / DM)), 0.f);
                const float mean = round_bf16((second ? mo[1] : mo[0]) + m1);
                const float inv = rcp_fast(round_bf16(sqrt_fast(round_bf16(round_bf16(var) + 1e-5f))));
                if ((lane & 15) == 0) st_tagged(g_stats + (uint32_t)(optr - g_xn) / DM + second, -mean, inv, 2 - (pk[38] & 1));
                const uint32_t split = pack_bf16(inv - round_bf16(inv), inv);
#pragma unroll
                for (int r = 0; r < 2; r++) {
                    const uint32_t f = __shfl_sync(0xffffffffu, split, r * 16);
                    pk[32 + 3 * r] = __byte_perm(__shfl_sync(0xffffffffu, __float_as_uint(mean), r * 16), 0, 0x3232);
                    pk[33 + 3 * r] = __byte_perm(f, 0, 0x3232);
                    pk[34 + 3 * r] = __byte_perm(f, 0, 0x1010);
                }
            } else if (k >= LN_STEP + 4 && k < LN_STEP + 7) {
#pragma unroll
                for (int i = (k - LN_STEP - 4) * 3; i < (k - LN_STEP - 3) * 3 && i < 8; i++) {
                    const uint32_t* n = pk + 32 + i / 4 * 3;
#pragma unroll
                    for (int j = 4 * i; j < 4 * i + 4; j++) pk[j] = mul2_bf16x2(sub_bf16x2(pk[j], n[0]), n[1], n[2]);
                    store_pk(optr + i * 256, i);
                }
                if (k == LN_STEP + 6) signal_stores(0);
            } else if (k == FOLD_STEP) {
                mbar_wait(fold_bar, 0);
#pragma unroll
                for (int j = 0; j < 16; j++) {
                    const uint4 c = lds128(colsum + j * 64 + (lane & 3) * 16);
                    pk[4 * j] = c.x; pk[4 * j + 1] = c.y; pk[4 * j + 2] = c.z; pk[4 * j + 3] = c.w;
                }
            }
        };

        bool gated = false;
#pragma unroll 1
        for (int t = 0; t < G1_TILES; t++) {
#pragma unroll
            for (int k = 0; k < G1_KSTEPS; k++) {
                const int s = k & 3;
                TRACE_STEP(t, k, 0);
                mbar_wait(full1(s), (k >> 2) & 1);
                if (k == 0) TRACE_S(12, t, 0);
                TRACE_STEP(t, k, 1);
                if (wg == 1 && k == G1_KSTEPS - (t ? G1_SKEW : SK0)) asm volatile("bar.sync 1, 256;" ::: "memory");
                mma_step(acc, da, db, s * G1_STAGE_BYTES / 16, k);
                if (wg == 0 && k == G1_KSTEPS - 1) asm volatile("bar.arrive 1, 256;" ::: "memory");
                wg_wait<1>();
                if (k > 0) release(empty1((k - 1) & 3));
                TRACE_STEP(t, k, 2);
                if (t == 0) chunk_ln(k);
                if (k >= 1 && k <= 8 && gated) {
                    chunk_geglu(k - 1);
                    if (k == 8) signal_stores(t == 1 ? 1 : t + 1);
                }
                if (t != 0 && !gated) {
                    if (k == 0) { chunk_qkv(0); chunk_qkv(1); }
                    if (k >= 6 && k <= 11) chunk_qkv(k - 4);
                    if ((k == 0 || k == 11) && t == 2) signal_stores(k ? 3 : 2);
                }
            }
            wg_wait<0>();
            fence_regs(acc);
            release(empty1(3));
            if (t == 0) {
                const uint32_t sp = stats + (cw * 16 + (lane >> 2)) * 8;
                const float2 sa = lds64f(sp), sb = lds64f(sp + 64);
#pragma unroll
                for (int i = 0; i < 128; i++) {
                    const float2 st = i & 2 ? sb : sa;
                    acc[i] = fmaf(st.x, __uint_as_float(pk[i / 4 * 2 + (~i & 1)]), acc[i]) * st.y;
                }
                fence_regs(acc);
            }
#pragma unroll
            for (int i = 0; i < 64; i++) {
                const int e = (i & ~7) * 2 + (i & 3) * 4 + (i & 4) / 2;
                pk[i] = pack_bf16(acc[e], acc[e + 1]);
            }
            const int nt = t * 8 + nslot;
            gated = !tile_is_qkv(nt);
            optr = !gated ? g_qkv + (size_t)orow * NQKV + tile_index(nt) * 256 + (lane & 3) * 8
                                : g_a2 + (size_t)orow * K2 + DM + tile_index(nt) * 128 + (lane & 3) * 8;
            TRACE_S(16 + wg * 8 + t, 0, 0);
        }

        float accd[64], accs[64];
#pragma unroll
        for (int i = 0; i < 64; i++) accd[i] = 0.f;
#pragma unroll
        for (int u = 0; u < 9; u++) {
            const int q = u % G2_STAGES;
            mbar_wait(full2(q), (u / G2_STAGES) & 1);
            mma_step(accd, da, db, q * G2_STAGE_BYTES / 16, u);
            wg_wait<1>();
            if (u > 0) release(empty2((u - 1) % G2_STAGES));
            if (u >= 1) { chunk_geglu(u - 1); if (u == 8) signal_stores(6); }
        }
        {
            int q = 9 % G2_STAGES, qp = 8 % G2_STAGES; uint32_t ph = (9 / G2_STAGES) & 1;
#pragma unroll 1
            for (int u = 9; u < G2_DSTEPS; u++) {
                mbar_wait(full2(q), ph);
                mma_step(accd, da, db, q * (G2_STAGE_BYTES / 16), 1);
                wg_wait<1>();
                release(empty2(qp));
                qp = q;
                if (++q == G2_STAGES) { q = 0; ph ^= 1; }
            }
        }
        TRACE_S(16 + wg * 8 + 5, 0, 0);
#pragma unroll
        for (int i = 0; i < 64; i++) accs[i] = 0.f;
        uint32_t gk[32], xr[32];
        const uint32_t xs = aux + cw * 2048;
        const uint32_t xrow = xs + ((lane & 7) + ((lane >> 3) & 1) * 8) * 128;
        auto xaddr = [&](int j) { return xrow + (j >> 2) * 16384 + (((((j & 3) * 2) + (lane >> 4)) ^ (lane & 7)) << 4); };
#pragma unroll
        for (int u = G2_DSTEPS; u < G2_KSTEPS; u++) {
            const int q = u % G2_STAGES, v = u - G2_DSTEPS;
            mbar_wait(full2(q), (u / G2_STAGES) & 1);
            if (G2_SKEW > 0 && wg == 1 && u == G2_KSTEPS - G2_SKEW) asm volatile("bar.sync 1, 256;" ::: "memory");
            mma_step(accs, da, db, q * G2_STAGE_BYTES / 16, v);
            if (G2_SKEW > 0 && wg == 0 && u == G2_KSTEPS - 1) asm volatile("bar.arrive 1, 256;" ::: "memory");
            if (v >= 1 && v <= 8) {
#pragma unroll
                for (int i = 4 * (v - 1); i < 4 * v; i++) {
                    const uint32_t d2 = pack_bf16(accd[2 * i], accd[2 * i + 1]);
                    gk[i] = pack_bf16(silu(bf_lo(d2)), silu(bf_hi(d2)));
                }
            }
            if (v == 9) mbar_wait(x_bar, 0);
            if (v >= 9 && v <= 12) {
#pragma unroll
                for (int j = 2 * (v - 9); j < 2 * (v - 8); j++)
                    asm volatile("ldmatrix.sync.aligned.m8n8.x4.shared.b16 {%0,%1,%2,%3}, [%4];"
                                 : "=r"(xr[4 * j]), "=r"(xr[4 * j + 1]), "=r"(xr[4 * j + 2]), "=r"(xr[4 * j + 3])
                                 : "r"(xaddr(j)) : "memory");
            }
            wg_wait<1>();
            if (v == 0) fence_regs(accd);
            if (u - 1 + G2_STAGES < G2_KSTEPS) release(empty2((u - 1) % G2_STAGES));
        }
        wg_wait<0>();
        fence_regs(accs);
        TRACE_S(16 + wg * 8 + 6, 0, 0);
#pragma unroll
        for (int j = 0; j < 8; j++) {
            uint32_t r[4];
#pragma unroll
            for (int i = 0; i < 4; i++) {
                const int e = j * 4 + i;
                r[i] = add_bf16x2(xr[e], mul_bf16x2(pack_bf16(accs[2 * e], accs[2 * e + 1]), gk[e]));
            }
            asm volatile("stmatrix.sync.aligned.m8n8.x4.shared.b16 [%0], {%1,%2,%3,%4};"
                         :: "r"(xaddr(j)), "r"(r[0]), "r"(r[1]), "r"(r[2]), "r"(r[3]) : "memory");
            if (j == 3 || j == 7) {
                asm volatile("fence.proxy.async.shared::cta;" ::: "memory");
                __syncwarp();
                if (lane == 0) {
                    tma_store_2d(&prm.out, xs + (j >> 2) * 16384, nslot * 128 + (j >> 2) * 64, mblk * 128 + cw * 16);
                    asm volatile("cp.async.bulk.commit_group;" ::: "memory");
                }
            }
        }
        if (lane == 0) asm volatile("cp.async.bulk.wait_group.read 0;" ::: "memory");
        if (tid == 0) { TRACE(16 + wg * 8 + 7); if (wg == 1) TRACE_GT(13); TRACE_DUMP(); }
    }
}

typedef CUresult (*EncodeFn)(CUtensorMap*, CUtensorMapDataType, cuuint32_t, void*, const cuuint64_t*, const cuuint64_t*,
                             const cuuint32_t*, const cuuint32_t*, CUtensorMapInterleave, CUtensorMapSwizzle,
                             CUtensorMapL2promotion, CUtensorMapFloatOOBfill);

void encode(EncodeFn fn, CUtensorMap* m, const void* ptr, int rank, const cuuint64_t* dims, const cuuint64_t* strides,
            const cuuint32_t* box) {
    const cuuint32_t es[5] = {1, 1, 1, 1, 1};
    fn(m, CU_TENSOR_MAP_DATA_TYPE_BFLOAT16, rank, const_cast<void*>(ptr), dims, strides, box, es,
       CU_TENSOR_MAP_INTERLEAVE_NONE, CU_TENSOR_MAP_SWIZZLE_128B, CU_TENSOR_MAP_L2_PROMOTION_L2_128B,
       CU_TENSOR_MAP_FLOAT_OOB_FILL_NONE);
}
void encode_2d(EncodeFn fn, CUtensorMap* m, const void* ptr, int cols, int box_rows) {
    const cuuint64_t dims[2] = {(cuuint64_t)cols, SEQ}, strides[1] = {(cuuint64_t)cols * 2};
    const cuuint32_t box[2] = {64, (cuuint32_t)box_rows};
    encode(fn, m, ptr, 2, dims, strides, box);
}
void encode_w1(EncodeFn fn, CUtensorMap* m, const void* ptr, int cols) {
    const cuuint64_t dims[3] = {64, DM, (cuuint64_t)cols / 64}, strides[2] = {(cuuint64_t)cols * 2, 128};
    const cuuint32_t box[3] = {64, 64, 2};
    encode(fn, m, ptr, 3, dims, strides, box);
}
void encode_qk(EncodeFn fn, CUtensorMap* m, const void* ptr) {
    const cuuint64_t dims[3] = {DM, SEQ, 3}, strides[2] = {NQKV * 2, DM * 2};
    const cuuint32_t box[3] = {64, 16, 2};
    encode(fn, m, ptr, 3, dims, strides, box);
}
void encode_a2(EncodeFn fn, CUtensorMap* m, const void* ptr) {
    const cuuint64_t dims[3] = {K2, 2, SEQ / 2}, strides[2] = {(cuuint64_t)SEQ * K2, K2 * 2};
    const cuuint32_t box[3] = {64, 2, 64};
    encode(fn, m, ptr, 3, dims, strides, box);
}
void encode_w2(EncodeFn fn, CUtensorMap* m, const void* ptr, int rows) {
    const cuuint64_t rb = DM * 2;
    const cuuint64_t dims[5] = {DM, 2, 4, 4, (cuuint64_t)rows / 32}, strides[4] = {rb, 8 * rb, 2 * rb, 32 * rb};
    const cuuint32_t box[5] = {64, 2, 4, 4, 2};
    encode(fn, m, ptr, 5, dims, strides, box);
}

}

extern "C" void kernel_launch(void* const* d_in, const int* in_sizes, int n_in, void* d_out, int out_size) {
    (void)in_sizes; (void)n_in; (void)out_size;
    static EncodeFn fn = nullptr;
    static void *p_xn = nullptr, *p_qkv = nullptr, *p_a2 = nullptr;
    if (!fn) {
        cudaDriverEntryPointQueryResult st;
        cudaGetDriverEntryPoint("cuTensorMapEncodeTiled", (void**)&fn, cudaEnableDefault, &st);
        cudaGetSymbolAddress(&p_xn, g_xn);
        cudaGetSymbolAddress(&p_qkv, g_qkv);
        cudaGetSymbolAddress(&p_a2, g_a2);
        cudaFuncSetAttribute(fused_kernel, cudaFuncAttributeMaxDynamicSharedMemorySize, SMEM_BYTES);
    }
    Params prm;
    encode_2d(fn, &prm.x, d_in[0], DM, 128);
    encode_2d(fn, &prm.xn, p_xn, DM, 128);
    encode_w1(fn, &prm.wqkv, d_in[1], NQKV);
    encode_w1(fn, &prm.wg, d_in[4], DF);
    encode_w1(fn, &prm.wu, d_in[5], DF);
    encode_qk(fn, &prm.qk, p_qkv);
    encode_2d(fn, &prm.v, p_qkv, NQKV, 16);
    encode_2d(fn, &prm.o, p_a2, K2, 16);
    encode_a2(fn, &prm.a2, p_a2);
    encode_w2(fn, &prm.wo, d_in[2], DM);
    encode_w2(fn, &prm.wd, d_in[6], DF);
    encode_2d(fn, &prm.out, d_out, DM, 16);
    prm.px = (const __nv_bfloat16*)d_in[0];
    prm.zero = 0;
    for (int b = 0; b < NCTA; b++) {
        const int c = b / 2;
        prm.role[b] = (c < 4 ? 32 + c * 8 : (c < 36 ? c - 4 : 33 + (c - 36) / 7 * 8 + (c - 36) % 7)) * 2 + b % 2;
    }
    fused_kernel<<<NCTA, 384, SMEM_BYTES>>>(prm);
}
```

```cpp
#include <cuda_runtime.h>
#include <cuda_bf16.h>
#include <cuda.h>
#include <stdint.h>
#include <type_traits>

#define LNS 3
#define FS 15
#define CSAT empty1(3)
#define SK0 3

namespace {

constexpr int SEQ = 2048, DM = 1024, DF = 3584, K2 = DM + DF, NQKV = 3 * DM;
constexpr int NGEMM = 128, NCTA = 132;
constexpr int G1_STAGES = 4, G1_STAGE_BYTES = 49152, G1_KSTEPS = 16, G1_TILES = 5;
constexpr int G2_STAGES = 6, G2_STAGE_BYTES = 32768, G2_KSTEPS = 72, G2_LATE = 40, G2_DSTEPS = 56, G2_LAST = 68;
constexpr int LN_STEP = LNS, FOLD_STEP = FS;
constexpr int A_BYTES = 16384;
constexpr int AUX_OFF = G1_STAGES * G1_STAGE_BYTES;
constexpr int BAR_OFF = AUX_OFF + 32768;
constexpr int SMEM_BYTES = BAR_OFF + 2816;
constexpr int G1_SKEW = 2, G2_SKEW = 2;
constexpr int CONSUMER_REGS = 224, AUX_REGS = 56;
constexpr int ATT_SLOT = 8192;

enum { F_LN = 0, F_QKV = 1, F_EARLY = 2, F_LATE = 3, F_O = 4 };
constexpr unsigned CNT_LN = 8, CNT_QKV = 32, CNT_REST = 36, CNT_EARLY = 20, CNT_LATE = 8, CNT_O = 4;

__device__ __align__(1024) __nv_bfloat16 g_xn[SEQ * DM];
__device__ __align__(1024) __nv_bfloat16 g_qkv[SEQ * NQKV];
__device__ __align__(1024) __nv_bfloat16 g_a2[SEQ * K2];
__device__ __align__(128) float2 g_stats[SEQ];
__device__ __align__(128) float g_colsum[16 * 1024];
__device__ __align__(128) unsigned g_flags[5 * 16 * 32];
__device__ __align__(128) unsigned g_epoch[NCTA * 16];

#define TRACE(slot) do {} while (0)
#define TRACE_GT(slot) do {} while (0)
#define TRACE_S(slot, v, want) do {} while (0)
#define TRACE_DUMP() do {} while (0)
#define TRACE_CLEAR() do {} while (0)
#define TRACE_STEP(t, k, i) do {} while (0)

__device__ __forceinline__ uint32_t smem_u32(const void* p) { return (uint32_t)__cvta_generic_to_shared(p); }
__device__ __forceinline__ void mbar_init(uint32_t bar, uint32_t cnt) {
    asm volatile("mbarrier.init.shared::cta.b64 [%0], %1;" :: "r"(bar), "r"(cnt) : "memory");
}
__device__ __forceinline__ void mbar_expect_tx(uint32_t bar, uint32_t bytes) {
    asm volatile("mbarrier.arrive.expect_tx.shared::cta.b64 _, [%0], %1;" :: "r"(bar), "r"(bytes) : "memory");
}
__device__ __forceinline__ void mbar_arrive(uint32_t bar) {
    asm volatile("mbarrier.arrive.shared::cta.b64 _, [%0];" :: "r"(bar) : "memory");
}
__device__ __forceinline__ void mbar_arrive_cluster(uint32_t bar, uint32_t cta) {
    asm volatile("{\n.reg .b32 ra;\nmapa.shared::cluster.u32 ra, %0, %1;\nmbarrier.arrive.shared::cluster.b64 _, [ra];\n}"
                 :: "r"(bar), "r"(cta) : "memory");
}
__device__ __forceinline__ bool mbar_try_wait(uint32_t bar, uint32_t parity) {
    uint32_t ok;
    asm volatile("{\n.reg .pred p;\nmbarrier.try_wait.parity.shared::cta.b64 p, [%1], %2;\nselp.u32 %0, 1, 0, p;\n}"
                 : "=r"(ok) : "r"(bar), "r"(parity) : "memory");
    return ok;
}
__device__ __forceinline__ bool mbar_test(uint32_t bar, uint32_t parity) {
    uint32_t ok;
    asm volatile("{\n.reg .pred p;\nmbarrier.test_wait.parity.shared::cta.b64 p, [%1], %2;\nselp.u32 %0, 1, 0, p;\n}"
                 : "=r"(ok) : "r"(bar), "r"(parity) : "memory");
    return ok;
}
__device__ __forceinline__ void mbar_wait(uint32_t bar, uint32_t parity) {
#pragma unroll 1
    for (int spins = 0; !mbar_try_wait(bar, parity) && spins < (1 << 17); spins++) {}
}
template <bool WARP = false> __device__ __forceinline__ void flag_wait(const unsigned* p, unsigned target) {
#pragma unroll 1
    for (int spins = 0; spins < (1 << 19); spins++) {
        unsigned v;
        asm volatile("ld.acquire.gpu.global.u32 %0, [%1];" : "=r"(v) : "l"(p) : "memory");
        if (WARP ? __all_sync(0xffffffffu, (int)(v - target) >= 0) : (int)(v - target) >= 0) break;
        __nanosleep(64);
    }
}
__device__ __forceinline__ void mbar_wait_warp(uint32_t bar, uint32_t parity) {
#pragma unroll 1
    for (int spins = 0; !__all_sync(0xffffffffu, mbar_try_wait(bar, parity)) && spins < (1 << 17); spins++) {}
}
__device__ __forceinline__ void flag_add(unsigned* p) {
    asm volatile("red.release.gpu.global.add.u32 [%0], 1;" :: "l"(p) : "memory");
}
__device__ __forceinline__ bool elect_one() {
    uint32_t ok;
    asm volatile("{\n.reg .pred p;\nelect.sync _|p, 0xffffffff;\nselp.u32 %0, 1, 0, p;\n}" : "=r"(ok));
    return ok;
}
__device__ __forceinline__ void fence_proxy_async() { asm volatile("fence.proxy.async.global;" ::: "memory"); }
__device__ __forceinline__ uint4 lds128(uint32_t addr) {
    uint4 v;
    asm volatile("ld.shared.v4.u32 {%0,%1,%2,%3}, [%4];" : "=r"(v.x), "=r"(v.y), "=r"(v.z), "=r"(v.w) : "r"(addr) : "memory");
    return v;
}
__device__ __forceinline__ float2 lds64f(uint32_t addr) {
    float2 v;
    asm volatile("ld.shared.v2.f32 {%0,%1}, [%2];" : "=f"(v.x), "=f"(v.y) : "r"(addr) : "memory");
    return v;
}
__device__ __forceinline__ void sts128(uint32_t addr, uint4 v) {
    asm volatile("st.shared.v4.u32 [%0], {%1,%2,%3,%4};" :: "r"(addr), "r"(v.x), "r"(v.y), "r"(v.z), "r"(v.w) : "memory");
}
__device__ __forceinline__ void sts64f(uint32_t addr, float a, float b) {
    asm volatile("st.shared.v2.f32 [%0], {%1,%2};" :: "r"(addr), "f"(a), "f"(b) : "memory");
}

__device__ __forceinline__ uint64_t stream_policy() {
    uint64_t p;
    asm("createpolicy.fractional.L2::evict_first.b64 %0, 1.0;" : "=l"(p));
    return p;
}
__device__ __forceinline__ void tma_2d(uint32_t dst, const CUtensorMap* m, uint32_t bar, int c0, int c1, uint64_t pol) {
    asm volatile("cp.async.bulk.tensor.2d.shared::cluster.global.mbarrier::complete_tx::bytes.L2::cache_hint"
                 " [%0], [%1, {%3, %4}], [%2], %5;"
                 :: "r"(dst), "l"(m), "r"(bar), "r"(c0), "r"(c1), "l"(pol) : "memory");
}
__device__ __forceinline__ void tma_3d(uint32_t dst, const CUtensorMap* m, uint32_t bar, int c0, int c1, int c2, uint64_t pol) {
    asm volatile("cp.async.bulk.tensor.3d.shared::cluster.global.mbarrier::complete_tx::bytes.L2::cache_hint"
                 " [%0], [%1, {%3, %4, %5}], [%2], %6;"
                 :: "r"(dst), "l"(m), "r"(bar), "r"(c0), "r"(c1), "r"(c2), "l"(pol) : "memory");
}
__device__ __forceinline__ void tma_3d_mc(uint32_t dst, const CUtensorMap* m, uint32_t bar, int c1, int c2, uint64_t pol) {
    asm volatile("cp.async.bulk.tensor.3d.shared::cluster.global.mbarrier::complete_tx::bytes.multicast::cluster.L2::cache_hint"
                 " [%0], [%1, {%3, %4, %5}], [%2], %6, %7;"
                 :: "r"(dst), "l"(m), "r"(bar), "r"(0), "r"(c1), "r"(c2), "h"((uint16_t)3), "l"(pol) : "memory");
}
__device__ __forceinline__ void load_stage1(uint32_t dst, uint32_t dst_b, uint32_t bar, const CUtensorMap* ma, const CUtensorMap* mb,
                                            int k, int row, int col, int keep_a, uint64_t pol) {
    asm volatile("{\n.reg .pred e, p, q;\nelect.sync _|e, 0xffffffff;\nsetp.ne.and.b32 p|q, %8, 0, e;\n"
        "@p cp.async.bulk.tensor.2d.shared::cluster.global.mbarrier::complete_tx::bytes [%0], [%3, {%5, %6}], [%2];\n"
        "@q cp.async.bulk.tensor.2d.shared::cluster.global.mbarrier::complete_tx::bytes.L2::cache_hint [%0], [%3, {%5, %6}], [%2], %9;\n"
        "@e cp.async.bulk.tensor.3d.shared::cluster.global.mbarrier::complete_tx::bytes.multicast::cluster.L2::cache_hint"
        " [%1], [%4, {%10, %5, %7}], [%2], %11, %9;\n"
        "@e mbarrier.arrive.expect_tx.shared::cta.b64 _, [%2], %12;\n}"
        :: "r"(dst), "r"(dst_b), "r"(bar), "l"(ma), "l"(mb), "r"(k), "r"(row), "r"(col), "r"(keep_a), "l"(pol), "r"(0),
           "h"((uint16_t)3), "n"(G1_STAGE_BYTES) : "memory");
}
__device__ __forceinline__ void load_stage2(uint32_t dst, uint32_t dst_b, uint32_t bar, const CUtensorMap* ma, const CUtensorMap* mb,
                                            int ka, int row, int col, int kb, uint64_t pol) {
    asm volatile("{\n.reg .pred e;\nelect.sync _|e, 0xffffffff;\n"
        "@e cp.async.bulk.tensor.3d.shared::cluster.global.mbarrier::complete_tx::bytes.L2::cache_hint [%0], [%3, {%5, %10, %6}], [%2], %9;\n"
        "@e cp.async.bulk.tensor.5d.shared::cluster.global.mbarrier::complete_tx::bytes.multicast::cluster.L2::cache_hint"
        " [%1], [%4, {%7, %10, %10, %10, %8}], [%2], %11, %9;\n"
        "@e mbarrier.arrive.expect_tx.shared::cta.b64 _, [%2], %12;\n}"
        :: "r"(dst), "r"(dst_b), "r"(bar), "l"(ma), "l"(mb), "r"(ka), "r"(row), "r"(col), "r"(kb), "l"(pol), "r"(0),
           "h"((uint16_t)3), "n"(G2_STAGE_BYTES) : "memory");
}
__device__ __forceinline__ void tma_store_2d(const CUtensorMap* m, uint32_t src, int c0, int c1) {
    asm volatile("cp.async.bulk.tensor.2d.global.shared::cta.bulk_group [%0, {%2, %3}], [%1];"
                 :: "l"(m), "r"(src), "r"(c0), "r"(c1) : "memory");
}
__device__ __forceinline__ uint4 ldg_stream(const void* p, uint64_t pol) {
    uint4 v;
    asm volatile("ld.global.nc.L1::no_allocate.L2::cache_hint.v4.u32 {%0,%1,%2,%3}, [%4], %5;"
                 : "=r"(v.x), "=r"(v.y), "=r"(v.z), "=r"(v.w) : "l"(p), "l"(pol));
    return v;
}
__device__ __forceinline__ void st_tagged(void* p, float a, float b, uint32_t tag) {
    asm volatile("st.relaxed.gpu.global.v2.b32 [%0], {%1,%2};"
                 :: "l"(p), "r"((__float_as_uint(a) & ~3u) | tag), "r"((__float_as_uint(b) & ~3u) | tag) : "memory");
}
__device__ __forceinline__ bool untagged(const uint4& v, uint32_t tag) {
    return ((v.x ^ tag) | (v.y ^ tag) | (v.z ^ tag) | (v.w ^ tag)) & 3;
}
__device__ __forceinline__ uint4 ld_relaxed(const void* p) {
    uint4 v;
    asm volatile("ld.relaxed.gpu.global.v4.b32 {%0,%1,%2,%3}, [%4];" : "=r"(v.x), "=r"(v.y), "=r"(v.z), "=r"(v.w) : "l"(p) : "memory");
    return v;
}
__device__ __forceinline__ void prefetch_3d(const CUtensorMap* m, int c1, int c2, uint64_t pol) {
    asm volatile("cp.async.bulk.prefetch.tensor.3d.L2.global.L2::cache_hint [%0, {%1, %2, %3}], %4;"
                 :: "l"(m), "r"(0), "r"(c1), "r"(c2), "l"(pol) : "memory");
}
__device__ __forceinline__ void prefetch_map(const CUtensorMap* m) {
    asm volatile("prefetch.tensormap [%0];" :: "l"(m) : "memory");
}
template <int N> __device__ __forceinline__ void wg_wait() { asm volatile("wgmma.wait_group.sync.aligned %0;" :: "n"(N) : "memory"); }

__device__ __forceinline__ uint32_t desc_a(uint32_t addr) { return (addr & 0x3FFFF) >> 4 | 1 << 16; }
__device__ __forceinline__ uint32_t desc_b(uint32_t addr) { return (addr & 0x3FFFF) >> 4 | 512 << 16; }

#define R8(d, o) "+f"(d[o]), "+f"(d[o+1]), "+f"(d[o+2]), "+f"(d[o+3]), "+f"(d[o+4]), "+f"(d[o+5]), "+f"(d[o+6]), "+f"(d[o+7])
#define R32(d, o) R8(d, o), R8(d, o+8), R8(d, o+16), R8(d, o+24)
#define R64(d, o) R32(d, o), R32(d, o+32)
#define ACC0 "%0,%1,%2,%3,%4,%5,%6,%7,%8,%9,%10,%11,%12,%13,%14,%15,%16,%17,%18,%19,%20,%21,%22,%23,%24,%25,%26,%27,%28,%29,%30,%31,"\
    "%32,%33,%34,%35,%36,%37,%38,%39,%40,%41,%42,%43,%44,%45,%46,%47,%48,%49,%50,%51,%52,%53,%54,%55,%56,%57,%58,%59,%60,%61,%62,%63"
#define ACC1 "%64,%65,%66,%67,%68,%69,%70,%71,%72,%73,%74,%75,%76,%77,%78,%79,%80,%81,%82,%83,%84,%85,%86,%87,%88,%89,%90,%91,%92,%93,%94,%95,"\
    "%96,%97,%98,%99,%100,%101,%102,%103,%104,%105,%106,%107,%108,%109,%110,%111,%112,%113,%114,%115,%116,%117,%118,%119"
#define ACC64 "{" ACC0 "}"
#define ACC120 "{" ACC0 "," ACC1 "}"
#define ACC128 "{" ACC0 "," ACC1 ",%120,%121,%122,%123,%124,%125,%126,%127}"
#define MMA_K16(shape, acc, keep, hb, sb) \
    "mov.b64 da, {la, 0x40000040};\nmov.b64 db, {lb, " hb "};\n" \
    "wgmma.mma_async.sync.aligned." shape ".f32.bf16.bf16 " acc ", da, db, " keep ", 1, 1, 0, 1;\n" \
    "add.u32 la, la, 2;\nadd.u32 lb, lb, " sb ";\n"
#define MMA_STEP_B(shape, acc, a, b, off, keep, hb, sb) \
    "{\n.reg .pred p, q;\n.reg .b32 la, lb;\n.reg .b64 da, db;\nsetp.ne.b32 p, " keep ", 0;\nsetp.eq.b32 q, 0, 0;\n" \
    "add.u32 la, " a ", " off ";\nadd.u32 lb, " b ", " off ";\nwgmma.fence.sync.aligned;\n" \
    MMA_K16(shape, acc, "p", hb, sb) MMA_K16(shape, acc, "q", hb, sb) MMA_K16(shape, acc, "q", hb, sb) \
    MMA_K16(shape, acc, "q", hb, sb) "wgmma.commit_group.sync.aligned;\n}"
#define MMA_STEP(shape, acc, a, b, off, keep) MMA_STEP_B(shape, acc, a, b, off, keep, "0x40000040", "128")

__device__ __forceinline__ void mma_step(float (&d)[128], uint32_t da, uint32_t db, uint32_t off, int keep) {
    asm volatile(MMA_STEP("m64n256k16", ACC128, "%128", "%129", "%130", "%131")
                 : R64(d, 0), R64(d, 64) : "r"(da), "r"(db), "r"(off), "r"(keep) : "memory");
}
__device__ __forceinline__ void mma_step240(float (&d)[128], uint32_t da, uint32_t db, uint32_t off, int keep) {
    asm volatile(MMA_STEP("m64n240k16", ACC120, "%120", "%121", "%122", "%123")
                 : R64(d, 0), R32(d, 64), R8(d, 96), R8(d, 104), R8(d, 112) : "r"(da), "r"(db), "r"(off), "r"(keep) : "memory");
}
__device__ __forceinline__ void mma_step(float (&d)[64], uint32_t da, uint32_t db, uint32_t off, int keep) {
    asm volatile(MMA_STEP("m64n128k16", ACC64, "%64", "%65", "%66", "%67")
                 : R64(d, 0) : "r"(da), "r"(db), "r"(off), "r"(keep) : "memory");
}

__device__ __forceinline__ void mma_step_tail(float (&d)[64], uint32_t da, uint32_t b, uint32_t off) {
    asm volatile(MMA_STEP_B("m64n128k16", ACC64, "%64", "%65", "%66", "1", "0xC0000010", "32")
                 : R64(d, 0) : "r"(da), "r"((b & 0x3FFFF) >> 4 | 128 << 16), "r"(off) : "memory");
}

__device__ __forceinline__ uint32_t pack_bf16(float lo, float hi) {
    uint32_t r; asm("cvt.rn.bf16x2.f32 %0, %1, %2;" : "=r"(r) : "f"(hi), "f"(lo)); return r;
}
__device__ __forceinline__ float bf_lo(uint32_t v) { return __uint_as_float(v << 16); }
__device__ __forceinline__ float bf_hi(uint32_t v) { return __uint_as_float(v & 0xffff0000u); }
__device__ __forceinline__ float round_bf16(float v) { return bf_lo(pack_bf16(v, 0.f)); }
__device__ __forceinline__ uint32_t mul_bf16x2(uint32_t a, uint32_t b) {
    uint32_t r; asm("mul.rn.bf16x2 %0, %1, %2;" : "=r"(r) : "r"(a), "r"(b)); return r;
}
__device__ __forceinline__ uint32_t add_bf16x2(uint32_t a, uint32_t b) {
    uint32_t r; asm("add.rn.bf16x2 %0, %1, %2;" : "=r"(r) : "r"(a), "r"(b)); return r;
}
__device__ __forceinline__ uint32_t sub_bf16x2(uint32_t a, uint32_t b) {
    uint32_t r; asm("sub.rn.bf16x2 %0, %1, %2;" : "=r"(r) : "r"(a), "r"(b)); return r;
}
__device__ __forceinline__ uint32_t mul2_bf16x2(uint32_t a, uint32_t hi, uint32_t lo) {
    uint32_t r; asm("fma.rn.bf16x2 %0, %1, %2, %3;" : "=r"(r) : "r"(a), "r"(hi), "r"(mul_bf16x2(a, lo))); return r;
}
__device__ __forceinline__ float tanh_fast(float x) { float r; asm("tanh.approx.f32 %0, %1;" : "=f"(r) : "f"(x)); return r; }
__device__ __forceinline__ float gelu_tanh(float g) {
    float t = fmaf(g * g, 0.044715f * 0.7978845608f, 0.7978845608f) * g;
    float hg = 0.5f * g;
    return fmaf(hg, tanh_fast(t), hg);
}
__device__ __forceinline__ uint32_t geglu2(uint32_t g2, uint32_t u2) {
    return mul_bf16x2(pack_bf16(gelu_tanh(bf_lo(g2)), gelu_tanh(bf_hi(g2))), u2);
}
__device__ __forceinline__ float silu(float d) {
    float hd = 0.5f * d;
    return fmaf(hd, tanh_fast(hd), hd);
}
__device__ __forceinline__ float ex2_fast(float x) { float r; asm("ex2.approx.ftz.f32 %0, %1;" : "=f"(r) : "f"(x)); return r; }
__device__ __forceinline__ void unpack8(uint4 v, float (&f)[8]) {
    f[0] = bf_lo(v.x); f[1] = bf_hi(v.x); f[2] = bf_lo(v.y); f[3] = bf_hi(v.y);
    f[4] = bf_lo(v.z); f[5] = bf_hi(v.z); f[6] = bf_lo(v.w); f[7] = bf_hi(v.w);
}
template <int N> __device__ __forceinline__ void fence_regs(float (&d)[N]) {
#pragma unroll
    for (int i = 0; i < N; i++) asm volatile("" : "+f"(d[i]) :: "memory");
}

__device__ __forceinline__ float rcp_fast(float x) { float r; asm("rcp.approx.ftz.f32 %0, %1;" : "=f"(r) : "f"(x)); return r; }
__device__ __forceinline__ float sqrt_fast(float x) { float r; asm("sqrt.approx.ftz.f32 %0, %1;" : "=f"(r) : "f"(x)); return r; }
__device__ __forceinline__ uint32_t max_bf16x2(uint32_t a, uint32_t b) {
    uint32_t r; asm("max.bf16x2 %0, %1, %2;" : "=r"(r) : "r"(a), "r"(b)); return r;
}
__device__ __forceinline__ uint4 ldsm4(uint32_t addr) {
    uint4 v;
    asm volatile("ldmatrix.sync.aligned.m8n8.x4.shared.b16 {%0,%1,%2,%3}, [%4];"
                 : "=r"(v.x), "=r"(v.y), "=r"(v.z), "=r"(v.w) : "r"(addr) : "memory");
    return v;
}
__device__ __forceinline__ uint4 ldsm4_t(uint32_t addr) {
    uint4 v;
    asm volatile("ldmatrix.sync.aligned.m8n8.x4.trans.shared.b16 {%0,%1,%2,%3}, [%4];"
                 : "=r"(v.x), "=r"(v.y), "=r"(v.z), "=r"(v.w) : "r"(addr) : "memory");
    return v;
}
__device__ __forceinline__ void mma_16816(float (&c)[4], uint32_t a0, uint32_t a1, uint32_t a2, uint32_t a3, uint32_t b0, uint32_t b1) {
    asm("mma.sync.aligned.m16n8k16.row.col.f32.bf16.bf16.f32 {%0,%1,%2,%3}, {%4,%5,%6,%7}, {%8,%9}, {%0,%1,%2,%3};"
        : "+f"(c[0]), "+f"(c[1]), "+f"(c[2]), "+f"(c[3]) : "r"(a0), "r"(a1), "r"(a2), "r"(a3), "r"(b0), "r"(b1));
}
__device__ __forceinline__ void mma_1688(float (&c)[4], uint32_t a0, uint32_t a1, uint32_t b0) {
    asm("mma.sync.aligned.m16n8k8.row.col.f32.bf16.bf16.f32 {%0,%1,%2,%3}, {%4,%5}, {%6}, {%0,%1,%2,%3};"
        : "+f"(c[0]), "+f"(c[1]), "+f"(c[2]), "+f"(c[3]) : "r"(a0), "r"(a1), "r"(b0));
}
__device__ __forceinline__ void qk_tile(float (&c)[4], const uint4& q0, const uint4& q1, const uint4& k, float init) {
    c[0] = c[1] = c[2] = c[3] = init;
    mma_16816(c, q0.x, q0.y, q0.z, q0.w, k.x, k.y);
    mma_16816(c, q1.x, q1.y, q1.z, q1.w, k.z, k.w);
}
__device__ __forceinline__ uint32_t scaled_logits(bool first, float a0, float a1, float b0, float b1) {
    return mul2_bf16x2(pack_bf16(first ? a0 : b0, first ? a1 : b1), 0x3e353e35u, 0x379e379eu);
}
template <typename T> __device__ __forceinline__ T uniform(T v) { return __shfl_sync(0xffffffffu, v, 0); }

__device__ __forceinline__ void attention(const CUtensorMap* maps, uint32_t base, uint32_t zero, unsigned epoch, int grp, int warp,
                                          int lane) {
    constexpr float LOG2E = 1.4426950408889634f;
    const int g = lane >> 2, t = lane & 3;
    const bool up0 = 2 * t > g, up1 = 2 * t + 1 > g;
    const uint32_t keep = (up0 ? 0x0000ffffu : 0u) | (up1 ? 0xffff0000u : 0u);
    const uint32_t buf = base + warp * 2 * ATT_SLOT, bar = base + AUX_OFF + warp * 16;
    const uint32_t qoff = (lane & 15) * 128 + (((lane >> 4) ^ (lane & 7)) << 4);
    const uint32_t koff = 2048 + (lane & 7) * 128 + (((lane >> 3) ^ (lane & 7)) << 4);
    const uint32_t rest_bar = base + AUX_OFF + 192;
    const int col = uniform(grp * 256), first = uniform((warp / 3 * 32 + warp % 3 * 11) * 16);
    const CUtensorMap* const mqk = reinterpret_cast<const CUtensorMap*>(uniform(reinterpret_cast<uint64_t>(maps)));
    const CUtensorMap *const mv = mqk + 1, *const mo = mqk + 2;
    const uint64_t pol = stream_policy();
    uint4 kp[2], vp[2];
    uint32_t l0[2], l1[2], m[2];
    float s[2][3][4];
    auto scores = [&](uint32_t st, int row) {
        const float before = (row & 1023) == 0 ? -5.656854e9f : 0.f;
#pragma unroll
        for (int h = 0; h < 2; h++) {
            const uint4 q0 = ldsm4(st + (qoff ^ (h * 64))), q1 = ldsm4(st + (qoff ^ (h * 64 + 32)));
            const uint4 k0 = ldsm4(st + (koff ^ (h * 64))), k1 = ldsm4(st + 1024 + (koff ^ (h * 64)));
            qk_tile(s[h][0], q0, q1, kp[h], before);
            qk_tile(s[h][1], q0, q1, k0, 0.f);
            qk_tile(s[h][2], q0, q1, k1, 0.f);
            kp[h] = k1;
        }
    };
    auto logits = [&]() {
#pragma unroll
        for (int h = 0; h < 2; h++) {
            l0[h] = scaled_logits(up0, s[h][0][0], s[h][1][2], s[h][1][0], s[h][2][2]);
            l1[h] = scaled_logits(up1, s[h][0][1], s[h][1][3], s[h][1][1], s[h][2][3]);
            m[h] = max_bf16x2(l0[h], l1[h]);
            m[h] = max_bf16x2(m[h], __shfl_xor_sync(0xffffffffu, m[h], 1));
        }
    };
    auto row_max = [&]() {
#pragma unroll
        for (int h = 0; h < 2; h++) m[h] = max_bf16x2(m[h], __shfl_xor_sync(0xffffffffu, m[h], 2));
    };
    auto next = [](uint32_t p) {
        return (0x80200400u >> (p >> 4 & 31) & 1) > (p >> 15 & 1) ? p + (64 << 16) + 0x8000 : (p + 16) & ~0x8800u;
    };
    auto exchange = [&](uint32_t st, uint32_t b, uint32_t po, uint32_t pv, uint32_t pq) {
        asm volatile("{\n.reg .pred e, p, q;\n"
            "fence.proxy.async.shared::cta;\n"
            "bar.warp.sync 0xffffffff;\n"
            "elect.sync _|e, 0xffffffff;\n"
            "setp.eq.and.b32 p, %12, 0, e;\n"
            "setp.lt.and.s32 q, %8, %13, e;\n"
            "@q mbarrier.arrive.expect_tx.shared::cta.b64 _, [%2], 6144;\n"
            "@q cp.async.bulk.tensor.3d.shared::cluster.global.mbarrier::complete_tx::bytes.L2::cache_hint [%0], [%3, {%6, %7, %14}], [%2], %15;\n"
            "@q cp.async.bulk.tensor.2d.shared::cluster.global.mbarrier::complete_tx::bytes.L2::cache_hint [%0 + 4096], [%4, {%8, %9}], [%2], %15;\n"
            "@e cp.async.bulk.wait_group.read 0;\n"
            "@p cp.async.bulk.tensor.2d.global.shared::cta.bulk_group [%5, {%10, %11}], [%1 + 6144];\n"
            "@e cp.async.bulk.commit_group;\n"
            "bar.warp.sync 0xffffffff;\n}"
            :: "r"(st), "r"(st ^ ATT_SLOT), "r"(b), "l"(mqk), "l"(mv), "l"(mo), "r"(pq >> 16), "r"(pq & 2047),
               "r"((pv >> 16) + 2 * DM), "r"(pv & 2047), "r"(po >> 16), "r"(po & 2047), "r"(po & 0x8000),
               "r"(col + 256 + 2 * DM), "r"(0), "l"(pol) : "memory");
    };
    auto publish = [&](auto pending, int part) {
        asm volatile("{\n.reg .pred e;\n.reg .u32 n;\n"
            "elect.sync _|e, 0xffffffff;\n"
            "cp.async.bulk.wait_group %2;\n"
            "@e atom.acq_rel.cta.shared.add.u32 n, [%1], 1;\n"
            "setp.eq.and.u32 e, n, 11, e;\n"
            "@e red.release.gpu.global.add.u32 [%0], 1;\n}"
            :: "l"(g_flags + F_O * 512 + part * 32), "r"(rest_bar + 8 + part * 4), "n"(pending.value) : "memory");
    };
    if (elect_one()) {
        mbar_init(bar, 1); mbar_init(bar + 8, 1);
        if (warp == 2) { mbar_init(rest_bar, 32); sts64f(rest_bar + 8, 0.f, 0.f); }
        asm volatile("fence.mbarrier_init.release.cluster;" ::: "memory");
        prefetch_map(mqk); prefetch_map(mv); prefetch_map(mo);
    }
    __syncthreads();
    if (warp == 11 && lane < 4) flag_add(g_flags + F_QKV * 512 + 128 + lane * 32);
    if (elect_one()) {
        g_epoch[blockIdx.x * 16] = epoch;
        flag_wait(g_flags + F_QKV * 512 + grp * 32, epoch * CNT_QKV);
        fence_proxy_async();
        mbar_expect_tx(bar + 8, 8192);
        tma_3d(buf + ATT_SLOT, mqk, bar + 8, col, first, 0, pol);
        tma_2d(buf + ATT_SLOT + 4096, mv, bar + 8, col + 2 * DM, first - 16, pol);
        tma_2d(buf + ATT_SLOT + 6144, mv, bar + 8, col + DM, first - 16, pol);
        mbar_expect_tx(bar, 6144);
        tma_3d(buf, mqk, bar, col, first + 16, 0, pol);
        tma_2d(buf + 4096, mv, bar, col + 2 * DM, first, pol);
        if (warp == 0) TRACE(9);
    }
    __syncwarp();
    mbar_wait(bar + 8, 0);
#pragma unroll
    for (int h = 0; h < 2; h++) {
        kp[h] = ldsm4(buf + ATT_SLOT + 5120 + (koff ^ (h * 64)));
        vp[h] = ldsm4_t(buf + ATT_SLOT + 3072 + (koff ^ (h * 64)));
    }
    scores(buf + ATT_SLOT, first);
    uint32_t pm = 0x8000, p0 = col << 16 | first, p1 = p0 + 16, p2 = p0 + 32, p3 = p0 + 48;
    exchange(buf + ATT_SLOT, bar + 8, pm, p1, p2);
    logits();
    row_max();
    uint32_t st = buf, b = bar, cnt = 1;
    const uint32_t relay = warp == 2 ? 7 : 0;
    bool ready = false;
#pragma unroll 1
    while (p0 >> 16 < col + 256) {
        uint32_t pa[2], pb[2];
        if (!ready) mbar_wait(b, (cnt >> 1) & 1);
        uint4 v[2][2];
#pragma unroll
        for (int h = 0; h < 2; h++) {
            const float ma = -LOG2E * bf_lo(m[h]), mb = -LOG2E * bf_hi(m[h]);
            const float a0 = ex2_fast(fmaf(bf_lo(l0[h]), LOG2E, ma)), a1 = ex2_fast(fmaf(bf_lo(l1[h]), LOG2E, ma));
            const float b0 = ex2_fast(fmaf(bf_hi(l0[h]), LOG2E, mb)), b1 = ex2_fast(fmaf(bf_hi(l1[h]), LOG2E, mb));
            float sum[4] = {0.f, 0.f, 0.f, 0.f};
            mma_1688(sum, pack_bf16(a0, a1), pack_bf16(b0, b1), 0x3f803f80u);
            const float ra = rcp_fast(sum[0]), rb = rcp_fast(sum[2]);
            pa[h] = pack_bf16(a0 * ra, a1 * ra);
            pb[h] = pack_bf16(b0 * rb, b1 * rb);
        }
        scores(st, p1);
#pragma unroll
        for (int h = 0; h < 2; h++) {
            v[h][0] = ldsm4_t(st + 4096 + (qoff ^ (h * 64)));
            v[h][1] = ldsm4_t(st + 4096 + (qoff ^ (h * 64 + 32)));
        }
        if (cnt == relay) {
            flag_wait<true>(g_flags + F_QKV * 512 + 128 + grp * 32, epoch * CNT_REST);
            fence_proxy_async();
            mbar_arrive(rest_bar);
        }
        if (cnt == 8) {
#pragma unroll 1
            for (int spins = 0; !__all_sync(0xffffffffu, mbar_try_wait(rest_bar, 0)) && spins < (1 << 17); spins++) {}
        }
        if (cnt == 37) publish(std::integral_constant<int, 1>(), 0);
        exchange(st, b, pm, p2, p3);
        pm = p0; p0 = p1; p1 = p2; p2 = p3; p3 = next(p3);
        logits();
        float o[2][4][4];
#pragma unroll
        for (int h = 0; h < 2; h++) {
            const uint32_t prev[4] = {vp[h].x, vp[h].y, vp[h].z, vp[h].w};
            const uint32_t own[8] = {v[h][0].x, v[h][0].y, v[h][0].z, v[h][0].w, v[h][1].x, v[h][1].y, v[h][1].z, v[h][1].w};
            const uint32_t a0 = pa[h] & keep, a1 = pa[h] & ~keep, a2 = pb[h] & keep, a3 = pb[h] & ~keep;
            const uint32_t z0 = pa[h] & zero, z1 = pb[h] & zero;
#pragma unroll
            for (int j = 0; j < 4; j++) {
                o[h][j][0] = o[h][j][1] = o[h][j][2] = o[h][j][3] = 0.f;
                mma_1688(o[h][j], a0, z0, prev[j]);
                mma_16816(o[h][j], a1, a2, z1, a3, own[2 * j], own[2 * j + 1]);
            }
            vp[h] = make_uint4(own[1], own[3], own[5], own[7]);
        }
        row_max();
        b ^= 8; cnt++;
        ready = mbar_test(b, (cnt >> 1) & 1);
#pragma unroll
        for (int h = 0; h < 2; h++) {
#pragma unroll
            for (int d = 0; d < 2; d++)
                asm volatile("stmatrix.sync.aligned.m8n8.x4.shared.b16 [%0], {%1,%2,%3,%4};"
                             :: "r"(st + 6144 + (qoff ^ (h * 64 + d * 32))),
                                "r"(pack_bf16(o[h][2 * d][0], o[h][2 * d][1])), "r"(pack_bf16(o[h][2 * d][2], o[h][2 * d][3])),
                                "r"(pack_bf16(o[h][2 * d + 1][0], o[h][2 * d + 1][1])),
                                "r"(pack_bf16(o[h][2 * d + 1][2], o[h][2 * d + 1][3])) : "memory");
        }
        st ^= ATT_SLOT;
    }
    exchange(st, b, pm, p0, p0);
    publish(std::integral_constant<int, 0>(), 1);
    if (threadIdx.x == 0) TRACE(10);
}

struct Params {
    CUtensorMap x, xn, wtail, wqkv, wg, wu, qk, v, o, a2, wo, wd, out;
    const __nv_bfloat16* px;
    uint32_t zero;
    uint32_t role[NCTA];
};

__device__ __forceinline__ void tail_gemm(const Params& prm, uint32_t base, uint32_t tag, int grp, int warp, int lane) {
    const uint32_t full = base + BAR_OFF, empty = full + 32, sum_bar = full + 64, colsum = full + 512;
    if (threadIdx.x == 0) {
        for (int s = 0; s < G1_STAGES; s++) { mbar_init(full + s * 8, 1); mbar_init(empty + s * 8, 4); }
        mbar_init(sum_bar, 2);
        asm volatile("fence.mbarrier_init.release.cluster;" ::: "memory");
    }
    __syncthreads();
    if (warp == 8) {
        if (elect_one()) {
#pragma unroll 1
            for (int i = 0; i < 32; i++) {
                const uint32_t dst = base + (i & 3) * G1_STAGE_BYTES, bar = full + (i & 3) * 8;
                mbar_wait(bar + 32, ~i >> 2 & 1);
                mbar_expect_tx(bar, G1_STAGE_BYTES);
                tma_2d(dst, &prm.x, bar, (i & 15) * 64, grp * 512 + (i >> 4) * 256, stream_policy());
                tma_2d(dst + 16384, &prm.x, bar, (i & 15) * 64, grp * 512 + (i >> 4) * 256 + 128, stream_policy());
                tma_3d(dst + 32768, &prm.wtail, bar, 0, (i & 15) * 64, 0, stream_policy());
            }
        }
    } else if (warp >= 10) {
        float cs[8];
#pragma unroll
        for (int d = 0; d < 8; d++) cs[d] = 0.f;
        const uint32_t wa = base + 32768 + (warp - 10) * 8192 + (lane >> 3) * 2048 + (lane & 7) * 16;
#pragma unroll 1
        for (int i = 0; i < 28; i++) {
            mbar_wait(full + (i & 3) * 8, i >> 2 & 1);
            if (i < 16) {
#pragma unroll
                for (int j = 0; j < 16; j++) {
                    float f[8];
                    unpack8(lds128((wa ^ (j & 1) * 16) + (i & 3) * G1_STAGE_BYTES + j * 128), f);
#pragma unroll
                    for (int d = 0; d < 8; d++) cs[d] += f[d];
                }
            }
            if (i == 15) {
#pragma unroll
                for (int d = 0; d < 8; d++) {
                    cs[d] += __shfl_xor_sync(0xffffffffu, cs[d], 2);
                    cs[d] += __shfl_xor_sync(0xffffffffu, cs[d], 4);
                }
#pragma unroll
                for (int d = 0; d < 8; d += 2)
                    sts64f(colsum + (warp - 10) * 256 + (lane >> 3) * 64 + (lane & 1) * 32 + d * 4, cs[d], cs[d + 1]);
            }
            __syncwarp();
            if (lane == 0) {
                mbar_arrive(empty + (i & 3) * 8);
                if (i == 15) mbar_arrive(sum_bar);
            }
        }
    } else if (warp < 8) {
        const uint32_t da = desc_a(base + (warp >> 2) * 16384);
#pragma unroll 1
        for (int pass = 0; pass < 2; pass++) {
            float acc[2][64];
#pragma unroll
            for (int i = 0; i < 64; i++) acc[0][i] = acc[1][i] = 0.f;
#pragma unroll 1
            for (int k = 0; k < G1_KSTEPS; k++) {
                mbar_wait(full + (k & 3) * 8, k >> 2 & 1);
                mma_step_tail(acc[0], da, base + 32768, (k & 3) * (G1_STAGE_BYTES / 16));
                mma_step_tail(acc[1], da + 512, base + 32768, (k & 3) * (G1_STAGE_BYTES / 16));
                wg_wait<2>();
                if (k > 0 && (threadIdx.x & 127) == 0) mbar_arrive(empty + (k - 1 & 3) * 8);
            }
            wg_wait<0>();
            fence_regs(acc[0]); fence_regs(acc[1]);
            if ((threadIdx.x & 127) == 0) mbar_arrive(empty + 24);
            mbar_wait(sum_bar, 0);
#pragma unroll
            for (int r = 0; r < 4; r++) {
                const int row = grp * 512 + pass * 256 + (warp >> 2) * 128 + r / 2 * 64 + (warp & 3) * 16 + r % 2 * 8 + (lane >> 2);
                uint4 st = make_uint4(0, 0, 0, 0);
#pragma unroll 1
                for (int spins = 0; untagged(st, tag) && spins < (1 << 16); spins++) st = ld_relaxed(g_stats + (row & ~1));
                const float shift = __uint_as_float((row & 1 ? st.z : st.x) ^ tag), inv = __uint_as_float((row & 1 ? st.w : st.y) ^ tag);
                __nv_bfloat16* const p = g_qkv + ((row & 1) * (SEQ / 2) + row / 2) * NQKV + 240 + (lane & 3) * 4;
#pragma unroll
                for (int q = 0; q < 8; q++) {
                    const float* a = acc[r / 2] + 8 * q + r % 2 * 2;
                    const float2 c0 = lds64f(colsum + q * 64 + (lane & 3) * 8), c1 = lds64f(colsum + q * 64 + 32 + (lane & 3) * 8);
                    *reinterpret_cast<uint2*>(p + q * 256) =
                        make_uint2(pack_bf16(fmaf(shift, c0.x, a[0]) * inv, fmaf(shift, c0.y, a[1]) * inv),
                                   pack_bf16(fmaf(shift, c1.x, a[4]) * inv, fmaf(shift, c1.y, a[5]) * inv));
                }
            }
            if (threadIdx.x == 0) TRACE(50 + pass);
        }
    }
}

__device__ __forceinline__ bool tile_is_qkv(int nt) { return nt < 4 || (nt >= 8 && nt < 16); }
__device__ __forceinline__ int tile_index(int nt) { return nt < 4 ? nt + 8 : (nt < 8 ? nt - 4 : (nt < 16 ? nt - 8 : nt - 12)); }

__global__ void __cluster_dims__(2, 1, 1) __launch_bounds__(384, 1)
fused_kernel(const __grid_constant__ Params prm) {
    extern __shared__ __align__(1024) uint8_t smem_raw[];
    const uint32_t base = smem_u32(smem_raw) & ~1023u;
    const uint32_t bars = base + BAR_OFF;
    auto full1 = [&](int s) { return bars + s * 8; };
    auto empty1 = [&](int s) { return bars + 32 + s * 8; };
    auto full2 = [&](int s) { return bars + 64 + s * 8; };
    auto empty2 = [&](int s) { return bars + 128 + s * 8; };
    const uint32_t sig_bar = bars + 192, dep_bar = bars + 256, cs_bar = bars + 304, fold_bar = bars + 320, x_bar = bars + 336;
    const uint32_t colsum = bars + 512, stats = bars + 1536;
    auto stage2 = [&](int q) { return base + q * G2_STAGE_BYTES; };
    const uint32_t aux = base + AUX_OFF;

    const int warp = __shfl_sync(0xffffffffu, threadIdx.x >> 5, 0);
    const int lane = threadIdx.x & 31;
    const int rank = blockIdx.x & 1;
    const uint32_t role = prm.role[blockIdx.x];
    const int mblk = role & 15, nslot = role >> 4;

    if (blockIdx.x >= NGEMM) {
        if (threadIdx.x == 0) { TRACE_GT(0); TRACE(1); }
        const unsigned epoch = __ldcg(g_epoch + blockIdx.x * 16) + 1;
        tail_gemm(prm, base, 1 + (epoch & 1), blockIdx.x - NGEMM, warp, lane);
        attention(&prm.qk, (base + 2 * ATT_SLOT - 1) & ~(2u * ATT_SLOT - 1), prm.zero, epoch, blockIdx.x - NGEMM, warp, lane);
    } else if (warp >= 8) {
        unsigned* const flags = g_flags + mblk * 32;
        const CUtensorMap* const w0 = nslot < 4 ? &prm.wqkv : (rank ? &prm.wu : &prm.wg);
        const int w0_col = nslot < 4 ? 32 + nslot * 4 + rank * 2 : nslot * 2 - 8;
        if (elect_one()) {
            if (warp == 8) {
                TRACE_GT(0); TRACE(1);
                prefetch_map(&prm.x); prefetch_map(w0);
                for (int s = 0; s < G1_STAGES; s++) { mbar_init(full1(s), 1); mbar_init(empty1(s), 4); }
            } else if (warp == 9) {
                for (int s = 0; s < G2_STAGES; s++) { mbar_init(full2(s), 1); mbar_init(empty2(s), 4); }
            } else if (warp == 10) {
                for (int s = 0; s < 7; s++) mbar_init(sig_bar + s * 8, 8);
                mbar_init(fold_bar, 2); mbar_init(x_bar, 1);
            } else {
                for (int s = 0; s < 8; s++) mbar_init(dep_bar + s * 8, 1);
                TRACE_CLEAR();
            }
            asm volatile("fence.mbarrier_init.release.cluster;" ::: "memory");
        }
        __syncwarp();
        asm volatile("barrier.cluster.arrive.relaxed.aligned;" ::: "memory");
        if (warp == 8 && lane == 0) {
            mbar_expect_tx(full1(0), G1_STAGE_BYTES);
            tma_2d(base, &prm.x, full1(0), 0, mblk * 128, stream_policy());
            prefetch_3d(w0, 0, w0_col, stream_policy());
            TRACE(15);
        }
        asm volatile("setmaxnreg.dec.sync.aligned.u32 %0;" :: "n"(AUX_REGS));
        asm volatile("barrier.cluster.wait.acquire.aligned;" ::: "memory");

        if (warp == 8) {
            if (elect_one()) { TRACE(2); tma_3d_mc(base + A_BYTES + rank * 16384, w0, full1(0), 0, w0_col, stream_policy()); }
            uint32_t ph = 1;
#pragma unroll 1
            for (int t = 0; t < G1_TILES; t++) {
                const int nt = t * 8 + nslot;
                const CUtensorMap* const mb = tile_is_qkv(nt) ? &prm.wqkv : (rank ? &prm.wu : &prm.wg);
                const int col = tile_is_qkv(nt) ? tile_index(nt) * 4 + rank * 2 : tile_index(nt) * 2;
                if (t == 1) { TRACE(14); mbar_wait_warp(dep_bar, 0); TRACE(3); }
#pragma unroll 1
                for (int k = t == 0; k < G1_KSTEPS; k++) {
                    const int s = k & 3;
                    if (t == 0 && k == G1_STAGES && elect_one()) {
                        prefetch_map(&prm.xn); prefetch_map(&prm.wqkv); prefetch_map(&prm.wu); prefetch_map(&prm.wg);
                        prefetch_map(&prm.a2); prefetch_map(&prm.wo); prefetch_map(&prm.wd); prefetch_map(&prm.out);
                    }
                    mbar_wait_warp(empty1(s), ph);
                    const uint32_t sa = base + s * G1_STAGE_BYTES;
                    load_stage1(sa, sa + A_BYTES + rank * 16384, full1(s), t ? &prm.xn : &prm.x, mb, k * 64, mblk * 128, col,
                                t & 3, stream_policy());
                    if (s == 3) ph ^= 1;
                }
            }
            if (elect_one()) {
                mbar_expect_tx(x_bar, 32768);
                tma_2d(aux, &prm.x, x_bar, nslot * 128, mblk * 128, stream_policy());
                tma_2d(aux + 16384, &prm.x, x_bar, nslot * 128 + 64, mblk * 128, stream_policy());
            }
            TRACE(4);
            mbar_wait_warp(dep_bar + 8, 0);
            TRACE(5);
            int q = 0; uint32_t ph2 = 1;
#pragma unroll 1
            for (int u = 0; u < G2_KSTEPS; u++) {
                if (u == G2_LATE || u == G2_DSTEPS || u == G2_LAST) {
                    TRACE(u == G2_LATE ? 6 : (u == G2_DSTEPS ? 32 : 40));
                    mbar_wait_warp(dep_bar + (u == G2_LATE ? 16 : (u == G2_DSTEPS ? 24 : 32)), 0);
                    TRACE(u == G2_LATE ? 7 : (u == G2_DSTEPS ? 33 : 41));
                }
                const uint32_t sa = stage2(q);
                const bool down = u < G2_DSTEPS;
                const int k = down ? u : (u & 3) * 4 + (u - G2_DSTEPS) / 4;
                mbar_wait_warp(u < G2_STAGES ? empty1((u * 2 + 1) / 3) : empty2(q), u < G2_STAGES ? ph : ph2);
                load_stage2(sa, sa + A_BYTES + rank * 8192, full2(q), &prm.a2, down ? &prm.wd : &prm.wo, (down ? DM : 0) + k * 64,
                            mblk * 64, nslot * 128 + rank * 64, k * 2, stream_policy());
                if (++q == G2_STAGES) { q = 0; ph2 ^= 1; }
            }
            TRACE(8);
        } else if (warp == 9) {
            if (lane == 0) {
                const unsigned epoch = __ldcg(g_epoch + blockIdx.x * 16 + 2) + 1;
                mbar_wait(sig_bar, 0);
                TRACE(11);
                flag_add(flags + F_LN * 512);
                TRACE(42);
                flag_wait(flags + F_LN * 512, epoch * CNT_LN);
                fence_proxy_async();
                mbar_arrive(dep_bar);
                g_epoch[blockIdx.x * 16 + 2] = epoch;
                for (int p = nslot < 4 ? 2 : 1; p < 7; p++) {
                    mbar_wait(sig_bar + p * 8, 0);
                    if (p == 2) TRACE(37);
                    flag_add(p == 2 || p == 3 ? g_flags + F_QKV * 512 + (p * 4 - 8 + (nslot & 3)) * 32
                                              : flags + (p < 6 ? F_EARLY : F_LATE) * 512);
                    if (p == 2) TRACE(43);
                }
            }
        } else {
            const int w = warp - 10;
            const unsigned epoch = __ldcg(g_epoch + blockIdx.x * 16 + w) + 1;
            const uint32_t tag = 1 + (epoch & 1);
            mbar_wait(CSAT, 0);
            if (elect_one()) {
                mbar_expect_tx(cs_bar + w * 8, 16384);
                tma_3d(aux + w * 16384, w0, cs_bar + w * 8, 0, ((mblk & ~1) + w) * 64, w0_col, stream_policy());
            }
            float cs[8];
#pragma unroll
            for (int d = 0; d < 8; d++) cs[d] = 0.f;
            const uint32_t wa = aux + w * 8192 + (lane >> 3) * 128 + (((lane & 7) ^ (lane >> 3)) << 4);
            uint4 v[9];
            auto fetch = [&](int h, int i) {
#pragma unroll
                for (int j = 0; j < 4; j++) v[h * 4 + j] = lds128((wa ^ (j & 1) * 64) + h * 16384 + i * 2048 + j * 512);
            };
            auto add = [&](int h) {
#pragma unroll
                for (int j = 0; j < 4; j++) {
                    float f[8];
                    unpack8(v[h * 4 + j], f);
#pragma unroll
                    for (int d = 0; d < 8; d++) cs[d] += f[d];
                }
            };
            mbar_wait(cs_bar, 0);
            fetch(0, 0);
            mbar_wait(cs_bar + 8, 0);
            if (w == 0 && lane == 0) TRACE(36);
#pragma unroll 1
            for (int i = 0; i < 4; i++) {
                fetch(1, i);
                add(0);
                fetch(0, (i + 1) & 3);
                add(1);
            }
#pragma unroll
            for (int d = 0; d < 4; d++)
                cs[d] = (lane & 16 ? cs[d + 4] : cs[d]) + __shfl_xor_sync(0xffffffffu, lane & 16 ? cs[d] : cs[d + 4], 16);
#pragma unroll
            for (int d = 0; d < 2; d++)
                cs[d] = (lane & 8 ? cs[d + 2] : cs[d]) + __shfl_xor_sync(0xffffffffu, lane & 8 ? cs[d] : cs[d + 2], 8);
            st_tagged(g_colsum + (nslot * 2 + rank) * 1024 + (mblk >> 1) * 128 + w * 64 + (lane & 7) * 8 + (lane >> 3) * 2,
                      cs[0], cs[1], tag);
            if (w == 0 && lane == 0) TRACE(34);
#pragma unroll
            for (int m = 0; m < 9; m++) v[m] = make_uint4(0, 0, 0, 0);
#pragma unroll 1
            for (int spins = 0; spins < (1 << 16); spins++) {
                bool missing = false;
#pragma unroll
                for (int m = 0; m < 9; m++) {
                    if (untagged(v[m], tag)) {
                        missing = true;
                        v[m] = m < 8 ? ld_relaxed(g_colsum + (nslot * 2 + w) * 1024 + m * 128 + lane * 4)
                                     : ld_relaxed(g_stats + mblk * 128 + w * 64 + lane * 2);
                    }
                }
                if (!missing) break;
            }
            float4 c = make_float4(0.f, 0.f, 0.f, 0.f);
#pragma unroll
            for (int m = 0; m < 8; m++) {
                c.x += __uint_as_float(v[m].x ^ tag); c.y += __uint_as_float(v[m].y ^ tag);
                c.z += __uint_as_float(v[m].z ^ tag); c.w += __uint_as_float(v[m].w ^ tag);
            }
            sts128(stats + w * 512 + lane * 16, make_uint4(v[8].x ^ tag, v[8].y ^ tag, v[8].z ^ tag, v[8].w ^ tag));
            const uint32_t ca = colsum + (w * 8 + (lane >> 2)) * 64 + (lane & 1) * 32 + (lane & 2) * 4;
            sts64f(ca, c.y, c.x);
            sts64f(ca + 16, c.w, c.z);
            __syncwarp();
            if (lane == 0) {
                mbar_arrive(fold_bar);
                g_epoch[blockIdx.x * 16 + w] = epoch;
                if (w == 0) {
                    TRACE(35);
                    flag_wait(flags + F_EARLY * 512, epoch * CNT_EARLY);
                    fence_proxy_async(); mbar_arrive(dep_bar + 8);
                    flag_wait(flags + F_LATE * 512, epoch * CNT_LATE);
                    fence_proxy_async(); mbar_arrive(dep_bar + 16);
                    flag_wait(g_flags + F_O * 512, epoch * CNT_O);
                    fence_proxy_async(); mbar_arrive(dep_bar + 24);
                    flag_wait(g_flags + F_O * 512 + 32, epoch * CNT_O);
                    fence_proxy_async(); mbar_arrive(dep_bar + 32);
                }
            }
        }
    } else {
        asm volatile("barrier.cluster.arrive.relaxed.aligned;" ::: "memory");
        asm volatile("setmaxnreg.inc.sync.aligned.u32 %0;" :: "n"(CONSUMER_REGS));
        const int wg = __shfl_sync(0xffffffffu, threadIdx.x >> 7, 0);
        const int cw = threadIdx.x >> 5;
        const int tid = threadIdx.x & 127;
        float acc[128];
        uint32_t pk[64];
#pragma unroll
        for (int i = 0; i < 64; i++) asm volatile("mov.b32 %0, 0;" : "=r"(pk[i]));
#pragma unroll
        for (int i = 0; i < 128; i++) asm volatile("mov.b32 %0, 0;" : "=f"(acc[i]));
        asm volatile("barrier.cluster.wait.acquire.aligned;" ::: "memory");

        const int orow = ((lane >> 2) & 1) * (SEQ / 2) + mblk * 64 + cw * 8 + (lane >> 3);
        __nv_bfloat16* optr = g_xn + (mblk * 128 + nslot * 16 + cw * 2) * DM + lane * 8;
        const uint32_t da = desc_a(base + wg * 8192), db = desc_b(base + A_BYTES);
        auto release = [&](uint32_t bar) { if (tid < 2) mbar_arrive_cluster(bar, tid); };
        auto store_pk = [&](__nv_bfloat16* p, int j) {
            *reinterpret_cast<uint4*>(p) = make_uint4(pk[4 * j], pk[4 * j + 1], pk[4 * j + 2], pk[4 * j + 3]);
        };
        auto chunk_geglu = [&](int j) {
#pragma unroll
            for (int i = 4 * j; i < 4 * j + 4; i++) pk[i] = geglu2(pk[i], pk[32 + i]);
            store_pk(optr + (j & 1) * 4 * K2 + (j >> 1) * 32, j);
        };
        auto chunk_qkv = [&](int c) {
            store_pk(optr + c * 32, 2 * c);
            store_pk(optr + 4 * NQKV + c * 32, 2 * c + 1);
        };
        auto signal_stores = [&](int p) { __syncwarp(); if (lane == 0) mbar_arrive(sig_bar + p * 8); };

        auto chunk_ln = [&](int k) {
            float* const mo = reinterpret_cast<float*>(pk + 32);
            if (k == 0) {
                const uint4* xp = reinterpret_cast<const uint4*>(prm.px + (optr - g_xn));
                pk[38] = __ldcg(g_epoch + blockIdx.x * 16 + 2);
#pragma unroll
                for (int i = 0; i < 8; i++) {
                    const uint4 v = ldg_stream(xp + i * 32, stream_policy());
                    pk[4 * i] = v.x; pk[4 * i + 1] = v.y; pk[4 * i + 2] = v.z; pk[4 * i + 3] = v.w;
                }
            } else if (k >= LN_STEP && k < LN_STEP + 3) {
                if (k == LN_STEP) {
                    mo[0] = bf_lo(uniform(pk[0])); mo[1] = bf_lo(uniform(pk[16]));
                    mo[2] = mo[3] = mo[4] = mo[5] = 0.f;
                }
#pragma unroll
                for (int i = (k - LN_STEP) * 11; i < (k - LN_STEP) * 11 + 11 && i < 32; i++) {
                    const int r = i & 1;
                    const uint32_t w = pk[r * 16 + i / 2];
                    const float lo = bf_lo(w) - mo[r], hi = bf_hi(w) - mo[r];
                    mo[2 + r] += lo + hi;
                    mo[4 + r] = fmaf(hi, hi, fmaf(lo, lo, mo[4 + r]));
                }
            } else if (k == LN_STEP + 3) {
                const bool second = lane & 16;
                float m1 = (second ? mo[3] : mo[2]) + __shfl_xor_sync(0xffffffffu, second ? mo[2] : mo[3], 16);
                float m2 = (second ? mo[5] : mo[4]) + __shfl_xor_sync(0xffffffffu, second ? mo[4] : mo[5], 16);
#pragma unroll
                for (int o = 8; o > 0; o >>= 1) {
                    m1 += __shfl_xor_sync(0xffffffffu, m1, o);
                    m2 += __shfl_xor_sync(0xffffffffu, m2, o);
                }
                m1 *= 1.f / DM;
                const float var = fmaxf(fmaf(-m1, m1, m2 * (1.f / DM)), 0.f);
                const float mean = round_bf16((second ? mo[1] : mo[0]) + m1);
                const float inv = rcp_fast(round_bf16(sqrt_fast(round_bf16(round_bf16(var) + 1e-5f))));
                if ((lane & 15) == 0) st_tagged(g_stats + (uint32_t)(optr - g_xn) / DM + second, -mean, inv, 2 - (pk[38] & 1));
                const uint32_t split = pack_bf16(inv - round_bf16(inv), inv);
#pragma unroll
                for (int r = 0; r < 2; r++) {
                    const uint32_t f = __shfl_sync(0xffffffffu, split, r * 16);
                    pk[32 + 3 * r] = __byte_perm(__shfl_sync(0xffffffffu, __float_as_uint(mean), r * 16), 0, 0x3232);
                    pk[33 + 3 * r] = __byte_perm(f, 0, 0x3232);
                    pk[34 + 3 * r] = __byte_perm(f, 0, 0x1010);
                }
            } else if (k >= LN_STEP + 4 && k < LN_STEP + 7) {
#pragma unroll
                for (int i = (k - LN_STEP - 4) * 3; i < (k - LN_STEP - 3) * 3 && i < 8; i++) {
                    const uint32_t* n = pk + 32 + i / 4 * 3;
#pragma unroll
                    for (int j = 4 * i; j < 4 * i + 4; j++) pk[j] = mul2_bf16x2(sub_bf16x2(pk[j], n[0]), n[1], n[2]);
                    store_pk(optr + i * 256, i);
                }
                if (k == LN_STEP + 6) signal_stores(0);
            } else if (k == FOLD_STEP) {
                mbar_wait(fold_bar, 0);
#pragma unroll
                for (int j = 0; j < 16; j++) {
                    const uint4 c = lds128(colsum + j * 64 + (lane & 3) * 16);
                    pk[4 * j] = c.x; pk[4 * j + 1] = c.y; pk[4 * j + 2] = c.z; pk[4 * j + 3] = c.w;
                }
            }
        };

        bool gated = false;
#pragma unroll 1
        for (int t = 0; t < G1_TILES; t++) {
#pragma unroll
            for (int k = 0; k < G1_KSTEPS; k++) {
                const int s = k & 3;
                TRACE_STEP(t, k, 0);
                mbar_wait(full1(s), (k >> 2) & 1);
                if (k == 0) TRACE_S(12, t, 0);
                TRACE_STEP(t, k, 1);
                if (wg == 1 && k == G1_KSTEPS - (t ? G1_SKEW : SK0)) asm volatile("bar.sync 1, 256;" ::: "memory");
                if (t == 1) mma_step240(acc, da, db, s * G1_STAGE_BYTES / 16, k);
                else mma_step(acc, da, db, s * G1_STAGE_BYTES / 16, k);
                if (wg == 0 && k == G1_KSTEPS - 1) asm volatile("bar.arrive 1, 256;" ::: "memory");
                wg_wait<1>();
                if (k > 0) release(empty1((k - 1) & 3));
                TRACE_STEP(t, k, 2);
                if (t == 0) chunk_ln(k);
                if (k >= 1 && k <= 8 && gated) {
                    chunk_geglu(k - 1);
                    if (k == 8) signal_stores(t == 1 ? 1 : t + 1);
                }
                if (t != 0 && !gated) {
                    if (k == 0) { chunk_qkv(0); chunk_qkv(1); }
                    if (k == 11 && t == 2) {
                        __nv_bfloat16* const p = optr + 224 - (lane & 3) * 4;
                        *reinterpret_cast<uint2*>(p) = make_uint2(pk[56], pk[57]);
                        *reinterpret_cast<uint2*>(p + 4 * NQKV) = make_uint2(pk[60], pk[61]);
                    } else if (k >= 6 && k <= 11) {
                        chunk_qkv(k - 4);
                    }
                    if ((k == 0 || k == 11) && t == 2) signal_stores(k ? 3 : 2);
                }
            }
            wg_wait<0>();
            fence_regs(acc);
            release(empty1(3));
            if (t == 0) {
                const uint32_t sp = stats + (cw * 16 + (lane >> 2)) * 8;
                const float2 sa = lds64f(sp), sb = lds64f(sp + 64);
#pragma unroll
                for (int i = 0; i < 128; i++) {
                    const float2 st = i & 2 ? sb : sa;
                    acc[i] = fmaf(st.x, __uint_as_float(pk[i / 4 * 2 + (~i & 1)]), acc[i]) * st.y;
                }
                fence_regs(acc);
            }
#pragma unroll
            for (int i = 0; i < 64; i++) {
                const int e = (i & ~7) * 2 + (i & 3) * 4 + (i & 4) / 2;
                pk[i] = pack_bf16(acc[e], acc[e + 1]);
            }
            const int nt = t * 8 + nslot;
            gated = !tile_is_qkv(nt);
            optr = !gated ? g_qkv + (size_t)orow * NQKV + tile_index(nt) * 256 + (lane & 3) * 8
                                : g_a2 + (size_t)orow * K2 + DM + tile_index(nt) * 128 + (lane & 3) * 8;
            TRACE_S(16 + wg * 8 + t, 0, 0);
        }

        float accd[64], accs[64];
#pragma unroll
        for (int i = 0; i < 64; i++) accd[i] = 0.f;
#pragma unroll
        for (int u = 0; u < 9; u++) {
            const int q = u % G2_STAGES;
            mbar_wait(full2(q), (u / G2_STAGES) & 1);
            mma_step(accd, da, db, q * G2_STAGE_BYTES / 16, u);
            wg_wait<1>();
            if (u > 0) release(empty2((u - 1) % G2_STAGES));
            if (u >= 1) { chunk_geglu(u - 1); if (u == 8) signal_stores(6); }
        }
        {
            int q = 9 % G2_STAGES, qp = 8 % G2_STAGES; uint32_t ph = (9 / G2_STAGES) & 1;
#pragma unroll 1
            for (int u = 9; u < G2_DSTEPS; u++) {
                mbar_wait(full2(q), ph);
                mma_step(accd, da, db, q * (G2_STAGE_BYTES / 16), 1);
                wg_wait<1>();
                release(empty2(qp));
                qp = q;
                if (++q == G2_STAGES) { q = 0; ph ^= 1; }
            }
        }
        TRACE_S(16 + wg * 8 + 5, 0, 0);
#pragma unroll
        for (int i = 0; i < 64; i++) accs[i] = 0.f;
        uint32_t gk[32], xr[32];
        const uint32_t xs = aux + cw * 2048;
        const uint32_t xrow = xs + ((lane & 7) + ((lane >> 3) & 1) * 8) * 128;
        auto xaddr = [&](int j) { return xrow + (j >> 2) * 16384 + (((((j & 3) * 2) + (lane >> 4)) ^ (lane & 7)) << 4); };
#pragma unroll
        for (int u = G2_DSTEPS; u < G2_KSTEPS; u++) {
            const int q = u % G2_STAGES, v = u - G2_DSTEPS;
            mbar_wait(full2(q), (u / G2_STAGES) & 1);
            if (G2_SKEW > 0 && wg == 1 && u == G2_KSTEPS - G2_SKEW) asm volatile("bar.sync 1, 256;" ::: "memory");
            mma_step(accs, da, db, q * G2_STAGE_BYTES / 16, v);
            if (G2_SKEW > 0 && wg == 0 && u == G2_KSTEPS - 1) asm volatile("bar.arrive 1, 256;" ::: "memory");
            if (v >= 1 && v <= 8) {
#pragma unroll
                for (int i = 4 * (v - 1); i < 4 * v; i++) {
                    const uint32_t d2 = pack_bf16(accd[2 * i], accd[2 * i + 1]);
                    gk[i] = pack_bf16(silu(bf_lo(d2)), silu(bf_hi(d2)));
                }
            }
            if (v == 9) mbar_wait(x_bar, 0);
            if (v >= 9 && v <= 12) {
#pragma unroll
                for (int j = 2 * (v - 9); j < 2 * (v - 8); j++)
                    asm volatile("ldmatrix.sync.aligned.m8n8.x4.shared.b16 {%0,%1,%2,%3}, [%4];"
                                 : "=r"(xr[4 * j]), "=r"(xr[4 * j + 1]), "=r"(xr[4 * j + 2]), "=r"(xr[4 * j + 3])
                                 : "r"(xaddr(j)) : "memory");
            }
            wg_wait<1>();
            if (v == 0) fence_regs(accd);
            if (u - 1 + G2_STAGES < G2_KSTEPS) release(empty2((u - 1) % G2_STAGES));
        }
        wg_wait<0>();
        fence_regs(accs);
        TRACE_S(16 + wg * 8 + 6, 0, 0);
#pragma unroll
        for (int j = 0; j < 8; j++) {
            uint32_t r[4];
#pragma unroll
            for (int i = 0; i < 4; i++) {
                const int e = j * 4 + i;
                r[i] = add_bf16x2(xr[e], mul_bf16x2(pack_bf16(accs[2 * e], accs[2 * e + 1]), gk[e]));
            }
            asm volatile("stmatrix.sync.aligned.m8n8.x4.shared.b16 [%0], {%1,%2,%3,%4};"
                         :: "r"(xaddr(j)), "r"(r[0]), "r"(r[1]), "r"(r[2]), "r"(r[3]) : "memory");
            if (j == 3 || j == 7) {
                asm volatile("fence.proxy.async.shared::cta;" ::: "memory");
                __syncwarp();
                if (lane == 0) {
                    tma_store_2d(&prm.out, xs + (j >> 2) * 16384, nslot * 128 + (j >> 2) * 64, mblk * 128 + cw * 16);
                    asm volatile("cp.async.bulk.commit_group;" ::: "memory");
                }
            }
        }
        if (lane == 0) asm volatile("cp.async.bulk.wait_group.read 0;" ::: "memory");
        if (tid == 0) { TRACE(16 + wg * 8 + 7); if (wg == 1) TRACE_GT(13); TRACE_DUMP(); }
    }
}

typedef CUresult (*EncodeFn)(CUtensorMap*, CUtensorMapDataType, cuuint32_t, void*, const cuuint64_t*, const cuuint64_t*,
                             const cuuint32_t*, const cuuint32_t*, CUtensorMapInterleave, CUtensorMapSwizzle,
                             CUtensorMapL2promotion, CUtensorMapFloatOOBfill);

void encode(EncodeFn fn, CUtensorMap* m, const void* ptr, int rank, const cuuint64_t* dims, const cuuint64_t* strides,
            const cuuint32_t* box) {
    const cuuint32_t es[5] = {1, 1, 1, 1, 1};
    fn(m, CU_TENSOR_MAP_DATA_TYPE_BFLOAT16, rank, const_cast<void*>(ptr), dims, strides, box, es,
       CU_TENSOR_MAP_INTERLEAVE_NONE, box[0] == 16 ? CU_TENSOR_MAP_SWIZZLE_32B : CU_TENSOR_MAP_SWIZZLE_128B,
       CU_TENSOR_MAP_L2_PROMOTION_L2_128B, CU_TENSOR_MAP_FLOAT_OOB_FILL_NONE);
}
void encode_2d(EncodeFn fn, CUtensorMap* m, const void* ptr, int cols, int box_rows) {
    const cuuint64_t dims[2] = {(cuuint64_t)cols, SEQ}, strides[1] = {(cuuint64_t)cols * 2};
    const cuuint32_t box[2] = {64, (cuuint32_t)box_rows};
    encode(fn, m, ptr, 2, dims, strides, box);
}
void encode_w1(EncodeFn fn, CUtensorMap* m, const void* ptr, int cols) {
    const cuuint64_t dims[3] = {64, DM, (cuuint64_t)cols / 64}, strides[2] = {(cuuint64_t)cols * 2, 128};
    const cuuint32_t box[3] = {64, 64, 2};
    encode(fn, m, ptr, 3, dims, strides, box);
}
void encode_tail(EncodeFn fn, CUtensorMap* m, const __nv_bfloat16* w) {
    const cuuint64_t dims[3] = {16, DM, 8}, strides[2] = {NQKV * 2, 512};
    const cuuint32_t box[3] = {16, 64, 8};
    encode(fn, m, w + 240, 3, dims, strides, box);
}
void encode_qk(EncodeFn fn, CUtensorMap* m, const void* ptr) {
    const cuuint64_t dims[3] = {DM, SEQ, 3}, strides[2] = {NQKV * 2, DM * 2};
    const cuuint32_t box[3] = {64, 16, 2};
    encode(fn, m, ptr, 3, dims, strides, box);
}
void encode_a2(EncodeFn fn, CUtensorMap* m, const void* ptr) {
    const cuuint64_t dims[3] = {K2, 2, SEQ / 2}, strides[2] = {(cuuint64_t)SEQ * K2, K2 * 2};
    const cuuint32_t box[3] = {64, 2, 64};
    encode(fn, m, ptr, 3, dims, strides, box);
}
void encode_w2(EncodeFn fn, CUtensorMap* m, const void* ptr, int rows) {
    const cuuint64_t rb = DM * 2;
    const cuuint64_t dims[5] = {DM, 2, 4, 4, (cuuint64_t)rows / 32}, strides[4] = {rb, 8 * rb, 2 * rb, 32 * rb};
    const cuuint32_t box[5] = {64, 2, 4, 4, 2};
    encode(fn, m, ptr, 5, dims, strides, box);
}

}

extern "C" void kernel_launch(void* const* d_in, const int* in_sizes, int n_in, void* d_out, int out_size) {
    (void)in_sizes; (void)n_in; (void)out_size;
    static EncodeFn fn = nullptr;
    static void *p_xn = nullptr, *p_qkv = nullptr, *p_a2 = nullptr;
    if (!fn) {
        cudaDriverEntryPointQueryResult st;
        cudaGetDriverEntryPoint("cuTensorMapEncodeTiled", (void**)&fn, cudaEnableDefault, &st);
        cudaGetSymbolAddress(&p_xn, g_xn);
        cudaGetSymbolAddress(&p_qkv, g_qkv);
        cudaGetSymbolAddress(&p_a2, g_a2);
        cudaFuncSetAttribute(fused_kernel, cudaFuncAttributeMaxDynamicSharedMemorySize, SMEM_BYTES);
    }
    Params prm;
    encode_2d(fn, &prm.x, d_in[0], DM, 128);
    encode_2d(fn, &prm.xn, p_xn, DM, 128);
    encode_tail(fn, &prm.wtail, (const __nv_bfloat16*)d_in[1]);
    encode_w1(fn, &prm.wqkv, d_in[1], NQKV);
    encode_w1(fn, &prm.wg, d_in[4], DF);
    encode_w1(fn, &prm.wu, d_in[5], DF);
    encode_qk(fn, &prm.qk, p_qkv);
    encode_2d(fn, &prm.v, p_qkv, NQKV, 16);
    encode_2d(fn, &prm.o, p_a2, K2, 16);
    encode_a2(fn, &prm.a2, p_a2);
    encode_w2(fn, &prm.wo, d_in[2], DM);
    encode_w2(fn, &prm.wd, d_in[6], DF);
    encode_2d(fn, &prm.out, d_out, DM, 16);
    prm.px = (const __nv_bfloat16*)d_in[0];
    prm.zero = 0;
    for (int b = 0; b < NCTA; b++) {
        const int c = b / 2;
        prm.role[b] = (c < 4 ? 32 + c * 8 : (c < 36 ? c - 4 : 33 + (c - 36) / 7 * 8 + (c - 36) % 7)) * 2 + b % 2;
    }
    fused_kernel<<<NCTA, 384, SMEM_BYTES>>>(prm);
}
```

```cpp
#include <cuda_runtime.h>
#include <cuda_bf16.h>
#include <cuda.h>
#include <stdint.h>
#include <type_traits>

#define LNS 3
#define FS 15
#define CSAT empty1(3)
#define SK0 3

namespace {

constexpr int SEQ = 2048, DM = 1024, DF = 3584, K2 = DM + DF, NQKV = 3 * DM;
constexpr int NGEMM = 128, NCTA = 132;
constexpr int G1_STAGES = 4, G1_STAGE_BYTES = 49152, G1_KSTEPS = 16, G1_TILES = 5;
constexpr int G2_STAGES = 6, G2_STAGE_BYTES = 32768, G2_KSTEPS = 72, G2_LATE = 40, G2_DSTEPS = 56, G2_LAST = 68;
constexpr int LN_STEP = LNS, FOLD_STEP = FS;
constexpr int A_BYTES = 16384;
constexpr int AUX_OFF = G1_STAGES * G1_STAGE_BYTES;
constexpr int BAR_OFF = AUX_OFF + 32768;
constexpr int SMEM_BYTES = BAR_OFF + 2816;
constexpr int G1_SKEW = 2, G2_SKEW = 2;
constexpr int CONSUMER_REGS = 224, AUX_REGS = 56;
constexpr int ATT_SLOT = 8192;

enum { F_LN = 0, F_QKV = 1, F_EARLY = 2, F_LATE = 3, F_O = 4 };
constexpr unsigned CNT_LN = 8, CNT_QKV = 32, CNT_EARLY = 21, CNT_LATE = 8, CNT_O = 4;

__device__ __align__(1024) __nv_bfloat16 g_xn[SEQ * DM];
__device__ __align__(1024) __nv_bfloat16 g_qkv[SEQ * NQKV];
__device__ __align__(1024) __nv_bfloat16 g_a2[SEQ * K2];
__device__ __align__(128) uint4 g_tail[NGEMM * 256];
__device__ __align__(128) float2 g_stats[SEQ];
__device__ __align__(128) float g_colsum[16 * 1024];
__device__ __align__(128) unsigned g_flags[5 * 16 * 32];
__device__ __align__(128) unsigned g_epoch[NCTA * 16];

#define TRACE(slot) do {} while (0)
#define TRACE_GT(slot) do {} while (0)
#define TRACE_S(slot, v, want) do {} while (0)
#define TRACE_DUMP() do {} while (0)
#define TRACE_CLEAR() do {} while (0)
#define TRACE_STEP(t, k, i) do {} while (0)

__device__ __forceinline__ uint32_t smem_u32(const void* p) { return (uint32_t)__cvta_generic_to_shared(p); }
__device__ __forceinline__ void mbar_init(uint32_t bar, uint32_t cnt) {
    asm volatile("mbarrier.init.shared::cta.b64 [%0], %1;" :: "r"(bar), "r"(cnt) : "memory");
}
__device__ __forceinline__ void mbar_expect_tx(uint32_t bar, uint32_t bytes) {
    asm volatile("mbarrier.arrive.expect_tx.shared::cta.b64 _, [%0], %1;" :: "r"(bar), "r"(bytes) : "memory");
}
__device__ __forceinline__ void mbar_arrive(uint32_t bar) {
    asm volatile("mbarrier.arrive.shared::cta.b64 _, [%0];" :: "r"(bar) : "memory");
}
__device__ __forceinline__ void mbar_arrive_cluster(uint32_t bar, uint32_t cta) {
    asm volatile("{\n.reg .b32 ra;\nmapa.shared::cluster.u32 ra, %0, %1;\nmbarrier.arrive.shared::cluster.b64 _, [ra];\n}"
                 :: "r"(bar), "r"(cta) : "memory");
}
__device__ __forceinline__ bool mbar_try_wait(uint32_t bar, uint32_t parity) {
    uint32_t ok;
    asm volatile("{\n.reg .pred p;\nmbarrier.try_wait.parity.shared::cta.b64 p, [%1], %2;\nselp.u32 %0, 1, 0, p;\n}"
                 : "=r"(ok) : "r"(bar), "r"(parity) : "memory");
    return ok;
}
__device__ __forceinline__ bool mbar_test(uint32_t bar, uint32_t parity) {
    uint32_t ok;
    asm volatile("{\n.reg .pred p;\nmbarrier.test_wait.parity.shared::cta.b64 p, [%1], %2;\nselp.u32 %0, 1, 0, p;\n}"
                 : "=r"(ok) : "r"(bar), "r"(parity) : "memory");
    return ok;
}
__device__ __forceinline__ void mbar_wait(uint32_t bar, uint32_t parity) {
#pragma unroll 1
    for (int spins = 0; !mbar_try_wait(bar, parity) && spins < (1 << 17); spins++) {}
}
template <bool WARP = false> __device__ __forceinline__ void flag_wait(const unsigned* p, unsigned target) {
#pragma unroll 1
    for (int spins = 0; spins < (1 << 19); spins++) {
        unsigned v;
        asm volatile("ld.acquire.gpu.global.u32 %0, [%1];" : "=r"(v) : "l"(p) : "memory");
        if (WARP ? __all_sync(0xffffffffu, (int)(v - target) >= 0) : (int)(v - target) >= 0) break;
        __nanosleep(64);
    }
}
__device__ __forceinline__ void mbar_wait_warp(uint32_t bar, uint32_t parity) {
#pragma unroll 1
    for (int spins = 0; !__all_sync(0xffffffffu, mbar_try_wait(bar, parity)) && spins < (1 << 17); spins++) {}
}
__device__ __forceinline__ void flag_add(unsigned* p) {
    asm volatile("red.release.gpu.global.add.u32 [%0], 1;" :: "l"(p) : "memory");
}
__device__ __forceinline__ bool elect_one() {
    uint32_t ok;
    asm volatile("{\n.reg .pred p;\nelect.sync _|p, 0xffffffff;\nselp.u32 %0, 1, 0, p;\n}" : "=r"(ok));
    return ok;
}
__device__ __forceinline__ void fence_proxy_async() { asm volatile("fence.proxy.async.global;" ::: "memory"); }
__device__ __forceinline__ uint4 lds128(uint32_t addr) {
    uint4 v;
    asm volatile("ld.shared.v4.u32 {%0,%1,%2,%3}, [%4];" : "=r"(v.x), "=r"(v.y), "=r"(v.z), "=r"(v.w) : "r"(addr) : "memory");
    return v;
}
__device__ __forceinline__ float2 lds64f(uint32_t addr) {
    float2 v;
    asm volatile("ld.shared.v2.f32 {%0,%1}, [%2];" : "=f"(v.x), "=f"(v.y) : "r"(addr) : "memory");
    return v;
}
__device__ __forceinline__ void sts128(uint32_t addr, uint4 v) {
    asm volatile("st.shared.v4.u32 [%0], {%1,%2,%3,%4};" :: "r"(addr), "r"(v.x), "r"(v.y), "r"(v.z), "r"(v.w) : "memory");
}
__device__ __forceinline__ void sts64f(uint32_t addr, float a, float b) {
    asm volatile("st.shared.v2.f32 [%0], {%1,%2};" :: "r"(addr), "f"(a), "f"(b) : "memory");
}

__device__ __forceinline__ uint64_t stream_policy() {
    uint64_t p;
    asm("createpolicy.fractional.L2::evict_first.b64 %0, 1.0;" : "=l"(p));
    return p;
}
__device__ __forceinline__ void tma_2d(uint32_t dst, const CUtensorMap* m, uint32_t bar, int c0, int c1, uint64_t pol) {
    asm volatile("cp.async.bulk.tensor.2d.shared::cluster.global.mbarrier::complete_tx::bytes.L2::cache_hint"
                 " [%0], [%1, {%3, %4}], [%2], %5;"
                 :: "r"(dst), "l"(m), "r"(bar), "r"(c0), "r"(c1), "l"(pol) : "memory");
}
__device__ __forceinline__ void tma_3d(uint32_t dst, const CUtensorMap* m, uint32_t bar, int c0, int c1, int c2, uint64_t pol) {
    asm volatile("cp.async.bulk.tensor.3d.shared::cluster.global.mbarrier::complete_tx::bytes.L2::cache_hint"
                 " [%0], [%1, {%3, %4, %5}], [%2], %6;"
                 :: "r"(dst), "l"(m), "r"(bar), "r"(c0), "r"(c1), "r"(c2), "l"(pol) : "memory");
}
__device__ __forceinline__ void tma_3d_mc(uint32_t dst, const CUtensorMap* m, uint32_t bar, int c1, int c2, uint64_t pol) {
    asm volatile("cp.async.bulk.tensor.3d.shared::cluster.global.mbarrier::complete_tx::bytes.multicast::cluster.L2::cache_hint"
                 " [%0], [%1, {%3, %4, %5}], [%2], %6, %7;"
                 :: "r"(dst), "l"(m), "r"(bar), "r"(0), "r"(c1), "r"(c2), "h"((uint16_t)3), "l"(pol) : "memory");
}
__device__ __forceinline__ void load_stage1(uint32_t dst, uint32_t dst_b, uint32_t bar, const CUtensorMap* ma, const CUtensorMap* mb,
                                            int k, int row, int col, int keep_a, uint64_t pol) {
    asm volatile("{\n.reg .pred e, p, q;\nelect.sync _|e, 0xffffffff;\nsetp.ne.and.b32 p|q, %8, 0, e;\n"
        "@p cp.async.bulk.tensor.2d.shared::cluster.global.mbarrier::complete_tx::bytes [%0], [%3, {%5, %6}], [%2];\n"
        "@q cp.async.bulk.tensor.2d.shared::cluster.global.mbarrier::complete_tx::bytes.L2::cache_hint [%0], [%3, {%5, %6}], [%2], %9;\n"
        "@e cp.async.bulk.tensor.3d.shared::cluster.global.mbarrier::complete_tx::bytes.multicast::cluster.L2::cache_hint"
        " [%1], [%4, {%10, %5, %7}], [%2], %11, %9;\n"
        "@e mbarrier.arrive.expect_tx.shared::cta.b64 _, [%2], %12;\n}"
        :: "r"(dst), "r"(dst_b), "r"(bar), "l"(ma), "l"(mb), "r"(k), "r"(row), "r"(col), "r"(keep_a), "l"(pol), "r"(0),
           "h"((uint16_t)3), "n"(G1_STAGE_BYTES) : "memory");
}
__device__ __forceinline__ void load_stage2(uint32_t dst, uint32_t dst_b, uint32_t bar, const CUtensorMap* ma, const CUtensorMap* mb,
                                            int ka, int row, int col, int kb, uint64_t pol) {
    asm volatile("{\n.reg .pred e;\nelect.sync _|e, 0xffffffff;\n"
        "@e cp.async.bulk.tensor.3d.shared::cluster.global.mbarrier::complete_tx::bytes.L2::cache_hint [%0], [%3, {%5, %10, %6}], [%2], %9;\n"
        "@e cp.async.bulk.tensor.5d.shared::cluster.global.mbarrier::complete_tx::bytes.multicast::cluster.L2::cache_hint"
        " [%1], [%4, {%7, %10, %10, %10, %8}], [%2], %11, %9;\n"
        "@e mbarrier.arrive.expect_tx.shared::cta.b64 _, [%2], %12;\n}"
        :: "r"(dst), "r"(dst_b), "r"(bar), "l"(ma), "l"(mb), "r"(ka), "r"(row), "r"(col), "r"(kb), "l"(pol), "r"(0),
           "h"((uint16_t)3), "n"(G2_STAGE_BYTES) : "memory");
}
__device__ __forceinline__ void tma_store_2d(const CUtensorMap* m, uint32_t src, int c0, int c1) {
    asm volatile("cp.async.bulk.tensor.2d.global.shared::cta.bulk_group [%0, {%2, %3}], [%1];"
                 :: "l"(m), "r"(src), "r"(c0), "r"(c1) : "memory");
}
__device__ __forceinline__ uint4 ldg_stream(const void* p, uint64_t pol) {
    uint4 v;
    asm volatile("ld.global.nc.L1::no_allocate.L2::cache_hint.v4.u32 {%0,%1,%2,%3}, [%4], %5;"
                 : "=r"(v.x), "=r"(v.y), "=r"(v.z), "=r"(v.w) : "l"(p), "l"(pol));
    return v;
}
__device__ __forceinline__ void st_tagged(void* p, float a, float b, uint32_t tag) {
    asm volatile("st.relaxed.gpu.global.v2.b32 [%0], {%1,%2};"
                 :: "l"(p), "r"((__float_as_uint(a) & ~3u) | tag), "r"((__float_as_uint(b) & ~3u) | tag) : "memory");
}
__device__ __forceinline__ bool untagged(const uint4& v, uint32_t tag) {
    return ((v.x ^ tag) | (v.y ^ tag) | (v.z ^ tag) | (v.w ^ tag)) & 3;
}
__device__ __forceinline__ uint4 ld_relaxed(const void* p) {
    uint4 v;
    asm volatile("ld.relaxed.gpu.global.v4.b32 {%0,%1,%2,%3}, [%4];" : "=r"(v.x), "=r"(v.y), "=r"(v.z), "=r"(v.w) : "l"(p) : "memory");
    return v;
}
__device__ __forceinline__ void prefetch_3d(const CUtensorMap* m, int c1, int c2, uint64_t pol) {
    asm volatile("cp.async.bulk.prefetch.tensor.3d.L2.global.L2::cache_hint [%0, {%1, %2, %3}], %4;"
                 :: "l"(m), "r"(0), "r"(c1), "r"(c2), "l"(pol) : "memory");
}
__device__ __forceinline__ void prefetch_map(const CUtensorMap* m) {
    asm volatile("prefetch.tensormap [%0];" :: "l"(m) : "memory");
}
template <int N> __device__ __forceinline__ void wg_wait() { asm volatile("wgmma.wait_group.sync.aligned %0;" :: "n"(N) : "memory"); }

__device__ __forceinline__ uint32_t desc_a(uint32_t addr) { return (addr & 0x3FFFF) >> 4 | 1 << 16; }
__device__ __forceinline__ uint32_t desc_b(uint32_t addr) { return (addr & 0x3FFFF) >> 4 | 512 << 16; }

#define R8(d, o) "+f"(d[o]), "+f"(d[o+1]), "+f"(d[o+2]), "+f"(d[o+3]), "+f"(d[o+4]), "+f"(d[o+5]), "+f"(d[o+6]), "+f"(d[o+7])
#define R32(d, o) R8(d, o), R8(d, o+8), R8(d, o+16), R8(d, o+24)
#define R64(d, o) R32(d, o), R32(d, o+32)
#define ACC0 "%0,%1,%2,%3,%4,%5,%6,%7,%8,%9,%10,%11,%12,%13,%14,%15,%16,%17,%18,%19,%20,%21,%22,%23,%24,%25,%26,%27,%28,%29,%30,%31,"\
    "%32,%33,%34,%35,%36,%37,%38,%39,%40,%41,%42,%43,%44,%45,%46,%47,%48,%49,%50,%51,%52,%53,%54,%55,%56,%57,%58,%59,%60,%61,%62,%63"
#define ACC1 "%64,%65,%66,%67,%68,%69,%70,%71,%72,%73,%74,%75,%76,%77,%78,%79,%80,%81,%82,%83,%84,%85,%86,%87,%88,%89,%90,%91,%92,%93,%94,%95,"\
    "%96,%97,%98,%99,%100,%101,%102,%103,%104,%105,%106,%107,%108,%109,%110,%111,%112,%113,%114,%115,%116,%117,%118,%119"
#define ACC64 "{" ACC0 "}"
#define ACC120 "{" ACC0 "," ACC1 "}"
#define ACC128 "{" ACC0 "," ACC1 ",%120,%121,%122,%123,%124,%125,%126,%127}"
#define MMA_K16(shape, acc, keep, hb, sb) \
    "mov.b64 da, {la, 0x40000040};\nmov.b64 db, {lb, " hb "};\n" \
    "wgmma.mma_async.sync.aligned." shape ".f32.bf16.bf16 " acc ", da, db, " keep ", 1, 1, 0, 1;\n" \
    "add.u32 la, la, 2;\nadd.u32 lb, lb, " sb ";\n"
#define MMA_STEP_B(shape, acc, a, b, off, keep, hb, sb) \
    "{\n.reg .pred p, q;\n.reg .b32 la, lb;\n.reg .b64 da, db;\nsetp.ne.b32 p, " keep ", 0;\nsetp.eq.b32 q, 0, 0;\n" \
    "add.u32 la, " a ", " off ";\nadd.u32 lb, " b ", " off ";\nwgmma.fence.sync.aligned;\n" \
    MMA_K16(shape, acc, "p", hb, sb) MMA_K16(shape, acc, "q", hb, sb) MMA_K16(shape, acc, "q", hb, sb) \
    MMA_K16(shape, acc, "q", hb, sb) "wgmma.commit_group.sync.aligned;\n}"
#define MMA_STEP(shape, acc, a, b, off, keep) MMA_STEP_B(shape, acc, a, b, off, keep, "0x40000040", "128")

__device__ __forceinline__ void mma_step(float (&d)[128], uint32_t da, uint32_t db, uint32_t off, int keep) {
    asm volatile(MMA_STEP("m64n256k16", ACC128, "%128", "%129", "%130", "%131")
                 : R64(d, 0), R64(d, 64) : "r"(da), "r"(db), "r"(off), "r"(keep) : "memory");
}
__device__ __forceinline__ void mma_step240(float (&d)[128], uint32_t da, uint32_t db, uint32_t off, int keep) {
    asm volatile(MMA_STEP("m64n240k16", ACC120, "%120", "%121", "%122", "%123")
                 : R64(d, 0), R32(d, 64), R8(d, 96), R8(d, 104), R8(d, 112) : "r"(da), "r"(db), "r"(off), "r"(keep) : "memory");
}
__device__ __forceinline__ void mma_step(float (&d)[64], uint32_t da, uint32_t db, uint32_t off, int keep) {
    asm volatile(MMA_STEP("m64n128k16", ACC64, "%64", "%65", "%66", "%67")
                 : R64(d, 0) : "r"(da), "r"(db), "r"(off), "r"(keep) : "memory");
}

__device__ __forceinline__ void mma_step_tail(float (&d)[64], uint32_t da, uint32_t b, uint32_t off) {
    asm volatile(MMA_STEP_B("m64n128k16", ACC64, "%64", "%65", "%66", "1", "0xC0000010", "32")
                 : R64(d, 0) : "r"(da), "r"((b & 0x3FFFF) >> 4 | 128 << 16), "r"(off) : "memory");
}

__device__ __forceinline__ uint32_t pack_bf16(float lo, float hi) {
    uint32_t r; asm("cvt.rn.bf16x2.f32 %0, %1, %2;" : "=r"(r) : "f"(hi), "f"(lo)); return r;
}
__device__ __forceinline__ float bf_lo(uint32_t v) { return __uint_as_float(v << 16); }
__device__ __forceinline__ float bf_hi(uint32_t v) { return __uint_as_float(v & 0xffff0000u); }
__device__ __forceinline__ float round_bf16(float v) { return bf_lo(pack_bf16(v, 0.f)); }
__device__ __forceinline__ uint32_t mul_bf16x2(uint32_t a, uint32_t b) {
    uint32_t r; asm("mul.rn.bf16x2 %0, %1, %2;" : "=r"(r) : "r"(a), "r"(b)); return r;
}
__device__ __forceinline__ uint32_t add_bf16x2(uint32_t a, uint32_t b) {
    uint32_t r; asm("add.rn.bf16x2 %0, %1, %2;" : "=r"(r) : "r"(a), "r"(b)); return r;
}
__device__ __forceinline__ uint32_t sub_bf16x2(uint32_t a, uint32_t b) {
    uint32_t r; asm("sub.rn.bf16x2 %0, %1, %2;" : "=r"(r) : "r"(a), "r"(b)); return r;
}
__device__ __forceinline__ uint32_t mul2_bf16x2(uint32_t a, uint32_t hi, uint32_t lo) {
    uint32_t r; asm("fma.rn.bf16x2 %0, %1, %2, %3;" : "=r"(r) : "r"(a), "r"(hi), "r"(mul_bf16x2(a, lo))); return r;
}
__device__ __forceinline__ float tanh_fast(float x) { float r; asm("tanh.approx.f32 %0, %1;" : "=f"(r) : "f"(x)); return r; }
__device__ __forceinline__ float gelu_tanh(float g) {
    float t = fmaf(g * g, 0.044715f * 0.7978845608f, 0.7978845608f) * g;
    float hg = 0.5f * g;
    return fmaf(hg, tanh_fast(t), hg);
}
__device__ __forceinline__ uint32_t geglu2(uint32_t g2, uint32_t u2) {
    return mul_bf16x2(pack_bf16(gelu_tanh(bf_lo(g2)), gelu_tanh(bf_hi(g2))), u2);
}
__device__ __forceinline__ float silu(float d) {
    float hd = 0.5f * d;
    return fmaf(hd, tanh_fast(hd), hd);
}
__device__ __forceinline__ float ex2_fast(float x) { float r; asm("ex2.approx.ftz.f32 %0, %1;" : "=f"(r) : "f"(x)); return r; }
__device__ __forceinline__ void unpack8(uint4 v, float (&f)[8]) {
    f[0] = bf_lo(v.x); f[1] = bf_hi(v.x); f[2] = bf_lo(v.y); f[3] = bf_hi(v.y);
    f[4] = bf_lo(v.z); f[5] = bf_hi(v.z); f[6] = bf_lo(v.w); f[7] = bf_hi(v.w);
}
template <int N> __device__ __forceinline__ void fence_regs(float (&d)[N]) {
#pragma unroll
    for (int i = 0; i < N; i++) asm volatile("" : "+f"(d[i]) :: "memory");
}

__device__ __forceinline__ float rcp_fast(float x) { float r; asm("rcp.approx.ftz.f32 %0, %1;" : "=f"(r) : "f"(x)); return r; }
__device__ __forceinline__ float sqrt_fast(float x) { float r; asm("sqrt.approx.ftz.f32 %0, %1;" : "=f"(r) : "f"(x)); return r; }
__device__ __forceinline__ uint32_t max_bf16x2(uint32_t a, uint32_t b) {
    uint32_t r; asm("max.bf16x2 %0, %1, %2;" : "=r"(r) : "r"(a), "r"(b)); return r;
}
__device__ __forceinline__ uint4 ldsm4(uint32_t addr) {
    uint4 v;
    asm volatile("ldmatrix.sync.aligned.m8n8.x4.shared.b16 {%0,%1,%2,%3}, [%4];"
                 : "=r"(v.x), "=r"(v.y), "=r"(v.z), "=r"(v.w) : "r"(addr) : "memory");
    return v;
}
__device__ __forceinline__ uint4 ldsm4_t(uint32_t addr) {
    uint4 v;
    asm volatile("ldmatrix.sync.aligned.m8n8.x4.trans.shared.b16 {%0,%1,%2,%3}, [%4];"
                 : "=r"(v.x), "=r"(v.y), "=r"(v.z), "=r"(v.w) : "r"(addr) : "memory");
    return v;
}
__device__ __forceinline__ void mma_16816(float (&c)[4], uint32_t a0, uint32_t a1, uint32_t a2, uint32_t a3, uint32_t b0, uint32_t b1) {
    asm("mma.sync.aligned.m16n8k16.row.col.f32.bf16.bf16.f32 {%0,%1,%2,%3}, {%4,%5,%6,%7}, {%8,%9}, {%0,%1,%2,%3};"
        : "+f"(c[0]), "+f"(c[1]), "+f"(c[2]), "+f"(c[3]) : "r"(a0), "r"(a1), "r"(a2), "r"(a3), "r"(b0), "r"(b1));
}
__device__ __forceinline__ void mma_1688(float (&c)[4], uint32_t a0, uint32_t a1, uint32_t b0) {
    asm("mma.sync.aligned.m16n8k8.row.col.f32.bf16.bf16.f32 {%0,%1,%2,%3}, {%4,%5}, {%6}, {%0,%1,%2,%3};"
        : "+f"(c[0]), "+f"(c[1]), "+f"(c[2]), "+f"(c[3]) : "r"(a0), "r"(a1), "r"(b0));
}
__device__ __forceinline__ void qk_tile(float (&c)[4], const uint4& q0, const uint4& q1, const uint4& k, float init) {
    c[0] = c[1] = c[2] = c[3] = init;
    mma_16816(c, q0.x, q0.y, q0.z, q0.w, k.x, k.y);
    mma_16816(c, q1.x, q1.y, q1.z, q1.w, k.z, k.w);
}
__device__ __forceinline__ uint32_t scaled_logits(bool first, float a0, float a1, float b0, float b1) {
    return mul2_bf16x2(pack_bf16(first ? a0 : b0, first ? a1 : b1), 0x3e353e35u, 0x379e379eu);
}
template <typename T> __device__ __forceinline__ T uniform(T v) { return __shfl_sync(0xffffffffu, v, 0); }

__device__ __forceinline__ void attention(const CUtensorMap* maps, uint32_t base, uint32_t zero, unsigned epoch, int grp, int warp,
                                          int lane) {
    constexpr float LOG2E = 1.4426950408889634f;
    const int g = lane >> 2, t = lane & 3;
    const bool up0 = 2 * t > g, up1 = 2 * t + 1 > g;
    const uint32_t keep = (up0 ? 0x0000ffffu : 0u) | (up1 ? 0xffff0000u : 0u);
    const uint32_t buf = base + warp * 2 * ATT_SLOT, bar = base + AUX_OFF + warp * 16;
    const uint32_t qoff = (lane & 15) * 128 + (((lane >> 4) ^ (lane & 7)) << 4);
    const uint32_t koff = 2048 + (lane & 7) * 128 + (((lane >> 3) ^ (lane & 7)) << 4);
    const uint32_t rest_bar = base + AUX_OFF + 192;
    const int col = uniform(grp * 256), first = uniform((warp / 3 * 32 + warp % 3 * 11) * 16);
    const CUtensorMap* const mqk = reinterpret_cast<const CUtensorMap*>(uniform(reinterpret_cast<uint64_t>(maps)));
    const CUtensorMap *const mv = mqk + 1, *const mo = mqk + 2;
    const uint64_t pol = stream_policy();
    uint4 kp[2], vp[2];
    uint32_t l0[2], l1[2], m[2];
    float s[2][3][4];
    auto scores = [&](uint32_t st, int row) {
        const float before = (row & 1023) == 0 ? -5.656854e9f : 0.f;
#pragma unroll
        for (int h = 0; h < 2; h++) {
            const uint4 q0 = ldsm4(st + (qoff ^ (h * 64))), q1 = ldsm4(st + (qoff ^ (h * 64 + 32)));
            const uint4 k0 = ldsm4(st + (koff ^ (h * 64))), k1 = ldsm4(st + 1024 + (koff ^ (h * 64)));
            qk_tile(s[h][0], q0, q1, kp[h], before);
            qk_tile(s[h][1], q0, q1, k0, 0.f);
            qk_tile(s[h][2], q0, q1, k1, 0.f);
            kp[h] = k1;
        }
    };
    auto logits = [&]() {
#pragma unroll
        for (int h = 0; h < 2; h++) {
            l0[h] = scaled_logits(up0, s[h][0][0], s[h][1][2], s[h][1][0], s[h][2][2]);
            l1[h] = scaled_logits(up1, s[h][0][1], s[h][1][3], s[h][1][1], s[h][2][3]);
            m[h] = max_bf16x2(l0[h], l1[h]);
            m[h] = max_bf16x2(m[h], __shfl_xor_sync(0xffffffffu, m[h], 1));
        }
    };
    auto row_max = [&]() {
#pragma unroll
        for (int h = 0; h < 2; h++) m[h] = max_bf16x2(m[h], __shfl_xor_sync(0xffffffffu, m[h], 2));
    };
    auto next = [](uint32_t p) {
        return (0x80200400u >> (p >> 4 & 31) & 1) > (p >> 15 & 1) ? p + (64 << 16) + 0x8000 : (p + 16) & ~0x8800u;
    };
    auto exchange = [&](uint32_t st, uint32_t b, uint32_t po, uint32_t pv, uint32_t pq) {
        asm volatile("{\n.reg .pred e, p, q;\n"
            "fence.proxy.async.shared::cta;\n"
            "bar.warp.sync 0xffffffff;\n"
            "elect.sync _|e, 0xffffffff;\n"
            "setp.eq.and.b32 p, %12, 0, e;\n"
            "setp.lt.and.s32 q, %8, %13, e;\n"
            "@q mbarrier.arrive.expect_tx.shared::cta.b64 _, [%2], 6144;\n"
            "@q cp.async.bulk.tensor.3d.shared::cluster.global.mbarrier::complete_tx::bytes.L2::cache_hint [%0], [%3, {%6, %7, %14}], [%2], %15;\n"
            "@q cp.async.bulk.tensor.2d.shared::cluster.global.mbarrier::complete_tx::bytes.L2::cache_hint [%0 + 4096], [%4, {%8, %9}], [%2], %15;\n"
            "@e cp.async.bulk.wait_group.read 0;\n"
            "@p cp.async.bulk.tensor.2d.global.shared::cta.bulk_group [%5, {%10, %11}], [%1 + 6144];\n"
            "@e cp.async.bulk.commit_group;\n"
            "bar.warp.sync 0xffffffff;\n}"
            :: "r"(st), "r"(st ^ ATT_SLOT), "r"(b), "l"(mqk), "l"(mv), "l"(mo), "r"(pq >> 16), "r"(pq & 2047),
               "r"((pv >> 16) + 2 * DM), "r"(pv & 2047), "r"(po >> 16), "r"(po & 2047), "r"(po & 0x8000),
               "r"(col + 256 + 2 * DM), "r"(0), "l"(pol) : "memory");
    };
    auto publish = [&](auto pending, int part) {
        asm volatile("{\n.reg .pred e;\n.reg .u32 n;\n"
            "elect.sync _|e, 0xffffffff;\n"
            "cp.async.bulk.wait_group %2;\n"
            "@e atom.acq_rel.cta.shared.add.u32 n, [%1], 1;\n"
            "setp.eq.and.u32 e, n, 11, e;\n"
            "@e red.release.gpu.global.add.u32 [%0], 1;\n}"
            :: "l"(g_flags + F_O * 512 + part * 32), "r"(rest_bar + 8 + part * 4), "n"(pending.value) : "memory");
    };
    if (elect_one()) {
        mbar_init(bar, 1); mbar_init(bar + 8, 1);
        if (warp == 2) { mbar_init(rest_bar, 32); sts64f(rest_bar + 8, 0.f, 0.f); }
        asm volatile("fence.mbarrier_init.release.cluster;" ::: "memory");
        if (warp == 9) {
            prefetch_map(mqk); prefetch_map(mv); prefetch_map(mo);
            flag_wait(g_flags + F_QKV * 512 + grp * 32, epoch * CNT_QKV);
        }
    }
    __syncthreads();
    if (elect_one()) {
        fence_proxy_async();
        mbar_expect_tx(bar + 8, 8192);
        tma_3d(buf + ATT_SLOT, mqk, bar + 8, col, first, 0, pol);
        tma_2d(buf + ATT_SLOT + 4096, mv, bar + 8, col + 2 * DM, first - 16, pol);
        tma_2d(buf + ATT_SLOT + 6144, mv, bar + 8, col + DM, first - 16, pol);
        mbar_expect_tx(bar, 6144);
        tma_3d(buf, mqk, bar, col, first + 16, 0, pol);
        tma_2d(buf + 4096, mv, bar, col + 2 * DM, first, pol);
        if (warp == 0) TRACE(9);
        if (warp == 9) g_epoch[blockIdx.x * 16] = epoch;
    }
    __syncwarp();
    if (warp == 11 && lane < 4) flag_add(g_flags + F_EARLY * 512 + (grp * 4 + lane) * 32);
    mbar_wait(bar + 8, 0);
#pragma unroll
    for (int h = 0; h < 2; h++) {
        kp[h] = ldsm4(buf + ATT_SLOT + 5120 + (koff ^ (h * 64)));
        vp[h] = ldsm4_t(buf + ATT_SLOT + 3072 + (koff ^ (h * 64)));
    }
    scores(buf + ATT_SLOT, first);
    uint32_t pm = 0x8000, p0 = col << 16 | first, p1 = p0 + 16, p2 = p0 + 32, p3 = p0 + 48;
    exchange(buf + ATT_SLOT, bar + 8, pm, p1, p2);
    logits();
    row_max();
    uint32_t st = buf, b = bar, cnt = 1;
    const uint32_t relay = warp == 2 ? 7 : 0;
    bool ready = false;
#pragma unroll 1
    while (p0 >> 16 < col + 256) {
        uint32_t pa[2], pb[2];
        if (!ready) mbar_wait(b, (cnt >> 1) & 1);
        uint4 v[2][2];
#pragma unroll
        for (int h = 0; h < 2; h++) {
            const float ma = -LOG2E * bf_lo(m[h]), mb = -LOG2E * bf_hi(m[h]);
            const float a0 = ex2_fast(fmaf(bf_lo(l0[h]), LOG2E, ma)), a1 = ex2_fast(fmaf(bf_lo(l1[h]), LOG2E, ma));
            const float b0 = ex2_fast(fmaf(bf_hi(l0[h]), LOG2E, mb)), b1 = ex2_fast(fmaf(bf_hi(l1[h]), LOG2E, mb));
            float sum[4] = {0.f, 0.f, 0.f, 0.f};
            mma_1688(sum, pack_bf16(a0, a1), pack_bf16(b0, b1), 0x3f803f80u);
            const float ra = rcp_fast(sum[0]), rb = rcp_fast(sum[2]);
            pa[h] = pack_bf16(a0 * ra, a1 * ra);
            pb[h] = pack_bf16(b0 * rb, b1 * rb);
        }
        scores(st, p1);
#pragma unroll
        for (int h = 0; h < 2; h++) {
            v[h][0] = ldsm4_t(st + 4096 + (qoff ^ (h * 64)));
            v[h][1] = ldsm4_t(st + 4096 + (qoff ^ (h * 64 + 32)));
        }
        if (cnt == relay) {
            flag_wait<true>(g_flags + F_QKV * 512 + 128 + grp * 32, epoch * CNT_QKV);
            fence_proxy_async();
            mbar_arrive(rest_bar);
        }
        if (cnt == 8) {
#pragma unroll 1
            for (int spins = 0; !__all_sync(0xffffffffu, mbar_try_wait(rest_bar, 0)) && spins < (1 << 17); spins++) {}
        }
        if (cnt == 37) publish(std::integral_constant<int, 1>(), 0);
        exchange(st, b, pm, p2, p3);
        pm = p0; p0 = p1; p1 = p2; p2 = p3; p3 = next(p3);
        logits();
        float o[2][4][4];
#pragma unroll
        for (int h = 0; h < 2; h++) {
            const uint32_t prev[4] = {vp[h].x, vp[h].y, vp[h].z, vp[h].w};
            const uint32_t own[8] = {v[h][0].x, v[h][0].y, v[h][0].z, v[h][0].w, v[h][1].x, v[h][1].y, v[h][1].z, v[h][1].w};
            const uint32_t a0 = pa[h] & keep, a1 = pa[h] & ~keep, a2 = pb[h] & keep, a3 = pb[h] & ~keep;
            const uint32_t z0 = pa[h] & zero, z1 = pb[h] & zero;
#pragma unroll
            for (int j = 0; j < 4; j++) {
                o[h][j][0] = o[h][j][1] = o[h][j][2] = o[h][j][3] = 0.f;
                mma_1688(o[h][j], a0, z0, prev[j]);
                mma_16816(o[h][j], a1, a2, z1, a3, own[2 * j], own[2 * j + 1]);
            }
            vp[h] = make_uint4(own[1], own[3], own[5], own[7]);
        }
        row_max();
        b ^= 8; cnt++;
        ready = mbar_test(b, (cnt >> 1) & 1);
#pragma unroll
        for (int h = 0; h < 2; h++) {
#pragma unroll
            for (int d = 0; d < 2; d++)
                asm volatile("stmatrix.sync.aligned.m8n8.x4.shared.b16 [%0], {%1,%2,%3,%4};"
                             :: "r"(st + 6144 + (qoff ^ (h * 64 + d * 32))),
                                "r"(pack_bf16(o[h][2 * d][0], o[h][2 * d][1])), "r"(pack_bf16(o[h][2 * d][2], o[h][2 * d][3])),
                                "r"(pack_bf16(o[h][2 * d + 1][0], o[h][2 * d + 1][1])),
                                "r"(pack_bf16(o[h][2 * d + 1][2], o[h][2 * d + 1][3])) : "memory");
        }
        st ^= ATT_SLOT;
    }
    exchange(st, b, pm, p0, p0);
    publish(std::integral_constant<int, 0>(), 1);
    if (threadIdx.x == 0) TRACE(10);
}

struct Params {
    CUtensorMap x, xn, wtail, wqkv, wg, wu, qk, v, o, a2, wo, wd, out;
    const __nv_bfloat16* px;
    uint32_t zero;
    uint32_t role[NCTA];
};

__device__ __forceinline__ void tail_gemm(const Params& prm, uint32_t base, uint32_t tag, int grp, int warp, int lane) {
    const uint32_t full = base + BAR_OFF, empty = full + 32, sum_bar = full + 64, colsum = full + 512;
    if (threadIdx.x == 0) {
        prefetch_map(&prm.x); prefetch_map(&prm.wtail);
        for (int s = 0; s < G1_STAGES; s++) { mbar_init(full + s * 8, 1); mbar_init(empty + s * 8, 4); }
        mbar_init(sum_bar, 2);
        asm volatile("fence.mbarrier_init.release.cluster;" ::: "memory");
    }
    __syncthreads();
    if (warp == 8) {
        if (elect_one()) {
#pragma unroll 1
            for (int i = 0; i < 32; i++) {
                const uint32_t dst = base + (i & 3) * G1_STAGE_BYTES, bar = full + (i & 3) * 8;
                mbar_wait(bar + 32, ~i >> 2 & 1);
                mbar_expect_tx(bar, G1_STAGE_BYTES);
                tma_2d(dst, &prm.x, bar, (i & 15) * 64, grp * 512 + (i >> 4) * 256, stream_policy());
                tma_2d(dst + 16384, &prm.x, bar, (i & 15) * 64, grp * 512 + (i >> 4) * 256 + 128, stream_policy());
                tma_3d(dst + 32768, &prm.wtail, bar, 0, (i & 15) * 64, 0, stream_policy());
            }
        }
    } else if (warp >= 10) {
        float cs[8];
#pragma unroll
        for (int d = 0; d < 8; d++) cs[d] = 0.f;
        const uint32_t wa = base + 32768 + (warp - 10) * 8192 + (lane >> 3) * 2048 + (lane & 7) * 16;
#pragma unroll 1
        for (int i = 0; i < 28; i++) {
            mbar_wait(full + (i & 3) * 8, i >> 2 & 1);
            if (i < 16) {
#pragma unroll
                for (int j = 0; j < 16; j++) {
                    float f[8];
                    unpack8(lds128((wa ^ (j & 1) * 16) + (i & 3) * G1_STAGE_BYTES + j * 128), f);
#pragma unroll
                    for (int d = 0; d < 8; d++) cs[d] += f[d];
                }
            }
            if (i == 15) {
#pragma unroll
                for (int d = 0; d < 8; d++) {
                    cs[d] += __shfl_xor_sync(0xffffffffu, cs[d], 2);
                    cs[d] += __shfl_xor_sync(0xffffffffu, cs[d], 4);
                }
#pragma unroll
                for (int d = 0; d < 8; d += 2)
                    sts64f(colsum + (warp - 10) * 256 + (lane >> 3) * 64 + (lane & 1) * 32 + d * 4, cs[d], cs[d + 1]);
            }
            __syncwarp();
            if (lane == 0) {
                mbar_arrive(empty + (i & 3) * 8);
                if (i == 15) mbar_arrive(sum_bar);
            }
        }
    } else if (warp < 8) {
        const uint32_t da = desc_a(base + (warp >> 2) * 16384);
#pragma unroll 1
        for (int pass = 0; pass < 2; pass++) {
            const int mblk = grp * 4 + pass * 2 + (warp >> 2);
            const float2* const sp = g_stats + mblk * 128 + (warp & 3) * 16 + (lane >> 2);
            uint2 st[4] = {};
            auto fetch_stats = [&]() {
                bool missing = false;
#pragma unroll
                for (int r = 0; r < 4; r++) {
                    if (((st[r].x ^ tag) | (st[r].y ^ tag)) & 3) {
                        missing = true;
                        asm volatile("ld.relaxed.gpu.global.v2.b32 {%0,%1}, [%2];"
                                     : "=r"(st[r].x), "=r"(st[r].y) : "l"(sp + r / 2 * 64 + r % 2 * 8) : "memory");
                    }
                }
                return missing;
            };
            float acc[2][64];
#pragma unroll
            for (int i = 0; i < 64; i++) acc[0][i] = acc[1][i] = 0.f;
#pragma unroll 1
            for (int k = 0; k < G1_KSTEPS; k++) {
                mbar_wait(full + (k & 3) * 8, k >> 2 & 1);
                mma_step_tail(acc[0], da, base + 32768, (k & 3) * (G1_STAGE_BYTES / 16));
                mma_step_tail(acc[1], da + 512, base + 32768, (k & 3) * (G1_STAGE_BYTES / 16));
                wg_wait<2>();
                if (k > 0 && (threadIdx.x & 127) == 0) mbar_arrive(empty + (k - 1 & 3) * 8);
                if (k == 13) fetch_stats();
            }
#pragma unroll 1
            for (int spins = 0; fetch_stats() && spins < (1 << 16); spins++) {}
            mbar_wait(sum_bar, 0);
            wg_wait<0>();
            fence_regs(acc[0]); fence_regs(acc[1]);
            if ((threadIdx.x & 127) == 0) mbar_arrive(empty + 24);
            if (threadIdx.x == 0) TRACE(52 + pass);
#pragma unroll
            for (int q = 0; q < 8; q++) {
                const float2 c0 = lds64f(colsum + q * 64 + (lane & 3) * 8), c1 = lds64f(colsum + q * 64 + 32 + (lane & 3) * 8);
                uint32_t v[8];
#pragma unroll
                for (int r = 0; r < 4; r++) {
                    const float* a = acc[r / 2] + 8 * q + r % 2 * 2;
                    const float shift = __uint_as_float(st[r].x ^ tag), inv = __uint_as_float(st[r].y ^ tag);
                    v[2 * r] = pack_bf16(fmaf(shift, c0.x, a[0]) * inv, fmaf(shift, c0.y, a[1]) * inv);
                    v[2 * r + 1] = pack_bf16(fmaf(shift, c1.x, a[4]) * inv, fmaf(shift, c1.y, a[5]) * inv);
                }
                uint4* const p = g_tail + (q * 16 + mblk) * 256 + (threadIdx.x & 127);
                p[0] = make_uint4(v[0], v[1], v[2], v[3]);
                p[128] = make_uint4(v[4], v[5], v[6], v[7]);
            }
            if (threadIdx.x == 0) TRACE(50 + pass);
        }
    }
}

__device__ __forceinline__ bool tile_is_qkv(int nt) { return nt < 4 || (nt >= 8 && nt < 16); }
__device__ __forceinline__ int tile_index(int nt) { return nt < 4 ? nt + 8 : (nt < 8 ? nt - 4 : (nt < 16 ? nt - 8 : nt - 12)); }

__global__ void __cluster_dims__(2, 1, 1) __launch_bounds__(384, 1)
fused_kernel(const __grid_constant__ Params prm) {
    extern __shared__ __align__(1024) uint8_t smem_raw[];
    const uint32_t base = smem_u32(smem_raw) & ~1023u;
    const uint32_t bars = base + BAR_OFF;
    auto full1 = [&](int s) { return bars + s * 8; };
    auto empty1 = [&](int s) { return bars + 32 + s * 8; };
    auto full2 = [&](int s) { return bars + 64 + s * 8; };
    auto empty2 = [&](int s) { return bars + 128 + s * 8; };
    const uint32_t sig_bar = bars + 192, dep_bar = bars + 256, cs_bar = bars + 304, fold_bar = bars + 320, x_bar = bars + 336;
    const uint32_t colsum = bars + 512, stats = bars + 1536;
    auto stage2 = [&](int q) { return base + q * G2_STAGE_BYTES; };
    const uint32_t aux = base + AUX_OFF;

    const int warp = __shfl_sync(0xffffffffu, threadIdx.x >> 5, 0);
    const int lane = threadIdx.x & 31;
    const int rank = blockIdx.x & 1;
    const uint32_t role = prm.role[blockIdx.x];
    const int mblk = role & 15, nslot = role >> 4;

    if (blockIdx.x >= NGEMM) {
        if (threadIdx.x == 0) { TRACE_GT(0); TRACE(1); }
        const unsigned epoch = __ldcg(g_epoch + blockIdx.x * 16) + 1;
        tail_gemm(prm, base, 1 + (epoch & 1), blockIdx.x - NGEMM, warp, lane);
        attention(&prm.qk, (base + 2 * ATT_SLOT - 1) & ~(2u * ATT_SLOT - 1), prm.zero, epoch, blockIdx.x - NGEMM, warp, lane);
    } else if (warp >= 8) {
        unsigned* const flags = g_flags + mblk * 32;
        const CUtensorMap* const w0 = nslot < 4 ? &prm.wqkv : (rank ? &prm.wu : &prm.wg);
        const int w0_col = nslot < 4 ? 32 + nslot * 4 + rank * 2 : nslot * 2 - 8;
        if (elect_one()) {
            if (warp == 8) {
                TRACE_GT(0); TRACE(1);
                prefetch_map(&prm.x); prefetch_map(w0);
                for (int s = 0; s < G1_STAGES; s++) { mbar_init(full1(s), 1); mbar_init(empty1(s), 4); }
            } else if (warp == 9) {
                for (int s = 0; s < G2_STAGES; s++) { mbar_init(full2(s), 1); mbar_init(empty2(s), 4); }
            } else if (warp == 10) {
                for (int s = 0; s < 7; s++) mbar_init(sig_bar + s * 8, 8);
                mbar_init(fold_bar, 2); mbar_init(x_bar, 1);
            } else {
                for (int s = 0; s < 8; s++) mbar_init(dep_bar + s * 8, 1);
                TRACE_CLEAR();
            }
            asm volatile("fence.mbarrier_init.release.cluster;" ::: "memory");
        }
        __syncwarp();
        asm volatile("barrier.cluster.arrive.relaxed.aligned;" ::: "memory");
        if (warp == 8 && lane == 0) {
            mbar_expect_tx(full1(0), G1_STAGE_BYTES);
            tma_2d(base, &prm.x, full1(0), 0, mblk * 128, stream_policy());
            prefetch_3d(w0, 0, w0_col, stream_policy());
            TRACE(15);
        }
        asm volatile("setmaxnreg.dec.sync.aligned.u32 %0;" :: "n"(AUX_REGS));
        asm volatile("barrier.cluster.wait.acquire.aligned;" ::: "memory");

        if (warp == 8) {
            if (elect_one()) { TRACE(2); tma_3d_mc(base + A_BYTES + rank * 16384, w0, full1(0), 0, w0_col, stream_policy()); }
            uint32_t ph = 1;
#pragma unroll 1
            for (int t = 0; t < G1_TILES; t++) {
                const int nt = t * 8 + nslot;
                const CUtensorMap* const mb = tile_is_qkv(nt) ? &prm.wqkv : (rank ? &prm.wu : &prm.wg);
                const int col = tile_is_qkv(nt) ? tile_index(nt) * 4 + rank * 2 : tile_index(nt) * 2;
                if (t == 1) { TRACE(14); mbar_wait_warp(dep_bar, 0); TRACE(3); }
#pragma unroll 1
                for (int k = t == 0; k < G1_KSTEPS; k++) {
                    const int s = k & 3;
                    if (t == 0 && k == G1_STAGES && elect_one()) {
                        prefetch_map(&prm.xn); prefetch_map(&prm.wqkv); prefetch_map(&prm.wu); prefetch_map(&prm.wg);
                        prefetch_map(&prm.a2); prefetch_map(&prm.wo); prefetch_map(&prm.wd); prefetch_map(&prm.out);
                    }
                    mbar_wait_warp(empty1(s), ph);
                    const uint32_t sa = base + s * G1_STAGE_BYTES;
                    load_stage1(sa, sa + A_BYTES + rank * 16384, full1(s), t ? &prm.xn : &prm.x, mb, k * 64, mblk * 128, col,
                                t & 3, stream_policy());
                    if (s == 3) ph ^= 1;
                }
            }
            if (elect_one()) {
                mbar_expect_tx(x_bar, 32768);
                tma_2d(aux, &prm.x, x_bar, nslot * 128, mblk * 128, stream_policy());
                tma_2d(aux + 16384, &prm.x, x_bar, nslot * 128 + 64, mblk * 128, stream_policy());
            }
            TRACE(4);
            mbar_wait_warp(dep_bar + 8, 0);
            TRACE(5);
            int q = 0; uint32_t ph2 = 1;
#pragma unroll 1
            for (int u = 0; u < G2_KSTEPS; u++) {
                if (u == G2_LATE || u == G2_DSTEPS || u == G2_LAST) {
                    TRACE(u == G2_LATE ? 6 : (u == G2_DSTEPS ? 32 : 40));
                    mbar_wait_warp(dep_bar + (u == G2_LATE ? 16 : (u == G2_DSTEPS ? 24 : 32)), 0);
                    TRACE(u == G2_LATE ? 7 : (u == G2_DSTEPS ? 33 : 41));
                }
                const uint32_t sa = stage2(q);
                const bool down = u < G2_DSTEPS;
                const int k = down ? u : (u & 3) * 4 + (u - G2_DSTEPS) / 4;
                mbar_wait_warp(u < G2_STAGES ? empty1((u * 2 + 1) / 3) : empty2(q), u < G2_STAGES ? ph : ph2);
                load_stage2(sa, sa + A_BYTES + rank * 8192, full2(q), &prm.a2, down ? &prm.wd : &prm.wo, (down ? DM : 0) + k * 64,
                            mblk * 64, nslot * 128 + rank * 64, k * 2, stream_policy());
                if (++q == G2_STAGES) { q = 0; ph2 ^= 1; }
            }
            TRACE(8);
        } else if (warp == 9) {
            if (lane == 0) {
                const unsigned epoch = __ldcg(g_epoch + blockIdx.x * 16 + 2) + 1;
                mbar_wait(sig_bar, 0);
                TRACE(11);
                flag_add(flags + F_LN * 512);
                TRACE(42);
                flag_wait(flags + F_LN * 512, epoch * CNT_LN);
                fence_proxy_async();
                mbar_arrive(dep_bar);
                g_epoch[blockIdx.x * 16 + 2] = epoch;
                for (int p = nslot < 4 ? 2 : 1; p < 7; p++) {
                    mbar_wait(sig_bar + p * 8, 0);
                    if (p == 2) TRACE(37);
                    flag_add(p == 2 || p == 3 ? g_flags + F_QKV * 512 + (p * 4 - 8 + (nslot & 3)) * 32
                                              : flags + (p < 6 ? F_EARLY : F_LATE) * 512);
                    if (p == 2) TRACE(43);
                }
            }
        } else {
            const int w = warp - 10;
            const unsigned epoch = __ldcg(g_epoch + blockIdx.x * 16 + w) + 1;
            const uint32_t tag = 1 + (epoch & 1);
            mbar_wait(CSAT, 0);
            if (elect_one()) {
                mbar_expect_tx(cs_bar + w * 8, 16384);
                tma_3d(aux + w * 16384, w0, cs_bar + w * 8, 0, ((mblk & ~1) + w) * 64, w0_col, stream_policy());
            }
            float cs[8];
#pragma unroll
            for (int d = 0; d < 8; d++) cs[d] = 0.f;
            const uint32_t wa = aux + w * 8192 + (lane >> 3) * 128 + (((lane & 7) ^ (lane >> 3)) << 4);
            uint4 v[9];
            auto fetch = [&](int h, int i) {
#pragma unroll
                for (int j = 0; j < 4; j++) v[h * 4 + j] = lds128((wa ^ (j & 1) * 64) + h * 16384 + i * 2048 + j * 512);
            };
            auto add = [&](int h) {
#pragma unroll
                for (int j = 0; j < 4; j++) {
                    float f[8];
                    unpack8(v[h * 4 + j], f);
#pragma unroll
                    for (int d = 0; d < 8; d++) cs[d] += f[d];
                }
            };
            mbar_wait(cs_bar, 0);
            fetch(0, 0);
            mbar_wait(cs_bar + 8, 0);
            if (w == 0 && lane == 0) TRACE(36);
#pragma unroll 1
            for (int i = 0; i < 4; i++) {
                fetch(1, i);
                add(0);
                fetch(0, (i + 1) & 3);
                add(1);
            }
#pragma unroll
            for (int d = 0; d < 4; d++)
                cs[d] = (lane & 16 ? cs[d + 4] : cs[d]) + __shfl_xor_sync(0xffffffffu, lane & 16 ? cs[d] : cs[d + 4], 16);
#pragma unroll
            for (int d = 0; d < 2; d++)
                cs[d] = (lane & 8 ? cs[d + 2] : cs[d]) + __shfl_xor_sync(0xffffffffu, lane & 8 ? cs[d] : cs[d + 2], 8);
            st_tagged(g_colsum + (nslot * 2 + rank) * 1024 + (mblk >> 1) * 128 + w * 64 + (lane & 7) * 8 + (lane >> 3) * 2,
                      cs[0], cs[1], tag);
            if (w == 0 && lane == 0) TRACE(34);
#pragma unroll
            for (int m = 0; m < 9; m++) v[m] = make_uint4(0, 0, 0, 0);
#pragma unroll 1
            for (int spins = 0; spins < (1 << 16); spins++) {
                bool missing = false;
#pragma unroll
                for (int m = 0; m < 9; m++) {
                    if (untagged(v[m], tag)) {
                        missing = true;
                        v[m] = m < 8 ? ld_relaxed(g_colsum + (nslot * 2 + w) * 1024 + m * 128 + lane * 4)
                                     : ld_relaxed(g_stats + mblk * 128 + w * 64 + lane * 2);
                    }
                }
                if (!missing) break;
            }
            float4 c = make_float4(0.f, 0.f, 0.f, 0.f);
#pragma unroll
            for (int m = 0; m < 8; m++) {
                c.x += __uint_as_float(v[m].x ^ tag); c.y += __uint_as_float(v[m].y ^ tag);
                c.z += __uint_as_float(v[m].z ^ tag); c.w += __uint_as_float(v[m].w ^ tag);
            }
            sts128(stats + w * 512 + lane * 16, make_uint4(v[8].x ^ tag, v[8].y ^ tag, v[8].z ^ tag, v[8].w ^ tag));
            const uint32_t ca = colsum + (w * 8 + (lane >> 2)) * 64 + (lane & 1) * 32 + (lane & 2) * 4;
            sts64f(ca, c.y, c.x);
            sts64f(ca + 16, c.w, c.z);
            __syncwarp();
            if (lane == 0) {
                mbar_arrive(fold_bar);
                g_epoch[blockIdx.x * 16 + w] = epoch;
                if (w == 0) {
                    TRACE(35);
                    flag_wait(flags + F_EARLY * 512, epoch * CNT_EARLY);
                    fence_proxy_async(); mbar_arrive(dep_bar + 8);
                    flag_wait(flags + F_LATE * 512, epoch * CNT_LATE);
                    fence_proxy_async(); mbar_arrive(dep_bar + 16);
                    flag_wait(g_flags + F_O * 512, epoch * CNT_O);
                    fence_proxy_async(); mbar_arrive(dep_bar + 24);
                    flag_wait(g_flags + F_O * 512 + 32, epoch * CNT_O);
                    fence_proxy_async(); mbar_arrive(dep_bar + 32);
                }
            }
        }
    } else {
        asm volatile("barrier.cluster.arrive.relaxed.aligned;" ::: "memory");
        asm volatile("setmaxnreg.inc.sync.aligned.u32 %0;" :: "n"(CONSUMER_REGS));
        const int wg = __shfl_sync(0xffffffffu, threadIdx.x >> 7, 0);
        const int cw = threadIdx.x >> 5;
        const int tid = threadIdx.x & 127;
        float acc[128];
        uint32_t pk[64];
#pragma unroll
        for (int i = 0; i < 64; i++) asm volatile("mov.b32 %0, 0;" : "=r"(pk[i]));
#pragma unroll
        for (int i = 0; i < 128; i++) asm volatile("mov.b32 %0, 0;" : "=f"(acc[i]));
        asm volatile("barrier.cluster.wait.acquire.aligned;" ::: "memory");

        const int orow = ((lane >> 2) & 1) * (SEQ / 2) + mblk * 64 + cw * 8 + (lane >> 3);
        __nv_bfloat16* optr = g_xn + (mblk * 128 + nslot * 16 + cw * 2) * DM + lane * 8;
        const uint32_t da = desc_a(base + wg * 8192), db = desc_b(base + A_BYTES);
        auto release = [&](uint32_t bar) { if (tid < 2) mbar_arrive_cluster(bar, tid); };
        auto store_pk = [&](__nv_bfloat16* p, int j) {
            *reinterpret_cast<uint4*>(p) = make_uint4(pk[4 * j], pk[4 * j + 1], pk[4 * j + 2], pk[4 * j + 3]);
        };
        auto chunk_geglu = [&](int j) {
#pragma unroll
            for (int i = 4 * j; i < 4 * j + 4; i++) pk[i] = geglu2(pk[i], pk[32 + i]);
            store_pk(optr + (j & 1) * 4 * K2 + (j >> 1) * 32, j);
        };
        auto chunk_qkv = [&](int c) {
            store_pk(optr + c * 32, 2 * c);
            store_pk(optr + 4 * NQKV + c * 32, 2 * c + 1);
        };
        auto signal_stores = [&](int p) { __syncwarp(); if (lane == 0) mbar_arrive(sig_bar + p * 8); };

        auto chunk_ln = [&](int k) {
            float* const mo = reinterpret_cast<float*>(pk + 32);
            if (k == 0) {
                const uint4* xp = reinterpret_cast<const uint4*>(prm.px + (optr - g_xn));
                pk[38] = __ldcg(g_epoch + blockIdx.x * 16 + 2);
#pragma unroll
                for (int i = 0; i < 8; i++) {
                    const uint4 v = ldg_stream(xp + i * 32, stream_policy());
                    pk[4 * i] = v.x; pk[4 * i + 1] = v.y; pk[4 * i + 2] = v.z; pk[4 * i + 3] = v.w;
                }
            } else if (k >= LN_STEP && k < LN_STEP + 3) {
                if (k == LN_STEP) {
                    mo[0] = bf_lo(uniform(pk[0])); mo[1] = bf_lo(uniform(pk[16]));
                    mo[2] = mo[3] = mo[4] = mo[5] = 0.f;
                }
#pragma unroll
                for (int i = (k - LN_STEP) * 11; i < (k - LN_STEP) * 11 + 11 && i < 32; i++) {
                    const int r = i & 1;
                    const uint32_t w = pk[r * 16 + i / 2];
                    const float lo = bf_lo(w) - mo[r], hi = bf_hi(w) - mo[r];
                    mo[2 + r] += lo + hi;
                    mo[4 + r] = fmaf(hi, hi, fmaf(lo, lo, mo[4 + r]));
                }
            } else if (k == LN_STEP + 3) {
                const bool second = lane & 16;
                float m1 = (second ? mo[3] : mo[2]) + __shfl_xor_sync(0xffffffffu, second ? mo[2] : mo[3], 16);
                float m2 = (second ? mo[5] : mo[4]) + __shfl_xor_sync(0xffffffffu, second ? mo[4] : mo[5], 16);
#pragma unroll
                for (int o = 8; o > 0; o >>= 1) {
                    m1 += __shfl_xor_sync(0xffffffffu, m1, o);
                    m2 += __shfl_xor_sync(0xffffffffu, m2, o);
                }
                m1 *= 1.f / DM;
                const float var = fmaxf(fmaf(-m1, m1, m2 * (1.f / DM)), 0.f);
                const float mean = round_bf16((second ? mo[1] : mo[0]) + m1);
                const float inv = rcp_fast(round_bf16(sqrt_fast(round_bf16(round_bf16(var) + 1e-5f))));
                if ((lane & 15) == 0) st_tagged(g_stats + (uint32_t)(optr - g_xn) / DM + second, -mean, inv, 2 - (pk[38] & 1));
                const uint32_t split = pack_bf16(inv - round_bf16(inv), inv);
#pragma unroll
                for (int r = 0; r < 2; r++) {
                    const uint32_t f = __shfl_sync(0xffffffffu, split, r * 16);
                    pk[32 + 3 * r] = __byte_perm(__shfl_sync(0xffffffffu, __float_as_uint(mean), r * 16), 0, 0x3232);
                    pk[33 + 3 * r] = __byte_perm(f, 0, 0x3232);
                    pk[34 + 3 * r] = __byte_perm(f, 0, 0x1010);
                }
            } else if (k >= LN_STEP + 4 && k < LN_STEP + 7) {
#pragma unroll
                for (int i = (k - LN_STEP - 4) * 3; i < (k - LN_STEP - 3) * 3 && i < 8; i++) {
                    const uint32_t* n = pk + 32 + i / 4 * 3;
#pragma unroll
                    for (int j = 4 * i; j < 4 * i + 4; j++) pk[j] = mul2_bf16x2(sub_bf16x2(pk[j], n[0]), n[1], n[2]);
                    store_pk(optr + i * 256, i);
                }
                if (k == LN_STEP + 6) signal_stores(0);
            } else if (k == FOLD_STEP) {
                mbar_wait(fold_bar, 0);
#pragma unroll
                for (int j = 0; j < 16; j++) {
                    const uint4 c = lds128(colsum + j * 64 + (lane & 3) * 16);
                    pk[4 * j] = c.x; pk[4 * j + 1] = c.y; pk[4 * j + 2] = c.z; pk[4 * j + 3] = c.w;
                }
            }
        };

        bool gated = false;
#pragma unroll 1
        for (int t = 0; t < G1_TILES; t++) {
#pragma unroll
            for (int k = 0; k < G1_KSTEPS; k++) {
                const int s = k & 3;
                TRACE_STEP(t, k, 0);
                mbar_wait(full1(s), (k >> 2) & 1);
                if (k == 0) TRACE_S(12, t, 0);
                TRACE_STEP(t, k, 1);
                if (wg == 1 && k == G1_KSTEPS - (t ? G1_SKEW : SK0)) asm volatile("bar.sync 1, 256;" ::: "memory");
                if (t == G1_TILES - 1) mma_step240(acc, da, db, s * G1_STAGE_BYTES / 16, k);
                else mma_step(acc, da, db, s * G1_STAGE_BYTES / 16, k);
                if (wg == 0 && k == G1_KSTEPS - 1) asm volatile("bar.arrive 1, 256;" ::: "memory");
                wg_wait<1>();
                if (k > 0) release(empty1((k - 1) & 3));
                TRACE_STEP(t, k, 2);
                if (t == 0) chunk_ln(k);
                if (k >= 1 && k <= 8 && gated) {
                    chunk_geglu(k - 1);
                    if (k == 8) signal_stores(t == 1 ? 1 : t + 1);
                }
                if (t != 0 && !gated) {
                    if (k == 0) { chunk_qkv(0); chunk_qkv(1); }
                    if (k >= 6 && k <= 11) chunk_qkv(k - 4);
                    if ((k == 0 || k == 11) && t == 2) signal_stores(k ? 3 : 2);
                }
            }
            wg_wait<0>();
            fence_regs(acc);
            release(empty1(3));
            if (t == 0) {
                const uint32_t sp = stats + (cw * 16 + (lane >> 2)) * 8;
                const float2 sa = lds64f(sp), sb = lds64f(sp + 64);
#pragma unroll
                for (int i = 0; i < 128; i++) {
                    const float2 st = i & 2 ? sb : sa;
                    acc[i] = fmaf(st.x, __uint_as_float(pk[i / 4 * 2 + (~i & 1)]), acc[i]) * st.y;
                }
                fence_regs(acc);
            }
#pragma unroll
            for (int i = 0; i < 64; i++) {
                const int e = (i & ~7) * 2 + (i & 3) * 4 + (i & 4) / 2;
                pk[i] = pack_bf16(acc[e], acc[e + 1]);
            }
            const int nt = t * 8 + nslot;
            gated = !tile_is_qkv(nt);
            optr = !gated ? g_qkv + (size_t)orow * NQKV + tile_index(nt) * 256 + (lane & 3) * 8
                                : g_a2 + (size_t)orow * K2 + DM + tile_index(nt) * 128 + (lane & 3) * 8;
            TRACE_S(16 + wg * 8 + t, 0, 0);
        }

        float accd[64], accs[64];
#pragma unroll
        for (int i = 0; i < 64; i++) accd[i] = 0.f;
#pragma unroll
        for (int u = 0; u < 9; u++) {
            const int q = u % G2_STAGES;
            mbar_wait(full2(q), (u / G2_STAGES) & 1);
            mma_step(accd, da, db, q * G2_STAGE_BYTES / 16, u);
            wg_wait<1>();
            if (u > 0) release(empty2((u - 1) % G2_STAGES));
            if (u == 0) {
                const uint4 v = ldg_stream(g_tail + role * 256 + threadIdx.x, stream_policy());
                pk[58] = v.x; pk[59] = v.y; pk[62] = v.z; pk[63] = v.w;
            }
            if (u >= 1) { chunk_geglu(u - 1); if (u == 8) signal_stores(6); }
        }
        {
            int q = 9 % G2_STAGES, qp = 8 % G2_STAGES; uint32_t ph = (9 / G2_STAGES) & 1;
#pragma unroll 1
            for (int u = 9; u < G2_DSTEPS; u++) {
                mbar_wait(full2(q), ph);
                mma_step(accd, da, db, q * (G2_STAGE_BYTES / 16), 1);
                wg_wait<1>();
                release(empty2(qp));
                qp = q;
                if (++q == G2_STAGES) { q = 0; ph ^= 1; }
            }
        }
        TRACE_S(16 + wg * 8 + 5, 0, 0);
#pragma unroll
        for (int i = 0; i < 64; i++) accs[i] = 0.f;
        uint32_t gk[32], xr[32];
        const uint32_t xs = aux + cw * 2048;
        const uint32_t xrow = xs + ((lane & 7) + ((lane >> 3) & 1) * 8) * 128;
        auto xaddr = [&](int j) { return xrow + (j >> 2) * 16384 + (((((j & 3) * 2) + (lane >> 4)) ^ (lane & 7)) << 4); };
#pragma unroll
        for (int u = G2_DSTEPS; u < G2_KSTEPS; u++) {
            const int q = u % G2_STAGES, v = u - G2_DSTEPS;
            mbar_wait(full2(q), (u / G2_STAGES) & 1);
            if (G2_SKEW > 0 && wg == 1 && u == G2_KSTEPS - G2_SKEW) asm volatile("bar.sync 1, 256;" ::: "memory");
            mma_step(accs, da, db, q * G2_STAGE_BYTES / 16, v);
            if (G2_SKEW > 0 && wg == 0 && u == G2_KSTEPS - 1) asm volatile("bar.arrive 1, 256;" ::: "memory");
            if (v >= 1 && v <= 8) {
#pragma unroll
                for (int i = 4 * (v - 1); i < 4 * v; i++) {
                    const uint32_t d2 = pack_bf16(accd[2 * i], accd[2 * i + 1]);
                    gk[i] = pack_bf16(silu(bf_lo(d2)), silu(bf_hi(d2)));
                }
            }
            if (v == 9) mbar_wait(x_bar, 0);
            if (v >= 9 && v <= 12) {
#pragma unroll
                for (int j = 2 * (v - 9); j < 2 * (v - 8); j++)
                    asm volatile("ldmatrix.sync.aligned.m8n8.x4.shared.b16 {%0,%1,%2,%3}, [%4];"
                                 : "=r"(xr[4 * j]), "=r"(xr[4 * j + 1]), "=r"(xr[4 * j + 2]), "=r"(xr[4 * j + 3])
                                 : "r"(xaddr(j)) : "memory");
            }
            wg_wait<1>();
            if (v == 0) fence_regs(accd);
            if (u - 1 + G2_STAGES < G2_KSTEPS) release(empty2((u - 1) % G2_STAGES));
        }
        wg_wait<0>();
        fence_regs(accs);
        TRACE_S(16 + wg * 8 + 6, 0, 0);
#pragma unroll
        for (int j = 0; j < 8; j++) {
            uint32_t r[4];
#pragma unroll
            for (int i = 0; i < 4; i++) {
                const int e = j * 4 + i;
                r[i] = add_bf16x2(xr[e], mul_bf16x2(pack_bf16(accs[2 * e], accs[2 * e + 1]), gk[e]));
            }
            asm volatile("stmatrix.sync.aligned.m8n8.x4.shared.b16 [%0], {%1,%2,%3,%4};"
                         :: "r"(xaddr(j)), "r"(r[0]), "r"(r[1]), "r"(r[2]), "r"(r[3]) : "memory");
            if (j == 3 || j == 7) {
                asm volatile("fence.proxy.async.shared::cta;" ::: "memory");
                __syncwarp();
                if (lane == 0) {
                    tma_store_2d(&prm.out, xs + (j >> 2) * 16384, nslot * 128 + (j >> 2) * 64, mblk * 128 + cw * 16);
                    asm volatile("cp.async.bulk.commit_group;" ::: "memory");
                }
            }
        }
        if (lane == 0) asm volatile("cp.async.bulk.wait_group.read 0;" ::: "memory");
        if (tid == 0) { TRACE(16 + wg * 8 + 7); if (wg == 1) TRACE_GT(13); TRACE_DUMP(); }
    }
}

typedef CUresult (*EncodeFn)(CUtensorMap*, CUtensorMapDataType, cuuint32_t, void*, const cuuint64_t*, const cuuint64_t*,
                             const cuuint32_t*, const cuuint32_t*, CUtensorMapInterleave, CUtensorMapSwizzle,
                             CUtensorMapL2promotion, CUtensorMapFloatOOBfill);

void encode(EncodeFn fn, CUtensorMap* m, const void* ptr, int rank, const cuuint64_t* dims, const cuuint64_t* strides,
            const cuuint32_t* box) {
    const cuuint32_t es[5] = {1, 1, 1, 1, 1};
    fn(m, CU_TENSOR_MAP_DATA_TYPE_BFLOAT16, rank, const_cast<void*>(ptr), dims, strides, box, es,
       CU_TENSOR_MAP_INTERLEAVE_NONE, box[0] == 16 ? CU_TENSOR_MAP_SWIZZLE_32B : CU_TENSOR_MAP_SWIZZLE_128B,
       CU_TENSOR_MAP_L2_PROMOTION_L2_128B, CU_TENSOR_MAP_FLOAT_OOB_FILL_NONE);
}
void encode_2d(EncodeFn fn, CUtensorMap* m, const void* ptr, int cols, int box_rows) {
    const cuuint64_t dims[2] = {(cuuint64_t)cols, SEQ}, strides[1] = {(cuuint64_t)cols * 2};
    const cuuint32_t box[2] = {64, (cuuint32_t)box_rows};
    encode(fn, m, ptr, 2, dims, strides, box);
}
void encode_w1(EncodeFn fn, CUtensorMap* m, const void* ptr, int cols) {
    const cuuint64_t dims[3] = {64, DM, (cuuint64_t)cols / 64}, strides[2] = {(cuuint64_t)cols * 2, 128};
    const cuuint32_t box[3] = {64, 64, 2};
    encode(fn, m, ptr, 3, dims, strides, box);
}
void encode_tail(EncodeFn fn, CUtensorMap* m, const __nv_bfloat16* w) {
    const cuuint64_t dims[3] = {16, DM, 8}, strides[2] = {DF * 2, 256};
    const cuuint32_t box[3] = {16, 64, 8};
    encode(fn, m, w + DF - 1024 + 112, 3, dims, strides, box);
}
void encode_qk(EncodeFn fn, CUtensorMap* m, const void* ptr) {
    const cuuint64_t dims[3] = {DM, SEQ, 3}, strides[2] = {NQKV * 2, DM * 2};
    const cuuint32_t box[3] = {64, 16, 2};
    encode(fn, m, ptr, 3, dims, strides, box);
}
void encode_a2(EncodeFn fn, CUtensorMap* m, const void* ptr) {
    const cuuint64_t dims[3] = {K2, 2, SEQ / 2}, strides[2] = {(cuuint64_t)SEQ * K2, K2 * 2};
    const cuuint32_t box[3] = {64, 2, 64};
    encode(fn, m, ptr, 3, dims, strides, box);
}
void encode_w2(EncodeFn fn, CUtensorMap* m, const void* ptr, int rows) {
    const cuuint64_t rb = DM * 2;
    const cuuint64_t dims[5] = {DM, 2, 4, 4, (cuuint64_t)rows / 32}, strides[4] = {rb, 8 * rb, 2 * rb, 32 * rb};
    const cuuint32_t box[5] = {64, 2, 4, 4, 2};
    encode(fn, m, ptr, 5, dims, strides, box);
}

}

extern "C" void kernel_launch(void* const* d_in, const int* in_sizes, int n_in, void* d_out, int out_size) {
    (void)in_sizes; (void)n_in; (void)out_size;
    static EncodeFn fn = nullptr;
    static void *p_xn = nullptr, *p_qkv = nullptr, *p_a2 = nullptr;
    if (!fn) {
        cudaDriverEntryPointQueryResult st;
        cudaGetDriverEntryPoint("cuTensorMapEncodeTiled", (void**)&fn, cudaEnableDefault, &st);
        cudaGetSymbolAddress(&p_xn, g_xn);
        cudaGetSymbolAddress(&p_qkv, g_qkv);
        cudaGetSymbolAddress(&p_a2, g_a2);
        cudaFuncSetAttribute(fused_kernel, cudaFuncAttributeMaxDynamicSharedMemorySize, SMEM_BYTES);
    }
    Params prm;
    encode_2d(fn, &prm.x, d_in[0], DM, 128);
    encode_2d(fn, &prm.xn, p_xn, DM, 128);
    encode_tail(fn, &prm.wtail, (const __nv_bfloat16*)d_in[5]);
    encode_w1(fn, &prm.wqkv, d_in[1], NQKV);
    encode_w1(fn, &prm.wg, d_in[4], DF);
    encode_w1(fn, &prm.wu, d_in[5], DF);
    encode_qk(fn, &prm.qk, p_qkv);
    encode_2d(fn, &prm.v, p_qkv, NQKV, 16);
    encode_2d(fn, &prm.o, p_a2, K2, 16);
    encode_a2(fn, &prm.a2, p_a2);
    encode_w2(fn, &prm.wo, d_in[2], DM);
    encode_w2(fn, &prm.wd, d_in[6], DF);
    encode_2d(fn, &prm.out, d_out, DM, 16);
    prm.px = (const __nv_bfloat16*)d_in[0];
    prm.zero = 0;
    for (int b = 0; b < NCTA; b++) {
        const int c = b / 2;
        prm.role[b] = (c < 4 ? 32 + c * 8 : (c < 36 ? c - 4 : 33 + (c - 36) / 7 * 8 + (c - 36) % 7)) * 2 + b % 2;
    }
    fused_kernel<<<NCTA, 384, SMEM_BYTES>>>(prm);
}
```

```cpp
#include <cuda_runtime.h>
#include <cuda_bf16.h>
#include <cuda.h>
#include <stdint.h>
#include <type_traits>

#define LNS 3
#define FS 15
#define CA 0x87658765u
#define CB 0x65876587u
#define CST 10
#define CIDX nslot
#define CKEEP 1
#define PACE0 300
#define PACE 450
#define TAIL 0
#define LNL 0
#define TDELAY 0
#define SK0 3

namespace {

constexpr int SEQ = 2048, DM = 1024, DF = 3584, K2 = DM + DF, NQKV = 3 * DM;
constexpr int NGEMM = 128, NCTA = 132;
constexpr int G1_STAGES = 4, G1_STAGE_BYTES = 49152, G1_KSTEPS = 16, G1_TILES = 5;
constexpr int G2_STAGES = 6, G2_STAGE_BYTES = 32768, G2_KSTEPS = 72, G2_LATE = 40, G2_DSTEPS = 56, G2_LAST = 68;
constexpr int LN_STEP = LNS, FOLD_STEP = FS;
constexpr int A_BYTES = 16384;
constexpr int AUX_OFF = G1_STAGES * G1_STAGE_BYTES;
constexpr int BAR_OFF = AUX_OFF + 32768;
constexpr int SMEM_BYTES = BAR_OFF + 2816;
constexpr int G1_SKEW = 2, G2_SKEW = 2;
constexpr int CONSUMER_REGS = 224, AUX_REGS = 56;
constexpr int ATT_SLOT = 8192;

enum { F_LN = 0, F_QKV = 1, F_EARLY = 2, F_LATE = 3, F_O = 4, F_LN2 = 5 };
constexpr unsigned CNT_LN = 8, CNT_QKV = 32, CNT_EARLY = 21, CNT_LATE = 8, CNT_O = 4;

__device__ __align__(1024) __nv_bfloat16 g_xn[SEQ * DM];
__device__ __align__(1024) __nv_bfloat16 g_qkv[SEQ * NQKV];
__device__ __align__(1024) __nv_bfloat16 g_a2[SEQ * K2];
__device__ __align__(128) uint4 g_tail[NGEMM * 256];
__device__ __align__(128) float2 g_stats[SEQ];
__device__ __align__(128) float g_colsum[16 * 1024];
__device__ __align__(128) unsigned g_flags[6 * 16 * 32];
__device__ __align__(128) unsigned g_epoch[NCTA * 16];

struct Params {
    const __nv_bfloat16* px;
    __nv_bfloat16 *pxn, *qkv, *pa2;
    uint4* tail;
    float2* stats;
    float* colsum;
    unsigned *flags, *epoch;
    unsigned long long* trace;
    uint32_t zero;
    CUtensorMap x, wqkv, wg, wu, xn, wtail, qk, v, o, a2, wo, wd, out;
};

extern __shared__ __align__(1024) uint8_t smem_raw[];

#define TRACE(slot) do {} while (0)
#define TRACE_GT(slot) do {} while (0)
#define TRACE_S(slot, v, want) do {} while (0)
#define TRACE_GET(v) do {} while (0)
#define TRACE_PUT(slot, v) do {} while (0)
#define TRACE_DUMP() do {} while (0)
#define TRACE_CLEAR() do {} while (0)
#define STAGE_TRACE 0
#define TRACE_STEP(t, k, i) do {} while (0)

__device__ __forceinline__ uint32_t smem_u32(const void* p) { return (uint32_t)__cvta_generic_to_shared(p); }
__device__ __forceinline__ void mbar_init(uint32_t bar, uint32_t cnt) {
    asm volatile("mbarrier.init.shared::cta.b64 [%0], %1;" :: "r"(bar), "r"(cnt) : "memory");
}
__device__ __forceinline__ void mbar_expect_tx(uint32_t bar, uint32_t bytes) {
    asm volatile("mbarrier.arrive.expect_tx.shared::cta.b64 _, [%0], %1;" :: "r"(bar), "r"(bytes) : "memory");
}
__device__ __forceinline__ void mbar_arrive(uint32_t bar) {
    asm volatile("mbarrier.arrive.shared::cta.b64 _, [%0];" :: "r"(bar) : "memory");
}
__device__ __forceinline__ void mbar_arrive_cluster(uint32_t bar, uint32_t cta) {
    asm volatile("{\n.reg .b32 ra;\nmapa.shared::cluster.u32 ra, %0, %1;\nmbarrier.arrive.shared::cluster.b64 _, [ra];\n}"
                 :: "r"(bar), "r"(cta) : "memory");
}
__device__ __forceinline__ bool mbar_try_wait(uint32_t bar, uint32_t parity) {
    uint32_t ok;
    asm volatile("{\n.reg .pred p;\nmbarrier.try_wait.parity.shared::cta.b64 p, [%1], %2;\nselp.u32 %0, 1, 0, p;\n}"
                 : "=r"(ok) : "r"(bar), "r"(parity) : "memory");
    return ok;
}
__device__ __forceinline__ bool mbar_test(uint32_t bar, uint32_t parity) {
    uint32_t ok;
    asm volatile("{\n.reg .pred p;\nmbarrier.test_wait.parity.shared::cta.b64 p, [%1], %2;\nselp.u32 %0, 1, 0, p;\n}"
                 : "=r"(ok) : "r"(bar), "r"(parity) : "memory");
    return ok;
}
__device__ __forceinline__ void mbar_wait(uint32_t bar, uint32_t parity) {
#pragma unroll 1
    for (int spins = 0; !mbar_try_wait(bar, parity) && spins < (1 << 17); spins++) {}
}
template <bool WARP = false> __device__ __forceinline__ void flag_wait(const unsigned* p, unsigned target) {
#pragma unroll 1
    for (int spins = 0; spins < (1 << 19); spins++) {
        unsigned v;
        asm volatile("ld.acquire.gpu.global.u32 %0, [%1];" : "=r"(v) : "l"(p) : "memory");
        if (WARP ? __all_sync(0xffffffffu, (int)(v - target) >= 0) : (int)(v - target) >= 0) break;
        __nanosleep(64);
    }
}
__device__ __forceinline__ void mbar_wait_warp(uint32_t bar, uint32_t parity) {
#pragma unroll 1
    for (int spins = 0; !__all_sync(0xffffffffu, mbar_try_wait(bar, parity)) && spins < (1 << 17); spins++) {}
}
__device__ __forceinline__ void flag_add(unsigned* p) {
    asm volatile("red.release.gpu.global.add.u32 [%0], 1;" :: "l"(p) : "memory");
}
__device__ __forceinline__ bool elect_one() {
    uint32_t ok;
    asm volatile("{\n.reg .pred p;\nelect.sync _|p, 0xffffffff;\nselp.u32 %0, 1, 0, p;\n}" : "=r"(ok));
    return ok;
}
__device__ __forceinline__ uint32_t pick(bool c, uint32_t a, uint32_t b) {
    uint32_t r;
    asm("{\n.reg .pred p;\nsetp.ne.b32 p, %3, 0;\nselp.b32 %0, %1, %2, p;\n}" : "=r"(r) : "r"(a), "r"(b), "r"((uint32_t)c));
    return r;
}
__device__ __forceinline__ void fence_proxy_async() { asm volatile("fence.proxy.async.global;" ::: "memory"); }
__device__ __forceinline__ uint4 lds128(uint32_t addr) {
    uint4 v;
    asm volatile("ld.shared.v4.u32 {%0,%1,%2,%3}, [%4];" : "=r"(v.x), "=r"(v.y), "=r"(v.z), "=r"(v.w) : "r"(addr) : "memory");
    return v;
}
__device__ __forceinline__ float2 lds64f(uint32_t addr) {
    float2 v;
    asm volatile("ld.shared.v2.f32 {%0,%1}, [%2];" : "=f"(v.x), "=f"(v.y) : "r"(addr) : "memory");
    return v;
}
__device__ __forceinline__ void sts128(uint32_t addr, uint4 v) {
    asm volatile("st.shared.v4.u32 [%0], {%1,%2,%3,%4};" :: "r"(addr), "r"(v.x), "r"(v.y), "r"(v.z), "r"(v.w) : "memory");
}
__device__ __forceinline__ void sts64f(uint32_t addr, float a, float b) {
    asm volatile("st.shared.v2.f32 [%0], {%1,%2};" :: "r"(addr), "f"(a), "f"(b) : "memory");
}

__device__ __forceinline__ uint64_t stream_policy() { return 0x12F0000000000000ull; }
__device__ __forceinline__ void tma_2d(uint32_t dst, const CUtensorMap* m, uint32_t bar, int c0, int c1, uint64_t pol) {
    asm volatile("cp.async.bulk.tensor.2d.shared::cluster.global.mbarrier::complete_tx::bytes.L2::cache_hint"
                 " [%0], [%1, {%3, %4}], [%2], %5;"
                 :: "r"(dst), "l"(m), "r"(bar), "r"(c0), "r"(c1), "l"(pol) : "memory");
}
__device__ __forceinline__ void tma_3d(uint32_t dst, const CUtensorMap* m, uint32_t bar, int c0, int c1, int c2, uint64_t pol) {
    asm volatile("cp.async.bulk.tensor.3d.shared::cluster.global.mbarrier::complete_tx::bytes.L2::cache_hint"
                 " [%0], [%1, {%3, %4, %5}], [%2], %6;"
                 :: "r"(dst), "l"(m), "r"(bar), "r"(c0), "r"(c1), "r"(c2), "l"(pol) : "memory");
}
__device__ __forceinline__ void tma_3d_mc(uint32_t dst, const CUtensorMap* m, uint32_t bar, int c1, int c2, uint64_t pol) {
    asm volatile("cp.async.bulk.tensor.3d.shared::cluster.global.mbarrier::complete_tx::bytes.multicast::cluster.L2::cache_hint"
                 " [%0], [%1, {%3, %4, %5}], [%2], %6, %7;"
                 :: "r"(dst), "l"(m), "r"(bar), "r"(0), "r"(c1), "r"(c2), "h"((uint16_t)3), "l"(pol) : "memory");
}
__device__ __forceinline__ void load_stage1(uint32_t dst, uint32_t dst_b, uint32_t bar, const CUtensorMap* ma, const CUtensorMap* mb,
                                            int k, int row, int col, int keep_a, uint64_t pol) {
    asm volatile("{\n.reg .pred e, p, q;\nelect.sync _|e, 0xffffffff;\nsetp.ne.and.b32 p|q, %8, 0, e;\n"
        "@p cp.async.bulk.tensor.2d.shared::cluster.global.mbarrier::complete_tx::bytes [%0], [%3, {%5, %6}], [%2];\n"
        "@q cp.async.bulk.tensor.2d.shared::cluster.global.mbarrier::complete_tx::bytes.L2::cache_hint [%0], [%3, {%5, %6}], [%2], %9;\n"
        "@e cp.async.bulk.tensor.3d.shared::cluster.global.mbarrier::complete_tx::bytes.multicast::cluster.L2::cache_hint"
        " [%1], [%4, {%10, %5, %7}], [%2], %11, %9;\n"
        "@e mbarrier.arrive.expect_tx.shared::cta.b64 _, [%2], %12;\n}"
        :: "r"(dst), "r"(dst_b), "r"(bar), "l"(ma), "l"(mb), "r"(k), "r"(row), "r"(col), "r"(keep_a), "l"(pol), "r"(0),
           "h"((uint16_t)3), "n"(G1_STAGE_BYTES) : "memory");
}
__device__ __forceinline__ void load_stage2(uint32_t dst, uint32_t dst_b, uint32_t bar, const CUtensorMap* ma, const CUtensorMap* mb,
                                            int ka, int row, int col, int kb, uint64_t pol) {
    asm volatile("{\n.reg .pred e;\nelect.sync _|e, 0xffffffff;\n"
        "@e cp.async.bulk.tensor.3d.shared::cluster.global.mbarrier::complete_tx::bytes.L2::cache_hint [%0], [%3, {%5, %10, %6}], [%2], %9;\n"
        "@e cp.async.bulk.tensor.5d.shared::cluster.global.mbarrier::complete_tx::bytes.multicast::cluster.L2::cache_hint"
        " [%1], [%4, {%7, %10, %10, %10, %8}], [%2], %11, %9;\n"
        "@e mbarrier.arrive.expect_tx.shared::cta.b64 _, [%2], %12;\n}"
        :: "r"(dst), "r"(dst_b), "r"(bar), "l"(ma), "l"(mb), "r"(ka), "r"(row), "r"(col), "r"(kb), "l"(pol), "r"(0),
           "h"((uint16_t)3), "n"(G2_STAGE_BYTES) : "memory");
}
__device__ __forceinline__ void tma_store_2d(const CUtensorMap* m, uint32_t src, int c0, int c1) {
    asm volatile("cp.async.bulk.tensor.2d.global.shared::cta.bulk_group [%0, {%2, %3}], [%1];"
                 :: "l"(m), "r"(src), "r"(c0), "r"(c1) : "memory");
}
__device__ __forceinline__ uint4 ldg_stream(const void* p, uint64_t pol) {
    uint4 v;
    asm volatile("ld.global.nc.L1::no_allocate.L2::cache_hint.v4.u32 {%0,%1,%2,%3}, [%4], %5;"
                 : "=r"(v.x), "=r"(v.y), "=r"(v.z), "=r"(v.w) : "l"(p), "l"(pol));
    return v;
}
__device__ __forceinline__ void st_tagged(void* p, float a, float b, uint32_t tag) {
    asm volatile("st.relaxed.gpu.global.v2.b32 [%0], {%1,%2};"
                 :: "l"(p), "r"((__float_as_uint(a) & ~3u) | tag), "r"((__float_as_uint(b) & ~3u) | tag) : "memory");
}
__device__ __forceinline__ bool untagged(const uint4& v, uint32_t tag) {
    return ((v.x ^ tag) | (v.y ^ tag) | (v.z ^ tag) | (v.w ^ tag)) & 3;
}
__device__ __forceinline__ uint4 ld_relaxed(const void* p) {
    uint4 v;
    asm volatile("ld.relaxed.gpu.global.v4.b32 {%0,%1,%2,%3}, [%4];" : "=r"(v.x), "=r"(v.y), "=r"(v.z), "=r"(v.w) : "l"(p) : "memory");
    return v;
}
__device__ __forceinline__ void prefetch_3d(const CUtensorMap* m, int c1, int c2, uint64_t pol) {
    asm volatile("cp.async.bulk.prefetch.tensor.3d.L2.global.L2::cache_hint [%0, {%1, %2, %3}], %4;"
                 :: "l"(m), "r"(0), "r"(c1), "r"(c2), "l"(pol) : "memory");
}
__device__ __forceinline__ void prefetch_map(const CUtensorMap* m) {
    asm volatile("prefetch.tensormap [%0];" :: "l"(m) : "memory");
}
template <int N> __device__ __forceinline__ void wg_wait() { asm volatile("wgmma.wait_group.sync.aligned %0;" :: "n"(N) : "memory"); }

__device__ __forceinline__ uint32_t desc_a(uint32_t addr) { return (addr & 0x3FFFF) >> 4 | 1 << 16; }
__device__ __forceinline__ uint32_t desc_b(uint32_t addr) { return (addr & 0x3FFFF) >> 4 | 512 << 16; }

#define R8(d, o) "+f"(d[o]), "+f"(d[o+1]), "+f"(d[o+2]), "+f"(d[o+3]), "+f"(d[o+4]), "+f"(d[o+5]), "+f"(d[o+6]), "+f"(d[o+7])
#define R32(d, o) R8(d, o), R8(d, o+8), R8(d, o+16), R8(d, o+24)
#define R64(d, o) R32(d, o), R32(d, o+32)
#define ACC0 "%0,%1,%2,%3,%4,%5,%6,%7,%8,%9,%10,%11,%12,%13,%14,%15,%16,%17,%18,%19,%20,%21,%22,%23,%24,%25,%26,%27,%28,%29,%30,%31,"\
    "%32,%33,%34,%35,%36,%37,%38,%39,%40,%41,%42,%43,%44,%45,%46,%47,%48,%49,%50,%51,%52,%53,%54,%55,%56,%57,%58,%59,%60,%61,%62,%63"
#define ACC1 "%64,%65,%66,%67,%68,%69,%70,%71,%72,%73,%74,%75,%76,%77,%78,%79,%80,%81,%82,%83,%84,%85,%86,%87,%88,%89,%90,%91,%92,%93,%94,%95,"\
    "%96,%97,%98,%99,%100,%101,%102,%103,%104,%105,%106,%107,%108,%109,%110,%111,%112,%113,%114,%115,%116,%117,%118,%119"
#define ACC64 "{" ACC0 "}"
#define ACC120 "{" ACC0 "," ACC1 "}"
#define ACC128 "{" ACC0 "," ACC1 ",%120,%121,%122,%123,%124,%125,%126,%127}"
#define MMA_K16(shape, acc, keep, hb, sb) \
    "mov.b64 da, {la, 0x40000040};\nmov.b64 db, {lb, " hb "};\n" \
    "wgmma.mma_async.sync.aligned." shape ".f32.bf16.bf16 " acc ", da, db, " keep ", 1, 1, 0, 1;\n" \
    "add.u32 la, la, 2;\nadd.u32 lb, lb, " sb ";\n"
#define MMA_STEP_B(shape, acc, a, b, off, keep, hb, sb) \
    "{\n.reg .pred p, q;\n.reg .b32 la, lb;\n.reg .b64 da, db;\nsetp.ne.b32 p, " keep ", 0;\nsetp.eq.b32 q, 0, 0;\n" \
    "add.u32 la, " a ", " off ";\nadd.u32 lb, " b ", " off ";\nwgmma.fence.sync.aligned;\n" \
    MMA_K16(shape, acc, "p", hb, sb) MMA_K16(shape, acc, "q", hb, sb) MMA_K16(shape, acc, "q", hb, sb) \
    MMA_K16(shape, acc, "q", hb, sb) "wgmma.commit_group.sync.aligned;\n}"
#define MMA_STEP(shape, acc, a, b, off, keep) MMA_STEP_B(shape, acc, a, b, off, keep, "0x40000040", "128")

__device__ __forceinline__ void mma_step(float (&d)[128], uint32_t da, uint32_t db, uint32_t off, int keep) {
    asm volatile(MMA_STEP("m64n256k16", ACC128, "%128", "%129", "%130", "%131")
                 : R64(d, 0), R64(d, 64) : "r"(da), "r"(db), "r"(off), "r"(keep) : "memory");
}
__device__ __forceinline__ void mma_step240(float (&d)[128], uint32_t da, uint32_t db, uint32_t off, int keep) {
    asm volatile(MMA_STEP("m64n240k16", ACC120, "%120", "%121", "%122", "%123")
                 : R64(d, 0), R32(d, 64), R8(d, 96), R8(d, 104), R8(d, 112) : "r"(da), "r"(db), "r"(off), "r"(keep) : "memory");
}
__device__ __forceinline__ void mma_step(float (&d)[64], uint32_t da, uint32_t db, uint32_t off, int keep) {
    asm volatile(MMA_STEP("m64n128k16", ACC64, "%64", "%65", "%66", "%67")
                 : R64(d, 0) : "r"(da), "r"(db), "r"(off), "r"(keep) : "memory");
}

__device__ __forceinline__ void mma_step_tail(float (&d)[64], uint32_t da, uint32_t b, uint32_t off) {
    asm volatile(MMA_STEP_B("m64n128k16", ACC64, "%64", "%65", "%66", "1", "0xC0000010", "32")
                 : R64(d, 0) : "r"(da), "r"((b & 0x3FFFF) >> 4 | 128 << 16), "r"(off) : "memory");
}

__device__ __forceinline__ uint32_t pack_bf16(float lo, float hi) {
    uint32_t r; asm("cvt.rn.bf16x2.f32 %0, %1, %2;" : "=r"(r) : "f"(hi), "f"(lo)); return r;
}
__device__ __forceinline__ float bf_lo(uint32_t v) { return __uint_as_float(v << 16); }
__device__ __forceinline__ float bf_hi(uint32_t v) { return __uint_as_float(v & 0xffff0000u); }
__device__ __forceinline__ float round_bf16(float v) { return bf_lo(pack_bf16(v, 0.f)); }
__device__ __forceinline__ uint32_t mul_bf16x2(uint32_t a, uint32_t b) {
    uint32_t r; asm("mul.rn.bf16x2 %0, %1, %2;" : "=r"(r) : "r"(a), "r"(b)); return r;
}
__device__ __forceinline__ uint32_t add_bf16x2(uint32_t a, uint32_t b) {
    uint32_t r; asm("add.rn.bf16x2 %0, %1, %2;" : "=r"(r) : "r"(a), "r"(b)); return r;
}
__device__ __forceinline__ uint32_t sub_bf16x2(uint32_t a, uint32_t b) {
    uint32_t r; asm("sub.rn.bf16x2 %0, %1, %2;" : "=r"(r) : "r"(a), "r"(b)); return r;
}
__device__ __forceinline__ uint32_t mul2_bf16x2(uint32_t a, uint32_t hi, uint32_t lo) {
    uint32_t r; asm("fma.rn.bf16x2 %0, %1, %2, %3;" : "=r"(r) : "r"(a), "r"(hi), "r"(mul_bf16x2(a, lo))); return r;
}
__device__ __forceinline__ float tanh_fast(float x) { float r; asm("tanh.approx.f32 %0, %1;" : "=f"(r) : "f"(x)); return r; }
__device__ __forceinline__ float gelu_tanh(float g) {
    float t = fmaf(g * g, 0.044715f * 0.7978845608f, 0.7978845608f) * g;
    float hg = 0.5f * g;
    return fmaf(hg, tanh_fast(t), hg);
}
__device__ __forceinline__ uint32_t geglu2(uint32_t g2, uint32_t u2) {
    return mul_bf16x2(pack_bf16(gelu_tanh(bf_lo(g2)), gelu_tanh(bf_hi(g2))), u2);
}
__device__ __forceinline__ float silu(float d) {
    float hd = 0.5f * d;
    return fmaf(hd, tanh_fast(hd), hd);
}
__device__ __forceinline__ float ex2_fast(float x) { float r; asm("ex2.approx.ftz.f32 %0, %1;" : "=f"(r) : "f"(x)); return r; }
__device__ __forceinline__ void unpack8(uint4 v, float (&f)[8]) {
    f[0] = bf_lo(v.x); f[1] = bf_hi(v.x); f[2] = bf_lo(v.y); f[3] = bf_hi(v.y);
    f[4] = bf_lo(v.z); f[5] = bf_hi(v.z); f[6] = bf_lo(v.w); f[7] = bf_hi(v.w);
}
template <int N> __device__ __forceinline__ void fence_regs(float (&d)[N]) {
#pragma unroll
    for (int i = 0; i < N; i++) asm volatile("" : "+f"(d[i]) :: "memory");
}

__device__ __forceinline__ float rcp_fast(float x) { float r; asm("rcp.approx.ftz.f32 %0, %1;" : "=f"(r) : "f"(x)); return r; }
__device__ __forceinline__ float sqrt_fast(float x) { float r; asm("sqrt.approx.ftz.f32 %0, %1;" : "=f"(r) : "f"(x)); return r; }
__device__ __forceinline__ uint32_t max_bf16x2(uint32_t a, uint32_t b) {
    uint32_t r; asm("max.bf16x2 %0, %1, %2;" : "=r"(r) : "r"(a), "r"(b)); return r;
}
__device__ __forceinline__ uint4 ldsm4(uint32_t addr) {
    uint4 v;
    asm volatile("ldmatrix.sync.aligned.m8n8.x4.shared.b16 {%0,%1,%2,%3}, [%4];"
                 : "=r"(v.x), "=r"(v.y), "=r"(v.z), "=r"(v.w) : "r"(addr) : "memory");
    return v;
}
__device__ __forceinline__ uint4 ldsm4_t(uint32_t addr) {
    uint4 v;
    asm volatile("ldmatrix.sync.aligned.m8n8.x4.trans.shared.b16 {%0,%1,%2,%3}, [%4];"
                 : "=r"(v.x), "=r"(v.y), "=r"(v.z), "=r"(v.w) : "r"(addr) : "memory");
    return v;
}
__device__ __forceinline__ void mma_16816(float (&c)[4], uint32_t a0, uint32_t a1, uint32_t a2, uint32_t a3, uint32_t b0, uint32_t b1) {
    asm("mma.sync.aligned.m16n8k16.row.col.f32.bf16.bf16.f32 {%0,%1,%2,%3}, {%4,%5,%6,%7}, {%8,%9}, {%0,%1,%2,%3};"
        : "+f"(c[0]), "+f"(c[1]), "+f"(c[2]), "+f"(c[3]) : "r"(a0), "r"(a1), "r"(a2), "r"(a3), "r"(b0), "r"(b1));
}
__device__ __forceinline__ void mma_1688(float (&c)[4], uint32_t a0, uint32_t a1, uint32_t b0) {
    asm("mma.sync.aligned.m16n8k8.row.col.f32.bf16.bf16.f32 {%0,%1,%2,%3}, {%4,%5}, {%6}, {%0,%1,%2,%3};"
        : "+f"(c[0]), "+f"(c[1]), "+f"(c[2]), "+f"(c[3]) : "r"(a0), "r"(a1), "r"(b0));
}
__device__ __forceinline__ void qk_tile(float (&c)[4], const uint4& q0, const uint4& q1, const uint4& k, float init) {
    c[0] = c[1] = c[2] = c[3] = init;
    mma_16816(c, q0.x, q0.y, q0.z, q0.w, k.x, k.y);
    mma_16816(c, q1.x, q1.y, q1.z, q1.w, k.z, k.w);
}
__device__ __forceinline__ uint32_t scaled_logits(bool first, float a0, float a1, float b0, float b1) {
    return mul2_bf16x2(pack_bf16(first ? a0 : b0, first ? a1 : b1), 0x3e353e35u, 0x379e379eu);
}
template <typename T> __device__ __forceinline__ T uniform(T v) { return __shfl_sync(0xffffffffu, v, 0); }

__device__ __forceinline__ void attention(const Params& prm, uint32_t base, unsigned epoch, int grp, int warp, int lane) {
    constexpr float LOG2E = 1.4426950408889634f;
    const int g = lane >> 2, t = lane & 3;
    const bool up0 = 2 * t > g, up1 = 2 * t + 1 > g;
    const uint32_t keep = (up0 ? 0x0000ffffu : 0u) | (up1 ? 0xffff0000u : 0u);
    const uint32_t buf = base + warp * 2 * ATT_SLOT, bar = base + AUX_OFF + warp * 16;
    const uint32_t qoff = (lane & 15) * 128 + (((lane >> 4) ^ (lane & 7)) << 4);
    const uint32_t koff = 2048 + (lane & 7) * 128 + (((lane >> 3) ^ (lane & 7)) << 4);
    const uint32_t rest_bar = base + AUX_OFF + 192;
    const int col = uniform(grp * 256), first = uniform((warp / 3 * 32 + warp % 3 * 11) * 16);
    const CUtensorMap* const mqk = reinterpret_cast<const CUtensorMap*>(uniform(reinterpret_cast<uint64_t>(&prm.qk)));
    const CUtensorMap *const mv = mqk + 1, *const mo = mqk + 2;
    const uint64_t pol = stream_policy();
    const uint32_t zero = prm.zero;
    uint4 kp[2], vp[2];
    uint32_t l0[2], l1[2], m[2];
    float s[2][3][4];
    auto scores = [&](uint32_t st, int row) {
        const float before = (row & 1023) == 0 ? -5.656854e9f : 0.f;
#pragma unroll
        for (int h = 0; h < 2; h++) {
            const uint4 q0 = ldsm4(st + (qoff ^ (h * 64))), q1 = ldsm4(st + (qoff ^ (h * 64 + 32)));
            const uint4 k0 = ldsm4(st + (koff ^ (h * 64))), k1 = ldsm4(st + 1024 + (koff ^ (h * 64)));
            qk_tile(s[h][0], q0, q1, kp[h], before);
            qk_tile(s[h][1], q0, q1, k0, 0.f);
            qk_tile(s[h][2], q0, q1, k1, 0.f);
            kp[h] = k1;
        }
    };
    auto logits = [&]() {
#pragma unroll
        for (int h = 0; h < 2; h++) {
            l0[h] = scaled_logits(up0, s[h][0][0], s[h][1][2], s[h][1][0], s[h][2][2]);
            l1[h] = scaled_logits(up1, s[h][0][1], s[h][1][3], s[h][1][1], s[h][2][3]);
            m[h] = max_bf16x2(l0[h], l1[h]);
            m[h] = max_bf16x2(m[h], __shfl_xor_sync(0xffffffffu, m[h], 1));
        }
    };
    auto row_max = [&]() {
#pragma unroll
        for (int h = 0; h < 2; h++) m[h] = max_bf16x2(m[h], __shfl_xor_sync(0xffffffffu, m[h], 2));
    };
    auto next = [](uint32_t p) {
        return (0x80200400u >> (p >> 4 & 31) & 1) > (p >> 15 & 1) ? p + (64 << 16) + 0x8000 : (p + 16) & ~0x8800u;
    };
    auto exchange = [&](uint32_t st, uint32_t b, uint32_t po, uint32_t pv, uint32_t pq) {
        asm volatile("{\n.reg .pred e, p, q;\n"
            "fence.proxy.async.shared::cta;\n"
            "bar.warp.sync 0xffffffff;\n"
            "elect.sync _|e, 0xffffffff;\n"
            "setp.eq.and.b32 p, %12, 0, e;\n"
            "setp.lt.and.s32 q, %8, %13, e;\n"
            "@q mbarrier.arrive.expect_tx.shared::cta.b64 _, [%2], 6144;\n"
            "@q cp.async.bulk.tensor.3d.shared::cluster.global.mbarrier::complete_tx::bytes.L2::cache_hint [%0], [%3, {%6, %7, %14}], [%2], %15;\n"
            "@q cp.async.bulk.tensor.2d.shared::cluster.global.mbarrier::complete_tx::bytes.L2::cache_hint [%0 + 4096], [%4, {%8, %9}], [%2], %15;\n"
            "@e cp.async.bulk.wait_group.read 0;\n"
            "@p cp.async.bulk.tensor.2d.global.shared::cta.bulk_group [%5, {%10, %11}], [%1 + 6144];\n"
            "@e cp.async.bulk.commit_group;\n"
            "bar.warp.sync 0xffffffff;\n}"
            :: "r"(st), "r"(st ^ ATT_SLOT), "r"(b), "l"(mqk), "l"(mv), "l"(mo), "r"(pq >> 16), "r"(pq & 2047),
               "r"((pv >> 16) + 2 * DM), "r"(pv & 2047), "r"(po >> 16), "r"(po & 2047), "r"(po & 0x8000),
               "r"(col + 256 + 2 * DM), "r"(0), "l"(pol) : "memory");
    };
    auto publish = [&](auto pending, int part) {
        asm volatile("{\n.reg .pred e;\n.reg .u32 n;\n"
            "elect.sync _|e, 0xffffffff;\n"
            "cp.async.bulk.wait_group %2;\n"
            "@e atom.acq_rel.cta.shared.add.u32 n, [%1], 1;\n"
            "setp.eq.and.u32 e, n, 11, e;\n"
            "@e red.release.gpu.global.add.u32 [%0], 1;\n}"
            :: "l"(prm.flags + F_O * 512 + part * 32), "r"(rest_bar + 8 + part * 4), "n"(pending.value) : "memory");
    };
    if (elect_one()) {
        mbar_init(bar, 1); mbar_init(bar + 8, 1);
        if (warp == 2) { mbar_init(rest_bar, 32); sts64f(rest_bar + 8, 0.f, 0.f); }
        asm volatile("fence.mbarrier_init.release.cluster;" ::: "memory");
        if (warp == 9) {
            prefetch_map(mqk); prefetch_map(mv); prefetch_map(mo);
            flag_wait(prm.flags + F_QKV * 512 + grp * 32, epoch * CNT_QKV);
        }
    }
    __syncthreads();
    if (elect_one()) {
        fence_proxy_async();
        mbar_expect_tx(bar + 8, 8192);
        tma_3d(buf + ATT_SLOT, mqk, bar + 8, col, first, 0, pol);
        tma_2d(buf + ATT_SLOT + 4096, mv, bar + 8, col + 2 * DM, first - 16, pol);
        tma_2d(buf + ATT_SLOT + 6144, mv, bar + 8, col + DM, first - 16, pol);
        mbar_expect_tx(bar, 6144);
        tma_3d(buf, mqk, bar, col, first + 16, 0, pol);
        tma_2d(buf + 4096, mv, bar, col + 2 * DM, first, pol);
        if (warp == 0) TRACE(9);
        if (warp == 9) prm.epoch[blockIdx.x * 16] = epoch;
    }
    __syncwarp();
    if (warp == 11 && lane < 4) flag_add(prm.flags + F_EARLY * 512 + (grp * 4 + lane) * 32);
    mbar_wait(bar + 8, 0);
#pragma unroll
    for (int h = 0; h < 2; h++) {
        kp[h] = ldsm4(buf + ATT_SLOT + 5120 + (koff ^ (h * 64)));
        vp[h] = ldsm4_t(buf + ATT_SLOT + 3072 + (koff ^ (h * 64)));
    }
    scores(buf + ATT_SLOT, first);
    uint32_t pm = 0x8000, p0 = col << 16 | first, p1 = p0 + 16, p2 = p0 + 32, p3 = p0 + 48;
    exchange(buf + ATT_SLOT, bar + 8, pm, p1, p2);
    logits();
    row_max();
    uint32_t st = buf, b = bar, cnt = 1;
    const uint32_t relay = warp == 2 ? 7 : 0;
    bool ready = false;
#pragma unroll 1
    while (p0 >> 16 < col + 256) {
        uint32_t pa[2], pb[2];
        if (!ready) mbar_wait(b, (cnt >> 1) & 1);
        uint4 v[2][2];
#pragma unroll
        for (int h = 0; h < 2; h++) {
            const float ma = -LOG2E * bf_lo(m[h]), mb = -LOG2E * bf_hi(m[h]);
            const float a0 = ex2_fast(fmaf(bf_lo(l0[h]), LOG2E, ma)), a1 = ex2_fast(fmaf(bf_lo(l1[h]), LOG2E, ma));
            const float b0 = ex2_fast(fmaf(bf_hi(l0[h]), LOG2E, mb)), b1 = ex2_fast(fmaf(bf_hi(l1[h]), LOG2E, mb));
            float sum[4] = {0.f, 0.f, 0.f, 0.f};
            mma_1688(sum, pack_bf16(a0, a1), pack_bf16(b0, b1), 0x3f803f80u);
            const float ra = rcp_fast(sum[0]), rb = rcp_fast(sum[2]);
            pa[h] = pack_bf16(a0 * ra, a1 * ra);
            pb[h] = pack_bf16(b0 * rb, b1 * rb);
        }
        scores(st, p1);
#pragma unroll
        for (int h = 0; h < 2; h++) {
            v[h][0] = ldsm4_t(st + 4096 + (qoff ^ (h * 64)));
            v[h][1] = ldsm4_t(st + 4096 + (qoff ^ (h * 64 + 32)));
        }
        if (cnt == relay) {
            flag_wait<true>(prm.flags + F_QKV * 512 + 128 + grp * 32, epoch * CNT_QKV);
            fence_proxy_async();
            mbar_arrive(rest_bar);
        }
        if (cnt == 8) {
#pragma unroll 1
            for (int spins = 0; !__all_sync(0xffffffffu, mbar_try_wait(rest_bar, 0)) && spins < (1 << 17); spins++) {}
        }
        if (cnt == 37) publish(std::integral_constant<int, 1>(), 0);
        exchange(st, b, pm, p2, p3);
        pm = p0; p0 = p1; p1 = p2; p2 = p3; p3 = next(p3);
        logits();
        float o[2][4][4];
#pragma unroll
        for (int h = 0; h < 2; h++) {
            const uint32_t prev[4] = {vp[h].x, vp[h].y, vp[h].z, vp[h].w};
            const uint32_t own[8] = {v[h][0].x, v[h][0].y, v[h][0].z, v[h][0].w, v[h][1].x, v[h][1].y, v[h][1].z, v[h][1].w};
            const uint32_t a0 = pa[h] & keep, a1 = pa[h] & ~keep, a2 = pb[h] & keep, a3 = pb[h] & ~keep;
            const uint32_t z0 = pa[h] & zero, z1 = pb[h] & zero;
#pragma unroll
            for (int j = 0; j < 4; j++) {
                o[h][j][0] = o[h][j][1] = o[h][j][2] = o[h][j][3] = 0.f;
                mma_1688(o[h][j], a0, z0, prev[j]);
                mma_16816(o[h][j], a1, a2, z1, a3, own[2 * j], own[2 * j + 1]);
            }
            vp[h] = make_uint4(own[1], own[3], own[5], own[7]);
        }
        row_max();
        b ^= 8; cnt++;
        ready = mbar_test(b, (cnt >> 1) & 1);
#pragma unroll
        for (int h = 0; h < 2; h++) {
#pragma unroll
            for (int d = 0; d < 2; d++)
                asm volatile("stmatrix.sync.aligned.m8n8.x4.shared.b16 [%0], {%1,%2,%3,%4};"
                             :: "r"(st + 6144 + (qoff ^ (h * 64 + d * 32))),
                                "r"(pack_bf16(o[h][2 * d][0], o[h][2 * d][1])), "r"(pack_bf16(o[h][2 * d][2], o[h][2 * d][3])),
                                "r"(pack_bf16(o[h][2 * d + 1][0], o[h][2 * d + 1][1])),
                                "r"(pack_bf16(o[h][2 * d + 1][2], o[h][2 * d + 1][3])) : "memory");
        }
        st ^= ATT_SLOT;
    }
    exchange(st, b, pm, p0, p0);
    publish(std::integral_constant<int, 0>(), 1);
    if (threadIdx.x == 0) { TRACE(10); TRACE_DUMP(); }
}

__device__ __forceinline__ void tail_gemm(const Params& prm, uint32_t base, uint32_t tag, int grp, int warp, int lane) {
    const uint32_t full = base + BAR_OFF, empty = full + 32, sum_bar = full + 320, colsum = full + 512;
    if (warp == 8) {
        if (elect_one()) {
            if (TDELAY) __nanosleep(TDELAY);
#pragma unroll 1
            for (int i = 0; i < 32; i++) {
                const uint32_t dst = base + (i & 3) * G1_STAGE_BYTES, bar = full + (i & 3) * 8;
                mbar_wait(bar + 32, ~i >> 2 & 1);
                mbar_expect_tx(bar, G1_STAGE_BYTES);
                tma_2d(dst, &prm.x, bar, (i & 15) * 64, grp * 512 + (i >> 4) * 256, stream_policy());
                tma_2d(dst + 16384, &prm.x, bar, (i & 15) * 64, grp * 512 + (i >> 4) * 256 + 128, stream_policy());
                tma_3d(dst + 32768, &prm.wtail, bar, 0, (i & 15) * 64, 0, stream_policy());
            }
        }
    } else if (warp >= 10) {
        float cs[8];
#pragma unroll
        for (int d = 0; d < 8; d++) cs[d] = 0.f;
        const uint32_t wa = base + 32768 + (warp - 10) * 8192 + (lane >> 3) * 2048 + (lane & 7) * 16;
#pragma unroll 1
        for (int i = 0; i < 28; i++) {
            mbar_wait(full + (i & 3) * 8, i >> 2 & 1);
            if (i < 16) {
#pragma unroll
                for (int j = 0; j < 16; j++) {
                    float f[8];
                    unpack8(lds128((wa ^ (j & 1) * 16) + (i & 3) * G1_STAGE_BYTES + j * 128), f);
#pragma unroll
                    for (int d = 0; d < 8; d++) cs[d] += f[d];
                }
            }
            if (i == 15) {
#pragma unroll
                for (int d = 0; d < 8; d++) {
                    cs[d] += __shfl_xor_sync(0xffffffffu, cs[d], 2);
                    cs[d] += __shfl_xor_sync(0xffffffffu, cs[d], 4);
                }
#pragma unroll
                for (int d = 0; d < 8; d += 2)
                    sts64f(colsum + (warp - 10) * 256 + (lane >> 3) * 64 + (lane & 1) * 32 + d * 4, cs[d], cs[d + 1]);
            }
            __syncwarp();
            if (lane == 0) {
                mbar_arrive(empty + (i & 3) * 8);
                if (i == 15) mbar_arrive(sum_bar);
            }
        }
    } else if (warp < 8) {
        const uint32_t da = desc_a(base + (warp >> 2) * 16384);
#pragma unroll 1
        for (int pass = 0; pass < 2; pass++) {
            const int mblk = grp * 4 + pass * 2 + (warp >> 2);
            const float2* const sp = prm.stats + mblk * 128 + (warp & 3) * 16 + (lane >> 2);
            uint2 st[4] = {};
            auto fetch_stats = [&]() {
                bool missing = false;
#pragma unroll
                for (int r = 0; r < 4; r++) {
                    if (((st[r].x ^ tag) | (st[r].y ^ tag)) & 3) {
                        missing = true;
                        asm volatile("ld.relaxed.gpu.global.v2.b32 {%0,%1}, [%2];"
                                     : "=r"(st[r].x), "=r"(st[r].y) : "l"(sp + r / 2 * 64 + r % 2 * 8) : "memory");
                    }
                }
                return missing;
            };
            float acc[2][64];
#pragma unroll
            for (int i = 0; i < 64; i++) acc[0][i] = acc[1][i] = 0.f;
#pragma unroll 1
            for (int k = 0; k < G1_KSTEPS; k++) {
                mbar_wait(full + (k & 3) * 8, k >> 2 & 1);
                mma_step_tail(acc[0], da, base + 32768, (k & 3) * (G1_STAGE_BYTES / 16));
                mma_step_tail(acc[1], da + 512, base + 32768, (k & 3) * (G1_STAGE_BYTES / 16));
                wg_wait<2>();
                if (k > 0 && (threadIdx.x & 127) == 0) mbar_arrive(empty + (k - 1 & 3) * 8);
                if (k == 13) fetch_stats();
            }
#pragma unroll 1
            for (int spins = 0; fetch_stats() && spins < (1 << 16); spins++) {}
            mbar_wait(sum_bar, 0);
            wg_wait<0>();
            fence_regs(acc[0]); fence_regs(acc[1]);
            if ((threadIdx.x & 127) == 0) mbar_arrive(empty + 24);
#pragma unroll
            for (int q = 0; q < 8; q++) {
                const float2 c0 = lds64f(colsum + q * 64 + (lane & 3) * 8), c1 = lds64f(colsum + q * 64 + 32 + (lane & 3) * 8);
                uint32_t v[8];
#pragma unroll
                for (int r = 0; r < 4; r++) {
                    const float* a = acc[r / 2] + 8 * q + r % 2 * 2;
                    const float shift = __uint_as_float(st[r].x ^ tag), inv = __uint_as_float(st[r].y ^ tag);
                    v[2 * r] = pack_bf16(fmaf(shift, c0.x, a[0]) * inv, fmaf(shift, c0.y, a[1]) * inv);
                    v[2 * r + 1] = pack_bf16(fmaf(shift, c1.x, a[4]) * inv, fmaf(shift, c1.y, a[5]) * inv);
                }
                uint4* const p = prm.tail + (q * 16 + mblk) * 256 + (threadIdx.x & 127);
                p[0] = make_uint4(v[0], v[1], v[2], v[3]);
                p[128] = make_uint4(v[4], v[5], v[6], v[7]);
            }
        }
    }
}

__device__ __forceinline__ bool tile_is_qkv(int nt) { return nt < 4 || (nt >= 8 && nt < 16); }
__device__ __forceinline__ int tile_index(int nt) { return nt < 4 ? nt + 8 : (nt < 8 ? nt - 4 : (nt < 16 ? nt - 8 : nt - 12)); }

__global__ void __cluster_dims__(2, 1, 1) __launch_bounds__(384, 1)
fused_kernel(const __grid_constant__ Params prm) {
    TRACE_GET(c0);
    const uint32_t base = smem_u32(smem_raw) & ~1023u;
    const uint32_t bars = base + BAR_OFF;
    auto full1 = [&](int s) { return bars + s * 8; };
    auto empty1 = [&](int s) { return bars + 32 + s * 8; };
    auto full2 = [&](int s) { return bars + 64 + s * 8; };
    auto empty2 = [&](int s) { return bars + 128 + s * 8; };
    const uint32_t sig_bar = bars + 192, dep_bar = bars + 256, cs_bar = bars + 304, fold_bar = bars + 320, x_bar = bars + 352;
    const uint32_t colsum = bars + 512, stats = bars + 1536;
    auto stage2 = [&](int q) { return base + q * G2_STAGE_BYTES; };
    const uint32_t aux = base + AUX_OFF;

    const int warp = __shfl_sync(0xffffffffu, threadIdx.x >> 5, 0);
    const int lane = threadIdx.x & 31;
    const int rank = blockIdx.x & 1;
    const uint32_t cl = blockIdx.x / 2;
    const uint32_t role = pick(cl < 4, 32 + cl * 8, cl - 8 + max(4u, (cl - 1) * 37 >> 8)) * 2 + rank;
    const int mblk = role & 15, nslot = role >> 4;
    const CUtensorMap* const w0 = &prm.wqkv + pick(nslot < 4, 0, 1 + rank);
    const int w0_col = pick(nslot < 4, 32 + nslot * 4 + rank * 2, nslot * 2 - 8);

    asm volatile("{\n.reg .pred e, p;\nelect.sync _|e, 0xffffffff;\nsetp.eq.and.u32 p, %2, 8, e;\n"
        "@p prefetch.tensormap [%3];\n@p prefetch.tensormap [%4];\n"
        "@e mbarrier.init.shared::cta.b64 [%0], %1;\n@e mbarrier.init.shared::cta.b64 [%0 + 8], %1;\n"
        "@e mbarrier.init.shared::cta.b64 [%0 + 16], %1;\n@e mbarrier.init.shared::cta.b64 [%0 + 24], %1;\n"
        "fence.mbarrier_init.release.cluster;\nbarrier.cluster.arrive.relaxed.aligned;\n"
        "@p cp.async.bulk.tensor.2d.shared::cluster.global.mbarrier::complete_tx::bytes.L2::cache_hint [%5], [%3, {%8, %6}], [%0], %9;\n"
        "@p cp.async.bulk.prefetch.tensor.3d.L2.global.L2::cache_hint [%4, {%8, %8, %7}], %9;\n"
        "barrier.cluster.wait.acquire.aligned;\n"
        "@p cp.async.bulk.tensor.3d.shared::cluster.global.mbarrier::complete_tx::bytes.multicast::cluster.L2::cache_hint"
        " [%10], [%4, {%8, %8, %7}], [%0], %11, %9;\n"
        "@p mbarrier.arrive.expect_tx.shared::cta.b64 _, [%0], %12;\n}"
        :: "r"(bars + pick(warp < 8, warp + 4, warp - 8) * 32), "r"(1 << (0x0810fa >> warp * 2 & 3)), "r"(warp | (blockIdx.x & NGEMM)),
           "l"(&prm.x), "l"(w0), "r"(base), "r"(mblk * 128), "r"(w0_col), "r"(0), "l"(stream_policy()),
           "r"(base + A_BYTES + rank * 16384), "h"((uint16_t)3), "n"(G1_STAGE_BYTES) : "memory");
    TRACE_GET(c2);

    if (blockIdx.x >= NGEMM) {
        if (warp == 9) { TRACE_CLEAR(); TRACE_GT(0); TRACE_PUT(1, c0); }
        const unsigned epoch = __ldcg(prm.epoch + blockIdx.x * 16) + 1;
        if (TAIL) tail_gemm(prm, base, 1 + (epoch & 1), blockIdx.x - NGEMM, warp, lane);
        uint32_t tid;
        asm volatile("mov.u32 %0, %%tid.x;" : "=r"(tid));
        attention(prm, (base + 2 * ATT_SLOT - 1) & ~(2u * ATT_SLOT - 1), epoch, blockIdx.x - NGEMM, uniform(tid >> 5), tid & 31);
    } else if (warp < 8) {
        asm volatile("setmaxnreg.inc.sync.aligned.u32 %0;" :: "n"(CONSUMER_REGS));
        const int wg = __shfl_sync(0xffffffffu, threadIdx.x >> 7, 0);
        const int cw = threadIdx.x >> 5;
        const int tid = threadIdx.x & 127;
        float acc[128];
        uint32_t pk[64];
#pragma unroll
        for (int i = 0; i < 64; i++) asm volatile("mov.b32 %0, 0;" : "=r"(pk[i]));
#pragma unroll
        for (int i = 0; i < 128; i++) asm volatile("mov.b32 %0, 0;" : "=f"(acc[i]));

        const int orow = ((lane >> 2) & 1) * (SEQ / 2) + mblk * 64 + cw * 8 + (lane >> 3);
        __nv_bfloat16* optr = prm.pxn + (mblk * 128 + nslot * 16 + cw * 2) * DM + lane * 8;
        const uint32_t da = desc_a(base + wg * 8192), db = desc_b(base + A_BYTES);
        auto release = [&](uint32_t bar) { if (tid < 2) mbar_arrive_cluster(bar, tid); };
        auto store_pk = [&](__nv_bfloat16* p, int j) {
            *reinterpret_cast<uint4*>(p) = make_uint4(pk[4 * j], pk[4 * j + 1], pk[4 * j + 2], pk[4 * j + 3]);
        };
        auto chunk_geglu = [&](int j) {
#pragma unroll
            for (int i = 4 * j; i < 4 * j + 4; i++) pk[i] = geglu2(pk[i], pk[32 + i]);
            store_pk(optr + (j & 1) * 4 * K2 + (j >> 1) * 32, j);
        };
        auto chunk_qkv = [&](int c) {
            store_pk(optr + c * 32, 2 * c);
            store_pk(optr + 4 * NQKV + c * 32, 2 * c + 1);
        };
        auto signal_stores = [&](int p) { __syncwarp(); if (lane == 0) mbar_arrive(sig_bar + p * 8); };

        auto chunk_ln = [&](int k) {
            float* const mo = reinterpret_cast<float*>(pk + 32);
            if (k == LNL) {
                const uint4* xp = reinterpret_cast<const uint4*>(prm.px + (optr - prm.pxn));
                pk[38] = __ldcg(prm.epoch + blockIdx.x * 16 + 2);
#pragma unroll
                for (int i = 0; i < 8; i++) {
                    const uint4 v = ldg_stream(xp + i * 32, stream_policy());
                    pk[4 * i] = v.x; pk[4 * i + 1] = v.y; pk[4 * i + 2] = v.z; pk[4 * i + 3] = v.w;
                }
            } else if (k >= LN_STEP && k < LN_STEP + 3) {
                if (k == LN_STEP) {
                    mo[0] = bf_lo(uniform(pk[0])); mo[1] = bf_lo(uniform(pk[16]));
                    mo[2] = mo[3] = mo[4] = mo[5] = 0.f;
                }
#pragma unroll
                for (int i = (k - LN_STEP) * 11; i < (k - LN_STEP) * 11 + 11 && i < 32; i++) {
                    const int r = i & 1;
                    const uint32_t w = pk[r * 16 + i / 2];
                    const float lo = bf_lo(w) - mo[r], hi = bf_hi(w) - mo[r];
                    mo[2 + r] += lo + hi;
                    mo[4 + r] = fmaf(hi, hi, fmaf(lo, lo, mo[4 + r]));
                }
            } else if (k == LN_STEP + 3) {
                const bool second = lane & 16;
                float m1 = (second ? mo[3] : mo[2]) + __shfl_xor_sync(0xffffffffu, second ? mo[2] : mo[3], 16);
                float m2 = (second ? mo[5] : mo[4]) + __shfl_xor_sync(0xffffffffu, second ? mo[4] : mo[5], 16);
#pragma unroll
                for (int o = 8; o > 0; o >>= 1) {
                    m1 += __shfl_xor_sync(0xffffffffu, m1, o);
                    m2 += __shfl_xor_sync(0xffffffffu, m2, o);
                }
                m1 *= 1.f / DM;
                const float var = fmaxf(fmaf(-m1, m1, m2 * (1.f / DM)), 0.f);
                const float mean = round_bf16((second ? mo[1] : mo[0]) + m1);
                const float inv = rcp_fast(round_bf16(sqrt_fast(round_bf16(round_bf16(var) + 1e-5f))));
                if ((lane & 15) == 0) st_tagged(prm.stats + (uint32_t)(optr - prm.pxn) / DM + second, -mean, inv, 2 - (pk[38] & 1));
                const uint32_t split = pack_bf16(inv - round_bf16(inv), inv);
#pragma unroll
                for (int r = 0; r < 2; r++) {
                    const uint32_t f = __shfl_sync(0xffffffffu, split, r * 16);
                    pk[32 + 3 * r] = __byte_perm(__shfl_sync(0xffffffffu, __float_as_uint(mean), r * 16), 0, 0x3232);
                    pk[33 + 3 * r] = __byte_perm(f, 0, 0x3232);
                    pk[34 + 3 * r] = __byte_perm(f, 0, 0x1010);
                }
            } else if (k >= LN_STEP + 4 && k < LN_STEP + 8) {
#pragma unroll
                for (int i = k - LN_STEP - 4; i < 8; i += 4) {
                    const uint32_t* n = pk + 32 + i / 4 * 3;
#pragma unroll
                    for (int j = 4 * i; j < 4 * i + 4; j++) pk[j] = mul2_bf16x2(sub_bf16x2(pk[j], n[0]), n[1], n[2]);
                    store_pk(optr + i * 256, i);
                }
                if (k == LN_STEP + 5 || k == LN_STEP + 7) signal_stores(k == LN_STEP + 5 ? 0 : 7);
            } else if (k == FOLD_STEP) {
                mbar_wait(fold_bar, 0);
#pragma unroll
                for (int j = 0; j < 16; j++) {
                    const uint4 c = lds128(colsum + j * 64 + (lane & 3) * 16);
                    pk[4 * j] = c.x; pk[4 * j + 1] = c.y; pk[4 * j + 2] = c.z; pk[4 * j + 3] = c.w;
                }
            }
        };

        bool gated = false;
#pragma unroll 1
        for (int t = 0; t < G1_TILES; t++) {
#pragma unroll
            for (int k = 0; k < G1_KSTEPS; k++) {
                const int s = k & 3;
                TRACE_STEP(t, k, 0);
                mbar_wait(full1(s), (k >> 2) & 1);
                if (k == 0) TRACE_S(12, t, 0);
                TRACE_STEP(t, k, 1);
                if (wg == 1 && k == G1_KSTEPS - (t ? G1_SKEW : SK0)) asm volatile("bar.sync 1, 256;" ::: "memory");
                if (TAIL && t == G1_TILES - 1) mma_step240(acc, da, db, s * G1_STAGE_BYTES / 16, k);
                else mma_step(acc, da, db, s * G1_STAGE_BYTES / 16, k);
                if (wg == 0 && k == G1_KSTEPS - 1) asm volatile("bar.arrive 1, 256;" ::: "memory");
                wg_wait<1>();
                if (k > 0) release(empty1((k - 1) & 3));
                TRACE_STEP(t, k, 2);
                if (t == 0) chunk_ln(k);
                if (k >= 1 && k <= 8 && gated) {
                    chunk_geglu(k - 1);
                    if (k == 8) signal_stores(t == 1 ? 1 : t + 1);
                }
                if (t != 0 && !gated) {
                    if (k == 0) { chunk_qkv(0); chunk_qkv(1); }
                    if (k >= 6 && k <= 11) chunk_qkv(k - 4);
                    if ((k == 0 || k == 11) && t == 2) signal_stores(k ? 3 : 2);
                }
            }
            wg_wait<0>();
            fence_regs(acc);
            release(empty1(3));
            if (t == 0) {
                const uint32_t sp = stats + (cw * 16 + (lane >> 2)) * 8;
                const float2 sa = lds64f(sp), sb = lds64f(sp + 64);
#pragma unroll
                for (int i = 0; i < 128; i++) {
                    const float2 st = i & 2 ? sb : sa;
                    acc[i] = fmaf(st.x, __uint_as_float(pk[i / 4 * 2 + (~i & 1)]), acc[i]) * st.y;
                }
                fence_regs(acc);
            }
#pragma unroll
            for (int i = 0; i < 64; i++) {
                const int e = (i & ~7) * 2 + (i & 3) * 4 + (i & 4) / 2;
                pk[i] = pack_bf16(acc[e], acc[e + 1]);
            }
            const int nt = t * 8 + nslot;
            gated = !tile_is_qkv(nt);
            optr = !gated ? prm.qkv + (size_t)orow * NQKV + tile_index(nt) * 256 + (lane & 3) * 8
                                : prm.pa2 + (size_t)orow * K2 + DM + tile_index(nt) * 128 + (lane & 3) * 8;
            TRACE_S(16 + wg * 8 + t, 0, 0);
        }

        float accd[64], accs[64];
#pragma unroll
        for (int i = 0; i < 64; i++) accd[i] = 0.f;
#pragma unroll
        for (int u = 0; u < 9; u++) {
            const int q = u % G2_STAGES;
            mbar_wait(full2(q), (u / G2_STAGES) & 1);
            mma_step(accd, da, db, q * G2_STAGE_BYTES / 16, u);
            wg_wait<1>();
            if (u > 0) release(empty2((u - 1) % G2_STAGES));
            if (TAIL && u == 0) {
                const uint4 v = ldg_stream(prm.tail + role * 256 + threadIdx.x, stream_policy());
                pk[58] = v.x; pk[59] = v.y; pk[62] = v.z; pk[63] = v.w;
            }
            if (u >= 1) { chunk_geglu(u - 1); if (u == 8) signal_stores(6); }
        }
        {
            int q = 9 % G2_STAGES, qp = 8 % G2_STAGES; uint32_t ph = (9 / G2_STAGES) & 1;
#pragma unroll 1
            for (int u = 9; u < G2_DSTEPS; u++) {
                mbar_wait(full2(q), ph);
                mma_step(accd, da, db, q * (G2_STAGE_BYTES / 16), 1);
                wg_wait<1>();
                release(empty2(qp));
                qp = q;
                if (++q == G2_STAGES) { q = 0; ph ^= 1; }
            }
        }
        TRACE_S(16 + wg * 8 + 5, 0, 0);
#pragma unroll
        for (int i = 0; i < 64; i++) accs[i] = 0.f;
        uint32_t gk[32], xr[32];
        const uint32_t xs = aux + cw * 2048;
        const uint32_t xrow = xs + ((lane & 7) + ((lane >> 3) & 1) * 8) * 128;
        auto xaddr = [&](int j) { return xrow + (j >> 2) * 16384 + (((((j & 3) * 2) + (lane >> 4)) ^ (lane & 7)) << 4); };
#pragma unroll
        for (int u = G2_DSTEPS; u < G2_KSTEPS; u++) {
            const int q = u % G2_STAGES, v = u - G2_DSTEPS;
            mbar_wait(full2(q), (u / G2_STAGES) & 1);
            if (G2_SKEW > 0 && wg == 1 && u == G2_KSTEPS - G2_SKEW) asm volatile("bar.sync 1, 256;" ::: "memory");
            mma_step(accs, da, db, q * G2_STAGE_BYTES / 16, v);
            if (G2_SKEW > 0 && wg == 0 && u == G2_KSTEPS - 1) asm volatile("bar.arrive 1, 256;" ::: "memory");
            if (v >= 1 && v <= 8) {
#pragma unroll
                for (int i = 4 * (v - 1); i < 4 * v; i++) {
                    const uint32_t d2 = pack_bf16(accd[2 * i], accd[2 * i + 1]);
                    gk[i] = pack_bf16(silu(bf_lo(d2)), silu(bf_hi(d2)));
                }
            }
            if (v == 9) mbar_wait(x_bar, 0);
            if (v >= 9 && v <= 12) {
#pragma unroll
                for (int j = 2 * (v - 9); j < 2 * (v - 8); j++)
                    asm volatile("ldmatrix.sync.aligned.m8n8.x4.shared.b16 {%0,%1,%2,%3}, [%4];"
                                 : "=r"(xr[4 * j]), "=r"(xr[4 * j + 1]), "=r"(xr[4 * j + 2]), "=r"(xr[4 * j + 3])
                                 : "r"(xaddr(j)) : "memory");
            }
            wg_wait<1>();
            if (v == 0) fence_regs(accd);
            if (u - 1 + G2_STAGES < G2_KSTEPS) release(empty2((u - 1) % G2_STAGES));
        }
        wg_wait<0>();
        fence_regs(accs);
        TRACE_S(16 + wg * 8 + 6, 0, 0);
#pragma unroll
        for (int j = 0; j < 8; j++) {
            uint32_t r[4];
#pragma unroll
            for (int i = 0; i < 4; i++) {
                const int e = j * 4 + i;
                r[i] = add_bf16x2(xr[e], mul_bf16x2(pack_bf16(accs[2 * e], accs[2 * e + 1]), gk[e]));
            }
            asm volatile("stmatrix.sync.aligned.m8n8.x4.shared.b16 [%0], {%1,%2,%3,%4};"
                         :: "r"(xaddr(j)), "r"(r[0]), "r"(r[1]), "r"(r[2]), "r"(r[3]) : "memory");
            if (j == 3 || j == 7) {
                asm volatile("fence.proxy.async.shared::cta;" ::: "memory");
                __syncwarp();
                if (lane == 0) {
                    tma_store_2d(&prm.out, xs + (j >> 2) * 16384, nslot * 128 + (j >> 2) * 64, mblk * 128 + cw * 16);
                    asm volatile("cp.async.bulk.commit_group;" ::: "memory");
                }
            }
        }
        if (lane == 0) asm volatile("cp.async.bulk.wait_group.read 0;" ::: "memory");
        if (tid == 0) { TRACE(16 + wg * 8 + 7); if (wg == 1) TRACE_GT(13); TRACE_DUMP(); }
    } else {
        asm volatile("setmaxnreg.dec.sync.aligned.u32 %0;" :: "n"(AUX_REGS));
        unsigned* const flags = prm.flags + mblk * 32;
        if (warp == 9) {
            TRACE_CLEAR(); TRACE_GT(0); TRACE(60);
            if (lane == 0) {
                const unsigned epoch = __ldcg(prm.epoch + blockIdx.x * 16 + 2) + 1;
                mbar_wait(sig_bar, 0);
                TRACE(11);
                flag_add(flags + F_LN * 512);
                TRACE(42);
                flag_wait(flags + F_LN * 512, epoch * CNT_LN);
                fence_proxy_async();
                mbar_arrive(dep_bar);
                mbar_wait(sig_bar + 56, 0);
                flag_add(flags + F_LN2 * 512);
                flag_wait(flags + F_LN2 * 512, epoch * CNT_LN);
                fence_proxy_async();
                mbar_arrive(dep_bar + 40);
                TRACE(59);
                prm.epoch[blockIdx.x * 16 + 2] = epoch;
                for (int p = nslot < 4 ? 2 : 1; p < 7; p++) {
                    mbar_wait(sig_bar + p * 8, 0);
                    if (p == 2) TRACE(37);
                    flag_add(p == 2 || p == 3 ? prm.flags + F_QKV * 512 + (p * 4 - 8 + (nslot & 3)) * 32
                                              : flags + (p < 6 ? F_EARLY : F_LATE) * 512);
                    if (p == 2) TRACE(43);
                }
            }
        } else if (warp > 9) {
            const int w = warp - 10;
            const unsigned epoch = __ldcg(prm.epoch + blockIdx.x * 16 + w) + 1;
            const uint32_t tag = 1 + (epoch & 1);
                const uint32_t at = (w ? CB : CA) >> (CIDX) * 4 & 15;
            mbar_wait(empty1(at & 3), 0);
            mbar_wait(empty1(at & 3), at >> 3);
            if (elect_one()) {
                mbar_expect_tx(cs_bar + w * 8, 16384);
                if (CKEEP) asm volatile("cp.async.bulk.tensor.3d.shared::cluster.global.mbarrier::complete_tx::bytes [%0], [%1, {%3, %4, %5}], [%2];"
                    :: "r"(aux + w * 16384), "l"(w0), "r"(cs_bar + w * 8), "r"(0), "r"(((mblk & ~1) + w) * 64), "r"(w0_col) : "memory");
                else tma_3d(aux + w * 16384, w0, cs_bar + w * 8, 0, ((mblk & ~1) + w) * 64, w0_col, stream_policy());
            }
            float cs[8];
#pragma unroll
            for (int d = 0; d < 8; d++) cs[d] = 0.f;
            const uint32_t wa = aux + w * 8192 + (lane >> 3) * 128 + (((lane & 7) ^ (lane >> 3)) << 4);
            uint4 v[9];
            auto fetch = [&](int h, uint32_t off) {
#pragma unroll
                for (int j = 0; j < 4; j++) v[h * 4 + j] = lds128((wa ^ (j & 1) * 64) + off + h * 2048 + j * 512);
            };
            auto add = [&](int h) {
#pragma unroll
                for (int j = 0; j < 4; j++) {
                    float f[8];
                    unpack8(v[h * 4 + j], f);
#pragma unroll
                    for (int d = 0; d < 8; d++) cs[d] += f[d];
                }
            };
            if (CST) { mbar_wait(empty1(CST & 3), 0); mbar_wait(empty1(CST & 3), CST >> 3); }
            mbar_wait(cs_bar, 0);

            fetch(0, 0);
#pragma unroll 1
            for (int i = 0; i < 4; i++) {
                fetch(1, (i >> 1) * 16384 + (i & 1) * 4096);
                add(0);
                if (i == 1) mbar_wait(cs_bar + 8, 0);
                fetch(0, (i + 1 & 2) * 8192 + (~i & 1) * 4096);
                add(1);
            }
#pragma unroll
            for (int d = 0; d < 4; d++)
                cs[d] = (lane & 16 ? cs[d + 4] : cs[d]) + __shfl_xor_sync(0xffffffffu, lane & 16 ? cs[d] : cs[d + 4], 16);
#pragma unroll
            for (int d = 0; d < 2; d++)
                cs[d] = (lane & 8 ? cs[d + 2] : cs[d]) + __shfl_xor_sync(0xffffffffu, lane & 8 ? cs[d] : cs[d + 2], 8);
            st_tagged(prm.colsum + (nslot * 2 + rank) * 1024 + (mblk >> 1) * 128 + w * 64 + (lane & 7) * 8 + (lane >> 3) * 2,
                      cs[0], cs[1], tag);

#pragma unroll
            for (int m = 0; m < 9; m++) v[m] = make_uint4(0, 0, 0, 0);
            const float* parts = prm.colsum + (nslot * 2 + w) * 1024 + lane * 4;
            const float* const rows = &prm.stats[mblk * 128 + w * 64 + lane * 2].x;
#pragma unroll 1
            for (int spins = 0; spins < (1 << 16); spins++) {
                bool missing = false;
                asm volatile("" : "+l"(parts));
#pragma unroll
                for (int m = 0; m < 9; m++) {
                    if (untagged(v[m], tag)) {
                        missing = true;
                        v[m] = ld_relaxed(m < 8 ? parts + m * 128 : rows);
                    }
                }
                if (!missing) break;
            }
            float4 c = make_float4(0.f, 0.f, 0.f, 0.f);
#pragma unroll
            for (int m = 0; m < 8; m++) {
                c.x += __uint_as_float(v[m].x ^ tag); c.y += __uint_as_float(v[m].y ^ tag);
                c.z += __uint_as_float(v[m].z ^ tag); c.w += __uint_as_float(v[m].w ^ tag);
            }
            sts128(stats + w * 512 + lane * 16, make_uint4(v[8].x ^ tag, v[8].y ^ tag, v[8].z ^ tag, v[8].w ^ tag));
            const uint32_t ca = colsum + (w * 8 + (lane >> 2)) * 64 + (lane & 1) * 32 + (lane & 2) * 4;
            sts64f(ca, c.y, c.x);
            sts64f(ca + 16, c.w, c.z);
            __syncwarp();
            if (lane == 0) {
                mbar_arrive(fold_bar);
                prm.epoch[blockIdx.x * 16 + w] = epoch;
                if (w == 0) {
                    TRACE_S(35, w, 0);
                    flag_wait(flags + F_EARLY * 512, epoch * CNT_EARLY);
                    fence_proxy_async(); mbar_arrive(dep_bar + 8);
                    flag_wait(flags + F_LATE * 512, epoch * CNT_LATE);
                    fence_proxy_async(); mbar_arrive(dep_bar + 16);
                    flag_wait(prm.flags + F_O * 512, epoch * CNT_O);
                    fence_proxy_async(); mbar_arrive(dep_bar + 24);
                    flag_wait(prm.flags + F_O * 512 + 32, epoch * CNT_O);
                    fence_proxy_async(); mbar_arrive(dep_bar + 32);
                }
            }
        } else {
            const uint32_t t0 = clock();
#pragma unroll
            for (int k = 1; k < G1_STAGES; k++) {
                const uint32_t sa = base + k * G1_STAGE_BYTES;
                if (PACE0 + PACE) while ((uint32_t)clock() - t0 < PACE0 + (k - 1) * PACE) {}
                load_stage1(sa, sa + A_BYTES + rank * 16384, full1(k), &prm.x, w0, k * 64, mblk * 128, w0_col, 0, stream_policy());
            }
            if (elect_one()) {
                prefetch_map(&prm.xn); prefetch_map(&prm.wqkv); prefetch_map(&prm.wu); prefetch_map(&prm.wg);
                prefetch_map(&prm.a2); prefetch_map(&prm.wo); prefetch_map(&prm.wd); prefetch_map(&prm.out);
            }
            uint32_t ph = 0;
#pragma unroll 1
            for (int t = 0; t < G1_TILES; t++) {
                const int nt = t * 8 + nslot;
                const CUtensorMap* const mb = tile_is_qkv(nt) ? &prm.wqkv : (rank ? &prm.wu : &prm.wg);
                const int col = tile_is_qkv(nt) ? tile_index(nt) * 4 + rank * 2 : tile_index(nt) * 2;
                if (t == 1) { TRACE_PUT(1, c0); TRACE_PUT(2, c2); TRACE(14); mbar_wait_warp(dep_bar, 0); TRACE(3); }
#pragma unroll 1
                for (int k = t ? 0 : G1_STAGES; k < G1_KSTEPS; k++) {
                    const int s = k & 3;
                    if (t == 1 && k == 8) mbar_wait_warp(dep_bar + 40, 0);
                    mbar_wait_warp(empty1(s), ph);
                    const uint32_t sa = base + s * G1_STAGE_BYTES;
                    load_stage1(sa, sa + A_BYTES + rank * 16384, full1(s), t ? &prm.xn : &prm.x, mb, k * 64, mblk * 128, col,
                                t & 3, stream_policy());
                    if (s == 3) ph ^= 1;
                }
            }
            if (elect_one()) {
                mbar_expect_tx(x_bar, 32768);
                tma_2d(aux, &prm.x, x_bar, nslot * 128, mblk * 128, stream_policy());
                tma_2d(aux + 16384, &prm.x, x_bar, nslot * 128 + 64, mblk * 128, stream_policy());
            }
            TRACE(4);
            mbar_wait_warp(dep_bar + 8, 0);
            TRACE(5);
            int q = 0; uint32_t ph2 = 1;
#pragma unroll 1
            for (int u = 0; u < G2_KSTEPS; u++) {
                if (u == G2_LATE || u == G2_DSTEPS || u == G2_LAST) {
                    TRACE(u == G2_LATE ? 6 : (u == G2_DSTEPS ? 32 : 40));
                    mbar_wait_warp(dep_bar + (u == G2_LATE ? 16 : (u == G2_DSTEPS ? 24 : 32)), 0);
                    TRACE(u == G2_LATE ? 7 : (u == G2_DSTEPS ? 33 : 41));
                }
                const uint32_t sa = stage2(q);
                const bool down = u < G2_DSTEPS;
                const int k = down ? u : (u & 3) * 4 + (u - G2_DSTEPS) / 4;
                mbar_wait_warp(u < G2_STAGES ? empty1((u * 2 + 1) / 3) : empty2(q), u < G2_STAGES ? ph : ph2);
                load_stage2(sa, sa + A_BYTES + rank * 8192, full2(q), &prm.a2, down ? &prm.wd : &prm.wo, (down ? DM : 0) + k * 64,
                            mblk * 64, nslot * 128 + rank * 64, k * 2, stream_policy());
                if (++q == G2_STAGES) { q = 0; ph2 ^= 1; }
            }
            TRACE(8);
        }
    }
}

typedef CUresult (*EncodeFn)(CUtensorMap*, CUtensorMapDataType, cuuint32_t, void*, const cuuint64_t*, const cuuint64_t*,
                             const cuuint32_t*, const cuuint32_t*, CUtensorMapInterleave, CUtensorMapSwizzle,
                             CUtensorMapL2promotion, CUtensorMapFloatOOBfill);

void encode(EncodeFn fn, CUtensorMap* m, const void* ptr, int rank, const cuuint64_t* dims, const cuuint64_t* strides,
            const cuuint32_t* box) {
    const cuuint32_t es[5] = {1, 1, 1, 1, 1};
    fn(m, CU_TENSOR_MAP_DATA_TYPE_BFLOAT16, rank, const_cast<void*>(ptr), dims, strides, box, es,
       CU_TENSOR_MAP_INTERLEAVE_NONE, box[0] == 16 ? CU_TENSOR_MAP_SWIZZLE_32B : CU_TENSOR_MAP_SWIZZLE_128B,
       CU_TENSOR_MAP_L2_PROMOTION_L2_128B, CU_TENSOR_MAP_FLOAT_OOB_FILL_NONE);
}
void encode_2d(EncodeFn fn, CUtensorMap* m, const void* ptr, int cols, int box_rows) {
    const cuuint64_t dims[2] = {(cuuint64_t)cols, SEQ}, strides[1] = {(cuuint64_t)cols * 2};
    const cuuint32_t box[2] = {64, (cuuint32_t)box_rows};
    encode(fn, m, ptr, 2, dims, strides, box);
}
void encode_w1(EncodeFn fn, CUtensorMap* m, const void* ptr, int cols) {
    const cuuint64_t dims[3] = {64, DM, (cuuint64_t)cols / 64}, strides[2] = {(cuuint64_t)cols * 2, 128};
    const cuuint32_t box[3] = {64, 64, 2};
    encode(fn, m, ptr, 3, dims, strides, box);
}
void encode_tail(EncodeFn fn, CUtensorMap* m, const __nv_bfloat16* w) {
    const cuuint64_t dims[3] = {16, DM, 8}, strides[2] = {DF * 2, 256};
    const cuuint32_t box[3] = {16, 64, 8};
    encode(fn, m, w + DF - 1024 + 112, 3, dims, strides, box);
}
void encode_qk(EncodeFn fn, CUtensorMap* m, const void* ptr) {
    const cuuint64_t dims[3] = {DM, SEQ, 3}, strides[2] = {NQKV * 2, DM * 2};
    const cuuint32_t box[3] = {64, 16, 2};
    encode(fn, m, ptr, 3, dims, strides, box);
}
void encode_a2(EncodeFn fn, CUtensorMap* m, const void* ptr) {
    const cuuint64_t dims[3] = {K2, 2, SEQ / 2}, strides[2] = {(cuuint64_t)SEQ * K2, K2 * 2};
    const cuuint32_t box[3] = {64, 2, 64};
    encode(fn, m, ptr, 3, dims, strides, box);
}
void encode_w2(EncodeFn fn, CUtensorMap* m, const void* ptr, int rows) {
    const cuuint64_t rb = DM * 2;
    const cuuint64_t dims[5] = {DM, 2, 4, 4, (cuuint64_t)rows / 32}, strides[4] = {rb, 8 * rb, 2 * rb, 32 * rb};
    const cuuint32_t box[5] = {64, 2, 4, 4, 2};
    encode(fn, m, ptr, 5, dims, strides, box);
}

}

extern "C" void kernel_launch(void* const* d_in, const int* in_sizes, int n_in, void* d_out, int out_size) {
    (void)in_sizes; (void)n_in; (void)out_size;
    static EncodeFn fn = nullptr;
    static Params prm;
    if (!fn) {
        cudaDriverEntryPointQueryResult st;
        cudaGetDriverEntryPoint("cuTensorMapEncodeTiled", (void**)&fn, cudaEnableDefault, &st);
        cudaGetSymbolAddress((void**)&prm.pxn, g_xn);
        cudaGetSymbolAddress((void**)&prm.qkv, g_qkv);
        cudaGetSymbolAddress((void**)&prm.pa2, g_a2);
        cudaGetSymbolAddress((void**)&prm.tail, g_tail);
        cudaGetSymbolAddress((void**)&prm.stats, g_stats);
        cudaGetSymbolAddress((void**)&prm.colsum, g_colsum);
        cudaGetSymbolAddress((void**)&prm.flags, g_flags);
        cudaGetSymbolAddress((void**)&prm.epoch, g_epoch);
        cudaFuncSetAttribute(fused_kernel, cudaFuncAttributeMaxDynamicSharedMemorySize, SMEM_BYTES);
    }
    encode_2d(fn, &prm.x, d_in[0], DM, 128);
    encode_2d(fn, &prm.xn, prm.pxn, DM, 128);
    encode_tail(fn, &prm.wtail, (const __nv_bfloat16*)d_in[5]);
    encode_w1(fn, &prm.wqkv, d_in[1], NQKV);
    encode_w1(fn, &prm.wg, d_in[4], DF);
    encode_w1(fn, &prm.wu, d_in[5], DF);
    encode_qk(fn, &prm.qk, prm.qkv);
    encode_2d(fn, &prm.v, prm.qkv, NQKV, 16);
    encode_2d(fn, &prm.o, prm.pa2, K2, 16);
    encode_a2(fn, &prm.a2, prm.pa2);
    encode_w2(fn, &prm.wo, d_in[2], DM);
    encode_w2(fn, &prm.wd, d_in[6], DF);
    encode_2d(fn, &prm.out, d_out, DM, 16);
    prm.px = (const __nv_bfloat16*)d_in[0];
    fused_kernel<<<NCTA, 384, SMEM_BYTES>>>(prm);
}
```

```cpp
#include <cuda_runtime.h>
#include <cuda_bf16.h>
#include <cuda.h>
#include <stdint.h>
#include <type_traits>

#define LNS 3
#define FS 14
#define CA 0x87658765u
#define CB 0x65876587u
#define CST 10
#define CIDX nslot
#define CKEEP 1
#define PACE0 900
#define PACE 425
#define PACE3 1700
#define TAIL 0
#define LNL 0
#define TDELAY 0
#define SV 0
#define SK0 2

namespace {

constexpr int SEQ = 2048, DM = 1024, DF = 3584, K2 = DM + DF, NQKV = 3 * DM;
constexpr int NGEMM = 128, NCTA = 132;
constexpr int G1_STAGES = 4, G1_STAGE_BYTES = 49152, G1_KSTEPS = 16, G1_TILES = 5;
constexpr int G2_STAGES = 6, G2_STAGE_BYTES = 32768, G2_KSTEPS = 72, G2_LATE = 40, G2_DSTEPS = 56, G2_LAST = 68;
constexpr int LN_STEP = LNS, FOLD_STEP = FS;
constexpr int A_BYTES = 16384;
constexpr int AUX_OFF = G1_STAGES * G1_STAGE_BYTES;
constexpr int BAR_OFF = AUX_OFF + 32768;
constexpr int SMEM_BYTES = BAR_OFF + 2816;
constexpr int G1_SKEW = 2, G2_SKEW = 2;
constexpr int CONSUMER_REGS = 224, AUX_REGS = 56;
constexpr int ATT_SLOT = 8192;

enum { F_LN = 0, F_QKV = 1, F_EARLY = 2, F_LATE = 3, F_O = 4, F_LN2 = 5 };
constexpr unsigned CNT_LN = 8, CNT_QKV = 32, CNT_EARLY = 21, CNT_LATE = 8, CNT_O = 4;

__device__ __align__(1024) __nv_bfloat16 g_xn[SEQ * DM];
__device__ __align__(1024) __nv_bfloat16 g_qkv[SEQ * NQKV];
__device__ __align__(1024) __nv_bfloat16 g_a2[SEQ * K2];
__device__ __align__(128) uint4 g_tail[NGEMM * 256];
__device__ __align__(128) float2 g_stats[SEQ];
__device__ __align__(128) float g_colsum[16 * 1024];
__device__ __align__(128) unsigned g_flags[6 * 16 * 32];
__device__ __align__(128) unsigned g_epoch[NCTA * 16];

struct Params {
    const __nv_bfloat16* px;
    __nv_bfloat16 *pxn, *qkv, *pa2;
    uint4* tail;
    float2* stats;
    float* colsum;
    unsigned *flags, *epoch;
    unsigned long long* trace;
    uint32_t zero;
    CUtensorMap x, wqkv, wg, wu, xn, wtail, qk, v, o, a2, wo, wd, out;
};

extern __shared__ __align__(1024) uint8_t smem_raw[];

#define TRACE(slot) do {} while (0)
#define TRACE_GT(slot) do {} while (0)
#define TRACE_S(slot, v, want) do {} while (0)
#define TRACE_GET(v) do {} while (0)
#define TRACE_PUT(slot, v) do {} while (0)
#define TRACE_SLOT(v, slot) do {} while (0)
#define TRACE_NEXT(v) do {} while (0)
#define TRACE_DUMP() do {} while (0)
#define TRACE_CLEAR() do {} while (0)
#define STAGE_TRACE 0
#define TRACE_STEP(t, k, i) do {} while (0)

__device__ __forceinline__ uint32_t smem_u32(const void* p) { return (uint32_t)__cvta_generic_to_shared(p); }
__device__ __forceinline__ void mbar_init(uint32_t bar, uint32_t cnt) {
    asm volatile("mbarrier.init.shared::cta.b64 [%0], %1;" :: "r"(bar), "r"(cnt) : "memory");
}
__device__ __forceinline__ void mbar_expect_tx(uint32_t bar, uint32_t bytes) {
    asm volatile("mbarrier.arrive.expect_tx.shared::cta.b64 _, [%0], %1;" :: "r"(bar), "r"(bytes) : "memory");
}
__device__ __forceinline__ void mbar_arrive(uint32_t bar) {
    asm volatile("mbarrier.arrive.shared::cta.b64 _, [%0];" :: "r"(bar) : "memory");
}
__device__ __forceinline__ void mbar_arrive_cluster(uint32_t bar, uint32_t cta) {
    asm volatile("{\n.reg .b32 ra;\nmapa.shared::cluster.u32 ra, %0, %1;\nmbarrier.arrive.shared::cluster.b64 _, [ra];\n}"
                 :: "r"(bar), "r"(cta) : "memory");
}
__device__ __forceinline__ bool mbar_try_wait(uint32_t bar, uint32_t parity) {
    uint32_t ok;
    asm volatile("{\n.reg .pred p;\nmbarrier.try_wait.parity.shared::cta.b64 p, [%1], %2;\nselp.u32 %0, 1, 0, p;\n}"
                 : "=r"(ok) : "r"(bar), "r"(parity) : "memory");
    return ok;
}
__device__ __forceinline__ bool mbar_test(uint32_t bar, uint32_t parity) {
    uint32_t ok;
    asm volatile("{\n.reg .pred p;\nmbarrier.test_wait.parity.shared::cta.b64 p, [%1], %2;\nselp.u32 %0, 1, 0, p;\n}"
                 : "=r"(ok) : "r"(bar), "r"(parity) : "memory");
    return ok;
}
__device__ __forceinline__ void mbar_wait(uint32_t bar, uint32_t parity) {
#pragma unroll 1
    for (int spins = 0; !mbar_try_wait(bar, parity) && spins < (1 << 17); spins++) {}
}
template <bool WARP = false> __device__ __forceinline__ void flag_wait(const unsigned* p, unsigned target) {
#pragma unroll 1
    for (int spins = 0; spins < (1 << 19); spins++) {
        unsigned v;
        asm volatile("ld.acquire.gpu.global.u32 %0, [%1];" : "=r"(v) : "l"(p) : "memory");
        if (WARP ? __all_sync(0xffffffffu, (int)(v - target) >= 0) : (int)(v - target) >= 0) break;
        __nanosleep(64);
    }
}
__device__ __forceinline__ void mbar_wait_warp(uint32_t bar, uint32_t parity) {
#pragma unroll 1
    for (int spins = 0; !__all_sync(0xffffffffu, mbar_try_wait(bar, parity)) && spins < (1 << 17); spins++) {}
}
__device__ __forceinline__ void flag_add(unsigned* p) {
    asm volatile("red.release.gpu.global.add.u32 [%0], 1;" :: "l"(p) : "memory");
}
__device__ __forceinline__ bool elect_one() {
    uint32_t ok;
    asm volatile("{\n.reg .pred p;\nelect.sync _|p, 0xffffffff;\nselp.u32 %0, 1, 0, p;\n}" : "=r"(ok));
    return ok;
}
__device__ __forceinline__ uint32_t pick(bool c, uint32_t a, uint32_t b) {
    uint32_t r;
    asm("{\n.reg .pred p;\nsetp.ne.b32 p, %3, 0;\nselp.b32 %0, %1, %2, p;\n}" : "=r"(r) : "r"(a), "r"(b), "r"((uint32_t)c));
    return r;
}
__device__ __forceinline__ void fence_proxy_async() { asm volatile("fence.proxy.async.global;" ::: "memory"); }
__device__ __forceinline__ uint4 lds128(uint32_t addr) {
    uint4 v;
    asm volatile("ld.shared.v4.u32 {%0,%1,%2,%3}, [%4];" : "=r"(v.x), "=r"(v.y), "=r"(v.z), "=r"(v.w) : "r"(addr) : "memory");
    return v;
}
__device__ __forceinline__ float2 lds64f(uint32_t addr) {
    float2 v;
    asm volatile("ld.shared.v2.f32 {%0,%1}, [%2];" : "=f"(v.x), "=f"(v.y) : "r"(addr) : "memory");
    return v;
}
__device__ __forceinline__ void sts128(uint32_t addr, uint4 v) {
    asm volatile("st.shared.v4.u32 [%0], {%1,%2,%3,%4};" :: "r"(addr), "r"(v.x), "r"(v.y), "r"(v.z), "r"(v.w) : "memory");
}
__device__ __forceinline__ void sts64f(uint32_t addr, float a, float b) {
    asm volatile("st.shared.v2.f32 [%0], {%1,%2};" :: "r"(addr), "f"(a), "f"(b) : "memory");
}

__device__ __forceinline__ uint64_t stream_policy() { return 0x12F0000000000000ull; }
__device__ __forceinline__ void tma_2d(uint32_t dst, const CUtensorMap* m, uint32_t bar, int c0, int c1, uint64_t pol) {
    asm volatile("cp.async.bulk.tensor.2d.shared::cluster.global.mbarrier::complete_tx::bytes.L2::cache_hint"
                 " [%0], [%1, {%3, %4}], [%2], %5;"
                 :: "r"(dst), "l"(m), "r"(bar), "r"(c0), "r"(c1), "l"(pol) : "memory");
}
__device__ __forceinline__ void tma_3d(uint32_t dst, const CUtensorMap* m, uint32_t bar, int c0, int c1, int c2, uint64_t pol) {
    asm volatile("cp.async.bulk.tensor.3d.shared::cluster.global.mbarrier::complete_tx::bytes.L2::cache_hint"
                 " [%0], [%1, {%3, %4, %5}], [%2], %6;"
                 :: "r"(dst), "l"(m), "r"(bar), "r"(c0), "r"(c1), "r"(c2), "l"(pol) : "memory");
}
__device__ __forceinline__ void tma_3d_mc(uint32_t dst, const CUtensorMap* m, uint32_t bar, int c1, int c2, uint64_t pol) {
    asm volatile("cp.async.bulk.tensor.3d.shared::cluster.global.mbarrier::complete_tx::bytes.multicast::cluster.L2::cache_hint"
                 " [%0], [%1, {%3, %4, %5}], [%2], %6, %7;"
                 :: "r"(dst), "l"(m), "r"(bar), "r"(0), "r"(c1), "r"(c2), "h"((uint16_t)3), "l"(pol) : "memory");
}
__device__ __forceinline__ void load_stage1(uint32_t dst, uint32_t dst_b, uint32_t bar, const CUtensorMap* ma, const CUtensorMap* mb,
                                            int k, int row, int col, int keep_a, uint64_t pol) {
    asm volatile("{\n.reg .pred e, p, q;\nelect.sync _|e, 0xffffffff;\nsetp.ne.and.b32 p|q, %8, 0, e;\n"
        "@p cp.async.bulk.tensor.2d.shared::cluster.global.mbarrier::complete_tx::bytes [%0], [%3, {%5, %6}], [%2];\n"
        "@q cp.async.bulk.tensor.2d.shared::cluster.global.mbarrier::complete_tx::bytes.L2::cache_hint [%0], [%3, {%5, %6}], [%2], %9;\n"
        "@e cp.async.bulk.tensor.3d.shared::cluster.global.mbarrier::complete_tx::bytes.multicast::cluster.L2::cache_hint"
        " [%1], [%4, {%10, %5, %7}], [%2], %11, %9;\n"
        "@e mbarrier.arrive.expect_tx.shared::cta.b64 _, [%2], %12;\n}"
        :: "r"(dst), "r"(dst_b), "r"(bar), "l"(ma), "l"(mb), "r"(k), "r"(row), "r"(col), "r"(keep_a), "l"(pol), "r"(0),
           "h"((uint16_t)3), "n"(G1_STAGE_BYTES) : "memory");
}
__device__ __forceinline__ void load_stage2(uint32_t dst, uint32_t dst_b, uint32_t bar, const CUtensorMap* ma, const CUtensorMap* mb,
                                            int ka, int row, int col, int kb, uint64_t pol) {
    asm volatile("{\n.reg .pred e;\nelect.sync _|e, 0xffffffff;\n"
        "@e cp.async.bulk.tensor.3d.shared::cluster.global.mbarrier::complete_tx::bytes.L2::cache_hint [%0], [%3, {%5, %10, %6}], [%2], %9;\n"
        "@e cp.async.bulk.tensor.5d.shared::cluster.global.mbarrier::complete_tx::bytes.multicast::cluster.L2::cache_hint"
        " [%1], [%4, {%7, %10, %10, %10, %8}], [%2], %11, %9;\n"
        "@e mbarrier.arrive.expect_tx.shared::cta.b64 _, [%2], %12;\n}"
        :: "r"(dst), "r"(dst_b), "r"(bar), "l"(ma), "l"(mb), "r"(ka), "r"(row), "r"(col), "r"(kb), "l"(pol), "r"(0),
           "h"((uint16_t)3), "n"(G2_STAGE_BYTES) : "memory");
}
__device__ __forceinline__ void tma_store_2d(const CUtensorMap* m, uint32_t src, int c0, int c1) {
    asm volatile("cp.async.bulk.tensor.2d.global.shared::cta.bulk_group [%0, {%2, %3}], [%1];"
                 :: "l"(m), "r"(src), "r"(c0), "r"(c1) : "memory");
}
__device__ __forceinline__ uint4 ldg_stream(const void* p, uint64_t pol) {
    uint4 v;
    asm volatile("ld.global.nc.L1::no_allocate.L2::cache_hint.v4.u32 {%0,%1,%2,%3}, [%4], %5;"
                 : "=r"(v.x), "=r"(v.y), "=r"(v.z), "=r"(v.w) : "l"(p), "l"(pol));
    return v;
}
__device__ __forceinline__ void st_tagged(void* p, float a, float b, uint32_t tag) {
    asm volatile("st.relaxed.gpu.global.v2.b32 [%0], {%1,%2};"
                 :: "l"(p), "r"((__float_as_uint(a) & ~3u) | tag), "r"((__float_as_uint(b) & ~3u) | tag) : "memory");
}
__device__ __forceinline__ bool untagged(const uint4& v, uint32_t tag) {
    return ((v.x ^ tag) | (v.y ^ tag) | (v.z ^ tag) | (v.w ^ tag)) & 3;
}
__device__ __forceinline__ uint4 ld_relaxed(const void* p) {
    uint4 v;
    asm volatile("ld.relaxed.gpu.global.v4.b32 {%0,%1,%2,%3}, [%4];" : "=r"(v.x), "=r"(v.y), "=r"(v.z), "=r"(v.w) : "l"(p) : "memory");
    return v;
}
__device__ __forceinline__ void prefetch_3d(const CUtensorMap* m, int c1, int c2, uint64_t pol) {
    asm volatile("cp.async.bulk.prefetch.tensor.3d.L2.global.L2::cache_hint [%0, {%1, %2, %3}], %4;"
                 :: "l"(m), "r"(0), "r"(c1), "r"(c2), "l"(pol) : "memory");
}
__device__ __forceinline__ void prefetch_map(const CUtensorMap* m) {
    asm volatile("prefetch.tensormap [%0];" :: "l"(m) : "memory");
}
template <int N> __device__ __forceinline__ void wg_wait() { asm volatile("wgmma.wait_group.sync.aligned %0;" :: "n"(N) : "memory"); }

__device__ __forceinline__ uint32_t desc_a(uint32_t addr) { return (addr & 0x3FFFF) >> 4 | 1 << 16; }
__device__ __forceinline__ uint32_t desc_b(uint32_t addr) { return (addr & 0x3FFFF) >> 4 | 512 << 16; }

#define R8(d, o) "+f"(d[o]), "+f"(d[o+1]), "+f"(d[o+2]), "+f"(d[o+3]), "+f"(d[o+4]), "+f"(d[o+5]), "+f"(d[o+6]), "+f"(d[o+7])
#define R32(d, o) R8(d, o), R8(d, o+8), R8(d, o+16), R8(d, o+24)
#define R64(d, o) R32(d, o), R32(d, o+32)
#define ACC0 "%0,%1,%2,%3,%4,%5,%6,%7,%8,%9,%10,%11,%12,%13,%14,%15,%16,%17,%18,%19,%20,%21,%22,%23,%24,%25,%26,%27,%28,%29,%30,%31,"\
    "%32,%33,%34,%35,%36,%37,%38,%39,%40,%41,%42,%43,%44,%45,%46,%47,%48,%49,%50,%51,%52,%53,%54,%55,%56,%57,%58,%59,%60,%61,%62,%63"
#define ACC1 "%64,%65,%66,%67,%68,%69,%70,%71,%72,%73,%74,%75,%76,%77,%78,%79,%80,%81,%82,%83,%84,%85,%86,%87,%88,%89,%90,%91,%92,%93,%94,%95,"\
    "%96,%97,%98,%99,%100,%101,%102,%103,%104,%105,%106,%107,%108,%109,%110,%111,%112,%113,%114,%115,%116,%117,%118,%119"
#define ACC64 "{" ACC0 "}"
#define ACC120 "{" ACC0 "," ACC1 "}"
#define ACC128 "{" ACC0 "," ACC1 ",%120,%121,%122,%123,%124,%125,%126,%127}"
#define MMA_K16(shape, acc, keep, hb, sb) \
    "mov.b64 da, {la, 0x40000040};\nmov.b64 db, {lb, " hb "};\n" \
    "wgmma.mma_async.sync.aligned." shape ".f32.bf16.bf16 " acc ", da, db, " keep ", 1, 1, 0, 1;\n" \
    "add.u32 la, la, 2;\nadd.u32 lb, lb, " sb ";\n"
#define MMA_STEP_B(shape, acc, a, b, off, keep, hb, sb) \
    "{\n.reg .pred p, q;\n.reg .b32 la, lb;\n.reg .b64 da, db;\nsetp.ne.b32 p, " keep ", 0;\nsetp.eq.b32 q, 0, 0;\n" \
    "add.u32 la, " a ", " off ";\nadd.u32 lb, " b ", " off ";\nwgmma.fence.sync.aligned;\n" \
    MMA_K16(shape, acc, "p", hb, sb) MMA_K16(shape, acc, "q", hb, sb) MMA_K16(shape, acc, "q", hb, sb) \
    MMA_K16(shape, acc, "q", hb, sb) "wgmma.commit_group.sync.aligned;\n}"
#define MMA_STEP(shape, acc, a, b, off, keep) MMA_STEP_B(shape, acc, a, b, off, keep, "0x40000040", "128")

__device__ __forceinline__ void mma_step(float (&d)[128], uint32_t da, uint32_t db, uint32_t off, int keep) {
    asm volatile(MMA_STEP("m64n256k16", ACC128, "%128", "%129", "%130", "%131")
                 : R64(d, 0), R64(d, 64) : "r"(da), "r"(db), "r"(off), "r"(keep) : "memory");
}
__device__ __forceinline__ void mma_rank(float (&d)[128], uint32_t a0, uint32_t a1, uint32_t db) {
    asm volatile("{\n.reg .pred q;\n.reg .b64 db;\nsetp.eq.b32 q, 0, 0;\nmov.b64 db, {%131, 0x40000040};\nwgmma.fence.sync.aligned;\n"
                 "wgmma.mma_async.sync.aligned.m64n256k16.f32.bf16.bf16 " ACC128 ", {%128, %129, %130, %130}, db, q, 1, 1, 1;\n}"
                 : R64(d, 0), R64(d, 64) : "r"(a0), "r"(a1), "r"(0), "r"(db) : "memory");
}
__device__ __forceinline__ void mma_step240(float (&d)[128], uint32_t da, uint32_t db, uint32_t off, int keep) {
    asm volatile(MMA_STEP("m64n240k16", ACC120, "%120", "%121", "%122", "%123")
                 : R64(d, 0), R32(d, 64), R8(d, 96), R8(d, 104), R8(d, 112) : "r"(da), "r"(db), "r"(off), "r"(keep) : "memory");
}
__device__ __forceinline__ void mma_step(float (&d)[64], uint32_t da, uint32_t db, uint32_t off, int keep) {
    asm volatile(MMA_STEP("m64n128k16", ACC64, "%64", "%65", "%66", "%67")
                 : R64(d, 0) : "r"(da), "r"(db), "r"(off), "r"(keep) : "memory");
}

__device__ __forceinline__ void mma_step_tail(float (&d)[64], uint32_t da, uint32_t b, uint32_t off) {
    asm volatile(MMA_STEP_B("m64n128k16", ACC64, "%64", "%65", "%66", "1", "0xC0000010", "32")
                 : R64(d, 0) : "r"(da), "r"((b & 0x3FFFF) >> 4 | 128 << 16), "r"(off) : "memory");
}

__device__ __forceinline__ uint32_t pack_bf16(float lo, float hi) {
    uint32_t r; asm("cvt.rn.bf16x2.f32 %0, %1, %2;" : "=r"(r) : "f"(hi), "f"(lo)); return r;
}
__device__ __forceinline__ float bf_lo(uint32_t v) { return __uint_as_float(v << 16); }
__device__ __forceinline__ float bf_hi(uint32_t v) { return __uint_as_float(v & 0xffff0000u); }
__device__ __forceinline__ float round_bf16(float v) { return bf_lo(pack_bf16(v, 0.f)); }
__device__ __forceinline__ uint32_t mul_bf16x2(uint32_t a, uint32_t b) {
    uint32_t r; asm("mul.rn.bf16x2 %0, %1, %2;" : "=r"(r) : "r"(a), "r"(b)); return r;
}
__device__ __forceinline__ uint32_t add_bf16x2(uint32_t a, uint32_t b) {
    uint32_t r; asm("add.rn.bf16x2 %0, %1, %2;" : "=r"(r) : "r"(a), "r"(b)); return r;
}
__device__ __forceinline__ uint32_t sub_bf16x2(uint32_t a, uint32_t b) {
    uint32_t r; asm("sub.rn.bf16x2 %0, %1, %2;" : "=r"(r) : "r"(a), "r"(b)); return r;
}
__device__ __forceinline__ uint32_t mul2_bf16x2(uint32_t a, uint32_t hi, uint32_t lo) {
    uint32_t r; asm("fma.rn.bf16x2 %0, %1, %2, %3;" : "=r"(r) : "r"(a), "r"(hi), "r"(mul_bf16x2(a, lo))); return r;
}
__device__ __forceinline__ float tanh_fast(float x) { float r; asm("tanh.approx.f32 %0, %1;" : "=f"(r) : "f"(x)); return r; }
__device__ __forceinline__ float gelu_tanh(float g) {
    float t = fmaf(g * g, 0.044715f * 0.7978845608f, 0.7978845608f) * g;
    float hg = 0.5f * g;
    return fmaf(hg, tanh_fast(t), hg);
}
__device__ __forceinline__ uint32_t geglu2(uint32_t g2, uint32_t u2) {
    return mul_bf16x2(pack_bf16(gelu_tanh(bf_lo(g2)), gelu_tanh(bf_hi(g2))), u2);
}
__device__ __forceinline__ float silu(float d) {
    float hd = 0.5f * d;
    return fmaf(hd, tanh_fast(hd), hd);
}
__device__ __forceinline__ float ex2_fast(float x) { float r; asm("ex2.approx.ftz.f32 %0, %1;" : "=f"(r) : "f"(x)); return r; }
__device__ __forceinline__ void unpack8(uint4 v, float (&f)[8]) {
    f[0] = bf_lo(v.x); f[1] = bf_hi(v.x); f[2] = bf_lo(v.y); f[3] = bf_hi(v.y);
    f[4] = bf_lo(v.z); f[5] = bf_hi(v.z); f[6] = bf_lo(v.w); f[7] = bf_hi(v.w);
}
template <int N> __device__ __forceinline__ void fence_regs(float (&d)[N]) {
#pragma unroll
    for (int i = 0; i < N; i++) asm volatile("" : "+f"(d[i]) :: "memory");
}

__device__ __forceinline__ float rcp_fast(float x) { float r; asm("rcp.approx.ftz.f32 %0, %1;" : "=f"(r) : "f"(x)); return r; }
__device__ __forceinline__ float sqrt_fast(float x) { float r; asm("sqrt.approx.ftz.f32 %0, %1;" : "=f"(r) : "f"(x)); return r; }
__device__ __forceinline__ uint32_t max_bf16x2(uint32_t a, uint32_t b) {
    uint32_t r; asm("max.bf16x2 %0, %1, %2;" : "=r"(r) : "r"(a), "r"(b)); return r;
}
__device__ __forceinline__ uint4 ldsm4(uint32_t addr) {
    uint4 v;
    asm volatile("ldmatrix.sync.aligned.m8n8.x4.shared.b16 {%0,%1,%2,%3}, [%4];"
                 : "=r"(v.x), "=r"(v.y), "=r"(v.z), "=r"(v.w) : "r"(addr) : "memory");
    return v;
}
__device__ __forceinline__ uint4 ldsm4_t(uint32_t addr) {
    uint4 v;
    asm volatile("ldmatrix.sync.aligned.m8n8.x4.trans.shared.b16 {%0,%1,%2,%3}, [%4];"
                 : "=r"(v.x), "=r"(v.y), "=r"(v.z), "=r"(v.w) : "r"(addr) : "memory");
    return v;
}
__device__ __forceinline__ void mma_16816(float (&c)[4], uint32_t a0, uint32_t a1, uint32_t a2, uint32_t a3, uint32_t b0, uint32_t b1) {
    asm("mma.sync.aligned.m16n8k16.row.col.f32.bf16.bf16.f32 {%0,%1,%2,%3}, {%4,%5,%6,%7}, {%8,%9}, {%0,%1,%2,%3};"
        : "+f"(c[0]), "+f"(c[1]), "+f"(c[2]), "+f"(c[3]) : "r"(a0), "r"(a1), "r"(a2), "r"(a3), "r"(b0), "r"(b1));
}
__device__ __forceinline__ void mma_1688(float (&c)[4], uint32_t a0, uint32_t a1, uint32_t b0) {
    asm("mma.sync.aligned.m16n8k8.row.col.f32.bf16.bf16.f32 {%0,%1,%2,%3}, {%4,%5}, {%6}, {%0,%1,%2,%3};"
        : "+f"(c[0]), "+f"(c[1]), "+f"(c[2]), "+f"(c[3]) : "r"(a0), "r"(a1), "r"(b0));
}
__device__ __forceinline__ void qk_tile(float (&c)[4], const uint4& q0, const uint4& q1, const uint4& k, float init) {
    c[0] = c[1] = c[2] = c[3] = init;
    mma_16816(c, q0.x, q0.y, q0.z, q0.w, k.x, k.y);
    mma_16816(c, q1.x, q1.y, q1.z, q1.w, k.z, k.w);
}
__device__ __forceinline__ uint32_t scaled_logits(bool first, float a0, float a1, float b0, float b1) {
    return mul2_bf16x2(pack_bf16(first ? a0 : b0, first ? a1 : b1), 0x3e353e35u, 0x379e379eu);
}
template <typename T> __device__ __forceinline__ T uniform(T v) { return __shfl_sync(0xffffffffu, v, 0); }

__device__ __forceinline__ void attention(const Params& prm, uint32_t base, unsigned epoch, int grp, int warp, int lane) {
    constexpr float LOG2E = 1.4426950408889634f;
    const int g = lane >> 2, t = lane & 3;
    const bool up0 = 2 * t > g, up1 = 2 * t + 1 > g;
    const uint32_t keep = (up0 ? 0x0000ffffu : 0u) | (up1 ? 0xffff0000u : 0u);
    const uint32_t buf = base + warp * 2 * ATT_SLOT, bar = base + AUX_OFF + warp * 16;
    const uint32_t qoff = (lane & 15) * 128 + (((lane >> 4) ^ (lane & 7)) << 4);
    const uint32_t koff = 2048 + (lane & 7) * 128 + (((lane >> 3) ^ (lane & 7)) << 4);
    const uint32_t rest_bar = base + AUX_OFF + 192;
    const int col = uniform(grp * 256), first = uniform((warp / 3 * 32 + warp % 3 * 11) * 16);
    const CUtensorMap* const mqk = reinterpret_cast<const CUtensorMap*>(uniform(reinterpret_cast<uint64_t>(&prm.qk)));
    const CUtensorMap *const mv = mqk + 1, *const mo = mqk + 2;
    const uint64_t pol = stream_policy();
    const uint32_t zero = prm.zero;
    uint4 kp[2], vp[2];
    uint32_t l0[2], l1[2], m[2];
    float s[2][3][4];
    auto scores = [&](uint32_t st, int row) {
        const float before = (row & 1023) == 0 ? -5.656854e9f : 0.f;
#pragma unroll
        for (int h = 0; h < 2; h++) {
            const uint4 q0 = ldsm4(st + (qoff ^ (h * 64))), q1 = ldsm4(st + (qoff ^ (h * 64 + 32)));
            const uint4 k0 = ldsm4(st + (koff ^ (h * 64))), k1 = ldsm4(st + 1024 + (koff ^ (h * 64)));
            qk_tile(s[h][0], q0, q1, kp[h], before);
            qk_tile(s[h][1], q0, q1, k0, 0.f);
            qk_tile(s[h][2], q0, q1, k1, 0.f);
            kp[h] = k1;
        }
    };
    auto logits = [&]() {
#pragma unroll
        for (int h = 0; h < 2; h++) {
            l0[h] = scaled_logits(up0, s[h][0][0], s[h][1][2], s[h][1][0], s[h][2][2]);
            l1[h] = scaled_logits(up1, s[h][0][1], s[h][1][3], s[h][1][1], s[h][2][3]);
            m[h] = max_bf16x2(l0[h], l1[h]);
            m[h] = max_bf16x2(m[h], __shfl_xor_sync(0xffffffffu, m[h], 1));
        }
    };
    auto row_max = [&]() {
#pragma unroll
        for (int h = 0; h < 2; h++) m[h] = max_bf16x2(m[h], __shfl_xor_sync(0xffffffffu, m[h], 2));
    };
    auto next = [](uint32_t p) {
        return (0x80200400u >> (p >> 4 & 31) & 1) > (p >> 15 & 1) ? p + (64 << 16) + 0x8000 : (p + 16) & ~0x8800u;
    };
    auto exchange = [&](uint32_t st, uint32_t b, uint32_t po, uint32_t pv, uint32_t pq) {
        asm volatile("{\n.reg .pred e, p, q;\n"
            "fence.proxy.async.shared::cta;\n"
            "bar.warp.sync 0xffffffff;\n"
            "elect.sync _|e, 0xffffffff;\n"
            "setp.eq.and.b32 p, %12, 0, e;\n"
            "setp.lt.and.s32 q, %8, %13, e;\n"
            "@q mbarrier.arrive.expect_tx.shared::cta.b64 _, [%2], 6144;\n"
            "@q cp.async.bulk.tensor.3d.shared::cluster.global.mbarrier::complete_tx::bytes.L2::cache_hint [%0], [%3, {%6, %7, %14}], [%2], %15;\n"
            "@q cp.async.bulk.tensor.2d.shared::cluster.global.mbarrier::complete_tx::bytes.L2::cache_hint [%0 + 4096], [%4, {%8, %9}], [%2], %15;\n"
            "@e cp.async.bulk.wait_group.read 0;\n"
            "@p cp.async.bulk.tensor.2d.global.shared::cta.bulk_group [%5, {%10, %11}], [%1 + 6144];\n"
            "@e cp.async.bulk.commit_group;\n"
            "bar.warp.sync 0xffffffff;\n}"
            :: "r"(st), "r"(st ^ ATT_SLOT), "r"(b), "l"(mqk), "l"(mv), "l"(mo), "r"(pq >> 16), "r"(pq & 2047),
               "r"((pv >> 16) + 2 * DM), "r"(pv & 2047), "r"(po >> 16), "r"(po & 2047), "r"(po & 0x8000),
               "r"(col + 256 + 2 * DM), "r"(0), "l"(pol) : "memory");
    };
    auto publish = [&](auto pending, int part) {
        asm volatile("{\n.reg .pred e;\n.reg .u32 n;\n"
            "elect.sync _|e, 0xffffffff;\n"
            "cp.async.bulk.wait_group %2;\n"
            "@e atom.acq_rel.cta.shared.add.u32 n, [%1], 1;\n"
            "setp.eq.and.u32 e, n, 11, e;\n"
            "@e red.release.gpu.global.add.u32 [%0], 1;\n}"
            :: "l"(prm.flags + F_O * 512 + part * 32), "r"(rest_bar + 8 + part * 4), "n"(pending.value) : "memory");
    };
    if (elect_one()) {
        mbar_init(bar, 1); mbar_init(bar + 8, 1);
        if (warp == 2) { mbar_init(rest_bar, 32); sts64f(rest_bar + 8, 0.f, 0.f); }
        asm volatile("fence.mbarrier_init.release.cluster;" ::: "memory");
        if (warp == 9) {
            prefetch_map(mqk); prefetch_map(mv); prefetch_map(mo);
            flag_wait(prm.flags + F_QKV * 512 + grp * 32, epoch * CNT_QKV);
        }
    }
    __syncthreads();
    if (elect_one()) {
        fence_proxy_async();
        mbar_expect_tx(bar + 8, 8192);
        tma_3d(buf + ATT_SLOT, mqk, bar + 8, col, first, 0, pol);
        tma_2d(buf + ATT_SLOT + 4096, mv, bar + 8, col + 2 * DM, first - 16, pol);
        tma_2d(buf + ATT_SLOT + 6144, mv, bar + 8, col + DM, first - 16, pol);
        mbar_expect_tx(bar, 6144);
        tma_3d(buf, mqk, bar, col, first + 16, 0, pol);
        tma_2d(buf + 4096, mv, bar, col + 2 * DM, first, pol);
        if (warp == 0) TRACE(9);
        if (warp == 9) prm.epoch[blockIdx.x * 16] = epoch;
    }
    __syncwarp();
    if (warp == 11 && lane < 4) flag_add(prm.flags + F_EARLY * 512 + (grp * 4 + lane) * 32);
    mbar_wait(bar + 8, 0);
#pragma unroll
    for (int h = 0; h < 2; h++) {
        kp[h] = ldsm4(buf + ATT_SLOT + 5120 + (koff ^ (h * 64)));
        vp[h] = ldsm4_t(buf + ATT_SLOT + 3072 + (koff ^ (h * 64)));
    }
    scores(buf + ATT_SLOT, first);
    uint32_t pm = 0x8000, p0 = col << 16 | first, p1 = p0 + 16, p2 = p0 + 32, p3 = p0 + 48;
    exchange(buf + ATT_SLOT, bar + 8, pm, p1, p2);
    logits();
    row_max();
    uint32_t st = buf, b = bar, cnt = 1;
    const uint32_t relay = warp == 2 ? 7 : 0;
    bool ready = false;
#pragma unroll 1
    while (p0 >> 16 < col + 256) {
        uint32_t pa[2], pb[2];
        if (!ready) mbar_wait(b, (cnt >> 1) & 1);
        uint4 v[2][2];
#pragma unroll
        for (int h = 0; h < 2; h++) {
            const float ma = -LOG2E * bf_lo(m[h]), mb = -LOG2E * bf_hi(m[h]);
            const float a0 = ex2_fast(fmaf(bf_lo(l0[h]), LOG2E, ma)), a1 = ex2_fast(fmaf(bf_lo(l1[h]), LOG2E, ma));
            const float b0 = ex2_fast(fmaf(bf_hi(l0[h]), LOG2E, mb)), b1 = ex2_fast(fmaf(bf_hi(l1[h]), LOG2E, mb));
            float sum[4] = {0.f, 0.f, 0.f, 0.f};
            mma_1688(sum, pack_bf16(a0, a1), pack_bf16(b0, b1), 0x3f803f80u);
            const float ra = rcp_fast(sum[0]), rb = rcp_fast(sum[2]);
            pa[h] = pack_bf16(a0 * ra, a1 * ra);
            pb[h] = pack_bf16(b0 * rb, b1 * rb);
        }
        scores(st, p1);
#pragma unroll
        for (int h = 0; h < 2; h++) {
            v[h][0] = ldsm4_t(st + 4096 + (qoff ^ (h * 64)));
            v[h][1] = ldsm4_t(st + 4096 + (qoff ^ (h * 64 + 32)));
        }
        if (cnt == relay) {
            flag_wait<true>(prm.flags + F_QKV * 512 + 128 + grp * 32, epoch * CNT_QKV);
            fence_proxy_async();
            mbar_arrive(rest_bar);
        }
        if (cnt == 8) {
#pragma unroll 1
            for (int spins = 0; !__all_sync(0xffffffffu, mbar_try_wait(rest_bar, 0)) && spins < (1 << 17); spins++) {}
        }
        if (cnt == 37) publish(std::integral_constant<int, 1>(), 0);
        exchange(st, b, pm, p2, p3);
        pm = p0; p0 = p1; p1 = p2; p2 = p3; p3 = next(p3);
        logits();
        float o[2][4][4];
#pragma unroll
        for (int h = 0; h < 2; h++) {
            const uint32_t prev[4] = {vp[h].x, vp[h].y, vp[h].z, vp[h].w};
            const uint32_t own[8] = {v[h][0].x, v[h][0].y, v[h][0].z, v[h][0].w, v[h][1].x, v[h][1].y, v[h][1].z, v[h][1].w};
            const uint32_t a0 = pa[h] & keep, a1 = pa[h] & ~keep, a2 = pb[h] & keep, a3 = pb[h] & ~keep;
            const uint32_t z0 = pa[h] & zero, z1 = pb[h] & zero;
#pragma unroll
            for (int j = 0; j < 4; j++) {
                o[h][j][0] = o[h][j][1] = o[h][j][2] = o[h][j][3] = 0.f;
                mma_1688(o[h][j], a0, z0, prev[j]);
                mma_16816(o[h][j], a1, a2, z1, a3, own[2 * j], own[2 * j + 1]);
            }
            vp[h] = make_uint4(own[1], own[3], own[5], own[7]);
        }
        row_max();
        b ^= 8; cnt++;
        ready = mbar_test(b, (cnt >> 1) & 1);
#pragma unroll
        for (int h = 0; h < 2; h++) {
#pragma unroll
            for (int d = 0; d < 2; d++)
                asm volatile("stmatrix.sync.aligned.m8n8.x4.shared.b16 [%0], {%1,%2,%3,%4};"
                             :: "r"(st + 6144 + (qoff ^ (h * 64 + d * 32))),
                                "r"(pack_bf16(o[h][2 * d][0], o[h][2 * d][1])), "r"(pack_bf16(o[h][2 * d][2], o[h][2 * d][3])),
                                "r"(pack_bf16(o[h][2 * d + 1][0], o[h][2 * d + 1][1])),
                                "r"(pack_bf16(o[h][2 * d + 1][2], o[h][2 * d + 1][3])) : "memory");
        }
        st ^= ATT_SLOT;
    }
    exchange(st, b, pm, p0, p0);
    publish(std::integral_constant<int, 0>(), 1);
    if (threadIdx.x == 0) { TRACE(10); TRACE_DUMP(); }
}

__device__ __forceinline__ void tail_gemm(const Params& prm, uint32_t base, uint32_t tag, int grp, int warp, int lane) {
    const uint32_t full = base + BAR_OFF, empty = full + 32, sum_bar = full + 320, colsum = full + 512;
    if (warp == 8) {
        if (elect_one()) {
            if (TDELAY) __nanosleep(TDELAY);
#pragma unroll 1
            for (int i = 0; i < 32; i++) {
                const uint32_t dst = base + (i & 3) * G1_STAGE_BYTES, bar = full + (i & 3) * 8;
                mbar_wait(bar + 32, ~i >> 2 & 1);
                mbar_expect_tx(bar, G1_STAGE_BYTES);
                tma_2d(dst, &prm.x, bar, (i & 15) * 64, grp * 512 + (i >> 4) * 256, stream_policy());
                tma_2d(dst + 16384, &prm.x, bar, (i & 15) * 64, grp * 512 + (i >> 4) * 256 + 128, stream_policy());
                tma_3d(dst + 32768, &prm.wtail, bar, 0, (i & 15) * 64, 0, stream_policy());
            }
        }
    } else if (warp >= 10) {
        float cs[8];
#pragma unroll
        for (int d = 0; d < 8; d++) cs[d] = 0.f;
        const uint32_t wa = base + 32768 + (warp - 10) * 8192 + (lane >> 3) * 2048 + (lane & 7) * 16;
#pragma unroll 1
        for (int i = 0; i < 28; i++) {
            mbar_wait(full + (i & 3) * 8, i >> 2 & 1);
            if (i < 16) {
#pragma unroll
                for (int j = 0; j < 16; j++) {
                    float f[8];
                    unpack8(lds128((wa ^ (j & 1) * 16) + (i & 3) * G1_STAGE_BYTES + j * 128), f);
#pragma unroll
                    for (int d = 0; d < 8; d++) cs[d] += f[d];
                }
            }
            if (i == 15) {
#pragma unroll
                for (int d = 0; d < 8; d++) {
                    cs[d] += __shfl_xor_sync(0xffffffffu, cs[d], 2);
                    cs[d] += __shfl_xor_sync(0xffffffffu, cs[d], 4);
                }
#pragma unroll
                for (int d = 0; d < 8; d += 2)
                    sts64f(colsum + (warp - 10) * 256 + (lane >> 3) * 64 + (lane & 1) * 32 + d * 4, cs[d], cs[d + 1]);
            }
            __syncwarp();
            if (lane == 0) {
                mbar_arrive(empty + (i & 3) * 8);
                if (i == 15) mbar_arrive(sum_bar);
            }
        }
    } else if (warp < 8) {
        const uint32_t da = desc_a(base + (warp >> 2) * 16384);
#pragma unroll 1
        for (int pass = 0; pass < 2; pass++) {
            const int mblk = grp * 4 + pass * 2 + (warp >> 2);
            const float2* const sp = prm.stats + mblk * 128 + (warp & 3) * 16 + (lane >> 2);
            uint2 st[4] = {};
            auto fetch_stats = [&]() {
                bool missing = false;
#pragma unroll
                for (int r = 0; r < 4; r++) {
                    if (((st[r].x ^ tag) | (st[r].y ^ tag)) & 3) {
                        missing = true;
                        asm volatile("ld.relaxed.gpu.global.v2.b32 {%0,%1}, [%2];"
                                     : "=r"(st[r].x), "=r"(st[r].y) : "l"(sp + r / 2 * 64 + r % 2 * 8) : "memory");
                    }
                }
                return missing;
            };
            float acc[2][64];
#pragma unroll
            for (int i = 0; i < 64; i++) acc[0][i] = acc[1][i] = 0.f;
#pragma unroll 1
            for (int k = 0; k < G1_KSTEPS; k++) {
                mbar_wait(full + (k & 3) * 8, k >> 2 & 1);
                mma_step_tail(acc[0], da, base + 32768, (k & 3) * (G1_STAGE_BYTES / 16));
                mma_step_tail(acc[1], da + 512, base + 32768, (k & 3) * (G1_STAGE_BYTES / 16));
                wg_wait<2>();
                if (k > 0 && (threadIdx.x & 127) == 0) mbar_arrive(empty + (k - 1 & 3) * 8);
                if (k == 13) fetch_stats();
            }
#pragma unroll 1
            for (int spins = 0; fetch_stats() && spins < (1 << 16); spins++) {}
            mbar_wait(sum_bar, 0);
            wg_wait<0>();
            fence_regs(acc[0]); fence_regs(acc[1]);
            if ((threadIdx.x & 127) == 0) mbar_arrive(empty + 24);
#pragma unroll
            for (int q = 0; q < 8; q++) {
                const float2 c0 = lds64f(colsum + q * 64 + (lane & 3) * 8), c1 = lds64f(colsum + q * 64 + 32 + (lane & 3) * 8);
                uint32_t v[8];
#pragma unroll
                for (int r = 0; r < 4; r++) {
                    const float* a = acc[r / 2] + 8 * q + r % 2 * 2;
                    const float shift = __uint_as_float(st[r].x ^ tag), inv = __uint_as_float(st[r].y ^ tag);
                    v[2 * r] = pack_bf16(fmaf(shift, c0.x, a[0]) * inv, fmaf(shift, c0.y, a[1]) * inv);
                    v[2 * r + 1] = pack_bf16(fmaf(shift, c1.x, a[4]) * inv, fmaf(shift, c1.y, a[5]) * inv);
                }
                uint4* const p = prm.tail + (q * 16 + mblk) * 256 + (threadIdx.x & 127);
                p[0] = make_uint4(v[0], v[1], v[2], v[3]);
                p[128] = make_uint4(v[4], v[5], v[6], v[7]);
            }
        }
    }
}

__device__ __forceinline__ bool tile_is_qkv(int nt) { return nt < 4 || (nt >= 8 && nt < 16); }
__device__ __forceinline__ int tile_index(int nt) { return nt < 4 ? nt + 8 : (nt < 8 ? nt - 4 : (nt < 16 ? nt - 8 : nt - 12)); }

struct Role {
    int rank, role, mblk, nslot, w0_col;
    const CUtensorMap* w0;
    __device__ __forceinline__ Role(const Params& prm) {
        uint32_t id;
        asm volatile("mov.u32 %0, %%ctaid.x;" : "=r"(id));
        const uint32_t cl = id / 2;
        rank = id & 1;
        role = pick(cl < 4, 32 + cl * 8, cl - 8 + max(4u, (cl - 1) * 37 >> 8)) * 2 + rank;
        mblk = role & 15; nslot = role >> 4;
        w0 = &prm.wqkv + pick(nslot < 4, 0, 1 + rank);
        w0_col = pick(nslot < 4, 32 + nslot * 4 + rank * 2, nslot * 2 - 8);
    }
};

__global__ void __cluster_dims__(2, 1, 1) __launch_bounds__(384, 1)
fused_kernel(const __grid_constant__ Params prm) {
    TRACE_GET(c0);
    const uint32_t base = smem_u32(smem_raw) & ~1023u;
    const uint32_t bars = base + BAR_OFF;
    auto full1 = [&](int s) { return bars + s * 8; };
    auto empty1 = [&](int s) { return bars + 32 + s * 8; };
    auto full2 = [&](int s) { return bars + 64 + s * 8; };
    auto empty2 = [&](int s) { return bars + 128 + s * 8; };
    const uint32_t sig_bar = bars + 192, dep_bar = bars + 256, cs_bar = bars + 304, fold_bar = bars + 320, x_bar = bars + 352;
    const uint32_t stats = bars + 1536;
    auto stage2 = [&](int q) { return base + q * G2_STAGE_BYTES; };
    const uint32_t aux = base + AUX_OFF;

    asm volatile("{\n.reg .pred p;\nsetp.eq.u32 p, %1, 0;\n@p mbarrier.init.shared::cta.b64 [%0], 1;\n"
        "fence.mbarrier_init.release.cluster;\nbarrier.cluster.arrive.relaxed.aligned;\n}" :: "r"(bars), "r"(threadIdx.x) : "memory");
    const int warp = __shfl_sync(0xffffffffu, threadIdx.x >> 5, 0);
    auto cluster_wait = []() { asm volatile("barrier.cluster.wait.acquire.aligned;" ::: "memory"); };
    if ((warp | (blockIdx.x & NGEMM)) == 8) {
        const Role r(prm);
        asm volatile("{\n.reg .pred e;\nelect.sync _|e, 0xffffffff;\n"
            "@e prefetch.tensormap [%0];\n@e prefetch.tensormap [%1];\n}" :: "l"(&prm.x), "l"(r.w0) : "memory");
        cluster_wait();
        load_stage1(base, base + A_BYTES + r.rank * 16384, full1(0), &prm.x, r.w0, 0, r.mblk * 128, r.w0_col, 0, stream_policy());
    } else {
        cluster_wait();
    }
    const uint32_t t0 = clock();
    asm volatile("{\n.reg .pred e, q;\nelect.sync _|e, 0xffffffff;\nsetp.ne.and.u32 q, %2, 0, e;\n"
        "@q mbarrier.init.shared::cta.b64 [%0], %1;\n@e mbarrier.init.shared::cta.b64 [%0 + 8], %1;\n"
        "@e mbarrier.init.shared::cta.b64 [%0 + 16], %1;\n@e mbarrier.init.shared::cta.b64 [%0 + 24], %1;\n"
        "fence.mbarrier_init.release.cluster;\nbarrier.cluster.arrive.relaxed.aligned;\n}"
        :: "r"(bars + warp * 32), "r"(1 << (0x10fa08 >> warp * 2 & 3)), "r"(warp) : "memory");
    const int lane = threadIdx.x & 31;
    const Role me(prm);
    const int rank = me.rank, role = me.role, mblk = me.mblk, nslot = me.nslot, w0_col = me.w0_col;
    const CUtensorMap* const w0 = me.w0;

    if (blockIdx.x >= NGEMM) {
        if (warp == 9) { TRACE_CLEAR(); TRACE_GT(0); TRACE_PUT(1, c0); }
        const unsigned epoch = __ldcg(prm.epoch + blockIdx.x * 16) + 1;
        cluster_wait();
        if (TAIL) tail_gemm(prm, base, 1 + (epoch & 1), blockIdx.x - NGEMM, warp, lane);
        uint32_t tid;
        asm volatile("mov.u32 %0, %%tid.x;" : "=r"(tid));
        attention(prm, (base + 2 * ATT_SLOT - 1) & ~(2u * ATT_SLOT - 1), epoch, blockIdx.x - NGEMM, uniform(tid >> 5), tid & 31);
    } else if (warp < 8) {
        asm volatile("setmaxnreg.inc.sync.aligned.u32 %0;" :: "n"(CONSUMER_REGS));
        const int wg = __shfl_sync(0xffffffffu, threadIdx.x >> 7, 0);
        const int cw = threadIdx.x >> 5;
        const int tid = threadIdx.x & 127;
        float acc[128];
        uint32_t pk[64];
#pragma unroll
        for (int i = 0; i < 64; i++) asm volatile("mov.b32 %0, 0;" : "=r"(pk[i]));
#pragma unroll
        for (int i = 0; i < 128; i++) asm volatile("mov.b32 %0, 0;" : "=f"(acc[i]));
        cluster_wait();

        const int orow = ((lane >> 2) & 1) * (SEQ / 2) + mblk * 64 + cw * 8 + (lane >> 3);
        __nv_bfloat16* optr = prm.pxn + (mblk * 128 + nslot * 16 + cw * 2) * DM + lane * 8;
        const uint32_t da = desc_a(base + wg * 8192), db = desc_b(base + A_BYTES);
        auto release = [&](uint32_t bar) { if (tid < 2) mbar_arrive_cluster(bar, tid); };
        auto store_pk = [&](__nv_bfloat16* p, int j) {
            asm volatile("st.global.v4.u32 [%0], {%1,%2,%3,%4};"
                         :: "l"(p), "r"(pk[4 * j]), "r"(pk[4 * j + 1]), "r"(pk[4 * j + 2]), "r"(pk[4 * j + 3]) : "memory");
        };
        auto chunk_geglu = [&](int j) {
#pragma unroll
            for (int i = 4 * j; i < 4 * j + 4; i++) pk[i] = geglu2(pk[i], pk[32 + i]);
            store_pk(optr + (j & 1) * 4 * K2 + (j >> 1) * 32, j);
        };
        auto chunk_qkv = [&](int c) {
            store_pk(optr + c * 32, 2 * c);
            store_pk(optr + 4 * NQKV + c * 32, 2 * c + 1);
        };
        auto signal_stores = [&](int p) { __syncwarp(); if (lane == 0) mbar_arrive(sig_bar + p * 8); };

        auto chunk_ln = [&](int k) {
            float* const mo = reinterpret_cast<float*>(pk + 32);
            if (k == LNL) {
                const uint4* xp = reinterpret_cast<const uint4*>(prm.px + (optr - prm.pxn));
                pk[38] = __ldcg(prm.epoch + blockIdx.x * 16 + 2);
#pragma unroll
                for (int i = 0; i < 8; i++) {
                    const uint4 v = ldg_stream(xp + i * 32, stream_policy());
                    pk[4 * i] = v.x; pk[4 * i + 1] = v.y; pk[4 * i + 2] = v.z; pk[4 * i + 3] = v.w;
                }
            } else if (k >= LN_STEP && k < LN_STEP + 3) {
                if (k == LN_STEP) {
                    mo[0] = bf_lo(uniform(pk[0])); mo[1] = bf_lo(uniform(pk[16]));
                    mo[2] = mo[3] = mo[4] = mo[5] = 0.f;
                }
#pragma unroll
                for (int i = (k - LN_STEP) * 11; i < (k - LN_STEP) * 11 + 11 && i < 32; i++) {
                    const int r = i & 1;
                    const uint32_t w = pk[r * 16 + i / 2];
                    const float lo = bf_lo(w) - mo[r], hi = bf_hi(w) - mo[r];
                    mo[2 + r] += lo + hi;
                    mo[4 + r] = fmaf(hi, hi, fmaf(lo, lo, mo[4 + r]));
                }
            } else if (k == LN_STEP + 3) {
                const bool second = lane & 16;
                float m1 = (second ? mo[3] : mo[2]) + __shfl_xor_sync(0xffffffffu, second ? mo[2] : mo[3], 16);
                float m2 = (second ? mo[5] : mo[4]) + __shfl_xor_sync(0xffffffffu, second ? mo[4] : mo[5], 16);
#pragma unroll
                for (int o = 8; o > 0; o >>= 1) {
                    m1 += __shfl_xor_sync(0xffffffffu, m1, o);
                    m2 += __shfl_xor_sync(0xffffffffu, m2, o);
                }
                m1 *= 1.f / DM;
                const float var = fmaxf(fmaf(-m1, m1, m2 * (1.f / DM)), 0.f);
                const float mean = round_bf16((second ? mo[1] : mo[0]) + m1);
                const float inv = rcp_fast(round_bf16(sqrt_fast(round_bf16(round_bf16(var) + 1e-5f))));
                if ((lane & 15) == 0) st_tagged(prm.stats + (uint32_t)(optr - prm.pxn) / DM + second, -mean, inv, 2 - (pk[38] & 1));
                const uint32_t split = pack_bf16(inv - round_bf16(inv), inv);
#pragma unroll
                for (int r = 0; r < 2; r++) {
                    const uint32_t f = __shfl_sync(0xffffffffu, split, r * 16);
                    pk[32 + 3 * r] = __byte_perm(__shfl_sync(0xffffffffu, __float_as_uint(mean), r * 16), 0, 0x3232);
                    pk[33 + 3 * r] = __byte_perm(f, 0, 0x3232);
                    pk[34 + 3 * r] = __byte_perm(f, 0, 0x1010);
                }
            } else if (k >= LN_STEP + 4 && k < LN_STEP + 8) {
#pragma unroll
                for (int i = k - LN_STEP - 4; i < 8; i += 4) {
                    const uint32_t* n = pk + 32 + i / 4 * 3;
#pragma unroll
                    for (int j = 4 * i; j < 4 * i + 4; j++) pk[j] = mul2_bf16x2(sub_bf16x2(pk[j], n[0]), n[1], n[2]);
                    store_pk(optr + i * 256, i);
                }
                if (k == LN_STEP + 5 || k == LN_STEP + 7) signal_stores(k == LN_STEP + 5 ? 0 : 7);
            } else if (k == FOLD_STEP) {
                mbar_wait(fold_bar, 0);
                const uint32_t sp = stats + (cw * 16 + (lane >> 2)) * 8;
                const uint32_t sel = lane & 2 ? 0x4444 : (lane & 1 ? 0x4432 : 0x3232);
                const float2 sa = lds64f(sp), sb = lds64f(sp + 64);
                mma_rank(acc, __byte_perm(__float_as_uint(sa.x), 0, sel), __byte_perm(__float_as_uint(sb.x), 0, sel), desc_b(aux));
                mo[0] = sa.y; mo[1] = sb.y;
            }
        };

        bool gated = false;
        TRACE_SLOT(tile_slot, 16 + wg * 8);
#pragma unroll 1
        for (int t = 0; t < G1_TILES; t++) {
#pragma unroll
            for (int k = 0; k < G1_KSTEPS; k++) {
                const int s = k & 3;
                TRACE_STEP(t, k, 0);
                mbar_wait(full1(s), (k >> 2) & 1);
                if (k == 0) TRACE_S(12, t, 0);
                TRACE_STEP(t, k, 1);
                if (wg == 1 && k == G1_KSTEPS - (t ? G1_SKEW : SK0)) asm volatile("bar.sync 1, 256;" ::: "memory");
                if (TAIL && t == G1_TILES - 1) mma_step240(acc, da, db, s * G1_STAGE_BYTES / 16, k);
                else mma_step(acc, da, db, s * G1_STAGE_BYTES / 16, k);
                if (wg == 0 && k == G1_KSTEPS - 1) asm volatile("bar.arrive 1, 256;" ::: "memory");
                wg_wait<1>();
                if (k > 0) release(empty1((k - 1) & 3));
                TRACE_STEP(t, k, 2);
                if (t == 0) chunk_ln(k);
                if (k >= 1 && k <= 8 && gated) {
                    chunk_geglu(k - 1);
                    if (k == 8) signal_stores(t == 1 ? 1 : t + 1);
                }
                if (t != 0 && !gated) {
                    if (k == 0) { chunk_qkv(0); chunk_qkv(1); }
                    if (k >= 6 && k <= 11) chunk_qkv(k - 4);
                    if ((k == 0 || k == 11) && t == 2) signal_stores(k ? 3 : 2);
                }
                if (k == 12) {
                    const int nt = t * 8 + nslot;
                    gated = !tile_is_qkv(nt);
                    optr = !gated ? prm.qkv + (size_t)orow * NQKV + tile_index(nt) * 256 + (lane & 3) * 8
                                  : prm.pa2 + (size_t)orow * K2 + DM + tile_index(nt) * 128 + (lane & 3) * 8;
                    asm volatile("" : "+l"(optr));
                }
            }
            wg_wait<0>();
            fence_regs(acc);
            release(empty1(3));
            if (t == 0) {
#pragma unroll
                for (int i = 0; i < 128; i++) acc[i] *= __uint_as_float(pk[32 + i / 2 % 2]);
                fence_regs(acc);
            }
#pragma unroll
            for (int i = 0; i < 64; i++) {
                const int e = (i & ~7) * 2 + (i & 3) * 4 + (i & 4) / 2;
                pk[i] = pack_bf16(acc[e], acc[e + 1]);
            }
            TRACE_NEXT(tile_slot);
        }

        float accd[64], accs[64];
#pragma unroll
        for (int i = 0; i < 64; i++) accd[i] = 0.f;
#pragma unroll
        for (int u = 0; u < 9; u++) {
            const int q = u % G2_STAGES;
            mbar_wait(full2(q), (u / G2_STAGES) & 1);
            mma_step(accd, da, db, q * G2_STAGE_BYTES / 16, u);
            wg_wait<1>();
            if (u > 0) release(empty2((u - 1) % G2_STAGES));
            if (TAIL && u == 0) {
                const uint4 v = ldg_stream(prm.tail + role * 256 + threadIdx.x, stream_policy());
                pk[58] = v.x; pk[59] = v.y; pk[62] = v.z; pk[63] = v.w;
            }
            if (u >= 1) { chunk_geglu(u - 1); if (u == 8) signal_stores(6); }
        }
        {
            int q = 9 % G2_STAGES, qp = 8 % G2_STAGES; uint32_t ph = (9 / G2_STAGES) & 1;
#pragma unroll 1
            for (int u = 9; u < G2_DSTEPS; u++) {
                mbar_wait(full2(q), ph);
                mma_step(accd, da, db, q * (G2_STAGE_BYTES / 16), 1);
                wg_wait<1>();
                release(empty2(qp));
                qp = q;
                if (++q == G2_STAGES) { q = 0; ph ^= 1; }
            }
        }
        TRACE_NEXT(tile_slot);
#pragma unroll
        for (int i = 0; i < 64; i++) accs[i] = 0.f;
        uint32_t gk[32], xr[32];
        const uint32_t xs = aux + cw * 2048;
        const uint32_t xrow = xs + ((lane & 7) + ((lane >> 3) & 1) * 8) * 128;
        auto xaddr = [&](int j) { return xrow + (j >> 2) * 16384 + (((((j & 3) * 2) + (lane >> 4)) ^ (lane & 7)) << 4); };
#pragma unroll
        for (int u = G2_DSTEPS; u < G2_KSTEPS; u++) {
            const int q = u % G2_STAGES, v = u - G2_DSTEPS;
            mbar_wait(full2(q), (u / G2_STAGES) & 1);
            if (G2_SKEW > 0 && wg == 1 && u == G2_KSTEPS - G2_SKEW) asm volatile("bar.sync 1, 256;" ::: "memory");
            mma_step(accs, da, db, q * G2_STAGE_BYTES / 16, v);
            if (G2_SKEW > 0 && wg == 0 && u == G2_KSTEPS - 1) asm volatile("bar.arrive 1, 256;" ::: "memory");
            if (SV & 1) {
                wg_wait<1>();
                if (u - 1 + G2_STAGES < G2_KSTEPS) release(empty2((u - 1) % G2_STAGES));
                if (v <= 8) fence_regs(accd);
            }
            if (v >= 1 && v <= 8) {
#pragma unroll
                for (int i = 4 * (v - 1); i < 4 * v; i++) {
                    const uint32_t d2 = pack_bf16(accd[2 * i], accd[2 * i + 1]);
                    gk[i] = pack_bf16(silu(bf_lo(d2)), silu(bf_hi(d2)));
                }
            }
            if (v == 9) mbar_wait(x_bar, 0);
            if (v >= 9 && v <= 12) {
#pragma unroll
                for (int j = 2 * (v - 9); j < 2 * (v - 8); j++)
                    asm volatile("ldmatrix.sync.aligned.m8n8.x4.shared.b16 {%0,%1,%2,%3}, [%4];"
                                 : "=r"(xr[4 * j]), "=r"(xr[4 * j + 1]), "=r"(xr[4 * j + 2]), "=r"(xr[4 * j + 3])
                                 : "r"(xaddr(j)) : "memory");
            }
            if (!(SV & 1)) {
                wg_wait<1>();
                if (v == 0) fence_regs(accd);
                if (u - 1 + G2_STAGES < G2_KSTEPS) release(empty2((u - 1) % G2_STAGES));
            }
        }
        wg_wait<0>();
        fence_regs(accs);
        TRACE_NEXT(tile_slot);
#pragma unroll
        for (int j = 0; j < 8; j++) {
            uint32_t r[4];
#pragma unroll
            for (int i = 0; i < 4; i++) {
                const int e = j * 4 + i;
                r[i] = add_bf16x2(xr[e], mul_bf16x2(pack_bf16(accs[2 * e], accs[2 * e + 1]), gk[e]));
            }
            asm volatile("stmatrix.sync.aligned.m8n8.x4.shared.b16 [%0], {%1,%2,%3,%4};"
                         :: "r"(xaddr(j)), "r"(r[0]), "r"(r[1]), "r"(r[2]), "r"(r[3]) : "memory");
            if (j == 3 || j == 7) {
                asm volatile("fence.proxy.async.shared::cta;" ::: "memory");
                __syncwarp();
                if (lane == 0) {
                    tma_store_2d(&prm.out, xs + (j >> 2) * 16384, nslot * 128 + (j >> 2) * 64, mblk * 128 + cw * 16);
                    asm volatile("cp.async.bulk.commit_group;" ::: "memory");
                }
            }
        }
        if (lane == 0) asm volatile("cp.async.bulk.wait_group.read 0;" ::: "memory");
        if (tid == 0) { TRACE_NEXT(tile_slot); if (wg == 1) TRACE_GT(13); TRACE_DUMP(); }
    } else {
        asm volatile("setmaxnreg.dec.sync.aligned.u32 %0;" :: "n"(AUX_REGS));
        cluster_wait();
        unsigned* const flags = prm.flags + mblk * 32;
        if (warp == 9) {
            TRACE_CLEAR(); TRACE_GT(0); TRACE(60);
            if (lane == 0) {
                const unsigned epoch = __ldcg(prm.epoch + blockIdx.x * 16 + 2) + 1;
                mbar_wait(sig_bar, 0);
                TRACE(11);
                flag_add(flags + F_LN * 512);
                TRACE(42);
                flag_wait(flags + F_LN * 512, epoch * CNT_LN);
                fence_proxy_async();
                mbar_arrive(dep_bar);
                mbar_wait(sig_bar + 56, 0);
                flag_add(flags + F_LN2 * 512);
                flag_wait(flags + F_LN2 * 512, epoch * CNT_LN);
                fence_proxy_async();
                mbar_arrive(dep_bar + 40);
                TRACE(59);
                prm.epoch[blockIdx.x * 16 + 2] = epoch;
                for (int p = nslot < 4 ? 2 : 1; p < 7; p++) {
                    mbar_wait(sig_bar + p * 8, 0);
                    if (p == 2) TRACE(37);
                    flag_add(p == 2 || p == 3 ? prm.flags + F_QKV * 512 + (p * 4 - 8 + (nslot & 3)) * 32
                                              : flags + (p < 6 ? F_EARLY : F_LATE) * 512);
                    if (p == 2) TRACE(43);
                }
            }
        } else if (warp > 9) {
            const int w = warp - 10;
            const unsigned epoch = __ldcg(prm.epoch + blockIdx.x * 16 + w) + 1;
            const uint32_t tag = 1 + (epoch & 1);
                const uint32_t at = (w ? CB : CA) >> (CIDX) * 4 & 15;
            mbar_wait(empty1(at & 3), 0);
            mbar_wait(empty1(at & 3), at >> 3);
            if (elect_one()) {
                mbar_expect_tx(cs_bar + w * 8, 16384);
                if (CKEEP) asm volatile("cp.async.bulk.tensor.3d.shared::cluster.global.mbarrier::complete_tx::bytes [%0], [%1, {%3, %4, %5}], [%2];"
                    :: "r"(aux + w * 16384), "l"(w0), "r"(cs_bar + w * 8), "r"(0), "r"(((mblk & ~1) + w) * 64), "r"(w0_col) : "memory");
                else tma_3d(aux + w * 16384, w0, cs_bar + w * 8, 0, ((mblk & ~1) + w) * 64, w0_col, stream_policy());
            }
            float cs[8];
#pragma unroll
            for (int d = 0; d < 8; d++) cs[d] = 0.f;
            const uint32_t wa = aux + w * 8192 + (lane >> 3) * 128 + (((lane & 7) ^ (lane >> 3)) << 4);
            uint4 v[9];
            auto fetch = [&](int h, uint32_t off) {
#pragma unroll
                for (int j = 0; j < 4; j++) v[h * 4 + j] = lds128((wa ^ (j & 1) * 64) + off + h * 2048 + j * 512);
            };
            auto add = [&](int h) {
#pragma unroll
                for (int j = 0; j < 4; j++) {
                    float f[8];
                    unpack8(v[h * 4 + j], f);
#pragma unroll
                    for (int d = 0; d < 8; d++) cs[d] += f[d];
                }
            };
            if (CST) { mbar_wait(empty1(CST & 3), 0); mbar_wait(empty1(CST & 3), CST >> 3); }
            mbar_wait(cs_bar, 0);

            fetch(0, 0);
#pragma unroll 1
            for (int i = 0; i < 4; i++) {
                fetch(1, (i >> 1) * 16384 + (i & 1) * 4096);
                add(0);
                if (i == 1) mbar_wait(cs_bar + 8, 0);
                fetch(0, (i + 1 & 2) * 8192 + (~i & 1) * 4096);
                add(1);
            }
#pragma unroll
            for (int d = 0; d < 4; d++)
                cs[d] = (lane & 16 ? cs[d + 4] : cs[d]) + __shfl_xor_sync(0xffffffffu, lane & 16 ? cs[d] : cs[d + 4], 16);
#pragma unroll
            for (int d = 0; d < 2; d++)
                cs[d] = (lane & 8 ? cs[d + 2] : cs[d]) + __shfl_xor_sync(0xffffffffu, lane & 8 ? cs[d] : cs[d + 2], 8);
            st_tagged(prm.colsum + (nslot * 2 + rank) * 1024 + (mblk >> 1) * 128 + w * 64 + (lane & 7) * 8 + (lane >> 3) * 2,
                      cs[0], cs[1], tag);

#pragma unroll
            for (int m = 0; m < 9; m++) v[m] = make_uint4(0, 0, 0, 0);
            const float* parts = prm.colsum + (nslot * 2 + (lane >> 4)) * 1024 + w * 64 + (lane & 15) * 4;
            const float* const rows = &prm.stats[mblk * 128 + w * 64 + lane * 2].x;
#pragma unroll 1
            for (int spins = 0; spins < (1 << 16); spins++) {
                bool missing = false;
                asm volatile("" : "+l"(parts));
#pragma unroll
                for (int m = 0; m < 9; m++) {
                    if (untagged(v[m], tag)) {
                        missing = true;
                        v[m] = ld_relaxed(m < 8 ? parts + m * 128 : rows);
                    }
                }
                if (!missing) break;
            }
            float4 c = make_float4(0.f, 0.f, 0.f, 0.f);
#pragma unroll
            for (int m = 0; m < 8; m++) {
                c.x += __uint_as_float(v[m].x ^ tag); c.y += __uint_as_float(v[m].y ^ tag);
                c.z += __uint_as_float(v[m].z ^ tag); c.w += __uint_as_float(v[m].w ^ tag);
            }
            sts128(stats + w * 512 + lane * 16, make_uint4(v[8].x ^ tag, v[8].y ^ tag, v[8].z ^ tag, v[8].w ^ tag));
            const uint32_t ca = aux + w * 8192 + (lane >> 4) * 16384 + (lane & 15) * 8;
#pragma unroll
            for (int r = 0; r < 3; r++) {
                const uint32_t lo = pack_bf16(c.x, c.y), hi = pack_bf16(c.z, c.w);
                sts64f((ca ^ r * 16) + r * 128, __uint_as_float(lo), __uint_as_float(hi));
                c.x -= bf_lo(lo); c.y -= bf_hi(lo); c.z -= bf_lo(hi); c.w -= bf_hi(hi);
            }
            asm volatile("fence.proxy.async.shared::cta;" ::: "memory");
            __syncwarp();
            if (lane == 0) {
                mbar_arrive(fold_bar);
                prm.epoch[blockIdx.x * 16 + w] = epoch;
                if (w == 0) {
                    TRACE_S(35, w, 0);
                    flag_wait(flags + F_EARLY * 512, epoch * CNT_EARLY);
                    fence_proxy_async(); mbar_arrive(dep_bar + 8);
                    flag_wait(flags + F_LATE * 512, epoch * CNT_LATE);
                    fence_proxy_async(); mbar_arrive(dep_bar + 16);
                    flag_wait(prm.flags + F_O * 512, epoch * CNT_O);
                    fence_proxy_async(); mbar_arrive(dep_bar + 24);
                    flag_wait(prm.flags + F_O * 512 + 32, epoch * CNT_O);
                    fence_proxy_async(); mbar_arrive(dep_bar + 32);
                }
            }
        } else {
#pragma unroll
            for (int k = 1; k < G1_STAGES; k++) {
                const uint32_t sa = base + k * G1_STAGE_BYTES;
                if (PACE0 + PACE) while ((uint32_t)clock() - t0 < (k == 3 ? PACE3 : PACE0 + (k - 1) * PACE)) {}
                load_stage1(sa, sa + A_BYTES + rank * 16384, full1(k), &prm.x, w0, k * 64, mblk * 128, w0_col, 0, stream_policy());
            }
            if (elect_one()) {
                prefetch_map(&prm.xn); prefetch_map(&prm.wqkv); prefetch_map(&prm.wu); prefetch_map(&prm.wg);
                prefetch_map(&prm.a2); prefetch_map(&prm.wo); prefetch_map(&prm.wd); prefetch_map(&prm.out);
            }
            uint32_t ph = 0;
#pragma unroll 1
            for (int t = 0; t < G1_TILES; t++) {
                const int nt = t * 8 + nslot;
                const CUtensorMap* const mb = tile_is_qkv(nt) ? &prm.wqkv : (rank ? &prm.wu : &prm.wg);
                const int col = tile_is_qkv(nt) ? tile_index(nt) * 4 + rank * 2 : tile_index(nt) * 2;
                if (t == 1) { TRACE_PUT(1, c0); TRACE_PUT(2, t0); TRACE(14); mbar_wait_warp(dep_bar, 0); TRACE(3); }
#pragma unroll 1
                for (int k = t ? 0 : G1_STAGES; k < G1_KSTEPS; k++) {
                    const int s = k & 3;
                    if (t == 1 && k == 8) mbar_wait_warp(dep_bar + 40, 0);
                    mbar_wait_warp(empty1(s), ph);
                    const uint32_t sa = base + s * G1_STAGE_BYTES;
                    load_stage1(sa, sa + A_BYTES + rank * 16384, full1(s), t ? &prm.xn : &prm.x, mb, k * 64, mblk * 128, col,
                                t & 3, stream_policy());
                    if (s == 3) ph ^= 1;
                }
            }
            if (elect_one()) {
                mbar_expect_tx(x_bar, 32768);
                tma_2d(aux, &prm.x, x_bar, nslot * 128, mblk * 128, stream_policy());
                tma_2d(aux + 16384, &prm.x, x_bar, nslot * 128 + 64, mblk * 128, stream_policy());
            }
            TRACE(4);
            mbar_wait_warp(dep_bar + 8, 0);
            TRACE(5);
            int q = 0; uint32_t ph2 = 1;
#pragma unroll 1
            for (int u = 0; u < G2_KSTEPS; u++) {
                if (u == G2_LATE || u == G2_DSTEPS || u == G2_LAST) {
                    TRACE(u == G2_LATE ? 6 : (u == G2_DSTEPS ? 32 : 40));
                    mbar_wait_warp(dep_bar + (u == G2_LATE ? 16 : (u == G2_DSTEPS ? 24 : 32)), 0);
                    TRACE(u == G2_LATE ? 7 : (u == G2_DSTEPS ? 33 : 41));
                }
                const uint32_t sa = stage2(q);
                const bool down = u < G2_DSTEPS;
                const int k = down ? u : (u & 3) * 4 + (u - G2_DSTEPS) / 4;
                mbar_wait_warp(u < G2_STAGES ? empty1((u * 2 + 1) / 3) : empty2(q), u < G2_STAGES ? ph : ph2);
                load_stage2(sa, sa + A_BYTES + rank * 8192, full2(q), &prm.a2, down ? &prm.wd : &prm.wo, (down ? DM : 0) + k * 64,
                            mblk * 64, nslot * 128 + rank * 64, k * 2, stream_policy());
                if (++q == G2_STAGES) { q = 0; ph2 ^= 1; }
            }
            TRACE(8);
        }
    }
}

typedef CUresult (*EncodeFn)(CUtensorMap*, CUtensorMapDataType, cuuint32_t, void*, const cuuint64_t*, const cuuint64_t*,
                             const cuuint32_t*, const cuuint32_t*, CUtensorMapInterleave, CUtensorMapSwizzle,
                             CUtensorMapL2promotion, CUtensorMapFloatOOBfill);

void encode(EncodeFn fn, CUtensorMap* m, const void* ptr, int rank, const cuuint64_t* dims, const cuuint64_t* strides,
            const cuuint32_t* box) {
    const cuuint32_t es[5] = {1, 1, 1, 1, 1};
    fn(m, CU_TENSOR_MAP_DATA_TYPE_BFLOAT16, rank, const_cast<void*>(ptr), dims, strides, box, es,
       CU_TENSOR_MAP_INTERLEAVE_NONE, box[0] == 16 ? CU_TENSOR_MAP_SWIZZLE_32B : CU_TENSOR_MAP_SWIZZLE_128B,
       CU_TENSOR_MAP_L2_PROMOTION_L2_128B, CU_TENSOR_MAP_FLOAT_OOB_FILL_NONE);
}
void encode_2d(EncodeFn fn, CUtensorMap* m, const void* ptr, int cols, int box_rows) {
    const cuuint64_t dims[2] = {(cuuint64_t)cols, SEQ}, strides[1] = {(cuuint64_t)cols * 2};
    const cuuint32_t box[2] = {64, (cuuint32_t)box_rows};
    encode(fn, m, ptr, 2, dims, strides, box);
}
void encode_w1(EncodeFn fn, CUtensorMap* m, const void* ptr, int cols) {
    const cuuint64_t dims[3] = {64, DM, (cuuint64_t)cols / 64}, strides[2] = {(cuuint64_t)cols * 2, 128};
    const cuuint32_t box[3] = {64, 64, 2};
    encode(fn, m, ptr, 3, dims, strides, box);
}
void encode_tail(EncodeFn fn, CUtensorMap* m, const __nv_bfloat16* w) {
    const cuuint64_t dims[3] = {16, DM, 8}, strides[2] = {DF * 2, 256};
    const cuuint32_t box[3] = {16, 64, 8};
    encode(fn, m, w + DF - 1024 + 112, 3, dims, strides, box);
}
void encode_qk(EncodeFn fn, CUtensorMap* m, const void* ptr) {
    const cuuint64_t dims[3] = {DM, SEQ, 3}, strides[2] = {NQKV * 2, DM * 2};
    const cuuint32_t box[3] = {64, 16, 2};
    encode(fn, m, ptr, 3, dims, strides, box);
}
void encode_a2(EncodeFn fn, CUtensorMap* m, const void* ptr) {
    const cuuint64_t dims[3] = {K2, 2, SEQ / 2}, strides[2] = {(cuuint64_t)SEQ * K2, K2 * 2};
    const cuuint32_t box[3] = {64, 2, 64};
    encode(fn, m, ptr, 3, dims, strides, box);
}
void encode_w2(EncodeFn fn, CUtensorMap* m, const void* ptr, int rows) {
    const cuuint64_t rb = DM * 2;
    const cuuint64_t dims[5] = {DM, 2, 4, 4, (cuuint64_t)rows / 32}, strides[4] = {rb, 8 * rb, 2 * rb, 32 * rb};
    const cuuint32_t box[5] = {64, 2, 4, 4, 2};
    encode(fn, m, ptr, 5, dims, strides, box);
}

}

extern "C" void kernel_launch(void* const* d_in, const int* in_sizes, int n_in, void* d_out, int out_size) {
    (void)in_sizes; (void)n_in; (void)out_size;
    static EncodeFn fn = nullptr;
    static Params prm;
    if (!fn) {
        cudaDriverEntryPointQueryResult st;
        cudaGetDriverEntryPoint("cuTensorMapEncodeTiled", (void**)&fn, cudaEnableDefault, &st);
        cudaGetSymbolAddress((void**)&prm.pxn, g_xn);
        cudaGetSymbolAddress((void**)&prm.qkv, g_qkv);
        cudaGetSymbolAddress((void**)&prm.pa2, g_a2);
        cudaGetSymbolAddress((void**)&prm.tail, g_tail);
        cudaGetSymbolAddress((void**)&prm.stats, g_stats);
        cudaGetSymbolAddress((void**)&prm.colsum, g_colsum);
        cudaGetSymbolAddress((void**)&prm.flags, g_flags);
        cudaGetSymbolAddress((void**)&prm.epoch, g_epoch);
        cudaFuncSetAttribute(fused_kernel, cudaFuncAttributeMaxDynamicSharedMemorySize, SMEM_BYTES);
    }
    encode_2d(fn, &prm.x, d_in[0], DM, 128);
    encode_2d(fn, &prm.xn, prm.pxn, DM, 128);
    encode_tail(fn, &prm.wtail, (const __nv_bfloat16*)d_in[5]);
    encode_w1(fn, &prm.wqkv, d_in[1], NQKV);
    encode_w1(fn, &prm.wg, d_in[4], DF);
    encode_w1(fn, &prm.wu, d_in[5], DF);
    encode_qk(fn, &prm.qk, prm.qkv);
    encode_2d(fn, &prm.v, prm.qkv, NQKV, 16);
    encode_2d(fn, &prm.o, prm.pa2, K2, 16);
    encode_a2(fn, &prm.a2, prm.pa2);
    encode_w2(fn, &prm.wo, d_in[2], DM);
    encode_w2(fn, &prm.wd, d_in[6], DF);
    encode_2d(fn, &prm.out, d_out, DM, 16);
    prm.px = (const __nv_bfloat16*)d_in[0];
    fused_kernel<<<NCTA, 384, SMEM_BYTES>>>(prm);
}
```

```cpp
#include <cuda_runtime.h>
#include <cuda_bf16.h>
#include <cuda.h>
#include <stdint.h>
#include <type_traits>

#define LNS 3
#define FS 14
#define CA 0x87658765u
#define CB 0x65876587u
#define CST 10
#define CIDX nslot
#define CKEEP 1
#define PACE0 900
#define PACE 425
#define PACE3 1700
#define TAIL 0
#define LNL 0
#define TDELAY 0
#define EPI 71
#define SK2 5
#define PFW 1
#define HALF 1
#define PFK 60 + mblk
#define PF0 0
#define PF1 16
#define XE 1
#define XL 0
#define XK 20 + nslot
#define SK0 2

namespace {

constexpr int SEQ = 2048, DM = 1024, DF = 3584, K2 = DM + DF, NQKV = 3 * DM;
constexpr int NGEMM = 128, NCTA = 132;
constexpr int G1_STAGES = 4, G1_STAGE_BYTES = 49152, G1_KSTEPS = 16, G1_TILES = 5;
constexpr int G2_STAGES = 6, G2_STAGE_BYTES = 32768, G2_KSTEPS = 72, G2_LATE = 40, G2_DSTEPS = 56, G2_LAST = 68;
constexpr int G2_HEAD = HALF ? 17 : 9;
constexpr int LN_STEP = LNS, FOLD_STEP = FS;
constexpr int A_BYTES = 16384;
constexpr int AUX_OFF = G1_STAGES * G1_STAGE_BYTES;
constexpr int BAR_OFF = AUX_OFF + 32768;
constexpr int SMEM_BYTES = BAR_OFF + 2816;
constexpr int G1_SKEW = 2, G2_SKEW = SK2;
constexpr int CONSUMER_REGS = 224, AUX_REGS = 56;
constexpr int ATT_SLOT = 8192;

enum { F_LN = 0, F_QKV = 1, F_EARLY = 2, F_LATE = 3, F_O = 4, F_LN2 = 5 };
constexpr unsigned CNT_LN = 8, CNT_QKV = 32, CNT_EARLY = 21, CNT_LATE = 8, CNT_O = 4;

__device__ __align__(1024) __nv_bfloat16 g_xn[SEQ * DM];
__device__ __align__(1024) __nv_bfloat16 g_qkv[SEQ * NQKV];
__device__ __align__(1024) __nv_bfloat16 g_a2[SEQ * K2];
__device__ __align__(128) uint4 g_tail[NGEMM * 256];
__device__ __align__(128) float2 g_stats[SEQ];
__device__ __align__(128) float g_colsum[16 * 1024];
__device__ __align__(128) unsigned g_flags[6 * 16 * 32];
__device__ __align__(128) unsigned g_epoch[NCTA * 16];

struct Params {
    const __nv_bfloat16* px;
    __nv_bfloat16 *pxn, *qkv, *pa2, *pout;
    uint4* tail;
    float2* stats;
    float* colsum;
    unsigned *flags, *epoch;
    unsigned long long* trace;
    uint32_t zero;
    CUtensorMap x, wqkv, wg, wu, xn, wtail, qk, v, o, a2, wo, wd, out;
};

extern __shared__ __align__(1024) uint8_t smem_raw[];

#define TRACE(slot) do {} while (0)
#define TRACE_GT(slot) do {} while (0)
#define TRACE_S(slot, v, want) do {} while (0)
#define TRACE_GET(v) do {} while (0)
#define TRACE_PUT(slot, v) do {} while (0)
#define TRACE_SLOT(v, slot) do {} while (0)
#define TRACE_NEXT(v) do {} while (0)
#define TRACE_DUMP() do {} while (0)
#define TRACE_CLEAR() do {} while (0)
#define STAGE_TRACE 0
#define TRACE_END() do {} while (0)
#define TRACE_STEP(t, k, i) do {} while (0)

__device__ __forceinline__ uint32_t smem_u32(const void* p) { return (uint32_t)__cvta_generic_to_shared(p); }
__device__ __forceinline__ void mbar_init(uint32_t bar, uint32_t cnt) {
    asm volatile("mbarrier.init.shared::cta.b64 [%0], %1;" :: "r"(bar), "r"(cnt) : "memory");
}
__device__ __forceinline__ void mbar_expect_tx(uint32_t bar, uint32_t bytes) {
    asm volatile("mbarrier.arrive.expect_tx.shared::cta.b64 _, [%0], %1;" :: "r"(bar), "r"(bytes) : "memory");
}
__device__ __forceinline__ void mbar_arrive(uint32_t bar) {
    asm volatile("mbarrier.arrive.shared::cta.b64 _, [%0];" :: "r"(bar) : "memory");
}
__device__ __forceinline__ void mbar_arrive_cluster(uint32_t bar, uint32_t cta) {
    asm volatile("{\n.reg .b32 ra;\nmapa.shared::cluster.u32 ra, %0, %1;\nmbarrier.arrive.shared::cluster.b64 _, [ra];\n}"
                 :: "r"(bar), "r"(cta) : "memory");
}
__device__ __forceinline__ bool mbar_try_wait(uint32_t bar, uint32_t parity) {
    uint32_t ok;
    asm volatile("{\n.reg .pred p;\nmbarrier.try_wait.parity.shared::cta.b64 p, [%1], %2;\nselp.u32 %0, 1, 0, p;\n}"
                 : "=r"(ok) : "r"(bar), "r"(parity) : "memory");
    return ok;
}
__device__ __forceinline__ bool mbar_test(uint32_t bar, uint32_t parity) {
    uint32_t ok;
    asm volatile("{\n.reg .pred p;\nmbarrier.test_wait.parity.shared::cta.b64 p, [%1], %2;\nselp.u32 %0, 1, 0, p;\n}"
                 : "=r"(ok) : "r"(bar), "r"(parity) : "memory");
    return ok;
}
__device__ __forceinline__ void mbar_wait(uint32_t bar, uint32_t parity) {
#pragma unroll 1
    for (int spins = 0; !mbar_try_wait(bar, parity) && spins < (1 << 17); spins++) {}
}
template <bool WARP = false> __device__ __forceinline__ void flag_wait(const unsigned* p, unsigned target) {
#pragma unroll 1
    for (int spins = 0; spins < (1 << 19); spins++) {
        unsigned v;
        asm volatile("ld.acquire.gpu.global.u32 %0, [%1];" : "=r"(v) : "l"(p) : "memory");
        if (WARP ? __all_sync(0xffffffffu, (int)(v - target) >= 0) : (int)(v - target) >= 0) break;
        __nanosleep(64);
    }
}
__device__ __forceinline__ void mbar_wait_warp(uint32_t bar, uint32_t parity) {
#pragma unroll 1
    for (int spins = 0; !__all_sync(0xffffffffu, mbar_try_wait(bar, parity)) && spins < (1 << 17); spins++) {}
}
__device__ __forceinline__ void flag_add(unsigned* p) {
    asm volatile("red.release.gpu.global.add.u32 [%0], 1;" :: "l"(p) : "memory");
}
__device__ __forceinline__ bool elect_one() {
    uint32_t ok;
    asm volatile("{\n.reg .pred p;\nelect.sync _|p, 0xffffffff;\nselp.u32 %0, 1, 0, p;\n}" : "=r"(ok));
    return ok;
}
__device__ __forceinline__ uint32_t pick(bool c, uint32_t a, uint32_t b) {
    uint32_t r;
    asm("{\n.reg .pred p;\nsetp.ne.b32 p, %3, 0;\nselp.b32 %0, %1, %2, p;\n}" : "=r"(r) : "r"(a), "r"(b), "r"((uint32_t)c));
    return r;
}
__device__ __forceinline__ void fence_proxy_async() { asm volatile("fence.proxy.async.global;" ::: "memory"); }
__device__ __forceinline__ uint4 lds128(uint32_t addr) {
    uint4 v;
    asm volatile("ld.shared.v4.u32 {%0,%1,%2,%3}, [%4];" : "=r"(v.x), "=r"(v.y), "=r"(v.z), "=r"(v.w) : "r"(addr) : "memory");
    return v;
}
__device__ __forceinline__ float2 lds64f(uint32_t addr) {
    float2 v;
    asm volatile("ld.shared.v2.f32 {%0,%1}, [%2];" : "=f"(v.x), "=f"(v.y) : "r"(addr) : "memory");
    return v;
}
__device__ __forceinline__ void sts128(uint32_t addr, uint4 v) {
    asm volatile("st.shared.v4.u32 [%0], {%1,%2,%3,%4};" :: "r"(addr), "r"(v.x), "r"(v.y), "r"(v.z), "r"(v.w) : "memory");
}
__device__ __forceinline__ void sts64f(uint32_t addr, float a, float b) {
    asm volatile("st.shared.v2.f32 [%0], {%1,%2};" :: "r"(addr), "f"(a), "f"(b) : "memory");
}

__device__ __forceinline__ uint64_t stream_policy() { return 0x12F0000000000000ull; }
__device__ __forceinline__ void tma_2d(uint32_t dst, const CUtensorMap* m, uint32_t bar, int c0, int c1, uint64_t pol) {
    asm volatile("cp.async.bulk.tensor.2d.shared::cluster.global.mbarrier::complete_tx::bytes.L2::cache_hint"
                 " [%0], [%1, {%3, %4}], [%2], %5;"
                 :: "r"(dst), "l"(m), "r"(bar), "r"(c0), "r"(c1), "l"(pol) : "memory");
}
__device__ __forceinline__ void tma_3d(uint32_t dst, const CUtensorMap* m, uint32_t bar, int c0, int c1, int c2, uint64_t pol) {
    asm volatile("cp.async.bulk.tensor.3d.shared::cluster.global.mbarrier::complete_tx::bytes.L2::cache_hint"
                 " [%0], [%1, {%3, %4, %5}], [%2], %6;"
                 :: "r"(dst), "l"(m), "r"(bar), "r"(c0), "r"(c1), "r"(c2), "l"(pol) : "memory");
}
__device__ __forceinline__ void tma_3d_mc(uint32_t dst, const CUtensorMap* m, uint32_t bar, int c1, int c2, uint64_t pol) {
    asm volatile("cp.async.bulk.tensor.3d.shared::cluster.global.mbarrier::complete_tx::bytes.multicast::cluster.L2::cache_hint"
                 " [%0], [%1, {%3, %4, %5}], [%2], %6, %7;"
                 :: "r"(dst), "l"(m), "r"(bar), "r"(0), "r"(c1), "r"(c2), "h"((uint16_t)3), "l"(pol) : "memory");
}
__device__ __forceinline__ void load_stage1(uint32_t dst, uint32_t dst_b, uint32_t bar, const CUtensorMap* ma, const CUtensorMap* mb,
                                            int k, int row, int col, int keep_a, uint64_t pol) {
    asm volatile("{\n.reg .pred e, p, q;\nelect.sync _|e, 0xffffffff;\nsetp.ne.and.b32 p|q, %8, 0, e;\n"
        "@p cp.async.bulk.tensor.2d.shared::cluster.global.mbarrier::complete_tx::bytes [%0], [%3, {%5, %6}], [%2];\n"
        "@q cp.async.bulk.tensor.2d.shared::cluster.global.mbarrier::complete_tx::bytes.L2::cache_hint [%0], [%3, {%5, %6}], [%2], %9;\n"
        "@e cp.async.bulk.tensor.3d.shared::cluster.global.mbarrier::complete_tx::bytes.multicast::cluster.L2::cache_hint"
        " [%1], [%4, {%10, %5, %7}], [%2], %11, %9;\n"
        "@e mbarrier.arrive.expect_tx.shared::cta.b64 _, [%2], %12;\n}"
        :: "r"(dst), "r"(dst_b), "r"(bar), "l"(ma), "l"(mb), "r"(k), "r"(row), "r"(col), "r"(keep_a), "l"(pol), "r"(0),
           "h"((uint16_t)3), "n"(G1_STAGE_BYTES) : "memory");
}
__device__ __forceinline__ void load_stage2(uint32_t dst, uint32_t dst_b, uint32_t bar, const CUtensorMap* ma, const CUtensorMap* mb,
                                            int ka, int row, int col, int kb, uint64_t pol) {
    asm volatile("{\n.reg .pred e;\nelect.sync _|e, 0xffffffff;\n"
        "@e cp.async.bulk.tensor.3d.shared::cluster.global.mbarrier::complete_tx::bytes.L2::cache_hint [%0], [%3, {%5, %10, %6}], [%2], %9;\n"
        "@e cp.async.bulk.tensor.5d.shared::cluster.global.mbarrier::complete_tx::bytes.multicast::cluster.L2::cache_hint"
        " [%1], [%4, {%7, %10, %10, %10, %8}], [%2], %11, %9;\n"
        "@e mbarrier.arrive.expect_tx.shared::cta.b64 _, [%2], %12;\n}"
        :: "r"(dst), "r"(dst_b), "r"(bar), "l"(ma), "l"(mb), "r"(ka), "r"(row), "r"(col), "r"(kb), "l"(pol), "r"(0),
           "h"((uint16_t)3), "n"(G2_STAGE_BYTES) : "memory");
}
__device__ __forceinline__ void tma_store_2d(const CUtensorMap* m, uint32_t src, int c0, int c1) {
    asm volatile("cp.async.bulk.tensor.2d.global.shared::cta.bulk_group [%0, {%2, %3}], [%1];"
                 :: "l"(m), "r"(src), "r"(c0), "r"(c1) : "memory");
}
__device__ __forceinline__ uint4 ldg_stream(const void* p, uint64_t pol) {
    uint4 v;
    asm volatile("ld.global.nc.L1::no_allocate.L2::cache_hint.v4.u32 {%0,%1,%2,%3}, [%4], %5;"
                 : "=r"(v.x), "=r"(v.y), "=r"(v.z), "=r"(v.w) : "l"(p), "l"(pol));
    return v;
}
__device__ __forceinline__ void st_tagged(void* p, float a, float b, uint32_t tag) {
    asm volatile("st.relaxed.gpu.global.v2.b32 [%0], {%1,%2};"
                 :: "l"(p), "r"((__float_as_uint(a) & ~3u) | tag), "r"((__float_as_uint(b) & ~3u) | tag) : "memory");
}
__device__ __forceinline__ bool untagged(const uint4& v, uint32_t tag) {
    return ((v.x ^ tag) | (v.y ^ tag) | (v.z ^ tag) | (v.w ^ tag)) & 3;
}
__device__ __forceinline__ uint4 ld_relaxed(const void* p) {
    uint4 v;
    asm volatile("ld.relaxed.gpu.global.v4.b32 {%0,%1,%2,%3}, [%4];" : "=r"(v.x), "=r"(v.y), "=r"(v.z), "=r"(v.w) : "l"(p) : "memory");
    return v;
}
__device__ __forceinline__ void prefetch_3d(const CUtensorMap* m, int c1, int c2, uint64_t pol) {
    asm volatile("cp.async.bulk.prefetch.tensor.3d.L2.global.L2::cache_hint [%0, {%1, %2, %3}], %4;"
                 :: "l"(m), "r"(0), "r"(c1), "r"(c2), "l"(pol) : "memory");
}
__device__ __forceinline__ void prefetch_map(const CUtensorMap* m) {
    asm volatile("prefetch.tensormap [%0];" :: "l"(m) : "memory");
}
template <int N> __device__ __forceinline__ void wg_wait() { asm volatile("wgmma.wait_group.sync.aligned %0;" :: "n"(N) : "memory"); }

__device__ __forceinline__ uint32_t desc_a(uint32_t addr) { return (addr & 0x3FFFF) >> 4 | 1 << 16; }
__device__ __forceinline__ uint32_t desc_b(uint32_t addr) { return (addr & 0x3FFFF) >> 4 | 512 << 16; }

#define R8(d, o) "+f"(d[o]), "+f"(d[o+1]), "+f"(d[o+2]), "+f"(d[o+3]), "+f"(d[o+4]), "+f"(d[o+5]), "+f"(d[o+6]), "+f"(d[o+7])
#define R32(d, o) R8(d, o), R8(d, o+8), R8(d, o+16), R8(d, o+24)
#define R64(d, o) R32(d, o), R32(d, o+32)
#define ACC0 "%0,%1,%2,%3,%4,%5,%6,%7,%8,%9,%10,%11,%12,%13,%14,%15,%16,%17,%18,%19,%20,%21,%22,%23,%24,%25,%26,%27,%28,%29,%30,%31,"\
    "%32,%33,%34,%35,%36,%37,%38,%39,%40,%41,%42,%43,%44,%45,%46,%47,%48,%49,%50,%51,%52,%53,%54,%55,%56,%57,%58,%59,%60,%61,%62,%63"
#define ACC1 "%64,%65,%66,%67,%68,%69,%70,%71,%72,%73,%74,%75,%76,%77,%78,%79,%80,%81,%82,%83,%84,%85,%86,%87,%88,%89,%90,%91,%92,%93,%94,%95,"\
    "%96,%97,%98,%99,%100,%101,%102,%103,%104,%105,%106,%107,%108,%109,%110,%111,%112,%113,%114,%115,%116,%117,%118,%119"
#define ACC64 "{" ACC0 "}"
#define ACC120 "{" ACC0 "," ACC1 "}"
#define ACC128 "{" ACC0 "," ACC1 ",%120,%121,%122,%123,%124,%125,%126,%127}"
#define MMA_K16(shape, acc, keep, hb, sb) \
    "mov.b64 da, {la, 0x40000040};\nmov.b64 db, {lb, " hb "};\n" \
    "wgmma.mma_async.sync.aligned." shape ".f32.bf16.bf16 " acc ", da, db, " keep ", 1, 1, 0, 1;\n" \
    "add.u32 la, la, 2;\nadd.u32 lb, lb, " sb ";\n"
#define MMA_STEP_B(shape, acc, a, b, off, keep, hb, sb) \
    "{\n.reg .pred p, q;\n.reg .b32 la, lb;\n.reg .b64 da, db;\nsetp.ne.b32 p, " keep ", 0;\nsetp.eq.b32 q, 0, 0;\n" \
    "add.u32 la, " a ", " off ";\nadd.u32 lb, " b ", " off ";\nwgmma.fence.sync.aligned;\n" \
    MMA_K16(shape, acc, "p", hb, sb) MMA_K16(shape, acc, "q", hb, sb) MMA_K16(shape, acc, "q", hb, sb) \
    MMA_K16(shape, acc, "q", hb, sb) "wgmma.commit_group.sync.aligned;\n}"
#define MMA_STEP(shape, acc, a, b, off, keep) MMA_STEP_B(shape, acc, a, b, off, keep, "0x40000040", "128")

__device__ __forceinline__ void mma_step(float (&d)[128], uint32_t da, uint32_t db, uint32_t off, int keep) {
    asm volatile(MMA_STEP("m64n256k16", ACC128, "%128", "%129", "%130", "%131")
                 : R64(d, 0), R64(d, 64) : "r"(da), "r"(db), "r"(off), "r"(keep) : "memory");
}
__device__ __forceinline__ void mma_rank(float (&d)[128], uint32_t a0, uint32_t a1, uint32_t db) {
    asm volatile("{\n.reg .pred q;\n.reg .b64 db;\nsetp.eq.b32 q, 0, 0;\nmov.b64 db, {%131, 0x40000040};\nwgmma.fence.sync.aligned;\n"
                 "wgmma.mma_async.sync.aligned.m64n256k16.f32.bf16.bf16 " ACC128 ", {%128, %129, %130, %130}, db, q, 1, 1, 1;\n}"
                 : R64(d, 0), R64(d, 64) : "r"(a0), "r"(a1), "r"(0), "r"(db) : "memory");
}
__device__ __forceinline__ void mma_step240(float (&d)[128], uint32_t da, uint32_t db, uint32_t off, int keep) {
    asm volatile(MMA_STEP("m64n240k16", ACC120, "%120", "%121", "%122", "%123")
                 : R64(d, 0), R32(d, 64), R8(d, 96), R8(d, 104), R8(d, 112) : "r"(da), "r"(db), "r"(off), "r"(keep) : "memory");
}
__device__ __forceinline__ void mma_step(float (&d)[64], uint32_t da, uint32_t db, uint32_t off, int keep) {
    asm volatile(MMA_STEP("m64n128k16", ACC64, "%64", "%65", "%66", "%67")
                 : R64(d, 0) : "r"(da), "r"(db), "r"(off), "r"(keep) : "memory");
}

__device__ __forceinline__ void mma_step_tail(float (&d)[64], uint32_t da, uint32_t b, uint32_t off) {
    asm volatile(MMA_STEP_B("m64n128k16", ACC64, "%64", "%65", "%66", "1", "0xC0000010", "32")
                 : R64(d, 0) : "r"(da), "r"((b & 0x3FFFF) >> 4 | 128 << 16), "r"(off) : "memory");
}

__device__ __forceinline__ uint32_t pack_bf16(float lo, float hi) {
    uint32_t r; asm("cvt.rn.bf16x2.f32 %0, %1, %2;" : "=r"(r) : "f"(hi), "f"(lo)); return r;
}
__device__ __forceinline__ float bf_lo(uint32_t v) { return __uint_as_float(v << 16); }
__device__ __forceinline__ float bf_hi(uint32_t v) { return __uint_as_float(v & 0xffff0000u); }
__device__ __forceinline__ float round_bf16(float v) { return bf_lo(pack_bf16(v, 0.f)); }
__device__ __forceinline__ uint32_t mul_bf16x2(uint32_t a, uint32_t b) {
    uint32_t r; asm("mul.rn.bf16x2 %0, %1, %2;" : "=r"(r) : "r"(a), "r"(b)); return r;
}
__device__ __forceinline__ uint32_t add_bf16x2(uint32_t a, uint32_t b) {
    uint32_t r; asm("add.rn.bf16x2 %0, %1, %2;" : "=r"(r) : "r"(a), "r"(b)); return r;
}
__device__ __forceinline__ uint32_t sub_bf16x2(uint32_t a, uint32_t b) {
    uint32_t r; asm("sub.rn.bf16x2 %0, %1, %2;" : "=r"(r) : "r"(a), "r"(b)); return r;
}
__device__ __forceinline__ uint32_t mul2_bf16x2(uint32_t a, uint32_t hi, uint32_t lo) {
    uint32_t r; asm("fma.rn.bf16x2 %0, %1, %2, %3;" : "=r"(r) : "r"(a), "r"(hi), "r"(mul_bf16x2(a, lo))); return r;
}
__device__ __forceinline__ float tanh_fast(float x) { float r; asm("tanh.approx.f32 %0, %1;" : "=f"(r) : "f"(x)); return r; }
__device__ __forceinline__ float gelu_tanh(float g) {
    float t = fmaf(g * g, 0.044715f * 0.7978845608f, 0.7978845608f) * g;
    float hg = 0.5f * g;
    return fmaf(hg, tanh_fast(t), hg);
}
__device__ __forceinline__ uint32_t geglu2(uint32_t g2, uint32_t u2) {
    return mul_bf16x2(pack_bf16(gelu_tanh(bf_lo(g2)), gelu_tanh(bf_hi(g2))), u2);
}
__device__ __forceinline__ float silu(float d) {
    float hd = 0.5f * d;
    return fmaf(hd, tanh_fast(hd), hd);
}
__device__ __forceinline__ float ex2_fast(float x) { float r; asm("ex2.approx.ftz.f32 %0, %1;" : "=f"(r) : "f"(x)); return r; }
__device__ __forceinline__ void unpack8(uint4 v, float (&f)[8]) {
    f[0] = bf_lo(v.x); f[1] = bf_hi(v.x); f[2] = bf_lo(v.y); f[3] = bf_hi(v.y);
    f[4] = bf_lo(v.z); f[5] = bf_hi(v.z); f[6] = bf_lo(v.w); f[7] = bf_hi(v.w);
}
template <int N> __device__ __forceinline__ void fence_regs(float (&d)[N]) {
#pragma unroll
    for (int i = 0; i < N; i++) asm volatile("" : "+f"(d[i]) :: "memory");
}

__device__ __forceinline__ float rcp_fast(float x) { float r; asm("rcp.approx.ftz.f32 %0, %1;" : "=f"(r) : "f"(x)); return r; }
__device__ __forceinline__ float sqrt_fast(float x) { float r; asm("sqrt.approx.ftz.f32 %0, %1;" : "=f"(r) : "f"(x)); return r; }
__device__ __forceinline__ uint32_t max_bf16x2(uint32_t a, uint32_t b) {
    uint32_t r; asm("max.bf16x2 %0, %1, %2;" : "=r"(r) : "r"(a), "r"(b)); return r;
}
__device__ __forceinline__ uint4 ldsm4(uint32_t addr) {
    uint4 v;
    asm volatile("ldmatrix.sync.aligned.m8n8.x4.shared.b16 {%0,%1,%2,%3}, [%4];"
                 : "=r"(v.x), "=r"(v.y), "=r"(v.z), "=r"(v.w) : "r"(addr) : "memory");
    return v;
}
__device__ __forceinline__ uint4 ldsm4_t(uint32_t addr) {
    uint4 v;
    asm volatile("ldmatrix.sync.aligned.m8n8.x4.trans.shared.b16 {%0,%1,%2,%3}, [%4];"
                 : "=r"(v.x), "=r"(v.y), "=r"(v.z), "=r"(v.w) : "r"(addr) : "memory");
    return v;
}
__device__ __forceinline__ void mma_16816(float (&c)[4], uint32_t a0, uint32_t a1, uint32_t a2, uint32_t a3, uint32_t b0, uint32_t b1) {
    asm("mma.sync.aligned.m16n8k16.row.col.f32.bf16.bf16.f32 {%0,%1,%2,%3}, {%4,%5,%6,%7}, {%8,%9}, {%0,%1,%2,%3};"
        : "+f"(c[0]), "+f"(c[1]), "+f"(c[2]), "+f"(c[3]) : "r"(a0), "r"(a1), "r"(a2), "r"(a3), "r"(b0), "r"(b1));
}
__device__ __forceinline__ void mma_1688(float (&c)[4], uint32_t a0, uint32_t a1, uint32_t b0) {
    asm("mma.sync.aligned.m16n8k8.row.col.f32.bf16.bf16.f32 {%0,%1,%2,%3}, {%4,%5}, {%6}, {%0,%1,%2,%3};"
        : "+f"(c[0]), "+f"(c[1]), "+f"(c[2]), "+f"(c[3]) : "r"(a0), "r"(a1), "r"(b0));
}
__device__ __forceinline__ void qk_tile(float (&c)[4], const uint4& q0, const uint4& q1, const uint4& k, float init) {
    c[0] = c[1] = c[2] = c[3] = init;
    mma_16816(c, q0.x, q0.y, q0.z, q0.w, k.x, k.y);
    mma_16816(c, q1.x, q1.y, q1.z, q1.w, k.z, k.w);
}
__device__ __forceinline__ uint32_t scaled_logits(bool first, float a0, float a1, float b0, float b1) {
    return mul2_bf16x2(pack_bf16(first ? a0 : b0, first ? a1 : b1), 0x3e353e35u, 0x379e379eu);
}
template <typename T> __device__ __forceinline__ T uniform(T v) { return __shfl_sync(0xffffffffu, v, 0); }

__device__ __forceinline__ void attention(const Params& prm, uint32_t base, unsigned epoch, int grp, int warp, int lane) {
    constexpr float LOG2E = 1.4426950408889634f;
    const int g = lane >> 2, t = lane & 3;
    const bool up0 = 2 * t > g, up1 = 2 * t + 1 > g;
    const uint32_t keep = (up0 ? 0x0000ffffu : 0u) | (up1 ? 0xffff0000u : 0u);
    const uint32_t buf = base + warp * 2 * ATT_SLOT, bar = base + AUX_OFF + warp * 16;
    const uint32_t qoff = (lane & 15) * 128 + (((lane >> 4) ^ (lane & 7)) << 4);
    const uint32_t koff = 2048 + (lane & 7) * 128 + (((lane >> 3) ^ (lane & 7)) << 4);
    const uint32_t rest_bar = base + AUX_OFF + 192;
    const int col = uniform(grp * 256), first = uniform((warp / 3 * 32 + warp % 3 * 11) * 16);
    const CUtensorMap* const mqk = reinterpret_cast<const CUtensorMap*>(uniform(reinterpret_cast<uint64_t>(&prm.qk)));
    const CUtensorMap *const mv = mqk + 1, *const mo = mqk + 2;
    const uint64_t pol = stream_policy();
    const uint32_t zero = prm.zero;
    uint4 kp[2], vp[2];
    uint32_t l0[2], l1[2], m[2];
    float s[2][3][4];
    auto scores = [&](uint32_t st, int row) {
        const float before = (row & 1023) == 0 ? -5.656854e9f : 0.f;
#pragma unroll
        for (int h = 0; h < 2; h++) {
            const uint4 q0 = ldsm4(st + (qoff ^ (h * 64))), q1 = ldsm4(st + (qoff ^ (h * 64 + 32)));
            const uint4 k0 = ldsm4(st + (koff ^ (h * 64))), k1 = ldsm4(st + 1024 + (koff ^ (h * 64)));
            qk_tile(s[h][0], q0, q1, kp[h], before);
            qk_tile(s[h][1], q0, q1, k0, 0.f);
            qk_tile(s[h][2], q0, q1, k1, 0.f);
            kp[h] = k1;
        }
    };
    auto logits = [&]() {
#pragma unroll
        for (int h = 0; h < 2; h++) {
            l0[h] = scaled_logits(up0, s[h][0][0], s[h][1][2], s[h][1][0], s[h][2][2]);
            l1[h] = scaled_logits(up1, s[h][0][1], s[h][1][3], s[h][1][1], s[h][2][3]);
            m[h] = max_bf16x2(l0[h], l1[h]);
            m[h] = max_bf16x2(m[h], __shfl_xor_sync(0xffffffffu, m[h], 1));
        }
    };
    auto row_max = [&]() {
#pragma unroll
        for (int h = 0; h < 2; h++) m[h] = max_bf16x2(m[h], __shfl_xor_sync(0xffffffffu, m[h], 2));
    };
    auto next = [](uint32_t p) {
        return (0x80200400u >> (p >> 4 & 31) & 1) > (p >> 15 & 1) ? p + (64 << 16) + 0x8000 : (p + 16) & ~0x8800u;
    };
    auto exchange = [&](uint32_t st, uint32_t b, uint32_t po, uint32_t pv, uint32_t pq) {
        asm volatile("{\n.reg .pred e, p, q;\n"
            "fence.proxy.async.shared::cta;\n"
            "bar.warp.sync 0xffffffff;\n"
            "elect.sync _|e, 0xffffffff;\n"
            "setp.eq.and.b32 p, %12, 0, e;\n"
            "setp.lt.and.s32 q, %8, %13, e;\n"
            "@q mbarrier.arrive.expect_tx.shared::cta.b64 _, [%2], 6144;\n"
            "@q cp.async.bulk.tensor.3d.shared::cluster.global.mbarrier::complete_tx::bytes.L2::cache_hint [%0], [%3, {%6, %7, %14}], [%2], %15;\n"
            "@q cp.async.bulk.tensor.2d.shared::cluster.global.mbarrier::complete_tx::bytes.L2::cache_hint [%0 + 4096], [%4, {%8, %9}], [%2], %15;\n"
            "@e cp.async.bulk.wait_group.read 0;\n"
            "@p cp.async.bulk.tensor.2d.global.shared::cta.bulk_group [%5, {%10, %11}], [%1 + 6144];\n"
            "@e cp.async.bulk.commit_group;\n"
            "bar.warp.sync 0xffffffff;\n}"
            :: "r"(st), "r"(st ^ ATT_SLOT), "r"(b), "l"(mqk), "l"(mv), "l"(mo), "r"(pq >> 16), "r"(pq & 2047),
               "r"((pv >> 16) + 2 * DM), "r"(pv & 2047), "r"(po >> 16), "r"(po & 2047), "r"(po & 0x8000),
               "r"(col + 256 + 2 * DM), "r"(0), "l"(pol) : "memory");
    };
    auto publish = [&](auto pending, int part) {
        asm volatile("{\n.reg .pred e;\n.reg .u32 n;\n"
            "elect.sync _|e, 0xffffffff;\n"
            "cp.async.bulk.wait_group %2;\n"
            "@e atom.acq_rel.cta.shared.add.u32 n, [%1], 1;\n"
            "setp.eq.and.u32 e, n, 11, e;\n"
            "@e red.release.gpu.global.add.u32 [%0], 1;\n}"
            :: "l"(prm.flags + F_O * 512 + part * 32), "r"(rest_bar + 8 + part * 4), "n"(pending.value) : "memory");
    };
    if (elect_one()) {
        mbar_init(bar, 1); mbar_init(bar + 8, 1);
        if (warp == 2) { mbar_init(rest_bar, 32); sts64f(rest_bar + 8, 0.f, 0.f); }
        asm volatile("fence.mbarrier_init.release.cluster;" ::: "memory");
        if (warp == 9) {
            prefetch_map(mqk); prefetch_map(mv); prefetch_map(mo);
            flag_wait(prm.flags + F_QKV * 512 + grp * 32, epoch * CNT_QKV);
        }
    }
    __syncthreads();
    if (elect_one()) {
        fence_proxy_async();
        mbar_expect_tx(bar + 8, 8192);
        tma_3d(buf + ATT_SLOT, mqk, bar + 8, col, first, 0, pol);
        tma_2d(buf + ATT_SLOT + 4096, mv, bar + 8, col + 2 * DM, first - 16, pol);
        tma_2d(buf + ATT_SLOT + 6144, mv, bar + 8, col + DM, first - 16, pol);
        mbar_expect_tx(bar, 6144);
        tma_3d(buf, mqk, bar, col, first + 16, 0, pol);
        tma_2d(buf + 4096, mv, bar, col + 2 * DM, first, pol);
        if (warp == 0) TRACE(9);
        if (warp == 9) prm.epoch[blockIdx.x * 16] = epoch;
    }
    __syncwarp();
    if (warp == 11 && lane < 4) flag_add(prm.flags + F_EARLY * 512 + (grp * 4 + lane) * 32);
    mbar_wait(bar + 8, 0);
#pragma unroll
    for (int h = 0; h < 2; h++) {
        kp[h] = ldsm4(buf + ATT_SLOT + 5120 + (koff ^ (h * 64)));
        vp[h] = ldsm4_t(buf + ATT_SLOT + 3072 + (koff ^ (h * 64)));
    }
    scores(buf + ATT_SLOT, first);
    uint32_t pm = 0x8000, p0 = col << 16 | first, p1 = p0 + 16, p2 = p0 + 32, p3 = p0 + 48;
    exchange(buf + ATT_SLOT, bar + 8, pm, p1, p2);
    logits();
    row_max();
    uint32_t st = buf, b = bar, cnt = 1;
    const uint32_t relay = warp == 2 ? 7 : 0;
    bool ready = false;
#pragma unroll 1
    while (p0 >> 16 < col + 256) {
        uint32_t pa[2], pb[2];
        if (!ready) mbar_wait(b, (cnt >> 1) & 1);
        uint4 v[2][2];
#pragma unroll
        for (int h = 0; h < 2; h++) {
            const float ma = -LOG2E * bf_lo(m[h]), mb = -LOG2E * bf_hi(m[h]);
            const float a0 = ex2_fast(fmaf(bf_lo(l0[h]), LOG2E, ma)), a1 = ex2_fast(fmaf(bf_lo(l1[h]), LOG2E, ma));
            const float b0 = ex2_fast(fmaf(bf_hi(l0[h]), LOG2E, mb)), b1 = ex2_fast(fmaf(bf_hi(l1[h]), LOG2E, mb));
            float sum[4] = {0.f, 0.f, 0.f, 0.f};
            mma_1688(sum, pack_bf16(a0, a1), pack_bf16(b0, b1), 0x3f803f80u);
            const float ra = rcp_fast(sum[0]), rb = rcp_fast(sum[2]);
            pa[h] = pack_bf16(a0 * ra, a1 * ra);
            pb[h] = pack_bf16(b0 * rb, b1 * rb);
        }
        scores(st, p1);
#pragma unroll
        for (int h = 0; h < 2; h++) {
            v[h][0] = ldsm4_t(st + 4096 + (qoff ^ (h * 64)));
            v[h][1] = ldsm4_t(st + 4096 + (qoff ^ (h * 64 + 32)));
        }
        if (cnt == relay) {
            flag_wait<true>(prm.flags + F_QKV * 512 + 128 + grp * 32, epoch * CNT_QKV);
            fence_proxy_async();
            mbar_arrive(rest_bar);
        }
        if (cnt == 8) {
#pragma unroll 1
            for (int spins = 0; !__all_sync(0xffffffffu, mbar_try_wait(rest_bar, 0)) && spins < (1 << 17); spins++) {}
        }
        if (cnt == 37) publish(std::integral_constant<int, 1>(), 0);
        exchange(st, b, pm, p2, p3);
        pm = p0; p0 = p1; p1 = p2; p2 = p3; p3 = next(p3);
        logits();
        float o[2][4][4];
#pragma unroll
        for (int h = 0; h < 2; h++) {
            const uint32_t prev[4] = {vp[h].x, vp[h].y, vp[h].z, vp[h].w};
            const uint32_t own[8] = {v[h][0].x, v[h][0].y, v[h][0].z, v[h][0].w, v[h][1].x, v[h][1].y, v[h][1].z, v[h][1].w};
            const uint32_t a0 = pa[h] & keep, a1 = pa[h] & ~keep, a2 = pb[h] & keep, a3 = pb[h] & ~keep;
            const uint32_t z0 = pa[h] & zero, z1 = pb[h] & zero;
#pragma unroll
            for (int j = 0; j < 4; j++) {
                o[h][j][0] = o[h][j][1] = o[h][j][2] = o[h][j][3] = 0.f;
                mma_1688(o[h][j], a0, z0, prev[j]);
                mma_16816(o[h][j], a1, a2, z1, a3, own[2 * j], own[2 * j + 1]);
            }
            vp[h] = make_uint4(own[1], own[3], own[5], own[7]);
        }
        row_max();
        b ^= 8; cnt++;
        ready = mbar_test(b, (cnt >> 1) & 1);
#pragma unroll
        for (int h = 0; h < 2; h++) {
#pragma unroll
            for (int d = 0; d < 2; d++)
                asm volatile("stmatrix.sync.aligned.m8n8.x4.shared.b16 [%0], {%1,%2,%3,%4};"
                             :: "r"(st + 6144 + (qoff ^ (h * 64 + d * 32))),
                                "r"(pack_bf16(o[h][2 * d][0], o[h][2 * d][1])), "r"(pack_bf16(o[h][2 * d][2], o[h][2 * d][3])),
                                "r"(pack_bf16(o[h][2 * d + 1][0], o[h][2 * d + 1][1])),
                                "r"(pack_bf16(o[h][2 * d + 1][2], o[h][2 * d + 1][3])) : "memory");
        }
        st ^= ATT_SLOT;
    }
    exchange(st, b, pm, p0, p0);
    publish(std::integral_constant<int, 0>(), 1);
    if (threadIdx.x == 0) { TRACE(10); TRACE_DUMP(); }
}

__device__ __forceinline__ void tail_gemm(const Params& prm, uint32_t base, uint32_t tag, int grp, int warp, int lane) {
    const uint32_t full = base + BAR_OFF, empty = full + 32, sum_bar = full + 320, colsum = full + 512;
    if (warp == 8) {
        if (elect_one()) {
            if (TDELAY) __nanosleep(TDELAY);
#pragma unroll 1
            for (int i = 0; i < 32; i++) {
                const uint32_t dst = base + (i & 3) * G1_STAGE_BYTES, bar = full + (i & 3) * 8;
                mbar_wait(bar + 32, ~i >> 2 & 1);
                mbar_expect_tx(bar, G1_STAGE_BYTES);
                tma_2d(dst, &prm.x, bar, (i & 15) * 64, grp * 512 + (i >> 4) * 256, stream_policy());
                tma_2d(dst + 16384, &prm.x, bar, (i & 15) * 64, grp * 512 + (i >> 4) * 256 + 128, stream_policy());
                tma_3d(dst + 32768, &prm.wtail, bar, 0, (i & 15) * 64, 0, stream_policy());
            }
        }
    } else if (warp >= 10) {
        float cs[8];
#pragma unroll
        for (int d = 0; d < 8; d++) cs[d] = 0.f;
        const uint32_t wa = base + 32768 + (warp - 10) * 8192 + (lane >> 3) * 2048 + (lane & 7) * 16;
#pragma unroll 1
        for (int i = 0; i < 28; i++) {
            mbar_wait(full + (i & 3) * 8, i >> 2 & 1);
            if (i < 16) {
#pragma unroll
                for (int j = 0; j < 16; j++) {
                    float f[8];
                    unpack8(lds128((wa ^ (j & 1) * 16) + (i & 3) * G1_STAGE_BYTES + j * 128), f);
#pragma unroll
                    for (int d = 0; d < 8; d++) cs[d] += f[d];
                }
            }
            if (i == 15) {
#pragma unroll
                for (int d = 0; d < 8; d++) {
                    cs[d] += __shfl_xor_sync(0xffffffffu, cs[d], 2);
                    cs[d] += __shfl_xor_sync(0xffffffffu, cs[d], 4);
                }
#pragma unroll
                for (int d = 0; d < 8; d += 2)
                    sts64f(colsum + (warp - 10) * 256 + (lane >> 3) * 64 + (lane & 1) * 32 + d * 4, cs[d], cs[d + 1]);
            }
            __syncwarp();
            if (lane == 0) {
                mbar_arrive(empty + (i & 3) * 8);
                if (i == 15) mbar_arrive(sum_bar);
            }
        }
    } else if (warp < 8) {
        const uint32_t da = desc_a(base + (warp >> 2) * 16384);
#pragma unroll 1
        for (int pass = 0; pass < 2; pass++) {
            const int mblk = grp * 4 + pass * 2 + (warp >> 2);
            const float2* const sp = prm.stats + mblk * 128 + (warp & 3) * 16 + (lane >> 2);
            uint2 st[4] = {};
            auto fetch_stats = [&]() {
                bool missing = false;
#pragma unroll
                for (int r = 0; r < 4; r++) {
                    if (((st[r].x ^ tag) | (st[r].y ^ tag)) & 3) {
                        missing = true;
                        asm volatile("ld.relaxed.gpu.global.v2.b32 {%0,%1}, [%2];"
                                     : "=r"(st[r].x), "=r"(st[r].y) : "l"(sp + r / 2 * 64 + r % 2 * 8) : "memory");
                    }
                }
                return missing;
            };
            float acc[2][64];
#pragma unroll
            for (int i = 0; i < 64; i++) acc[0][i] = acc[1][i] = 0.f;
#pragma unroll 1
            for (int k = 0; k < G1_KSTEPS; k++) {
                mbar_wait(full + (k & 3) * 8, k >> 2 & 1);
                mma_step_tail(acc[0], da, base + 32768, (k & 3) * (G1_STAGE_BYTES / 16));
                mma_step_tail(acc[1], da + 512, base + 32768, (k & 3) * (G1_STAGE_BYTES / 16));
                wg_wait<2>();
                if (k > 0 && (threadIdx.x & 127) == 0) mbar_arrive(empty + (k - 1 & 3) * 8);
                if (k == 13) fetch_stats();
            }
#pragma unroll 1
            for (int spins = 0; fetch_stats() && spins < (1 << 16); spins++) {}
            mbar_wait(sum_bar, 0);
            wg_wait<0>();
            fence_regs(acc[0]); fence_regs(acc[1]);
            if ((threadIdx.x & 127) == 0) mbar_arrive(empty + 24);
#pragma unroll
            for (int q = 0; q < 8; q++) {
                const float2 c0 = lds64f(colsum + q * 64 + (lane & 3) * 8), c1 = lds64f(colsum + q * 64 + 32 + (lane & 3) * 8);
                uint32_t v[8];
#pragma unroll
                for (int r = 0; r < 4; r++) {
                    const float* a = acc[r / 2] + 8 * q + r % 2 * 2;
                    const float shift = __uint_as_float(st[r].x ^ tag), inv = __uint_as_float(st[r].y ^ tag);
                    v[2 * r] = pack_bf16(fmaf(shift, c0.x, a[0]) * inv, fmaf(shift, c0.y, a[1]) * inv);
                    v[2 * r + 1] = pack_bf16(fmaf(shift, c1.x, a[4]) * inv, fmaf(shift, c1.y, a[5]) * inv);
                }
                uint4* const p = prm.tail + (q * 16 + mblk) * 256 + (threadIdx.x & 127);
                p[0] = make_uint4(v[0], v[1], v[2], v[3]);
                p[128] = make_uint4(v[4], v[5], v[6], v[7]);
            }
        }
    }
}

__device__ __forceinline__ bool tile_is_qkv(int nt) { return nt < 4 || (nt >= 8 && nt < 16); }
__device__ __forceinline__ int tile_index(int nt) { return nt < 4 ? nt + 8 : (nt < 8 ? nt - 4 : (nt < 16 ? nt - 8 : nt - 12)); }

struct Role {
    int rank, role, mblk, nslot, w0_col;
    const CUtensorMap* w0;
    __device__ __forceinline__ Role(const Params& prm) {
        uint32_t id;
        asm volatile("mov.u32 %0, %%ctaid.x;" : "=r"(id));
        const uint32_t cl = id / 2;
        rank = id & 1;
        role = pick(cl < 4, 32 + cl * 8, cl - 8 + max(4u, (cl - 1) * 37 >> 8)) * 2 + rank;
        mblk = role & 15; nslot = role >> 4;
        w0 = &prm.wqkv + pick(nslot < 4, 0, 1 + rank);
        w0_col = pick(nslot < 4, 32 + nslot * 4 + rank * 2, nslot * 2 - 8);
    }
};

__global__ void __cluster_dims__(2, 1, 1) __launch_bounds__(384, 1)
fused_kernel(const __grid_constant__ Params prm) {
    TRACE_GET(c0);
    const uint32_t base = smem_u32(smem_raw) & ~1023u;
    const uint32_t bars = base + BAR_OFF;
    auto full1 = [&](int s) { return bars + s * 8; };
    auto empty1 = [&](int s) { return bars + 32 + s * 8; };
    auto full2 = [&](int s) { return bars + 64 + s * 8; };
    auto empty2 = [&](int s) { return bars + 128 + s * 8; };
    const uint32_t sig_bar = bars + 192, dep_bar = bars + 256, cs_bar = bars + 304, fold_bar = bars + 320, x_bar = bars + 352;
    const uint32_t stats = bars + 1536;
    auto stage2 = [&](int q) { return base + q * G2_STAGE_BYTES; };
    const uint32_t aux = base + AUX_OFF;

    asm volatile("{\n.reg .pred p;\nsetp.eq.u32 p, %1, 0;\n@p mbarrier.init.shared::cta.b64 [%0], 1;\n"
        "fence.mbarrier_init.release.cluster;\nbarrier.cluster.arrive.relaxed.aligned;\n}" :: "r"(bars), "r"(threadIdx.x) : "memory");
    const int warp = __shfl_sync(0xffffffffu, threadIdx.x >> 5, 0);
    auto cluster_wait = []() { asm volatile("barrier.cluster.wait.acquire.aligned;" ::: "memory"); };
    if ((warp | (blockIdx.x & NGEMM)) == 8) {
        const Role r(prm);
        asm volatile("{\n.reg .pred e;\nelect.sync _|e, 0xffffffff;\n"
            "@e prefetch.tensormap [%0];\n@e prefetch.tensormap [%1];\n}" :: "l"(&prm.x), "l"(r.w0) : "memory");
        cluster_wait();
        load_stage1(base, base + A_BYTES + r.rank * 16384, full1(0), &prm.x, r.w0, 0, r.mblk * 128, r.w0_col, 0, stream_policy());
    } else {
        cluster_wait();
    }
    const uint32_t t0 = clock();
    asm volatile("{\n.reg .pred e, q;\nelect.sync _|e, 0xffffffff;\nsetp.ne.and.u32 q, %2, 0, e;\n"
        "@q mbarrier.init.shared::cta.b64 [%0], %1;\n@e mbarrier.init.shared::cta.b64 [%0 + 8], %1;\n"
        "@e mbarrier.init.shared::cta.b64 [%0 + 16], %1;\n@e mbarrier.init.shared::cta.b64 [%0 + 24], %1;\n"
        "fence.mbarrier_init.release.cluster;\nbarrier.cluster.arrive.relaxed.aligned;\n}"
        :: "r"(bars + warp * 32), "r"(1 << (0x10fa08 >> warp * 2 & 3)), "r"(warp) : "memory");
    const int lane = threadIdx.x & 31;
    const Role me(prm);
    const int rank = me.rank, role = me.role, mblk = me.mblk, nslot = me.nslot, w0_col = me.w0_col;
    const CUtensorMap* const w0 = me.w0;

    if (blockIdx.x >= NGEMM) {
        if (warp == 9) { TRACE_CLEAR(); TRACE_GT(0); TRACE_PUT(1, c0); }
        const unsigned epoch = __ldcg(prm.epoch + blockIdx.x * 16) + 1;
        cluster_wait();
        if (TAIL) tail_gemm(prm, base, 1 + (epoch & 1), blockIdx.x - NGEMM, warp, lane);
        uint32_t tid;
        asm volatile("mov.u32 %0, %%tid.x;" : "=r"(tid));
        attention(prm, (base + 2 * ATT_SLOT - 1) & ~(2u * ATT_SLOT - 1), epoch, blockIdx.x - NGEMM, uniform(tid >> 5), tid & 31);
    } else if (warp < 8) {
        asm volatile("setmaxnreg.inc.sync.aligned.u32 %0;" :: "n"(CONSUMER_REGS));
        const int wg = __shfl_sync(0xffffffffu, threadIdx.x >> 7, 0);
        const int cw = threadIdx.x >> 5;
        const int tid = threadIdx.x & 127;
        float acc[128];
        uint32_t pk[64];
#pragma unroll
        for (int i = 0; i < 64; i++) asm volatile("mov.b32 %0, 0;" : "=r"(pk[i]));
#pragma unroll
        for (int i = 0; i < 128; i++) asm volatile("mov.b32 %0, 0;" : "=f"(acc[i]));
        cluster_wait();

        const int orow = ((lane >> 2) & 1) * (SEQ / 2) + mblk * 64 + cw * 8 + (lane >> 3);
        __nv_bfloat16* optr = prm.pxn + (mblk * 128 + nslot * 16 + cw * 2) * DM + lane * 8;
        const uint32_t da = desc_a(base + wg * 8192), db = desc_b(base + A_BYTES);
        auto release = [&](uint32_t bar) { if (tid < 2) mbar_arrive_cluster(bar, tid); };
        auto store_pk = [&](__nv_bfloat16* p, int j) {
            asm volatile("st.global.v4.u32 [%0], {%1,%2,%3,%4};"
                         :: "l"(p), "r"(pk[4 * j]), "r"(pk[4 * j + 1]), "r"(pk[4 * j + 2]), "r"(pk[4 * j + 3]) : "memory");
        };
        auto chunk_geglu = [&](int j) {
#pragma unroll
            for (int i = 4 * j; i < 4 * j + 4; i++) pk[i] = geglu2(pk[i], pk[32 + i]);
            store_pk(optr + (j & 1) * 4 * K2 + (j >> 1) * 32, j);
        };
        auto chunk_qkv = [&](int c) {
            store_pk(optr + c * 32, 2 * c);
            store_pk(optr + 4 * NQKV + c * 32, 2 * c + 1);
        };
        auto signal_stores = [&](int p) { __syncwarp(); if (lane == 0) mbar_arrive(sig_bar + p * 8); };

        auto chunk_ln = [&](int k) {
            float* const mo = reinterpret_cast<float*>(pk + 32);
            if (k == LNL) {
                const uint4* xp = reinterpret_cast<const uint4*>(prm.px + (optr - prm.pxn));
                pk[38] = __ldcg(prm.epoch + blockIdx.x * 16 + 2);
#pragma unroll
                for (int i = 0; i < 8; i++) {
                    const uint4 v = ldg_stream(xp + i * 32, stream_policy());
                    pk[4 * i] = v.x; pk[4 * i + 1] = v.y; pk[4 * i + 2] = v.z; pk[4 * i + 3] = v.w;
                }
            } else if (k >= LN_STEP && k < LN_STEP + 3) {
                if (k == LN_STEP) {
                    mo[0] = bf_lo(uniform(pk[0])); mo[1] = bf_lo(uniform(pk[16]));
                    mo[2] = mo[3] = mo[4] = mo[5] = 0.f;
                }
#pragma unroll
                for (int i = (k - LN_STEP) * 11; i < (k - LN_STEP) * 11 + 11 && i < 32; i++) {
                    const int r = i & 1;
                    const uint32_t w = pk[r * 16 + i / 2];
                    const float lo = bf_lo(w) - mo[r], hi = bf_hi(w) - mo[r];
                    mo[2 + r] += lo + hi;
                    mo[4 + r] = fmaf(hi, hi, fmaf(lo, lo, mo[4 + r]));
                }
            } else if (k == LN_STEP + 3) {
                const bool second = lane & 16;
                float m1 = (second ? mo[3] : mo[2]) + __shfl_xor_sync(0xffffffffu, second ? mo[2] : mo[3], 16);
                float m2 = (second ? mo[5] : mo[4]) + __shfl_xor_sync(0xffffffffu, second ? mo[4] : mo[5], 16);
#pragma unroll
                for (int o = 8; o > 0; o >>= 1) {
                    m1 += __shfl_xor_sync(0xffffffffu, m1, o);
                    m2 += __shfl_xor_sync(0xffffffffu, m2, o);
                }
                m1 *= 1.f / DM;
                const float var = fmaxf(fmaf(-m1, m1, m2 * (1.f / DM)), 0.f);
                const float mean = round_bf16((second ? mo[1] : mo[0]) + m1);
                const float inv = rcp_fast(round_bf16(sqrt_fast(round_bf16(round_bf16(var) + 1e-5f))));
                if ((lane & 15) == 0) st_tagged(prm.stats + (uint32_t)(optr - prm.pxn) / DM + second, -mean, inv, 2 - (pk[38] & 1));
                const uint32_t split = pack_bf16(inv - round_bf16(inv), inv);
#pragma unroll
                for (int r = 0; r < 2; r++) {
                    const uint32_t f = __shfl_sync(0xffffffffu, split, r * 16);
                    pk[32 + 3 * r] = __byte_perm(__shfl_sync(0xffffffffu, __float_as_uint(mean), r * 16), 0, 0x3232);
                    pk[33 + 3 * r] = __byte_perm(f, 0, 0x3232);
                    pk[34 + 3 * r] = __byte_perm(f, 0, 0x1010);
                }
            } else if (k >= LN_STEP + 4 && k < LN_STEP + 8) {
#pragma unroll
                for (int i = k - LN_STEP - 4; i < 8; i += 4) {
                    const uint32_t* n = pk + 32 + i / 4 * 3;
#pragma unroll
                    for (int j = 4 * i; j < 4 * i + 4; j++) pk[j] = mul2_bf16x2(sub_bf16x2(pk[j], n[0]), n[1], n[2]);
                    store_pk(optr + i * 256, i);
                }
                if (k == LN_STEP + 5 || k == LN_STEP + 7) signal_stores(k == LN_STEP + 5 ? 0 : 7);
            } else if (k == FOLD_STEP) {
                mbar_wait(fold_bar, 0);
                const uint32_t sp = stats + (cw * 16 + (lane >> 2)) * 8;
                const uint32_t sel = lane & 2 ? 0x4444 : (lane & 1 ? 0x4432 : 0x3232);
                const float2 sa = lds64f(sp), sb = lds64f(sp + 64);
                mma_rank(acc, __byte_perm(__float_as_uint(sa.x), 0, sel), __byte_perm(__float_as_uint(sb.x), 0, sel), desc_b(aux));
                mo[0] = sa.y; mo[1] = sb.y;
            }
        };

        bool gated = false;
        TRACE_SLOT(tile_slot, 16 + wg * 8);
#pragma unroll 1
        for (int t = 0; t < G1_TILES; t++) {
#pragma unroll
            for (int k = 0; k < G1_KSTEPS; k++) {
                const int s = k & 3;
                TRACE_STEP(t, k, 0);
                mbar_wait(full1(s), (k >> 2) & 1);
                if (k == 0) TRACE_S(12, t, 0);
                TRACE_STEP(t, k, 1);
                if (wg == 1 && k == G1_KSTEPS - (t ? G1_SKEW : SK0)) asm volatile("bar.sync 1, 256;" ::: "memory");
                if (TAIL && t == G1_TILES - 1) mma_step240(acc, da, db, s * G1_STAGE_BYTES / 16, k);
                else mma_step(acc, da, db, s * G1_STAGE_BYTES / 16, k);
                if (wg == 0 && k == G1_KSTEPS - 1) asm volatile("bar.arrive 1, 256;" ::: "memory");
                wg_wait<1>();
                if (k > 0) release(empty1((k - 1) & 3));
                TRACE_STEP(t, k, 2);
                if (t == 0) chunk_ln(k);
                if (k >= 1 && k <= 8 && gated) {
                    chunk_geglu(k - 1);
                    if (k == 8) signal_stores(t == 1 ? 1 : t + 1);
                }
                if (t != 0 && !gated) {
                    if (k == 0) { chunk_qkv(0); chunk_qkv(1); }
                    if (k >= 6 && k <= 11) chunk_qkv(k - 4);
                    if ((k == 0 || k == 11) && t == 2) signal_stores(k ? 3 : 2);
                }
                if (k == 12) {
                    const int nt = t * 8 + nslot;
                    gated = !tile_is_qkv(nt);
                    optr = !gated ? prm.qkv + (size_t)orow * NQKV + tile_index(nt) * 256 + (lane & 3) * 8
                                  : prm.pa2 + (size_t)orow * K2 + DM + tile_index(nt) * 128 + (lane & 3) * 8;
                    asm volatile("" : "+l"(optr));
                }
            }
            wg_wait<0>();
            fence_regs(acc);
            release(empty1(3));
            if (t == 0) {
#pragma unroll
                for (int i = 0; i < 128; i++) acc[i] *= __uint_as_float(pk[32 + i / 2 % 2]);
                fence_regs(acc);
            }
#pragma unroll
            for (int i = 0; i < 64; i++) {
                const int e = (i & ~7) * 2 + (i & 3) * 4 + (i & 4) / 2;
                pk[i] = pack_bf16(acc[e], acc[e + 1]);
            }
            TRACE_NEXT(tile_slot);
        }

        float accd[64], accs[64];
#pragma unroll
        for (int i = 0; i < 64; i++) accd[i] = 0.f;
#pragma unroll
        for (int u = 0; u < G2_HEAD; u++) {
            const int q = u % G2_STAGES;
            mbar_wait(full2(q), (u / G2_STAGES) & 1);
            mma_step(accd, da, db, q * G2_STAGE_BYTES / 16, u);
            wg_wait<1>();
            if (u > 0) release(empty2((u - 1) % G2_STAGES));
            if (TAIL && u == 0) {
                const uint4 v = ldg_stream(prm.tail + role * 256 + threadIdx.x, stream_policy());
                pk[58] = v.x; pk[59] = v.y; pk[62] = v.z; pk[63] = v.w;
            }
            if (HALF == 0 && u >= 1) chunk_geglu(u - 1);
            if (HALF == 1 && u >= 1) {
                const int j = (u - 1) / 2;
#pragma unroll
                for (int i = 2 * u - 2; i < 2 * u; i++) pk[i] = geglu2(pk[i], pk[32 + i]);
                if (u % 2 == 0) store_pk(optr + (j & 1) * 4 * K2 + (j >> 1) * 32, j);
            }
            if (HALF == 2 && u % 2 == 0 && u > 0) chunk_geglu(u / 2 - 1);
            if (u == G2_HEAD - 1) signal_stores(6);
        }
        {
            int q = G2_HEAD % G2_STAGES, qp = (G2_HEAD - 1) % G2_STAGES; uint32_t ph = (G2_HEAD / G2_STAGES) & 1;
#pragma unroll 1
            for (int u = G2_HEAD; u < G2_DSTEPS; u++) {
                mbar_wait(full2(q), ph);
                mma_step(accd, da, db, q * (G2_STAGE_BYTES / 16), 1);
                wg_wait<1>();
                release(empty2(qp));
                qp = q;
                if (++q == G2_STAGES) { q = 0; ph ^= 1; }
            }
        }
        TRACE_NEXT(tile_slot);
#pragma unroll
        for (int i = 0; i < 64; i++) accs[i] = 0.f;
        uint32_t gk[32], xr[32];
        const uint32_t xs = aux + cw * 2048;
        const uint32_t xrow = xs + ((lane & 7) + ((lane >> 3) & 1) * 8) * 128;
        auto xaddr = [&](int j) { return xrow + (j >> 2) * 16384 + (((((j & 3) * 2) + (lane >> 4)) ^ (lane & 7)) << 4); };
#pragma unroll
        for (int u = G2_DSTEPS; u < G2_KSTEPS; u++) {
            const int q = u % G2_STAGES, v = u - G2_DSTEPS;
            mbar_wait(full2(q), (u / G2_STAGES) & 1);
            if (G2_SKEW > 0 && wg == 1 && u == G2_KSTEPS - G2_SKEW) asm volatile("bar.sync 1, 256;" ::: "memory");
            mma_step(accs, da, db, q * G2_STAGE_BYTES / 16, v);
            if (G2_SKEW > 0 && wg == 0 && u == G2_KSTEPS - 1) asm volatile("bar.arrive 1, 256;" ::: "memory");
            if (v >= 1 && v <= 8) {
#pragma unroll
                for (int i = 4 * (v - 1); i < 4 * v; i++) {
                    const uint32_t d2 = pack_bf16(accd[2 * i], accd[2 * i + 1]);
                    gk[i] = pack_bf16(silu(bf_lo(d2)), silu(bf_hi(d2)));
                }
            }
            if (v == 9) mbar_wait(x_bar, 0);
            if (v >= 9 && v <= 12) {
#pragma unroll
                for (int j = 2 * (v - 9); j < 2 * (v - 8); j++)
                    asm volatile("ldmatrix.sync.aligned.m8n8.x4.shared.b16 {%0,%1,%2,%3}, [%4];"
                                 : "=r"(xr[4 * j]), "=r"(xr[4 * j + 1]), "=r"(xr[4 * j + 2]), "=r"(xr[4 * j + 3])
                                 : "r"(xaddr(j)) : "memory");
            }
            wg_wait<1>();
            if (v == 0) fence_regs(accd);
            if (u - 1 + G2_STAGES < G2_KSTEPS) release(empty2((u - 1) % G2_STAGES));
        }
        __nv_bfloat16* po = prm.pout + (mblk * 128 + cw * 16 + (lane >> 3)) * DM + nslot * 128 + (lane & 7) * 8;
        uint32_t so = xs + (lane >> 3) * 128 + (((lane & 7) ^ (lane >> 3)) << 4);
        const int c0 = uniform(nslot * 128), c1 = uniform(mblk * 128 + cw * 16);
        const uint32_t xu = uniform(xs);
        if (EPI & 2) asm volatile("" : "+l"(po), "+r"(so));
        wg_wait<0>();
        fence_regs(accs);
        TRACE_NEXT(tile_slot);
        TRACE_END();
        if ((EPI & 16) && prm.zero == 0) return;
        if ((EPI & 32) && prm.zero == wg) return;
#pragma unroll
        for (int j = 0; j < 8; j++) {
            uint32_t r[4];
#pragma unroll
            for (int i = 0; i < 4; i++) {
                const int e = j * 4 + i;
                const uint32_t s2 = pack_bf16(accs[2 * e], accs[2 * e + 1]);
                if (EPI & 1) asm("fma.rn.bf16x2 %0, %1, %2, %3;" : "=r"(r[i]) : "r"(s2), "r"(gk[e]), "r"(xr[e]));
                else r[i] = add_bf16x2(xr[e], mul_bf16x2(s2, gk[e]));
            }
            asm volatile("stmatrix.sync.aligned.m8n8.x4.shared.b16 [%0], {%1,%2,%3,%4};"
                         :: "r"(xaddr(j)), "r"(r[0]), "r"(r[1]), "r"(r[2]), "r"(r[3]) : "memory");
            if ((EPI & 2) && (!(EPI & 4) || j / 4 == (EPI >> 6 & 1))) {
                if (j == 3 || j == 7) {
                    __syncwarp();
#pragma unroll
                    for (int i = 0; i < 4; i++) {
                        const uint4 v = lds128((so ^ (i & 1) * 64) + (j >> 2) * 16384 + i * 512);
                        asm volatile("st.global.v4.u32 [%0], {%1,%2,%3,%4};"
                                     :: "l"(po + (j >> 2) * 64 + i * 4 * DM), "r"(v.x), "r"(v.y), "r"(v.z), "r"(v.w) : "memory");
                    }
                }
            } else if (EPI & 4) {
                if (j == 7 || (j == 3 && !(EPI & 8))) {
                    asm volatile("{\n.reg .pred e;\nfence.proxy.async.shared::cta;\nbar.warp.sync 0xffffffff;\nelect.sync _|e, 0xffffffff;\n"
                        "@e cp.async.bulk.tensor.2d.global.shared::cta.bulk_group [%0, {%2, %3}], [%1];\n}"
                        :: "l"(&prm.out), "r"(xu + (j >> 2) * 16384), "r"(c0 + (j >> 2) * 64), "r"(c1) : "memory");
                    if (EPI & 8) asm volatile("{\n.reg .pred e;\nelect.sync _|e, 0xffffffff;\n"
                        "@e cp.async.bulk.tensor.2d.global.shared::cta.bulk_group [%0, {%2, %3}], [%1];\n}"
                        :: "l"(&prm.out), "r"(xu), "r"(c0), "r"(c1) : "memory");
                }
            } else if (j == 3 || j == 7) {
                asm volatile("fence.proxy.async.shared::cta;" ::: "memory");
                __syncwarp();
                if (lane == 0) {
                    tma_store_2d(&prm.out, xs + (j >> 2) * 16384, nslot * 128 + (j >> 2) * 64, mblk * 128 + cw * 16);
                    asm volatile("cp.async.bulk.commit_group;" ::: "memory");
                }
            }
        }
        if (EPI & 4) asm volatile("cp.async.bulk.commit_group;\ncp.async.bulk.wait_group.read 0;" ::: "memory");
        else if (!(EPI & 2) && lane == 0) asm volatile("cp.async.bulk.wait_group.read 0;" ::: "memory");
        if (tid == 0) { TRACE_NEXT(tile_slot); if (wg == 1) TRACE_GT(13); TRACE_DUMP(); }
    } else {
        asm volatile("setmaxnreg.dec.sync.aligned.u32 %0;" :: "n"(AUX_REGS));
        cluster_wait();
        unsigned* const flags = prm.flags + mblk * 32;
        if (warp == 9) {
            TRACE_CLEAR(); TRACE_GT(0); TRACE(60);
            if (lane == 0) {
                const unsigned epoch = __ldcg(prm.epoch + blockIdx.x * 16 + 2) + 1;
                mbar_wait(sig_bar, 0);
                TRACE(11);
                flag_add(flags + F_LN * 512);
                TRACE(42);
                flag_wait(flags + F_LN * 512, epoch * CNT_LN);
                fence_proxy_async();
                mbar_arrive(dep_bar);
                mbar_wait(sig_bar + 56, 0);
                flag_add(flags + F_LN2 * 512);
                flag_wait(flags + F_LN2 * 512, epoch * CNT_LN);
                fence_proxy_async();
                mbar_arrive(dep_bar + 40);
                TRACE(59);
                prm.epoch[blockIdx.x * 16 + 2] = epoch;
                for (int p = nslot < 4 ? 2 : 1; p < 7; p++) {
                    mbar_wait(sig_bar + p * 8, 0);
                    if (p == 2) TRACE(37);
                    flag_add(p == 2 || p == 3 ? prm.flags + F_QKV * 512 + (p * 4 - 8 + (nslot & 3)) * 32
                                              : flags + (p < 6 ? F_EARLY : F_LATE) * 512);
                    if (p == 2) TRACE(43);
                }
            }
        } else if (warp > 9) {
            const int w = warp - 10;
            const unsigned epoch = __ldcg(prm.epoch + blockIdx.x * 16 + w) + 1;
            const uint32_t tag = 1 + (epoch & 1);
                const uint32_t at = (w ? CB : CA) >> (CIDX) * 4 & 15;
            mbar_wait(empty1(at & 3), 0);
            mbar_wait(empty1(at & 3), at >> 3);
            if (elect_one()) {
                mbar_expect_tx(cs_bar + w * 8, 16384);
                if (CKEEP) asm volatile("cp.async.bulk.tensor.3d.shared::cluster.global.mbarrier::complete_tx::bytes [%0], [%1, {%3, %4, %5}], [%2];"
                    :: "r"(aux + w * 16384), "l"(w0), "r"(cs_bar + w * 8), "r"(0), "r"(((mblk & ~1) + w) * 64), "r"(w0_col) : "memory");
                else tma_3d(aux + w * 16384, w0, cs_bar + w * 8, 0, ((mblk & ~1) + w) * 64, w0_col, stream_policy());
            }
            float cs[8];
#pragma unroll
            for (int d = 0; d < 8; d++) cs[d] = 0.f;
            const uint32_t wa = aux + w * 8192 + (lane >> 3) * 128 + (((lane & 7) ^ (lane >> 3)) << 4);
            uint4 v[9];
            auto fetch = [&](int h, uint32_t off) {
#pragma unroll
                for (int j = 0; j < 4; j++) v[h * 4 + j] = lds128((wa ^ (j & 1) * 64) + off + h * 2048 + j * 512);
            };
            auto add = [&](int h) {
#pragma unroll
                for (int j = 0; j < 4; j++) {
                    float f[8];
                    unpack8(v[h * 4 + j], f);
#pragma unroll
                    for (int d = 0; d < 8; d++) cs[d] += f[d];
                }
            };
            if (CST) { mbar_wait(empty1(CST & 3), 0); mbar_wait(empty1(CST & 3), CST >> 3); }
            mbar_wait(cs_bar, 0);

            fetch(0, 0);
#pragma unroll 1
            for (int i = 0; i < 4; i++) {
                fetch(1, (i >> 1) * 16384 + (i & 1) * 4096);
                add(0);
                if (i == 1) mbar_wait(cs_bar + 8, 0);
                fetch(0, (i + 1 & 2) * 8192 + (~i & 1) * 4096);
                add(1);
            }
#pragma unroll
            for (int d = 0; d < 4; d++)
                cs[d] = (lane & 16 ? cs[d + 4] : cs[d]) + __shfl_xor_sync(0xffffffffu, lane & 16 ? cs[d] : cs[d + 4], 16);
#pragma unroll
            for (int d = 0; d < 2; d++)
                cs[d] = (lane & 8 ? cs[d + 2] : cs[d]) + __shfl_xor_sync(0xffffffffu, lane & 8 ? cs[d] : cs[d + 2], 8);
            st_tagged(prm.colsum + (nslot * 2 + rank) * 1024 + (mblk >> 1) * 128 + w * 64 + (lane & 7) * 8 + (lane >> 3) * 2,
                      cs[0], cs[1], tag);

#pragma unroll
            for (int m = 0; m < 9; m++) v[m] = make_uint4(0, 0, 0, 0);
            const float* parts = prm.colsum + (nslot * 2 + (lane >> 4)) * 1024 + w * 64 + (lane & 15) * 4;
            const float* const rows = &prm.stats[mblk * 128 + w * 64 + lane * 2].x;
#pragma unroll 1
            for (int spins = 0; spins < (1 << 16); spins++) {
                bool missing = false;
                asm volatile("" : "+l"(parts));
#pragma unroll
                for (int m = 0; m < 9; m++) {
                    if (untagged(v[m], tag)) {
                        missing = true;
                        v[m] = ld_relaxed(m < 8 ? parts + m * 128 : rows);
                    }
                }
                if (!missing) break;
            }
            float4 c = make_float4(0.f, 0.f, 0.f, 0.f);
#pragma unroll
            for (int m = 0; m < 8; m++) {
                c.x += __uint_as_float(v[m].x ^ tag); c.y += __uint_as_float(v[m].y ^ tag);
                c.z += __uint_as_float(v[m].z ^ tag); c.w += __uint_as_float(v[m].w ^ tag);
            }
            sts128(stats + w * 512 + lane * 16, make_uint4(v[8].x ^ tag, v[8].y ^ tag, v[8].z ^ tag, v[8].w ^ tag));
            const uint32_t ca = aux + w * 8192 + (lane >> 4) * 16384 + (lane & 15) * 8;
#pragma unroll
            for (int r = 0; r < 3; r++) {
                const uint32_t lo = pack_bf16(c.x, c.y), hi = pack_bf16(c.z, c.w);
                sts64f((ca ^ r * 16) + r * 128, __uint_as_float(lo), __uint_as_float(hi));
                c.x -= bf_lo(lo); c.y -= bf_hi(lo); c.z -= bf_lo(hi); c.w -= bf_hi(hi);
            }
            asm volatile("fence.proxy.async.shared::cta;" ::: "memory");
            __syncwarp();
            if (lane == 0) {
                mbar_arrive(fold_bar);
                prm.epoch[blockIdx.x * 16 + w] = epoch;
                if (w == 0) {
                    TRACE_S(35, w, 0);
                    flag_wait(flags + F_EARLY * 512, epoch * CNT_EARLY);
                    fence_proxy_async(); mbar_arrive(dep_bar + 8);
                    flag_wait(flags + F_LATE * 512, epoch * CNT_LATE);
                    fence_proxy_async(); mbar_arrive(dep_bar + 16);
                    flag_wait(prm.flags + F_O * 512, epoch * CNT_O);
                    fence_proxy_async(); mbar_arrive(dep_bar + 24);
                    flag_wait(prm.flags + F_O * 512 + 32, epoch * CNT_O);
                    fence_proxy_async(); mbar_arrive(dep_bar + 32);
                }
            }
        } else {
#pragma unroll
            for (int k = 1; k < G1_STAGES; k++) {
                const uint32_t sa = base + k * G1_STAGE_BYTES;
                if (PACE0 + PACE) while ((uint32_t)clock() - t0 < (k == 3 ? PACE3 : PACE0 + (k - 1) * PACE)) {}
                load_stage1(sa, sa + A_BYTES + rank * 16384, full1(k), &prm.x, w0, k * 64, mblk * 128, w0_col, 0, stream_policy());
            }
            if (elect_one()) {
                prefetch_map(&prm.xn); prefetch_map(&prm.wqkv); prefetch_map(&prm.wu); prefetch_map(&prm.wg);
                prefetch_map(&prm.a2); prefetch_map(&prm.wo); prefetch_map(&prm.wd); prefetch_map(&prm.out);
            }
            auto load_x = [&]() {
                if (elect_one()) {
                    mbar_expect_tx(x_bar, 32768);
                    tma_2d(aux, &prm.x, x_bar, nslot * 128, mblk * 128, stream_policy());
                    tma_2d(aux + 16384, &prm.x, x_bar, nslot * 128 + 64, mblk * 128, stream_policy());
                }
                __syncwarp();
            };
            uint32_t ph = 0;
#pragma unroll 1
            for (int t = 0; t < G1_TILES; t++) {
                const int nt = t * 8 + nslot;
                const CUtensorMap* const mb = tile_is_qkv(nt) ? &prm.wqkv : (rank ? &prm.wu : &prm.wg);
                const int col = tile_is_qkv(nt) ? tile_index(nt) * 4 + rank * 2 : tile_index(nt) * 2;
                if (t == 1) { TRACE_PUT(1, c0); TRACE_PUT(2, t0); TRACE(14); mbar_wait_warp(dep_bar, 0); TRACE(3); }
#pragma unroll 1
                for (int k = t ? 0 : G1_STAGES; k < G1_KSTEPS; k++) {
                    const int s = k & 3;
                    if (t == 1 && k == 8) mbar_wait_warp(dep_bar + 40, 0);
                    if (PFW && t * 16 + k == (PFK) && mblk >= PF0 && mblk < PF1) {
                        asm volatile("{\n.reg .pred e;\nelect.sync _|e, 0xffffffff;\n"
                            "@e cp.async.bulk.prefetch.tensor.5d.L2.global [%0, {%1, %4, %4, %4, %3}];\n"
                            "@e cp.async.bulk.prefetch.tensor.5d.L2.global [%0, {%2, %4, %4, %4, %3}];\n}"
                            :: "l"(&prm.wd), "r"(nslot * 128), "r"(nslot * 128 + 64), "r"(mblk * 2), "r"(0) : "memory");
                    }
                    mbar_wait_warp(empty1(s), ph);
                    const uint32_t sa = base + s * G1_STAGE_BYTES;
                    load_stage1(sa, sa + A_BYTES + rank * 16384, full1(s), t ? &prm.xn : &prm.x, mb, k * 64, mblk * 128, col,
                                t & 3, stream_policy());
                    if (s == 3) ph ^= 1;
                    if (XE && t * 16 + k == (XK)) load_x();
                }
            }
            if (!XE && !XL) load_x();
            TRACE(4);
            mbar_wait_warp(dep_bar + 8, 0);
            TRACE(5);
            int q = 0; uint32_t ph2 = 1;
#pragma unroll 1
            for (int u = 0; u < G2_KSTEPS; u++) {
                if (u == G2_LATE || u == G2_DSTEPS || u == G2_LAST) {
                    TRACE(u == G2_LATE ? 6 : (u == G2_DSTEPS ? 32 : 40));
                    mbar_wait_warp(dep_bar + (u == G2_LATE ? 16 : (u == G2_DSTEPS ? 24 : 32)), 0);
                    TRACE(u == G2_LATE ? 7 : (u == G2_DSTEPS ? 33 : 41));
                }
                const uint32_t sa = stage2(q);
                const bool down = u < G2_DSTEPS;
                const int k = down ? u : (u & 3) * 4 + (u - G2_DSTEPS) / 4;
                mbar_wait_warp(u < G2_STAGES ? empty1((u * 2 + 1) / 3) : empty2(q), u < G2_STAGES ? ph : ph2);
                load_stage2(sa, sa + A_BYTES + rank * 8192, full2(q), &prm.a2, down ? &prm.wd : &prm.wo, (down ? DM : 0) + k * 64,
                            mblk * 64, nslot * 128 + rank * 64, k * 2, stream_policy());
                if (++q == G2_STAGES) { q = 0; ph2 ^= 1; }
                if (XL && u == (XK)) load_x();
            }
            TRACE(8);
        }
    }
}

typedef CUresult (*EncodeFn)(CUtensorMap*, CUtensorMapDataType, cuuint32_t, void*, const cuuint64_t*, const cuuint64_t*,
                             const cuuint32_t*, const cuuint32_t*, CUtensorMapInterleave, CUtensorMapSwizzle,
                             CUtensorMapL2promotion, CUtensorMapFloatOOBfill);

void encode(EncodeFn fn, CUtensorMap* m, const void* ptr, int rank, const cuuint64_t* dims, const cuuint64_t* strides,
            const cuuint32_t* box) {
    const cuuint32_t es[5] = {1, 1, 1, 1, 1};
    fn(m, CU_TENSOR_MAP_DATA_TYPE_BFLOAT16, rank, const_cast<void*>(ptr), dims, strides, box, es,
       CU_TENSOR_MAP_INTERLEAVE_NONE, box[0] == 16 ? CU_TENSOR_MAP_SWIZZLE_32B : CU_TENSOR_MAP_SWIZZLE_128B,
       CU_TENSOR_MAP_L2_PROMOTION_L2_128B, CU_TENSOR_MAP_FLOAT_OOB_FILL_NONE);
}
void encode_2d(EncodeFn fn, CUtensorMap* m, const void* ptr, int cols, int box_rows) {
    const cuuint64_t dims[2] = {(cuuint64_t)cols, SEQ}, strides[1] = {(cuuint64_t)cols * 2};
    const cuuint32_t box[2] = {64, (cuuint32_t)box_rows};
    encode(fn, m, ptr, 2, dims, strides, box);
}
void encode_w1(EncodeFn fn, CUtensorMap* m, const void* ptr, int cols) {
    const cuuint64_t dims[3] = {64, DM, (cuuint64_t)cols / 64}, strides[2] = {(cuuint64_t)cols * 2, 128};
    const cuuint32_t box[3] = {64, 64, 2};
    encode(fn, m, ptr, 3, dims, strides, box);
}
void encode_tail(EncodeFn fn, CUtensorMap* m, const __nv_bfloat16* w) {
    const cuuint64_t dims[3] = {16, DM, 8}, strides[2] = {DF * 2, 256};
    const cuuint32_t box[3] = {16, 64, 8};
    encode(fn, m, w + DF - 1024 + 112, 3, dims, strides, box);
}
void encode_qk(EncodeFn fn, CUtensorMap* m, const void* ptr) {
    const cuuint64_t dims[3] = {DM, SEQ, 3}, strides[2] = {NQKV * 2, DM * 2};
    const cuuint32_t box[3] = {64, 16, 2};
    encode(fn, m, ptr, 3, dims, strides, box);
}
void encode_a2(EncodeFn fn, CUtensorMap* m, const void* ptr) {
    const cuuint64_t dims[3] = {K2, 2, SEQ / 2}, strides[2] = {(cuuint64_t)SEQ * K2, K2 * 2};
    const cuuint32_t box[3] = {64, 2, 64};
    encode(fn, m, ptr, 3, dims, strides, box);
}
void encode_w2(EncodeFn fn, CUtensorMap* m, const void* ptr, int rows) {
    const cuuint64_t rb = DM * 2;
    const cuuint64_t dims[5] = {DM, 2, 4, 4, (cuuint64_t)rows / 32}, strides[4] = {rb, 8 * rb, 2 * rb, 32 * rb};
    const cuuint32_t box[5] = {64, 2, 4, 4, 2};
    encode(fn, m, ptr, 5, dims, strides, box);
}

}

extern "C" void kernel_launch(void* const* d_in, const int* in_sizes, int n_in, void* d_out, int out_size) {
    (void)in_sizes; (void)n_in; (void)out_size;
    static EncodeFn fn = nullptr;
    static Params prm;
    if (!fn) {
        cudaDriverEntryPointQueryResult st;
        cudaGetDriverEntryPoint("cuTensorMapEncodeTiled", (void**)&fn, cudaEnableDefault, &st);
        cudaGetSymbolAddress((void**)&prm.pxn, g_xn);
        cudaGetSymbolAddress((void**)&prm.qkv, g_qkv);
        cudaGetSymbolAddress((void**)&prm.pa2, g_a2);
        cudaGetSymbolAddress((void**)&prm.tail, g_tail);
        cudaGetSymbolAddress((void**)&prm.stats, g_stats);
        cudaGetSymbolAddress((void**)&prm.colsum, g_colsum);
        cudaGetSymbolAddress((void**)&prm.flags, g_flags);
        cudaGetSymbolAddress((void**)&prm.epoch, g_epoch);
        cudaFuncSetAttribute(fused_kernel, cudaFuncAttributeMaxDynamicSharedMemorySize, SMEM_BYTES);
    }
    encode_2d(fn, &prm.x, d_in[0], DM, 128);
    encode_2d(fn, &prm.xn, prm.pxn, DM, 128);
    encode_tail(fn, &prm.wtail, (const __nv_bfloat16*)d_in[5]);
    encode_w1(fn, &prm.wqkv, d_in[1], NQKV);
    encode_w1(fn, &prm.wg, d_in[4], DF);
    encode_w1(fn, &prm.wu, d_in[5], DF);
    encode_qk(fn, &prm.qk, prm.qkv);
    encode_2d(fn, &prm.v, prm.qkv, NQKV, 16);
    encode_2d(fn, &prm.o, prm.pa2, K2, 16);
    encode_a2(fn, &prm.a2, prm.pa2);
    encode_w2(fn, &prm.wo, d_in[2], DM);
    encode_w2(fn, &prm.wd, d_in[6], DF);
    encode_2d(fn, &prm.out, d_out, DM, 16);
    prm.px = (const __nv_bfloat16*)d_in[0];
    prm.pout = (__nv_bfloat16*)d_out;
    fused_kernel<<<NCTA, 384, SMEM_BYTES>>>(prm);
}
```

```cpp
#include <cuda_runtime.h>
#include <cuda_bf16.h>
#include <cuda.h>
#include <stdint.h>
#include <type_traits>

#define LNS 3
#define FS 14
#define CA 0x87658765u
#define CB 0x65876587u
#define CST 10
#define CIDX nslot
#define CKEEP 1
#define PACE0 900
#define PACE 425
#define PACE3 1700
#define TAIL 6
#define LNL 0
#define EPI 71
#define SK2 5
#define PFW 1
#define HALF 1
#define PFK 60 + mblk
#define PF0 0
#define PF1 16
#define XE 1
#define XL 0
#define XK 20 + nslot
#define TSK 2
#define TLD 10
#define SK0 2

namespace {

constexpr int SEQ = 2048, DM = 1024, DF = 3584, K2 = DM + DF, NQKV = 3 * DM;
constexpr int NGEMM = 128, NCTA = 132;
constexpr int G1_STAGES = 4, G1_STAGE_BYTES = 49152, G1_KSTEPS = 16, G1_TILES = 5;
constexpr int G2_STAGES = 6, G2_STAGE_BYTES = 32768, G2_KSTEPS = 72, G2_LATE = 40, G2_DSTEPS = 56, G2_LAST = 68;
constexpr int G2_HEAD = HALF ? 17 : 9;
constexpr int LN_STEP = LNS, FOLD_STEP = FS;
constexpr int A_BYTES = 16384;
constexpr int AUX_OFF = G1_STAGES * G1_STAGE_BYTES;
constexpr int BAR_OFF = AUX_OFF + 32768;
constexpr int SMEM_BYTES = BAR_OFF + 2816;
constexpr int G1_SKEW = 2, G2_SKEW = SK2;
constexpr int CONSUMER_REGS = 224, AUX_REGS = 56;
constexpr int ATT_SLOT = 8192;

enum { F_LN = 0, F_QKV = 1, F_EARLY = 2, F_LATE = 3, F_O = 4, F_LN2 = 5, F_TAIL = 6 };
constexpr unsigned CNT_LN = 8, CNT_QKV = 32, CNT_EARLY = 20, CNT_LATE = 8, CNT_O = 4;

__device__ __align__(1024) __nv_bfloat16 g_xn[SEQ * DM];
__device__ __align__(1024) __nv_bfloat16 g_qkv[SEQ * NQKV];
__device__ __align__(1024) __nv_bfloat16 g_a2[SEQ * K2];
__device__ __align__(128) uint4 g_tail[NGEMM * 512];
__device__ __align__(128) float2 g_stats[SEQ];
__device__ __align__(128) float g_colsum[16 * 1024];
__device__ __align__(128) unsigned g_flags[7 * 16 * 32];
__device__ __align__(128) unsigned g_epoch[NCTA * 16];

struct Params {
    const __nv_bfloat16* px;
    __nv_bfloat16 *pxn, *qkv, *pa2, *pout;
    uint4* tail;
    float2* stats;
    float* colsum;
    unsigned *flags, *epoch;
    unsigned long long* trace;
    uint32_t zero;
    CUtensorMap x, wqkv, wg, wu, xn, wtail, qk, v, o, a2, wo, wd, out;
};

extern __shared__ __align__(1024) uint8_t smem_raw[];

#define TRACE(slot) do {} while (0)
#define TRACE_GT(slot) do {} while (0)
#define TRACE_S(slot, v, want) do {} while (0)
#define TRACE_GET(v) do {} while (0)
#define TRACE_PUT(slot, v) do {} while (0)
#define TRACE_SLOT(v, slot) do {} while (0)
#define TRACE_NEXT(v) do {} while (0)
#define TRACE_DUMP() do {} while (0)
#define TRACE_CLEAR() do {} while (0)
#define STAGE_TRACE 0
#define TRACE_END() do {} while (0)
#define TRACE_TAIL(j) do { const int v_ = warp * 64 + i; TRACE_S(44 + j, v_, 0); TRACE_S(50 + j, v_, 4); TRACE_S(52 + j, v_, TAIL); TRACE_S(56 + j, v_, 4 * TAIL - 1); } while (0)
#define TRACE_STEP(t, k, i) do {} while (0)

__device__ __forceinline__ uint32_t smem_u32(const void* p) { return (uint32_t)__cvta_generic_to_shared(p); }
__device__ __forceinline__ void mbar_init(uint32_t bar, uint32_t cnt) {
    asm volatile("mbarrier.init.shared::cta.b64 [%0], %1;" :: "r"(bar), "r"(cnt) : "memory");
}
__device__ __forceinline__ void mbar_expect_tx(uint32_t bar, uint32_t bytes) {
    asm volatile("mbarrier.arrive.expect_tx.shared::cta.b64 _, [%0], %1;" :: "r"(bar), "r"(bytes) : "memory");
}
__device__ __forceinline__ void mbar_arrive(uint32_t bar) {
    asm volatile("mbarrier.arrive.shared::cta.b64 _, [%0];" :: "r"(bar) : "memory");
}
__device__ __forceinline__ void mbar_arrive_cluster(uint32_t bar, uint32_t cta) {
    asm volatile("{\n.reg .b32 ra;\nmapa.shared::cluster.u32 ra, %0, %1;\nmbarrier.arrive.shared::cluster.b64 _, [ra];\n}"
                 :: "r"(bar), "r"(cta) : "memory");
}
__device__ __forceinline__ bool mbar_try_wait(uint32_t bar, uint32_t parity) {
    uint32_t ok;
    asm volatile("{\n.reg .pred p;\nmbarrier.try_wait.parity.shared::cta.b64 p, [%1], %2;\nselp.u32 %0, 1, 0, p;\n}"
                 : "=r"(ok) : "r"(bar), "r"(parity) : "memory");
    return ok;
}
__device__ __forceinline__ bool mbar_test(uint32_t bar, uint32_t parity) {
    uint32_t ok;
    asm volatile("{\n.reg .pred p;\nmbarrier.test_wait.parity.shared::cta.b64 p, [%1], %2;\nselp.u32 %0, 1, 0, p;\n}"
                 : "=r"(ok) : "r"(bar), "r"(parity) : "memory");
    return ok;
}
__device__ __forceinline__ void mbar_wait(uint32_t bar, uint32_t parity) {
#pragma unroll 1
    for (int spins = 0; !mbar_try_wait(bar, parity) && spins < (1 << 17); spins++) {}
}
template <bool WARP = false> __device__ __forceinline__ void flag_wait(const unsigned* p, unsigned target) {
#pragma unroll 1
    for (int spins = 0; spins < (1 << 19); spins++) {
        unsigned v;
        asm volatile("ld.acquire.gpu.global.u32 %0, [%1];" : "=r"(v) : "l"(p) : "memory");
        if (WARP ? __all_sync(0xffffffffu, (int)(v - target) >= 0) : (int)(v - target) >= 0) break;
        __nanosleep(64);
    }
}
__device__ __forceinline__ void mbar_wait_warp(uint32_t bar, uint32_t parity) {
#pragma unroll 1
    for (int spins = 0; !__all_sync(0xffffffffu, mbar_try_wait(bar, parity)) && spins < (1 << 17); spins++) {}
}
__device__ __forceinline__ void flag_add(unsigned* p) {
    asm volatile("red.release.gpu.global.add.u32 [%0], 1;" :: "l"(p) : "memory");
}
__device__ __forceinline__ bool elect_one() {
    uint32_t ok;
    asm volatile("{\n.reg .pred p;\nelect.sync _|p, 0xffffffff;\nselp.u32 %0, 1, 0, p;\n}" : "=r"(ok));
    return ok;
}
__device__ __forceinline__ uint32_t pick(bool c, uint32_t a, uint32_t b) {
    uint32_t r;
    asm("{\n.reg .pred p;\nsetp.ne.b32 p, %3, 0;\nselp.b32 %0, %1, %2, p;\n}" : "=r"(r) : "r"(a), "r"(b), "r"((uint32_t)c));
    return r;
}
__device__ __forceinline__ void fence_proxy_async() { asm volatile("fence.proxy.async.global;" ::: "memory"); }
__device__ __forceinline__ uint4 lds128(uint32_t addr) {
    uint4 v;
    asm volatile("ld.shared.v4.u32 {%0,%1,%2,%3}, [%4];" : "=r"(v.x), "=r"(v.y), "=r"(v.z), "=r"(v.w) : "r"(addr) : "memory");
    return v;
}
__device__ __forceinline__ float2 lds64f(uint32_t addr) {
    float2 v;
    asm volatile("ld.shared.v2.f32 {%0,%1}, [%2];" : "=f"(v.x), "=f"(v.y) : "r"(addr) : "memory");
    return v;
}
__device__ __forceinline__ void sts128(uint32_t addr, uint4 v) {
    asm volatile("st.shared.v4.u32 [%0], {%1,%2,%3,%4};" :: "r"(addr), "r"(v.x), "r"(v.y), "r"(v.z), "r"(v.w) : "memory");
}
__device__ __forceinline__ void sts64f(uint32_t addr, float a, float b) {
    asm volatile("st.shared.v2.f32 [%0], {%1,%2};" :: "r"(addr), "f"(a), "f"(b) : "memory");
}

__device__ __forceinline__ uint64_t stream_policy() { return 0x12F0000000000000ull; }
__device__ __forceinline__ void tma_2d(uint32_t dst, const CUtensorMap* m, uint32_t bar, int c0, int c1, uint64_t pol) {
    asm volatile("cp.async.bulk.tensor.2d.shared::cluster.global.mbarrier::complete_tx::bytes.L2::cache_hint"
                 " [%0], [%1, {%3, %4}], [%2], %5;"
                 :: "r"(dst), "l"(m), "r"(bar), "r"(c0), "r"(c1), "l"(pol) : "memory");
}
__device__ __forceinline__ void tma_3d(uint32_t dst, const CUtensorMap* m, uint32_t bar, int c0, int c1, int c2, uint64_t pol) {
    asm volatile("cp.async.bulk.tensor.3d.shared::cluster.global.mbarrier::complete_tx::bytes.L2::cache_hint"
                 " [%0], [%1, {%3, %4, %5}], [%2], %6;"
                 :: "r"(dst), "l"(m), "r"(bar), "r"(c0), "r"(c1), "r"(c2), "l"(pol) : "memory");
}
__device__ __forceinline__ void tma_3d_mc(uint32_t dst, const CUtensorMap* m, uint32_t bar, int c1, int c2, uint64_t pol) {
    asm volatile("cp.async.bulk.tensor.3d.shared::cluster.global.mbarrier::complete_tx::bytes.multicast::cluster.L2::cache_hint"
                 " [%0], [%1, {%3, %4, %5}], [%2], %6, %7;"
                 :: "r"(dst), "l"(m), "r"(bar), "r"(0), "r"(c1), "r"(c2), "h"((uint16_t)3), "l"(pol) : "memory");
}
__device__ __forceinline__ void load_stage1(uint32_t dst, uint32_t dst_b, uint32_t bar, const CUtensorMap* ma, const CUtensorMap* mb,
                                            int k, int row, int col, int keep_a, uint64_t pol) {
    asm volatile("{\n.reg .pred e, p, q;\nelect.sync _|e, 0xffffffff;\nsetp.ne.and.b32 p|q, %8, 0, e;\n"
        "@p cp.async.bulk.tensor.2d.shared::cluster.global.mbarrier::complete_tx::bytes [%0], [%3, {%5, %6}], [%2];\n"
        "@q cp.async.bulk.tensor.2d.shared::cluster.global.mbarrier::complete_tx::bytes.L2::cache_hint [%0], [%3, {%5, %6}], [%2], %9;\n"
        "@e cp.async.bulk.tensor.3d.shared::cluster.global.mbarrier::complete_tx::bytes.multicast::cluster.L2::cache_hint"
        " [%1], [%4, {%10, %5, %7}], [%2], %11, %9;\n"
        "@e mbarrier.arrive.expect_tx.shared::cta.b64 _, [%2], %12;\n}"
        :: "r"(dst), "r"(dst_b), "r"(bar), "l"(ma), "l"(mb), "r"(k), "r"(row), "r"(col), "r"(keep_a), "l"(pol), "r"(0),
           "h"((uint16_t)3), "n"(G1_STAGE_BYTES) : "memory");
}
__device__ __forceinline__ void load_stage2(uint32_t dst, uint32_t dst_b, uint32_t bar, const CUtensorMap* ma, const CUtensorMap* mb,
                                            int ka, int row, int col, int kb, uint64_t pol) {
    asm volatile("{\n.reg .pred e;\nelect.sync _|e, 0xffffffff;\n"
        "@e cp.async.bulk.tensor.3d.shared::cluster.global.mbarrier::complete_tx::bytes.L2::cache_hint [%0], [%3, {%5, %10, %6}], [%2], %9;\n"
        "@e cp.async.bulk.tensor.5d.shared::cluster.global.mbarrier::complete_tx::bytes.multicast::cluster.L2::cache_hint"
        " [%1], [%4, {%7, %10, %10, %10, %8}], [%2], %11, %9;\n"
        "@e mbarrier.arrive.expect_tx.shared::cta.b64 _, [%2], %12;\n}"
        :: "r"(dst), "r"(dst_b), "r"(bar), "l"(ma), "l"(mb), "r"(ka), "r"(row), "r"(col), "r"(kb), "l"(pol), "r"(0),
           "h"((uint16_t)3), "n"(G2_STAGE_BYTES) : "memory");
}
__device__ __forceinline__ void tma_store_2d(const CUtensorMap* m, uint32_t src, int c0, int c1) {
    asm volatile("cp.async.bulk.tensor.2d.global.shared::cta.bulk_group [%0, {%2, %3}], [%1];"
                 :: "l"(m), "r"(src), "r"(c0), "r"(c1) : "memory");
}
__device__ __forceinline__ uint4 ldg_stream(const void* p, uint64_t pol) {
    uint4 v;
    asm volatile("ld.global.nc.L1::no_allocate.L2::cache_hint.v4.u32 {%0,%1,%2,%3}, [%4], %5;"
                 : "=r"(v.x), "=r"(v.y), "=r"(v.z), "=r"(v.w) : "l"(p), "l"(pol));
    return v;
}
__device__ __forceinline__ void st_tagged(void* p, float a, float b, uint32_t tag) {
    asm volatile("st.relaxed.gpu.global.v2.b32 [%0], {%1,%2};"
                 :: "l"(p), "r"((__float_as_uint(a) & ~3u) | tag), "r"((__float_as_uint(b) & ~3u) | tag) : "memory");
}
__device__ __forceinline__ bool untagged(const uint4& v, uint32_t tag) {
    return ((v.x ^ tag) | (v.y ^ tag) | (v.z ^ tag) | (v.w ^ tag)) & 3;
}
__device__ __forceinline__ uint4 ld_relaxed(const void* p) {
    uint4 v;
    asm volatile("ld.relaxed.gpu.global.v4.b32 {%0,%1,%2,%3}, [%4];" : "=r"(v.x), "=r"(v.y), "=r"(v.z), "=r"(v.w) : "l"(p) : "memory");
    return v;
}
__device__ __forceinline__ void prefetch_3d(const CUtensorMap* m, int c1, int c2, uint64_t pol) {
    asm volatile("cp.async.bulk.prefetch.tensor.3d.L2.global.L2::cache_hint [%0, {%1, %2, %3}], %4;"
                 :: "l"(m), "r"(0), "r"(c1), "r"(c2), "l"(pol) : "memory");
}
__device__ __forceinline__ void prefetch_map(const CUtensorMap* m) {
    asm volatile("prefetch.tensormap [%0];" :: "l"(m) : "memory");
}
template <int N> __device__ __forceinline__ void wg_wait() { asm volatile("wgmma.wait_group.sync.aligned %0;" :: "n"(N) : "memory"); }

__device__ __forceinline__ uint32_t desc_a(uint32_t addr) { return (addr & 0x3FFFF) >> 4 | 1 << 16; }
__device__ __forceinline__ uint32_t desc_b(uint32_t addr) { return (addr & 0x3FFFF) >> 4 | 512 << 16; }

#define R8(d, o) "+f"(d[o]), "+f"(d[o+1]), "+f"(d[o+2]), "+f"(d[o+3]), "+f"(d[o+4]), "+f"(d[o+5]), "+f"(d[o+6]), "+f"(d[o+7])
#define R32(d, o) R8(d, o), R8(d, o+8), R8(d, o+16), R8(d, o+24)
#define R64(d, o) R32(d, o), R32(d, o+32)
#define ACC0 "%0,%1,%2,%3,%4,%5,%6,%7,%8,%9,%10,%11,%12,%13,%14,%15,%16,%17,%18,%19,%20,%21,%22,%23,%24,%25,%26,%27,%28,%29,%30,%31,"\
    "%32,%33,%34,%35,%36,%37,%38,%39,%40,%41,%42,%43,%44,%45,%46,%47,%48,%49,%50,%51,%52,%53,%54,%55,%56,%57,%58,%59,%60,%61,%62,%63"
#define ACC1 "%64,%65,%66,%67,%68,%69,%70,%71,%72,%73,%74,%75,%76,%77,%78,%79,%80,%81,%82,%83,%84,%85,%86,%87,%88,%89,%90,%91,%92,%93,%94,%95,"\
    "%96,%97,%98,%99,%100,%101,%102,%103,%104,%105,%106,%107,%108,%109,%110,%111"
#define ACC64 "{" ACC0 "}"
#define ACC112 "{" ACC0 "," ACC1 "}"
#define ACC128 "{" ACC0 "," ACC1 ",%112,%113,%114,%115,%116,%117,%118,%119,%120,%121,%122,%123,%124,%125,%126,%127}"
#define MMA_K16(shape, acc, keep, hb, sb) \
    "mov.b64 da, {la, 0x40000040};\nmov.b64 db, {lb, " hb "};\n" \
    "wgmma.mma_async.sync.aligned." shape ".f32.bf16.bf16 " acc ", da, db, " keep ", 1, 1, 0, 1;\n" \
    "add.u32 la, la, 2;\nadd.u32 lb, lb, " sb ";\n"
#define MMA_STEP_B(shape, acc, a, b, off, keep, hb, sb) \
    "{\n.reg .pred p, q;\n.reg .b32 la, lb;\n.reg .b64 da, db;\nsetp.ne.b32 p, " keep ", 0;\nsetp.eq.b32 q, 0, 0;\n" \
    "add.u32 la, " a ", " off ";\nadd.u32 lb, " b ", " off ";\nwgmma.fence.sync.aligned;\n" \
    MMA_K16(shape, acc, "p", hb, sb) MMA_K16(shape, acc, "q", hb, sb) MMA_K16(shape, acc, "q", hb, sb) \
    MMA_K16(shape, acc, "q", hb, sb) "wgmma.commit_group.sync.aligned;\n}"
#define MMA_STEP(shape, acc, a, b, off, keep) MMA_STEP_B(shape, acc, a, b, off, keep, "0x40000040", "128")

__device__ __forceinline__ void mma_step(float (&d)[128], uint32_t da, uint32_t db, uint32_t off, int keep) {
    asm volatile(MMA_STEP("m64n256k16", ACC128, "%128", "%129", "%130", "%131")
                 : R64(d, 0), R64(d, 64) : "r"(da), "r"(db), "r"(off), "r"(keep) : "memory");
}
__device__ __forceinline__ void mma_rank(float (&d)[128], uint32_t a0, uint32_t a1, uint32_t db) {
    asm volatile("{\n.reg .pred q;\n.reg .b64 db;\nsetp.eq.b32 q, 0, 0;\nmov.b64 db, {%131, 0x40000040};\nwgmma.fence.sync.aligned;\n"
                 "wgmma.mma_async.sync.aligned.m64n256k16.f32.bf16.bf16 " ACC128 ", {%128, %129, %130, %130}, db, q, 1, 1, 1;\n}"
                 : R64(d, 0), R64(d, 64) : "r"(a0), "r"(a1), "r"(0), "r"(db) : "memory");
}
__device__ __forceinline__ void mma_step224(float (&d)[128], uint32_t da, uint32_t db, uint32_t off, int keep) {
    asm volatile(MMA_STEP("m64n224k16", ACC112, "%112", "%113", "%114", "%115")
                 : R64(d, 0), R32(d, 64), R8(d, 96), R8(d, 104) : "r"(da), "r"(db), "r"(off), "r"(keep) : "memory");
}
__device__ __forceinline__ void mma_step(float (&d)[64], uint32_t da, uint32_t db, uint32_t off, int keep) {
    asm volatile(MMA_STEP("m64n128k16", ACC64, "%64", "%65", "%66", "%67")
                 : R64(d, 0) : "r"(da), "r"(db), "r"(off), "r"(keep) : "memory");
}

__device__ __forceinline__ void mma_step_tail(float (&d)[128], uint32_t da, uint32_t b, uint32_t off, int keep) {
    asm volatile(MMA_STEP_B("m64n256k16", ACC128, "%128", "%129", "%130", "%131", "0x80000020", "64")
                 : R64(d, 0), R64(d, 64) : "r"(da), "r"((b & 0x3FFFF) >> 4 | 256 << 16), "r"(off), "r"(keep) : "memory");
}

__device__ __forceinline__ uint32_t pack_bf16(float lo, float hi) {
    uint32_t r; asm("cvt.rn.bf16x2.f32 %0, %1, %2;" : "=r"(r) : "f"(hi), "f"(lo)); return r;
}
__device__ __forceinline__ float bf_lo(uint32_t v) { return __uint_as_float(v << 16); }
__device__ __forceinline__ float bf_hi(uint32_t v) { return __uint_as_float(v & 0xffff0000u); }
__device__ __forceinline__ float round_bf16(float v) { return bf_lo(pack_bf16(v, 0.f)); }
__device__ __forceinline__ uint32_t mul_bf16x2(uint32_t a, uint32_t b) {
    uint32_t r; asm("mul.rn.bf16x2 %0, %1, %2;" : "=r"(r) : "r"(a), "r"(b)); return r;
}
__device__ __forceinline__ uint32_t add_bf16x2(uint32_t a, uint32_t b) {
    uint32_t r; asm("add.rn.bf16x2 %0, %1, %2;" : "=r"(r) : "r"(a), "r"(b)); return r;
}
__device__ __forceinline__ uint32_t sub_bf16x2(uint32_t a, uint32_t b) {
    uint32_t r; asm("sub.rn.bf16x2 %0, %1, %2;" : "=r"(r) : "r"(a), "r"(b)); return r;
}
__device__ __forceinline__ uint32_t mul2_bf16x2(uint32_t a, uint32_t hi, uint32_t lo) {
    uint32_t r; asm("fma.rn.bf16x2 %0, %1, %2, %3;" : "=r"(r) : "r"(a), "r"(hi), "r"(mul_bf16x2(a, lo))); return r;
}
__device__ __forceinline__ float tanh_fast(float x) { float r; asm("tanh.approx.f32 %0, %1;" : "=f"(r) : "f"(x)); return r; }
__device__ __forceinline__ float gelu_tanh(float g) {
    float t = fmaf(g * g, 0.044715f * 0.7978845608f, 0.7978845608f) * g;
    float hg = 0.5f * g;
    return fmaf(hg, tanh_fast(t), hg);
}
__device__ __forceinline__ uint32_t geglu2(uint32_t g2, uint32_t u2) {
    return mul_bf16x2(pack_bf16(gelu_tanh(bf_lo(g2)), gelu_tanh(bf_hi(g2))), u2);
}
__device__ __forceinline__ float silu(float d) {
    float hd = 0.5f * d;
    return fmaf(hd, tanh_fast(hd), hd);
}
__device__ __forceinline__ float ex2_fast(float x) { float r; asm("ex2.approx.ftz.f32 %0, %1;" : "=f"(r) : "f"(x)); return r; }
__device__ __forceinline__ void unpack8(uint4 v, float (&f)[8]) {
    f[0] = bf_lo(v.x); f[1] = bf_hi(v.x); f[2] = bf_lo(v.y); f[3] = bf_hi(v.y);
    f[4] = bf_lo(v.z); f[5] = bf_hi(v.z); f[6] = bf_lo(v.w); f[7] = bf_hi(v.w);
}
template <int N> __device__ __forceinline__ void fence_regs(float (&d)[N]) {
#pragma unroll
    for (int i = 0; i < N; i++) asm volatile("" : "+f"(d[i]) :: "memory");
}

__device__ __forceinline__ float rcp_fast(float x) { float r; asm("rcp.approx.ftz.f32 %0, %1;" : "=f"(r) : "f"(x)); return r; }
__device__ __forceinline__ float sqrt_fast(float x) { float r; asm("sqrt.approx.ftz.f32 %0, %1;" : "=f"(r) : "f"(x)); return r; }
__device__ __forceinline__ uint32_t max_bf16x2(uint32_t a, uint32_t b) {
    uint32_t r; asm("max.bf16x2 %0, %1, %2;" : "=r"(r) : "r"(a), "r"(b)); return r;
}
__device__ __forceinline__ uint4 ldsm4(uint32_t addr) {
    uint4 v;
    asm volatile("ldmatrix.sync.aligned.m8n8.x4.shared.b16 {%0,%1,%2,%3}, [%4];"
                 : "=r"(v.x), "=r"(v.y), "=r"(v.z), "=r"(v.w) : "r"(addr) : "memory");
    return v;
}
__device__ __forceinline__ uint4 ldsm4_t(uint32_t addr) {
    uint4 v;
    asm volatile("ldmatrix.sync.aligned.m8n8.x4.trans.shared.b16 {%0,%1,%2,%3}, [%4];"
                 : "=r"(v.x), "=r"(v.y), "=r"(v.z), "=r"(v.w) : "r"(addr) : "memory");
    return v;
}
__device__ __forceinline__ void mma_16816(float (&c)[4], uint32_t a0, uint32_t a1, uint32_t a2, uint32_t a3, uint32_t b0, uint32_t b1) {
    asm("mma.sync.aligned.m16n8k16.row.col.f32.bf16.bf16.f32 {%0,%1,%2,%3}, {%4,%5,%6,%7}, {%8,%9}, {%0,%1,%2,%3};"
        : "+f"(c[0]), "+f"(c[1]), "+f"(c[2]), "+f"(c[3]) : "r"(a0), "r"(a1), "r"(a2), "r"(a3), "r"(b0), "r"(b1));
}
__device__ __forceinline__ void mma_1688(float (&c)[4], uint32_t a0, uint32_t a1, uint32_t b0) {
    asm("mma.sync.aligned.m16n8k8.row.col.f32.bf16.bf16.f32 {%0,%1,%2,%3}, {%4,%5}, {%6}, {%0,%1,%2,%3};"
        : "+f"(c[0]), "+f"(c[1]), "+f"(c[2]), "+f"(c[3]) : "r"(a0), "r"(a1), "r"(b0));
}
__device__ __forceinline__ void qk_tile(float (&c)[4], const uint4& q0, const uint4& q1, const uint4& k, float init) {
    c[0] = c[1] = c[2] = c[3] = init;
    mma_16816(c, q0.x, q0.y, q0.z, q0.w, k.x, k.y);
    mma_16816(c, q1.x, q1.y, q1.z, q1.w, k.z, k.w);
}
__device__ __forceinline__ uint32_t scaled_logits(bool first, float a0, float a1, float b0, float b1) {
    return mul2_bf16x2(pack_bf16(first ? a0 : b0, first ? a1 : b1), 0x3e353e35u, 0x379e379eu);
}
template <typename T> __device__ __forceinline__ T uniform(T v) { return __shfl_sync(0xffffffffu, v, 0); }

__device__ __forceinline__ void attention(const Params& prm, uint32_t base, unsigned epoch, int grp, int warp, int lane) {
    constexpr float LOG2E = 1.4426950408889634f;
    const int g = lane >> 2, t = lane & 3;
    const bool up0 = 2 * t > g, up1 = 2 * t + 1 > g;
    const uint32_t keep = (up0 ? 0x0000ffffu : 0u) | (up1 ? 0xffff0000u : 0u);
    const uint32_t buf = base + warp * 2 * ATT_SLOT, bar = base + AUX_OFF + warp * 16;
    const uint32_t qoff = (lane & 15) * 128 + (((lane >> 4) ^ (lane & 7)) << 4);
    const uint32_t koff = 2048 + (lane & 7) * 128 + (((lane >> 3) ^ (lane & 7)) << 4);
    const uint32_t rest_bar = base + AUX_OFF + 192;
    const int col = uniform(grp * 256), first = uniform((warp / 3 * 32 + warp % 3 * 11) * 16);
    const CUtensorMap* const mqk = reinterpret_cast<const CUtensorMap*>(uniform(reinterpret_cast<uint64_t>(&prm.qk)));
    const CUtensorMap *const mv = mqk + 1, *const mo = mqk + 2;
    const uint64_t pol = stream_policy();
    const uint32_t zero = prm.zero;
    uint4 kp[2], vp[2];
    uint32_t l0[2], l1[2], m[2];
    float s[2][3][4];
    auto scores = [&](uint32_t st, int row) {
        const float before = (row & 1023) == 0 ? -5.656854e9f : 0.f;
#pragma unroll
        for (int h = 0; h < 2; h++) {
            const uint4 q0 = ldsm4(st + (qoff ^ (h * 64))), q1 = ldsm4(st + (qoff ^ (h * 64 + 32)));
            const uint4 k0 = ldsm4(st + (koff ^ (h * 64))), k1 = ldsm4(st + 1024 + (koff ^ (h * 64)));
            qk_tile(s[h][0], q0, q1, kp[h], before);
            qk_tile(s[h][1], q0, q1, k0, 0.f);
            qk_tile(s[h][2], q0, q1, k1, 0.f);
            kp[h] = k1;
        }
    };
    auto logits = [&]() {
#pragma unroll
        for (int h = 0; h < 2; h++) {
            l0[h] = scaled_logits(up0, s[h][0][0], s[h][1][2], s[h][1][0], s[h][2][2]);
            l1[h] = scaled_logits(up1, s[h][0][1], s[h][1][3], s[h][1][1], s[h][2][3]);
            m[h] = max_bf16x2(l0[h], l1[h]);
            m[h] = max_bf16x2(m[h], __shfl_xor_sync(0xffffffffu, m[h], 1));
        }
    };
    auto row_max = [&]() {
#pragma unroll
        for (int h = 0; h < 2; h++) m[h] = max_bf16x2(m[h], __shfl_xor_sync(0xffffffffu, m[h], 2));
    };
    auto next = [](uint32_t p) {
        return (0x80200400u >> (p >> 4 & 31) & 1) > (p >> 15 & 1) ? p + (64 << 16) + 0x8000 : (p + 16) & ~0x8800u;
    };
    auto exchange = [&](uint32_t st, uint32_t b, uint32_t po, uint32_t pv, uint32_t pq) {
        asm volatile("{\n.reg .pred e, p, q;\n"
            "fence.proxy.async.shared::cta;\n"
            "bar.warp.sync 0xffffffff;\n"
            "elect.sync _|e, 0xffffffff;\n"
            "setp.eq.and.b32 p, %12, 0, e;\n"
            "setp.lt.and.s32 q, %8, %13, e;\n"
            "@q mbarrier.arrive.expect_tx.shared::cta.b64 _, [%2], 6144;\n"
            "@q cp.async.bulk.tensor.3d.shared::cluster.global.mbarrier::complete_tx::bytes.L2::cache_hint [%0], [%3, {%6, %7, %14}], [%2], %15;\n"
            "@q cp.async.bulk.tensor.2d.shared::cluster.global.mbarrier::complete_tx::bytes.L2::cache_hint [%0 + 4096], [%4, {%8, %9}], [%2], %15;\n"
            "@e cp.async.bulk.wait_group.read 0;\n"
            "@p cp.async.bulk.tensor.2d.global.shared::cta.bulk_group [%5, {%10, %11}], [%1 + 6144];\n"
            "@e cp.async.bulk.commit_group;\n"
            "bar.warp.sync 0xffffffff;\n}"
            :: "r"(st), "r"(st ^ ATT_SLOT), "r"(b), "l"(mqk), "l"(mv), "l"(mo), "r"(pq >> 16), "r"(pq & 2047),
               "r"((pv >> 16) + 2 * DM), "r"(pv & 2047), "r"(po >> 16), "r"(po & 2047), "r"(po & 0x8000),
               "r"(col + 256 + 2 * DM), "r"(0), "l"(pol) : "memory");
    };
    auto publish = [&](auto pending, int part) {
        asm volatile("{\n.reg .pred e;\n.reg .u32 n;\n"
            "elect.sync _|e, 0xffffffff;\n"
            "cp.async.bulk.wait_group %2;\n"
            "@e atom.acq_rel.cta.shared.add.u32 n, [%1], 1;\n"
            "setp.eq.and.u32 e, n, 11, e;\n"
            "@e red.release.gpu.global.add.u32 [%0], 1;\n}"
            :: "l"(prm.flags + F_O * 512 + part * 32), "r"(rest_bar + 8 + part * 4), "n"(pending.value) : "memory");
    };
    if (elect_one()) {
        mbar_init(bar, 1); mbar_init(bar + 8, 1);
        if (warp == 2) { mbar_init(rest_bar, 32); sts64f(rest_bar + 8, 0.f, 0.f); }
        asm volatile("fence.mbarrier_init.release.cluster;" ::: "memory");
        if (warp == 9) {
            prefetch_map(mqk); prefetch_map(mv); prefetch_map(mo);
            flag_wait(prm.flags + F_QKV * 512 + grp * 32, epoch * CNT_QKV);
        }
    }
    __syncthreads();
    if (elect_one()) {
        fence_proxy_async();
        mbar_expect_tx(bar + 8, 8192);
        tma_3d(buf + ATT_SLOT, mqk, bar + 8, col, first, 0, pol);
        tma_2d(buf + ATT_SLOT + 4096, mv, bar + 8, col + 2 * DM, first - 16, pol);
        tma_2d(buf + ATT_SLOT + 6144, mv, bar + 8, col + DM, first - 16, pol);
        mbar_expect_tx(bar, 6144);
        tma_3d(buf, mqk, bar, col, first + 16, 0, pol);
        tma_2d(buf + 4096, mv, bar, col + 2 * DM, first, pol);
        if (warp == 0) TRACE(9);
        if (warp == 9) prm.epoch[blockIdx.x * 16] = epoch;
    }
    __syncwarp();
    if (TAIL && warp == 11 && lane == 0) flag_add(prm.flags + F_TAIL * 512 + (grp * 4 + 3) * 32);
    mbar_wait(bar + 8, 0);
#pragma unroll
    for (int h = 0; h < 2; h++) {
        kp[h] = ldsm4(buf + ATT_SLOT + 5120 + (koff ^ (h * 64)));
        vp[h] = ldsm4_t(buf + ATT_SLOT + 3072 + (koff ^ (h * 64)));
    }
    scores(buf + ATT_SLOT, first);
    uint32_t pm = 0x8000, p0 = col << 16 | first, p1 = p0 + 16, p2 = p0 + 32, p3 = p0 + 48;
    exchange(buf + ATT_SLOT, bar + 8, pm, p1, p2);
    logits();
    row_max();
    uint32_t st = buf, b = bar, cnt = 1;
    const uint32_t relay = warp == 2 ? 7 : 0;
    bool ready = false;
#pragma unroll 1
    while (p0 >> 16 < col + 256) {
        uint32_t pa[2], pb[2];
        if (!ready) mbar_wait(b, (cnt >> 1) & 1);
        uint4 v[2][2];
#pragma unroll
        for (int h = 0; h < 2; h++) {
            const float ma = -LOG2E * bf_lo(m[h]), mb = -LOG2E * bf_hi(m[h]);
            const float a0 = ex2_fast(fmaf(bf_lo(l0[h]), LOG2E, ma)), a1 = ex2_fast(fmaf(bf_lo(l1[h]), LOG2E, ma));
            const float b0 = ex2_fast(fmaf(bf_hi(l0[h]), LOG2E, mb)), b1 = ex2_fast(fmaf(bf_hi(l1[h]), LOG2E, mb));
            float sum[4] = {0.f, 0.f, 0.f, 0.f};
            mma_1688(sum, pack_bf16(a0, a1), pack_bf16(b0, b1), 0x3f803f80u);
            const float ra = rcp_fast(sum[0]), rb = rcp_fast(sum[2]);
            pa[h] = pack_bf16(a0 * ra, a1 * ra);
            pb[h] = pack_bf16(b0 * rb, b1 * rb);
        }
        scores(st, p1);
#pragma unroll
        for (int h = 0; h < 2; h++) {
            v[h][0] = ldsm4_t(st + 4096 + (qoff ^ (h * 64)));
            v[h][1] = ldsm4_t(st + 4096 + (qoff ^ (h * 64 + 32)));
        }
        if (cnt == relay) {
            flag_wait<true>(prm.flags + F_QKV * 512 + 128 + grp * 32, epoch * CNT_QKV);
            fence_proxy_async();
            mbar_arrive(rest_bar);
        }
        if (cnt == 8) {
#pragma unroll 1
            for (int spins = 0; !__all_sync(0xffffffffu, mbar_try_wait(rest_bar, 0)) && spins < (1 << 17); spins++) {}
        }
        if (cnt == 37) publish(std::integral_constant<int, 1>(), 0);
        exchange(st, b, pm, p2, p3);
        pm = p0; p0 = p1; p1 = p2; p2 = p3; p3 = next(p3);
        logits();
        float o[2][4][4];
#pragma unroll
        for (int h = 0; h < 2; h++) {
            const uint32_t prev[4] = {vp[h].x, vp[h].y, vp[h].z, vp[h].w};
            const uint32_t own[8] = {v[h][0].x, v[h][0].y, v[h][0].z, v[h][0].w, v[h][1].x, v[h][1].y, v[h][1].z, v[h][1].w};
            const uint32_t a0 = pa[h] & keep, a1 = pa[h] & ~keep, a2 = pb[h] & keep, a3 = pb[h] & ~keep;
            const uint32_t z0 = pa[h] & zero, z1 = pb[h] & zero;
#pragma unroll
            for (int j = 0; j < 4; j++) {
                o[h][j][0] = o[h][j][1] = o[h][j][2] = o[h][j][3] = 0.f;
                mma_1688(o[h][j], a0, z0, prev[j]);
                mma_16816(o[h][j], a1, a2, z1, a3, own[2 * j], own[2 * j + 1]);
            }
            vp[h] = make_uint4(own[1], own[3], own[5], own[7]);
        }
        row_max();
        b ^= 8; cnt++;
        ready = mbar_test(b, (cnt >> 1) & 1);
#pragma unroll
        for (int h = 0; h < 2; h++) {
#pragma unroll
            for (int d = 0; d < 2; d++)
                asm volatile("stmatrix.sync.aligned.m8n8.x4.shared.b16 [%0], {%1,%2,%3,%4};"
                             :: "r"(st + 6144 + (qoff ^ (h * 64 + d * 32))),
                                "r"(pack_bf16(o[h][2 * d][0], o[h][2 * d][1])), "r"(pack_bf16(o[h][2 * d][2], o[h][2 * d][3])),
                                "r"(pack_bf16(o[h][2 * d + 1][0], o[h][2 * d + 1][1])),
                                "r"(pack_bf16(o[h][2 * d + 1][2], o[h][2 * d + 1][3])) : "memory");
        }
        st ^= ATT_SLOT;
    }
    exchange(st, b, pm, p0, p0);
    publish(std::integral_constant<int, 0>(), 1);
    if (threadIdx.x == 0) { TRACE(10); TRACE_DUMP(); }
}

__device__ __forceinline__ void tail_gemm(const Params& prm, uint32_t base, unsigned epoch, int grp, int warp, int lane) {
    const uint32_t full = base + BAR_OFF, empty = full + 320, sig = full + 192, dep = full + 256;
    unsigned* const flags = prm.flags + grp * 128;
    if (warp == 8) {
        if (elect_one()) { prefetch_map(&prm.xn); prefetch_map(&prm.wtail); }
        flag_wait<true>(flags + F_LN * 512 + (lane & 3) * 32, epoch * CNT_LN);
        fence_proxy_async();
        TRACE(62);
#pragma unroll 1
        for (int i = 0, k = 0, row = grp * 512; i < 4 * TAIL; i++) {
            if (i == 8) mbar_wait_warp(dep, 0);
            mbar_wait_warp(empty + (i & 3) * 8, ~i >> 2 & 1);
            asm volatile("{\n.reg .pred e;\nelect.sync _|e, 0xffffffff;\n"
                "@e cp.async.bulk.tensor.2d.shared::cluster.global.mbarrier::complete_tx::bytes [%0], [%2, {%4, %5}], [%1];\n"
                "@e cp.async.bulk.tensor.3d.shared::cluster.global.mbarrier::complete_tx::bytes [%0 + 16384], [%3, {%6, %4, %6}], [%1];\n"
                "@e mbarrier.arrive.expect_tx.shared::cta.b64 _, [%1], %7;\n}"
                :: "r"(base + (i & 3) * G1_STAGE_BYTES), "r"(full + (i & 3) * 8), "l"(&prm.xn), "l"(&prm.wtail), "r"(k), "r"(row),
                   "r"(0), "n"(G1_STAGE_BYTES) : "memory");
            k += 64;
            if (k == TAIL * 64) { k = 0; row += 128; }
        }
    } else if (warp == 10) {
        flag_wait<true>(flags + F_LN2 * 512 + (lane & 3) * 32, epoch * CNT_LN);
        fence_proxy_async();
        __syncwarp();
        if (lane == 0) {
            mbar_arrive(dep);
#pragma unroll 1
            for (int p = 0; p < 3; p++) {
                mbar_wait(sig + p * 8, 0);
                flag_add(flags + F_TAIL * 512 + p * 32);
            }
        }
        __syncwarp();
    } else if (warp < 8) {
        const uint32_t da = desc_a(base + (warp >> 2) * 8192);
        uint4* out = prm.tail + grp * 2048 + threadIdx.x;
        float acc[128];
        int i = 0;
        auto step = [&](int k) {
            TRACE_TAIL(0);
            mbar_wait(full + (i & 3) * 8, i >> 2 & 1);
            TRACE_TAIL(1);
            if (warp >= 4 && k == TAIL - TSK) asm volatile("bar.sync 1, 256;" ::: "memory");
            mma_step_tail(acc, da, base + A_BYTES, (i & 3) * (G1_STAGE_BYTES / 16), k != 0);
            if (warp < 4 && k == TAIL - 1) asm volatile("bar.arrive 1, 256;" ::: "memory");
        };
        auto release = [&]() { if ((threadIdx.x & 127) == 0) mbar_arrive(empty + (i - 1 & 3) * 8); };
#pragma unroll
        for (int j = 0; j < 128; j++) asm volatile("mov.b32 %0, 0;" : "=f"(acc[j]));
#pragma unroll 1
        for (int p = 0; p < 4; p++) {
            step(0);
            i++;
#pragma unroll 1
            for (int k = 1; k < TAIL; k++, i++) {
                __builtin_assume(k != 0);
                step(k);
                wg_wait<1>();
                release();
            }
            wg_wait<0>();
            fence_regs(acc);
            release();
            TRACE_S(48, p + warp * 4, 0);
#pragma unroll
            for (int j = 0; j < 16; j++) {
                const float* a = acc + 8 * j;
                asm volatile("st.global.v4.u32 [%0], {%1,%2,%3,%4};"
                             :: "l"(out + j / 2 * 8192 + j % 2 * 256), "r"(pack_bf16(a[0], a[1])), "r"(pack_bf16(a[2], a[3])),
                                "r"(pack_bf16(a[4], a[5])), "r"(pack_bf16(a[6], a[7])) : "memory");
            }
            __syncwarp();
            if (lane == 0) mbar_arrive(sig + p * 8);
            out += 512;
            TRACE_S(49, p + warp * 4, 0); TRACE_S(58, p + warp * 4, 19);
        }
    }
}

__device__ __forceinline__ bool tile_is_qkv(int nt) { return nt < 4 || (nt >= 8 && nt < 16); }
__device__ __forceinline__ int tile_index(int nt) { return nt < 4 ? nt + 8 : (nt < 8 ? nt - 4 : (nt < 16 ? nt - 8 : nt - 12)); }

struct Role {
    int rank, role, mblk, nslot, w0_col;
    const CUtensorMap* w0;
    __device__ __forceinline__ Role(const Params& prm) {
        uint32_t id;
        asm volatile("mov.u32 %0, %%ctaid.x;" : "=r"(id));
        const uint32_t cl = id / 2;
        rank = id & 1;
        role = pick(cl < 4, 32 + cl * 8, cl - 8 + max(4u, (cl - 1) * 37 >> 8)) * 2 + rank;
        mblk = role & 15; nslot = role >> 4;
        w0 = &prm.wqkv + pick(nslot < 4, 0, 1 + rank);
        w0_col = pick(nslot < 4, 32 + nslot * 4 + rank * 2, nslot * 2 - 8);
    }
};

__global__ void __cluster_dims__(2, 1, 1) __launch_bounds__(384, 1)
fused_kernel(const __grid_constant__ Params prm) {
    TRACE_GET(c0);
    const uint32_t base = smem_u32(smem_raw) & ~1023u;
    const uint32_t bars = base + BAR_OFF;
    auto full1 = [&](int s) { return bars + s * 8; };
    auto empty1 = [&](int s) { return bars + 32 + s * 8; };
    auto full2 = [&](int s) { return bars + 64 + s * 8; };
    auto empty2 = [&](int s) { return bars + 128 + s * 8; };
    const uint32_t sig_bar = bars + 192, dep_bar = bars + 256, cs_bar = bars + 304, fold_bar = bars + 320, x_bar = bars + 352;
    const uint32_t stats = bars + 1536;
    auto stage2 = [&](int q) { return base + q * G2_STAGE_BYTES; };
    const uint32_t aux = base + AUX_OFF;

    asm volatile("{\n.reg .pred p;\nsetp.eq.u32 p, %1, 0;\n@p mbarrier.init.shared::cta.b64 [%0], 1;\n"
        "fence.mbarrier_init.release.cluster;\nbarrier.cluster.arrive.relaxed.aligned;\n}" :: "r"(bars), "r"(threadIdx.x) : "memory");
    const int warp = __shfl_sync(0xffffffffu, threadIdx.x >> 5, 0);
    auto cluster_wait = []() { asm volatile("barrier.cluster.wait.acquire.aligned;" ::: "memory"); };
    if ((warp | (blockIdx.x & NGEMM)) == 8) {
        const Role r(prm);
        asm volatile("{\n.reg .pred e;\nelect.sync _|e, 0xffffffff;\n"
            "@e prefetch.tensormap [%0];\n@e prefetch.tensormap [%1];\n}" :: "l"(&prm.x), "l"(r.w0) : "memory");
        cluster_wait();
        load_stage1(base, base + A_BYTES + r.rank * 16384, full1(0), &prm.x, r.w0, 0, r.mblk * 128, r.w0_col, 0, stream_policy());
    } else {
        cluster_wait();
    }
    const uint32_t t0 = clock();
    asm volatile("{\n.reg .pred e, q;\nelect.sync _|e, 0xffffffff;\nsetp.ne.and.u32 q, %2, 0, e;\n"
        "@q mbarrier.init.shared::cta.b64 [%0], %1;\n@e mbarrier.init.shared::cta.b64 [%0 + 8], %1;\n"
        "@e mbarrier.init.shared::cta.b64 [%0 + 16], %1;\n@e mbarrier.init.shared::cta.b64 [%0 + 24], %1;\n"
        "fence.mbarrier_init.release.cluster;\nbarrier.cluster.arrive.relaxed.aligned;\n}"
        :: "r"(bars + warp * 32), "r"(1 << (0x10fa08 >> warp * 2 & 3)), "r"(warp) : "memory");
    const int lane = threadIdx.x & 31;
    const Role me(prm);
    const int rank = me.rank, role = me.role, mblk = me.mblk, nslot = me.nslot, w0_col = me.w0_col;
    const CUtensorMap* const w0 = me.w0;

    if (blockIdx.x >= NGEMM) {
        if (warp == 9) { TRACE_CLEAR(); TRACE_GT(0); TRACE_PUT(1, c0); }
        cluster_wait();
        const uint32_t seen = __ldcg(prm.epoch + blockIdx.x * 16);
        if (TAIL) tail_gemm(prm, base, seen + 1, blockIdx.x - NGEMM, warp, lane);
        uint32_t tid;
        asm volatile("mov.u32 %0, %%tid.x;" : "=r"(tid));
        attention(prm, (base + 2 * ATT_SLOT - 1) & ~(2u * ATT_SLOT - 1), seen + 1, blockIdx.x - NGEMM, uniform(tid >> 5), tid & 31);
    } else if (warp < 8) {
        asm volatile("setmaxnreg.inc.sync.aligned.u32 %0;" :: "n"(CONSUMER_REGS));
        const int wg = __shfl_sync(0xffffffffu, threadIdx.x >> 7, 0);
        const int cw = threadIdx.x >> 5;
        const int tid = threadIdx.x & 127;
        float acc[128];
        uint32_t pk[64];
#pragma unroll
        for (int i = 0; i < 64; i++) asm volatile("mov.b32 %0, 0;" : "=r"(pk[i]));
#pragma unroll
        for (int i = 0; i < 128; i++) asm volatile("mov.b32 %0, 0;" : "=f"(acc[i]));
        cluster_wait();

        const int orow = ((lane >> 2) & 1) * (SEQ / 2) + mblk * 64 + cw * 8 + (lane >> 3);
        __nv_bfloat16* optr = prm.pxn + (mblk * 128 + nslot * 16 + cw * 2) * DM + lane * 8;
        const uint32_t da = desc_a(base + wg * 8192), db = desc_b(base + A_BYTES);
        auto release = [&](uint32_t bar) { if (tid < 2) mbar_arrive_cluster(bar, tid); };
        auto store_pk = [&](__nv_bfloat16* p, int j) {
            asm volatile("st.global.v4.u32 [%0], {%1,%2,%3,%4};"
                         :: "l"(p), "r"(pk[4 * j]), "r"(pk[4 * j + 1]), "r"(pk[4 * j + 2]), "r"(pk[4 * j + 3]) : "memory");
        };
        auto chunk_geglu = [&](int j) {
#pragma unroll
            for (int i = 4 * j; i < 4 * j + 4; i++) pk[i] = geglu2(pk[i], pk[32 + i]);
            store_pk(optr + (j & 1) * 4 * K2 + (j >> 1) * 32, j);
        };
        auto chunk_qkv = [&](int c) {
            store_pk(optr + c * 32, 2 * c);
            store_pk(optr + 4 * NQKV + c * 32, 2 * c + 1);
        };
        auto signal_stores = [&](int p) { __syncwarp(); if (lane == 0) mbar_arrive(sig_bar + p * 8); };

        auto chunk_ln = [&](int k) {
            float* const mo = reinterpret_cast<float*>(pk + 32);
            if (k == LNL) {
                const uint4* xp = reinterpret_cast<const uint4*>(prm.px + (optr - prm.pxn));
                pk[38] = __ldcg(prm.epoch + blockIdx.x * 16 + 2);
#pragma unroll
                for (int i = 0; i < 8; i++) {
                    const uint4 v = ldg_stream(xp + i * 32, stream_policy());
                    pk[4 * i] = v.x; pk[4 * i + 1] = v.y; pk[4 * i + 2] = v.z; pk[4 * i + 3] = v.w;
                }
            } else if (k >= LN_STEP && k < LN_STEP + 3) {
                if (k == LN_STEP) {
                    mo[0] = bf_lo(uniform(pk[0])); mo[1] = bf_lo(uniform(pk[16]));
                    mo[2] = mo[3] = mo[4] = mo[5] = 0.f;
                }
#pragma unroll
                for (int i = (k - LN_STEP) * 11; i < (k - LN_STEP) * 11 + 11 && i < 32; i++) {
                    const int r = i & 1;
                    const uint32_t w = pk[r * 16 + i / 2];
                    const float lo = bf_lo(w) - mo[r], hi = bf_hi(w) - mo[r];
                    mo[2 + r] += lo + hi;
                    mo[4 + r] = fmaf(hi, hi, fmaf(lo, lo, mo[4 + r]));
                }
            } else if (k == LN_STEP + 3) {
                const bool second = lane & 16;
                float m1 = (second ? mo[3] : mo[2]) + __shfl_xor_sync(0xffffffffu, second ? mo[2] : mo[3], 16);
                float m2 = (second ? mo[5] : mo[4]) + __shfl_xor_sync(0xffffffffu, second ? mo[4] : mo[5], 16);
#pragma unroll
                for (int o = 8; o > 0; o >>= 1) {
                    m1 += __shfl_xor_sync(0xffffffffu, m1, o);
                    m2 += __shfl_xor_sync(0xffffffffu, m2, o);
                }
                m1 *= 1.f / DM;
                const float var = fmaxf(fmaf(-m1, m1, m2 * (1.f / DM)), 0.f);
                const float mean = round_bf16((second ? mo[1] : mo[0]) + m1);
                const float inv = rcp_fast(round_bf16(sqrt_fast(round_bf16(round_bf16(var) + 1e-5f))));
                if ((lane & 15) == 0) st_tagged(prm.stats + (uint32_t)(optr - prm.pxn) / DM + second, -mean, inv, 2 - (pk[38] & 1));
                const uint32_t split = pack_bf16(inv - round_bf16(inv), inv);
#pragma unroll
                for (int r = 0; r < 2; r++) {
                    const uint32_t f = __shfl_sync(0xffffffffu, split, r * 16);
                    pk[32 + 3 * r] = __byte_perm(__shfl_sync(0xffffffffu, __float_as_uint(mean), r * 16), 0, 0x3232);
                    pk[33 + 3 * r] = __byte_perm(f, 0, 0x3232);
                    pk[34 + 3 * r] = __byte_perm(f, 0, 0x1010);
                }
            } else if (k >= LN_STEP + 4 && k < LN_STEP + 8) {
#pragma unroll
                for (int i = k - LN_STEP - 4; i < 8; i += 4) {
                    const uint32_t* n = pk + 32 + i / 4 * 3;
#pragma unroll
                    for (int j = 4 * i; j < 4 * i + 4; j++) pk[j] = mul2_bf16x2(sub_bf16x2(pk[j], n[0]), n[1], n[2]);
                    store_pk(optr + i * 256, i);
                }
                if (k == LN_STEP + 5 || k == LN_STEP + 7) signal_stores(k == LN_STEP + 5 ? 0 : 7);
            } else if (k == FOLD_STEP) {
                mbar_wait(fold_bar, 0);
                const uint32_t sp = stats + (cw * 16 + (lane >> 2)) * 8;
                const uint32_t sel = lane & 2 ? 0x4444 : (lane & 1 ? 0x4432 : 0x3232);
                const float2 sa = lds64f(sp), sb = lds64f(sp + 64);
                mma_rank(acc, __byte_perm(__float_as_uint(sa.x), 0, sel), __byte_perm(__float_as_uint(sb.x), 0, sel), desc_b(aux));
                mo[0] = sa.y; mo[1] = sb.y;
            }
        };

        bool gated = false;
        TRACE_SLOT(tile_slot, 16 + wg * 8);
#pragma unroll 1
        for (int t = 0; t < G1_TILES; t++) {
#pragma unroll
            for (int k = 0; k < G1_KSTEPS; k++) {
                const int s = k & 3;
                TRACE_STEP(t, k, 0);
                mbar_wait(full1(s), (k >> 2) & 1);
                if (k == 0) TRACE_S(12, t, 0);
                TRACE_STEP(t, k, 1);
                if (wg == 1 && k == G1_KSTEPS - (t ? G1_SKEW : SK0)) asm volatile("bar.sync 1, 256;" ::: "memory");
                if (k >= G1_KSTEPS - TAIL && t == G1_TILES - 1) mma_step224(acc, da, db, s * G1_STAGE_BYTES / 16, k);
                else mma_step(acc, da, db, s * G1_STAGE_BYTES / 16, k);
                if (wg == 0 && k == G1_KSTEPS - 1) asm volatile("bar.arrive 1, 256;" ::: "memory");
                wg_wait<1>();
                if (k > 0) release(empty1((k - 1) & 3));
                TRACE_STEP(t, k, 2);
                if (t == 0) chunk_ln(k);
                if (k >= 1 && k <= 8 && gated) {
                    chunk_geglu(k - 1);
                    if (k == 8) signal_stores(t == 1 ? 1 : t + 1);
                }
                if (t != 0 && !gated) {
                    if (k == 0) { chunk_qkv(0); chunk_qkv(1); }
                    if (k >= 6 && k <= 11) chunk_qkv(k - 4);
                    if ((k == 0 || k == 11) && t == 2) signal_stores(k ? 3 : 2);
                }
                if (TAIL && k == TLD && t == G1_TILES - 1) {
#pragma unroll
                    for (int i = 0; i < 2; i++) {
                        const uint4 v = ldg_stream(prm.tail + role * 512 + i * 256 + threadIdx.x, stream_policy());
                        pk[16 + 4 * i] = v.x; pk[17 + 4 * i] = v.y; pk[18 + 4 * i] = v.z; pk[19 + 4 * i] = v.w;
                    }
                }
                if (TAIL && k == TLD + 3 && t == G1_TILES - 1) {
#pragma unroll
                    for (int i = 0; i < 8; i++)
                        asm volatile("shl.b32 %0, %2, 16;\nand.b32 %1, %2, 0xffff0000;" : "=r"(pk[2 * i]), "=r"(pk[2 * i + 1]) : "r"(pk[16 + i]));
                }
                if (k == 12) {
                    const int nt = t * 8 + nslot;
                    gated = !tile_is_qkv(nt);
                    optr = !gated ? prm.qkv + (size_t)orow * NQKV + tile_index(nt) * 256 + (lane & 3) * 8
                                  : prm.pa2 + (size_t)orow * K2 + DM + tile_index(nt) * 128 + (lane & 3) * 8;
                    asm volatile("" : "+l"(optr));
                }
            }
            wg_wait<0>();
            fence_regs(acc);
            release(empty1(3));
            if (t == 0) {
#pragma unroll
                for (int i = 0; i < 128; i++) acc[i] *= __uint_as_float(pk[32 + i / 2 % 2]);
                fence_regs(acc);
            }
            if (TAIL && t == G1_TILES - 1) {
#pragma unroll
                for (int i = 0; i < 16; i++) acc[112 + i] += __uint_as_float(pk[i]);
                fence_regs(acc);
            }
#pragma unroll
            for (int i = 0; i < 64; i++) {
                const int e = (i & ~7) * 2 + (i & 3) * 4 + (i & 4) / 2;
                pk[i] = pack_bf16(acc[e], acc[e + 1]);
            }
            TRACE_NEXT(tile_slot);
        }

        float accd[64], accs[64];
#pragma unroll
        for (int i = 0; i < 64; i++) accd[i] = 0.f;
#pragma unroll
        for (int u = 0; u < G2_HEAD; u++) {
            const int q = u % G2_STAGES;
            mbar_wait(full2(q), (u / G2_STAGES) & 1);
            mma_step(accd, da, db, q * G2_STAGE_BYTES / 16, u);
            wg_wait<1>();
            if (u > 0) release(empty2((u - 1) % G2_STAGES));
            if (HALF == 0 && u >= 1) chunk_geglu(u - 1);
            if (HALF == 1 && u >= 1) {
                const int j = (u - 1) / 2;
#pragma unroll
                for (int i = 2 * u - 2; i < 2 * u; i++) pk[i] = geglu2(pk[i], pk[32 + i]);
                if (u % 2 == 0) store_pk(optr + (j & 1) * 4 * K2 + (j >> 1) * 32, j);
            }
            if (HALF == 2 && u % 2 == 0 && u > 0) chunk_geglu(u / 2 - 1);
            if (u == G2_HEAD - 1) signal_stores(6);
        }
        {
            int q = G2_HEAD % G2_STAGES, qp = (G2_HEAD - 1) % G2_STAGES; uint32_t ph = (G2_HEAD / G2_STAGES) & 1;
#pragma unroll 1
            for (int u = G2_HEAD; u < G2_DSTEPS; u++) {
                mbar_wait(full2(q), ph);
                mma_step(accd, da, db, q * (G2_STAGE_BYTES / 16), 1);
                wg_wait<1>();
                release(empty2(qp));
                qp = q;
                if (++q == G2_STAGES) { q = 0; ph ^= 1; }
            }
        }
        TRACE_NEXT(tile_slot);
#pragma unroll
        for (int i = 0; i < 64; i++) accs[i] = 0.f;
        uint32_t gk[32], xr[32];
        const uint32_t xs = aux + cw * 2048;
        const uint32_t xrow = xs + ((lane & 7) + ((lane >> 3) & 1) * 8) * 128;
        auto xaddr = [&](int j) { return xrow + (j >> 2) * 16384 + (((((j & 3) * 2) + (lane >> 4)) ^ (lane & 7)) << 4); };
#pragma unroll
        for (int u = G2_DSTEPS; u < G2_KSTEPS; u++) {
            const int q = u % G2_STAGES, v = u - G2_DSTEPS;
            mbar_wait(full2(q), (u / G2_STAGES) & 1);
            if (G2_SKEW > 0 && wg == 1 && u == G2_KSTEPS - G2_SKEW) asm volatile("bar.sync 1, 256;" ::: "memory");
            mma_step(accs, da, db, q * G2_STAGE_BYTES / 16, v);
            if (G2_SKEW > 0 && wg == 0 && u == G2_KSTEPS - 1) asm volatile("bar.arrive 1, 256;" ::: "memory");
            if (v >= 1 && v <= 8) {
#pragma unroll
                for (int i = 4 * (v - 1); i < 4 * v; i++) {
                    const uint32_t d2 = pack_bf16(accd[2 * i], accd[2 * i + 1]);
                    gk[i] = pack_bf16(silu(bf_lo(d2)), silu(bf_hi(d2)));
                }
            }
            if (v == 9) mbar_wait(x_bar, 0);
            if (v >= 9 && v <= 12) {
#pragma unroll
                for (int j = 2 * (v - 9); j < 2 * (v - 8); j++)
                    asm volatile("ldmatrix.sync.aligned.m8n8.x4.shared.b16 {%0,%1,%2,%3}, [%4];"
                                 : "=r"(xr[4 * j]), "=r"(xr[4 * j + 1]), "=r"(xr[4 * j + 2]), "=r"(xr[4 * j + 3])
                                 : "r"(xaddr(j)) : "memory");
            }
            wg_wait<1>();
            if (v == 0) fence_regs(accd);
            if (u - 1 + G2_STAGES < G2_KSTEPS) release(empty2((u - 1) % G2_STAGES));
        }
        __nv_bfloat16* po = prm.pout + (mblk * 128 + cw * 16 + (lane >> 3)) * DM + nslot * 128 + (lane & 7) * 8;
        uint32_t so = xs + (lane >> 3) * 128 + (((lane & 7) ^ (lane >> 3)) << 4);
        const int c0 = uniform(nslot * 128), c1 = uniform(mblk * 128 + cw * 16);
        const uint32_t xu = uniform(xs);
        if (EPI & 2) asm volatile("" : "+l"(po), "+r"(so));
        wg_wait<0>();
        fence_regs(accs);
        TRACE_NEXT(tile_slot);
        TRACE_END();
        if ((EPI & 16) && prm.zero == 0) return;
        if ((EPI & 32) && prm.zero == wg) return;
#pragma unroll
        for (int j = 0; j < 8; j++) {
            uint32_t r[4];
#pragma unroll
            for (int i = 0; i < 4; i++) {
                const int e = j * 4 + i;
                const uint32_t s2 = pack_bf16(accs[2 * e], accs[2 * e + 1]);
                if (EPI & 1) asm("fma.rn.bf16x2 %0, %1, %2, %3;" : "=r"(r[i]) : "r"(s2), "r"(gk[e]), "r"(xr[e]));
                else r[i] = add_bf16x2(xr[e], mul_bf16x2(s2, gk[e]));
            }
            asm volatile("stmatrix.sync.aligned.m8n8.x4.shared.b16 [%0], {%1,%2,%3,%4};"
                         :: "r"(xaddr(j)), "r"(r[0]), "r"(r[1]), "r"(r[2]), "r"(r[3]) : "memory");
            if ((EPI & 2) && (!(EPI & 4) || j / 4 == (EPI >> 6 & 1))) {
                if (j == 3 || j == 7) {
                    __syncwarp();
#pragma unroll
                    for (int i = 0; i < 4; i++) {
                        const uint4 v = lds128((so ^ (i & 1) * 64) + (j >> 2) * 16384 + i * 512);
                        asm volatile("st.global.v4.u32 [%0], {%1,%2,%3,%4};"
                                     :: "l"(po + (j >> 2) * 64 + i * 4 * DM), "r"(v.x), "r"(v.y), "r"(v.z), "r"(v.w) : "memory");
                    }
                }
            } else if (EPI & 4) {
                if (j == 7 || (j == 3 && !(EPI & 8))) {
                    asm volatile("{\n.reg .pred e;\nfence.proxy.async.shared::cta;\nbar.warp.sync 0xffffffff;\nelect.sync _|e, 0xffffffff;\n"
                        "@e cp.async.bulk.tensor.2d.global.shared::cta.bulk_group [%0, {%2, %3}], [%1];\n}"
                        :: "l"(&prm.out), "r"(xu + (j >> 2) * 16384), "r"(c0 + (j >> 2) * 64), "r"(c1) : "memory");
                    if (EPI & 8) asm volatile("{\n.reg .pred e;\nelect.sync _|e, 0xffffffff;\n"
                        "@e cp.async.bulk.tensor.2d.global.shared::cta.bulk_group [%0, {%2, %3}], [%1];\n}"
                        :: "l"(&prm.out), "r"(xu), "r"(c0), "r"(c1) : "memory");
                }
            } else if (j == 3 || j == 7) {
                asm volatile("fence.proxy.async.shared::cta;" ::: "memory");
                __syncwarp();
                if (lane == 0) {
                    tma_store_2d(&prm.out, xs + (j >> 2) * 16384, nslot * 128 + (j >> 2) * 64, mblk * 128 + cw * 16);
                    asm volatile("cp.async.bulk.commit_group;" ::: "memory");
                }
            }
        }
        if (EPI & 4) asm volatile("cp.async.bulk.commit_group;\ncp.async.bulk.wait_group.read 0;" ::: "memory");
        else if (!(EPI & 2) && lane == 0) asm volatile("cp.async.bulk.wait_group.read 0;" ::: "memory");
        if (tid == 0) { TRACE_NEXT(tile_slot); if (wg == 1) TRACE_GT(13); TRACE_DUMP(); }
    } else {
        asm volatile("setmaxnreg.dec.sync.aligned.u32 %0;" :: "n"(AUX_REGS));
        cluster_wait();
        unsigned* const flags = prm.flags + mblk * 32;
        if (warp == 9) {
            TRACE_CLEAR(); TRACE_GT(0); TRACE(60);
            if (lane == 0) {
                const unsigned epoch = __ldcg(prm.epoch + blockIdx.x * 16 + 2) + 1;
                mbar_wait(sig_bar, 0);
                TRACE(11);
                flag_add(flags + F_LN * 512);
                TRACE(42);
                flag_wait(flags + F_LN * 512, epoch * CNT_LN);
                fence_proxy_async();
                mbar_arrive(dep_bar);
                mbar_wait(sig_bar + 56, 0);
                flag_add(flags + F_LN2 * 512);
                flag_wait(flags + F_LN2 * 512, epoch * CNT_LN);
                fence_proxy_async();
                mbar_arrive(dep_bar + 40);
                TRACE(59);
                prm.epoch[blockIdx.x * 16 + 2] = epoch;
                for (int p = nslot < 4 ? 2 : 1; p < 7; p++) {
                    mbar_wait(sig_bar + p * 8, 0);
                    if (p == 2) TRACE(37);
                    flag_add(p == 2 || p == 3 ? prm.flags + F_QKV * 512 + (p * 4 - 8 + (nslot & 3)) * 32
                                              : flags + (p < 6 ? F_EARLY : F_LATE) * 512);
                    if (p == 2) TRACE(43);
                }
            }
        } else if (warp > 9) {
            const int w = warp - 10;
            const unsigned epoch = __ldcg(prm.epoch + blockIdx.x * 16 + w) + 1;
            const uint32_t tag = 1 + (epoch & 1);
                const uint32_t at = (w ? CB : CA) >> (CIDX) * 4 & 15;
            mbar_wait(empty1(at & 3), 0);
            mbar_wait(empty1(at & 3), at >> 3);
            if (elect_one()) {
                mbar_expect_tx(cs_bar + w * 8, 16384);
                if (CKEEP) asm volatile("cp.async.bulk.tensor.3d.shared::cluster.global.mbarrier::complete_tx::bytes [%0], [%1, {%3, %4, %5}], [%2];"
                    :: "r"(aux + w * 16384), "l"(w0), "r"(cs_bar + w * 8), "r"(0), "r"(((mblk & ~1) + w) * 64), "r"(w0_col) : "memory");
                else tma_3d(aux + w * 16384, w0, cs_bar + w * 8, 0, ((mblk & ~1) + w) * 64, w0_col, stream_policy());
            }
            float cs[8];
#pragma unroll
            for (int d = 0; d < 8; d++) cs[d] = 0.f;
            const uint32_t wa = aux + w * 8192 + (lane >> 3) * 128 + (((lane & 7) ^ (lane >> 3)) << 4);
            uint4 v[9];
            auto fetch = [&](int h, uint32_t off) {
#pragma unroll
                for (int j = 0; j < 4; j++) v[h * 4 + j] = lds128((wa ^ (j & 1) * 64) + off + h * 2048 + j * 512);
            };
            auto add = [&](int h) {
#pragma unroll
                for (int j = 0; j < 4; j++) {
                    float f[8];
                    unpack8(v[h * 4 + j], f);
#pragma unroll
                    for (int d = 0; d < 8; d++) cs[d] += f[d];
                }
            };
            if (CST) { mbar_wait(empty1(CST & 3), 0); mbar_wait(empty1(CST & 3), CST >> 3); }
            mbar_wait(cs_bar, 0);

            fetch(0, 0);
#pragma unroll 1
            for (int i = 0; i < 4; i++) {
                fetch(1, (i >> 1) * 16384 + (i & 1) * 4096);
                add(0);
                if (i == 1) mbar_wait(cs_bar + 8, 0);
                fetch(0, (i + 1 & 2) * 8192 + (~i & 1) * 4096);
                add(1);
            }
#pragma unroll
            for (int d = 0; d < 4; d++)
                cs[d] = (lane & 16 ? cs[d + 4] : cs[d]) + __shfl_xor_sync(0xffffffffu, lane & 16 ? cs[d] : cs[d + 4], 16);
#pragma unroll
            for (int d = 0; d < 2; d++)
                cs[d] = (lane & 8 ? cs[d + 2] : cs[d]) + __shfl_xor_sync(0xffffffffu, lane & 8 ? cs[d] : cs[d + 2], 8);
            st_tagged(prm.colsum + (nslot * 2 + rank) * 1024 + (mblk >> 1) * 128 + w * 64 + (lane & 7) * 8 + (lane >> 3) * 2,
                      cs[0], cs[1], tag);

#pragma unroll
            for (int m = 0; m < 9; m++) v[m] = make_uint4(0, 0, 0, 0);
            const float* parts = prm.colsum + (nslot * 2 + (lane >> 4)) * 1024 + w * 64 + (lane & 15) * 4;
            const float* const rows = &prm.stats[mblk * 128 + w * 64 + lane * 2].x;
#pragma unroll 1
            for (int spins = 0; spins < (1 << 16); spins++) {
                bool missing = false;
                asm volatile("" : "+l"(parts));
#pragma unroll
                for (int m = 0; m < 9; m++) {
                    if (untagged(v[m], tag)) {
                        missing = true;
                        v[m] = ld_relaxed(m < 8 ? parts + m * 128 : rows);
                    }
                }
                if (!missing) break;
            }
            float4 c = make_float4(0.f, 0.f, 0.f, 0.f);
#pragma unroll
            for (int m = 0; m < 8; m++) {
                c.x += __uint_as_float(v[m].x ^ tag); c.y += __uint_as_float(v[m].y ^ tag);
                c.z += __uint_as_float(v[m].z ^ tag); c.w += __uint_as_float(v[m].w ^ tag);
            }
            sts128(stats + w * 512 + lane * 16, make_uint4(v[8].x ^ tag, v[8].y ^ tag, v[8].z ^ tag, v[8].w ^ tag));
            const uint32_t ca = aux + w * 8192 + (lane >> 4) * 16384 + (lane & 15) * 8;
#pragma unroll
            for (int r = 0; r < 3; r++) {
                const uint32_t lo = pack_bf16(c.x, c.y), hi = pack_bf16(c.z, c.w);
                sts64f((ca ^ r * 16) + r * 128, __uint_as_float(lo), __uint_as_float(hi));
                c.x -= bf_lo(lo); c.y -= bf_hi(lo); c.z -= bf_lo(hi); c.w -= bf_hi(hi);
            }
            asm volatile("fence.proxy.async.shared::cta;" ::: "memory");
            __syncwarp();
            if (lane == 0) {
                mbar_arrive(fold_bar);
                prm.epoch[blockIdx.x * 16 + w] = epoch;
                if (w == 0) {
                    TRACE_S(35, w, 0);
                    if (TAIL) { flag_wait(flags + F_TAIL * 512, epoch); mbar_arrive(x_bar + 8); }
                    flag_wait(flags + F_EARLY * 512, epoch * CNT_EARLY);
                    fence_proxy_async(); mbar_arrive(dep_bar + 8);
                    flag_wait(flags + F_LATE * 512, epoch * CNT_LATE);
                    fence_proxy_async(); mbar_arrive(dep_bar + 16);
                    flag_wait(prm.flags + F_O * 512, epoch * CNT_O);
                    fence_proxy_async(); mbar_arrive(dep_bar + 24);
                    flag_wait(prm.flags + F_O * 512 + 32, epoch * CNT_O);
                    fence_proxy_async(); mbar_arrive(dep_bar + 32);
                }
            }
        } else {
#pragma unroll
            for (int k = 1; k < G1_STAGES; k++) {
                const uint32_t sa = base + k * G1_STAGE_BYTES;
                if (PACE0 + PACE) while ((uint32_t)clock() - t0 < (k == 3 ? PACE3 : PACE0 + (k - 1) * PACE)) {}
                load_stage1(sa, sa + A_BYTES + rank * 16384, full1(k), &prm.x, w0, k * 64, mblk * 128, w0_col, 0, stream_policy());
            }
            if (elect_one()) {
                prefetch_map(&prm.xn); prefetch_map(&prm.wqkv); prefetch_map(&prm.wu); prefetch_map(&prm.wg);
                prefetch_map(&prm.a2); prefetch_map(&prm.wo); prefetch_map(&prm.wd); prefetch_map(&prm.out);
            }
            auto load_x = [&]() {
                if (elect_one()) {
                    mbar_expect_tx(x_bar, 32768);
                    tma_2d(aux, &prm.x, x_bar, nslot * 128, mblk * 128, stream_policy());
                    tma_2d(aux + 16384, &prm.x, x_bar, nslot * 128 + 64, mblk * 128, stream_policy());
                }
                __syncwarp();
            };
            uint32_t ph = 0;
#pragma unroll 1
            for (int t = 0; t < G1_TILES; t++) {
                const int nt = t * 8 + nslot;
                const CUtensorMap* const mb = tile_is_qkv(nt) ? &prm.wqkv : (rank ? &prm.wu : &prm.wg);
                const int col = tile_is_qkv(nt) ? tile_index(nt) * 4 + rank * 2 : tile_index(nt) * 2;
                if (t == 1) { TRACE_PUT(1, c0); TRACE_PUT(2, t0); TRACE(14); mbar_wait_warp(dep_bar, 0); TRACE(3); }
#pragma unroll 1
                for (int k = t ? 0 : G1_STAGES; k < G1_KSTEPS; k++) {
                    const int s = k & 3;
                    if (t == 1 && k == 8) mbar_wait_warp(dep_bar + 40, 0);
                    if (TAIL && t * 16 + k == 64 + TLD) { TRACE(61); mbar_wait_warp(x_bar + 8, 0); TRACE(63); }
                    if (PFW && t * 16 + k == (PFK) && mblk >= PF0 && mblk < PF1) {
                        asm volatile("{\n.reg .pred e;\nelect.sync _|e, 0xffffffff;\n"
                            "@e cp.async.bulk.prefetch.tensor.5d.L2.global [%0, {%1, %4, %4, %4, %3}];\n"
                            "@e cp.async.bulk.prefetch.tensor.5d.L2.global [%0, {%2, %4, %4, %4, %3}];\n}"
                            :: "l"(&prm.wd), "r"(nslot * 128), "r"(nslot * 128 + 64), "r"(mblk * 2), "r"(0) : "memory");
                    }
                    mbar_wait_warp(empty1(s), ph);
                    const uint32_t sa = base + s * G1_STAGE_BYTES;
                    load_stage1(sa, sa + A_BYTES + rank * 16384, full1(s), t ? &prm.xn : &prm.x, mb, (k + (t >> 2) * TAIL & 15) * 64, mblk * 128, col,
                                t & 3, stream_policy());
                    if (s == 3) ph ^= 1;
                    if (XE && t * 16 + k == (XK)) load_x();
                }
            }
            if (!XE && !XL) load_x();
            TRACE(4);
            mbar_wait_warp(dep_bar + 8, 0);
            TRACE(5);
            int q = 0; uint32_t ph2 = 1;
#pragma unroll 1
            for (int u = 0; u < G2_KSTEPS; u++) {
                if (u == G2_LATE || u == G2_DSTEPS || u == G2_LAST) {
                    TRACE(u == G2_LATE ? 6 : (u == G2_DSTEPS ? 32 : 40));
                    mbar_wait_warp(dep_bar + (u == G2_LATE ? 16 : (u == G2_DSTEPS ? 24 : 32)), 0);
                    TRACE(u == G2_LATE ? 7 : (u == G2_DSTEPS ? 33 : 41));
                }
                const uint32_t sa = stage2(q);
                const bool down = u < G2_DSTEPS;
                const int k = down ? u : (u & 3) * 4 + (u - G2_DSTEPS) / 4;
                mbar_wait_warp(u < G2_STAGES ? empty1((u * 2 + 1) / 3) : empty2(q), u < G2_STAGES ? ph : ph2);
                load_stage2(sa, sa + A_BYTES + rank * 8192, full2(q), &prm.a2, down ? &prm.wd : &prm.wo, (down ? DM : 0) + k * 64,
                            mblk * 64, nslot * 128 + rank * 64, k * 2, stream_policy());
                if (++q == G2_STAGES) { q = 0; ph2 ^= 1; }
                if (XL && u == (XK)) load_x();
            }
            TRACE(8);
        }
    }
}

typedef CUresult (*EncodeFn)(CUtensorMap*, CUtensorMapDataType, cuuint32_t, void*, const cuuint64_t*, const cuuint64_t*,
                             const cuuint32_t*, const cuuint32_t*, CUtensorMapInterleave, CUtensorMapSwizzle,
                             CUtensorMapL2promotion, CUtensorMapFloatOOBfill);

void encode(EncodeFn fn, CUtensorMap* m, const void* ptr, int rank, const cuuint64_t* dims, const cuuint64_t* strides,
            const cuuint32_t* box) {
    const cuuint32_t es[5] = {1, 1, 1, 1, 1};
    fn(m, CU_TENSOR_MAP_DATA_TYPE_BFLOAT16, rank, const_cast<void*>(ptr), dims, strides, box, es,
       CU_TENSOR_MAP_INTERLEAVE_NONE, box[0] == 32 ? CU_TENSOR_MAP_SWIZZLE_64B : CU_TENSOR_MAP_SWIZZLE_128B,
       CU_TENSOR_MAP_L2_PROMOTION_L2_128B, CU_TENSOR_MAP_FLOAT_OOB_FILL_NONE);
}
void encode_2d(EncodeFn fn, CUtensorMap* m, const void* ptr, int cols, int box_rows) {
    const cuuint64_t dims[2] = {(cuuint64_t)cols, SEQ}, strides[1] = {(cuuint64_t)cols * 2};
    const cuuint32_t box[2] = {64, (cuuint32_t)box_rows};
    encode(fn, m, ptr, 2, dims, strides, box);
}
void encode_w1(EncodeFn fn, CUtensorMap* m, const void* ptr, int cols) {
    const cuuint64_t dims[3] = {64, DM, (cuuint64_t)cols / 64}, strides[2] = {(cuuint64_t)cols * 2, 128};
    const cuuint32_t box[3] = {64, 64, 2};
    encode(fn, m, ptr, 3, dims, strides, box);
}
void encode_tail(EncodeFn fn, CUtensorMap* m, const __nv_bfloat16* w) {
    const cuuint64_t dims[3] = {32, DM, 8}, strides[2] = {DF * 2, 256};
    const cuuint32_t box[3] = {32, 64, 8};
    encode(fn, m, w + DF - 1024 + 96, 3, dims, strides, box);
}
void encode_qk(EncodeFn fn, CUtensorMap* m, const void* ptr) {
    const cuuint64_t dims[3] = {DM, SEQ, 3}, strides[2] = {NQKV * 2, DM * 2};
    const cuuint32_t box[3] = {64, 16, 2};
    encode(fn, m, ptr, 3, dims, strides, box);
}
void encode_a2(EncodeFn fn, CUtensorMap* m, const void* ptr) {
    const cuuint64_t dims[3] = {K2, 2, SEQ / 2}, strides[2] = {(cuuint64_t)SEQ * K2, K2 * 2};
    const cuuint32_t box[3] = {64, 2, 64};
    encode(fn, m, ptr, 3, dims, strides, box);
}
void encode_w2(EncodeFn fn, CUtensorMap* m, const void* ptr, int rows) {
    const cuuint64_t rb = DM * 2;
    const cuuint64_t dims[5] = {DM, 2, 4, 4, (cuuint64_t)rows / 32}, strides[4] = {rb, 8 * rb, 2 * rb, 32 * rb};
    const cuuint32_t box[5] = {64, 2, 4, 4, 2};
    encode(fn, m, ptr, 5, dims, strides, box);
}

}

extern "C" void kernel_launch(void* const* d_in, const int* in_sizes, int n_in, void* d_out, int out_size) {
    (void)in_sizes; (void)n_in; (void)out_size;
    static EncodeFn fn = nullptr;
    static Params prm;
    if (!fn) {
        cudaDriverEntryPointQueryResult st;
        cudaGetDriverEntryPoint("cuTensorMapEncodeTiled", (void**)&fn, cudaEnableDefault, &st);
        cudaGetSymbolAddress((void**)&prm.pxn, g_xn);
        cudaGetSymbolAddress((void**)&prm.qkv, g_qkv);
        cudaGetSymbolAddress((void**)&prm.pa2, g_a2);
        cudaGetSymbolAddress((void**)&prm.tail, g_tail);
        cudaGetSymbolAddress((void**)&prm.stats, g_stats);
        cudaGetSymbolAddress((void**)&prm.colsum, g_colsum);
        cudaGetSymbolAddress((void**)&prm.flags, g_flags);
        cudaGetSymbolAddress((void**)&prm.epoch, g_epoch);
        cudaFuncSetAttribute(fused_kernel, cudaFuncAttributeMaxDynamicSharedMemorySize, SMEM_BYTES);
    }
    encode_2d(fn, &prm.x, d_in[0], DM, 128);
    encode_2d(fn, &prm.xn, prm.pxn, DM, 128);
    encode_tail(fn, &prm.wtail, (const __nv_bfloat16*)d_in[5]);
    encode_w1(fn, &prm.wqkv, d_in[1], NQKV);
    encode_w1(fn, &prm.wg, d_in[4], DF);
    encode_w1(fn, &prm.wu, d_in[5], DF);
    encode_qk(fn, &prm.qk, prm.qkv);
    encode_2d(fn, &prm.v, prm.qkv, NQKV, 16);
    encode_2d(fn, &prm.o, prm.pa2, K2, 16);
    encode_a2(fn, &prm.a2, prm.pa2);
    encode_w2(fn, &prm.wo, d_in[2], DM);
    encode_w2(fn, &prm.wd, d_in[6], DF);
    encode_2d(fn, &prm.out, d_out, DM, 16);
    prm.px = (const __nv_bfloat16*)d_in[0];
    prm.pout = (__nv_bfloat16*)d_out;
    fused_kernel<<<NCTA, 384, SMEM_BYTES>>>(prm);
}
```

```cpp
#include <cuda_runtime.h>
#include <cuda_bf16.h>
#include <cuda.h>
#include <stdint.h>
#include <type_traits>

#define LNS 3
#define FS 14
#define CA 0x87658765u
#define CB 0x65876587u
#define CST 10
#define CIDX nslot
#define CKEEP 1
#define PACE0 900
#define PACE 425
#define PACE3 1700
#define TAIL 7
#define LNL 0
#define EPI 71
#define SK2 5
#define PFW 1
#define HALF 1
#define PFK 60 + mblk
#define PF0 0
#define PF1 16
#define XE 1
#define XL 0
#define XK 20 + nslot
#define TSK 2
#define QK0 0
#define STG 1
#define TW0 9000
#define TLD 10
#define SK0 2

namespace {

constexpr int SEQ = 2048, DM = 1024, DF = 3584, K2 = DM + DF, NQKV = 3 * DM;
constexpr int NGEMM = 128, NCTA = 132;
constexpr int G1_STAGES = 4, G1_STAGE_BYTES = 49152, G1_KSTEPS = 16, G1_TILES = 5;
constexpr int G2_STAGES = 6, G2_STAGE_BYTES = 32768, G2_KSTEPS = 72, G2_LATE = 40, G2_DSTEPS = 56, G2_LAST = 68;
constexpr int G2_HEAD = HALF ? 17 : 9;
constexpr int LN_STEP = LNS, FOLD_STEP = FS;
constexpr int A_BYTES = 16384;
constexpr int AUX_OFF = G1_STAGES * G1_STAGE_BYTES;
constexpr int BAR_OFF = AUX_OFF + 32768;
constexpr int SMEM_BYTES = BAR_OFF + 2816;
constexpr int G1_SKEW = 2, G2_SKEW = SK2;
constexpr int CONSUMER_REGS = 224, AUX_REGS = 56;
constexpr int ATT_SLOT = 6144;

enum { F_LN = 0, F_QKV = 1, F_EARLY = 2, F_LATE = 3, F_O = 4, F_LN2 = 5, F_TAIL = 6 };
constexpr unsigned CNT_LN = 8, CNT_QKV = 32, CNT_EARLY = 20, CNT_LATE = 8, CNT_O = 4;

__device__ __align__(1024) __nv_bfloat16 g_xn[SEQ * DM];
__device__ __align__(1024) __nv_bfloat16 g_qkv[SEQ * NQKV];
__device__ __align__(1024) __nv_bfloat16 g_a2[SEQ * K2];
__device__ __align__(128) uint4 g_tail[NGEMM * 512];
__device__ __align__(128) float2 g_stats[SEQ];
__device__ __align__(128) float g_colsum[16 * 1024];
__device__ __align__(128) unsigned g_flags[7 * 16 * 32];
__device__ __align__(128) unsigned g_epoch[NCTA * 16];

struct Params {
    const __nv_bfloat16* px;
    __nv_bfloat16 *pxn, *qkv, *pa2, *pout;
    uint4* tail;
    float2* stats;
    float* colsum;
    unsigned *flags, *epoch;
    unsigned long long* trace;
    uint32_t zero;
    CUtensorMap x, wqkv, wg, wu, xn, wtail, qkv3, o, a2, wo, wd, out;
};

extern __shared__ __align__(1024) uint8_t smem_raw[];

#define TRACE(slot) do {} while (0)
#define TRACE_GT(slot) do {} while (0)
#define TRACE_S(slot, v, want) do {} while (0)
#define TRACE_GET(v) do {} while (0)
#define TRACE_PUT(slot, v) do {} while (0)
#define TRACE_SLOT(v, slot) do {} while (0)
#define TRACE_NEXT(v) do {} while (0)
#define TRACE_DUMP() do {} while (0)
#define TRACE_CLEAR() do {} while (0)
#define STAGE_TRACE 0
#define TRACE_END() do {} while (0)
#define TRACE_TAIL(j) do { const int v_ = warp * 64 + i; TRACE_S(44 + j, v_, 0); TRACE_S(52 + j, v_, TAIL); TRACE_S(56 + j, v_, 4 * TAIL - 1); } while (0)
#define TRACE_STEP(t, k, i) do {} while (0)

__device__ __forceinline__ uint32_t smem_u32(const void* p) { return (uint32_t)__cvta_generic_to_shared(p); }
__device__ __forceinline__ void mbar_init(uint32_t bar, uint32_t cnt) {
    asm volatile("mbarrier.init.shared::cta.b64 [%0], %1;" :: "r"(bar), "r"(cnt) : "memory");
}
__device__ __forceinline__ void mbar_expect_tx(uint32_t bar, uint32_t bytes) {
    asm volatile("mbarrier.arrive.expect_tx.shared::cta.b64 _, [%0], %1;" :: "r"(bar), "r"(bytes) : "memory");
}
__device__ __forceinline__ void mbar_arrive(uint32_t bar) {
    asm volatile("mbarrier.arrive.shared::cta.b64 _, [%0];" :: "r"(bar) : "memory");
}
__device__ __forceinline__ void mbar_arrive_cluster(uint32_t bar, uint32_t cta) {
    asm volatile("{\n.reg .b32 ra;\nmapa.shared::cluster.u32 ra, %0, %1;\nmbarrier.arrive.shared::cluster.b64 _, [ra];\n}"
                 :: "r"(bar), "r"(cta) : "memory");
}
__device__ __forceinline__ bool mbar_try_wait(uint32_t bar, uint32_t parity) {
    uint32_t ok;
    asm volatile("{\n.reg .pred p;\nmbarrier.try_wait.parity.shared::cta.b64 p, [%1], %2;\nselp.u32 %0, 1, 0, p;\n}"
                 : "=r"(ok) : "r"(bar), "r"(parity) : "memory");
    return ok;
}
__device__ __forceinline__ bool mbar_test(uint32_t bar, uint32_t parity) {
    uint32_t ok;
    asm volatile("{\n.reg .pred p;\nmbarrier.test_wait.parity.shared::cta.b64 p, [%1], %2;\nselp.u32 %0, 1, 0, p;\n}"
                 : "=r"(ok) : "r"(bar), "r"(parity) : "memory");
    return ok;
}
__device__ __forceinline__ void mbar_wait(uint32_t bar, uint32_t parity) {
#pragma unroll 1
    for (int spins = 0; !mbar_try_wait(bar, parity) && spins < (1 << 17); spins++) {}
}
template <bool WARP = false> __device__ __forceinline__ void flag_wait(const unsigned* p, unsigned target) {
#pragma unroll 1
    for (int spins = 0; spins < (1 << 19); spins++) {
        unsigned v;
        asm volatile("ld.acquire.gpu.global.u32 %0, [%1];" : "=r"(v) : "l"(p) : "memory");
        if (WARP ? __all_sync(0xffffffffu, (int)(v - target) >= 0) : (int)(v - target) >= 0) break;
        __nanosleep(64);
    }
}
__device__ __forceinline__ void mbar_wait_warp(uint32_t bar, uint32_t parity) {
#pragma unroll 1
    for (int spins = 0; !__all_sync(0xffffffffu, mbar_try_wait(bar, parity)) && spins < (1 << 17); spins++) {}
}
__device__ __forceinline__ void flag_add(unsigned* p) {
    asm volatile("red.release.gpu.global.add.u32 [%0], 1;" :: "l"(p) : "memory");
}
__device__ __forceinline__ bool elect_one() {
    uint32_t ok;
    asm volatile("{\n.reg .pred p;\nelect.sync _|p, 0xffffffff;\nselp.u32 %0, 1, 0, p;\n}" : "=r"(ok));
    return ok;
}
__device__ __forceinline__ uint32_t pick(bool c, uint32_t a, uint32_t b) {
    uint32_t r;
    asm("{\n.reg .pred p;\nsetp.ne.b32 p, %3, 0;\nselp.b32 %0, %1, %2, p;\n}" : "=r"(r) : "r"(a), "r"(b), "r"((uint32_t)c));
    return r;
}
__device__ __forceinline__ void fence_proxy_async() { asm volatile("fence.proxy.async.global;" ::: "memory"); }
__device__ __forceinline__ uint4 lds128(uint32_t addr) {
    uint4 v;
    asm volatile("ld.shared.v4.u32 {%0,%1,%2,%3}, [%4];" : "=r"(v.x), "=r"(v.y), "=r"(v.z), "=r"(v.w) : "r"(addr) : "memory");
    return v;
}
__device__ __forceinline__ float2 lds64f(uint32_t addr) {
    float2 v;
    asm volatile("ld.shared.v2.f32 {%0,%1}, [%2];" : "=f"(v.x), "=f"(v.y) : "r"(addr) : "memory");
    return v;
}
__device__ __forceinline__ void sts128(uint32_t addr, uint4 v) {
    asm volatile("st.shared.v4.u32 [%0], {%1,%2,%3,%4};" :: "r"(addr), "r"(v.x), "r"(v.y), "r"(v.z), "r"(v.w) : "memory");
}
__device__ __forceinline__ void sts64f(uint32_t addr, float a, float b) {
    asm volatile("st.shared.v2.f32 [%0], {%1,%2};" :: "r"(addr), "f"(a), "f"(b) : "memory");
}

__device__ __forceinline__ uint64_t stream_policy() { return 0x12F0000000000000ull; }
__device__ __forceinline__ void tma_2d(uint32_t dst, const CUtensorMap* m, uint32_t bar, int c0, int c1, uint64_t pol) {
    asm volatile("cp.async.bulk.tensor.2d.shared::cluster.global.mbarrier::complete_tx::bytes.L2::cache_hint"
                 " [%0], [%1, {%3, %4}], [%2], %5;"
                 :: "r"(dst), "l"(m), "r"(bar), "r"(c0), "r"(c1), "l"(pol) : "memory");
}
__device__ __forceinline__ void tma_3d(uint32_t dst, const CUtensorMap* m, uint32_t bar, int c0, int c1, int c2, uint64_t pol) {
    asm volatile("cp.async.bulk.tensor.3d.shared::cluster.global.mbarrier::complete_tx::bytes.L2::cache_hint"
                 " [%0], [%1, {%3, %4, %5}], [%2], %6;"
                 :: "r"(dst), "l"(m), "r"(bar), "r"(c0), "r"(c1), "r"(c2), "l"(pol) : "memory");
}
__device__ __forceinline__ void tma_3d_mc(uint32_t dst, const CUtensorMap* m, uint32_t bar, int c1, int c2, uint64_t pol) {
    asm volatile("cp.async.bulk.tensor.3d.shared::cluster.global.mbarrier::complete_tx::bytes.multicast::cluster.L2::cache_hint"
                 " [%0], [%1, {%3, %4, %5}], [%2], %6, %7;"
                 :: "r"(dst), "l"(m), "r"(bar), "r"(0), "r"(c1), "r"(c2), "h"((uint16_t)3), "l"(pol) : "memory");
}
__device__ __forceinline__ void load_stage1(uint32_t dst, uint32_t dst_b, uint32_t bar, const CUtensorMap* ma, const CUtensorMap* mb,
                                            int k, int row, int col, int keep_a, uint64_t pol) {
    asm volatile("{\n.reg .pred e, p, q;\nelect.sync _|e, 0xffffffff;\nsetp.ne.and.b32 p|q, %8, 0, e;\n"
        "@p cp.async.bulk.tensor.2d.shared::cluster.global.mbarrier::complete_tx::bytes [%0], [%3, {%5, %6}], [%2];\n"
        "@q cp.async.bulk.tensor.2d.shared::cluster.global.mbarrier::complete_tx::bytes.L2::cache_hint [%0], [%3, {%5, %6}], [%2], %9;\n"
        "@e cp.async.bulk.tensor.3d.shared::cluster.global.mbarrier::complete_tx::bytes.multicast::cluster.L2::cache_hint"
        " [%1], [%4, {%10, %5, %7}], [%2], %11, %9;\n"
        "@e mbarrier.arrive.expect_tx.shared::cta.b64 _, [%2], %12;\n}"
        :: "r"(dst), "r"(dst_b), "r"(bar), "l"(ma), "l"(mb), "r"(k), "r"(row), "r"(col), "r"(keep_a), "l"(pol), "r"(0),
           "h"((uint16_t)3), "n"(G1_STAGE_BYTES) : "memory");
}
__device__ __forceinline__ void load_stage2(uint32_t dst, uint32_t dst_b, uint32_t bar, const CUtensorMap* ma, const CUtensorMap* mb,
                                            int ka, int row, int col, int kb2, int kb4, uint64_t pol) {
    asm volatile("{\n.reg .pred e;\nelect.sync _|e, 0xffffffff;\n"
        "@e cp.async.bulk.tensor.3d.shared::cluster.global.mbarrier::complete_tx::bytes.L2::cache_hint [%0], [%3, {%5, %10, %6}], [%2], %9;\n"
        "@e cp.async.bulk.tensor.5d.shared::cluster.global.mbarrier::complete_tx::bytes.multicast::cluster.L2::cache_hint"
        " [%1], [%4, {%7, %10, %13, %10, %8}], [%2], %11, %9;\n"
        "@e mbarrier.arrive.expect_tx.shared::cta.b64 _, [%2], %12;\n}"
        :: "r"(dst), "r"(dst_b), "r"(bar), "l"(ma), "l"(mb), "r"(ka), "r"(row), "r"(col), "r"(kb4), "l"(pol), "r"(0),
           "h"((uint16_t)3), "n"(G2_STAGE_BYTES), "r"(kb2) : "memory");
}
__device__ __forceinline__ void tma_store_2d(const CUtensorMap* m, uint32_t src, int c0, int c1) {
    asm volatile("cp.async.bulk.tensor.2d.global.shared::cta.bulk_group [%0, {%2, %3}], [%1];"
                 :: "l"(m), "r"(src), "r"(c0), "r"(c1) : "memory");
}
__device__ __forceinline__ uint4 ldg_stream(const void* p, uint64_t pol) {
    uint4 v;
    asm volatile("ld.global.nc.L1::no_allocate.L2::cache_hint.v4.u32 {%0,%1,%2,%3}, [%4], %5;"
                 : "=r"(v.x), "=r"(v.y), "=r"(v.z), "=r"(v.w) : "l"(p), "l"(pol));
    return v;
}
__device__ __forceinline__ void st_tagged(void* p, float a, float b, uint32_t tag) {
    asm volatile("st.relaxed.gpu.global.v2.b32 [%0], {%1,%2};"
                 :: "l"(p), "r"((__float_as_uint(a) & ~3u) | tag), "r"((__float_as_uint(b) & ~3u) | tag) : "memory");
}
__device__ __forceinline__ bool untagged(const uint4& v, uint32_t tag) {
    return ((v.x ^ tag) | (v.y ^ tag) | (v.z ^ tag) | (v.w ^ tag)) & 3;
}
__device__ __forceinline__ uint4 ld_relaxed(const void* p) {
    uint4 v;
    asm volatile("ld.relaxed.gpu.global.v4.b32 {%0,%1,%2,%3}, [%4];" : "=r"(v.x), "=r"(v.y), "=r"(v.z), "=r"(v.w) : "l"(p) : "memory");
    return v;
}
__device__ __forceinline__ void prefetch_3d(const CUtensorMap* m, int c1, int c2, uint64_t pol) {
    asm volatile("cp.async.bulk.prefetch.tensor.3d.L2.global.L2::cache_hint [%0, {%1, %2, %3}], %4;"
                 :: "l"(m), "r"(0), "r"(c1), "r"(c2), "l"(pol) : "memory");
}
__device__ __forceinline__ void prefetch_map(const CUtensorMap* m) {
    asm volatile("prefetch.tensormap [%0];" :: "l"(m) : "memory");
}
template <int N> __device__ __forceinline__ void wg_wait() { asm volatile("wgmma.wait_group.sync.aligned %0;" :: "n"(N) : "memory"); }

__device__ __forceinline__ uint32_t desc_a(uint32_t addr) { return (addr & 0x3FFFF) >> 4 | 1 << 16; }
__device__ __forceinline__ uint32_t desc_b(uint32_t addr) { return (addr & 0x3FFFF) >> 4 | 512 << 16; }

#define R8(d, o) "+f"(d[o]), "+f"(d[o+1]), "+f"(d[o+2]), "+f"(d[o+3]), "+f"(d[o+4]), "+f"(d[o+5]), "+f"(d[o+6]), "+f"(d[o+7])
#define R32(d, o) R8(d, o), R8(d, o+8), R8(d, o+16), R8(d, o+24)
#define R64(d, o) R32(d, o), R32(d, o+32)
#define ACC0 "%0,%1,%2,%3,%4,%5,%6,%7,%8,%9,%10,%11,%12,%13,%14,%15,%16,%17,%18,%19,%20,%21,%22,%23,%24,%25,%26,%27,%28,%29,%30,%31,"\
    "%32,%33,%34,%35,%36,%37,%38,%39,%40,%41,%42,%43,%44,%45,%46,%47,%48,%49,%50,%51,%52,%53,%54,%55,%56,%57,%58,%59,%60,%61,%62,%63"
#define ACC1 "%64,%65,%66,%67,%68,%69,%70,%71,%72,%73,%74,%75,%76,%77,%78,%79,%80,%81,%82,%83,%84,%85,%86,%87,%88,%89,%90,%91,%92,%93,%94,%95,"\
    "%96,%97,%98,%99,%100,%101,%102,%103,%104,%105,%106,%107,%108,%109,%110,%111"
#define ACC64 "{" ACC0 "}"
#define ACC112 "{" ACC0 "," ACC1 "}"
#define ACC128 "{" ACC0 "," ACC1 ",%112,%113,%114,%115,%116,%117,%118,%119,%120,%121,%122,%123,%124,%125,%126,%127}"
#define MMA_K16(shape, acc, keep, hb, sb) \
    "mov.b64 da, {la, 0x40000040};\nmov.b64 db, {lb, " hb "};\n" \
    "wgmma.mma_async.sync.aligned." shape ".f32.bf16.bf16 " acc ", da, db, " keep ", 1, 1, 0, 1;\n" \
    "add.u32 la, la, 2;\nadd.u32 lb, lb, " sb ";\n"
#define MMA_STEP_B(shape, acc, a, b, off, keep, hb, sb) \
    "{\n.reg .pred p, q;\n.reg .b32 la, lb;\n.reg .b64 da, db;\nsetp.ne.b32 p, " keep ", 0;\nsetp.eq.b32 q, 0, 0;\n" \
    "add.u32 la, " a ", " off ";\nadd.u32 lb, " b ", " off ";\nwgmma.fence.sync.aligned;\n" \
    MMA_K16(shape, acc, "p", hb, sb) MMA_K16(shape, acc, "q", hb, sb) MMA_K16(shape, acc, "q", hb, sb) \
    MMA_K16(shape, acc, "q", hb, sb) "wgmma.commit_group.sync.aligned;\n}"
#define MMA_STEP(shape, acc, a, b, off, keep) MMA_STEP_B(shape, acc, a, b, off, keep, "0x40000040", "128")

__device__ __forceinline__ void mma_step(float (&d)[128], uint32_t da, uint32_t db, uint32_t off, int keep) {
    asm volatile(MMA_STEP("m64n256k16", ACC128, "%128", "%129", "%130", "%131")
                 : R64(d, 0), R64(d, 64) : "r"(da), "r"(db), "r"(off), "r"(keep) : "memory");
}
__device__ __forceinline__ void mma_rank(float (&d)[128], uint32_t a0, uint32_t a1, uint32_t db) {
    asm volatile("{\n.reg .pred q;\n.reg .b64 db;\nsetp.eq.b32 q, 0, 0;\nmov.b64 db, {%131, 0x40000040};\nwgmma.fence.sync.aligned;\n"
                 "wgmma.mma_async.sync.aligned.m64n256k16.f32.bf16.bf16 " ACC128 ", {%128, %129, %130, %130}, db, q, 1, 1, 1;\n}"
                 : R64(d, 0), R64(d, 64) : "r"(a0), "r"(a1), "r"(0), "r"(db) : "memory");
}
__device__ __forceinline__ void mma_step224(float (&d)[128], uint32_t da, uint32_t db, uint32_t off, int keep) {
    asm volatile(MMA_STEP("m64n224k16", ACC112, "%112", "%113", "%114", "%115")
                 : R64(d, 0), R32(d, 64), R8(d, 96), R8(d, 104) : "r"(da), "r"(db), "r"(off), "r"(keep) : "memory");
}
__device__ __forceinline__ void mma_step(float (&d)[64], uint32_t da, uint32_t db, uint32_t off, int keep) {
    asm volatile(MMA_STEP("m64n128k16", ACC64, "%64", "%65", "%66", "%67")
                 : R64(d, 0) : "r"(da), "r"(db), "r"(off), "r"(keep) : "memory");
}

__device__ __forceinline__ void mma_step_tail(float (&d)[128], uint32_t da, uint32_t b, uint32_t off, int keep) {
    asm volatile(MMA_STEP_B("m64n256k16", ACC128, "%128", "%129", "%130", "%131", "0x80000020", "64")
                 : R64(d, 0), R64(d, 64) : "r"(da), "r"((b & 0x3FFFF) >> 4 | 256 << 16), "r"(off), "r"(keep) : "memory");
}

__device__ __forceinline__ uint32_t pack_bf16(float lo, float hi) {
    uint32_t r; asm("cvt.rn.bf16x2.f32 %0, %1, %2;" : "=r"(r) : "f"(hi), "f"(lo)); return r;
}
__device__ __forceinline__ float bf_lo(uint32_t v) { return __uint_as_float(v << 16); }
__device__ __forceinline__ float bf_hi(uint32_t v) { return __uint_as_float(v & 0xffff0000u); }
__device__ __forceinline__ float round_bf16(float v) { return bf_lo(pack_bf16(v, 0.f)); }
__device__ __forceinline__ uint32_t mul_bf16x2(uint32_t a, uint32_t b) {
    uint32_t r; asm("mul.rn.bf16x2 %0, %1, %2;" : "=r"(r) : "r"(a), "r"(b)); return r;
}
__device__ __forceinline__ uint32_t add_bf16x2(uint32_t a, uint32_t b) {
    uint32_t r; asm("add.rn.bf16x2 %0, %1, %2;" : "=r"(r) : "r"(a), "r"(b)); return r;
}
__device__ __forceinline__ uint32_t sub_bf16x2(uint32_t a, uint32_t b) {
    uint32_t r; asm("sub.rn.bf16x2 %0, %1, %2;" : "=r"(r) : "r"(a), "r"(b)); return r;
}
__device__ __forceinline__ uint32_t mul2_bf16x2(uint32_t a, uint32_t hi, uint32_t lo) {
    uint32_t r; asm("fma.rn.bf16x2 %0, %1, %2, %3;" : "=r"(r) : "r"(a), "r"(hi), "r"(mul_bf16x2(a, lo))); return r;
}
__device__ __forceinline__ float tanh_fast(float x) { float r; asm("tanh.approx.f32 %0, %1;" : "=f"(r) : "f"(x)); return r; }
__device__ __forceinline__ float gelu_tanh(float g) {
    float t = fmaf(g * g, 0.044715f * 0.7978845608f, 0.7978845608f) * g;
    float hg = 0.5f * g;
    return fmaf(hg, tanh_fast(t), hg);
}
__device__ __forceinline__ uint32_t geglu2(uint32_t g2, uint32_t u2) {
    return mul_bf16x2(pack_bf16(gelu_tanh(bf_lo(g2)), gelu_tanh(bf_hi(g2))), u2);
}
__device__ __forceinline__ float silu(float d) {
    float hd = 0.5f * d;
    return fmaf(hd, tanh_fast(hd), hd);
}
__device__ __forceinline__ float ex2_fast(float x) { float r; asm("ex2.approx.ftz.f32 %0, %1;" : "=f"(r) : "f"(x)); return r; }
__device__ __forceinline__ void unpack8(uint4 v, float (&f)[8]) {
    f[0] = bf_lo(v.x); f[1] = bf_hi(v.x); f[2] = bf_lo(v.y); f[3] = bf_hi(v.y);
    f[4] = bf_lo(v.z); f[5] = bf_hi(v.z); f[6] = bf_lo(v.w); f[7] = bf_hi(v.w);
}
template <int N> __device__ __forceinline__ void fence_regs(float (&d)[N]) {
#pragma unroll
    for (int i = 0; i < N; i++) asm volatile("" : "+f"(d[i]) :: "memory");
}

__device__ __forceinline__ float rcp_fast(float x) { float r; asm("rcp.approx.ftz.f32 %0, %1;" : "=f"(r) : "f"(x)); return r; }
__device__ __forceinline__ float sqrt_fast(float x) { float r; asm("sqrt.approx.ftz.f32 %0, %1;" : "=f"(r) : "f"(x)); return r; }
__device__ __forceinline__ uint32_t max_bf16x2(uint32_t a, uint32_t b) {
    uint32_t r; asm("max.bf16x2 %0, %1, %2;" : "=r"(r) : "r"(a), "r"(b)); return r;
}
__device__ __forceinline__ uint4 ldsm4(uint32_t addr) {
    uint4 v;
    asm volatile("ldmatrix.sync.aligned.m8n8.x4.shared.b16 {%0,%1,%2,%3}, [%4];"
                 : "=r"(v.x), "=r"(v.y), "=r"(v.z), "=r"(v.w) : "r"(addr) : "memory");
    return v;
}
__device__ __forceinline__ uint4 ldsm4_t(uint32_t addr) {
    uint4 v;
    asm volatile("ldmatrix.sync.aligned.m8n8.x4.trans.shared.b16 {%0,%1,%2,%3}, [%4];"
                 : "=r"(v.x), "=r"(v.y), "=r"(v.z), "=r"(v.w) : "r"(addr) : "memory");
    return v;
}
__device__ __forceinline__ void mma_16816(float (&c)[4], uint32_t a0, uint32_t a1, uint32_t a2, uint32_t a3, uint32_t b0, uint32_t b1) {
    asm("mma.sync.aligned.m16n8k16.row.col.f32.bf16.bf16.f32 {%0,%1,%2,%3}, {%4,%5,%6,%7}, {%8,%9}, {%0,%1,%2,%3};"
        : "+f"(c[0]), "+f"(c[1]), "+f"(c[2]), "+f"(c[3]) : "r"(a0), "r"(a1), "r"(a2), "r"(a3), "r"(b0), "r"(b1));
}
__device__ __forceinline__ void mma_1688(float (&c)[4], uint32_t a0, uint32_t a1, uint32_t b0) {
    asm("mma.sync.aligned.m16n8k8.row.col.f32.bf16.bf16.f32 {%0,%1,%2,%3}, {%4,%5}, {%6}, {%0,%1,%2,%3};"
        : "+f"(c[0]), "+f"(c[1]), "+f"(c[2]), "+f"(c[3]) : "r"(a0), "r"(a1), "r"(b0));
}
__device__ __forceinline__ void qk_tile(float (&c)[4], const uint4& q0, const uint4& q1, const uint4& k) {
    c[0] = c[1] = c[2] = c[3] = 0.f;
    mma_16816(c, q0.x, q0.y, q0.z, q0.w, k.x, k.y);
    mma_16816(c, q1.x, q1.y, q1.z, q1.w, k.z, k.w);
}
__device__ __forceinline__ uint32_t scaled_logits(bool first, float a0, float a1, float b0, float b1) {
    return mul2_bf16x2(pack_bf16(first ? a0 : b0, first ? a1 : b1), 0x3e353e35u, 0x379e379eu);
}
template <typename T> __device__ __forceinline__ T uniform(T v) { return __shfl_sync(0xffffffffu, v, 0); }

__device__ __forceinline__ void load_unit(const Params& prm, uint32_t base, int warp, int slot, int col, int row, uint32_t bytes) {
    asm volatile("{\n.reg .pred e;\nbar.warp.sync 0xffffffff;\nelect.sync _|e, 0xffffffff;\n"
        "@e mbarrier.arrive.expect_tx.shared::cta.b64 _, [%1], %7;\n"
        "@e cp.async.bulk.tensor.3d.shared::cluster.global.mbarrier::complete_tx::bytes.L2::cache_hint [%0], [%2, {%3, %4, %5}], [%1], %6;\n}"
        :: "r"(base + warp * 16384 + slot * ATT_SLOT), "r"(base + BAR_OFF + 512 + warp * 32 + slot * 8), "l"(&prm.qkv3), "r"(col),
           "r"(row), "r"(0), "l"(stream_policy()), "r"(bytes) : "memory");
}
__device__ __forceinline__ int walk_start(int warp) { return (warp & 2) * 512 + (warp & 1) * (16 - STG) * 32; }
__device__ __forceinline__ void attention(const Params& prm, uint32_t base, int grp, int warp, int lane) {
    constexpr float LOG2E = 1.4426950408889634f;
    const int g = lane >> 2, t = lane & 3;
    const bool up0 = 2 * t > g, up1 = 2 * t + 1 > g;
    const uint32_t keep = (up0 ? 0x0000ffffu : 0u) | (up1 ? 0xffff0000u : 0u);
    const uint32_t buf = base + warp * 16384, bar = base + BAR_OFF + 512 + warp * 32;
    const uint32_t qa = buf + (lane & 15) * 128 + (((lane >> 4) ^ (lane & 7)) << 4);
    const uint32_t ka = buf + 2048 + (lane & 7) * 128 + (((lane >> 3) ^ (lane & 7)) << 4);
    const uint32_t va = buf + 4096 + ((lane & 7) + (lane >> 4) * 8) * 128 + (((lane >> 3 & 1) ^ (lane & 7)) << 4);
    const uint32_t oa = buf + 2 * ATT_SLOT + t * 256 + ((g ^ 2 * t) << 4);
    const int len1 = 16 - STG + (warp & 1) * 2 * STG, len2 = warp < 10 ? 22 - len1 : (warp & 1 ? 2 - STG : 2 + STG);
    int row = walk_start(warp) + 16, end = row - 16 + len1 * 32, col = grp * 256 + (warp >> 2) * 64, orow = 0, ocol = 0;
    auto load = [&](int p, uint32_t read) {
        load_unit(prm, base, warp, p, col, row < end ? row : SEQ, read & prm.zero | ATT_SLOT);
        row += 16;
    };
    const uint32_t done = base + BAR_OFF + 528;
    auto stored = [&](auto part) {
        asm volatile("{\n.reg .pred e;\nelect.sync _|e, 0xffffffff;\ncp.async.bulk.wait_group %1;\n"
            "@e mbarrier.arrive.shared::cta.b64 _, [%0];\n}" :: "r"(done + part.value * 32), "n"(1 - part.value) : "memory");
    };
    uint4 k1[2][2], v[2][2][2];
    uint32_t l0[2], l1[2], m[2];
    uint32_t ph = 0;
    bool ready;
    auto logits = [&](int p) {
#pragma unroll
        for (int h = 0; h < 2; h++) {
            float s[3][4];
            const uint4 q0 = ldsm4((qa ^ h * 64) + p * ATT_SLOT), q1 = ldsm4((qa ^ h * 64 + 32) + p * ATT_SLOT);
            const uint4 k0 = ldsm4((ka ^ h * 64) + p * ATT_SLOT);
            k1[p][h] = ldsm4((ka ^ h * 64) + p * ATT_SLOT + 1024);
            qk_tile(s[0], q0, q1, k1[p ^ 1][h]);
            qk_tile(s[1], q0, q1, k0);
            qk_tile(s[2], q0, q1, k1[p][h]);
            l0[h] = scaled_logits(up0, s[0][0], s[1][2], s[1][0], s[2][2]);
            l1[h] = scaled_logits(up1, s[0][1], s[1][3], s[1][1], s[2][3]);
        }
    };
    auto values = [&](int p, int h, int d) { v[p][h][d] = ldsm4_t((va ^ h * 64 + d * 32) + p * ATT_SLOT); };
    auto next = [&](int p) {
        load(p, l0[0] | l0[1] | v[p][0][0].z | v[p][0][1].z | v[p][1][0].z | v[p][1][1].z);
        ph ^= p;
        ready = mbar_test(bar + (p ^ 1) * 8, ph);
#pragma unroll
        for (int h = 0; h < 2; h++) {
            m[h] = max_bf16x2(l0[h], l1[h]);
            m[h] = max_bf16x2(m[h], __shfl_xor_sync(0xffffffffu, m[h], 1));
            m[h] = max_bf16x2(m[h], __shfl_xor_sync(0xffffffffu, m[h], 2));
        }
    };
    auto step = [&](int p) {
        uint32_t pa[2], pb[2];
        float o[2][2][2][4];
        if (!ready) mbar_wait(bar + p * 8, ph);
#pragma unroll
        for (int h = 0; h < 2; h++) {
            const float ma = -LOG2E * bf_lo(m[h]), mb = -LOG2E * bf_hi(m[h]);
            const float a0 = ex2_fast(fmaf(bf_lo(l0[h]), LOG2E, ma)), a1 = ex2_fast(fmaf(bf_lo(l1[h]), LOG2E, ma));
            const float b0 = ex2_fast(fmaf(bf_hi(l0[h]), LOG2E, mb)), b1 = ex2_fast(fmaf(bf_hi(l1[h]), LOG2E, mb));
            float sum[4] = {0.f, 0.f, 0.f, 0.f};
            mma_1688(sum, pack_bf16(a0, a1), pack_bf16(b0, b1), 0x3f803f80u);
            const float ra = rcp_fast(sum[0]), rb = rcp_fast(sum[2]);
            pa[h] = pack_bf16(a0 * ra, a1 * ra);
            pb[h] = pack_bf16(b0 * rb, b1 * rb);
        }
        logits(p);
#pragma unroll
        for (int h = 0; h < 2; h++) {
#pragma unroll
            for (int d = 0; d < 2; d++) {
                const uint4& w = v[p ^ 1][h][d];
#pragma unroll
                for (int i = 0; i < 4; i++) o[0][h][d][i] = o[1][h][d][i] = 0.f;
                mma_1688(o[0][h][d], v[p][h][d].z, v[p][h][d].w, pa[h] & keep);
                values(p, h, d);
                mma_1688(o[0][h][d], w.x, w.y, pa[h] & ~keep);
                mma_16816(o[1][h][d], w.x, w.y, w.z, w.w, pb[h] & keep, pb[h] & ~keep);
            }
        }
        next(p);
        if (p == 0) asm volatile("cp.async.bulk.wait_group.read 0;\nbar.warp.sync 0xffffffff;" ::: "memory");
#pragma unroll
        for (int j = 0; j < 4; j++) {
            const float (&c)[2][2][4] = o[j / 2];
            const int e = j % 2;
            sts128((oa ^ e * 144) + p * 2048 + j / 2 * 1024,
                   make_uint4(pack_bf16(c[0][0][e], c[0][0][e + 2]), pack_bf16(c[0][1][e], c[0][1][e + 2]),
                              pack_bf16(c[1][0][e], c[1][0][e + 2]), pack_bf16(c[1][1][e], c[1][1][e + 2])));
        }
    };
#pragma unroll 1
    for (int seg = 0; seg < 4; seg++) {
        TRACE_S(9, warp * 8 + seg, 0); TRACE_S(53, warp * 8 + seg, 1); TRACE_S(54, warp * 8 + seg, 2); TRACE_S(55, warp * 8 + seg, 3);
        TRACE_S(46, warp * 8 + seg, 32); TRACE_S(47, warp * 8 + seg, 72);
        if (seg == 1) {
            row = (warp < 8 ? (warp & 2) * 16 + (warp & 4) * 3 + (warp & 1) * (6 + STG)
                            : (24 | 56 << 8 | (62 - STG) << 16 | (30 + STG) << 24) >> (warp & 3) * 8 & 63) * 32 - 16;
            end = row + 16 + len2 * 32;
            col = grp * 256 + 192;
        } else if (seg == 3) {
            stored(std::integral_constant<int, 0>());
        } else {
            orow = row - 16; ocol = col;
            mbar_wait(bar, ph);
#pragma unroll
            for (int h = 0; h < 2; h++) {
                k1[0][h] = ldsm4((ka ^ h * 64) + 1024);
                values(0, h, 0); values(0, h, 1);
            }
            load(0, k1[0][0].x | k1[0][1].x | v[0][0][0].z | v[0][0][1].z | v[0][1][0].z | v[0][1][1].z);
            mbar_wait(bar + 8, ph);
            logits(1);
#pragma unroll
            for (int h = 0; h < 2; h++) {
                values(1, h, 0); values(1, h, 1);
                if (up0 && (orow & 1023) == 0) l0[h] = __byte_perm(l0[h], 0xce6e, 0x3254);
                if (up1 && (orow & 1023) == 0) l1[h] = __byte_perm(l1[h], 0xce6e, 0x3254);
            }
            next(1);
            TRACE_S(51, warp * 8 + seg, 0);
        }
#pragma unroll 1
        for (int n = seg == 0 ? len1 - 1 : (seg == 3 ? len2 - 1 : 1); n > 0; n--) {
            step(0);
            step(1);
            asm volatile("{\n.reg .pred e;\nfence.proxy.async.shared::cta;\nbar.warp.sync 0xffffffff;\nelect.sync _|e, 0xffffffff;\n"
                "@e cp.async.bulk.tensor.2d.global.shared::cta.bulk_group [%0, {%2, %3}], [%1];\ncp.async.bulk.commit_group;\n}"
                :: "l"(&prm.o), "r"(buf + 2 * ATT_SLOT), "r"(ocol), "r"(orow) : "memory");
            orow += 32;
        }
    }
    stored(std::integral_constant<int, 1>());
    TRACE_S(57, warp, 0); TRACE_S(60, warp, 9);
    if (warp == 11 && lane == 0) {
#pragma unroll 1
        for (int part = 0; part < 2; part++) {
            mbar_wait(done + part * 32, 0);
            TRACE_S(36, part, 0); TRACE_S(10, part, 1);
            flag_add(prm.flags + F_O * 512 + part * 32);
            TRACE_S(34, part, 0); TRACE_S(50, part, 1);
        }
        TRACE_DUMP();
    }
    mbar_wait(bar, ph);
    mbar_wait(bar + 8, ph);
}

__device__ __forceinline__ void tail_gemm(const Params& prm, uint32_t base, uint32_t t0, unsigned epoch, int grp, int warp, int lane) {
    const uint32_t full = base + BAR_OFF, empty = full + 320, sig = full + 192, dep = full + 256;
    unsigned* const flags = prm.flags + grp * 128;
    if (warp >= 8) asm volatile("setmaxnreg.dec.sync.aligned.u32 %0;" :: "n"(AUX_REGS));
    if (warp == 8) {
        if (elect_one()) { prefetch_map(&prm.xn); prefetch_map(&prm.wtail); }
        auto load_w = [&](int i, int k) {
            asm volatile("{\n.reg .pred e;\nelect.sync _|e, 0xffffffff;\n"
                "@e cp.async.bulk.tensor.3d.shared::cluster.global.mbarrier::complete_tx::bytes [%0], [%2, {%4, %3, %4}], [%1];\n"
                "@e mbarrier.arrive.expect_tx.shared::cta.b64 _, [%1], %5;\n}"
                :: "r"(base + (i & 3) * G1_STAGE_BYTES + A_BYTES), "r"(full + (i & 3) * 8), "l"(&prm.wtail), "r"(k), "r"(0),
                   "n"(G1_STAGE_BYTES) : "memory");
        };
        while ((uint32_t)clock() - t0 < TW0) {}
#pragma unroll 1
        for (int i = 0; i < 4; i++) load_w(i, i * 64);
        flag_wait<true>(flags + F_LN * 512 + (lane & 3) * 32, epoch * CNT_LN);
        fence_proxy_async();
        TRACE(62);
#pragma unroll 1
        for (int i = 0, k = 0, row = grp * 512; i < 4 * TAIL; i++) {
            if (TAIL > 8 && i == 8) mbar_wait_warp(dep, 0);
            mbar_wait_warp(empty + (i & 3) * 8, ~i >> 2 & 1);
            asm volatile("{\n.reg .pred e;\nelect.sync _|e, 0xffffffff;\n"
                "@e cp.async.bulk.tensor.2d.shared::cluster.global.mbarrier::complete_tx::bytes [%0], [%2, {%3, %4}], [%1];\n}"
                :: "r"(base + (i & 3) * G1_STAGE_BYTES), "r"(full + (i & 3) * 8), "l"(&prm.xn), "r"(k), "r"(row) : "memory");
            if (i >= 4) load_w(i, k);
            k += 64;
            if (k == TAIL * 64) { k = 0; row += 128; }
        }
    } else if (warp == 9) {
        if (TAIL > 8) {
            flag_wait<true>(flags + F_LN2 * 512 + (lane & 3) * 32, epoch * CNT_LN);
            fence_proxy_async();
            __syncwarp();
        }
        if (lane == 0) {
            mbar_arrive(dep);
            prefetch_map(&prm.qkv3); prefetch_map(&prm.o);
            flag_wait(prm.flags + F_QKV * 512 + grp * 32, epoch * CNT_QKV);
        }
        __syncwarp();
    } else if (warp == 10) {
        if (lane == 0) {
#pragma unroll 1
            for (int p = 0; p < 2; p++) {
                mbar_wait(sig + p * 8, 0);
                flag_add(flags + F_TAIL * 512 + p * 32);
            }
        }
        __syncwarp();
    }
    if (warp >= 8) {
        asm volatile("bar.sync 2, 128;" ::: "memory");
        fence_proxy_async();
        mbar_wait_warp(empty + (warp - 8) * 8, ~TAIL & 1);
#pragma unroll 1
        for (int i = warp * 6 - 48; i < warp * 6 - 42; i++)
            load_unit(prm, base, i >> 1, i & 1, grp * 256 + (i >> 3) * 64, walk_start(i >> 1) - 16 + (i & 1) * 16, ATT_SLOT);
        if (warp == 9 && lane == 0) prm.epoch[blockIdx.x * 16] = epoch;
        if (warp == 10 && lane < 2) {
            mbar_wait(sig + 24, 0);
            flag_add(flags + F_TAIL * 512 + 64 + lane * 32);
        }
        asm volatile("bar.warp.sync 0xffffffff;\nsetmaxnreg.inc.sync.aligned.u32 168;" ::: "memory");
        return;
    }
    asm volatile("setmaxnreg.inc.sync.aligned.u32 %0;\nbar.sync 1, 256;" :: "n"(CONSUMER_REGS) : "memory");
    const uint32_t da = desc_a(base + (warp >> 2) * 8192);
    uint4* out = prm.tail + grp * 2048 - 512 + threadIdx.x;
    float acc[128];
    uint32_t pk[64];
    int i = 0;
    auto release = [&]() { if ((threadIdx.x & 127) == 0) mbar_arrive(empty + (i - 1 & 3) * 8); };
    auto store = [&](int j) {
        asm volatile("st.global.v4.u32 [%0], {%1,%2,%3,%4};" :: "l"(out + j / 2 * 8192 + j % 2 * 256),
                     "r"(pk[4 * j]), "r"(pk[4 * j + 1]), "r"(pk[4 * j + 2]), "r"(pk[4 * j + 3]) : "memory");
    };
#pragma unroll
    for (int j = 0; j < 128; j++) asm volatile("mov.b32 %0, 0;" : "=f"(acc[j]));
#pragma unroll
    for (int j = 0; j < 64; j++) asm volatile("mov.b32 %0, 0;" : "=r"(pk[j]));
#pragma unroll 1
    for (int p = 0; p < 4; p++) {
#pragma unroll
        for (int k = 0; k < TAIL; k++, i++) {
            TRACE_TAIL(0);
            mbar_wait(full + (i & 3) * 8, i >> 2 & 1);
            TRACE_S(45, warp * 64 + i, 0);
            if (warp >= 4 && k == TAIL - TSK) asm volatile("bar.sync 1, 256;" ::: "memory");
            mma_step_tail(acc, da, base + A_BYTES, (i & 3) * (G1_STAGE_BYTES / 16), k);
            if (warp < 4 && k == TAIL - 1) asm volatile("bar.arrive 1, 256;" ::: "memory");
            wg_wait<1>();
            if (k) release();
            if (p) {
#pragma unroll
                for (int j = k * 16 / TAIL; j < (k + 1) * 16 / TAIL; j++) store(j);
                if (k == TAIL - 1) { __syncwarp(); if (lane == 0) mbar_arrive(sig + p * 8 - 8); }
            }
        }
        wg_wait<0>();
        fence_regs(acc);
        release();
        TRACE_S(48, p + warp * 4, 0);
#pragma unroll
        for (int j = 0; j < 64; j++) pk[j] = pack_bf16(acc[2 * j], acc[2 * j + 1]);
        out += 512;
        TRACE_S(49, p + warp * 4, 19);
    }
#pragma unroll
    for (int j = 0; j < 16; j++) store(j);
    __syncwarp();
    if (lane == 0) mbar_arrive(sig + 24);
    TRACE_S(58, warp, 4);
    asm volatile("setmaxnreg.dec.sync.aligned.u32 168;");
}

__device__ __forceinline__ bool tile_is_qkv(int nt) { return nt < 4 || (nt >= 8 && nt < 16); }
__device__ __forceinline__ int tile_index(int nt) { return nt < 4 ? nt + 8 : (nt < 8 ? nt - 4 : (nt < 16 ? nt - 8 : nt - 12)); }

struct Role {
    int rank, role, mblk, nslot, w0_col;
    const CUtensorMap* w0;
    __device__ __forceinline__ Role(const Params& prm) {
        uint32_t id;
        asm volatile("mov.u32 %0, %%ctaid.x;" : "=r"(id));
        const uint32_t cl = id / 2;
        rank = id & 1;
        role = pick(cl < 4, 32 + cl * 8, cl - 8 + max(4u, (cl - 1) * 37 >> 8)) * 2 + rank;
        mblk = role & 15; nslot = role >> 4;
        w0 = &prm.wqkv + pick(nslot < 4, 0, 1 + rank);
        w0_col = pick(nslot < 4, 32 + nslot * 4 + rank * 2, nslot * 2 - 8);
    }
};

__global__ void __cluster_dims__(2, 1, 1) __launch_bounds__(384, 1)
fused_kernel(const __grid_constant__ Params prm) {
    TRACE_GET(c0);
    const uint32_t base = smem_u32(smem_raw) & ~1023u;
    const uint32_t bars = base + BAR_OFF;
    auto full1 = [&](int s) { return bars + s * 8; };
    auto empty1 = [&](int s) { return bars + 32 + s * 8; };
    auto full2 = [&](int s) { return bars + 64 + s * 8; };
    auto empty2 = [&](int s) { return bars + 128 + s * 8; };
    const uint32_t sig_bar = bars + 192, dep_bar = bars + 256, cs_bar = bars + 304, fold_bar = bars + 320, x_bar = bars + 352;
    const uint32_t stats = bars + 1536;
    auto stage2 = [&](int q) { return base + q * G2_STAGE_BYTES; };
    const uint32_t aux = base + AUX_OFF;

    asm volatile("{\n.reg .pred p;\nsetp.eq.u32 p, %1, 0;\n@p mbarrier.init.shared::cta.b64 [%0], 1;\n"
        "fence.mbarrier_init.release.cluster;\nbarrier.cluster.arrive.relaxed.aligned;\n}" :: "r"(bars), "r"(threadIdx.x) : "memory");
    const int warp = __shfl_sync(0xffffffffu, threadIdx.x >> 5, 0);
    auto cluster_wait = []() { asm volatile("barrier.cluster.wait.acquire.aligned;" ::: "memory"); };
    if ((warp | (blockIdx.x & NGEMM)) == 8) {
        const Role r(prm);
        asm volatile("{\n.reg .pred e;\nelect.sync _|e, 0xffffffff;\n"
            "@e prefetch.tensormap [%0];\n@e prefetch.tensormap [%1];\n}" :: "l"(&prm.x), "l"(r.w0) : "memory");
        cluster_wait();
        load_stage1(base, base + A_BYTES + r.rank * 16384, full1(0), &prm.x, r.w0, 0, r.mblk * 128, r.w0_col, 0, stream_policy());
    } else {
        cluster_wait();
    }
    const uint32_t t0 = clock();
    asm volatile("{\n.reg .pred e, q;\nelect.sync _|e, 0xffffffff;\nsetp.ne.and.u32 q, %2, 0, e;\n"
        "@q mbarrier.init.shared::cta.b64 [%0], %1;\n@e mbarrier.init.shared::cta.b64 [%0 + 8], %1;\n"
        "@e mbarrier.init.shared::cta.b64 [%0 + 16], %1;\n@e mbarrier.init.shared::cta.b64 [%0 + 24], %1;\n"
        "fence.mbarrier_init.release.cluster;\nbarrier.cluster.arrive.relaxed.aligned;\n}"
        :: "r"(bars + warp * 32), "r"(1 << (0x10fa08 >> warp * 2 & 3)), "r"(warp) : "memory");
    const int lane = threadIdx.x & 31;
    const Role me(prm);
    const int rank = me.rank, role = me.role, mblk = me.mblk, nslot = me.nslot, w0_col = me.w0_col;
    const CUtensorMap* const w0 = me.w0;

    if (blockIdx.x >= NGEMM) {
        if (warp == 9) { TRACE_CLEAR(); TRACE_GT(0); TRACE_PUT(1, c0); }
        if (elect_one()) {
            mbar_init(bars + 512 + warp * 32, 1); mbar_init(bars + 520 + warp * 32, 1);
            mbar_init(bars + 528 + warp * 32, 12);
            asm volatile("fence.mbarrier_init.release.cluster;" ::: "memory");
        }
        cluster_wait();
        const uint32_t seen = __ldcg(prm.epoch + blockIdx.x * 16);
        tail_gemm(prm, base, t0, seen + 1, blockIdx.x - NGEMM, warp, lane);
        uint32_t tid;
        asm volatile("mov.u32 %0, %%tid.x;" : "=r"(tid));
        attention(prm, base, blockIdx.x - NGEMM, uniform(tid >> 5), tid & 31);
    } else if (warp < 8) {
        asm volatile("setmaxnreg.inc.sync.aligned.u32 %0;" :: "n"(CONSUMER_REGS));
        const int wg = __shfl_sync(0xffffffffu, threadIdx.x >> 7, 0);
        const int cw = threadIdx.x >> 5;
        const int tid = threadIdx.x & 127;
        float acc[128];
        uint32_t pk[64];
#pragma unroll
        for (int i = 0; i < 64; i++) asm volatile("mov.b32 %0, 0;" : "=r"(pk[i]));
#pragma unroll
        for (int i = 0; i < 128; i++) asm volatile("mov.b32 %0, 0;" : "=f"(acc[i]));
        cluster_wait();

        const int orow = ((lane >> 2) & 1) * (SEQ / 2) + mblk * 64 + cw * 8 + (lane >> 3);
        __nv_bfloat16* optr = prm.pxn + (mblk * 128 + nslot * 16 + cw * 2) * DM + lane * 8;
        const uint32_t da = desc_a(base + wg * 8192), db = desc_b(base + A_BYTES);
        auto release = [&](uint32_t bar) { if (tid < 2) mbar_arrive_cluster(bar, tid); };
        auto store_pk = [&](__nv_bfloat16* p, int j) {
            asm volatile("st.global.v4.u32 [%0], {%1,%2,%3,%4};"
                         :: "l"(p), "r"(pk[4 * j]), "r"(pk[4 * j + 1]), "r"(pk[4 * j + 2]), "r"(pk[4 * j + 3]) : "memory");
        };
        auto chunk_geglu = [&](int j) {
#pragma unroll
            for (int i = 4 * j; i < 4 * j + 4; i++) pk[i] = geglu2(pk[i], pk[32 + i]);
            store_pk(optr + (j & 1) * 4 * K2 + (j >> 1) * 32, j);
        };
        auto chunk_qkv = [&](int c) {
            store_pk(optr + c * 32, 2 * c);
            store_pk(optr + 4 * NQKV + c * 32, 2 * c + 1);
        };
        auto signal_stores = [&](int p) { __syncwarp(); if (lane == 0) mbar_arrive(sig_bar + p * 8); };

        auto chunk_ln = [&](int k) {
            float* const mo = reinterpret_cast<float*>(pk + 32);
            if (k == LNL) {
                const uint4* xp = reinterpret_cast<const uint4*>(prm.px + (optr - prm.pxn));
                pk[38] = __ldcg(prm.epoch + blockIdx.x * 16 + 2);
#pragma unroll
                for (int i = 0; i < 8; i++) {
                    const uint4 v = ldg_stream(xp + i * 32, stream_policy());
                    pk[4 * i] = v.x; pk[4 * i + 1] = v.y; pk[4 * i + 2] = v.z; pk[4 * i + 3] = v.w;
                }
            } else if (k >= LN_STEP && k < LN_STEP + 3) {
                if (k == LN_STEP) {
                    mo[0] = bf_lo(uniform(pk[0])); mo[1] = bf_lo(uniform(pk[16]));
                    mo[2] = mo[3] = mo[4] = mo[5] = 0.f;
                }
#pragma unroll
                for (int i = (k - LN_STEP) * 11; i < (k - LN_STEP) * 11 + 11 && i < 32; i++) {
                    const int r = i & 1;
                    const uint32_t w = pk[r * 16 + i / 2];
                    const float lo = bf_lo(w) - mo[r], hi = bf_hi(w) - mo[r];
                    mo[2 + r] += lo + hi;
                    mo[4 + r] = fmaf(hi, hi, fmaf(lo, lo, mo[4 + r]));
                }
            } else if (k == LN_STEP + 3) {
                const bool second = lane & 16;
                float m1 = (second ? mo[3] : mo[2]) + __shfl_xor_sync(0xffffffffu, second ? mo[2] : mo[3], 16);
                float m2 = (second ? mo[5] : mo[4]) + __shfl_xor_sync(0xffffffffu, second ? mo[4] : mo[5], 16);
#pragma unroll
                for (int o = 8; o > 0; o >>= 1) {
                    m1 += __shfl_xor_sync(0xffffffffu, m1, o);
                    m2 += __shfl_xor_sync(0xffffffffu, m2, o);
                }
                m1 *= 1.f / DM;
                const float var = fmaxf(fmaf(-m1, m1, m2 * (1.f / DM)), 0.f);
                const float mean = round_bf16((second ? mo[1] : mo[0]) + m1);
                const float inv = rcp_fast(round_bf16(sqrt_fast(round_bf16(round_bf16(var) + 1e-5f))));
                if ((lane & 15) == 0) st_tagged(prm.stats + (uint32_t)(optr - prm.pxn) / DM + second, -mean, inv, 2 - (pk[38] & 1));
                const uint32_t split = pack_bf16(inv - round_bf16(inv), inv);
#pragma unroll
                for (int r = 0; r < 2; r++) {
                    const uint32_t f = __shfl_sync(0xffffffffu, split, r * 16);
                    pk[32 + 3 * r] = __byte_perm(__shfl_sync(0xffffffffu, __float_as_uint(mean), r * 16), 0, 0x3232);
                    pk[33 + 3 * r] = __byte_perm(f, 0, 0x3232);
                    pk[34 + 3 * r] = __byte_perm(f, 0, 0x1010);
                }
            } else if (k >= LN_STEP + 4 && k < LN_STEP + 8) {
#pragma unroll
                for (int i = k - LN_STEP - 4; i < 8; i += 4) {
                    const uint32_t* n = pk + 32 + i / 4 * 3;
#pragma unroll
                    for (int j = 4 * i; j < 4 * i + 4; j++) pk[j] = mul2_bf16x2(sub_bf16x2(pk[j], n[0]), n[1], n[2]);
                    store_pk(optr + i * 256, i);
                }
                if (k == LN_STEP + 5 || k == LN_STEP + 7) signal_stores(k == LN_STEP + 5 ? 0 : 7);
            } else if (k == FOLD_STEP) {
                mbar_wait(fold_bar, 0);
                const uint32_t sp = stats + (cw * 16 + (lane >> 2)) * 8;
                const uint32_t sel = lane & 2 ? 0x4444 : (lane & 1 ? 0x4432 : 0x3232);
                const float2 sa = lds64f(sp), sb = lds64f(sp + 64);
                mma_rank(acc, __byte_perm(__float_as_uint(sa.x), 0, sel), __byte_perm(__float_as_uint(sb.x), 0, sel), desc_b(aux));
                mo[0] = sa.y; mo[1] = sb.y;
            }
        };

        bool gated = false;
        TRACE_SLOT(tile_slot, 16 + wg * 8);
#pragma unroll 1
        for (int t = 0; t < G1_TILES; t++) {
#pragma unroll
            for (int k = 0; k < G1_KSTEPS; k++) {
                const int s = k & 3;
                TRACE_STEP(t, k, 0);
                mbar_wait(full1(s), (k >> 2) & 1);
                if (k == 0) TRACE_S(12, t, 0);
                TRACE_STEP(t, k, 1);
                if (wg == 1 && k == G1_KSTEPS - (t ? G1_SKEW : SK0)) asm volatile("bar.sync 1, 256;" ::: "memory");
                if (k >= G1_KSTEPS - TAIL && t == G1_TILES - 1) mma_step224(acc, da, db, s * G1_STAGE_BYTES / 16, k);
                else mma_step(acc, da, db, s * G1_STAGE_BYTES / 16, k);
                if (wg == 0 && k == G1_KSTEPS - 1) asm volatile("bar.arrive 1, 256;" ::: "memory");
                wg_wait<1>();
                if (k > 0) release(empty1((k - 1) & 3));
                TRACE_STEP(t, k, 2);
                if (t == 0) chunk_ln(k);
                if (k >= 1 && k <= 8 && gated) {
                    chunk_geglu(k - 1);
                    if (k == 8) signal_stores(t + 1);
                }
                if (t != 0 && !gated) {
                    if (k >= QK0 && k < QK0 + 8) chunk_qkv(k + 5 & 7);
                    if (k == QK0 + 7 && t == 2) signal_stores(3);
                }
                if (TAIL && k == TLD && t == G1_TILES - 1) {
#pragma unroll
                    for (int i = 0; i < 2; i++) {
                        const uint4 v = ldg_stream(prm.tail + role * 512 + i * 256 + threadIdx.x, stream_policy());
                        pk[16 + 4 * i] = v.x; pk[17 + 4 * i] = v.y; pk[18 + 4 * i] = v.z; pk[19 + 4 * i] = v.w;
                    }
                }
                if (TAIL && k == TLD + 3 && t == G1_TILES - 1) {
#pragma unroll
                    for (int i = 0; i < 8; i++)
                        asm volatile("shl.b32 %0, %2, 16;\nand.b32 %1, %2, 0xffff0000;" : "=r"(pk[2 * i]), "=r"(pk[2 * i + 1]) : "r"(pk[16 + i]));
                }
                if (k == 12) {
                    const int nt = t * 8 + nslot;
                    gated = !tile_is_qkv(nt);
                    optr = !gated ? prm.qkv + (size_t)orow * NQKV + tile_index(nt) * 256 + (lane & 3) * 8
                                  : prm.pa2 + (size_t)orow * K2 + DM + tile_index(nt) * 128 + (lane & 3) * 8;
                    asm volatile("" : "+l"(optr));
                }
            }
            wg_wait<0>();
            fence_regs(acc);
            release(empty1(3));
            if (t == 0) {
#pragma unroll
                for (int i = 0; i < 128; i++) acc[i] *= __uint_as_float(pk[32 + i / 2 % 2]);
                fence_regs(acc);
            }
            if (TAIL && t == G1_TILES - 1) {
#pragma unroll
                for (int i = 0; i < 16; i++) acc[112 + i] += __uint_as_float(pk[i]);
                fence_regs(acc);
            }
#pragma unroll
            for (int i = 0; i < 64; i++) {
                const int e = (i & ~7) * 2 + (i & 3) * 4 + (i & 4) / 2;
                pk[i] = pack_bf16(acc[e], acc[e + 1]);
            }
            TRACE_NEXT(tile_slot);
        }

        float accd[64], accs[64];
#pragma unroll
        for (int i = 0; i < 64; i++) accd[i] = 0.f;
#pragma unroll
        for (int u = 0; u < G2_HEAD; u++) {
            const int q = u % G2_STAGES;
            mbar_wait(full2(q), (u / G2_STAGES) & 1);
            mma_step(accd, da, db, q * G2_STAGE_BYTES / 16, u);
            wg_wait<1>();
            if (u > 0) release(empty2((u - 1) % G2_STAGES));
            if (HALF == 0 && u >= 1) chunk_geglu(u - 1);
            if (HALF == 1 && u >= 1) {
                const int j = (u - 1) / 2;
#pragma unroll
                for (int i = 2 * u - 2; i < 2 * u; i++) pk[i] = geglu2(pk[i], pk[32 + i]);
                if (u % 2 == 0) store_pk(optr + (j & 1) * 4 * K2 + (j >> 1) * 32, j);
            }
            if (HALF == 2 && u % 2 == 0 && u > 0) chunk_geglu(u / 2 - 1);
            if (u == G2_HEAD - 1) signal_stores(6);
        }
        {
            int q = G2_HEAD % G2_STAGES, qp = (G2_HEAD - 1) % G2_STAGES; uint32_t ph = (G2_HEAD / G2_STAGES) & 1;
#pragma unroll 1
            for (int u = G2_HEAD; u < G2_DSTEPS; u++) {
                mbar_wait(full2(q), ph);
                mma_step(accd, da, db, q * (G2_STAGE_BYTES / 16), 1);
                wg_wait<1>();
                release(empty2(qp));
                qp = q;
                if (++q == G2_STAGES) { q = 0; ph ^= 1; }
            }
        }
        TRACE_NEXT(tile_slot);
#pragma unroll
        for (int i = 0; i < 64; i++) accs[i] = 0.f;
        uint32_t gk[32], xr[32];
        const uint32_t xs = aux + cw * 2048;
        const uint32_t xrow = xs + ((lane & 7) + ((lane >> 3) & 1) * 8) * 128;
        auto xaddr = [&](int j) { return xrow + (j >> 2) * 16384 + (((((j & 3) * 2) + (lane >> 4)) ^ (lane & 7)) << 4); };
#pragma unroll
        for (int u = G2_DSTEPS; u < G2_KSTEPS; u++) {
            const int q = u % G2_STAGES, v = u - G2_DSTEPS;
            mbar_wait(full2(q), (u / G2_STAGES) & 1);
            if (G2_SKEW > 0 && wg == 1 && u == G2_KSTEPS - G2_SKEW) asm volatile("bar.sync 1, 256;" ::: "memory");
            mma_step(accs, da, db, q * G2_STAGE_BYTES / 16, v);
            if (G2_SKEW > 0 && wg == 0 && u == G2_KSTEPS - 1) asm volatile("bar.arrive 1, 256;" ::: "memory");
            if (v >= 1 && v <= 8) {
#pragma unroll
                for (int i = 4 * (v - 1); i < 4 * v; i++) {
                    const uint32_t d2 = pack_bf16(accd[2 * i], accd[2 * i + 1]);
                    gk[i] = pack_bf16(silu(bf_lo(d2)), silu(bf_hi(d2)));
                }
            }
            if (v == 9) mbar_wait(x_bar, 0);
            if (v >= 9 && v <= 12) {
#pragma unroll
                for (int j = 2 * (v - 9); j < 2 * (v - 8); j++)
                    asm volatile("ldmatrix.sync.aligned.m8n8.x4.shared.b16 {%0,%1,%2,%3}, [%4];"
                                 : "=r"(xr[4 * j]), "=r"(xr[4 * j + 1]), "=r"(xr[4 * j + 2]), "=r"(xr[4 * j + 3])
                                 : "r"(xaddr(j)) : "memory");
            }
            wg_wait<1>();
            if (v == 0) fence_regs(accd);
            if (u - 1 + G2_STAGES < G2_KSTEPS) release(empty2((u - 1) % G2_STAGES));
        }
        __nv_bfloat16* po = prm.pout + (mblk * 128 + cw * 16 + (lane >> 3)) * DM + nslot * 128 + (lane & 7) * 8;
        uint32_t so = xs + (lane >> 3) * 128 + (((lane & 7) ^ (lane >> 3)) << 4);
        const int c0 = uniform(nslot * 128), c1 = uniform(mblk * 128 + cw * 16);
        const uint32_t xu = uniform(xs);
        if (EPI & 2) asm volatile("" : "+l"(po), "+r"(so));
        wg_wait<0>();
        fence_regs(accs);
        TRACE_NEXT(tile_slot);
        TRACE_END();
        if ((EPI & 16) && prm.zero == 0) return;
        if ((EPI & 32) && prm.zero == wg) return;
#pragma unroll
        for (int j = 0; j < 8; j++) {
            uint32_t r[4];
#pragma unroll
            for (int i = 0; i < 4; i++) {
                const int e = j * 4 + i;
                const uint32_t s2 = pack_bf16(accs[2 * e], accs[2 * e + 1]);
                if (EPI & 1) asm("fma.rn.bf16x2 %0, %1, %2, %3;" : "=r"(r[i]) : "r"(s2), "r"(gk[e]), "r"(xr[e]));
                else r[i] = add_bf16x2(xr[e], mul_bf16x2(s2, gk[e]));
            }
            asm volatile("stmatrix.sync.aligned.m8n8.x4.shared.b16 [%0], {%1,%2,%3,%4};"
                         :: "r"(xaddr(j)), "r"(r[0]), "r"(r[1]), "r"(r[2]), "r"(r[3]) : "memory");
            if ((EPI & 2) && (!(EPI & 4) || j / 4 == (EPI >> 6 & 1))) {
                if (j == 3 || j == 7) {
                    __syncwarp();
#pragma unroll
                    for (int i = 0; i < 4; i++) {
                        const uint4 v = lds128((so ^ (i & 1) * 64) + (j >> 2) * 16384 + i * 512);
                        asm volatile("st.global.v4.u32 [%0], {%1,%2,%3,%4};"
                                     :: "l"(po + (j >> 2) * 64 + i * 4 * DM), "r"(v.x), "r"(v.y), "r"(v.z), "r"(v.w) : "memory");
                    }
                }
            } else if (EPI & 4) {
                if (j == 7 || (j == 3 && !(EPI & 8))) {
                    asm volatile("{\n.reg .pred e;\nfence.proxy.async.shared::cta;\nbar.warp.sync 0xffffffff;\nelect.sync _|e, 0xffffffff;\n"
                        "@e cp.async.bulk.tensor.2d.global.shared::cta.bulk_group [%0, {%2, %3}], [%1];\n}"
                        :: "l"(&prm.out), "r"(xu + (j >> 2) * 16384), "r"(c0 + (j >> 2) * 64), "r"(c1) : "memory");
                    if (EPI & 8) asm volatile("{\n.reg .pred e;\nelect.sync _|e, 0xffffffff;\n"
                        "@e cp.async.bulk.tensor.2d.global.shared::cta.bulk_group [%0, {%2, %3}], [%1];\n}"
                        :: "l"(&prm.out), "r"(xu), "r"(c0), "r"(c1) : "memory");
                }
            } else if (j == 3 || j == 7) {
                asm volatile("fence.proxy.async.shared::cta;" ::: "memory");
                __syncwarp();
                if (lane == 0) {
                    tma_store_2d(&prm.out, xs + (j >> 2) * 16384, nslot * 128 + (j >> 2) * 64, mblk * 128 + cw * 16);
                    asm volatile("cp.async.bulk.commit_group;" ::: "memory");
                }
            }
        }
        if (EPI & 4) asm volatile("cp.async.bulk.commit_group;\ncp.async.bulk.wait_group.read 0;" ::: "memory");
        else if (!(EPI & 2) && lane == 0) asm volatile("cp.async.bulk.wait_group.read 0;" ::: "memory");
        if (tid == 0) { TRACE_NEXT(tile_slot); if (wg == 1) TRACE_GT(13); TRACE_DUMP(); }
    } else {
        asm volatile("setmaxnreg.dec.sync.aligned.u32 %0;" :: "n"(AUX_REGS));
        cluster_wait();
        unsigned* const flags = prm.flags + mblk * 32;
        if (warp == 9) {
            TRACE_CLEAR(); TRACE_GT(0);
            if (lane == 0) {
                const unsigned epoch = __ldcg(prm.epoch + blockIdx.x * 16 + 2) + 1;
                mbar_wait(sig_bar, 0);
                TRACE(11);
                flag_add(flags + F_LN * 512);
                TRACE(42);
                flag_wait(flags + F_LN * 512, epoch * CNT_LN);
                fence_proxy_async();
                mbar_arrive(dep_bar);
                mbar_wait(sig_bar + 56, 0);
                flag_add(flags + F_LN2 * 512);
                flag_wait(flags + F_LN2 * 512, epoch * CNT_LN);
                fence_proxy_async();
                mbar_arrive(dep_bar + 40);
                TRACE(59);
                prm.epoch[blockIdx.x * 16 + 2] = epoch;
                for (int p = nslot < 4 ? 3 : 2; p < 7; p++) {
                    mbar_wait(sig_bar + p * 8, 0);
                    if (p == 3) TRACE(37);
                    flag_add(p == 3 ? prm.flags + F_QKV * 512 + (nslot & 3) * 32 : flags + (p < 6 ? F_EARLY : F_LATE) * 512);
                    if (p == 3) TRACE(43);
                }
            }
        } else if (warp > 9) {
            const int w = warp - 10;
            const unsigned epoch = __ldcg(prm.epoch + blockIdx.x * 16 + w) + 1;
            const uint32_t tag = 1 + (epoch & 1);
                const uint32_t at = (w ? CB : CA) >> (CIDX) * 4 & 15;
            mbar_wait(empty1(at & 3), 0);
            mbar_wait(empty1(at & 3), at >> 3);
            if (elect_one()) {
                mbar_expect_tx(cs_bar + w * 8, 16384);
                if (CKEEP) asm volatile("cp.async.bulk.tensor.3d.shared::cluster.global.mbarrier::complete_tx::bytes [%0], [%1, {%3, %4, %5}], [%2];"
                    :: "r"(aux + w * 16384), "l"(w0), "r"(cs_bar + w * 8), "r"(0), "r"(((mblk & ~1) + w) * 64), "r"(w0_col) : "memory");
                else tma_3d(aux + w * 16384, w0, cs_bar + w * 8, 0, ((mblk & ~1) + w) * 64, w0_col, stream_policy());
            }
            float cs[8];
#pragma unroll
            for (int d = 0; d < 8; d++) cs[d] = 0.f;
            const uint32_t wa = aux + w * 8192 + (lane >> 3) * 128 + (((lane & 7) ^ (lane >> 3)) << 4);
            uint4 v[9];
            auto fetch = [&](int h, uint32_t off) {
#pragma unroll
                for (int j = 0; j < 4; j++) v[h * 4 + j] = lds128((wa ^ (j & 1) * 64) + off + h * 2048 + j * 512);
            };
            auto add = [&](int h) {
#pragma unroll
                for (int j = 0; j < 4; j++) {
                    float f[8];
                    unpack8(v[h * 4 + j], f);
#pragma unroll
                    for (int d = 0; d < 8; d++) cs[d] += f[d];
                }
            };
            if (CST) { mbar_wait(empty1(CST & 3), 0); mbar_wait(empty1(CST & 3), CST >> 3); }
            mbar_wait(cs_bar, 0);

            fetch(0, 0);
#pragma unroll 1
            for (int i = 0; i < 4; i++) {
                fetch(1, (i >> 1) * 16384 + (i & 1) * 4096);
                add(0);
                if (i == 1) mbar_wait(cs_bar + 8, 0);
                fetch(0, (i + 1 & 2) * 8192 + (~i & 1) * 4096);
                add(1);
            }
#pragma unroll
            for (int d = 0; d < 4; d++)
                cs[d] = (lane & 16 ? cs[d + 4] : cs[d]) + __shfl_xor_sync(0xffffffffu, lane & 16 ? cs[d] : cs[d + 4], 16);
#pragma unroll
            for (int d = 0; d < 2; d++)
                cs[d] = (lane & 8 ? cs[d + 2] : cs[d]) + __shfl_xor_sync(0xffffffffu, lane & 8 ? cs[d] : cs[d + 2], 8);
            st_tagged(prm.colsum + (nslot * 2 + rank) * 1024 + (mblk >> 1) * 128 + w * 64 + (lane & 7) * 8 + (lane >> 3) * 2,
                      cs[0], cs[1], tag);

#pragma unroll
            for (int m = 0; m < 9; m++) v[m] = make_uint4(0, 0, 0, 0);
            const float* parts = prm.colsum + (nslot * 2 + (lane >> 4)) * 1024 + w * 64 + (lane & 15) * 4;
            const float* const rows = &prm.stats[mblk * 128 + w * 64 + lane * 2].x;
#pragma unroll 1
            for (int spins = 0; spins < (1 << 16); spins++) {
                bool missing = false;
                asm volatile("" : "+l"(parts));
#pragma unroll
                for (int m = 0; m < 9; m++) {
                    if (untagged(v[m], tag)) {
                        missing = true;
                        v[m] = ld_relaxed(m < 8 ? parts + m * 128 : rows);
                    }
                }
                if (!missing) break;
            }
            float4 c = make_float4(0.f, 0.f, 0.f, 0.f);
#pragma unroll
            for (int m = 0; m < 8; m++) {
                c.x += __uint_as_float(v[m].x ^ tag); c.y += __uint_as_float(v[m].y ^ tag);
                c.z += __uint_as_float(v[m].z ^ tag); c.w += __uint_as_float(v[m].w ^ tag);
            }
            sts128(stats + w * 512 + lane * 16, make_uint4(v[8].x ^ tag, v[8].y ^ tag, v[8].z ^ tag, v[8].w ^ tag));
            const uint32_t ca = aux + w * 8192 + (lane >> 4) * 16384 + (lane & 15) * 8;
#pragma unroll
            for (int r = 0; r < 3; r++) {
                const uint32_t lo = pack_bf16(c.x, c.y), hi = pack_bf16(c.z, c.w);
                sts64f((ca ^ r * 16) + r * 128, __uint_as_float(lo), __uint_as_float(hi));
                c.x -= bf_lo(lo); c.y -= bf_hi(lo); c.z -= bf_lo(hi); c.w -= bf_hi(hi);
            }
            asm volatile("fence.proxy.async.shared::cta;" ::: "memory");
            __syncwarp();
            if (lane == 0) {
                mbar_arrive(fold_bar);
                prm.epoch[blockIdx.x * 16 + w] = epoch;
                if (w == 0) {
                    TRACE_S(35, w, 0);
                    if (TAIL) { flag_wait(flags + F_TAIL * 512, epoch); mbar_arrive(x_bar + 8); }
                    flag_wait(flags + F_EARLY * 512, epoch * CNT_EARLY);
                    fence_proxy_async(); mbar_arrive(dep_bar + 8);
                    flag_wait(flags + F_LATE * 512, epoch * CNT_LATE);
                    fence_proxy_async(); mbar_arrive(dep_bar + 16);
                    flag_wait(prm.flags + F_O * 512, epoch * CNT_O);
                    fence_proxy_async(); mbar_arrive(dep_bar + 24);
                    flag_wait(prm.flags + F_O * 512 + 32, epoch * CNT_O);
                    fence_proxy_async(); mbar_arrive(dep_bar + 32);
                }
            }
        } else {
#pragma unroll
            for (int k = 1; k < G1_STAGES; k++) {
                const uint32_t sa = base + k * G1_STAGE_BYTES;
                if (PACE0 + PACE) while ((uint32_t)clock() - t0 < (k == 3 ? PACE3 : PACE0 + (k - 1) * PACE)) {}
                load_stage1(sa, sa + A_BYTES + rank * 16384, full1(k), &prm.x, w0, k * 64, mblk * 128, w0_col, 0, stream_policy());
            }
            if (elect_one()) {
                prefetch_map(&prm.xn); prefetch_map(&prm.wqkv); prefetch_map(&prm.wu); prefetch_map(&prm.wg);
                prefetch_map(&prm.a2); prefetch_map(&prm.wo); prefetch_map(&prm.wd); prefetch_map(&prm.out);
            }
            auto load_x = [&]() {
                if (elect_one()) {
                    mbar_expect_tx(x_bar, 32768);
                    tma_2d(aux, &prm.x, x_bar, nslot * 128, mblk * 128, stream_policy());
                    tma_2d(aux + 16384, &prm.x, x_bar, nslot * 128 + 64, mblk * 128, stream_policy());
                }
                __syncwarp();
            };
            uint32_t ph = 0;
#pragma unroll 1
            for (int t = 0; t < G1_TILES; t++) {
                const int nt = t * 8 + nslot;
                const CUtensorMap* const mb = tile_is_qkv(nt) ? &prm.wqkv : (rank ? &prm.wu : &prm.wg);
                const int col = tile_is_qkv(nt) ? tile_index(nt) * 4 + rank * 2 : tile_index(nt) * 2;
                if (t == 1) { TRACE_PUT(1, c0); TRACE_PUT(2, t0); TRACE(14); mbar_wait_warp(dep_bar, 0); TRACE(3); }
#pragma unroll 1
                for (int k = t ? 0 : G1_STAGES; k < G1_KSTEPS; k++) {
                    const int s = k & 3;
                    if (t == 1 && k == 8) mbar_wait_warp(dep_bar + 40, 0);
                    if (TAIL && t * 16 + k == 64 + TLD) { TRACE(61); mbar_wait_warp(x_bar + 8, 0); TRACE(63); }
                    if (PFW && t * 16 + k == (PFK) && mblk >= PF0 && mblk < PF1) {
                        asm volatile("{\n.reg .pred e;\nelect.sync _|e, 0xffffffff;\n"
                            "@e cp.async.bulk.prefetch.tensor.5d.L2.global [%0, {%1, %4, %4, %4, %3}];\n"
                            "@e cp.async.bulk.prefetch.tensor.5d.L2.global [%0, {%2, %4, %4, %4, %3}];\n}"
                            :: "l"(&prm.wd), "r"(nslot * 128), "r"(nslot * 128 + 64), "r"(mblk * 2), "r"(0) : "memory");
                    }
                    mbar_wait_warp(empty1(s), ph);
                    const uint32_t sa = base + s * G1_STAGE_BYTES;
                    load_stage1(sa, sa + A_BYTES + rank * 16384, full1(s), t ? &prm.xn : &prm.x, mb, (k + (t >> 2) * TAIL & 15) * 64, mblk * 128, col,
                                t & 3, stream_policy());
                    if (s == 3) ph ^= 1;
                    if (XE && t * 16 + k == (XK)) load_x();
                }
            }
            if (!XE && !XL) load_x();
            TRACE(4);
            mbar_wait_warp(dep_bar + 8, 0);
            TRACE(5);
            int q = 0; uint32_t ph2 = 1;
#pragma unroll 1
            for (int u = 0; u < G2_KSTEPS; u++) {
                if (u == G2_LATE || u == G2_DSTEPS || u == G2_LAST) {
                    TRACE(u == G2_LATE ? 6 : (u == G2_DSTEPS ? 32 : 40));
                    mbar_wait_warp(dep_bar + (u == G2_LATE ? 16 : (u == G2_DSTEPS ? 24 : 32)), 0);
                    TRACE(u == G2_LATE ? 7 : (u == G2_DSTEPS ? 33 : 41));
                }
                const uint32_t sa = stage2(q);
                const bool down = u < G2_DSTEPS;
                const int k = down ? u : (u & 3) * 4 + (u - G2_DSTEPS) / 4;
                mbar_wait_warp(u < G2_STAGES ? empty1((u * 2 + 1) / 3) : empty2(q), u < G2_STAGES ? ph : ph2);
                load_stage2(sa, sa + A_BYTES + rank * 8192, full2(q), &prm.a2, down ? &prm.wd : &prm.wo, (down ? DM : 0) + k * 64,
                            mblk * 64, nslot * 128 + rank * 64, down ? 0 : k * 2, down ? k * 2 : 0, stream_policy());
                if (++q == G2_STAGES) { q = 0; ph2 ^= 1; }
                if (XL && u == (XK)) load_x();
            }
            TRACE(8);
        }
    }
}

typedef CUresult (*EncodeFn)(CUtensorMap*, CUtensorMapDataType, cuuint32_t, void*, const cuuint64_t*, const cuuint64_t*,
                             const cuuint32_t*, const cuuint32_t*, CUtensorMapInterleave, CUtensorMapSwizzle,
                             CUtensorMapL2promotion, CUtensorMapFloatOOBfill);

void encode(EncodeFn fn, CUtensorMap* m, const void* ptr, int rank, const cuuint64_t* dims, const cuuint64_t* strides,
            const cuuint32_t* box) {
    const cuuint32_t es[5] = {1, 1, 1, 1, 1};
    fn(m, CU_TENSOR_MAP_DATA_TYPE_BFLOAT16, rank, const_cast<void*>(ptr), dims, strides, box, es,
       CU_TENSOR_MAP_INTERLEAVE_NONE, box[0] == 32 ? CU_TENSOR_MAP_SWIZZLE_64B : CU_TENSOR_MAP_SWIZZLE_128B,
       CU_TENSOR_MAP_L2_PROMOTION_L2_128B, CU_TENSOR_MAP_FLOAT_OOB_FILL_NONE);
}
void encode_2d(EncodeFn fn, CUtensorMap* m, const void* ptr, int cols, int box_rows) {
    const cuuint64_t dims[2] = {(cuuint64_t)cols, SEQ}, strides[1] = {(cuuint64_t)cols * 2};
    const cuuint32_t box[2] = {64, (cuuint32_t)box_rows};
    encode(fn, m, ptr, 2, dims, strides, box);
}
void encode_w1(EncodeFn fn, CUtensorMap* m, const void* ptr, int cols) {
    const cuuint64_t dims[3] = {64, DM, (cuuint64_t)cols / 64}, strides[2] = {(cuuint64_t)cols * 2, 128};
    const cuuint32_t box[3] = {64, 64, 2};
    encode(fn, m, ptr, 3, dims, strides, box);
}
void encode_tail(EncodeFn fn, CUtensorMap* m, const __nv_bfloat16* w) {
    const cuuint64_t dims[3] = {32, DM, 8}, strides[2] = {DF * 2, 256};
    const cuuint32_t box[3] = {32, 64, 8};
    encode(fn, m, w + DF - 1024 + 96, 3, dims, strides, box);
}
void encode_qkv(EncodeFn fn, CUtensorMap* m, const void* ptr) {
    const cuuint64_t dims[3] = {DM, SEQ, 3}, strides[2] = {NQKV * 2, DM * 2};
    const cuuint32_t box[3] = {64, 16, 3};
    encode(fn, m, ptr, 3, dims, strides, box);
}
void encode_a2(EncodeFn fn, CUtensorMap* m, const void* ptr) {
    const cuuint64_t dims[3] = {K2, 2, SEQ / 2}, strides[2] = {(cuuint64_t)SEQ * K2, K2 * 2};
    const cuuint32_t box[3] = {64, 2, 64};
    encode(fn, m, ptr, 3, dims, strides, box);
}
void encode_w2(EncodeFn fn, CUtensorMap* m, const void* ptr, int rows) {
    const cuuint64_t rb = DM * 2;
    const cuuint64_t dims[5] = {DM, 2, 4, 4, (cuuint64_t)rows / 32}, strides[4] = {rb, 8 * rb, 2 * rb, 32 * rb};
    const cuuint32_t box[5] = {64, 2, 4, 4, 2};
    encode(fn, m, ptr, 5, dims, strides, box);
}
void encode_wo(EncodeFn fn, CUtensorMap* m, const void* ptr) {
    const cuuint64_t rb = DM * 2;
    const cuuint64_t dims[5] = {DM, 4, DM / 32, 2, 4}, strides[4] = {2 * rb, 32 * rb, rb, 8 * rb};
    const cuuint32_t box[5] = {64, 4, 2, 2, 4};
    encode(fn, m, ptr, 5, dims, strides, box);
}

}

extern "C" void kernel_launch(void* const* d_in, const int* in_sizes, int n_in, void* d_out, int out_size) {
    (void)in_sizes; (void)n_in; (void)out_size;
    static EncodeFn fn = nullptr;
    static Params prm;
    if (!fn) {
        cudaDriverEntryPointQueryResult st;
        cudaGetDriverEntryPoint("cuTensorMapEncodeTiled", (void**)&fn, cudaEnableDefault, &st);
        cudaGetSymbolAddress((void**)&prm.pxn, g_xn);
        cudaGetSymbolAddress((void**)&prm.qkv, g_qkv);
        cudaGetSymbolAddress((void**)&prm.pa2, g_a2);
        cudaGetSymbolAddress((void**)&prm.tail, g_tail);
        cudaGetSymbolAddress((void**)&prm.stats, g_stats);
        cudaGetSymbolAddress((void**)&prm.colsum, g_colsum);
        cudaGetSymbolAddress((void**)&prm.flags, g_flags);
        cudaGetSymbolAddress((void**)&prm.epoch, g_epoch);
        cudaFuncSetAttribute(fused_kernel, cudaFuncAttributeMaxDynamicSharedMemorySize, SMEM_BYTES);
    }
    encode_2d(fn, &prm.x, d_in[0], DM, 128);
    encode_2d(fn, &prm.xn, prm.pxn, DM, 128);
    encode_tail(fn, &prm.wtail, (const __nv_bfloat16*)d_in[5]);
    encode_w1(fn, &prm.wqkv, d_in[1], NQKV);
    encode_w1(fn, &prm.wg, d_in[4], DF);
    encode_w1(fn, &prm.wu, d_in[5], DF);
    encode_qkv(fn, &prm.qkv3, prm.qkv);
    encode_2d(fn, &prm.o, prm.pa2, K2, 32);
    encode_a2(fn, &prm.a2, prm.pa2);
    encode_wo(fn, &prm.wo, d_in[2]);
    encode_w2(fn, &prm.wd, d_in[6], DF);
    encode_2d(fn, &prm.out, d_out, DM, 16);
    prm.px = (const __nv_bfloat16*)d_in[0];
    prm.pout = (__nv_bfloat16*)d_out;
    fused_kernel<<<NCTA, 384, SMEM_BYTES>>>(prm);
}
```

```cpp
#include <cuda_runtime.h>
#include <cuda_bf16.h>
#include <cuda.h>
#include <stdint.h>
#include <type_traits>

#define LNS 3
#define FS 14
#define CA 0x87658765u
#define CB 0x65876587u
#define CST 10
#define CIDX nslot
#define PACE0 900
#define PACE 425
#define PACE3 1700
#define TAIL1 11
#define TAIL2 10
#define NAR0 18
#define NARS 2
#define MIXQ 10
#define MIXV 10
#define TST 4
#define TLD2 4
#define XLD 9
#define SK2 5
#define PFK 60 + mblk
#define XK 66 + nslot
#define TSK 2
#define TW0 9000
#define TLD 10
#define SK0 2

namespace {

constexpr int SEQ = 2048, DM = 1024, DF = 3584, K2 = DM + DF, NQKV = 3 * DM;
constexpr int NGEMM = 128, NCTA = 132;
constexpr int G1_STAGES = 4, G1_STAGE_BYTES = 49152, G1_KSTEPS = 16, G1_TILES = 5;
constexpr int G2_STAGES = 6, G2_STAGE_BYTES = 32768, G2_KSTEPS = 72, G2_LATE = 40, G2_DSTEPS = 56;
constexpr int G2_HEAD = 17;
constexpr int LN_STEP = LNS, FOLD_STEP = FS;
constexpr int A_BYTES = 16384;
constexpr int AUX_OFF = G1_STAGES * G1_STAGE_BYTES;
constexpr int BAR_OFF = AUX_OFF + 32768;
constexpr int SMEM_BYTES = BAR_OFF + 2816;
constexpr int G1_SKEW = 2, G2_SKEW = SK2;
constexpr int CONSUMER_REGS = 224, AUX_REGS = 56;
constexpr int HALO_BYTES = 4096;
constexpr uint64_t narrow_steps() {
    uint64_t m = 0;
    for (int i = 0; i < TAIL2; i++) m |= 1ull << NAR0 + i * NARS;
    return m;
}
constexpr uint64_t G2_NARROW = narrow_steps();
static_assert(G2_NARROW >> G2_LATE == 0, "narrow steps use early columns");

enum { F_LN = 0, F_LN2 = 1, F_FIRST = 2, F_EARLY = 3, F_LATE = 4, F_TAIL = 5, F_HALO = 6 };
constexpr unsigned CNT_LN = 8, CNT_FIRST = 8, CNT_EARLY = 16, CNT_LATE = 8;

__device__ __align__(1024) __nv_bfloat16 g_xn[SEQ * DM];
__device__ __align__(1024) __nv_bfloat16 g_a2[SEQ * K2];
__device__ __align__(128) uint4 g_tail[2 * NGEMM * 512];
__device__ __align__(128) uint8_t g_halo[(2 * NGEMM + 1) * HALO_BYTES];
__device__ __align__(128) float2 g_stats[SEQ];
__device__ __align__(128) float g_colsum[16 * 1024];
__device__ __align__(128) unsigned g_flags[(F_HALO + 8) * 16 * 32];
__device__ __align__(128) unsigned g_epoch[NCTA * 16];

struct Params {
    const __nv_bfloat16* px;
    __nv_bfloat16 *pxn, *pa2, *pout;
    uint4* tail;
    uint8_t* halo;
    float2* stats;
    float* colsum;
    unsigned *flags, *epoch;
    unsigned long long* trace;
    CUtensorMap x, wg, wu, xn, wqkv, a2, wu_tail, wd_tail, wo, wd, out;
};

extern __shared__ __align__(1024) uint8_t smem_raw[];

#define TRACE(slot) do {} while (0)
#define TRACE_GT(slot) do {} while (0)
#define TRACE_S(slot, v, want) do {} while (0)
#define TRACE_GET(v) do {} while (0)
#define TRACE_PUT(slot, v) do {} while (0)
#define TRACE_SLOT(v, slot) do {} while (0)
#define TRACE_NEXT(v) do {} while (0)
#define TRACE_DUMP() do {} while (0)
#define TRACE_CLEAR() do {} while (0)
#define STAGE_TRACE 0
#define TRACE_END() do {} while (0)
#define TRACE_STEP(t, k, i) do {} while (0)

__device__ __forceinline__ uint32_t smem_u32(const void* p) { return (uint32_t)__cvta_generic_to_shared(p); }
__device__ __forceinline__ void mbar_init(uint32_t bar, uint32_t cnt) {
    asm volatile("mbarrier.init.shared::cta.b64 [%0], %1;" :: "r"(bar), "r"(cnt) : "memory");
}
__device__ __forceinline__ void mbar_expect_tx(uint32_t bar, uint32_t bytes) {
    asm volatile("mbarrier.arrive.expect_tx.shared::cta.b64 _, [%0], %1;" :: "r"(bar), "r"(bytes) : "memory");
}
__device__ __forceinline__ void mbar_arrive(uint32_t bar) {
    asm volatile("mbarrier.arrive.shared::cta.b64 _, [%0];" :: "r"(bar) : "memory");
}
__device__ __forceinline__ void mbar_arrive_cluster(uint32_t bar, uint32_t cta) {
    asm volatile("{\n.reg .b32 ra;\nmapa.shared::cluster.u32 ra, %0, %1;\nmbarrier.arrive.shared::cluster.b64 _, [ra];\n}"
                 :: "r"(bar), "r"(cta) : "memory");
}
__device__ __forceinline__ bool mbar_try_wait(uint32_t bar, uint32_t parity) {
    uint32_t ok;
    asm volatile("{\n.reg .pred p;\nmbarrier.try_wait.parity.shared::cta.b64 p, [%1], %2;\nselp.u32 %0, 1, 0, p;\n}"
                 : "=r"(ok) : "r"(bar), "r"(parity) : "memory");
    return ok;
}
__device__ __forceinline__ void mbar_wait(uint32_t bar, uint32_t parity) {
#pragma unroll 1
    for (int spins = 0; !mbar_try_wait(bar, parity) && spins < (1 << 17); spins++) {}
}
template <bool WARP = false> __device__ __forceinline__ void flag_wait(const unsigned* p, unsigned target) {
#pragma unroll 1
    for (int spins = 0; spins < (1 << 19); spins++) {
        unsigned v;
        asm volatile("ld.acquire.gpu.global.u32 %0, [%1];" : "=r"(v) : "l"(p) : "memory");
        if (WARP ? __all_sync(0xffffffffu, (int)(v - target) >= 0) : (int)(v - target) >= 0) break;
        __nanosleep(64);
    }
}
__device__ __forceinline__ void mbar_wait_warp(uint32_t bar, uint32_t parity) {
#pragma unroll 1
    for (int spins = 0; !__all_sync(0xffffffffu, mbar_try_wait(bar, parity)) && spins < (1 << 17); spins++) {}
}
__device__ __forceinline__ void flag_add(unsigned* p) {
    asm volatile("red.release.gpu.global.add.u32 [%0], 1;" :: "l"(p) : "memory");
}
__device__ __forceinline__ bool elect_one() {
    uint32_t ok;
    asm volatile("{\n.reg .pred p;\nelect.sync _|p, 0xffffffff;\nselp.u32 %0, 1, 0, p;\n}" : "=r"(ok));
    return ok;
}
__device__ __forceinline__ uint32_t pick(bool c, uint32_t a, uint32_t b) {
    uint32_t r;
    asm("{\n.reg .pred p;\nsetp.ne.b32 p, %3, 0;\nselp.b32 %0, %1, %2, p;\n}" : "=r"(r) : "r"(a), "r"(b), "r"((uint32_t)c));
    return r;
}
__device__ __forceinline__ void fence_proxy_async() { asm volatile("fence.proxy.async.global;" ::: "memory"); }
__device__ __forceinline__ uint4 lds128(uint32_t addr) {
    uint4 v;
    asm volatile("ld.shared.v4.u32 {%0,%1,%2,%3}, [%4];" : "=r"(v.x), "=r"(v.y), "=r"(v.z), "=r"(v.w) : "r"(addr) : "memory");
    return v;
}
__device__ __forceinline__ float2 lds64f(uint32_t addr) {
    float2 v;
    asm volatile("ld.shared.v2.f32 {%0,%1}, [%2];" : "=f"(v.x), "=f"(v.y) : "r"(addr) : "memory");
    return v;
}
__device__ __forceinline__ void sts128(uint32_t addr, uint4 v) {
    asm volatile("st.shared.v4.u32 [%0], {%1,%2,%3,%4};" :: "r"(addr), "r"(v.x), "r"(v.y), "r"(v.z), "r"(v.w) : "memory");
}
__device__ __forceinline__ void sts64f(uint32_t addr, float a, float b) {
    asm volatile("st.shared.v2.f32 [%0], {%1,%2};" :: "r"(addr), "f"(a), "f"(b) : "memory");
}

__device__ __forceinline__ uint64_t stream_policy() { return 0x12F0000000000000ull; }
__device__ __forceinline__ void tma_3d(uint32_t dst, const CUtensorMap* m, uint32_t bar, int c0, int c1, int c2, uint64_t pol) {
    asm volatile("cp.async.bulk.tensor.3d.shared::cluster.global.mbarrier::complete_tx::bytes.L2::cache_hint"
                 " [%0], [%1, {%3, %4, %5}], [%2], %6;"
                 :: "r"(dst), "l"(m), "r"(bar), "r"(c0), "r"(c1), "r"(c2), "l"(pol) : "memory");
}
__device__ __forceinline__ void load_stage1(uint32_t dst, uint32_t dst_b, uint32_t bar, const CUtensorMap* ma, const CUtensorMap* mb0,
                                            const CUtensorMap* mb1, int k, int row, int col0, int col1, int keep_a, uint64_t pol) {
    asm volatile("{\n.reg .pred e, p, q;\nelect.sync _|e, 0xffffffff;\nsetp.ne.and.b32 p|q, %8, 0, e;\n"
        "@p cp.async.bulk.tensor.3d.shared::cluster.global.mbarrier::complete_tx::bytes [%0], [%3, {%5, %6, %10}], [%2];\n"
        "@q cp.async.bulk.tensor.3d.shared::cluster.global.mbarrier::complete_tx::bytes.L2::cache_hint [%0], [%3, {%5, %6, %10}], [%2], %9;\n"
        "@e cp.async.bulk.tensor.2d.shared::cluster.global.mbarrier::complete_tx::bytes.multicast::cluster.L2::cache_hint"
        " [%1], [%4, {%7, %5}], [%2], %11, %9;\n"
        "@e cp.async.bulk.tensor.2d.shared::cluster.global.mbarrier::complete_tx::bytes.multicast::cluster.L2::cache_hint"
        " [%1 + 8192], [%13, {%14, %5}], [%2], %11, %9;\n"
        "@e mbarrier.arrive.expect_tx.shared::cta.b64 _, [%2], %12;\n}"
        :: "r"(dst), "r"(dst_b), "r"(bar), "l"(ma), "l"(mb0), "r"(k), "r"(row), "r"(col0), "r"(keep_a), "l"(pol), "r"(0),
           "h"((uint16_t)3), "n"(G1_STAGE_BYTES), "l"(mb1), "r"(col1) : "memory");
}
__device__ __forceinline__ void load_stage2(uint32_t dst, uint32_t dst_b, uint32_t bar, const CUtensorMap* ma, const CUtensorMap* mb,
                                            int ka, int row, int col, int kb2, int kb4, uint64_t pol) {
    asm volatile("{\n.reg .pred e;\nelect.sync _|e, 0xffffffff;\n"
        "@e cp.async.bulk.tensor.3d.shared::cluster.global.mbarrier::complete_tx::bytes.L2::cache_hint [%0], [%3, {%5, %6, %10}], [%2], %9;\n"
        "@e cp.async.bulk.tensor.5d.shared::cluster.global.mbarrier::complete_tx::bytes.multicast::cluster.L2::cache_hint"
        " [%1], [%4, {%7, %10, %13, %10, %8}], [%2], %11, %9;\n"
        "@e mbarrier.arrive.expect_tx.shared::cta.b64 _, [%2], %12;\n}"
        :: "r"(dst), "r"(dst_b), "r"(bar), "l"(ma), "l"(mb), "r"(ka), "r"(row), "r"(col), "r"(kb4), "l"(pol), "r"(0),
           "h"((uint16_t)3), "n"(G2_STAGE_BYTES), "r"(kb2) : "memory");
}
__device__ __forceinline__ uint4 ldg_stream(const void* p, uint64_t pol) {
    uint4 v;
    asm volatile("ld.global.nc.L1::no_allocate.L2::cache_hint.v4.u32 {%0,%1,%2,%3}, [%4], %5;"
                 : "=r"(v.x), "=r"(v.y), "=r"(v.z), "=r"(v.w) : "l"(p), "l"(pol));
    return v;
}
__device__ __forceinline__ void st_tagged(void* p, float a, float b, uint32_t tag) {
    asm volatile("st.relaxed.gpu.global.v2.b32 [%0], {%1,%2};"
                 :: "l"(p), "r"((__float_as_uint(a) & ~3u) | tag), "r"((__float_as_uint(b) & ~3u) | tag) : "memory");
}
__device__ __forceinline__ bool untagged(const uint4& v, uint32_t tag) {
    return ((v.x ^ tag) | (v.y ^ tag) | (v.z ^ tag) | (v.w ^ tag)) & 3;
}
__device__ __forceinline__ uint4 ld_relaxed(const void* p) {
    uint4 v;
    asm volatile("ld.relaxed.gpu.global.v4.b32 {%0,%1,%2,%3}, [%4];" : "=r"(v.x), "=r"(v.y), "=r"(v.z), "=r"(v.w) : "l"(p) : "memory");
    return v;
}
__device__ __forceinline__ void prefetch_map(const CUtensorMap* m) {
    asm volatile("prefetch.tensormap [%0];" :: "l"(m) : "memory");
}
template <int N> __device__ __forceinline__ void wg_wait() { asm volatile("wgmma.wait_group.sync.aligned %0;" :: "n"(N) : "memory"); }

__device__ __forceinline__ uint32_t desc_a(uint32_t addr) { return (addr & 0x3FFFF) >> 4 | 1 << 16; }
__device__ __forceinline__ uint32_t desc_b(uint32_t addr) { return (addr & 0x3FFFF) >> 4 | 512 << 16; }

#define R8(d, o) "+f"(d[o]), "+f"(d[o+1]), "+f"(d[o+2]), "+f"(d[o+3]), "+f"(d[o+4]), "+f"(d[o+5]), "+f"(d[o+6]), "+f"(d[o+7])
#define R32(d, o) R8(d, o), R8(d, o+8), R8(d, o+16), R8(d, o+24)
#define R64(d, o) R32(d, o), R32(d, o+32)
#define ACC00 "%0,%1,%2,%3,%4,%5,%6,%7,%8,%9,%10,%11,%12,%13,%14,%15,%16,%17,%18,%19,%20,%21,%22,%23,%24,%25,%26,%27,%28,%29,%30,%31,"\
    "%32,%33,%34,%35,%36,%37,%38,%39,%40,%41,%42,%43,%44,%45,%46,%47"
#define ACC0 ACC00 ",%48,%49,%50,%51,%52,%53,%54,%55,%56,%57,%58,%59,%60,%61,%62,%63"
#define ACC1 "%64,%65,%66,%67,%68,%69,%70,%71,%72,%73,%74,%75,%76,%77,%78,%79,%80,%81,%82,%83,%84,%85,%86,%87,%88,%89,%90,%91,%92,%93,%94,%95,"\
    "%96,%97,%98,%99,%100,%101,%102,%103,%104,%105,%106,%107,%108,%109,%110,%111"
#define ACC48 "{" ACC00 "}"
#define ACC64 "{" ACC0 "}"
#define ACC112 "{" ACC0 "," ACC1 "}"
#define ACC128 "{" ACC0 "," ACC1 ",%112,%113,%114,%115,%116,%117,%118,%119,%120,%121,%122,%123,%124,%125,%126,%127}"
#define MMA_K16(shape, acc, keep, hb, sb) \
    "mov.b64 da, {la, 0x40000040};\nmov.b64 db, {lb, " hb "};\n" \
    "wgmma.mma_async.sync.aligned." shape ".f32.bf16.bf16 " acc ", da, db, " keep ", 1, 1, 0, 1;\n" \
    "add.u32 la, la, 2;\nadd.s32 lb, lb, " sb ";\n"
#define MMA_STEP_B(shape, acc, a, b, off, keep, hb, sb, sb2) \
    "{\n.reg .pred p, q;\n.reg .b32 la, lb;\n.reg .b64 da, db;\nsetp.ne.b32 p, " keep ", 0;\nsetp.eq.b32 q, 0, 0;\n" \
    "add.u32 la, " a ", " off ";\nadd.u32 lb, " b ", " off ";\nwgmma.fence.sync.aligned;\n" \
    MMA_K16(shape, acc, "p", hb, sb) MMA_K16(shape, acc, "q", hb, sb2) MMA_K16(shape, acc, "q", hb, sb) \
    MMA_K16(shape, acc, "q", hb, sb) "wgmma.commit_group.sync.aligned;\n}"
#define MMA_STEP(shape, acc, a, b, off, keep) MMA_STEP_B(shape, acc, a, b, off, keep, "0x40000040", "128", "128")

__device__ __forceinline__ void mma_step(float (&d)[128], uint32_t da, uint32_t db, uint32_t off, int keep) {
    asm volatile(MMA_STEP("m64n256k16", ACC128, "%128", "%129", "%130", "%131")
                 : R64(d, 0), R64(d, 64) : "r"(da), "r"(db), "r"(off), "r"(keep) : "memory");
}
__device__ __forceinline__ void mma_rank(float (&d)[128], uint32_t a0, uint32_t a1, uint32_t db) {
    asm volatile("{\n.reg .pred q;\n.reg .b64 db;\nsetp.eq.b32 q, 0, 0;\nmov.b64 db, {%131, 0x40000040};\nwgmma.fence.sync.aligned;\n"
                 "wgmma.mma_async.sync.aligned.m64n256k16.f32.bf16.bf16 " ACC128 ", {%128, %129, %130, %130}, db, q, 1, 1, 1;\n}"
                 : R64(d, 0), R64(d, 64) : "r"(a0), "r"(a1), "r"(0), "r"(db) : "memory");
}
__device__ __forceinline__ void mma_step224(float (&d)[128], uint32_t da, uint32_t db, uint32_t off, int keep) {
    asm volatile(MMA_STEP("m64n224k16", ACC112, "%112", "%113", "%114", "%115")
                 : R64(d, 0), R32(d, 64), R8(d, 96), R8(d, 104) : "r"(da), "r"(db), "r"(off), "r"(keep) : "memory");
}
__device__ __forceinline__ void mma_step(float (&d)[64], uint32_t da, uint32_t db, uint32_t off, int keep) {
    asm volatile(MMA_STEP("m64n128k16", ACC64, "%64", "%65", "%66", "%67")
                 : R64(d, 0) : "r"(da), "r"(db), "r"(off), "r"(keep) : "memory");
}
__device__ __forceinline__ void mma_step96(float (&d)[64], uint32_t da, uint32_t db, uint32_t off) {
    asm volatile(MMA_STEP("m64n96k16", ACC48, "%48", "%49", "%50", "1")
                 : R32(d, 0), R8(d, 32), R8(d, 40) : "r"(da), "r"(db), "r"(off) : "memory");
}
__device__ __forceinline__ void mma_step_tail(float (&d)[128], uint32_t da, uint32_t b, uint32_t off, int keep) {
    asm volatile(MMA_STEP_B("m64n256k16", ACC128, "%128", "%129", "%130", "%131", "0x80000040", "128", "-96")
                 : R64(d, 0), R64(d, 64) : "r"(da), "r"((b & 0x3FFFF) >> 4 | 256 << 16), "r"(off), "r"(keep) : "memory");
}

__device__ __forceinline__ uint32_t pack_bf16(float lo, float hi) {
    uint32_t r; asm("cvt.rn.bf16x2.f32 %0, %1, %2;" : "=r"(r) : "f"(hi), "f"(lo)); return r;
}
__device__ __forceinline__ float bf_lo(uint32_t v) { return __uint_as_float(v << 16); }
__device__ __forceinline__ float bf_hi(uint32_t v) { return __uint_as_float(v & 0xffff0000u); }
__device__ __forceinline__ float round_bf16(float v) { return bf_lo(pack_bf16(v, 0.f)); }
__device__ __forceinline__ uint32_t mul_bf16x2(uint32_t a, uint32_t b) {
    uint32_t r; asm("mul.rn.bf16x2 %0, %1, %2;" : "=r"(r) : "r"(a), "r"(b)); return r;
}
__device__ __forceinline__ uint32_t sub_bf16x2(uint32_t a, uint32_t b) {
    uint32_t r; asm("sub.rn.bf16x2 %0, %1, %2;" : "=r"(r) : "r"(a), "r"(b)); return r;
}
__device__ __forceinline__ uint32_t mul2_bf16x2(uint32_t a, uint32_t hi, uint32_t lo) {
    uint32_t r; asm("fma.rn.bf16x2 %0, %1, %2, %3;" : "=r"(r) : "r"(a), "r"(hi), "r"(mul_bf16x2(a, lo))); return r;
}
__device__ __forceinline__ float tanh_fast(float x) { float r; asm("tanh.approx.f32 %0, %1;" : "=f"(r) : "f"(x)); return r; }
__device__ __forceinline__ float gelu_tanh(float g) {
    float t = fmaf(g * g, 0.044715f * 0.7978845608f, 0.7978845608f) * g;
    float hg = 0.5f * g;
    return fmaf(hg, tanh_fast(t), hg);
}
__device__ __forceinline__ uint32_t geglu2(uint32_t g2, uint32_t u2) {
    return mul_bf16x2(pack_bf16(gelu_tanh(bf_lo(g2)), gelu_tanh(bf_hi(g2))), u2);
}
__device__ __forceinline__ float silu(float d) {
    float hd = 0.5f * d;
    return fmaf(hd, tanh_fast(hd), hd);
}
__device__ __forceinline__ float ex2_fast(float x) { float r; asm("ex2.approx.ftz.f32 %0, %1;" : "=f"(r) : "f"(x)); return r; }
__device__ __forceinline__ void unpack8(uint4 v, float (&f)[8]) {
    f[0] = bf_lo(v.x); f[1] = bf_hi(v.x); f[2] = bf_lo(v.y); f[3] = bf_hi(v.y);
    f[4] = bf_lo(v.z); f[5] = bf_hi(v.z); f[6] = bf_lo(v.w); f[7] = bf_hi(v.w);
}
template <int N> __device__ __forceinline__ void fence_regs(float (&d)[N]) {
#pragma unroll
    for (int i = 0; i < N; i++) asm volatile("" : "+f"(d[i]) :: "memory");
}

__device__ __forceinline__ float rcp_fast(float x) { float r; asm("rcp.approx.ftz.f32 %0, %1;" : "=f"(r) : "f"(x)); return r; }
__device__ __forceinline__ float sqrt_fast(float x) { float r; asm("sqrt.approx.ftz.f32 %0, %1;" : "=f"(r) : "f"(x)); return r; }
__device__ __forceinline__ uint32_t max_bf16x2(uint32_t a, uint32_t b) {
    uint32_t r; asm("max.bf16x2 %0, %1, %2;" : "=r"(r) : "r"(a), "r"(b)); return r;
}
__device__ __forceinline__ uint32_t transpose8(uint32_t a) {
    uint32_t r; asm volatile("movmatrix.sync.aligned.m8n8.trans.b16 %0, %1;" : "=r"(r) : "r"(a)); return r;
}
__device__ __forceinline__ void mma_set(uint32_t* d, const uint32_t* a, uint32_t b0, uint32_t b1) {
    asm volatile("mma.sync.aligned.m16n8k16.row.col.f32.bf16.bf16.f32 {%0,%1,%2,%3}, {%4,%5,%6,%7}, {%8,%9}, {%10,%10,%10,%10};"
        : "=r"(d[0]), "=r"(d[1]), "=r"(d[2]), "=r"(d[3]) : "r"(a[0]), "r"(a[1]), "r"(a[2]), "r"(a[3]), "r"(b0), "r"(b1), "r"(0));
}
__device__ __forceinline__ void mma_add(uint32_t* d, const uint32_t* a, uint32_t b0, uint32_t b1) {
    asm volatile("mma.sync.aligned.m16n8k16.row.col.f32.bf16.bf16.f32 {%0,%1,%2,%3}, {%4,%5,%6,%7}, {%8,%9}, {%0,%1,%2,%3};"
        : "+r"(d[0]), "+r"(d[1]), "+r"(d[2]), "+r"(d[3]) : "r"(a[0]), "r"(a[1]), "r"(a[2]), "r"(a[3]), "r"(b0), "r"(b1));
}
__device__ __forceinline__ uint32_t fresh_tid() { uint32_t r; asm volatile("mov.u32 %0, %%tid.x;" : "=r"(r)); return r; }
template <typename T> __device__ __forceinline__ T uniform(T v) { return __shfl_sync(0xffffffffu, v, 0); }

__device__ __forceinline__ void tail_gemm(const Params& prm, uint32_t base, uint32_t t0, unsigned epoch, int grp, int warp, int lane) {
    const uint32_t full = base + BAR_OFF, empty = full + 320, sig = full + 192, dep = full + 256;
    unsigned* const flags = prm.flags + grp * 128;
    if (warp >= 8) asm volatile("setmaxnreg.dec.sync.aligned.u32 %0;" :: "n"(AUX_REGS));
    if (warp == 8) {
        if (elect_one()) { prefetch_map(&prm.xn); prefetch_map(&prm.wu_tail); prefetch_map(&prm.a2); prefetch_map(&prm.wd_tail); }
        auto load_w = [&](int i, const CUtensorMap* m, int k) {
            asm volatile("{\n.reg .pred e;\nelect.sync _|e, 0xffffffff;\n"
                "@e cp.async.bulk.tensor.5d.shared::cluster.global.mbarrier::complete_tx::bytes [%0], [%2, {%4, %4, %3, %4, %4}], [%1];\n"
                "@e mbarrier.arrive.expect_tx.shared::cta.b64 _, [%1], %5;\n}"
                :: "r"(base + (i & 3) * G1_STAGE_BYTES + A_BYTES), "r"(full + (i & 3) * 8), "l"(m), "r"(k), "r"(0),
                   "n"(G1_STAGE_BYTES) : "memory");
        };
        while ((uint32_t)clock() - t0 < TW0) {}
#pragma unroll 1
        for (int i = 0; i < 4; i++) load_w(i, &prm.wu_tail, i * 2);
        flag_wait<true>(flags + F_LN * 512 + (lane & 3) * 32, epoch * CNT_LN);
        fence_proxy_async();
        TRACE(62);
#pragma unroll 1
        for (int p = 0, i = 0; p < 8; p++) {
            const bool first = p < 4;
            if (p == 4) mbar_wait_warp(dep + 8, 0);
#pragma unroll 1
            for (int k = 0; k < (first ? TAIL1 : TAIL2); k++, i++) {
                if (i == 8) mbar_wait_warp(dep, 0);
                mbar_wait_warp(empty + (i & 3) * 8, ~i >> 2 & 1);
                asm volatile("{\n.reg .pred e;\nelect.sync _|e, 0xffffffff;\n"
                    "@e cp.async.bulk.tensor.3d.shared::cluster.global.mbarrier::complete_tx::bytes [%0], [%2, {%3, %4, %5}], [%1];\n}"
                    :: "r"(base + (i & 3) * G1_STAGE_BYTES), "r"(full + (i & 3) * 8), "l"(first ? &prm.xn : &prm.a2),
                       "r"((first ? 0 : DM) + k * 64), "r"(grp * 256 + (p & 3) * 64), "r"(0) : "memory");
                if (i >= 4) load_w(i, first ? &prm.wu_tail : &prm.wd_tail, first ? k * 2 : k * 8);
            }
        }
    } else if (warp == 9) {
#pragma unroll 1
        for (int j = 0; j < 2; j++) {
            flag_wait<true>(flags + (F_LN2 + j) * 512 + (lane & 3) * 32, epoch * CNT_LN);
            fence_proxy_async();
            __syncwarp();
            if (lane == 0) mbar_arrive(dep + j * 8);
        }
    } else if (warp == 10 && lane == 0) {
#pragma unroll 1
        for (int p = 0; p < 8; p++) {
            mbar_wait(sig + p * 8, 0);
            flag_add(flags + F_TAIL * 512 + (p & 3) * 32);
            TRACE_S(50, p, 3); TRACE_S(51, p, 7);
        }
        prm.epoch[blockIdx.x * 16] = epoch;
        TRACE_DUMP();
    }
    if (warp >= 8) return;
    asm volatile("setmaxnreg.inc.sync.aligned.u32 %0;" :: "n"(CONSUMER_REGS) : "memory");
    const uint32_t da = desc_a(base + (warp >> 2) * 8192);
    uint4* out = prm.tail + grp * 2048 - 512 + threadIdx.x;
    float acc[128];
    uint32_t pk[64];
    int i = 0;
    auto release = [&]() { if ((threadIdx.x & 127) == 0) mbar_arrive(empty + (i - 1 & 3) * 8); };
    auto store = [&](int j) {
        asm volatile("st.global.v4.u32 [%0], {%1,%2,%3,%4};" :: "l"(out + j / 2 * 8192 + j % 2 * 256),
                     "r"(pk[4 * j]), "r"(pk[4 * j + 1]), "r"(pk[4 * j + 2]), "r"(pk[4 * j + 3]) : "memory");
    };
    auto step = [&](int k, int left) {
        mbar_wait(full + (i & 3) * 8, i >> 2 & 1);
        TRACE_S(45, warp * 128 + i, 0);
        if (warp >= 4 && left == TSK) asm volatile("bar.sync 1, 256;" ::: "memory");
        mma_step_tail(acc, da, base + A_BYTES, (i & 3) * (G1_STAGE_BYTES / 16), k);
        if (warp < 4 && left == 1) asm volatile("bar.arrive 1, 256;" ::: "memory");
        wg_wait<1>();
        if (k) release();
        i++;
    };
#pragma unroll
    for (int j = 0; j < 128; j++) asm volatile("mov.b32 %0, 0;" : "=f"(acc[j]));
#pragma unroll
    for (int j = 0; j < 64; j++) asm volatile("mov.b32 %0, 0;" : "=r"(pk[j]));
#pragma unroll 1
    for (int p = 0; p < 8; p++) {
#pragma unroll
        for (int k = 0; k < TST; k++) {
            step(k, 0);
            if (p) {
#pragma unroll
                for (int j = k * 16 / TST; j < (k + 1) * 16 / TST; j++) store(j);
                if (k == TST - 1) { __syncwarp(); if (lane == 0) mbar_arrive(sig + p * 8 - 8); }
            }
        }
#pragma unroll 1
        for (int left = (p < 4 ? TAIL1 : TAIL2) - TST; left > 0; left--) step(1, left);
        wg_wait<0>();
        fence_regs(acc);
        release();
        TRACE_S(48, p + warp * 8, 0); TRACE_S(49, p + warp * 8, 35); TRACE_S(52, p + warp * 8, 39);
#pragma unroll
        for (int j = 0; j < 64; j++) pk[j] = pack_bf16(acc[2 * j], acc[2 * j + 1]);
        out += p == 4 ? NGEMM * 512 - 1536 : 512;
    }
#pragma unroll
    for (int j = 0; j < 16; j++) store(j);
    __syncwarp();
    TRACE_S(58, warp, 4);
    if (lane == 0) mbar_arrive(sig + 56);
}

__device__ __forceinline__ int gate_col(int t, int nslot) { return t == 2 ? 1024 + nslot * 64 : max(t * 1024 - 1536, 0) + nslot * 128; }

struct Role {
    int rank, role, mblk, nslot;
    __device__ __forceinline__ Role() {
        uint32_t id;
        asm volatile("mov.u32 %0, %%ctaid.x;" : "=r"(id));
        const uint32_t cl = id / 2;
        rank = id & 1;
        role = pick(cl < 4, 32 + cl * 8, cl - 8 + max(4u, (cl - 1) * 37 >> 8)) * 2 + rank;
        mblk = role & 15; nslot = role >> 4;
    }
};

__global__ void __cluster_dims__(2, 1, 1) __launch_bounds__(384, 1)
fused_kernel(const __grid_constant__ Params prm) {
    TRACE_GET(c0);
    const uint32_t base = smem_u32(smem_raw) & ~1023u;
    const uint32_t bars = base + BAR_OFF;
    auto full1 = [&](int s) { return bars + s * 8; };
    auto empty1 = [&](int s) { return bars + 32 + s * 8; };
    auto full2 = [&](int s) { return bars + 64 + s * 8; };
    auto empty2 = [&](int s) { return bars + 128 + s * 8; };
    const uint32_t sig_bar = bars + 192, dep_bar = bars + 256, cs_bar = bars + 304, fold_bar = bars + 320, x_bar = bars + 352;
    const uint32_t halo_bar = dep_bar + 32;
    const uint32_t stats = bars + 1536;
    auto stage2 = [&](int q) { return base + q * G2_STAGE_BYTES; };
    const uint32_t aux = base + AUX_OFF;

    asm volatile("{\n.reg .pred p;\nsetp.eq.u32 p, %1, 0;\n@p mbarrier.init.shared::cta.b64 [%0], 1;\n"
        "fence.mbarrier_init.release.cluster;\nbarrier.cluster.arrive.relaxed.aligned;\n}" :: "r"(bars), "r"(threadIdx.x) : "memory");
    const int warp = __shfl_sync(0xffffffffu, threadIdx.x >> 5, 0);
    auto cluster_wait = []() { asm volatile("barrier.cluster.wait.acquire.aligned;" ::: "memory"); };
    if ((warp | (blockIdx.x & NGEMM)) == 8) {
        const Role r;
        asm volatile("{\n.reg .pred e;\nelect.sync _|e, 0xffffffff;\n"
            "@e prefetch.tensormap [%0];\n@e prefetch.tensormap [%1];\n}" :: "l"(&prm.x), "l"(&prm.wg + r.rank) : "memory");
        cluster_wait();
        load_stage1(base, base + A_BYTES + r.rank * 16384, full1(0), &prm.x, &prm.wg + r.rank, &prm.wg + r.rank, 0, r.mblk * 64,
                    r.nslot * 128, r.nslot * 128 + 64, 0, stream_policy());
    } else {
        cluster_wait();
    }
    const uint32_t t0 = clock();
    asm volatile("{\n.reg .pred e, q;\nelect.sync _|e, 0xffffffff;\nsetp.ne.and.u32 q, %2, 0, e;\n"
        "@q mbarrier.init.shared::cta.b64 [%0], %1;\n@e mbarrier.init.shared::cta.b64 [%0 + 8], %1;\n"
        "@e mbarrier.init.shared::cta.b64 [%0 + 16], %1;\n@e mbarrier.init.shared::cta.b64 [%0 + 24], %1;\n"
        "fence.mbarrier_init.release.cluster;\nbarrier.cluster.arrive.relaxed.aligned;\n}"
        :: "r"(bars + warp * 32), "r"(1 << (0x10fa08 >> warp * 2 & 3)), "r"(warp) : "memory");
    const int lane = threadIdx.x & 31;
    const Role me;
    const int rank = me.rank, role = me.role, mblk = me.mblk, nslot = me.nslot;
    const CUtensorMap* const w0 = &prm.wg + rank;

    if (blockIdx.x >= NGEMM) {
        if (warp == 9) { TRACE_CLEAR(); TRACE_GT(0); TRACE_PUT(1, c0); }
        cluster_wait();
        const uint32_t seen = __ldcg(prm.epoch + blockIdx.x * 16);
        tail_gemm(prm, base, t0, seen + 1, blockIdx.x - NGEMM, warp, lane);
    } else if (warp < 8) {
        asm volatile("setmaxnreg.inc.sync.aligned.u32 %0;" :: "n"(CONSUMER_REGS));
        const int wg = __shfl_sync(0xffffffffu, threadIdx.x >> 7, 0);
        const int cw = threadIdx.x >> 5;
        const int tid = threadIdx.x & 127;
        float acc[128];
        uint32_t pk[64];
#pragma unroll
        for (int i = 0; i < 64; i++) asm volatile("mov.b32 %0, 0;" : "=r"(pk[i]));
#pragma unroll
        for (int i = 0; i < 128; i++) asm volatile("mov.b32 %0, 0;" : "=f"(acc[i]));
        cluster_wait();

        const int row0 = mblk * 128 + (cw & 3) * 32 + wg;
        __nv_bfloat16* optr = prm.pxn + (mblk * 128 + nslot * 16 + cw * 2) * DM + lane * 8;
        const uint32_t da = desc_a(base + wg * 8192), db = desc_b(base + A_BYTES);
        auto release = [&](uint32_t bar) { if (tid < 2) mbar_arrive_cluster(bar, tid); };
        auto up = [](int i) { return 32 + (i & 24) + (i & 3) * 2 + (i >> 2 & 1); };
        auto store_pk = [&](__nv_bfloat16* p, int j) {
            asm volatile("st.global.v4.u32 [%0], {%1,%2,%3,%4};"
                         :: "l"(p), "r"(pk[4 * j]), "r"(pk[4 * j + 1]), "r"(pk[4 * j + 2]), "r"(pk[4 * j + 3]) : "memory");
        };
        auto chunk_geglu = [&](int j) {
#pragma unroll
            for (int i = 4 * j; i < 4 * j + 4; i++) pk[i] = geglu2(pk[i], pk[up(i)]);
            store_pk(optr + (j & 1) * 16 * K2 + (j >> 1) * 32, j);
        };
        auto signal_stores = [&](int p) { __syncwarp(); if (lane == 0) mbar_arrive(sig_bar + p * 8); };

        auto chunk_ln = [&](int k) {
            float* const mo = reinterpret_cast<float*>(pk + 32);
            if (k == 0) {
                const uint4* xp = reinterpret_cast<const uint4*>(prm.px + (optr - prm.pxn));
                pk[38] = __ldcg(prm.epoch + blockIdx.x * 16 + 2);
#pragma unroll
                for (int i = 0; i < 8; i++) {
                    const uint4 v = ldg_stream(xp + i * 32, stream_policy());
                    pk[4 * i] = v.x; pk[4 * i + 1] = v.y; pk[4 * i + 2] = v.z; pk[4 * i + 3] = v.w;
                }
            } else if (k >= LN_STEP && k < LN_STEP + 3) {
                if (k == LN_STEP) {
                    mo[0] = bf_lo(uniform(pk[0])); mo[1] = bf_lo(uniform(pk[16]));
                    mo[2] = mo[3] = mo[4] = mo[5] = 0.f;
                }
#pragma unroll
                for (int i = (k - LN_STEP) * 11; i < (k - LN_STEP) * 11 + 11 && i < 32; i++) {
                    const int r = i & 1;
                    const uint32_t w = pk[r * 16 + i / 2];
                    const float lo = bf_lo(w) - mo[r], hi = bf_hi(w) - mo[r];
                    mo[2 + r] += lo + hi;
                    mo[4 + r] = fmaf(hi, hi, fmaf(lo, lo, mo[4 + r]));
                }
            } else if (k == LN_STEP + 3) {
                const bool second = lane & 16;
                float m1 = (second ? mo[3] : mo[2]) + __shfl_xor_sync(0xffffffffu, second ? mo[2] : mo[3], 16);
                float m2 = (second ? mo[5] : mo[4]) + __shfl_xor_sync(0xffffffffu, second ? mo[4] : mo[5], 16);
#pragma unroll
                for (int o = 8; o > 0; o >>= 1) {
                    m1 += __shfl_xor_sync(0xffffffffu, m1, o);
                    m2 += __shfl_xor_sync(0xffffffffu, m2, o);
                }
                m1 *= 1.f / DM;
                const float var = fmaxf(fmaf(-m1, m1, m2 * (1.f / DM)), 0.f);
                const float mean = round_bf16((second ? mo[1] : mo[0]) + m1);
                const float inv = rcp_fast(round_bf16(sqrt_fast(round_bf16(round_bf16(var) + 1e-5f))));
                if ((lane & 15) == 0) st_tagged(prm.stats + (uint32_t)(optr - prm.pxn) / DM + second, -mean, inv, 2 - (pk[38] & 1));
                const uint32_t split = pack_bf16(inv - round_bf16(inv), inv);
#pragma unroll
                for (int r = 0; r < 2; r++) {
                    const uint32_t f = __shfl_sync(0xffffffffu, split, r * 16);
                    pk[32 + 3 * r] = __byte_perm(__shfl_sync(0xffffffffu, __float_as_uint(mean), r * 16), 0, 0x3232);
                    pk[33 + 3 * r] = __byte_perm(f, 0, 0x3232);
                    pk[34 + 3 * r] = __byte_perm(f, 0, 0x1010);
                }
            } else if (k >= LN_STEP + 4 && k < LN_STEP + 8) {
#pragma unroll
                for (int i = k - LN_STEP - 4; i < 8; i += 4) {
                    const uint32_t* n = pk + 32 + i / 4 * 3;
#pragma unroll
                    for (int j = 4 * i; j < 4 * i + 4; j++) pk[j] = mul2_bf16x2(sub_bf16x2(pk[j], n[0]), n[1], n[2]);
                    store_pk(optr + i * 256, i);
                }
                if (k == LN_STEP + 5 || k == LN_STEP + 7) signal_stores(k == LN_STEP + 5 ? 0 : 7);
            } else if (k == FOLD_STEP) {
                mbar_wait(fold_bar, 0);
                const uint32_t sp = stats + (row0 % 128 + (lane >> 2) * 2) * 8;
                const uint32_t sel = lane & 2 ? 0x4444 : (lane & 1 ? 0x4432 : 0x3232);
                const float2 sa = lds64f(sp), sb = lds64f(sp + 128);
                mma_rank(acc, __byte_perm(__float_as_uint(sa.x), 0, sel), __byte_perm(__float_as_uint(sb.x), 0, sel), desc_b(aux));
                mo[0] = sa.y; mo[1] = sb.y;
            }
        };

        uint32_t sx[8];
        auto halo = [&](int bytes) { const uint32_t id = fresh_tid(); return aux + (id & 96) * 128 + (id & 128) * 16 + (id & 31) * bytes; };
        auto scores = [&](int h, int b) { return b ? (h < 2 ? sx + 4 * h : pk + 8 * h - 12) : pk + (h < 2 ? 8 * h + 20 : 8 * h - 16); };
        auto values = [&](int h, int b) { return pk + (h & 2) * 16 + (h & 1) * 8 + b * 16; };
        auto publish = [&](int p) { asm volatile("fence.proxy.async.shared::cta;" ::: "memory"); signal_stores(p); };
        auto mix_qk = [&]() {
            const uint32_t a = halo(4);
            mbar_wait(halo_bar, 0);
#pragma unroll
            for (int n = 0; n < 16; n++) {
                const int b = 1 - n / 8, h = (n & 4) / 2 + n % 2, j = n / 2 % 2;
                uint32_t* const kq = pk + 32 + 8 * h + 4 * j;
                const uint32_t q0 = pk[8 * h + 4 * b + 2 * j], q1 = pk[8 * h + 4 * b + 2 * j + 1];
                if (j) mma_add(scores(h, b), kq, q0, q1);
                else mma_set(scores(h, b), kq, q0, q1);
                if (b) asm volatile("ld.shared.u32 %0, [%2];\nld.shared.u32 %1, [%2 + 128];"
                                    : "=r"(kq[1]), "=r"(kq[3]) : "r"(a + (h * 2 + j) * 256) : "memory");
            }
        };
        auto chunk_qk = [&](int k) {
            constexpr float LOG2E = 1.4426950408889634f;
            uint32_t* const l = pk + 32;
            float* const e = reinterpret_cast<float*>(pk + 48);
            if (k == 0) {
                const uint32_t a = halo(4) + HALO_BYTES;
#pragma unroll
                for (int i = 0; i < 16; i++) asm volatile("st.shared.u32 [%0], %1;" :: "r"(a + i * 128), "r"(pk[33 + 2 * i]) : "memory");
                publish(1);
            } else if (k == MIXQ) {
                const uint32_t id = fresh_tid() & 31;
                const bool u0 = id / 4 > id % 4 * 2, u1 = id / 4 > id % 4 * 2 + 1;
                const uint32_t gone = row0 < 2 ? (u0 ? 0xffffu : 0u) | (u1 ? 0xffff0000u : 0u) : 0u;
#pragma unroll
                for (int n = 0; n < 8; n++) {
                    const int b = n % 2;
                    const uint32_t* const c = scores(n / 2, b);
                    uint32_t v = pack_bf16(__uint_as_float(pick(u0, c[2 - 2 * b], c[2 * b])), __uint_as_float(pick(u1, c[3 - 2 * b], c[1 + 2 * b])));
                    v = mul2_bf16x2(v, 0x3e353e35u, 0x379e379eu);
                    if (!b) v = v & ~gone | 0xce6ece6eu & gone;
                    l[n] = transpose8(v);
                }
            } else if (k == MIXQ + 1) {
#pragma unroll
                for (int h = 0; h < 4; h++) {
                    uint32_t m = max_bf16x2(__byte_perm(l[2 * h], l[2 * h + 1], 0x5410), __byte_perm(l[2 * h], l[2 * h + 1], 0x7632));
                    m = max_bf16x2(m, __shfl_xor_sync(0xffffffffu, m, 1));
                    l[8 + h] = max_bf16x2(m, __shfl_xor_sync(0xffffffffu, m, 2));
                }
#pragma unroll
                for (int n = 0; n < 8; n++) {
                    const float m = -LOG2E * (n % 2 ? bf_hi(l[8 + n / 2]) : bf_lo(l[8 + n / 2]));
                    e[2 * n] = ex2_fast(fmaf(bf_lo(l[n]), LOG2E, m));
                    e[2 * n + 1] = ex2_fast(fmaf(bf_hi(l[n]), LOG2E, m));
                }
            } else if (k == MIXQ + 2) {
#pragma unroll
                for (int n = 0; n < 8; n++) {
                    float sum = e[2 * n] + e[2 * n + 1];
                    sum += __shfl_xor_sync(0xffffffffu, sum, 1);
                    sum += __shfl_xor_sync(0xffffffffu, sum, 2);
                    const float r = rcp_fast(sum);
                    l[n] = pack_bf16(e[2 * n] * r, e[2 * n + 1] * r);
                }
                const uint32_t a = aux + 5 * HALO_BYTES + fresh_tid() * 16;
                sts128(a, make_uint4(l[0], l[1], l[2], l[3]));
                sts128(a + 4096, make_uint4(l[4], l[5], l[6], l[7]));
            }
        };
        auto mix_pv = [&]() {
            const uint32_t a = halo(8), id = fresh_tid();
            const uint32_t keep = (id % 4 * 2 > id % 32 / 4 ? 0xffffu : 0u) | (id % 4 * 2 + 1 > id % 32 / 4 ? 0xffff0000u : 0u);
            const uint4 p0 = lds128(aux + 5 * HALO_BYTES + id * 16), p1 = lds128(aux + 6 * HALO_BYTES + id * 16);
            const uint32_t p[8] = {p0.x, p0.y, p0.z, p0.w, p1.x, p1.y, p1.z, p1.w};
            mbar_wait(halo_bar, 1);
#pragma unroll
            for (int n = 0; n < 8; n++) {
                uint32_t* const w = values(n / 2, 0) + n % 2 * 4;
                asm volatile("mov.b32 %0, %4;\nmov.b32 %1, %5;\nld.shared.v2.u32 {%2, %3}, [%6];"
                             : "=r"(w[0]), "=r"(w[1]), "=r"(w[2]), "=r"(w[3]) : "r"(w[16]), "r"(w[17]), "r"(a + n * 256) : "memory");
            }
#pragma unroll
            for (int n = 0; n < 16; n++) {
                const int b = n / 2 % 2;
                uint32_t* const w = values(n / 4, b) + n % 2 * 4;
                mma_set(w, w, p[n / 2] & (b ? keep : ~keep), p[n / 2] & (b ? ~keep : keep));
            }
        };
        auto chunk_pv = [&](int k) {
            if (k == 0) {
                const uint32_t a = halo(8) + HALO_BYTES;
#pragma unroll
                for (int h = 0; h < 4; h++) {
                    uint32_t* const w = values(h, 1);
                    uint32_t v[8];
#pragma unroll
                    for (int i = 0; i < 8; i++) v[i] = transpose8(w[h < 2 ? (i & 1) + (i & 2) * 2 + (i & 4) / 2 : (i & 1) * 2 + (i & 2) / 2 + (i & 4)]);
#pragma unroll
                    for (int i = 0; i < 8; i++) w[i] = v[i];
                    sts64f(a + h * 512, __uint_as_float(w[2]), __uint_as_float(w[3]));
                    sts64f(a + h * 512 + 256, __uint_as_float(w[6]), __uint_as_float(w[7]));
                }
                publish(3);
            } else if (k == 5) {
                optr = prm.pa2 + (size_t)(row0 + (lane & 3) * 4) * K2 + nslot * 128 + (lane >> 2) * 8;
                asm volatile("" : "+l"(optr));
            } else if (k == MIXV || k == MIXV + 1) {
#pragma unroll
                for (int n = 0; n < 4; n++) {
                    const float* const c = reinterpret_cast<float*>(values(n & 2, k - MIXV)) + n % 2;
                    asm volatile("st.global.v4.u32 [%0], {%1,%2,%3,%4};"
                                 :: "l"(optr + ((k - MIXV) * 16 + n % 2 * 2) * K2 + n / 2 * 64), "r"(pack_bf16(c[0], c[2])),
                                    "r"(pack_bf16(c[4], c[6])), "r"(pack_bf16(c[8], c[10])), "r"(pack_bf16(c[12], c[14])) : "memory");
                }
                if (k > MIXV) signal_stores(4);
            }
        };

        TRACE_SLOT(tile_slot, 16 + wg * 8);
#pragma unroll 1
        for (int t = 0; t < G1_TILES; t++) {
#pragma unroll
            for (int k = 0; k < G1_KSTEPS; k++) {
                const int s = k & 3;
                TRACE_STEP(t, k, 0);
                mbar_wait(full1(s), (k >> 2) & 1);
                if (k == 0) TRACE_S(12, t, 0);
                TRACE_STEP(t, k, 1);
                if (k == MIXQ) {
#pragma unroll
                    for (int i = 0; i < 8; i++) asm volatile("" : "=r"(sx[i]));
                    if (t == 2) mix_qk();
                }
                if (k == MIXV && t == 3) mix_pv();
                if (wg == 1 && k == G1_KSTEPS - (t ? G1_SKEW : SK0)) asm volatile("bar.sync 1, 256;" ::: "memory");
                if (k >= G1_KSTEPS - TAIL1 && t == G1_TILES - 1) mma_step224(acc, da, db, s * G1_STAGE_BYTES / 16, k);
                else mma_step(acc, da, db, s * G1_STAGE_BYTES / 16, k);
                if (wg == 0 && k == G1_KSTEPS - 1) asm volatile("bar.arrive 1, 256;" ::: "memory");
                wg_wait<1>();
                if (k > 0) release(empty1((k - 1) & 3));
                TRACE_STEP(t, k, 2);
                if (t == 0) chunk_ln(k);
                if (t == 2) chunk_qk(k);
                if (t == 3) chunk_pv(k);
                if (k >= 1 && k <= 8 && ((k <= 4 ? 0x1a : 0x12) >> t & 1)) {
                    chunk_geglu(k - 1);
                    if (k == 8) signal_stores(t + 1);
                }
                if (k == TLD && t == G1_TILES - 1) {
#pragma unroll
                    for (int i = 0; i < 2; i++) {
                        const uint4 v = ldg_stream(prm.tail + role * 512 + i * 256 + threadIdx.x, stream_policy());
                        pk[16 + 4 * i] = v.x; pk[17 + 4 * i] = v.y; pk[18 + 4 * i] = v.z; pk[19 + 4 * i] = v.w;
                    }
                }
                if (k == TLD + 3 && t == G1_TILES - 1) {
#pragma unroll
                    for (int i = 0; i < 8; i++)
                        asm volatile("shl.b32 %0, %2, 16;\nand.b32 %1, %2, 0xffff0000;" : "=r"(pk[2 * i]), "=r"(pk[2 * i + 1]) : "r"(pk[16 + i]));
                }
                if (k == 13) {
                    optr = prm.pa2 + (size_t)(row0 + (lane >> 2) * 2) * K2 + DM + gate_col(t, nslot) + (lane & 3) * 8;
                    asm volatile("" : "+l"(optr));
                }
            }
            wg_wait<0>();
            fence_regs(acc);
            release(empty1(3));
            if (t == 0) {
#pragma unroll
                for (int i = 0; i < 128; i++) acc[i] *= __uint_as_float(pk[32 + i / 2 % 2]);
                fence_regs(acc);
            }
            if (t == G1_TILES - 1) {
#pragma unroll
                for (int i = 0; i < 16; i++) acc[112 + i] += __uint_as_float(pk[i]);
                fence_regs(acc);
            }
#pragma unroll
            for (int i = 0; i < 64; i++) {
                const int e = i < 32 ? (i & ~7) * 2 + (i & 3) * 4 + (i & 4) / 2 : i * 2;
                pk[i] = pack_bf16(acc[e], acc[e + 1]);
            }
            TRACE_NEXT(tile_slot);
        }

        float accd[64], accs[64];
#pragma unroll
        for (int i = 0; i < 64; i++) accd[i] = 0.f;
#pragma unroll
        for (int u = 0; u < G2_HEAD; u++) {
            const int q = u % G2_STAGES;
            mbar_wait(full2(q), (u / G2_STAGES) & 1);
            mma_step(accd, da, db, q * G2_STAGE_BYTES / 16, u);
            wg_wait<1>();
            if (u > 0) release(empty2((u - 1) % G2_STAGES));
            if (u >= 1) {
                const int j = (u - 1) / 2;
#pragma unroll
                for (int i = 2 * u - 2; i < 2 * u; i++) pk[i] = geglu2(pk[i], pk[up(i)]);
                if (u % 2 == 0) store_pk(optr + (j & 1) * 16 * K2 + (j >> 1) * 32, j);
            }
            if (u == G2_HEAD - 1) signal_stores(6);
        }
        {
            int q = G2_HEAD % G2_STAGES, qp = (G2_HEAD - 1) % G2_STAGES; uint32_t ph = (G2_HEAD / G2_STAGES) & 1;
#pragma unroll 1
            for (int u = G2_HEAD; u < G2_DSTEPS; u++) {
                mbar_wait(full2(q), ph);
                if (G2_NARROW >> u & 1) mma_step96(accd, da, db, q * (G2_STAGE_BYTES / 16));
                else mma_step(accd, da, db, q * (G2_STAGE_BYTES / 16), 1);
                wg_wait<1>();
                release(empty2(qp));
                qp = q;
                if (++q == G2_STAGES) { q = 0; ph ^= 1; }
            }
        }
        TRACE_NEXT(tile_slot);
#pragma unroll
        for (int i = 0; i < 64; i++) accs[i] = 0.f;
        uint32_t gk[32], xr[32];
        const uint32_t xs = aux + cw * 2048;
        const uint32_t xrow = xs + ((lane & 7) + ((lane >> 3) & 1) * 8) * 128;
        auto xaddr = [&](int j) { return xrow + (j >> 2) * 16384 + (((((j & 3) * 2) + (lane >> 4)) ^ (lane & 7)) << 4); };
#pragma unroll
        for (int u = G2_DSTEPS; u < G2_KSTEPS; u++) {
            const int q = u % G2_STAGES, v = u - G2_DSTEPS;
            mbar_wait(full2(q), (u / G2_STAGES) & 1);
            if (G2_SKEW > 0 && wg == 1 && u == G2_KSTEPS - G2_SKEW) asm volatile("bar.sync 1, 256;" ::: "memory");
            mma_step(accs, da, db, q * G2_STAGE_BYTES / 16, v);
            if (G2_SKEW > 0 && wg == 0 && u == G2_KSTEPS - 1) asm volatile("bar.arrive 1, 256;" ::: "memory");
            if (v == TLD2) {
                TRACE_S(32, wg, 0);
                mbar_wait(dep_bar + 24, 0);
                TRACE_S(33, wg, 0);
#pragma unroll
                for (int i = 0; i < 2; i++) {
                    const uint4 w = ldg_stream(prm.tail + (NGEMM + role) * 512 + i * 256 + threadIdx.x, stream_policy());
                    gk[24 + 4 * i] = w.x; gk[25 + 4 * i] = w.y; gk[26 + 4 * i] = w.z; gk[27 + 4 * i] = w.w;
                }
            }
            const int gate = v <= 6 ? v - 1 : v - TLD2 + 3;
            if (gate >= (v <= 6 ? 0 : 6) && gate < 8) {
#pragma unroll
                for (int i = 4 * gate; i < 4 * gate + 4; i++) {
                    const uint32_t d2 = i < 24 ? pack_bf16(accd[2 * i], accd[2 * i + 1])
                                               : pack_bf16(accd[2 * i] + bf_lo(gk[i]), accd[2 * i + 1] + bf_hi(gk[i]));
                    gk[i] = pack_bf16(silu(bf_lo(d2)), silu(bf_hi(d2)));
                }
            }
            if (v == XLD) mbar_wait(x_bar, 0);
            if (v >= XLD && v < XLD + 4) {
#pragma unroll
                for (int j = 2 * (v - XLD); j < 2 * (v - XLD + 1); j++)
                    asm volatile("ldmatrix.sync.aligned.m8n8.x4.shared.b16 {%0,%1,%2,%3}, [%4];"
                                 : "=r"(xr[4 * j]), "=r"(xr[4 * j + 1]), "=r"(xr[4 * j + 2]), "=r"(xr[4 * j + 3])
                                 : "r"(xaddr(j)) : "memory");
            }
            wg_wait<1>();
            if (v == 0) fence_regs(accd);
            if (u - 1 + G2_STAGES < G2_KSTEPS) release(empty2((u - 1) % G2_STAGES));
        }
        __nv_bfloat16* po = prm.pout + (row0 + (lane >> 3) * 2) * DM + nslot * 128 + 64 + (lane & 7) * 8;
        uint32_t so = xs + 16384 + (lane >> 3) * 128 + (((lane & 7) ^ (lane >> 3)) << 4);
        const int c0 = uniform(nslot * 128), c1 = uniform(row0 >> 1);
        const uint32_t xu = uniform(xs);
        asm volatile("" : "+l"(po), "+r"(so));
        wg_wait<0>();
        fence_regs(accs);
        TRACE_NEXT(tile_slot);
        TRACE_END();
#pragma unroll
        for (int j = 0; j < 8; j++) {
            uint32_t r[4];
#pragma unroll
            for (int i = 0; i < 4; i++) {
                const int e = j * 4 + i;
                asm("fma.rn.bf16x2 %0, %1, %2, %3;" : "=r"(r[i]) : "r"(pack_bf16(accs[2 * e], accs[2 * e + 1])), "r"(gk[e]), "r"(xr[e]));
            }
            asm volatile("stmatrix.sync.aligned.m8n8.x4.shared.b16 [%0], {%1,%2,%3,%4};"
                         :: "r"(xaddr(j)), "r"(r[0]), "r"(r[1]), "r"(r[2]), "r"(r[3]) : "memory");
            if (j == 3)
                asm volatile("{\n.reg .pred e;\nfence.proxy.async.shared::cta;\nbar.warp.sync 0xffffffff;\nelect.sync _|e, 0xffffffff;\n"
                    "@e cp.async.bulk.tensor.3d.global.shared::cta.bulk_group [%0, {%2, %3, %4}], [%1];\n}"
                    :: "l"(&prm.out), "r"(xu), "r"(c0), "r"(c1), "r"(wg) : "memory");
        }
        __syncwarp();
#pragma unroll
        for (int i = 0; i < 4; i++) {
            const uint4 v = lds128((so ^ (i & 1) * 64) + i * 512);
            asm volatile("st.global.v4.u32 [%0], {%1,%2,%3,%4};" :: "l"(po + i * 8 * DM), "r"(v.x), "r"(v.y), "r"(v.z), "r"(v.w) : "memory");
        }
        asm volatile("cp.async.bulk.commit_group;\ncp.async.bulk.wait_group.read 0;" ::: "memory");
        if (tid == 0) { TRACE_NEXT(tile_slot); if (wg == 1) TRACE_GT(13); TRACE_DUMP(); }
    } else {
        asm volatile("setmaxnreg.dec.sync.aligned.u32 %0;" :: "n"(AUX_REGS));
        cluster_wait();
        unsigned* const flags = prm.flags + mblk * 32;
        if (warp == 9) {
            TRACE_CLEAR(); TRACE_GT(0);
            if (lane == 0) {
                const unsigned epoch = __ldcg(prm.epoch + blockIdx.x * 16 + 2) + 1;
                mbar_wait(sig_bar, 0);
                TRACE(11);
                flag_add(flags + F_LN * 512);
                TRACE(42);
                flag_wait(flags + F_LN * 512, epoch * CNT_LN);
                fence_proxy_async();
                mbar_arrive(dep_bar);
                mbar_wait(sig_bar + 56, 0);
                flag_add(flags + F_LN2 * 512);
                flag_wait(flags + F_LN2 * 512, epoch * CNT_LN);
                fence_proxy_async();
                mbar_arrive(dep_bar + 40);
                TRACE(59);
                prm.epoch[blockIdx.x * 16 + 2] = epoch;
#pragma unroll 1
                for (int p = 3; p < 7; p++) {
                    mbar_wait(sig_bar + (p == 3 ? 16 : p * 8), 0);
                    TRACE_S(37, p, 4);
                    flag_add(flags + (p / 2 + 1) * 512);
                    TRACE_S(43, p, 4);
                }
            }
        } else if (warp > 9) {
            const int w = warp - 10;
            const unsigned epoch = __ldcg(prm.epoch + blockIdx.x * 16 + w) + 1;
            const uint32_t tag = 1 + (epoch & 1);
            const uint32_t at = (w ? CB : CA) >> (CIDX) * 4 & 15;
            mbar_wait(empty1(at & 3), 0);
            mbar_wait(empty1(at & 3), at >> 3);
            if (elect_one()) {
                mbar_expect_tx(cs_bar + w * 8, 16384);
                asm volatile("cp.async.bulk.tensor.2d.shared::cluster.global.mbarrier::complete_tx::bytes [%0], [%1, {%3, %5}], [%2];\n"
                    "cp.async.bulk.tensor.2d.shared::cluster.global.mbarrier::complete_tx::bytes [%0 + 8192], [%1, {%4, %5}], [%2];"
                    :: "r"(aux + w * 16384), "l"(w0), "r"(cs_bar + w * 8), "r"(nslot * 128), "r"(nslot * 128 + 64),
                       "r"(((mblk & ~1) + w) * 64) : "memory");
            }
            float cs[8];
#pragma unroll
            for (int d = 0; d < 8; d++) cs[d] = 0.f;
            const uint32_t wa = aux + w * 8192 + (lane >> 3) * 128 + (((lane & 7) ^ (lane >> 3)) << 4);
            uint4 v[9];
            auto fetch = [&](int h, uint32_t off) {
#pragma unroll
                for (int j = 0; j < 4; j++) v[h * 4 + j] = lds128((wa ^ (j & 1) * 64) + off + h * 2048 + j * 512);
            };
            auto add = [&](int h) {
#pragma unroll
                for (int j = 0; j < 4; j++) {
                    float f[8];
                    unpack8(v[h * 4 + j], f);
#pragma unroll
                    for (int d = 0; d < 8; d++) cs[d] += f[d];
                }
            };
            if (CST) { mbar_wait(empty1(CST & 3), 0); mbar_wait(empty1(CST & 3), CST >> 3); }
            mbar_wait(cs_bar, 0);

            fetch(0, 0);
#pragma unroll 1
            for (int i = 0; i < 4; i++) {
                fetch(1, (i >> 1) * 16384 + (i & 1) * 4096);
                add(0);
                if (i == 1) mbar_wait(cs_bar + 8, 0);
                fetch(0, (i + 1 & 2) * 8192 + (~i & 1) * 4096);
                add(1);
            }
#pragma unroll
            for (int d = 0; d < 4; d++)
                cs[d] = (lane & 16 ? cs[d + 4] : cs[d]) + __shfl_xor_sync(0xffffffffu, lane & 16 ? cs[d] : cs[d + 4], 16);
#pragma unroll
            for (int d = 0; d < 2; d++)
                cs[d] = (lane & 8 ? cs[d + 2] : cs[d]) + __shfl_xor_sync(0xffffffffu, lane & 8 ? cs[d] : cs[d + 2], 8);
            st_tagged(prm.colsum + (nslot * 2 + rank) * 1024 + (mblk >> 1) * 128 + w * 64 + (lane & 7) * 8 + (lane >> 3) * 2,
                      cs[0], cs[1], tag);

#pragma unroll
            for (int m = 0; m < 9; m++) v[m] = make_uint4(0, 0, 0, 0);
            const float* parts = prm.colsum + (nslot * 2 + (lane >> 4)) * 1024 + w * 64 + (lane & 15) * 4;
            const float* const rows = &prm.stats[mblk * 128 + w * 64 + lane * 2].x;
#pragma unroll 1
            for (int spins = 0; spins < (1 << 16); spins++) {
                bool missing = false;
                asm volatile("" : "+l"(parts));
#pragma unroll
                for (int m = 0; m < 9; m++) {
                    if (untagged(v[m], tag)) {
                        missing = true;
                        v[m] = ld_relaxed(m < 8 ? parts + m * 128 : rows);
                    }
                }
                if (!missing) break;
            }
            float4 c = make_float4(0.f, 0.f, 0.f, 0.f);
#pragma unroll
            for (int m = 0; m < 8; m++) {
                c.x += __uint_as_float(v[m].x ^ tag); c.y += __uint_as_float(v[m].y ^ tag);
                c.z += __uint_as_float(v[m].z ^ tag); c.w += __uint_as_float(v[m].w ^ tag);
            }
            sts128(stats + w * 512 + lane * 16, make_uint4(v[8].x ^ tag, v[8].y ^ tag, v[8].z ^ tag, v[8].w ^ tag));
            const uint32_t ca = aux + w * 8192 + (lane >> 4) * 16384 + (lane & 15) * 8;
#pragma unroll
            for (int r = 0; r < 3; r++) {
                const uint32_t lo = pack_bf16(c.x, c.y), hi = pack_bf16(c.z, c.w);
                sts64f((ca ^ r * 16) + r * 128, __uint_as_float(lo), __uint_as_float(hi));
                c.x -= bf_lo(lo); c.y -= bf_hi(lo); c.z -= bf_lo(hi); c.w -= bf_hi(hi);
            }
            asm volatile("fence.proxy.async.shared::cta;" ::: "memory");
            __syncwarp();
            if (lane == 0) {
                mbar_arrive(fold_bar);
                prm.epoch[blockIdx.x * 16 + w] = epoch;
                if (w == 0) {
                    TRACE_S(35, w, 0);
                    flag_wait(flags + F_TAIL * 512, epoch * 2 - 1);
                    mbar_arrive(x_bar + 8);
                    flag_wait(flags + F_FIRST * 512, epoch * CNT_FIRST);
                    flag_wait(flags + F_EARLY * 512, epoch * CNT_EARLY);
                    fence_proxy_async(); mbar_arrive(dep_bar + 8);
                    flag_wait(flags + F_LATE * 512, epoch * CNT_LATE);
                    fence_proxy_async(); mbar_arrive(dep_bar + 16);
                    flag_wait(flags + F_TAIL * 512, epoch * 2);
                    mbar_arrive(dep_bar + 24);
                } else {
#pragma unroll 1
                    for (int j = 0; j < 2; j++) {
                        uint8_t* const h = prm.halo + (j * NGEMM + role) * HALO_BYTES;
                        unsigned* const f = prm.flags + F_HALO * 512 + role * 32;
                        mbar_wait(sig_bar + 8 + j * 16, 0);
                        TRACE_S(38, j, 0); TRACE_S(46, j, 1);
                        asm volatile("cp.async.bulk.global.shared::cta.bulk_group [%0], [%1], %2;\n"
                            "cp.async.bulk.commit_group;\ncp.async.bulk.wait_group 0;"
                            :: "l"(h + HALO_BYTES), "r"(aux + 4 * HALO_BYTES), "n"(HALO_BYTES) : "memory");
                        fence_proxy_async();
                        TRACE_S(39, j, 0); TRACE_S(47, j, 1);
                        flag_add(f);
                        TRACE_S(40, j, 0); TRACE_S(53, j, 1);
                        if (mblk) flag_wait(f - 32, epoch * 2 - 1 + j);
                        fence_proxy_async();
                        TRACE_S(41, j, 0); TRACE_S(54, j, 1);
                        mbar_expect_tx(halo_bar, HALO_BYTES);
                        asm volatile("cp.async.bulk.shared::cluster.global.mbarrier::complete_tx::bytes [%0], [%1], %2, [%3];"
                            :: "r"(aux), "l"(mblk ? h : prm.halo), "n"(HALO_BYTES), "r"(halo_bar) : "memory");
                    }
                }
            }
        } else {
#pragma unroll
            for (int k = 1; k < G1_STAGES; k++) {
                const uint32_t sa = base + k * G1_STAGE_BYTES;
                if (PACE0 + PACE) while ((uint32_t)clock() - t0 < (k == 3 ? PACE3 : PACE0 + (k - 1) * PACE)) {}
                load_stage1(sa, sa + A_BYTES + rank * 16384, full1(k), &prm.x, w0, w0, k * 64, mblk * 64, nslot * 128,
                            nslot * 128 + 64, 0, stream_policy());
            }
            if (elect_one()) {
                prefetch_map(&prm.xn); prefetch_map(&prm.wqkv);
                prefetch_map(&prm.a2); prefetch_map(&prm.wo); prefetch_map(&prm.wd); prefetch_map(&prm.out);
            }
            auto load_x = [&]() {
                if (elect_one()) {
                    mbar_expect_tx(x_bar, 32768);
                    tma_3d(aux, &prm.x, x_bar, nslot * 128, mblk * 64, 0, stream_policy());
                    tma_3d(aux + 16384, &prm.x, x_bar, nslot * 128 + 64, mblk * 64, 0, stream_policy());
                }
                __syncwarp();
            };
            uint32_t ph = 0;
#pragma unroll 1
            for (int t = 0; t < G1_TILES; t++) {
                const int col0 = t == 1 ? rank * DM + nslot * 128 : gate_col(t, nslot);
                const int col1 = t == 2 ? 2 * DM + nslot * 128 + rank * 64 : col0 + 64;
                if (t == 1) { TRACE_PUT(1, c0); TRACE_PUT(2, t0); TRACE(14); mbar_wait_warp(dep_bar, 0); TRACE(3); }
#pragma unroll 1
                for (int k = t ? 0 : G1_STAGES; k < G1_KSTEPS; k++) {
                    const int s = k & 3;
                    if (t == 1 && k == 8) mbar_wait_warp(dep_bar + 40, 0);
                    if (t * 16 + k == 64 + TLD) { TRACE(61); mbar_wait_warp(x_bar + 8, 0); TRACE(63); }
                    if (t * 16 + k == (PFK)) {
                        asm volatile("{\n.reg .pred e;\nelect.sync _|e, 0xffffffff;\n"
                            "@e cp.async.bulk.prefetch.tensor.5d.L2.global [%0, {%1, %4, %4, %4, %3}];\n"
                            "@e cp.async.bulk.prefetch.tensor.5d.L2.global [%0, {%2, %4, %4, %4, %3}];\n}"
                            :: "l"(&prm.wd), "r"(nslot * 128), "r"(nslot * 128 + 64), "r"((mblk + TAIL2) * 2), "r"(0) : "memory");
                    }
                    mbar_wait_warp(empty1(s), ph);
                    const uint32_t sa = base + s * G1_STAGE_BYTES;
                    load_stage1(sa, sa + A_BYTES + rank * 16384, full1(s), t ? &prm.xn : &prm.x, t == 1 ? &prm.wqkv : w0,
                                t == 1 || t == 2 ? &prm.wqkv : w0, (k + (t >> 2) * TAIL1 & 15) * 64, mblk * 64, col0, col1, t & 3,
                                stream_policy());
                    if (s == 3) ph ^= 1;
                    if (t * 16 + k == (XK)) load_x();
                }
            }
            TRACE(4);
            mbar_wait_warp(dep_bar + 8, 0);
            TRACE(5);
            int q = 0, narrow = 0; uint32_t ph2 = 1;
#pragma unroll 1
            for (int u = 0; u < G2_KSTEPS; u++) {
                if (u == G2_LATE) { TRACE(6); mbar_wait_warp(dep_bar + 16, 0); TRACE(7); }
                const uint32_t sa = stage2(q);
                const bool down = u < G2_DSTEPS;
                const int k = !down ? u - G2_DSTEPS : (G2_NARROW >> u & 1 ? narrow++ : u + TAIL2 - narrow);
                mbar_wait_warp(u < G2_STAGES ? empty1((u * 2 + 1) / 3) : empty2(q), u < G2_STAGES ? ph : ph2);
                load_stage2(sa, sa + A_BYTES + rank * 8192, full2(q), &prm.a2, down ? &prm.wd : &prm.wo, (down ? DM : 0) + k * 64,
                            mblk * 64, nslot * 128 + rank * 64, down ? 0 : k * 2, down ? k * 2 : 0, stream_policy());
                if (++q == G2_STAGES) { q = 0; ph2 ^= 1; }
            }
            TRACE(8);
        }
    }
}

typedef CUresult (*EncodeFn)(CUtensorMap*, CUtensorMapDataType, cuuint32_t, void*, const cuuint64_t*, const cuuint64_t*,
                             const cuuint32_t*, const cuuint32_t*, CUtensorMapInterleave, CUtensorMapSwizzle,
                             CUtensorMapL2promotion, CUtensorMapFloatOOBfill);

void encode(EncodeFn fn, CUtensorMap* m, const void* ptr, int rank, const cuuint64_t* dims, const cuuint64_t* strides,
            const cuuint32_t* box) {
    const cuuint32_t es[5] = {1, 1, 1, 1, 1};
    fn(m, CU_TENSOR_MAP_DATA_TYPE_BFLOAT16, rank, const_cast<void*>(ptr), dims, strides, box, es,
       CU_TENSOR_MAP_INTERLEAVE_NONE, box[0] == 32 ? CU_TENSOR_MAP_SWIZZLE_64B : CU_TENSOR_MAP_SWIZZLE_128B,
       CU_TENSOR_MAP_L2_PROMOTION_L2_128B, CU_TENSOR_MAP_FLOAT_OOB_FILL_NONE);
}
void encode_rows(EncodeFn fn, CUtensorMap* m, const void* ptr, int cols, int box_rows, int box_parity) {
    const cuuint64_t dims[3] = {(cuuint64_t)cols, SEQ / 2, 2}, strides[2] = {(cuuint64_t)cols * 4, (cuuint64_t)cols * 2};
    const cuuint32_t box[3] = {64, (cuuint32_t)box_rows, (cuuint32_t)box_parity};
    encode(fn, m, ptr, 3, dims, strides, box);
}
void encode_w1(EncodeFn fn, CUtensorMap* m, const void* ptr, int cols) {
    const cuuint64_t dims[2] = {(cuuint64_t)cols, DM}, strides[1] = {(cuuint64_t)cols * 2};
    const cuuint32_t box[2] = {64, 64};
    encode(fn, m, ptr, 2, dims, strides, box);
}
void encode_tail(EncodeFn fn, CUtensorMap* m, const void* ptr, int rows, int cols, int n) {
    const cuuint64_t rb = cols * 2;
    const cuuint64_t dims[5] = {32, (cuuint64_t)n, (cuuint64_t)rows / (4 * n), 4, 8}, strides[4] = {rb, 4 * n * rb, n * rb, 256};
    const cuuint32_t box[5] = {32, (cuuint32_t)n, 16 / (cuuint32_t)n, 4, 8};
    encode(fn, m, (const __nv_bfloat16*)ptr + cols - 1024 + 96, 5, dims, strides, box);
}
void encode_w2(EncodeFn fn, CUtensorMap* m, const void* ptr, int rows) {
    const cuuint64_t rb = DM * 2;
    const cuuint64_t dims[5] = {DM, 2, 4, 4, (cuuint64_t)rows / 32}, strides[4] = {rb, 8 * rb, 2 * rb, 32 * rb};
    const cuuint32_t box[5] = {64, 2, 4, 4, 2};
    encode(fn, m, ptr, 5, dims, strides, box);
}
void encode_wo(EncodeFn fn, CUtensorMap* m, const void* ptr) {
    const cuuint64_t rb = DM * 2;
    const cuuint64_t dims[5] = {DM, 4, DM / 32, 2, 4}, strides[4] = {8 * rb, 32 * rb, rb, 2 * rb};
    const cuuint32_t box[5] = {64, 4, 2, 2, 4};
    encode(fn, m, ptr, 5, dims, strides, box);
}

}

extern "C" void kernel_launch(void* const* d_in, const int* in_sizes, int n_in, void* d_out, int out_size) {
    (void)in_sizes; (void)n_in; (void)out_size;
    static EncodeFn fn = nullptr;
    static Params prm;
    if (!fn) {
        cudaDriverEntryPointQueryResult st;
        cudaGetDriverEntryPoint("cuTensorMapEncodeTiled", (void**)&fn, cudaEnableDefault, &st);
        cudaGetSymbolAddress((void**)&prm.pxn, g_xn);
        cudaGetSymbolAddress((void**)&prm.pa2, g_a2);
        cudaGetSymbolAddress((void**)&prm.tail, g_tail);
        cudaGetSymbolAddress((void**)&prm.halo, g_halo);
        cudaGetSymbolAddress((void**)&prm.stats, g_stats);
        cudaGetSymbolAddress((void**)&prm.colsum, g_colsum);
        cudaGetSymbolAddress((void**)&prm.flags, g_flags);
        cudaGetSymbolAddress((void**)&prm.epoch, g_epoch);
        cudaFuncSetAttribute(fused_kernel, cudaFuncAttributeMaxDynamicSharedMemorySize, SMEM_BYTES);
    }
    encode_rows(fn, &prm.x, d_in[0], DM, 64, 2);
    encode_rows(fn, &prm.xn, prm.pxn, DM, 64, 2);
    encode_rows(fn, &prm.a2, prm.pa2, K2, 64, 2);
    encode_rows(fn, &prm.out, d_out, DM, 16, 1);
    encode_w1(fn, &prm.wqkv, d_in[1], NQKV);
    encode_w1(fn, &prm.wg, d_in[4], DF);
    encode_w1(fn, &prm.wu, d_in[5], DF);
    encode_tail(fn, &prm.wu_tail, d_in[5], DM, DF, 8);
    encode_tail(fn, &prm.wd_tail, d_in[6], DF, DM, 2);
    encode_wo(fn, &prm.wo, d_in[2]);
    encode_w2(fn, &prm.wd, d_in[6], DF);
    prm.px = (const __nv_bfloat16*)d_in[0];
    prm.pout = (__nv_bfloat16*)d_out;
    fused_kernel<<<NCTA, 384, SMEM_BYTES>>>(prm);
}
```

```cpp
#include <cuda_runtime.h>
#include <cuda_bf16.h>
#include <cuda.h>
#include <stdint.h>
#include <type_traits>

#define LNS 3
#define FS 14
#define CA 0x87658765u
#define CB 0x65876587u
#define CST 10
#define CIDX nslot
#define PACE0 900
#define PACE 425
#define PACE3 1700
#define TAIL1 11
#define TAIL2 10
#define NAR0 18
#define NARS 2
#define MIXQ 9
#define MIXV 10
#define TST 4
#define TLD2 4
#define XLD 9
#define VK 1
#define VN 2
#define KK 1
#define EREL 0
#define MEET 2
#define OVS 3
#define SK2 5
#define PFK 60 + mblk
#define XK 66 + nslot
#define TSK 2
#define TW0 9000
#define TLD 10
#define SK0 2

namespace {

constexpr int SEQ = 2048, DM = 1024, DF = 3584, K2 = DM + DF, NQKV = 3 * DM;
constexpr int NGEMM = 128, NCTA = 132;
constexpr int G1_STAGES = 4, G1_STAGE_BYTES = 49152, G1_KSTEPS = 16, G1_TILES = 5;
constexpr int G2_STAGES = 6, G2_STAGE_BYTES = 32768, G2_KSTEPS = 72, G2_LATE = 40, G2_DSTEPS = 56;
constexpr int G2_HEAD = 17;
constexpr int LN_STEP = LNS, FOLD_STEP = FS;
constexpr int A_BYTES = 16384;
constexpr int AUX_OFF = G1_STAGES * G1_STAGE_BYTES;
constexpr int BAR_OFF = AUX_OFF + 32768;
constexpr int SMEM_BYTES = BAR_OFF + 2816;
constexpr int G1_SKEW = 2, G2_SKEW = SK2;
constexpr int CONSUMER_REGS = 224, AUX_REGS = 56;
constexpr int HALO_BYTES = 4096;
constexpr uint64_t narrow_steps() {
    uint64_t m = 0;
    for (int i = 0; i < TAIL2; i++) m |= 1ull << NAR0 + i * NARS;
    return m;
}
constexpr uint64_t G2_NARROW = narrow_steps();
static_assert(G2_NARROW >> G2_LATE == 0, "narrow steps use early columns");

enum { F_LN = 0, F_LN2 = 1, F_FIRST = 2, F_EARLY = 3, F_LATE = 4, F_TAIL = 5, F_HALO = 6 };
constexpr unsigned CNT_LN = 8, CNT_FIRST = 8, CNT_EARLY = 16, CNT_LATE = 8;

__device__ __align__(1024) __nv_bfloat16 g_xn[SEQ * DM];
__device__ __align__(1024) __nv_bfloat16 g_a2[SEQ * K2];
__device__ __align__(128) uint4 g_tail[2 * NGEMM * 512];
__device__ __align__(128) uint8_t g_halo[(2 * NGEMM + 1) * HALO_BYTES];
__device__ __align__(128) float2 g_stats[SEQ];
__device__ __align__(128) float g_colsum[16 * 1024];
__device__ __align__(128) unsigned g_flags[(F_HALO + 8) * 16 * 32];
__device__ __align__(128) unsigned g_epoch[NCTA * 16];

struct Params {
    const __nv_bfloat16* px;
    __nv_bfloat16 *pxn, *pa2, *pout;
    uint4* tail;
    uint8_t* halo;
    float2* stats;
    float* colsum;
    unsigned *flags, *epoch;
    unsigned long long* trace;
    CUtensorMap x, wg, wu, xn, wqkv, a2, wu_tail, wd_tail, wo, wd, out;
};

extern __shared__ __align__(1024) uint8_t smem_raw[];

#define TRACE(slot) do {} while (0)
#define TRACE_GT(slot) do {} while (0)
#define TRACE_S(slot, v, want) do {} while (0)
#define TRACE_GET(v) do {} while (0)
#define TRACE_PUT(slot, v) do {} while (0)
#define TRACE_SLOT(v, slot) do {} while (0)
#define TRACE_NEXT(v) do {} while (0)
#define TRACE_DUMP() do {} while (0)
#define TRACE_CLEAR() do {} while (0)
#define STAGE_TRACE 0
#define TRACE_END() do {} while (0)
#define TRACE_STEP(t, k, i) do {} while (0)

__device__ __forceinline__ uint32_t smem_u32(const void* p) { return (uint32_t)__cvta_generic_to_shared(p); }
__device__ __forceinline__ void mbar_init(uint32_t bar, uint32_t cnt) {
    asm volatile("mbarrier.init.shared::cta.b64 [%0], %1;" :: "r"(bar), "r"(cnt) : "memory");
}
__device__ __forceinline__ void mbar_expect_tx(uint32_t bar, uint32_t bytes) {
    asm volatile("mbarrier.arrive.expect_tx.shared::cta.b64 _, [%0], %1;" :: "r"(bar), "r"(bytes) : "memory");
}
__device__ __forceinline__ void mbar_arrive(uint32_t bar) {
    asm volatile("mbarrier.arrive.shared::cta.b64 _, [%0];" :: "r"(bar) : "memory");
}
__device__ __forceinline__ void mbar_arrive_cluster(uint32_t bar, uint32_t cta) {
    asm volatile("{\n.reg .b32 ra;\nmapa.shared::cluster.u32 ra, %0, %1;\nmbarrier.arrive.shared::cluster.b64 _, [ra];\n}"
                 :: "r"(bar), "r"(cta) : "memory");
}
__device__ __forceinline__ bool mbar_try_wait(uint32_t bar, uint32_t parity) {
    uint32_t ok;
    asm volatile("{\n.reg .pred p;\nmbarrier.try_wait.parity.shared::cta.b64 p, [%1], %2;\nselp.u32 %0, 1, 0, p;\n}"
                 : "=r"(ok) : "r"(bar), "r"(parity) : "memory");
    return ok;
}
__device__ __forceinline__ void mbar_wait(uint32_t bar, uint32_t parity) {
#pragma unroll 1
    for (int spins = 0; !mbar_try_wait(bar, parity) && spins < (1 << 17); spins++) {}
}
template <bool WARP = false> __device__ __forceinline__ void flag_wait(const unsigned* p, unsigned target) {
#pragma unroll 1
    for (int spins = 0; spins < (1 << 19); spins++) {
        unsigned v;
        asm volatile("ld.acquire.gpu.global.u32 %0, [%1];" : "=r"(v) : "l"(p) : "memory");
        if (WARP ? __all_sync(0xffffffffu, (int)(v - target) >= 0) : (int)(v - target) >= 0) break;
        __nanosleep(64);
    }
}
__device__ __forceinline__ void mbar_wait_warp(uint32_t bar, uint32_t parity) {
#pragma unroll 1
    for (int spins = 0; !__all_sync(0xffffffffu, mbar_try_wait(bar, parity)) && spins < (1 << 17); spins++) {}
}
__device__ __forceinline__ void flag_add(unsigned* p) {
    asm volatile("red.release.gpu.global.add.u32 [%0], 1;" :: "l"(p) : "memory");
}
__device__ __forceinline__ bool elect_one() {
    uint32_t ok;
    asm volatile("{\n.reg .pred p;\nelect.sync _|p, 0xffffffff;\nselp.u32 %0, 1, 0, p;\n}" : "=r"(ok));
    return ok;
}
__device__ __forceinline__ uint32_t pick(bool c, uint32_t a, uint32_t b) {
    uint32_t r;
    asm("{\n.reg .pred p;\nsetp.ne.b32 p, %3, 0;\nselp.b32 %0, %1, %2, p;\n}" : "=r"(r) : "r"(a), "r"(b), "r"((uint32_t)c));
    return r;
}
__device__ __forceinline__ void fence_proxy_async() { asm volatile("fence.proxy.async.global;" ::: "memory"); }
__device__ __forceinline__ uint4 lds128(uint32_t addr) {
    uint4 v;
    asm volatile("ld.shared.v4.u32 {%0,%1,%2,%3}, [%4];" : "=r"(v.x), "=r"(v.y), "=r"(v.z), "=r"(v.w) : "r"(addr) : "memory");
    return v;
}
__device__ __forceinline__ float2 lds64f(uint32_t addr) {
    float2 v;
    asm volatile("ld.shared.v2.f32 {%0,%1}, [%2];" : "=f"(v.x), "=f"(v.y) : "r"(addr) : "memory");
    return v;
}
__device__ __forceinline__ void sts128(uint32_t addr, uint4 v) {
    asm volatile("st.shared.v4.u32 [%0], {%1,%2,%3,%4};" :: "r"(addr), "r"(v.x), "r"(v.y), "r"(v.z), "r"(v.w) : "memory");
}
__device__ __forceinline__ void sts64f(uint32_t addr, float a, float b) {
    asm volatile("st.shared.v2.f32 [%0], {%1,%2};" :: "r"(addr), "f"(a), "f"(b) : "memory");
}

__device__ __forceinline__ uint64_t stream_policy() { return 0x12F0000000000000ull; }
__device__ __forceinline__ void tma_3d(uint32_t dst, const CUtensorMap* m, uint32_t bar, int c0, int c1, int c2, uint64_t pol) {
    asm volatile("cp.async.bulk.tensor.3d.shared::cluster.global.mbarrier::complete_tx::bytes.L2::cache_hint"
                 " [%0], [%1, {%3, %4, %5}], [%2], %6;"
                 :: "r"(dst), "l"(m), "r"(bar), "r"(c0), "r"(c1), "r"(c2), "l"(pol) : "memory");
}
__device__ __forceinline__ void load_stage1(uint32_t dst, uint32_t dst_b, uint32_t bar, const CUtensorMap* ma, const CUtensorMap* mb0,
                                            const CUtensorMap* mb1, int k, int row, int col0, int col1, int keep_a, uint64_t pol) {
    asm volatile("{\n.reg .pred e, p, q;\nelect.sync _|e, 0xffffffff;\nsetp.ne.and.b32 p|q, %8, 0, e;\n"
        "@p cp.async.bulk.tensor.3d.shared::cluster.global.mbarrier::complete_tx::bytes [%0], [%3, {%5, %6, %10}], [%2];\n"
        "@q cp.async.bulk.tensor.3d.shared::cluster.global.mbarrier::complete_tx::bytes.L2::cache_hint [%0], [%3, {%5, %6, %10}], [%2], %9;\n"
        "@e cp.async.bulk.tensor.2d.shared::cluster.global.mbarrier::complete_tx::bytes.multicast::cluster.L2::cache_hint"
        " [%1], [%4, {%7, %5}], [%2], %11, %9;\n"
        "@e cp.async.bulk.tensor.2d.shared::cluster.global.mbarrier::complete_tx::bytes.multicast::cluster.L2::cache_hint"
        " [%1 + 8192], [%13, {%14, %5}], [%2], %11, %9;\n"
        "@e mbarrier.arrive.expect_tx.shared::cta.b64 _, [%2], %12;\n}"
        :: "r"(dst), "r"(dst_b), "r"(bar), "l"(ma), "l"(mb0), "r"(k), "r"(row), "r"(col0), "r"(keep_a), "l"(pol), "r"(0),
           "h"((uint16_t)3), "n"(G1_STAGE_BYTES), "l"(mb1), "r"(col1) : "memory");
}
__device__ __forceinline__ void load_stage2(uint32_t dst, uint32_t dst_b, uint32_t bar, const CUtensorMap* ma, const CUtensorMap* mb,
                                            int ka, int row, int col, int kb2, int kb4, uint64_t pol) {
    asm volatile("{\n.reg .pred e;\nelect.sync _|e, 0xffffffff;\n"
        "@e cp.async.bulk.tensor.3d.shared::cluster.global.mbarrier::complete_tx::bytes.L2::cache_hint [%0], [%3, {%5, %6, %10}], [%2], %9;\n"
        "@e cp.async.bulk.tensor.5d.shared::cluster.global.mbarrier::complete_tx::bytes.multicast::cluster.L2::cache_hint"
        " [%1], [%4, {%7, %10, %13, %10, %8}], [%2], %11, %9;\n"
        "@e mbarrier.arrive.expect_tx.shared::cta.b64 _, [%2], %12;\n}"
        :: "r"(dst), "r"(dst_b), "r"(bar), "l"(ma), "l"(mb), "r"(ka), "r"(row), "r"(col), "r"(kb4), "l"(pol), "r"(0),
           "h"((uint16_t)3), "n"(G2_STAGE_BYTES), "r"(kb2) : "memory");
}
__device__ __forceinline__ uint4 ldg_stream(const void* p, uint64_t pol) {
    uint4 v;
    asm volatile("ld.global.nc.L1::no_allocate.L2::cache_hint.v4.u32 {%0,%1,%2,%3}, [%4], %5;"
                 : "=r"(v.x), "=r"(v.y), "=r"(v.z), "=r"(v.w) : "l"(p), "l"(pol));
    return v;
}
__device__ __forceinline__ void st_tagged(void* p, float a, float b, uint32_t tag) {
    asm volatile("st.relaxed.gpu.global.v2.b32 [%0], {%1,%2};"
                 :: "l"(p), "r"((__float_as_uint(a) & ~3u) | tag), "r"((__float_as_uint(b) & ~3u) | tag) : "memory");
}
__device__ __forceinline__ bool untagged(const uint4& v, uint32_t tag) {
    return ((v.x ^ tag) | (v.y ^ tag) | (v.z ^ tag) | (v.w ^ tag)) & 3;
}
__device__ __forceinline__ uint4 ld_relaxed(const void* p) {
    uint4 v;
    asm volatile("ld.relaxed.gpu.global.v4.b32 {%0,%1,%2,%3}, [%4];" : "=r"(v.x), "=r"(v.y), "=r"(v.z), "=r"(v.w) : "l"(p) : "memory");
    return v;
}
__device__ __forceinline__ void prefetch_map(const CUtensorMap* m) {
    asm volatile("prefetch.tensormap [%0];" :: "l"(m) : "memory");
}
template <int N> __device__ __forceinline__ void wg_wait() { asm volatile("wgmma.wait_group.sync.aligned %0;" :: "n"(N) : "memory"); }

__device__ __forceinline__ uint32_t desc_a(uint32_t addr) { return (addr & 0x3FFFF) >> 4 | 1 << 16; }
__device__ __forceinline__ uint32_t desc_b(uint32_t addr) { return (addr & 0x3FFFF) >> 4 | 512 << 16; }

#define R8(d, o) "+f"(d[o]), "+f"(d[o+1]), "+f"(d[o+2]), "+f"(d[o+3]), "+f"(d[o+4]), "+f"(d[o+5]), "+f"(d[o+6]), "+f"(d[o+7])
#define R32(d, o) R8(d, o), R8(d, o+8), R8(d, o+16), R8(d, o+24)
#define R64(d, o) R32(d, o), R32(d, o+32)
#define ACC00 "%0,%1,%2,%3,%4,%5,%6,%7,%8,%9,%10,%11,%12,%13,%14,%15,%16,%17,%18,%19,%20,%21,%22,%23,%24,%25,%26,%27,%28,%29,%30,%31,"\
    "%32,%33,%34,%35,%36,%37,%38,%39,%40,%41,%42,%43,%44,%45,%46,%47"
#define ACC0 ACC00 ",%48,%49,%50,%51,%52,%53,%54,%55,%56,%57,%58,%59,%60,%61,%62,%63"
#define ACC1 "%64,%65,%66,%67,%68,%69,%70,%71,%72,%73,%74,%75,%76,%77,%78,%79,%80,%81,%82,%83,%84,%85,%86,%87,%88,%89,%90,%91,%92,%93,%94,%95,"\
    "%96,%97,%98,%99,%100,%101,%102,%103,%104,%105,%106,%107,%108,%109,%110,%111"
#define ACC48 "{" ACC00 "}"
#define ACC64 "{" ACC0 "}"
#define ACC112 "{" ACC0 "," ACC1 "}"
#define ACC128 "{" ACC0 "," ACC1 ",%112,%113,%114,%115,%116,%117,%118,%119,%120,%121,%122,%123,%124,%125,%126,%127}"
#define MMA_K16(shape, acc, keep, hb, sb) \
    "mov.b64 da, {la, 0x40000040};\nmov.b64 db, {lb, " hb "};\n" \
    "wgmma.mma_async.sync.aligned." shape ".f32.bf16.bf16 " acc ", da, db, " keep ", 1, 1, 0, 1;\n" \
    "add.u32 la, la, 2;\nadd.s32 lb, lb, " sb ";\n"
#define MMA_STEP_B(shape, acc, a, b, off, keep, hb, sb, sb2) \
    "{\n.reg .pred p, q;\n.reg .b32 la, lb;\n.reg .b64 da, db;\nsetp.ne.b32 p, " keep ", 0;\nsetp.eq.b32 q, 0, 0;\n" \
    "add.u32 la, " a ", " off ";\nadd.u32 lb, " b ", " off ";\nwgmma.fence.sync.aligned;\n" \
    MMA_K16(shape, acc, "p", hb, sb) MMA_K16(shape, acc, "q", hb, sb2) MMA_K16(shape, acc, "q", hb, sb) \
    MMA_K16(shape, acc, "q", hb, sb) "wgmma.commit_group.sync.aligned;\n}"
#define MMA_STEP(shape, acc, a, b, off, keep) MMA_STEP_B(shape, acc, a, b, off, keep, "0x40000040", "128", "128")

__device__ __forceinline__ void mma_step(float (&d)[128], uint32_t da, uint32_t db, uint32_t off, int keep) {
    asm volatile(MMA_STEP("m64n256k16", ACC128, "%128", "%129", "%130", "%131")
                 : R64(d, 0), R64(d, 64) : "r"(da), "r"(db), "r"(off), "r"(keep) : "memory");
}
__device__ __forceinline__ void mma_rank(float (&d)[128], uint32_t a0, uint32_t a1, uint32_t db) {
    asm volatile("{\n.reg .pred q;\n.reg .b64 db;\nsetp.eq.b32 q, 0, 0;\nmov.b64 db, {%131, 0x40000040};\nwgmma.fence.sync.aligned;\n"
                 "wgmma.mma_async.sync.aligned.m64n256k16.f32.bf16.bf16 " ACC128 ", {%128, %129, %130, %130}, db, q, 1, 1, 1;\n}"
                 : R64(d, 0), R64(d, 64) : "r"(a0), "r"(a1), "r"(0), "r"(db) : "memory");
}
__device__ __forceinline__ void mma_step224(float (&d)[128], uint32_t da, uint32_t db, uint32_t off, int keep) {
    asm volatile(MMA_STEP("m64n224k16", ACC112, "%112", "%113", "%114", "%115")
                 : R64(d, 0), R32(d, 64), R8(d, 96), R8(d, 104) : "r"(da), "r"(db), "r"(off), "r"(keep) : "memory");
}
__device__ __forceinline__ void mma_step(float (&d)[64], uint32_t da, uint32_t db, uint32_t off, int keep) {
    asm volatile(MMA_STEP("m64n128k16", ACC64, "%64", "%65", "%66", "%67")
                 : R64(d, 0) : "r"(da), "r"(db), "r"(off), "r"(keep) : "memory");
}
__device__ __forceinline__ void mma_step96(float (&d)[64], uint32_t da, uint32_t db, uint32_t off) {
    asm volatile(MMA_STEP("m64n96k16", ACC48, "%48", "%49", "%50", "1")
                 : R32(d, 0), R8(d, 32), R8(d, 40) : "r"(da), "r"(db), "r"(off) : "memory");
}
__device__ __forceinline__ void mma_step_tail(float (&d)[128], uint32_t da, uint32_t b, uint32_t off, int keep) {
    asm volatile(MMA_STEP_B("m64n256k16", ACC128, "%128", "%129", "%130", "%131", "0x80000040", "128", "-96")
                 : R64(d, 0), R64(d, 64) : "r"(da), "r"((b & 0x3FFFF) >> 4 | 256 << 16), "r"(off), "r"(keep) : "memory");
}

__device__ __forceinline__ uint32_t pack_bf16(float lo, float hi) {
    uint32_t r; asm("cvt.rn.bf16x2.f32 %0, %1, %2;" : "=r"(r) : "f"(hi), "f"(lo)); return r;
}
__device__ __forceinline__ float bf_lo(uint32_t v) { return __uint_as_float(v << 16); }
__device__ __forceinline__ float bf_hi(uint32_t v) { return __uint_as_float(v & 0xffff0000u); }
__device__ __forceinline__ float round_bf16(float v) { return bf_lo(pack_bf16(v, 0.f)); }
__device__ __forceinline__ uint32_t mul_bf16x2(uint32_t a, uint32_t b) {
    uint32_t r; asm("mul.rn.bf16x2 %0, %1, %2;" : "=r"(r) : "r"(a), "r"(b)); return r;
}
__device__ __forceinline__ uint32_t sub_bf16x2(uint32_t a, uint32_t b) {
    uint32_t r; asm("sub.rn.bf16x2 %0, %1, %2;" : "=r"(r) : "r"(a), "r"(b)); return r;
}
__device__ __forceinline__ uint32_t mul2_bf16x2(uint32_t a, uint32_t hi, uint32_t lo) {
    uint32_t r; asm("fma.rn.bf16x2 %0, %1, %2, %3;" : "=r"(r) : "r"(a), "r"(hi), "r"(mul_bf16x2(a, lo))); return r;
}
__device__ __forceinline__ float tanh_fast(float x) { float r; asm("tanh.approx.f32 %0, %1;" : "=f"(r) : "f"(x)); return r; }
__device__ __forceinline__ float gelu_tanh(float g) {
    float t = fmaf(g * g, 0.044715f * 0.7978845608f, 0.7978845608f) * g;
    float hg = 0.5f * g;
    return fmaf(hg, tanh_fast(t), hg);
}
__device__ __forceinline__ uint32_t geglu2(uint32_t g2, uint32_t u2) {
    return mul_bf16x2(pack_bf16(gelu_tanh(bf_lo(g2)), gelu_tanh(bf_hi(g2))), u2);
}
__device__ __forceinline__ float silu(float d) {
    float hd = 0.5f * d;
    return fmaf(hd, tanh_fast(hd), hd);
}
__device__ __forceinline__ float ex2_fast(float x) { float r; asm("ex2.approx.ftz.f32 %0, %1;" : "=f"(r) : "f"(x)); return r; }
__device__ __forceinline__ void unpack8(uint4 v, float (&f)[8]) {
    f[0] = bf_lo(v.x); f[1] = bf_hi(v.x); f[2] = bf_lo(v.y); f[3] = bf_hi(v.y);
    f[4] = bf_lo(v.z); f[5] = bf_hi(v.z); f[6] = bf_lo(v.w); f[7] = bf_hi(v.w);
}
template <int N> __device__ __forceinline__ void fence_regs(float (&d)[N]) {
#pragma unroll
    for (int i = 0; i < N; i++) asm volatile("" : "+f"(d[i]) :: "memory");
}

__device__ __forceinline__ float rcp_fast(float x) { float r; asm("rcp.approx.ftz.f32 %0, %1;" : "=f"(r) : "f"(x)); return r; }
__device__ __forceinline__ float sqrt_fast(float x) { float r; asm("sqrt.approx.ftz.f32 %0, %1;" : "=f"(r) : "f"(x)); return r; }
__device__ __forceinline__ uint32_t max_bf16x2(uint32_t a, uint32_t b) {
    uint32_t r; asm("max.bf16x2 %0, %1, %2;" : "=r"(r) : "r"(a), "r"(b)); return r;
}
__device__ __forceinline__ uint32_t transpose8(uint32_t a) {
    uint32_t r; asm volatile("movmatrix.sync.aligned.m8n8.trans.b16 %0, %1;" : "=r"(r) : "r"(a)); return r;
}
__device__ __forceinline__ void mma_sync(uint32_t* d, const uint32_t* a, uint32_t b0, uint32_t b1, const uint32_t* c) {
    asm volatile("mma.sync.aligned.m16n8k16.row.col.f32.bf16.bf16.f32 {%0,%1,%2,%3}, {%4,%5,%6,%7}, {%8,%9}, {%10,%11,%12,%13};"
        : "=r"(d[0]), "=r"(d[1]), "=r"(d[2]), "=r"(d[3])
        : "r"(a[0]), "r"(a[1]), "r"(a[2]), "r"(a[3]), "r"(b0), "r"(b1), "r"(c[0]), "r"(c[1]), "r"(c[2]), "r"(c[3]));
}
template <int N> struct Floats {
    float f[N];
    __device__ __forceinline__ Floats() {}
    __device__ __forceinline__ Floats(const uint32_t* p) {
#pragma unroll
        for (int i = 0; i < N; i++) asm("mov.b32 %0, %1;" : "=f"(f[i]) : "r"(p[i]));
    }
    __device__ __forceinline__ void put(uint32_t* p) const {
#pragma unroll
        for (int i = 0; i < N; i++) asm("mov.b32 %0, %1;" : "=r"(p[i]) : "f"(f[i]));
    }
    __device__ __forceinline__ float& operator[](int i) { return f[i]; }
};
__device__ __forceinline__ uint32_t fresh_tid() { uint32_t r; asm volatile("mov.u32 %0, %%tid.x;" : "=r"(r)); return r; }
template <typename T> __device__ __forceinline__ T uniform(T v) { return __shfl_sync(0xffffffffu, v, 0); }

__device__ __forceinline__ void tail_gemm(const Params& prm, uint32_t base, uint32_t t0, unsigned epoch, int grp, int warp, int lane) {
    const uint32_t full = base + BAR_OFF, empty = full + 320, sig = full + 192, dep = full + 256;
    unsigned* const flags = prm.flags + grp * 128;
    if (warp >= 8) asm volatile("setmaxnreg.dec.sync.aligned.u32 %0;" :: "n"(AUX_REGS));
    if (warp == 8) {
        if (elect_one()) { prefetch_map(&prm.xn); prefetch_map(&prm.wu_tail); prefetch_map(&prm.a2); prefetch_map(&prm.wd_tail); }
        auto load_w = [&](int i, const CUtensorMap* m, int k) {
            asm volatile("{\n.reg .pred e;\nelect.sync _|e, 0xffffffff;\n"
                "@e cp.async.bulk.tensor.5d.shared::cluster.global.mbarrier::complete_tx::bytes [%0], [%2, {%4, %4, %3, %4, %4}], [%1];\n"
                "@e mbarrier.arrive.expect_tx.shared::cta.b64 _, [%1], %5;\n}"
                :: "r"(base + (i & 3) * G1_STAGE_BYTES + A_BYTES), "r"(full + (i & 3) * 8), "l"(m), "r"(k), "r"(0),
                   "n"(G1_STAGE_BYTES) : "memory");
        };
        while ((uint32_t)clock() - t0 < TW0) {}
#pragma unroll 1
        for (int i = 0; i < 4; i++) load_w(i, &prm.wu_tail, i * 2);
        flag_wait<true>(flags + F_LN * 512 + (lane & 3) * 32, epoch * CNT_LN);
        fence_proxy_async();
        TRACE(62);
#pragma unroll 1
        for (int p = 0, i = 0; p < 8; p++) {
            const bool first = p < 4;
            if (p == 4) mbar_wait_warp(dep + 8, 0);
#pragma unroll 1
            for (int k = 0; k < (first ? TAIL1 : TAIL2); k++, i++) {
                if (i == 8) mbar_wait_warp(dep, 0);
                mbar_wait_warp(empty + (i & 3) * 8, ~i >> 2 & 1);
                asm volatile("{\n.reg .pred e;\nelect.sync _|e, 0xffffffff;\n"
                    "@e cp.async.bulk.tensor.3d.shared::cluster.global.mbarrier::complete_tx::bytes [%0], [%2, {%3, %4, %5}], [%1];\n}"
                    :: "r"(base + (i & 3) * G1_STAGE_BYTES), "r"(full + (i & 3) * 8), "l"(first ? &prm.xn : &prm.a2),
                       "r"((first ? 0 : DM) + k * 64), "r"(grp * 256 + (p & 3) * 64), "r"(0) : "memory");
                if (i >= 4) load_w(i, first ? &prm.wu_tail : &prm.wd_tail, first ? k * 2 : k * 8);
            }
        }
    } else if (warp == 9) {
#pragma unroll 1
        for (int j = 0; j < 2; j++) {
            flag_wait<true>(flags + (F_LN2 + j) * 512 + (lane & 3) * 32, epoch * CNT_LN);
            fence_proxy_async();
            __syncwarp();
            if (lane == 0) mbar_arrive(dep + j * 8);
        }
    } else if (warp == 10 && lane == 0) {
#pragma unroll 1
        for (int p = 0; p < 8; p++) {
            mbar_wait(sig + p * 8, 0);
            flag_add(flags + F_TAIL * 512 + (p & 3) * 32);
            TRACE_S(50, p, 3); TRACE_S(51, p, 7);
        }
        prm.epoch[blockIdx.x * 16] = epoch;
        TRACE_DUMP();
    }
    if (warp >= 8) return;
    asm volatile("setmaxnreg.inc.sync.aligned.u32 %0;" :: "n"(CONSUMER_REGS) : "memory");
    const uint32_t da = desc_a(base + (warp >> 2) * 8192);
    uint4* out = prm.tail + grp * 2048 - 512 + threadIdx.x;
    float acc[128];
    uint32_t pk[64];
    int i = 0;
    auto release = [&]() { if ((threadIdx.x & 127) == 0) mbar_arrive(empty + (i - 1 & 3) * 8); };
    auto store = [&](int j) {
        asm volatile("st.global.v4.u32 [%0], {%1,%2,%3,%4};" :: "l"(out + j / 2 * 8192 + j % 2 * 256),
                     "r"(pk[4 * j]), "r"(pk[4 * j + 1]), "r"(pk[4 * j + 2]), "r"(pk[4 * j + 3]) : "memory");
    };
    auto step = [&](int k, int left) {
        mbar_wait(full + (i & 3) * 8, i >> 2 & 1);
        TRACE_S(45, warp * 128 + i, 0);
        if (warp >= 4 && left == TSK) asm volatile("bar.sync 1, 256;" ::: "memory");
        mma_step_tail(acc, da, base + A_BYTES, (i & 3) * (G1_STAGE_BYTES / 16), k);
        if (warp < 4 && left == 1) asm volatile("bar.arrive 1, 256;" ::: "memory");
        wg_wait<1>();
        if (k) release();
        i++;
    };
#pragma unroll
    for (int j = 0; j < 128; j++) asm volatile("mov.b32 %0, 0;" : "=f"(acc[j]));
#pragma unroll
    for (int j = 0; j < 64; j++) asm volatile("mov.b32 %0, 0;" : "=r"(pk[j]));
#pragma unroll 1
    for (int p = 0; p < 8; p++) {
#pragma unroll
        for (int k = 0; k < TST; k++) {
            step(k, 0);
            if (p) {
#pragma unroll
                for (int j = k * 16 / TST; j < (k + 1) * 16 / TST; j++) store(j);
                if (k == TST - 1) { __syncwarp(); if (lane == 0) mbar_arrive(sig + p * 8 - 8); }
            }
        }
#pragma unroll 1
        for (int left = (p < 4 ? TAIL1 : TAIL2) - TST; left > 0; left--) step(1, left);
        wg_wait<0>();
        fence_regs(acc);
        release();
        TRACE_S(48, p + warp * 8, 0); TRACE_S(49, p + warp * 8, 35); TRACE_S(52, p + warp * 8, 39);
#pragma unroll
        for (int j = 0; j < 64; j++) pk[j] = pack_bf16(acc[2 * j], acc[2 * j + 1]);
        out += p == 4 ? NGEMM * 512 - 1536 : 512;
    }
#pragma unroll
    for (int j = 0; j < 16; j++) store(j);
    __syncwarp();
    TRACE_S(58, warp, 4);
    if (lane == 0) mbar_arrive(sig + 56);
}

__device__ __forceinline__ int gate_col(int t, int nslot) { return t == 2 ? 960 + nslot * 64 : max(t * 1024 - 1536, 0) + nslot * 128; }

struct Role {
    int rank, role, mblk, nslot;
    __device__ __forceinline__ Role() {
        uint32_t id;
        asm volatile("mov.u32 %0, %%ctaid.x;" : "=r"(id));
        const uint32_t cl = id / 2;
        rank = id & 1;
        role = pick(cl < 4, 32 + cl * 8, cl - 8 + max(4u, (cl - 1) * 37 >> 8)) * 2 + rank;
        mblk = role & 15; nslot = role >> 4;
    }
};

__global__ void __cluster_dims__(2, 1, 1) __launch_bounds__(384, 1)
fused_kernel(const __grid_constant__ Params prm) {
    TRACE_GET(c0);
    const uint32_t base = smem_u32(smem_raw) & ~1023u;
    const uint32_t bars = base + BAR_OFF;
    auto full1 = [&](int s) { return bars + s * 8; };
    auto empty1 = [&](int s) { return bars + 32 + s * 8; };
    auto full2 = [&](int s) { return bars + 64 + s * 8; };
    auto empty2 = [&](int s) { return bars + 128 + s * 8; };
    const uint32_t sig_bar = bars + 192, dep_bar = bars + 256, cs_bar = bars + 304, fold_bar = bars + 320, x_bar = bars + 352;
    const uint32_t halo_bar = dep_bar + 32;
    const uint32_t stats = bars + 1536;
    auto stage2 = [&](int q) { return base + q * G2_STAGE_BYTES; };
    const uint32_t aux = base + AUX_OFF;

    asm volatile("{\n.reg .pred p;\nsetp.eq.u32 p, %1, 0;\n@p mbarrier.init.shared::cta.b64 [%0], 1;\n"
        "fence.mbarrier_init.release.cluster;\nbarrier.cluster.arrive.relaxed.aligned;\n}" :: "r"(bars), "r"(threadIdx.x) : "memory");
    const int warp = __shfl_sync(0xffffffffu, threadIdx.x >> 5, 0);
    auto cluster_wait = []() { asm volatile("barrier.cluster.wait.acquire.aligned;" ::: "memory"); };
    if ((warp | (blockIdx.x & NGEMM)) == 8) {
        const Role r;
        asm volatile("{\n.reg .pred e;\nelect.sync _|e, 0xffffffff;\n"
            "@e prefetch.tensormap [%0];\n@e prefetch.tensormap [%1];\n}" :: "l"(&prm.x), "l"(&prm.wg + r.rank) : "memory");
        cluster_wait();
        load_stage1(base, base + A_BYTES + r.rank * 16384, full1(0), &prm.x, &prm.wg + r.rank, &prm.wg + r.rank, 0, r.mblk * 64,
                    r.nslot * 128, r.nslot * 128 + 64, 0, stream_policy());
    } else {
        cluster_wait();
    }
    const uint32_t t0 = clock();
    asm volatile("{\n.reg .pred e, q;\nelect.sync _|e, 0xffffffff;\nsetp.ne.and.u32 q, %2, 0, e;\n"
        "@q mbarrier.init.shared::cta.b64 [%0], %1;\n@e mbarrier.init.shared::cta.b64 [%0 + 8], %1;\n"
        "@e mbarrier.init.shared::cta.b64 [%0 + 16], %1;\n@e mbarrier.init.shared::cta.b64 [%0 + 24], %1;\n"
        "fence.mbarrier_init.release.cluster;\nbarrier.cluster.arrive.relaxed.aligned;\n}"
        :: "r"(bars + warp * 32), "r"(1 << (0x10fa08 >> warp * 2 & 3)), "r"(warp) : "memory");
    const int lane = threadIdx.x & 31;
    const Role me;
    const int rank = me.rank, role = me.role, mblk = me.mblk, nslot = me.nslot;
    const CUtensorMap* const w0 = &prm.wg + rank;

    if (blockIdx.x >= NGEMM) {
        if (warp == 9) { TRACE_CLEAR(); TRACE_GT(0); TRACE_PUT(1, c0); }
        cluster_wait();
        const uint32_t seen = __ldcg(prm.epoch + blockIdx.x * 16);
        tail_gemm(prm, base, t0, seen + 1, blockIdx.x - NGEMM, warp, lane);
    } else if (warp < 8) {
        asm volatile("setmaxnreg.inc.sync.aligned.u32 %0;" :: "n"(CONSUMER_REGS));
        const int wg = __shfl_sync(0xffffffffu, threadIdx.x >> 7, 0);
        const int cw = threadIdx.x >> 5;
        const int tid = threadIdx.x & 127;
        float acc[128];
        uint32_t pk[64];
#pragma unroll
        for (int i = 0; i < 64; i++) asm volatile("mov.b32 %0, 0;" : "=r"(pk[i]));
#pragma unroll
        for (int i = 0; i < 128; i++) asm volatile("mov.b32 %0, 0;" : "=f"(acc[i]));
        cluster_wait();

        auto row0 = [&](uint32_t id) { return mblk * 128 + (id & 96) + wg; };
        __nv_bfloat16* optr = prm.pxn + (mblk * 128 + nslot * 16 + cw * 2) * DM + lane * 8;
        const uint32_t da = desc_a(base + wg * 8192), db = desc_b(base + A_BYTES);
        auto release = [&](uint32_t bar) { if (tid < 2) mbar_arrive_cluster(bar, tid); };
        auto up = [](int i) { return 32 + (i & 24) + (i & 3) * 2 + (i >> 2 & 1); };
        auto store_pk = [&](__nv_bfloat16* p, int j) {
            asm volatile("st.global.v4.u32 [%0], {%1,%2,%3,%4};"
                         :: "l"(p), "r"(pk[4 * j]), "r"(pk[4 * j + 1]), "r"(pk[4 * j + 2]), "r"(pk[4 * j + 3]) : "memory");
        };
        auto chunk_geglu = [&](int j) {
#pragma unroll
            for (int i = 4 * j; i < 4 * j + 4; i++) pk[i] = geglu2(pk[i], pk[up(i)]);
            store_pk(optr + (j & 1) * 16 * K2 + (j >> 1) * 32, j);
        };
        auto signal_stores = [&](int p) { __syncwarp(); if (lane == 0) mbar_arrive(sig_bar + p * 8); };

        auto chunk_ln = [&](int k) {
            Floats<6> mo(pk + 32);
            if (k == 0) {
                const uint4* xp = reinterpret_cast<const uint4*>(prm.px + (optr - prm.pxn));
                pk[38] = __ldcg(prm.epoch + blockIdx.x * 16 + 2);
#pragma unroll
                for (int i = 0; i < 8; i++) {
                    const uint4 v = ldg_stream(xp + i * 32, stream_policy());
                    pk[4 * i] = v.x; pk[4 * i + 1] = v.y; pk[4 * i + 2] = v.z; pk[4 * i + 3] = v.w;
                }
            } else if (k >= LN_STEP && k < LN_STEP + 3) {
                if (k == LN_STEP) {
                    mo[0] = bf_lo(uniform(pk[0])); mo[1] = bf_lo(uniform(pk[16]));
                    mo[2] = mo[3] = mo[4] = mo[5] = 0.f;
                }
#pragma unroll
                for (int i = (k - LN_STEP) * 11; i < (k - LN_STEP) * 11 + 11 && i < 32; i++) {
                    const int r = i & 1;
                    const uint32_t w = pk[r * 16 + i / 2];
                    const float lo = bf_lo(w) - mo[r], hi = bf_hi(w) - mo[r];
                    mo[2 + r] += lo + hi;
                    mo[4 + r] = fmaf(hi, hi, fmaf(lo, lo, mo[4 + r]));
                }
                mo.put(pk + 32);
            } else if (k == LN_STEP + 3) {
                const bool second = lane & 16;
                float m1 = (second ? mo[3] : mo[2]) + __shfl_xor_sync(0xffffffffu, second ? mo[2] : mo[3], 16);
                float m2 = (second ? mo[5] : mo[4]) + __shfl_xor_sync(0xffffffffu, second ? mo[4] : mo[5], 16);
#pragma unroll
                for (int o = 8; o > 0; o >>= 1) {
                    m1 += __shfl_xor_sync(0xffffffffu, m1, o);
                    m2 += __shfl_xor_sync(0xffffffffu, m2, o);
                }
                m1 *= 1.f / DM;
                const float var = fmaxf(fmaf(-m1, m1, m2 * (1.f / DM)), 0.f);
                const float mean = round_bf16((second ? mo[1] : mo[0]) + m1);
                const float inv = rcp_fast(round_bf16(sqrt_fast(round_bf16(round_bf16(var) + 1e-5f))));
                if ((lane & 15) == 0) st_tagged(prm.stats + (uint32_t)(optr - prm.pxn) / DM + second, -mean, inv, 2 - (pk[38] & 1));
                const uint32_t split = pack_bf16(inv - round_bf16(inv), inv);
#pragma unroll
                for (int r = 0; r < 2; r++) {
                    const uint32_t f = __shfl_sync(0xffffffffu, split, r * 16);
                    pk[32 + 3 * r] = __byte_perm(__shfl_sync(0xffffffffu, __float_as_uint(mean), r * 16), 0, 0x3232);
                    pk[33 + 3 * r] = __byte_perm(f, 0, 0x3232);
                    pk[34 + 3 * r] = __byte_perm(f, 0, 0x1010);
                }
            } else if (k >= LN_STEP + 4 && k < LN_STEP + 8) {
#pragma unroll
                for (int i = k - LN_STEP - 4; i < 8; i += 4) {
                    const uint32_t* n = pk + 32 + i / 4 * 3;
#pragma unroll
                    for (int j = 4 * i; j < 4 * i + 4; j++) pk[j] = mul2_bf16x2(sub_bf16x2(pk[j], n[0]), n[1], n[2]);
                    store_pk(optr + i * 256, i);
                }
                if (k == LN_STEP + 5 || k == LN_STEP + 7) signal_stores(k == LN_STEP + 5 ? 0 : 7);
            } else if (k == FOLD_STEP) {
                mbar_wait(fold_bar, 0);
                const uint32_t id = fresh_tid(), sp = stats + (id & 96) * 8 + (id & 28) * 4 + wg * 8;
                const uint32_t sel = lane & 2 ? 0x4444 : (lane & 1 ? 0x4432 : 0x3232);
                const float2 sa = lds64f(sp), sb = lds64f(sp + 128);
                mma_rank(acc, __byte_perm(__float_as_uint(sa.x), 0, sel), __byte_perm(__float_as_uint(sb.x), 0, sel), desc_b(aux));
                mo[0] = sa.y; mo[1] = sb.y;
                mo.put(pk + 32);
            }
        };

        auto halo = [&]() { const uint32_t id = fresh_tid(); return aux + (id & 96) * 128 + (id & 128) * 16 + (id & 31) * 4; };
        auto put = [&](uint32_t a, uint32_t v0, uint32_t v1) {
            asm volatile("st.shared.u32 [%0], %1;\nst.shared.u32 [%0 + 128], %2;" :: "r"(a + HALO_BYTES), "r"(v0), "r"(v1) : "memory");
        };
        auto get = [&](uint32_t a, uint32_t& v0, uint32_t& v1) {
            asm volatile("ld.shared.u32 %0, [%2];\nld.shared.u32 %1, [%2 + 128];" : "=r"(v0), "=r"(v1) : "r"(a) : "memory");
        };
        auto publish = [&](int p) { asm volatile("fence.proxy.async.shared::cta;" ::: "memory"); signal_stores(p); };
        const uint32_t zero[4] = {0, 0, 0, 0};
        auto meet = [&](int n) {
            if (n == 15 - MEET) asm volatile("{\n.reg .u32 c;\nmov.u32 c, %%clock;\nlop3.b32 c, c, %1, 1, 0x80;\nadd.u32 c, c, %0;\nbar.arrive c, 256;\n}"
                                             :: "r"(2 + wg), "r"((uint32_t)(uintptr_t)optr) : "memory");
        };
        auto mix_qk = [&]() {
            uint32_t c[2][4];
            const uint32_t a = halo();
            if (EREL) { wg_wait<0>(); release(empty1((MIXQ - 1) & 3)); }
            mbar_wait(halo_bar, 0);
#pragma unroll
            for (int n = 0; n < 16; n++) {
                const int b = 1 - n / 8, h = (n & 4) / 2 + n % 2, j = n / 2 % 2;
                uint32_t* const kq = pk + 32 + 8 * h + 4 * j;
                uint32_t* const q = pk + 8 * h + 4 * b;
                mma_sync(j ? q : c[n % 2], kq, q[2 * j], q[2 * j + 1], j ? c[n % 2] : zero);
                if (b) get(a + (h * 2 + j) * 256, kq[1], kq[3]);
                meet(n);
            }
        };
        auto chunk_qk = [&](int k) {
            constexpr float LOG2E = 1.4426950408889634f;
            uint32_t* const l = pk + 32;
            Floats<16> e(pk);
            if (k == KK) {
                const uint32_t a = halo();
#pragma unroll
                for (int i = 0; i < 8; i++) put(a + i * 256, pk[33 + 4 * i], pk[35 + 4 * i]);
                publish(1);
            } else if (k == MIXQ + 1) {
                const uint32_t id = fresh_tid();
                const bool u0 = id % 32 / 4 > id % 4 * 2, u1 = id % 32 / 4 > id % 4 * 2 + 1;
                const uint32_t gone = row0(id) < 2 ? (u0 ? 0xffffu : 0u) | (u1 ? 0xffff0000u : 0u) : 0u;
#pragma unroll
                for (int n = 0; n < 8; n++) {
                    const int b = n % 2;
                    const uint32_t* const c = pk + 4 * n;
                    uint32_t v = pack_bf16(__uint_as_float(pick(u0, c[2 - 2 * b], c[2 * b])), __uint_as_float(pick(u1, c[3 - 2 * b], c[1 + 2 * b])));
                    v = mul2_bf16x2(v, 0x3e353e35u, 0x379e379eu);
                    if (!b) v = v & ~gone | 0xce6ece6eu & gone;
                    l[n] = transpose8(v);
                }
            } else if (k == MIXQ + 2) {
#pragma unroll
                for (int h = 0; h < 4; h++) {
                    uint32_t m = max_bf16x2(__byte_perm(l[2 * h], l[2 * h + 1], 0x5410), __byte_perm(l[2 * h], l[2 * h + 1], 0x7632));
                    m = max_bf16x2(m, __shfl_xor_sync(0xffffffffu, m, 1));
                    m = max_bf16x2(m, __shfl_xor_sync(0xffffffffu, m, 2));
#pragma unroll
                    for (int n = 2 * h; n < 2 * h + 2; n++) {
                        const float f = -LOG2E * (n % 2 ? bf_hi(m) : bf_lo(m));
                        e[2 * n] = ex2_fast(fmaf(bf_lo(l[n]), LOG2E, f));
                        e[2 * n + 1] = ex2_fast(fmaf(bf_hi(l[n]), LOG2E, f));
                    }
                }
                e.put(pk);
            } else if (k == MIXQ + 3) {
                uint32_t p[8];
#pragma unroll
                for (int n = 0; n < 8; n++) {
                    float sum = e[2 * n] + e[2 * n + 1];
                    sum += __shfl_xor_sync(0xffffffffu, sum, 1);
                    sum += __shfl_xor_sync(0xffffffffu, sum, 2);
                    const float r = rcp_fast(sum);
                    p[n] = pack_bf16(e[2 * n] * r, e[2 * n + 1] * r);
                }
                const uint32_t a = aux + 5 * HALO_BYTES + fresh_tid() * 16;
                sts128(a, make_uint4(p[0], p[1], p[2], p[3]));
                sts128(a + 4096, make_uint4(p[4], p[5], p[6], p[7]));
            }
        };
        auto values = [&](int h) { return pk + (h & 2) * 16 + (h & 1) * 8; };
        auto mix_pv = [&]() {
            uint32_t lo[8], hi[8];
            const uint32_t id = fresh_tid();
            const uint32_t keep = (id % 4 * 2 > id % 32 / 4 ? 0xffffu : 0u) | (id % 4 * 2 + 1 > id % 32 / 4 ? 0xffff0000u : 0u);
            const uint4 p0 = lds128(aux + 5 * HALO_BYTES + id * 16), p1 = lds128(aux + 6 * HALO_BYTES + id * 16);
            const uint32_t p[8] = {p0.x, p0.y, p0.z, p0.w, p1.x, p1.y, p1.z, p1.w};
#pragma unroll
            for (int n = 0; n < 8; n++)
                asm volatile("and.b32 %0, %2, %3;\nand.b32 %1, %2, %4;" : "=r"(lo[n]), "=r"(hi[n])
                             : "r"(p[n]), "r"(n % 2 ? keep : ~keep), "r"(n % 2 ? ~keep : keep));
            if (EREL) { wg_wait<0>(); release(empty1((MIXV - 1) & 3)); }
            mbar_wait(halo_bar, 1);
#pragma unroll
            for (int n = 0; n < 16; n++) {
                const int i = (n & 8) / 2 + (n & 2) + (n & 4) / 4;
                mma_sync(pk + 4 * (n ^ 4), pk + 4 * (n ^ 4), lo[i], hi[i], zero);
                meet(n);
            }
        };
        auto chunk_pv = [&](int k) {
            if (k >= VK && k < VK + VN) {
                const uint32_t a = halo();
#pragma unroll
                for (int h = (k - VK) * 4 / VN; h < (k - VK + 1) * 4 / VN; h++) {
                    uint32_t* const w = values(h);
                    uint32_t v[8];
#pragma unroll
                    for (int i = 0; i < 8; i++) v[i] = transpose8(w[h < 2 ? (i & 1) + (i & 2) * 2 + (i & 4) / 2 : (i & 1) * 2 + (i & 2) / 2 + (i & 4)]);
#pragma unroll
                    for (int i = 0; i < 8; i++) w[i] = v[i];
                    put(a + h * 512, w[2], w[3]);
                    put(a + h * 512 + 256, w[6], w[7]);
                }
                if (k == VK + VN - 1) publish(3);
            } else if (k == MIXV - 1) {
                const uint32_t a = halo(), id = fresh_tid();
                optr = prm.pa2 + (size_t)(row0(id) + id % 4 * 4) * K2 + nslot * 128 + (id & 28) * 2;
                mbar_wait(halo_bar, 1);
#pragma unroll
                for (int n = 0; n < 8; n++) {
                    uint32_t* const w = values(n / 2) + n % 2 * 4;
                    w[16] = w[0]; w[17] = w[1];
                    get(a + n * 256, w[18], w[19]);
                }
            } else if (k > MIXV && k <= MIXV + OVS) {
#pragma unroll
                for (int j = 0; j < 8; j++) {
                    if (j * OVS / 8 != k - MIXV - 1) continue;
                    Floats<15> c(pk + j / 2 * 16 + j % 2);
                    asm volatile("st.global.v4.u32 [%0], {%1,%2,%3,%4};"
                                 :: "l"(optr + ((~j & 2) * 8 + j % 2 * 2) * K2 + j / 4 * 64), "r"(pack_bf16(c[0], c[2])),
                                    "r"(pack_bf16(c[4], c[6])), "r"(pack_bf16(c[8], c[10])), "r"(pack_bf16(c[12], c[14])) : "memory");
                }
                if (k == MIXV + OVS) signal_stores(4);
            }
        };

        TRACE_SLOT(tile_slot, 16 + wg * 8);
#pragma unroll 1
        for (int t = 0; t < G1_TILES; t++) {
#pragma unroll
            for (int k = 0; k < G1_KSTEPS; k++) {
                const int s = k & 3;
                TRACE_STEP(t, k, 0);
                uint32_t other = k == MIXV && t == 3 || k == MIXQ && t == 2 ? 3 - wg : 0;
                if (k == MIXV || k == MIXQ) asm volatile("" : "+r"(other));
                mbar_wait(full1(s), (k >> 2) & 1);
                if (k == 0) TRACE_S(12, t, 0);
                TRACE_STEP(t, k, 1);
                if (k == MIXV && t == 3) mix_pv();
                else if (k == MIXQ && t == 2) mix_qk();
                if (k == MIXV || k == MIXQ)
                    asm volatile("{\n.reg .pred p;\nsetp.ne.u32 p, %0, 0;\n@p bar.sync %0, 256;\n}" :: "r"(other) : "memory");
                if (wg == 1 && k == G1_KSTEPS - (t ? G1_SKEW : SK0)) asm volatile("bar.sync 1, 256;" ::: "memory");
                if (k >= G1_KSTEPS - TAIL1 && t == G1_TILES - 1) mma_step224(acc, da, db, s * G1_STAGE_BYTES / 16, k);
                else mma_step(acc, da, db, s * G1_STAGE_BYTES / 16, k);
                if (wg == 0 && k == G1_KSTEPS - 1) asm volatile("bar.arrive 1, 256;" ::: "memory");
                wg_wait<1>();
                if (k > 0 && !(EREL && (k == MIXV && t == 3 || k == MIXQ && t == 2))) release(empty1((k - 1) & 3));
                TRACE_STEP(t, k, 2);
                if (t == 0) chunk_ln(k);
                if (k >= 1 && k <= 8 && ((k <= 4 ? 0x12 : 0x1a) >> t & 1)) {
                    chunk_geglu(k - 1);
                    if (k == 8 && t != 3) signal_stores(t + 1);
                }
                if (t == 2) chunk_qk(k);
                if (t == 3) chunk_pv(k);
                if (k == TLD && t == G1_TILES - 1) {
#pragma unroll
                    for (int i = 0; i < 2; i++) {
                        const uint4 v = ldg_stream(prm.tail + role * 512 + i * 256 + threadIdx.x, stream_policy());
                        pk[16 + 4 * i] = v.x; pk[17 + 4 * i] = v.y; pk[18 + 4 * i] = v.z; pk[19 + 4 * i] = v.w;
                    }
                }
                if (k == TLD + 3 && t == G1_TILES - 1) {
#pragma unroll
                    for (int i = 0; i < 8; i++)
                        asm volatile("shl.b32 %0, %2, 16;\nand.b32 %1, %2, 0xffff0000;" : "=r"(pk[2 * i]), "=r"(pk[2 * i + 1]) : "r"(pk[16 + i]));
                }
                if (k == 13) {
                    const uint32_t id = fresh_tid();
                    optr = prm.pa2 + (size_t)(row0(id) + (id & 28) / 2) * K2 + DM + gate_col(t, nslot) + id % 4 * 8;
                    asm volatile("" : "+l"(optr));
                }
            }
            wg_wait<0>();
            fence_regs(acc);
            release(empty1(3));
            if (t == 0) {
                Floats<2> inv(pk + 32);
#pragma unroll
                for (int i = 0; i < 128; i++) acc[i] *= inv[i / 2 % 2];
                fence_regs(acc);
            }
            if (t == G1_TILES - 1) {
                Floats<16> part(pk);
#pragma unroll
                for (int i = 0; i < 16; i++) acc[112 + i] += part[i];
                fence_regs(acc);
            }
#pragma unroll
            for (int i = 0; i < 64; i++) {
                const int e = i < 32 ? (i & ~7) * 2 + (i & 3) * 4 + (i & 4) / 2 : i * 2;
                pk[i] = pack_bf16(acc[e], acc[e + 1]);
            }
            TRACE_NEXT(tile_slot);
        }

        float accd[64], accs[64];
#pragma unroll
        for (int i = 0; i < 64; i++) accd[i] = 0.f;
#pragma unroll
        for (int u = 0; u < G2_HEAD; u++) {
            const int q = u % G2_STAGES;
            mbar_wait(full2(q), (u / G2_STAGES) & 1);
            mma_step(accd, da, db, q * G2_STAGE_BYTES / 16, u);
            wg_wait<1>();
            if (u > 0) release(empty2((u - 1) % G2_STAGES));
            if (u >= 1) {
                const int j = (u - 1) / 2;
#pragma unroll
                for (int i = 2 * u - 2; i < 2 * u; i++) pk[i] = geglu2(pk[i], pk[up(i)]);
                if (u % 2 == 0) store_pk(optr + (j & 1) * 16 * K2 + (j >> 1) * 32, j);
            }
            if (u == G2_HEAD - 1) signal_stores(6);
        }
        {
            int q = G2_HEAD % G2_STAGES, qp = (G2_HEAD - 1) % G2_STAGES; uint32_t ph = (G2_HEAD / G2_STAGES) & 1;
#pragma unroll 1
            for (int u = G2_HEAD; u < G2_DSTEPS; u++) {
                mbar_wait(full2(q), ph);
                if (G2_NARROW >> u & 1) mma_step96(accd, da, db, q * (G2_STAGE_BYTES / 16));
                else mma_step(accd, da, db, q * (G2_STAGE_BYTES / 16), 1);
                wg_wait<1>();
                release(empty2(qp));
                qp = q;
                if (++q == G2_STAGES) { q = 0; ph ^= 1; }
            }
        }
        TRACE_NEXT(tile_slot);
#pragma unroll
        for (int i = 0; i < 64; i++) accs[i] = 0.f;
        uint32_t gk[32], xr[32];
        const uint32_t xs = aux + cw * 2048;
        const uint32_t xrow = xs + ((lane & 7) + ((lane >> 3) & 1) * 8) * 128;
        auto xaddr = [&](int j) { return xrow + (j >> 2) * 16384 + (((((j & 3) * 2) + (lane >> 4)) ^ (lane & 7)) << 4); };
#pragma unroll
        for (int u = G2_DSTEPS; u < G2_KSTEPS; u++) {
            const int q = u % G2_STAGES, v = u - G2_DSTEPS;
            mbar_wait(full2(q), (u / G2_STAGES) & 1);
            if (G2_SKEW > 0 && wg == 1 && u == G2_KSTEPS - G2_SKEW) asm volatile("bar.sync 1, 256;" ::: "memory");
            mma_step(accs, da, db, q * G2_STAGE_BYTES / 16, v);
            if (G2_SKEW > 0 && wg == 0 && u == G2_KSTEPS - 1) asm volatile("bar.arrive 1, 256;" ::: "memory");
            if (v == TLD2) {
                TRACE_S(32, wg, 0);
                mbar_wait(dep_bar + 24, 0);
                TRACE_S(33, wg, 0);
#pragma unroll
                for (int i = 0; i < 2; i++) {
                    const uint4 w = ldg_stream(prm.tail + (NGEMM + role) * 512 + i * 256 + threadIdx.x, stream_policy());
                    gk[24 + 4 * i] = w.x; gk[25 + 4 * i] = w.y; gk[26 + 4 * i] = w.z; gk[27 + 4 * i] = w.w;
                }
            }
            const int gate = v <= 6 ? v - 1 : v - TLD2 + 3;
            if (gate >= (v <= 6 ? 0 : 6) && gate < 8) {
#pragma unroll
                for (int i = 4 * gate; i < 4 * gate + 4; i++) {
                    const uint32_t d2 = i < 24 ? pack_bf16(accd[2 * i], accd[2 * i + 1])
                                               : pack_bf16(accd[2 * i] + bf_lo(gk[i]), accd[2 * i + 1] + bf_hi(gk[i]));
                    gk[i] = pack_bf16(silu(bf_lo(d2)), silu(bf_hi(d2)));
                }
            }
            if (v == XLD) mbar_wait(x_bar, 0);
            if (v >= XLD && v < XLD + 4) {
#pragma unroll
                for (int j = 2 * (v - XLD); j < 2 * (v - XLD + 1); j++)
                    asm volatile("ldmatrix.sync.aligned.m8n8.x4.shared.b16 {%0,%1,%2,%3}, [%4];"
                                 : "=r"(xr[4 * j]), "=r"(xr[4 * j + 1]), "=r"(xr[4 * j + 2]), "=r"(xr[4 * j + 3])
                                 : "r"(xaddr(j)) : "memory");
            }
            wg_wait<1>();
            if (v == 0) fence_regs(accd);
            if (u - 1 + G2_STAGES < G2_KSTEPS) release(empty2((u - 1) % G2_STAGES));
        }
        __nv_bfloat16* po = prm.pout + (row0(fresh_tid()) + (lane >> 3) * 2) * DM + nslot * 128 + 64 + (lane & 7) * 8;
        uint32_t so = xs + 16384 + (lane >> 3) * 128 + (((lane & 7) ^ (lane >> 3)) << 4);
        const int c0 = uniform(nslot * 128), c1 = uniform(row0(fresh_tid()) >> 1);
        const uint32_t xu = uniform(xs);
        asm volatile("" : "+l"(po), "+r"(so));
        wg_wait<0>();
        fence_regs(accs);
        TRACE_NEXT(tile_slot);
        TRACE_END();
#pragma unroll
        for (int j = 0; j < 8; j++) {
            uint32_t r[4];
#pragma unroll
            for (int i = 0; i < 4; i++) {
                const int e = j * 4 + i;
                asm("fma.rn.bf16x2 %0, %1, %2, %3;" : "=r"(r[i]) : "r"(pack_bf16(accs[2 * e], accs[2 * e + 1])), "r"(gk[e]), "r"(xr[e]));
            }
            asm volatile("stmatrix.sync.aligned.m8n8.x4.shared.b16 [%0], {%1,%2,%3,%4};"
                         :: "r"(xaddr(j)), "r"(r[0]), "r"(r[1]), "r"(r[2]), "r"(r[3]) : "memory");
            if (j == 3)
                asm volatile("{\n.reg .pred e;\nfence.proxy.async.shared::cta;\nbar.warp.sync 0xffffffff;\nelect.sync _|e, 0xffffffff;\n"
                    "@e cp.async.bulk.tensor.3d.global.shared::cta.bulk_group [%0, {%2, %3, %4}], [%1];\n}"
                    :: "l"(&prm.out), "r"(xu), "r"(c0), "r"(c1), "r"(wg) : "memory");
        }
        __syncwarp();
#pragma unroll
        for (int i = 0; i < 4; i++) {
            const uint4 v = lds128((so ^ (i & 1) * 64) + i * 512);
            asm volatile("st.global.v4.u32 [%0], {%1,%2,%3,%4};" :: "l"(po + i * 8 * DM), "r"(v.x), "r"(v.y), "r"(v.z), "r"(v.w) : "memory");
        }
        asm volatile("cp.async.bulk.commit_group;\ncp.async.bulk.wait_group.read 0;" ::: "memory");
        if (tid == 0) { TRACE_NEXT(tile_slot); if (wg == 1) TRACE_GT(13); TRACE_DUMP(); }
    } else {
        asm volatile("setmaxnreg.dec.sync.aligned.u32 %0;" :: "n"(AUX_REGS));
        cluster_wait();
        unsigned* const flags = prm.flags + mblk * 32;
        if (warp == 9) {
            TRACE_CLEAR(); TRACE_GT(0);
            if (lane == 0) {
                const unsigned epoch = __ldcg(prm.epoch + blockIdx.x * 16 + 2) + 1;
                mbar_wait(sig_bar, 0);
                TRACE(11);
                flag_add(flags + F_LN * 512);
                TRACE(42);
                flag_wait(flags + F_LN * 512, epoch * CNT_LN);
                fence_proxy_async();
                mbar_arrive(dep_bar);
                mbar_wait(sig_bar + 56, 0);
                flag_add(flags + F_LN2 * 512);
                flag_wait(flags + F_LN2 * 512, epoch * CNT_LN);
                fence_proxy_async();
                mbar_arrive(dep_bar + 40);
                TRACE(59);
                prm.epoch[blockIdx.x * 16 + 2] = epoch;
#pragma unroll 1
                for (int p = 3; p < 7; p++) {
                    mbar_wait(sig_bar + (p == 3 ? 16 : p * 8), 0);
                    TRACE_S(37, p, 4);
                    flag_add(flags + (p / 2 + 1) * 512);
                    TRACE_S(43, p, 4);
                }
            }
        } else if (warp > 9) {
            const int w = warp - 10;
            const unsigned epoch = __ldcg(prm.epoch + blockIdx.x * 16 + w) + 1;
            const uint32_t tag = 1 + (epoch & 1);
            const uint32_t at = (w ? CB : CA) >> (CIDX) * 4 & 15;
            mbar_wait(empty1(at & 3), 0);
            mbar_wait(empty1(at & 3), at >> 3);
            if (elect_one()) {
                mbar_expect_tx(cs_bar + w * 8, 16384);
                asm volatile("cp.async.bulk.tensor.2d.shared::cluster.global.mbarrier::complete_tx::bytes [%0], [%1, {%3, %5}], [%2];\n"
                    "cp.async.bulk.tensor.2d.shared::cluster.global.mbarrier::complete_tx::bytes [%0 + 8192], [%1, {%4, %5}], [%2];"
                    :: "r"(aux + w * 16384), "l"(w0), "r"(cs_bar + w * 8), "r"(nslot * 128), "r"(nslot * 128 + 64),
                       "r"(((mblk & ~1) + w) * 64) : "memory");
            }
            float cs[8];
#pragma unroll
            for (int d = 0; d < 8; d++) cs[d] = 0.f;
            const uint32_t wa = aux + w * 8192 + (lane >> 3) * 128 + (((lane & 7) ^ (lane >> 3)) << 4);
            uint4 v[9];
            auto fetch = [&](int h, uint32_t off) {
#pragma unroll
                for (int j = 0; j < 4; j++) v[h * 4 + j] = lds128((wa ^ (j & 1) * 64) + off + h * 2048 + j * 512);
            };
            auto add = [&](int h) {
#pragma unroll
                for (int j = 0; j < 4; j++) {
                    float f[8];
                    unpack8(v[h * 4 + j], f);
#pragma unroll
                    for (int d = 0; d < 8; d++) cs[d] += f[d];
                }
            };
            if (CST) { mbar_wait(empty1(CST & 3), 0); mbar_wait(empty1(CST & 3), CST >> 3); }
            mbar_wait(cs_bar, 0);

            fetch(0, 0);
#pragma unroll 1
            for (int i = 0; i < 4; i++) {
                fetch(1, (i >> 1) * 16384 + (i & 1) * 4096);
                add(0);
                if (i == 1) mbar_wait(cs_bar + 8, 0);
                fetch(0, (i + 1 & 2) * 8192 + (~i & 1) * 4096);
                add(1);
            }
#pragma unroll
            for (int d = 0; d < 4; d++)
                cs[d] = (lane & 16 ? cs[d + 4] : cs[d]) + __shfl_xor_sync(0xffffffffu, lane & 16 ? cs[d] : cs[d + 4], 16);
#pragma unroll
            for (int d = 0; d < 2; d++)
                cs[d] = (lane & 8 ? cs[d + 2] : cs[d]) + __shfl_xor_sync(0xffffffffu, lane & 8 ? cs[d] : cs[d + 2], 8);
            st_tagged(prm.colsum + (nslot * 2 + rank) * 1024 + (mblk >> 1) * 128 + w * 64 + (lane & 7) * 8 + (lane >> 3) * 2,
                      cs[0], cs[1], tag);

#pragma unroll
            for (int m = 0; m < 9; m++) v[m] = make_uint4(0, 0, 0, 0);
            const float* parts = prm.colsum + (nslot * 2 + (lane >> 4)) * 1024 + w * 64 + (lane & 15) * 4;
            const float* const rows = &prm.stats[mblk * 128 + w * 64 + lane * 2].x;
#pragma unroll 1
            for (int spins = 0; spins < (1 << 16); spins++) {
                bool missing = false;
                asm volatile("" : "+l"(parts));
#pragma unroll
                for (int m = 0; m < 9; m++) {
                    if (untagged(v[m], tag)) {
                        missing = true;
                        v[m] = ld_relaxed(m < 8 ? parts + m * 128 : rows);
                    }
                }
                if (!missing) break;
            }
            float4 c = make_float4(0.f, 0.f, 0.f, 0.f);
#pragma unroll
            for (int m = 0; m < 8; m++) {
                c.x += __uint_as_float(v[m].x ^ tag); c.y += __uint_as_float(v[m].y ^ tag);
                c.z += __uint_as_float(v[m].z ^ tag); c.w += __uint_as_float(v[m].w ^ tag);
            }
            sts128(stats + w * 512 + lane * 16, make_uint4(v[8].x ^ tag, v[8].y ^ tag, v[8].z ^ tag, v[8].w ^ tag));
            const uint32_t ca = aux + w * 8192 + (lane >> 4) * 16384 + (lane & 15) * 8;
#pragma unroll
            for (int r = 0; r < 3; r++) {
                const uint32_t lo = pack_bf16(c.x, c.y), hi = pack_bf16(c.z, c.w);
                sts64f((ca ^ r * 16) + r * 128, __uint_as_float(lo), __uint_as_float(hi));
                c.x -= bf_lo(lo); c.y -= bf_hi(lo); c.z -= bf_lo(hi); c.w -= bf_hi(hi);
            }
            asm volatile("fence.proxy.async.shared::cta;" ::: "memory");
            __syncwarp();
            if (lane == 0) {
                mbar_arrive(fold_bar);
                prm.epoch[blockIdx.x * 16 + w] = epoch;
                if (w == 0) {
                    TRACE_S(35, w, 0);
                    flag_wait(flags + F_TAIL * 512, epoch * 2 - 1);
                    mbar_arrive(x_bar + 8);
                    flag_wait(flags + F_FIRST * 512, epoch * CNT_FIRST);
                    flag_wait(flags + F_EARLY * 512, epoch * CNT_EARLY);
                    fence_proxy_async(); mbar_arrive(dep_bar + 8);
                    flag_wait(flags + F_LATE * 512, epoch * CNT_LATE);
                    fence_proxy_async(); mbar_arrive(dep_bar + 16);
                    flag_wait(flags + F_TAIL * 512, epoch * 2);
                    mbar_arrive(dep_bar + 24);
                } else {
#pragma unroll 1
                    for (int j = 0; j < 2; j++) {
                        uint8_t* const h = prm.halo + (j * NGEMM + role) * HALO_BYTES;
                        unsigned* const f = prm.flags + F_HALO * 512 + role * 32;
                        mbar_wait(sig_bar + 8 + j * 16, 0);
                        TRACE_S(38, j, 0); TRACE_S(9, j, 1);
                        asm volatile("cp.async.bulk.global.shared::cta.bulk_group [%0], [%1], %2;\n"
                            "cp.async.bulk.commit_group;\ncp.async.bulk.wait_group 0;"
                            :: "l"(h + HALO_BYTES), "r"(aux + 4 * HALO_BYTES), "n"(HALO_BYTES) : "memory");
                        fence_proxy_async();
                        TRACE_S(39, j, 0); TRACE_S(10, j, 1);
                        flag_add(f);
                        TRACE_S(40, j, 0); TRACE_S(34, j, 1);
                        if (mblk) flag_wait(f - 32, epoch * 2 - 1 + j);
                        fence_proxy_async();
                        TRACE_S(41, j, 0); TRACE_S(36, j, 1);
                        mbar_expect_tx(halo_bar, HALO_BYTES);
                        asm volatile("cp.async.bulk.shared::cluster.global.mbarrier::complete_tx::bytes [%0], [%1], %2, [%3];"
                            :: "r"(aux), "l"(mblk ? h : prm.halo), "n"(HALO_BYTES), "r"(halo_bar) : "memory");
                    }
                }
            }
        } else {
#pragma unroll
            for (int k = 1; k < G1_STAGES; k++) {
                const uint32_t sa = base + k * G1_STAGE_BYTES;
                if (PACE0 + PACE) while ((uint32_t)clock() - t0 < (k == 3 ? PACE3 : PACE0 + (k - 1) * PACE)) {}
                load_stage1(sa, sa + A_BYTES + rank * 16384, full1(k), &prm.x, w0, w0, k * 64, mblk * 64, nslot * 128,
                            nslot * 128 + 64, 0, stream_policy());
            }
            if (elect_one()) {
                prefetch_map(&prm.xn); prefetch_map(&prm.wqkv);
                prefetch_map(&prm.a2); prefetch_map(&prm.wo); prefetch_map(&prm.wd); prefetch_map(&prm.out);
            }
            auto load_x = [&]() {
                if (elect_one()) {
                    mbar_expect_tx(x_bar, 32768);
                    tma_3d(aux, &prm.x, x_bar, nslot * 128, mblk * 64, 0, stream_policy());
                    tma_3d(aux + 16384, &prm.x, x_bar, nslot * 128 + 64, mblk * 64, 0, stream_policy());
                }
                __syncwarp();
            };
            uint32_t ph = 0;
#pragma unroll 1
            for (int t = 0; t < G1_TILES; t++) {
                const int col1 = (t == 1 ? rank * DM + nslot * 128 : gate_col(t, nslot)) + 64;
                const int col0 = t == 2 ? 2 * DM + nslot * 128 + rank * 64 : col1 - 64;
                if (t == 1) { TRACE_PUT(1, c0); TRACE_PUT(2, t0); TRACE(14); mbar_wait_warp(dep_bar, 0); TRACE(3); }
#pragma unroll 1
                for (int k = t ? 0 : G1_STAGES; k < G1_KSTEPS; k++) {
                    const int s = k & 3;
                    if (t == 1 && k == 8) mbar_wait_warp(dep_bar + 40, 0);
                    if (t * 16 + k == 64 + TLD) { TRACE(61); mbar_wait_warp(x_bar + 8, 0); TRACE(63); }
                    if (t * 16 + k == (PFK)) {
                        asm volatile("{\n.reg .pred e;\nelect.sync _|e, 0xffffffff;\n"
                            "@e cp.async.bulk.prefetch.tensor.5d.L2.global [%0, {%1, %4, %4, %4, %3}];\n"
                            "@e cp.async.bulk.prefetch.tensor.5d.L2.global [%0, {%2, %4, %4, %4, %3}];\n}"
                            :: "l"(&prm.wd), "r"(nslot * 128), "r"(nslot * 128 + 64), "r"((mblk + TAIL2) * 2), "r"(0) : "memory");
                    }
                    mbar_wait_warp(empty1(s), ph);
                    const uint32_t sa = base + s * G1_STAGE_BYTES;
                    load_stage1(sa, sa + A_BYTES + rank * 16384, full1(s), t ? &prm.xn : &prm.x, t == 1 || t == 2 ? &prm.wqkv : w0,
                                t == 1 ? &prm.wqkv : w0, (k + (t >> 2) * TAIL1 & 15) * 64, mblk * 64, col0, col1, t & 3,
                                stream_policy());
                    if (s == 3) ph ^= 1;
                    if (t * 16 + k == (XK)) load_x();
                }
            }
            TRACE(4);
            mbar_wait_warp(dep_bar + 8, 0);
            TRACE(5);
            int q = 0, narrow = 0; uint32_t ph2 = 1;
#pragma unroll 1
            for (int u = 0; u < G2_KSTEPS; u++) {
                if (u == G2_LATE) { TRACE(6); mbar_wait_warp(dep_bar + 16, 0); TRACE(7); }
                const uint32_t sa = stage2(q);
                const bool down = u < G2_DSTEPS;
                const int k = !down ? u - G2_DSTEPS : (G2_NARROW >> u & 1 ? narrow++ : u + TAIL2 - narrow);
                mbar_wait_warp(u < G2_STAGES ? empty1((u * 2 + 1) / 3) : empty2(q), u < G2_STAGES ? ph : ph2);
                load_stage2(sa, sa + A_BYTES + rank * 8192, full2(q), &prm.a2, down ? &prm.wd : &prm.wo, (down ? DM : 0) + k * 64,
                            mblk * 64, nslot * 128 + rank * 64, down ? 0 : k * 2, down ? k * 2 : 0, stream_policy());
                if (++q == G2_STAGES) { q = 0; ph2 ^= 1; }
            }
            TRACE(8);
        }
    }
}

typedef CUresult (*EncodeFn)(CUtensorMap*, CUtensorMapDataType, cuuint32_t, void*, const cuuint64_t*, const cuuint64_t*,
                             const cuuint32_t*, const cuuint32_t*, CUtensorMapInterleave, CUtensorMapSwizzle,
                             CUtensorMapL2promotion, CUtensorMapFloatOOBfill);

void encode(EncodeFn fn, CUtensorMap* m, const void* ptr, int rank, const cuuint64_t* dims, const cuuint64_t* strides,
            const cuuint32_t* box) {
    const cuuint32_t es[5] = {1, 1, 1, 1, 1};
    fn(m, CU_TENSOR_MAP_DATA_TYPE_BFLOAT16, rank, const_cast<void*>(ptr), dims, strides, box, es,
       CU_TENSOR_MAP_INTERLEAVE_NONE, box[0] == 32 ? CU_TENSOR_MAP_SWIZZLE_64B : CU_TENSOR_MAP_SWIZZLE_128B,
       CU_TENSOR_MAP_L2_PROMOTION_L2_128B, CU_TENSOR_MAP_FLOAT_OOB_FILL_NONE);
}
void encode_rows(EncodeFn fn, CUtensorMap* m, const void* ptr, int cols, int box_rows, int box_parity) {
    const cuuint64_t dims[3] = {(cuuint64_t)cols, SEQ / 2, 2}, strides[2] = {(cuuint64_t)cols * 4, (cuuint64_t)cols * 2};
    const cuuint32_t box[3] = {64, (cuuint32_t)box_rows, (cuuint32_t)box_parity};
    encode(fn, m, ptr, 3, dims, strides, box);
}
void encode_w1(EncodeFn fn, CUtensorMap* m, const void* ptr, int cols) {
    const cuuint64_t dims[2] = {(cuuint64_t)cols, DM}, strides[1] = {(cuuint64_t)cols * 2};
    const cuuint32_t box[2] = {64, 64};
    encode(fn, m, ptr, 2, dims, strides, box);
}
void encode_tail(EncodeFn fn, CUtensorMap* m, const void* ptr, int rows, int cols, int n) {
    const cuuint64_t rb = cols * 2;
    const cuuint64_t dims[5] = {32, (cuuint64_t)n, (cuuint64_t)rows / (4 * n), 4, 8}, strides[4] = {rb, 4 * n * rb, n * rb, 256};
    const cuuint32_t box[5] = {32, (cuuint32_t)n, 16 / (cuuint32_t)n, 4, 8};
    encode(fn, m, (const __nv_bfloat16*)ptr + cols - 1024 + 96, 5, dims, strides, box);
}
void encode_w2(EncodeFn fn, CUtensorMap* m, const void* ptr, int rows) {
    const cuuint64_t rb = DM * 2;
    const cuuint64_t dims[5] = {DM, 2, 4, 4, (cuuint64_t)rows / 32}, strides[4] = {rb, 8 * rb, 2 * rb, 32 * rb};
    const cuuint32_t box[5] = {64, 2, 4, 4, 2};
    encode(fn, m, ptr, 5, dims, strides, box);
}
void encode_wo(EncodeFn fn, CUtensorMap* m, const void* ptr) {
    const cuuint64_t rb = DM * 2;
    const cuuint64_t dims[5] = {DM, 4, DM / 32, 2, 4}, strides[4] = {8 * rb, 32 * rb, rb, 2 * rb};
    const cuuint32_t box[5] = {64, 4, 2, 2, 4};
    encode(fn, m, ptr, 5, dims, strides, box);
}

}

extern "C" void kernel_launch(void* const* d_in, const int* in_sizes, int n_in, void* d_out, int out_size) {
    (void)in_sizes; (void)n_in; (void)out_size;
    static EncodeFn fn = nullptr;
    static Params prm;
    if (!fn) {
        cudaDriverEntryPointQueryResult st;
        cudaGetDriverEntryPoint("cuTensorMapEncodeTiled", (void**)&fn, cudaEnableDefault, &st);
        cudaGetSymbolAddress((void**)&prm.pxn, g_xn);
        cudaGetSymbolAddress((void**)&prm.pa2, g_a2);
        cudaGetSymbolAddress((void**)&prm.tail, g_tail);
        cudaGetSymbolAddress((void**)&prm.halo, g_halo);
        cudaGetSymbolAddress((void**)&prm.stats, g_stats);
        cudaGetSymbolAddress((void**)&prm.colsum, g_colsum);
        cudaGetSymbolAddress((void**)&prm.flags, g_flags);
        cudaGetSymbolAddress((void**)&prm.epoch, g_epoch);
        cudaFuncSetAttribute(fused_kernel, cudaFuncAttributeMaxDynamicSharedMemorySize, SMEM_BYTES);
    }
    encode_rows(fn, &prm.x, d_in[0], DM, 64, 2);
    encode_rows(fn, &prm.xn, prm.pxn, DM, 64, 2);
    encode_rows(fn, &prm.a2, prm.pa2, K2, 64, 2);
    encode_rows(fn, &prm.out, d_out, DM, 16, 1);
    encode_w1(fn, &prm.wqkv, d_in[1], NQKV);
    encode_w1(fn, &prm.wg, d_in[4], DF);
    encode_w1(fn, &prm.wu, d_in[5], DF);
    encode_tail(fn, &prm.wu_tail, d_in[5], DM, DF, 8);
    encode_tail(fn, &prm.wd_tail, d_in[6], DF, DM, 2);
    encode_wo(fn, &prm.wo, d_in[2]);
    encode_w2(fn, &prm.wd, d_in[6], DF);
    prm.px = (const __nv_bfloat16*)d_in[0];
    prm.pout = (__nv_bfloat16*)d_out;
    fused_kernel<<<NCTA, 384, SMEM_BYTES>>>(prm);
}
```

```cpp
#include <cuda_runtime.h>
#include <cuda_bf16.h>
#include <cuda.h>
#include <stdint.h>
#include <type_traits>

#define LNS 3
#define FS 14
#define CA 0x87658765u
#define CB 0x65876587u
#define CST 10
#define CIDX nslot
#define PACE0 900
#define PACE 425
#define PACE3 1700
#define TAIL1 12
#define TAIL2 11
#define NAR0 19
#define NARS 2
#define MIXQ 8
#define MIXV 8
#define TLD2 7
#define XLD 7
#define VK 1
#define VN 2
#define KK 1
#define EREL 0
#define MEET 2
#define OVS 5
#define GV 3
#define SK2 5
#define PFK 60 + mblk
#define XK 66 + nslot
#define TSK 2
#define TW0 9000
#define TLD 12
#define SK0 2

namespace {

constexpr int SEQ = 2048, DM = 1024, DF = 3584, K2 = DM + DF, NQKV = 3 * DM;
constexpr int NGEMM = 128, NCTA = 132;
constexpr int G1_STAGES = 4, G1_STAGE_BYTES = 49152, G1_KSTEPS = 16, G1_TILES = 5;
constexpr int G2_STAGES = 6, G2_STAGE_BYTES = 32768, G2_KSTEPS = 72, G2_LATE = 40, G2_DSTEPS = 56;
constexpr int G2_HEAD = 17;
constexpr int LN_STEP = LNS, FOLD_STEP = FS;
constexpr int A_BYTES = 16384;
constexpr int AUX_OFF = G1_STAGES * G1_STAGE_BYTES;
constexpr int BAR_OFF = AUX_OFF + 32768;
constexpr int SMEM_BYTES = BAR_OFF + 2816;
constexpr int G1_SKEW = 2, G2_SKEW = SK2;
constexpr int CONSUMER_REGS = 224, AUX_REGS = 56;
constexpr int HALO_BYTES = 4096;
constexpr uint64_t narrow_steps() {
    uint64_t m = 0;
    for (int i = 0; i < TAIL2; i++) m |= 1ull << NAR0 + i * NARS;
    return m;
}
constexpr uint64_t G2_NARROW = narrow_steps();
static_assert(G2_NARROW >> G2_LATE == 0 && NAR0 >= 18 && NAR0 < 18 + NARS && 6 % NARS == 0, "narrow steps use early columns");

enum { F_LN = 0, F_LN2 = 1, F_FIRST = 2, F_EARLY = 3, F_LATE = 4, F_TAIL = 5, F_HALO = 6 };
constexpr unsigned CNT_LN = 8, CNT_FIRST = 8, CNT_EARLY = 16, CNT_LATE = 8;

__device__ __align__(1024) __nv_bfloat16 g_xn[SEQ * DM];
__device__ __align__(1024) __nv_bfloat16 g_a2[SEQ * K2];
__device__ __align__(128) uint4 g_tail[2 * NGEMM * 512];
__device__ __align__(128) uint8_t g_halo[(2 * NGEMM + 1) * HALO_BYTES];
__device__ __align__(128) float2 g_stats[SEQ];
__device__ __align__(128) float g_colsum[16 * 1024];
__device__ __align__(128) unsigned g_flags[(F_HALO + 8) * 16 * 32];
__device__ __align__(128) unsigned g_epoch[NCTA * 16];

struct Params {
    const __nv_bfloat16* px;
    __nv_bfloat16 *pxn, *pa2, *pout;
    uint4* tail;
    uint8_t* halo;
    float2* stats;
    float* colsum;
    unsigned *flags, *epoch;
    unsigned long long* trace;
    CUtensorMap x, wg, wu, xn, wqkv, a2, wu_tail, wd_tail, wo, wd, out;
};

extern __shared__ __align__(1024) uint8_t smem_raw[];

#define TRACE(slot) do {} while (0)
#define TRACE_GT(slot) do {} while (0)
#define TRACE_S(slot, v, want) do {} while (0)
#define TRACE_GET(v) do {} while (0)
#define TRACE_PUT(slot, v) do {} while (0)
#define TRACE_SLOT(v, slot) do {} while (0)
#define TRACE_NEXT(v) do {} while (0)
#define TRACE_DUMP() do {} while (0)
#define TRACE_CLEAR() do {} while (0)
#define STAGE_TRACE 0
#define TRACE_END() do {} while (0)
#define TRACE_LITE(i, c) do {} while (0)
#define TRACE_STEP(t, k, i) do {} while (0)

__device__ __forceinline__ uint32_t smem_u32(const void* p) { return (uint32_t)__cvta_generic_to_shared(p); }
__device__ __forceinline__ void mbar_init(uint32_t bar, uint32_t cnt) {
    asm volatile("mbarrier.init.shared::cta.b64 [%0], %1;" :: "r"(bar), "r"(cnt) : "memory");
}
__device__ __forceinline__ void mbar_expect_tx(uint32_t bar, uint32_t bytes) {
    asm volatile("mbarrier.arrive.expect_tx.shared::cta.b64 _, [%0], %1;" :: "r"(bar), "r"(bytes) : "memory");
}
__device__ __forceinline__ void mbar_arrive(uint32_t bar) {
    asm volatile("mbarrier.arrive.shared::cta.b64 _, [%0];" :: "r"(bar) : "memory");
}
__device__ __forceinline__ bool mbar_try_wait(uint32_t bar, uint32_t parity) {
    uint32_t ok;
    asm volatile("{\n.reg .pred p;\nmbarrier.try_wait.parity.shared::cta.b64 p, [%1], %2;\nselp.u32 %0, 1, 0, p;\n}"
                 : "=r"(ok) : "r"(bar), "r"(parity) : "memory");
    return ok;
}
__device__ __forceinline__ void mbar_wait(uint32_t bar, uint32_t parity) {
#pragma unroll 1
    for (int spins = 0; !mbar_try_wait(bar, parity) && spins < (1 << 17); spins++) {}
}
__device__ __forceinline__ void mbar_wait(uint32_t bar, uint32_t parity, int& spins) {
    asm volatile("{\n.reg .pred p;\nagain:\nmbarrier.try_wait.parity.shared::cta.b64 p, [%1], %2;\n@p bra done;\n"
                 "add.s32 %0, %0, -1;\nsetp.gt.s32 p, %0, 0;\n@p bra again;\ndone:\n}" : "+r"(spins) : "r"(bar), "r"(parity) : "memory");
}
template <bool WARP = false> __device__ __forceinline__ void flag_wait(const unsigned* p, unsigned target) {
#pragma unroll 1
    for (int spins = 0; spins < (1 << 19); spins++) {
        unsigned v;
        asm volatile("ld.acquire.gpu.global.u32 %0, [%1];" : "=r"(v) : "l"(p) : "memory");
        if (WARP ? __all_sync(0xffffffffu, (int)(v - target) >= 0) : (int)(v - target) >= 0) break;
        __nanosleep(64);
    }
}
__device__ __forceinline__ void mbar_wait_warp(uint32_t bar, uint32_t parity) {
#pragma unroll 1
    for (int spins = 0; !__all_sync(0xffffffffu, mbar_try_wait(bar, parity)) && spins < (1 << 17); spins++) {}
}
__device__ __forceinline__ void flag_add(unsigned* p) {
    asm volatile("red.release.gpu.global.add.u32 [%0], 1;" :: "l"(p) : "memory");
}
__device__ __forceinline__ bool elect_one() {
    uint32_t ok;
    asm volatile("{\n.reg .pred p;\nelect.sync _|p, 0xffffffff;\nselp.u32 %0, 1, 0, p;\n}" : "=r"(ok));
    return ok;
}
__device__ __forceinline__ uint32_t pick(bool c, uint32_t a, uint32_t b) {
    uint32_t r;
    asm("{\n.reg .pred p;\nsetp.ne.b32 p, %3, 0;\nselp.b32 %0, %1, %2, p;\n}" : "=r"(r) : "r"(a), "r"(b), "r"((uint32_t)c));
    return r;
}
__device__ __forceinline__ void fence_proxy_async() { asm volatile("fence.proxy.async.global;" ::: "memory"); }
__device__ __forceinline__ uint4 lds128(uint32_t addr) {
    uint4 v;
    asm volatile("ld.shared.v4.u32 {%0,%1,%2,%3}, [%4];" : "=r"(v.x), "=r"(v.y), "=r"(v.z), "=r"(v.w) : "r"(addr) : "memory");
    return v;
}
__device__ __forceinline__ float2 lds64f(uint32_t addr) {
    float2 v;
    asm volatile("ld.shared.v2.f32 {%0,%1}, [%2];" : "=f"(v.x), "=f"(v.y) : "r"(addr) : "memory");
    return v;
}
__device__ __forceinline__ void sts128(uint32_t addr, uint4 v) {
    asm volatile("st.shared.v4.u32 [%0], {%1,%2,%3,%4};" :: "r"(addr), "r"(v.x), "r"(v.y), "r"(v.z), "r"(v.w) : "memory");
}
__device__ __forceinline__ void sts64f(uint32_t addr, float a, float b) {
    asm volatile("st.shared.v2.f32 [%0], {%1,%2};" :: "r"(addr), "f"(a), "f"(b) : "memory");
}

__device__ __forceinline__ uint64_t stream_policy() { return 0x12F0000000000000ull; }
__device__ __forceinline__ void tma_3d(uint32_t dst, const CUtensorMap* m, uint32_t bar, int c0, int c1, int c2, uint64_t pol) {
    asm volatile("cp.async.bulk.tensor.3d.shared::cluster.global.mbarrier::complete_tx::bytes.L2::cache_hint"
                 " [%0], [%1, {%3, %4, %5}], [%2], %6;"
                 :: "r"(dst), "l"(m), "r"(bar), "r"(c0), "r"(c1), "r"(c2), "l"(pol) : "memory");
}
__device__ __forceinline__ void load_stage1(uint32_t dst, uint32_t dst_b, uint32_t bar, const CUtensorMap* ma, const CUtensorMap* mb0,
                                            const CUtensorMap* mb1, int k, int row, int col0, int col1, int keep_a, uint64_t pol) {
    asm volatile("{\n.reg .pred e, p, q;\nelect.sync _|e, 0xffffffff;\nsetp.ne.and.b32 p|q, %8, 0, e;\n"
        "@p cp.async.bulk.tensor.3d.shared::cluster.global.mbarrier::complete_tx::bytes [%0], [%3, {%5, %6, %10}], [%2];\n"
        "@q cp.async.bulk.tensor.3d.shared::cluster.global.mbarrier::complete_tx::bytes.L2::cache_hint [%0], [%3, {%5, %6, %10}], [%2], %9;\n"
        "@e cp.async.bulk.tensor.2d.shared::cluster.global.mbarrier::complete_tx::bytes.multicast::cluster.L2::cache_hint"
        " [%1], [%4, {%7, %5}], [%2], %11, %9;\n"
        "@e cp.async.bulk.tensor.2d.shared::cluster.global.mbarrier::complete_tx::bytes.multicast::cluster.L2::cache_hint"
        " [%1 + 8192], [%13, {%14, %5}], [%2], %11, %9;\n"
        "@e mbarrier.arrive.expect_tx.shared::cta.b64 _, [%2], %12;\n}"
        :: "r"(dst), "r"(dst_b), "r"(bar), "l"(ma), "l"(mb0), "r"(k), "r"(row), "r"(col0), "r"(keep_a), "l"(pol), "r"(0),
           "h"((uint16_t)3), "n"(G1_STAGE_BYTES), "l"(mb1), "r"(col1) : "memory");
}
__device__ __forceinline__ void load_stage2(uint32_t dst, uint32_t dst_b, uint32_t bar, const CUtensorMap* ma, const CUtensorMap* mb,
                                            int ka, int row, int col, int kb2, int kb4, uint64_t pol) {
    asm volatile("{\n.reg .pred e;\nelect.sync _|e, 0xffffffff;\n"
        "@e cp.async.bulk.tensor.3d.shared::cluster.global.mbarrier::complete_tx::bytes.L2::cache_hint [%0], [%3, {%5, %6, %10}], [%2], %9;\n"
        "@e cp.async.bulk.tensor.5d.shared::cluster.global.mbarrier::complete_tx::bytes.multicast::cluster.L2::cache_hint"
        " [%1], [%4, {%7, %10, %13, %10, %8}], [%2], %11, %9;\n"
        "@e mbarrier.arrive.expect_tx.shared::cta.b64 _, [%2], %12;\n}"
        :: "r"(dst), "r"(dst_b), "r"(bar), "l"(ma), "l"(mb), "r"(ka), "r"(row), "r"(col), "r"(kb4), "l"(pol), "r"(0),
           "h"((uint16_t)3), "n"(G2_STAGE_BYTES), "r"(kb2) : "memory");
}
__device__ __forceinline__ uint4 ldg_stream(const void* p, uint64_t pol) {
    uint4 v;
    asm volatile("ld.global.nc.L1::no_allocate.L2::cache_hint.v4.u32 {%0,%1,%2,%3}, [%4], %5;"
                 : "=r"(v.x), "=r"(v.y), "=r"(v.z), "=r"(v.w) : "l"(p), "l"(pol));
    return v;
}
__device__ __forceinline__ void st_tagged(void* p, float a, float b, uint32_t tag) {
    asm volatile("st.relaxed.gpu.global.v2.b32 [%0], {%1,%2};"
                 :: "l"(p), "r"((__float_as_uint(a) & ~3u) | tag), "r"((__float_as_uint(b) & ~3u) | tag) : "memory");
}
__device__ __forceinline__ bool untagged(const uint4& v, uint32_t tag) {
    return ((v.x ^ tag) | (v.y ^ tag) | (v.z ^ tag) | (v.w ^ tag)) & 3;
}
__device__ __forceinline__ uint4 ld_relaxed(const void* p) {
    uint4 v;
    asm volatile("ld.relaxed.gpu.global.v4.b32 {%0,%1,%2,%3}, [%4];" : "=r"(v.x), "=r"(v.y), "=r"(v.z), "=r"(v.w) : "l"(p) : "memory");
    return v;
}
__device__ __forceinline__ void prefetch_map(const CUtensorMap* m) {
    asm volatile("prefetch.tensormap [%0];" :: "l"(m) : "memory");
}
template <int N> __device__ __forceinline__ void wg_wait() { asm volatile("wgmma.wait_group.sync.aligned %0;" :: "n"(N) : "memory"); }

__device__ __forceinline__ uint32_t desc_a(uint32_t addr) { return (addr & 0x3FFFF) >> 4 | 1 << 16; }
__device__ __forceinline__ uint32_t desc_b(uint32_t addr) { return (addr & 0x3FFFF) >> 4 | 512 << 16; }

#define R8(d, o) "+f"(d[o]), "+f"(d[o+1]), "+f"(d[o+2]), "+f"(d[o+3]), "+f"(d[o+4]), "+f"(d[o+5]), "+f"(d[o+6]), "+f"(d[o+7])
#define R32(d, o) R8(d, o), R8(d, o+8), R8(d, o+16), R8(d, o+24)
#define R64(d, o) R32(d, o), R32(d, o+32)
#define ACC00 "%0,%1,%2,%3,%4,%5,%6,%7,%8,%9,%10,%11,%12,%13,%14,%15,%16,%17,%18,%19,%20,%21,%22,%23,%24,%25,%26,%27,%28,%29,%30,%31,"\
    "%32,%33,%34,%35,%36,%37,%38,%39,%40,%41,%42,%43,%44,%45,%46,%47"
#define ACC0 ACC00 ",%48,%49,%50,%51,%52,%53,%54,%55,%56,%57,%58,%59,%60,%61,%62,%63"
#define ACC1 "%64,%65,%66,%67,%68,%69,%70,%71,%72,%73,%74,%75,%76,%77,%78,%79,%80,%81,%82,%83,%84,%85,%86,%87,%88,%89,%90,%91,%92,%93,%94,%95,"\
    "%96,%97,%98,%99,%100,%101,%102,%103,%104,%105,%106,%107,%108,%109,%110,%111"
#define ACC48 "{" ACC00 "}"
#define ACC64 "{" ACC0 "}"
#define ACC112 "{" ACC0 "," ACC1 "}"
#define ACC128 "{" ACC0 "," ACC1 ",%112,%113,%114,%115,%116,%117,%118,%119,%120,%121,%122,%123,%124,%125,%126,%127}"
#define MMA_K16(shape, acc, a, b, keep, hb) \
    "mov.b64 da, {" a ", 0x40000040};\nmov.b64 db, {" b ", " hb "};\n" \
    "wgmma.mma_async.sync.aligned." shape ".f32.bf16.bf16 " acc ", da, db, " keep ", 1, 1, 0, 1;\n"
#define MMA_NEXT(op, a, b, sa, sb) op " " a ", " a ", " sa ";\n" op " " b ", " b ", " sb ";\n"
#define MMA_STEP_B(shape, acc, a, b, na, nb, keep, hb, sb) \
    "{\n.reg .pred p, q;\n.reg .b64 da, db;\nsetp.ne.b32 p, " keep ", 0;\nsetp.eq.b32 q, 0, 0;\nwgmma.fence.sync.aligned;\n" \
    MMA_K16(shape, acc, a, b, "p", hb) MMA_NEXT("xor.b32", a, b, "2", "128") MMA_K16(shape, acc, a, b, "q", hb) MMA_NEXT("add.s32", a, b, "2", sb) \
    MMA_K16(shape, acc, a, b, "q", hb) MMA_NEXT("xor.b32", a, b, "2", "128") MMA_K16(shape, acc, a, b, "q", hb) MMA_NEXT("add.s32", a, b, na, nb) \
    "wgmma.commit_group.sync.aligned;\n}"
#define MMA_STEP(shape, acc, a, b, na, nb, keep) MMA_STEP_B(shape, acc, a, b, na, nb, keep, "0x40000040", "128")
#define MMA_ARGS "+r"(da), "+r"(db) : "r"(next / 16 - 6), "r"(next / 16 - 384), "r"(keep) : "memory"

__device__ __forceinline__ void mma_step(float (&d)[128], uint32_t& da, uint32_t& db, int next, int keep) {
    asm volatile(MMA_STEP("m64n256k16", ACC128, "%128", "%129", "%130", "%131", "%132") : R64(d, 0), R64(d, 64), MMA_ARGS);
}
__device__ __forceinline__ void mma_rank(float (&d)[128], uint32_t a0, uint32_t a1, uint32_t db) {
    asm volatile("{\n.reg .pred q;\n.reg .b64 db;\nsetp.eq.b32 q, 0, 0;\nmov.b64 db, {%131, 0x40000040};\nwgmma.fence.sync.aligned;\n"
                 "wgmma.mma_async.sync.aligned.m64n256k16.f32.bf16.bf16 " ACC128 ", {%128, %129, %130, %130}, db, q, 1, 1, 1;\n}"
                 : R64(d, 0), R64(d, 64) : "r"(a0), "r"(a1), "r"(0), "r"(db) : "memory");
}
__device__ __forceinline__ void mma_step224(float (&d)[128], uint32_t& da, uint32_t& db, int next, int keep) {
    asm volatile(MMA_STEP("m64n224k16", ACC112, "%112", "%113", "%114", "%115", "%116")
                 : R64(d, 0), R32(d, 64), R8(d, 96), R8(d, 104), MMA_ARGS);
}
__device__ __forceinline__ void mma_step(float (&d)[64], uint32_t& da, uint32_t& db, int next, int keep) {
    asm volatile(MMA_STEP("m64n128k16", ACC64, "%64", "%65", "%66", "%67", "%68") : R64(d, 0), MMA_ARGS);
}
__device__ __forceinline__ void mma_step96(float (&d)[64], uint32_t& da, uint32_t& db, int next, int keep) {
    asm volatile(MMA_STEP("m64n96k16", ACC48, "%48", "%49", "%50", "%51", "%52") : R32(d, 0), R8(d, 32), R8(d, 40), MMA_ARGS);
}
__device__ __forceinline__ void mma_step_tail(float (&d)[128], uint32_t da, uint32_t b, int keep) {
    uint32_t db = (b & 0x3FFFF) >> 4 | 256 << 16;
    const int next = 0;
    asm volatile(MMA_STEP_B("m64n256k16", ACC128, "%128", "%129", "%130", "%131", "%132", "0x80000040", "-96")
                 : R64(d, 0), R64(d, 64), MMA_ARGS);
}

__device__ __forceinline__ uint32_t pack_bf16(float lo, float hi) {
    uint32_t r; asm("cvt.rn.bf16x2.f32 %0, %1, %2;" : "=r"(r) : "f"(hi), "f"(lo)); return r;
}
__device__ __forceinline__ float bf_lo(uint32_t v) { return __uint_as_float(v << 16); }
__device__ __forceinline__ float bf_hi(uint32_t v) { return __uint_as_float(v & 0xffff0000u); }
__device__ __forceinline__ float round_bf16(float v) { return bf_lo(pack_bf16(v, 0.f)); }
__device__ __forceinline__ uint32_t mul_bf16x2(uint32_t a, uint32_t b) {
    uint32_t r; asm("mul.rn.bf16x2 %0, %1, %2;" : "=r"(r) : "r"(a), "r"(b)); return r;
}
__device__ __forceinline__ uint32_t sub_bf16x2(uint32_t a, uint32_t b) {
    uint32_t r; asm("sub.rn.bf16x2 %0, %1, %2;" : "=r"(r) : "r"(a), "r"(b)); return r;
}
__device__ __forceinline__ uint32_t mul2_bf16x2(uint32_t a, uint32_t hi, uint32_t lo) {
    uint32_t r; asm("fma.rn.bf16x2 %0, %1, %2, %3;" : "=r"(r) : "r"(a), "r"(hi), "r"(mul_bf16x2(a, lo))); return r;
}
__device__ __forceinline__ float tanh_fast(float x) { float r; asm("tanh.approx.f32 %0, %1;" : "=f"(r) : "f"(x)); return r; }
__device__ __forceinline__ float gelu_twice(float g) {
    return fmaf(g, tanh_fast(fmaf(g * g, 0.044715f * 0.7978845608f, 0.7978845608f) * g), g);
}
__device__ __forceinline__ uint32_t geglu2(uint32_t g2, uint32_t u2) {
    return mul_bf16x2(pack_bf16(gelu_twice(bf_lo(g2)), gelu_twice(bf_hi(g2))), u2);
}
__device__ __forceinline__ uint32_t silu2(float lo, float hi) {
    const uint32_t h = mul_bf16x2(pack_bf16(lo, hi), 0x3e803e80u);
    return pack_bf16(fmaf(bf_lo(h), tanh_fast(bf_lo(h)), bf_lo(h)), fmaf(bf_hi(h), tanh_fast(bf_hi(h)), bf_hi(h)));
}
__device__ __forceinline__ float ex2_fast(float x) { float r; asm("ex2.approx.ftz.f32 %0, %1;" : "=f"(r) : "f"(x)); return r; }
__device__ __forceinline__ void unpack8(uint4 v, float (&f)[8]) {
    f[0] = bf_lo(v.x); f[1] = bf_hi(v.x); f[2] = bf_lo(v.y); f[3] = bf_hi(v.y);
    f[4] = bf_lo(v.z); f[5] = bf_hi(v.z); f[6] = bf_lo(v.w); f[7] = bf_hi(v.w);
}
template <int N> __device__ __forceinline__ void fence_regs(float (&d)[N]) {
#pragma unroll
    for (int i = 0; i < N; i++) asm volatile("" : "+f"(d[i]) :: "memory");
}

__device__ __forceinline__ float rcp_fast(float x) { float r; asm("rcp.approx.ftz.f32 %0, %1;" : "=f"(r) : "f"(x)); return r; }
__device__ __forceinline__ float sqrt_fast(float x) { float r; asm("sqrt.approx.ftz.f32 %0, %1;" : "=f"(r) : "f"(x)); return r; }
__device__ __forceinline__ uint32_t max_bf16x2(uint32_t a, uint32_t b) {
    uint32_t r; asm("max.bf16x2 %0, %1, %2;" : "=r"(r) : "r"(a), "r"(b)); return r;
}
__device__ __forceinline__ uint32_t transpose8(uint32_t a) {
    uint32_t r; asm volatile("movmatrix.sync.aligned.m8n8.trans.b16 %0, %1;" : "=r"(r) : "r"(a)); return r;
}
__device__ __forceinline__ void mma_sync(uint32_t* d, const uint32_t* a, uint32_t b0, uint32_t b1, const uint32_t* c) {
    asm volatile("mma.sync.aligned.m16n8k16.row.col.f32.bf16.bf16.f32 {%0,%1,%2,%3}, {%4,%5,%6,%7}, {%8,%9}, {%10,%11,%12,%13};"
        : "=r"(d[0]), "=r"(d[1]), "=r"(d[2]), "=r"(d[3])
        : "r"(a[0]), "r"(a[1]), "r"(a[2]), "r"(a[3]), "r"(b0), "r"(b1), "r"(c[0]), "r"(c[1]), "r"(c[2]), "r"(c[3]));
}
template <int N> struct Floats {
    float f[N];
    __device__ __forceinline__ Floats() {}
    __device__ __forceinline__ Floats(const uint32_t* p) {
#pragma unroll
        for (int i = 0; i < N; i++) asm("mov.b32 %0, %1;" : "=f"(f[i]) : "r"(p[i]));
    }
    __device__ __forceinline__ void put(uint32_t* p) const {
#pragma unroll
        for (int i = 0; i < N; i++) asm("mov.b32 %0, %1;" : "=r"(p[i]) : "f"(f[i]));
    }
    __device__ __forceinline__ float& operator[](int i) { return f[i]; }
};
__device__ __forceinline__ uint32_t fresh_tid() { uint32_t r; asm volatile("mov.u32 %0, %%tid.x;" : "=r"(r)); return r; }
template <typename T> __device__ __forceinline__ T uniform(T v) { return __shfl_sync(0xffffffffu, v, 0); }

__device__ __forceinline__ void tail_gemm(const Params& prm, uint32_t base, uint32_t t0, unsigned epoch, int grp, int warp, int lane) {
    const uint32_t full = base + BAR_OFF, empty = full + 320, sig = full + 192, dep = full + 256;
    unsigned* const flags = prm.flags + grp * 128;
    if (warp >= 8) asm volatile("setmaxnreg.dec.sync.aligned.u32 %0;" :: "n"(AUX_REGS));
    if (warp == 8) {
        if (elect_one()) { prefetch_map(&prm.xn); prefetch_map(&prm.wu_tail); prefetch_map(&prm.a2); prefetch_map(&prm.wd_tail); }
        auto load_w = [&](int i, const CUtensorMap* m, int k) {
            asm volatile("{\n.reg .pred e;\nelect.sync _|e, 0xffffffff;\n"
                "@e cp.async.bulk.tensor.5d.shared::cluster.global.mbarrier::complete_tx::bytes [%0], [%2, {%4, %4, %3, %4, %4}], [%1];\n"
                "@e mbarrier.arrive.expect_tx.shared::cta.b64 _, [%1], %5;\n}"
                :: "r"(base + (i & 3) * G1_STAGE_BYTES + A_BYTES), "r"(full + (i & 3) * 8), "l"(m), "r"(k), "r"(0),
                   "n"(G1_STAGE_BYTES) : "memory");
        };
        while ((uint32_t)clock() - t0 < TW0) {}
#pragma unroll 1
        for (int i = 0; i < 4; i++) load_w(i, &prm.wu_tail, i * 2);
        flag_wait<true>(flags + F_LN * 512 + (lane & 3) * 32, epoch * CNT_LN);
        fence_proxy_async();
        TRACE(62);
#pragma unroll 1
        for (int p = 0, i = 0; p < 8; p++) {
            const bool first = p < 4;
            if (p == 4) mbar_wait_warp(dep + 8, 0);
#pragma unroll 1
            for (int k = 0; k < (first ? TAIL1 : TAIL2); k++, i++) {
                if (i == 8) mbar_wait_warp(dep, 0);
                mbar_wait_warp(empty + (i & 3) * 8, ~i >> 2 & 1);
                asm volatile("{\n.reg .pred e;\nelect.sync _|e, 0xffffffff;\n"
                    "@e cp.async.bulk.tensor.3d.shared::cluster.global.mbarrier::complete_tx::bytes [%0], [%2, {%3, %4, %5}], [%1];\n}"
                    :: "r"(base + (i & 3) * G1_STAGE_BYTES), "r"(full + (i & 3) * 8), "l"(first ? &prm.xn : &prm.a2),
                       "r"((first ? 0 : DM) + k * 64), "r"(grp * 256 + (p & 3) * 64), "r"(0) : "memory");
                if (i >= 4) load_w(i, first ? &prm.wu_tail : &prm.wd_tail, first ? k * 2 : k * 8);
            }
        }
    } else if (warp == 9) {
#pragma unroll 1
        for (int j = 0; j < 2; j++) {
            flag_wait<true>(flags + (F_LN2 + j) * 512 + (lane & 3) * 32, epoch * CNT_LN);
            fence_proxy_async();
            __syncwarp();
            if (lane == 0) mbar_arrive(dep + j * 8);
        }
    } else if (warp == 10 && lane == 0) {
#pragma unroll 1
        for (int p = 0; p < 8; p++) {
            mbar_wait(sig + p * 8, 0);
            flag_add(flags + F_TAIL * 512 + (p & 3) * 32);
            TRACE_S(50, p, 3); TRACE_S(51, p, 7);
        }
        prm.epoch[blockIdx.x * 16] = epoch;
        TRACE_DUMP();
    }
    if (warp >= 8) return;
    asm volatile("setmaxnreg.inc.sync.aligned.u32 %0;" :: "n"(CONSUMER_REGS) : "memory");
    const uint32_t da = desc_a(base + (warp >> 2) * 8192);
    uint4* out = prm.tail;
    float acc[128];
    uint32_t pk[64];
    int i = 0;
    auto release = [&]() { if ((threadIdx.x & 127) == 0) mbar_arrive(empty + (i - 1 & 3) * 8); };
    auto store = [&](int j) {
        asm volatile("st.global.v4.u32 [%0], {%1,%2,%3,%4};" :: "l"(out + j / 2 * 8192 + j % 2 * 256),
                     "r"(pk[4 * j]), "r"(pk[4 * j + 1]), "r"(pk[4 * j + 2]), "r"(pk[4 * j + 3]) : "memory");
    };
    auto step = [&](int k, int left) {
        mbar_wait(full + (i & 3) * 8, i >> 2 & 1);
        TRACE_S(45, warp * 128 + i, 0);
        if (warp >= 4 && left == TSK) asm volatile("bar.sync 1, 256;" ::: "memory");
        mma_step_tail(acc, da + (i & 3) * (G1_STAGE_BYTES / 16), base + A_BYTES + (i & 3) * G1_STAGE_BYTES, k);
        if (warp < 4 && left == 1) asm volatile("bar.arrive 1, 256;" ::: "memory");
        wg_wait<1>();
        if (k) release();
        i++;
    };
#pragma unroll
    for (int j = 0; j < 128; j++) asm volatile("mov.b32 %0, 0;" : "=f"(acc[j]));
#pragma unroll
    for (int j = 0; j < 64; j++) asm volatile("mov.b32 %0, 0;" : "=r"(pk[j]));
#pragma unroll 1
    for (int p = 0; p < 8; p++) {
        step(0, 0);
#pragma unroll 1
        for (int left = (p < 4 ? TAIL1 : TAIL2) - 1, n = p ? 8 : 0; left > 0; left--) {
            if (n > 0) { store(0); store(1); }
#pragma unroll
            for (int j = 8; j < 64; j++) asm volatile("mov.b32 %0, %1;" : "=r"(pk[j - 8]) : "r"(pk[j]));
            out += 8192;
            __syncwarp();
            if (--n == 0 && lane == 0) mbar_arrive(sig + p * 8 - 8);
            step(1, left);
        }
        wg_wait<0>();
        fence_regs(acc);
        release();
        TRACE_S(46, p + warp * 8, 32); TRACE_S(47, p + warp * 8, 33); TRACE_S(48, p + warp * 8, 34); TRACE_S(49, p + warp * 8, 35);
        TRACE_S(53, p + warp * 8, 36); TRACE_S(54, p + warp * 8, 37); TRACE_S(55, p + warp * 8, 38); TRACE_S(56, p + warp * 8, 39);
#pragma unroll
        for (int j = 0; j < 64; j++) pk[j] = pack_bf16(acc[2 * j], acc[2 * j + 1]);
        out = prm.tail + p / 4 * NGEMM * 512 + (grp * 4 + p % 4) * 512 + threadIdx.x;
    }
#pragma unroll
    for (int j = 0; j < 16; j++) store(j);
    __syncwarp();
    TRACE_S(58, warp, 4);
    if (lane == 0) mbar_arrive(sig + 56);
}

__device__ __forceinline__ int gate_col(int t, int nslot) { return t == 2 ? 960 + nslot * 64 : max(t * 1024 - 1536, 0) + nslot * 128; }

struct Role {
    int rank, role, mblk, nslot;
    __device__ __forceinline__ Role() {
        uint32_t id;
        asm volatile("mov.u32 %0, %%ctaid.x;" : "=r"(id));
        const uint32_t cl = id / 2;
        rank = id & 1;
        role = pick(cl < 4, 32 + cl * 8, cl - 8 + max(4u, (cl - 1) * 37 >> 8)) * 2 + rank;
        mblk = role & 15; nslot = role >> 4;
    }
};

__global__ void __cluster_dims__(2, 1, 1) __launch_bounds__(384, 1)
fused_kernel(const __grid_constant__ Params prm) {
    TRACE_GET(c0);
    const uint32_t base = smem_u32(smem_raw) & ~1023u;
    const uint32_t bars = base + BAR_OFF;
    auto full1 = [&](int s) { return bars + s * 8; };
    auto empty1 = [&](int s) { return bars + 32 + s * 8; };
    auto full2 = [&](int s) { return bars + 64 + s * 8; };
    auto empty2 = [&](int s) { return bars + 128 + s * 8; };
    const uint32_t sig_bar = bars + 192, dep_bar = bars + 256, cs_bar = bars + 304, fold_bar = bars + 320, x_bar = bars + 352;
    const uint32_t halo_bar = dep_bar + 32;
    const uint32_t stats = bars + 1536;
    auto stage2 = [&](int q) { return base + q * G2_STAGE_BYTES; };
    const uint32_t aux = base + AUX_OFF;

    asm volatile("{\n.reg .pred p;\nsetp.eq.u32 p, %1, 0;\n@p mbarrier.init.shared::cta.b64 [%0], 1;\n"
        "fence.mbarrier_init.release.cluster;\nbarrier.cluster.arrive.relaxed.aligned;\n}" :: "r"(bars), "r"(threadIdx.x) : "memory");
    const int warp = __shfl_sync(0xffffffffu, threadIdx.x >> 5, 0);
    auto cluster_wait = []() { asm volatile("barrier.cluster.wait.acquire.aligned;" ::: "memory"); };
    if ((warp | (blockIdx.x & NGEMM)) == 8) {
        const Role r;
        asm volatile("{\n.reg .pred e;\nelect.sync _|e, 0xffffffff;\n"
            "@e prefetch.tensormap [%0];\n@e prefetch.tensormap [%1];\n}" :: "l"(&prm.x), "l"(&prm.wg + r.rank) : "memory");
        cluster_wait();
        load_stage1(base, base + A_BYTES + r.rank * 16384, full1(0), &prm.x, &prm.wg + r.rank, &prm.wg + r.rank, 0, r.mblk * 64,
                    r.nslot * 128, r.nslot * 128 + 64, 0, stream_policy());
    } else {
        cluster_wait();
    }
    const uint32_t t0 = clock();
    asm volatile("{\n.reg .pred e, q;\nelect.sync _|e, 0xffffffff;\nsetp.ne.and.u32 q, %2, 0, e;\n"
        "@q mbarrier.init.shared::cta.b64 [%0], %1;\n@e mbarrier.init.shared::cta.b64 [%0 + 8], %1;\n"
        "@e mbarrier.init.shared::cta.b64 [%0 + 16], %1;\n@e mbarrier.init.shared::cta.b64 [%0 + 24], %1;\n"
        "fence.mbarrier_init.release.cluster;\nbarrier.cluster.arrive.relaxed.aligned;\n}"
        :: "r"(bars + warp * 32), "r"(1 << (0x10fa08 >> warp * 2 & 3)), "r"(warp) : "memory");
    const int lane = threadIdx.x & 31;
    const Role me;
    const int rank = me.rank, role = me.role, mblk = me.mblk, nslot = me.nslot;
    const CUtensorMap* const w0 = &prm.wg + rank;

    if (blockIdx.x >= NGEMM) {
        if (warp == 9) { TRACE_CLEAR(); TRACE_GT(0); TRACE_PUT(1, c0); }
        cluster_wait();
        const uint32_t seen = __ldcg(prm.epoch + blockIdx.x * 16);
        tail_gemm(prm, base, t0, seen + 1, blockIdx.x - NGEMM, warp, lane);
    } else if (warp < 8) {
        asm volatile("setmaxnreg.inc.sync.aligned.u32 %0;" :: "n"(CONSUMER_REGS));
        const int wg = __shfl_sync(0xffffffffu, threadIdx.x >> 7, 0);
        const int cw = threadIdx.x >> 5;
        const int tid = threadIdx.x & 127;
        int spins = 1 << 18;
        float acc[128];
        uint32_t pk[64];
#pragma unroll
        for (int i = 0; i < 64; i++) asm volatile("mov.b32 %0, 0;" : "=r"(pk[i]));
#pragma unroll
        for (int i = 0; i < 128; i++) asm volatile("mov.b32 %0, 0;" : "=f"(acc[i]));
        cluster_wait();

        auto row0 = [&](uint32_t id) { return mblk * 128 + (id & 96) + wg; };
        __nv_bfloat16* optr = prm.pxn + (mblk * 128 + nslot * 16 + cw * 2) * DM + lane * 8;
        uint32_t da = desc_a(base + wg * 8192), db = desc_b(base + A_BYTES);
        auto next1 = [](int s) { return ((s + 1) % G1_STAGES - s) * G1_STAGE_BYTES; };
        auto next2 = [](int q) { return ((q + 1) % G2_STAGES - q) * G2_STAGE_BYTES; };
        uint32_t peer_bars;
        asm volatile("mapa.shared::cluster.u32 %0, %1, %2;" : "=r"(peer_bars) : "r"(bars), "r"(tid & 1));
        if (tid >= 2) peer_bars = 0;
        auto release = [&](uint32_t bar) {
            if (peer_bars) asm volatile("mbarrier.arrive.shared::cluster.b64 _, [%0];" :: "r"(peer_bars + (bar - bars)) : "memory");
        };
        auto up = [](int i) { return 32 + (i & 24) + (i & 3) * 2 + (i >> 2 & 1); };
        auto store_pk = [&](__nv_bfloat16* p, int j) {
            asm volatile("st.global.v4.u32 [%0], {%1,%2,%3,%4};"
                         :: "l"(p), "r"(pk[4 * j]), "r"(pk[4 * j + 1]), "r"(pk[4 * j + 2]), "r"(pk[4 * j + 3]) : "memory");
        };
        auto chunk_geglu = [&](int j) {
#pragma unroll
            for (int i = 4 * j; i < 4 * j + 4; i++) pk[i] = geglu2(pk[i], pk[up(i)]);
            store_pk(optr + (j & 1) * 16 * K2 + (j >> 1) * 32, j);
        };
        auto signal_stores = [&](int p) { __syncwarp(); if (lane == 0) mbar_arrive(sig_bar + p * 8); };

        auto chunk_ln = [&](int k) {
            Floats<6> mo(pk + 32);
            if (k == 0) {
                const uint4* xp = reinterpret_cast<const uint4*>(prm.px + (optr - prm.pxn));
                pk[38] = __ldcg(prm.epoch + blockIdx.x * 16 + 2);
#pragma unroll
                for (int i = 0; i < 8; i++) {
                    const uint4 v = ldg_stream(xp + i * 32, stream_policy());
                    pk[4 * i] = v.x; pk[4 * i + 1] = v.y; pk[4 * i + 2] = v.z; pk[4 * i + 3] = v.w;
                }
            } else if (k >= LN_STEP && k < LN_STEP + 3) {
                if (k == LN_STEP) {
                    mo[0] = bf_lo(uniform(pk[0])); mo[1] = bf_lo(uniform(pk[16]));
                    mo[2] = mo[3] = mo[4] = mo[5] = 0.f;
                }
#pragma unroll
                for (int i = (k - LN_STEP) * 11; i < (k - LN_STEP) * 11 + 11 && i < 32; i++) {
                    const int r = i & 1;
                    const uint32_t w = pk[r * 16 + i / 2];
                    const float lo = bf_lo(w) - mo[r], hi = bf_hi(w) - mo[r];
                    mo[2 + r] += lo + hi;
                    mo[4 + r] = fmaf(hi, hi, fmaf(lo, lo, mo[4 + r]));
                }
                mo.put(pk + 32);
            } else if (k == LN_STEP + 3) {
                const bool second = lane & 16;
                float m1 = (second ? mo[3] : mo[2]) + __shfl_xor_sync(0xffffffffu, second ? mo[2] : mo[3], 16);
                float m2 = (second ? mo[5] : mo[4]) + __shfl_xor_sync(0xffffffffu, second ? mo[4] : mo[5], 16);
#pragma unroll
                for (int o = 8; o > 0; o >>= 1) {
                    m1 += __shfl_xor_sync(0xffffffffu, m1, o);
                    m2 += __shfl_xor_sync(0xffffffffu, m2, o);
                }
                m1 *= 1.f / DM;
                const float var = fmaxf(fmaf(-m1, m1, m2 * (1.f / DM)), 0.f);
                const float mean = round_bf16((second ? mo[1] : mo[0]) + m1);
                const float inv = rcp_fast(round_bf16(sqrt_fast(round_bf16(round_bf16(var) + 1e-5f))));
                if ((lane & 15) == 0) st_tagged(prm.stats + (uint32_t)(optr - prm.pxn) / DM + second, -mean, inv, 2 - (pk[38] & 1));
                const uint32_t split = pack_bf16(inv - round_bf16(inv), inv);
#pragma unroll
                for (int r = 0; r < 2; r++) {
                    const uint32_t f = __shfl_sync(0xffffffffu, split, r * 16);
                    pk[32 + 3 * r] = __byte_perm(__shfl_sync(0xffffffffu, __float_as_uint(mean), r * 16), 0, 0x3232);
                    pk[33 + 3 * r] = __byte_perm(f, 0, 0x3232);
                    pk[34 + 3 * r] = __byte_perm(f, 0, 0x1010);
                }
            } else if (k >= LN_STEP + 4 && k < LN_STEP + 8) {
#pragma unroll
                for (int i = k - LN_STEP - 4; i < 8; i += 4) {
                    const uint32_t* n = pk + 32 + i / 4 * 3;
#pragma unroll
                    for (int j = 4 * i; j < 4 * i + 4; j++) pk[j] = mul2_bf16x2(sub_bf16x2(pk[j], n[0]), n[1], n[2]);
                    store_pk(optr + i * 256, i);
                }
                if (k == LN_STEP + 5 || k == LN_STEP + 7) signal_stores(k == LN_STEP + 5 ? 0 : 7);
            } else if (k == FOLD_STEP) {
                mbar_wait(fold_bar, 0, spins);
                const uint32_t id = fresh_tid(), sp = stats + (id & 96) * 8 + (id & 28) * 4 + wg * 8;
                const uint32_t sel = lane & 2 ? 0x4444 : (lane & 1 ? 0x4432 : 0x3232);
                const float2 sa = lds64f(sp), sb = lds64f(sp + 128);
                mma_rank(acc, __byte_perm(__float_as_uint(sa.x), 0, sel), __byte_perm(__float_as_uint(sb.x), 0, sel), desc_b(aux));
                mo[0] = sa.y; mo[1] = sb.y;
                mo.put(pk + 32);
            }
        };

        auto halo = [&]() { const uint32_t id = fresh_tid(); return aux + (id & 96) * 128 + (id & 128) * 16 + (id & 31) * 4; };
        auto put = [&](uint32_t a, uint32_t v0, uint32_t v1) {
            asm volatile("st.shared.u32 [%0], %1;\nst.shared.u32 [%0 + 128], %2;" :: "r"(a + HALO_BYTES), "r"(v0), "r"(v1) : "memory");
        };
        auto get = [&](uint32_t a, uint32_t& v0, uint32_t& v1) {
            asm volatile("ld.shared.u32 %0, [%2];\nld.shared.u32 %1, [%2 + 128];" : "=r"(v0), "=r"(v1) : "r"(a) : "memory");
        };
        auto publish = [&](int p) { asm volatile("fence.proxy.async.shared::cta;" ::: "memory"); signal_stores(p); };
        const uint32_t zero[4] = {0, 0, 0, 0};
        auto meet = [&](int n) {
            if (n == 15 - MEET) asm volatile("{\n.reg .u32 c;\nmov.u32 c, %%clock;\nlop3.b32 c, c, %1, 1, 0x80;\nadd.u32 c, c, %0;\nbar.arrive c, 256;\n}"
                                             :: "r"(2 + wg), "r"((uint32_t)(uintptr_t)optr) : "memory");
        };
        auto mix_qk = [&]() {
            uint32_t c[2][4];
            const uint32_t a = halo();
            if (EREL) { wg_wait<0>(); release(empty1((MIXQ - 1) & 3)); }
            mbar_wait(halo_bar, 0, spins);
#pragma unroll
            for (int n = 0; n < 16; n++) {
                const int b = 1 - n / 8, h = (n & 4) / 2 + n % 2, j = n / 2 % 2;
                uint32_t* const kq = pk + 32 + 8 * h + 4 * j;
                uint32_t* const q = pk + 8 * h + 4 * b;
                mma_sync(j ? q : c[n % 2], kq, q[2 * j], q[2 * j + 1], j ? c[n % 2] : zero);
                if (b) get(a + (h * 2 + j) * 256, kq[1], kq[3]);
                meet(n);
            }
        };
        auto chunk_qk = [&](int k) {
            constexpr float LOG2E = 1.4426950408889634f;
            uint32_t* const l = pk + 32;
            Floats<16> e(pk);
            if (k == KK) {
                const uint32_t a = halo();
#pragma unroll
                for (int i = 0; i < 8; i++) put(a + i * 256, pk[33 + 4 * i], pk[35 + 4 * i]);
                publish(1);
            } else if (k == MIXQ + 1) {
                const uint32_t id = fresh_tid();
                const bool u0 = id % 32 / 4 > id % 4 * 2, u1 = id % 32 / 4 > id % 4 * 2 + 1;
                const uint32_t gone = row0(id) < 2 ? (u0 ? 0xffffu : 0u) | (u1 ? 0xffff0000u : 0u) : 0u;
#pragma unroll
                for (int n = 0; n < 8; n++) {
                    const int b = n % 2;
                    const uint32_t* const c = pk + 4 * n;
                    uint32_t v = pack_bf16(__uint_as_float(pick(u0, c[2 - 2 * b], c[2 * b])), __uint_as_float(pick(u1, c[3 - 2 * b], c[1 + 2 * b])));
                    v = mul2_bf16x2(v, 0x3e353e35u, 0x379e379eu);
                    if (!b) v = v & ~gone | 0xce6ece6eu & gone;
                    l[n] = transpose8(v);
                }
            } else if (k == MIXQ + 2) {
#pragma unroll
                for (int h = 0; h < 4; h++) {
                    uint32_t m = max_bf16x2(__byte_perm(l[2 * h], l[2 * h + 1], 0x5410), __byte_perm(l[2 * h], l[2 * h + 1], 0x7632));
                    m = max_bf16x2(m, __shfl_xor_sync(0xffffffffu, m, 1));
                    m = max_bf16x2(m, __shfl_xor_sync(0xffffffffu, m, 2));
#pragma unroll
                    for (int n = 2 * h; n < 2 * h + 2; n++) {
                        const float f = -LOG2E * (n % 2 ? bf_hi(m) : bf_lo(m));
                        e[2 * n] = ex2_fast(fmaf(bf_lo(l[n]), LOG2E, f));
                        e[2 * n + 1] = ex2_fast(fmaf(bf_hi(l[n]), LOG2E, f));
                    }
                }
                e.put(pk);
            } else if (k == MIXQ + 3) {
                uint32_t p[8];
#pragma unroll
                for (int n = 0; n < 8; n++) {
                    float sum = e[2 * n] + e[2 * n + 1];
                    sum += __shfl_xor_sync(0xffffffffu, sum, 1);
                    sum += __shfl_xor_sync(0xffffffffu, sum, 2);
                    const float r = rcp_fast(sum);
                    p[n] = pack_bf16(e[2 * n] * r, e[2 * n + 1] * r);
                }
                const uint32_t a = aux + 5 * HALO_BYTES + fresh_tid() * 16;
                sts128(a, make_uint4(p[0], p[1], p[2], p[3]));
                sts128(a + 4096, make_uint4(p[4], p[5], p[6], p[7]));
            }
        };
        auto values = [&](int h) { return pk + (h & 2) * 16 + (h & 1) * 8; };
        auto mix_pv = [&]() {
            uint32_t lo[8], hi[8];
            const uint32_t id = fresh_tid();
            const uint32_t keep = (id % 4 * 2 > id % 32 / 4 ? 0xffffu : 0u) | (id % 4 * 2 + 1 > id % 32 / 4 ? 0xffff0000u : 0u);
            const uint4 p0 = lds128(aux + 5 * HALO_BYTES + id * 16), p1 = lds128(aux + 6 * HALO_BYTES + id * 16);
            const uint32_t p[8] = {p0.x, p0.y, p0.z, p0.w, p1.x, p1.y, p1.z, p1.w};
#pragma unroll
            for (int n = 0; n < 8; n++)
                asm volatile("and.b32 %0, %2, %3;\nand.b32 %1, %2, %4;" : "=r"(lo[n]), "=r"(hi[n])
                             : "r"(p[n]), "r"(n % 2 ? keep : ~keep), "r"(n % 2 ? ~keep : keep));
            if (EREL) { wg_wait<0>(); release(empty1((MIXV - 1) & 3)); }
            mbar_wait(halo_bar, 1, spins);
#pragma unroll
            for (int n = 0; n < 16; n++) {
                const int i = (n & 8) / 2 + (n & 2) + (n & 4) / 4;
                mma_sync(pk + 4 * (n ^ 4), pk + 4 * (n ^ 4), lo[i], hi[i], zero);
                meet(n);
            }
        };
        auto chunk_pv = [&](int k) {
            if (k >= VK && k < VK + VN) {
                const uint32_t a = halo();
#pragma unroll
                for (int h = (k - VK) * 4 / VN; h < (k - VK + 1) * 4 / VN; h++) {
                    uint32_t* const w = values(h);
                    uint32_t v[8];
#pragma unroll
                    for (int i = 0; i < 8; i++) v[i] = transpose8(w[h < 2 ? (i & 1) + (i & 2) * 2 + (i & 4) / 2 : (i & 1) * 2 + (i & 2) / 2 + (i & 4)]);
#pragma unroll
                    for (int i = 0; i < 8; i++) w[i] = v[i];
                    put(a + h * 512, w[2], w[3]);
                    put(a + h * 512 + 256, w[6], w[7]);
                }
                if (k == VK + VN - 1) publish(3);
            } else if (k == MIXV - 1) {
                const uint32_t a = halo(), id = fresh_tid();
                optr = prm.pa2 + (size_t)(row0(id) + id % 4 * 4) * K2 + nslot * 128 + (id & 28) * 2;
                mbar_wait(halo_bar, 1, spins);
#pragma unroll
                for (int n = 0; n < 8; n++) {
                    uint32_t* const w = values(n / 2) + n % 2 * 4;
                    w[16] = w[0]; w[17] = w[1];
                    get(a + n * 256, w[18], w[19]);
                }
            } else if (k > MIXV && k <= MIXV + OVS) {
#pragma unroll
                for (int j = 0; j < 8; j++) {
                    if (j * OVS / 8 != k - MIXV - 1) continue;
                    Floats<15> c(pk + j / 2 * 16 + j % 2);
                    asm volatile("st.global.v4.u32 [%0], {%1,%2,%3,%4};"
                                 :: "l"(optr + ((~j & 2) * 8 + j % 2 * 2) * K2 + j / 4 * 64), "r"(pack_bf16(c[0], c[2])),
                                    "r"(pack_bf16(c[4], c[6])), "r"(pack_bf16(c[8], c[10])), "r"(pack_bf16(c[12], c[14])) : "memory");
                }
                if (k == MIXV + OVS) signal_stores(4);
            }
        };

        TRACE_SLOT(tile_slot, 16 + wg * 8);
#pragma unroll 1
        for (int t = 0; t < G1_TILES; t++) {
#pragma unroll
            for (int k = 0; k < G1_KSTEPS; k++) {
                const int s = k & 3;
                TRACE_STEP(t, k, 0);
                uint32_t other = k == MIXV && t == 3 || k == MIXQ && t == 2 ? 3 - wg : 0;
                if (k == MIXV || k == MIXQ) asm volatile("" : "+r"(other));
                mbar_wait(full1(s), (k >> 2) & 1, spins);
                if (k == 0) TRACE_S(12, t, 0);
                TRACE_STEP(t, k, 1);
                if (k == MIXV && t == 3) mix_pv();
                else if (k == MIXQ && t == 2) mix_qk();
                if (k == MIXV || k == MIXQ)
                    asm volatile("{\n.reg .pred p;\nsetp.ne.u32 p, %0, 0;\n@p bar.sync %0, 256;\n}" :: "r"(other) : "memory");
                if (wg == 1 && k == G1_KSTEPS - (t ? G1_SKEW : SK0)) asm volatile("bar.sync 1, 256;" ::: "memory");
                if (k >= G1_KSTEPS - TAIL1 && t == G1_TILES - 1) mma_step224(acc, da, db, next1(s), k);
                else mma_step(acc, da, db, next1(s), k);
                if (wg == 0 && k == G1_KSTEPS - 1) asm volatile("bar.arrive 1, 256;" ::: "memory");
                wg_wait<1>();
                if (k > 0 && !(EREL && (k == MIXV && t == 3 || k == MIXQ && t == 2))) release(empty1((k - 1) & 3));
                TRACE_STEP(t, k, 2);
                if (t == 0) chunk_ln(k);
                if (k >= 1 && k <= 8 && ((k < GV || k > GV + 3 ? 0x12 : 0x1a) >> t & 1)) {
                    chunk_geglu(k < GV ? k - 1 : (k > GV + 3 ? k - 5 : k - GV + 4));
                    if (k == 8 && t != 3) signal_stores(t + 1);
                }
                if (t == 2) chunk_qk(k);
                if (t == 3) chunk_pv(k);
                if (k == TLD && t == G1_TILES - 1) {
#pragma unroll
                    for (int i = 0; i < 2; i++) {
                        const uint4 v = ldg_stream(prm.tail + role * 512 + i * 256 + threadIdx.x, stream_policy());
                        pk[16 + 4 * i] = v.x; pk[17 + 4 * i] = v.y; pk[18 + 4 * i] = v.z; pk[19 + 4 * i] = v.w;
                    }
                }
                if (k == TLD + 3 && t == G1_TILES - 1) {
#pragma unroll
                    for (int i = 0; i < 8; i++)
                        asm volatile("shl.b32 %0, %2, 16;\nand.b32 %1, %2, 0xffff0000;" : "=r"(pk[2 * i]), "=r"(pk[2 * i + 1]) : "r"(pk[16 + i]));
                }
                if (k == 13) {
                    const uint32_t id = fresh_tid();
                    optr = prm.pa2 + (size_t)(row0(id) + (id & 28) / 2) * K2 + DM + gate_col(t, nslot) + id % 4 * 8;
                    asm volatile("" : "+l"(optr));
                }
            }
            wg_wait<0>();
            fence_regs(acc);
            release(empty1(3));
            if (t == 0) {
                Floats<2> inv(pk + 32);
#pragma unroll
                for (int i = 0; i < 128; i++) acc[i] *= inv[i / 2 % 2];
                fence_regs(acc);
            }
            if (t == G1_TILES - 1) {
                Floats<16> part(pk);
#pragma unroll
                for (int i = 0; i < 16; i++) acc[112 + i] += part[i];
                fence_regs(acc);
            }
#pragma unroll
            for (int i = 0; i < 64; i++) {
                const int e = i < 32 ? (i & ~7) * 2 + (i & 3) * 4 + (i & 4) / 2 : i * 2;
                pk[i] = pack_bf16(acc[e], acc[e + 1]);
            }
            TRACE_NEXT(tile_slot);
        }

        float accd[64], accs[64];
#pragma unroll
        for (int i = 0; i < 64; i++) accd[i] = 0.f;
#pragma unroll
        for (int u = 0; u < G2_HEAD; u++) {
            const int q = u % G2_STAGES;
            mbar_wait(full2(q), (u / G2_STAGES) & 1, spins);
            mma_step(accd, da, db, next2(q), u);
            wg_wait<1>();
            if (u > 0) release(empty2((u - 1) % G2_STAGES));
            if (u >= 1) {
                const int j = (u - 1) / 2;
#pragma unroll
                for (int i = 2 * u - 2; i < 2 * u; i++) pk[i] = geglu2(pk[i], pk[up(i)]);
                if (u % 2 == 0) store_pk(optr + (j & 1) * 16 * K2 + (j >> 1) * 32, j);
            }
            if (u == G2_HEAD - 1) signal_stores(6);
        }
        auto down = [&](int q, uint32_t phase, bool narrow) {
            mbar_wait(full2(q), phase, spins);
            if (narrow) mma_step96(accd, da, db, next2(q), 1);
            else mma_step(accd, da, db, next2(q), 1);
            wg_wait<1>();
            release(empty2((q + G2_STAGES - 1) % G2_STAGES));
        };
        down(5, 0, false);
#pragma unroll 1
        for (uint32_t r = 3; r < 9; r++) {
#pragma unroll
            for (int q = 0; q < G2_STAGES; q++) down(q, r & 1, (NAR0 - q) % NARS == 0 && r <= (NAR0 + TAIL2 * NARS - 1 - q) / G2_STAGES);
        }
        down(0, 1, false);
        down(1, 1, false);
        TRACE_NEXT(tile_slot);
#pragma unroll
        for (int i = 0; i < 64; i++) accs[i] = 0.f;
        uint32_t gk[32], xr[32];
        const uint32_t xs = aux + cw * 2048;
        const uint32_t xrow = xs + ((lane & 7) + ((lane >> 3) & 1) * 8) * 128;
        auto xaddr = [&](int j) { return xrow + (j >> 2) * 16384 + (((((j & 3) * 2) + (lane >> 4)) ^ (lane & 7)) << 4); };
#pragma unroll
        for (int u = G2_DSTEPS; u < G2_KSTEPS; u++) {
            const int q = u % G2_STAGES, v = u - G2_DSTEPS;
            mbar_wait(full2(q), (u / G2_STAGES) & 1, spins);
            if (G2_SKEW > 0 && wg == 1 && u == G2_KSTEPS - G2_SKEW) asm volatile("bar.sync 1, 256;" ::: "memory");
            mma_step(accs, da, db, next2(q), v);
            if (G2_SKEW > 0 && wg == 0 && u == G2_KSTEPS - 1) asm volatile("bar.arrive 1, 256;" ::: "memory");
            if (v == TLD2) {
                TRACE_S(32, wg, 0);
                mbar_wait(dep_bar + 24, 0, spins);
                TRACE_S(33, wg, 0);
#pragma unroll
                for (int i = 0; i < 2; i++) {
                    const uint4 w = ldg_stream(prm.tail + (NGEMM + role) * 512 + i * 256 + threadIdx.x, stream_policy());
                    gk[24 + 4 * i] = w.x; gk[25 + 4 * i] = w.y; gk[26 + 4 * i] = w.z; gk[27 + 4 * i] = w.w;
                }
            }
            const int gate = v <= 6 ? v - 1 : v - TLD2 + 3;
            if (gate >= (v <= 6 ? 0 : 6) && gate < 8) {
#pragma unroll
                for (int i = 4 * gate; i < 4 * gate + 4; i++) {
                    gk[i] = i < 24 ? silu2(accd[2 * i], accd[2 * i + 1])
                                   : silu2(accd[2 * i] + bf_lo(gk[i]), accd[2 * i + 1] + bf_hi(gk[i]));
                }
            }
            if (v == XLD) mbar_wait(x_bar, 0, spins);
            if (v >= XLD && v < XLD + 4) {
#pragma unroll
                for (int j = 2 * (v - XLD); j < 2 * (v - XLD + 1); j++)
                    asm volatile("ldmatrix.sync.aligned.m8n8.x4.shared.b16 {%0,%1,%2,%3}, [%4];"
                                 : "=r"(xr[4 * j]), "=r"(xr[4 * j + 1]), "=r"(xr[4 * j + 2]), "=r"(xr[4 * j + 3])
                                 : "r"(xaddr(j)) : "memory");
            }
            wg_wait<1>();
            if (v == 0) fence_regs(accd);
            if (u - 1 + G2_STAGES < G2_KSTEPS) release(empty2((u - 1) % G2_STAGES));
        }
        __nv_bfloat16* po = prm.pout + (row0(fresh_tid()) + (lane >> 3) * 2) * DM + nslot * 128 + 64 + (lane & 7) * 8;
        uint32_t so = xs + 16384 + (lane >> 3) * 128 + (((lane & 7) ^ (lane >> 3)) << 4);
        const int c0 = uniform(nslot * 128), c1 = uniform(row0(fresh_tid()) >> 1);
        const uint32_t xu = uniform(xs);
        asm volatile("" : "+l"(po), "+r"(so));
        wg_wait<0>();
        fence_regs(accs);
        TRACE_NEXT(tile_slot);
        TRACE_END();
#pragma unroll
        for (int j = 0; j < 8; j++) {
            uint32_t r[4];
#pragma unroll
            for (int i = 0; i < 4; i++) {
                const int e = j * 4 + i;
                asm("fma.rn.bf16x2 %0, %1, %2, %3;" : "=r"(r[i]) : "r"(pack_bf16(accs[2 * e], accs[2 * e + 1])), "r"(gk[e]), "r"(xr[e]));
            }
            asm volatile("stmatrix.sync.aligned.m8n8.x4.shared.b16 [%0], {%1,%2,%3,%4};"
                         :: "r"(xaddr(j)), "r"(r[0]), "r"(r[1]), "r"(r[2]), "r"(r[3]) : "memory");
            if (j == 3)
                asm volatile("{\n.reg .pred e;\nfence.proxy.async.shared::cta;\nbar.warp.sync 0xffffffff;\nelect.sync _|e, 0xffffffff;\n"
                    "@e cp.async.bulk.tensor.3d.global.shared::cta.bulk_group [%0, {%2, %3, %4}], [%1];\n}"
                    :: "l"(&prm.out), "r"(xu), "r"(c0), "r"(c1), "r"(wg) : "memory");
        }
        __syncwarp();
#pragma unroll
        for (int i = 0; i < 4; i++) {
            const uint4 v = lds128((so ^ (i & 1) * 64) + i * 512);
            asm volatile("st.global.v4.u32 [%0], {%1,%2,%3,%4};" :: "l"(po + i * 8 * DM), "r"(v.x), "r"(v.y), "r"(v.z), "r"(v.w) : "memory");
        }
        asm volatile("cp.async.bulk.commit_group;\ncp.async.bulk.wait_group.read 0;" ::: "memory");
        TRACE_LITE(10, clock());
        if (tid == 0) { TRACE_NEXT(tile_slot); if (wg == 1) TRACE_GT(13); TRACE_DUMP(); }
    } else {
        asm volatile("setmaxnreg.dec.sync.aligned.u32 %0;" :: "n"(AUX_REGS));
        cluster_wait();
        unsigned* const flags = prm.flags + mblk * 32;
        if (warp == 9) {
            TRACE_CLEAR(); TRACE_GT(0); TRACE_LITE(8, t0);
            if (lane == 0) {
                const unsigned epoch = __ldcg(prm.epoch + blockIdx.x * 16 + 2) + 1;
                mbar_wait(sig_bar, 0);
                TRACE(11);
                flag_add(flags + F_LN * 512);
                TRACE(42);
                flag_wait(flags + F_LN * 512, epoch * CNT_LN);
                fence_proxy_async();
                mbar_arrive(dep_bar);
                mbar_wait(sig_bar + 56, 0);
                flag_add(flags + F_LN2 * 512);
                flag_wait(flags + F_LN2 * 512, epoch * CNT_LN);
                fence_proxy_async();
                mbar_arrive(dep_bar + 40);
                TRACE(59);
                prm.epoch[blockIdx.x * 16 + 2] = epoch;
#pragma unroll 1
                for (int p = 3; p < 7; p++) {
                    mbar_wait(sig_bar + (p == 3 ? 16 : p * 8), 0);
                    TRACE_S(37, p, 4);
                    flag_add(flags + (p / 2 + 1) * 512);
                    TRACE_S(43, p, 4);
                }
            }
        } else if (warp > 9) {
            const int w = warp - 10;
            const unsigned epoch = __ldcg(prm.epoch + blockIdx.x * 16 + w) + 1;
            const uint32_t tag = 1 + (epoch & 1);
            const uint32_t at = (w ? CB : CA) >> (CIDX) * 4 & 15;
            mbar_wait(empty1(at & 3), 0);
            mbar_wait(empty1(at & 3), at >> 3);
            if (elect_one()) {
                mbar_expect_tx(cs_bar + w * 8, 16384);
                asm volatile("cp.async.bulk.tensor.2d.shared::cluster.global.mbarrier::complete_tx::bytes [%0], [%1, {%3, %5}], [%2];\n"
                    "cp.async.bulk.tensor.2d.shared::cluster.global.mbarrier::complete_tx::bytes [%0 + 8192], [%1, {%4, %5}], [%2];"
                    :: "r"(aux + w * 16384), "l"(w0), "r"(cs_bar + w * 8), "r"(nslot * 128), "r"(nslot * 128 + 64),
                       "r"(((mblk & ~1) + w) * 64) : "memory");
            }
            float cs[8];
#pragma unroll
            for (int d = 0; d < 8; d++) cs[d] = 0.f;
            const uint32_t wa = aux + w * 8192 + (lane >> 3) * 128 + (((lane & 7) ^ (lane >> 3)) << 4);
            uint4 v[9];
            auto fetch = [&](int h, uint32_t off) {
#pragma unroll
                for (int j = 0; j < 4; j++) v[h * 4 + j] = lds128((wa ^ (j & 1) * 64) + off + h * 2048 + j * 512);
            };
            auto add = [&](int h) {
#pragma unroll
                for (int j = 0; j < 4; j++) {
                    float f[8];
                    unpack8(v[h * 4 + j], f);
#pragma unroll
                    for (int d = 0; d < 8; d++) cs[d] += f[d];
                }
            };
            if (CST) { mbar_wait(empty1(CST & 3), 0); mbar_wait(empty1(CST & 3), CST >> 3); }
            mbar_wait(cs_bar, 0);

            fetch(0, 0);
#pragma unroll 1
            for (int i = 0; i < 4; i++) {
                fetch(1, (i >> 1) * 16384 + (i & 1) * 4096);
                add(0);
                if (i == 1) mbar_wait(cs_bar + 8, 0);
                fetch(0, (i + 1 & 2) * 8192 + (~i & 1) * 4096);
                add(1);
            }
#pragma unroll
            for (int d = 0; d < 4; d++)
                cs[d] = (lane & 16 ? cs[d + 4] : cs[d]) + __shfl_xor_sync(0xffffffffu, lane & 16 ? cs[d] : cs[d + 4], 16);
#pragma unroll
            for (int d = 0; d < 2; d++)
                cs[d] = (lane & 8 ? cs[d + 2] : cs[d]) + __shfl_xor_sync(0xffffffffu, lane & 8 ? cs[d] : cs[d + 2], 8);
            st_tagged(prm.colsum + (nslot * 2 + rank) * 1024 + (mblk >> 1) * 128 + w * 64 + (lane & 7) * 8 + (lane >> 3) * 2,
                      cs[0], cs[1], tag);

#pragma unroll
            for (int m = 0; m < 9; m++) v[m] = make_uint4(0, 0, 0, 0);
            const float* parts = prm.colsum + (nslot * 2 + (lane >> 4)) * 1024 + w * 64 + (lane & 15) * 4;
            const float* const rows = &prm.stats[mblk * 128 + w * 64 + lane * 2].x;
#pragma unroll 1
            for (int spins = 0; spins < (1 << 16); spins++) {
                bool missing = false;
                asm volatile("" : "+l"(parts));
#pragma unroll
                for (int m = 0; m < 9; m++) {
                    if (untagged(v[m], tag)) {
                        missing = true;
                        v[m] = ld_relaxed(m < 8 ? parts + m * 128 : rows);
                    }
                }
                if (!missing) break;
            }
            float4 c = make_float4(0.f, 0.f, 0.f, 0.f);
#pragma unroll
            for (int m = 0; m < 8; m++) {
                c.x += __uint_as_float(v[m].x ^ tag); c.y += __uint_as_float(v[m].y ^ tag);
                c.z += __uint_as_float(v[m].z ^ tag); c.w += __uint_as_float(v[m].w ^ tag);
            }
            sts128(stats + w * 512 + lane * 16, make_uint4(v[8].x ^ tag, v[8].y ^ tag, v[8].z ^ tag, v[8].w ^ tag));
            const uint32_t ca = aux + w * 8192 + (lane >> 4) * 16384 + (lane & 15) * 8;
#pragma unroll
            for (int r = 0; r < 3; r++) {
                const uint32_t lo = pack_bf16(c.x, c.y), hi = pack_bf16(c.z, c.w);
                sts64f((ca ^ r * 16) + r * 128, __uint_as_float(lo), __uint_as_float(hi));
                c.x -= bf_lo(lo); c.y -= bf_hi(lo); c.z -= bf_lo(hi); c.w -= bf_hi(hi);
            }
            asm volatile("fence.proxy.async.shared::cta;" ::: "memory");
            __syncwarp();
            if (lane == 0) {
                mbar_arrive(fold_bar);
                prm.epoch[blockIdx.x * 16 + w] = epoch;
                if (w == 0) {
                    TRACE_S(35, w, 0);
                    flag_wait(flags + F_TAIL * 512, epoch * 2 - 1);
                    mbar_arrive(x_bar + 8);
                    flag_wait(flags + F_FIRST * 512, epoch * CNT_FIRST);
                    flag_wait(flags + F_EARLY * 512, epoch * CNT_EARLY);
                    fence_proxy_async(); mbar_arrive(dep_bar + 8);
                    flag_wait(flags + F_LATE * 512, epoch * CNT_LATE);
                    fence_proxy_async(); mbar_arrive(dep_bar + 16);
                    flag_wait(flags + F_TAIL * 512, epoch * 2);
                    mbar_arrive(dep_bar + 24);
                } else {
#pragma unroll 1
                    for (int j = 0; j < 2; j++) {
                        uint8_t* const h = prm.halo + (j * NGEMM + role) * HALO_BYTES;
                        unsigned* const f = prm.flags + F_HALO * 512 + role * 32;
                        mbar_wait(sig_bar + 8 + j * 16, 0);
                        TRACE_S(38, j, 0); TRACE_S(9, j, 1);
                        asm volatile("cp.async.bulk.global.shared::cta.bulk_group [%0], [%1], %2;\n"
                            "cp.async.bulk.commit_group;\ncp.async.bulk.wait_group 0;"
                            :: "l"(h + HALO_BYTES), "r"(aux + 4 * HALO_BYTES), "n"(HALO_BYTES) : "memory");
                        fence_proxy_async();
                        TRACE_S(39, j, 0); TRACE_S(10, j, 1);
                        flag_add(f);
                        TRACE_S(40, j, 0); TRACE_S(34, j, 1);
                        if (mblk) flag_wait(f - 32, epoch * 2 - 1 + j);
                        fence_proxy_async();
                        TRACE_S(41, j, 0); TRACE_S(36, j, 1);
                        mbar_expect_tx(halo_bar, HALO_BYTES);
                        asm volatile("cp.async.bulk.shared::cluster.global.mbarrier::complete_tx::bytes [%0], [%1], %2, [%3];"
                            :: "r"(aux), "l"(mblk ? h : prm.halo), "n"(HALO_BYTES), "r"(halo_bar) : "memory");
                    }
                }
            }
        } else {
#pragma unroll
            for (int k = 1; k < G1_STAGES; k++) {
                const uint32_t sa = base + k * G1_STAGE_BYTES;
                if (PACE0 + PACE) while ((uint32_t)clock() - t0 < (k == 3 ? PACE3 : PACE0 + (k - 1) * PACE)) {}
                load_stage1(sa, sa + A_BYTES + rank * 16384, full1(k), &prm.x, w0, w0, k * 64, mblk * 64, nslot * 128,
                            nslot * 128 + 64, 0, stream_policy());
            }
            if (elect_one()) {
                prefetch_map(&prm.xn); prefetch_map(&prm.wqkv);
                prefetch_map(&prm.a2); prefetch_map(&prm.wo); prefetch_map(&prm.wd); prefetch_map(&prm.out);
            }
            auto load_x = [&]() {
                if (elect_one()) {
                    mbar_expect_tx(x_bar, 32768);
                    tma_3d(aux, &prm.x, x_bar, nslot * 128, mblk * 64, 0, stream_policy());
                    tma_3d(aux + 16384, &prm.x, x_bar, nslot * 128 + 64, mblk * 64, 0, stream_policy());
                }
                __syncwarp();
            };
            uint32_t ph = 0;
#pragma unroll 1
            for (int t = 0; t < G1_TILES; t++) {
                const int col1 = (t == 1 ? rank * DM + nslot * 128 : gate_col(t, nslot)) + 64;
                const int col0 = t == 2 ? 2 * DM + nslot * 128 + rank * 64 : col1 - 64;
                if (t == 1) { TRACE_PUT(1, c0); TRACE_PUT(2, t0); TRACE(14); mbar_wait_warp(dep_bar, 0); TRACE(3); }
#pragma unroll 1
                for (int k = t ? 0 : G1_STAGES; k < G1_KSTEPS; k++) {
                    const int s = k & 3;
                    if (t == 1 && k == 8) mbar_wait_warp(dep_bar + 40, 0);
                    if (t * 16 + k == 64 + TLD) { TRACE(61); mbar_wait_warp(x_bar + 8, 0); TRACE(63); }
                    if (t * 16 + k == (PFK)) {
                        asm volatile("{\n.reg .pred e;\nelect.sync _|e, 0xffffffff;\n"
                            "@e cp.async.bulk.prefetch.tensor.5d.L2.global [%0, {%1, %4, %4, %4, %3}];\n"
                            "@e cp.async.bulk.prefetch.tensor.5d.L2.global [%0, {%2, %4, %4, %4, %3}];\n}"
                            :: "l"(&prm.wd), "r"(nslot * 128), "r"(nslot * 128 + 64), "r"((mblk + TAIL2) * 2), "r"(0) : "memory");
                    }
                    mbar_wait_warp(empty1(s), ph);
                    const uint32_t sa = base + s * G1_STAGE_BYTES;
                    load_stage1(sa, sa + A_BYTES + rank * 16384, full1(s), t ? &prm.xn : &prm.x, t == 1 || t == 2 ? &prm.wqkv : w0,
                                t == 1 ? &prm.wqkv : w0, (k + (t >> 2) * TAIL1 & 15) * 64, mblk * 64, col0, col1, t & 3,
                                stream_policy());
                    if (s == 3) ph ^= 1;
                    if (t * 16 + k == (XK)) load_x();
                }
            }
            TRACE(4);
            mbar_wait_warp(dep_bar + 8, 0);
            TRACE(5);
            int q = 0, narrow = 0; uint32_t ph2 = 1;
#pragma unroll 1
            for (int u = 0; u < G2_KSTEPS; u++) {
                if (u == G2_LATE) { TRACE(6); mbar_wait_warp(dep_bar + 16, 0); TRACE(7); }
                const uint32_t sa = stage2(q);
                const bool down = u < G2_DSTEPS;
                const int k = !down ? u - G2_DSTEPS : (G2_NARROW >> u & 1 ? narrow++ : u + TAIL2 - narrow);
                mbar_wait_warp(u < G2_STAGES ? empty1((u * 2 + 1) / 3) : empty2(q), u < G2_STAGES ? ph : ph2);
                load_stage2(sa, sa + A_BYTES + rank * 8192, full2(q), &prm.a2, down ? &prm.wd : &prm.wo, (down ? DM : 0) + k * 64,
                            mblk * 64, nslot * 128 + rank * 64, down ? 0 : k * 2, down ? k * 2 : 0, stream_policy());
                if (++q == G2_STAGES) { q = 0; ph2 ^= 1; }
            }
            TRACE(8);
        }
    }
}

typedef CUresult (*EncodeFn)(CUtensorMap*, CUtensorMapDataType, cuuint32_t, void*, const cuuint64_t*, const cuuint64_t*,
                             const cuuint32_t*, const cuuint32_t*, CUtensorMapInterleave, CUtensorMapSwizzle,
                             CUtensorMapL2promotion, CUtensorMapFloatOOBfill);

void encode(EncodeFn fn, CUtensorMap* m, const void* ptr, int rank, const cuuint64_t* dims, const cuuint64_t* strides,
            const cuuint32_t* box) {
    const cuuint32_t es[5] = {1, 1, 1, 1, 1};
    fn(m, CU_TENSOR_MAP_DATA_TYPE_BFLOAT16, rank, const_cast<void*>(ptr), dims, strides, box, es,
       CU_TENSOR_MAP_INTERLEAVE_NONE, box[0] == 32 ? CU_TENSOR_MAP_SWIZZLE_64B : CU_TENSOR_MAP_SWIZZLE_128B,
       CU_TENSOR_MAP_L2_PROMOTION_L2_128B, CU_TENSOR_MAP_FLOAT_OOB_FILL_NONE);
}
void encode_rows(EncodeFn fn, CUtensorMap* m, const void* ptr, int cols, int box_rows, int box_parity) {
    const cuuint64_t dims[3] = {(cuuint64_t)cols, SEQ / 2, 2}, strides[2] = {(cuuint64_t)cols * 4, (cuuint64_t)cols * 2};
    const cuuint32_t box[3] = {64, (cuuint32_t)box_rows, (cuuint32_t)box_parity};
    encode(fn, m, ptr, 3, dims, strides, box);
}
void encode_w1(EncodeFn fn, CUtensorMap* m, const void* ptr, int cols) {
    const cuuint64_t dims[2] = {(cuuint64_t)cols, DM}, strides[1] = {(cuuint64_t)cols * 2};
    const cuuint32_t box[2] = {64, 64};
    encode(fn, m, ptr, 2, dims, strides, box);
}
void encode_tail(EncodeFn fn, CUtensorMap* m, const void* ptr, int rows, int cols, int n) {
    const cuuint64_t rb = cols * 2;
    const cuuint64_t dims[5] = {32, (cuuint64_t)n, (cuuint64_t)rows / (4 * n), 4, 8}, strides[4] = {rb, 4 * n * rb, n * rb, 256};
    const cuuint32_t box[5] = {32, (cuuint32_t)n, 16 / (cuuint32_t)n, 4, 8};
    encode(fn, m, (const __nv_bfloat16*)ptr + cols - 1024 + 96, 5, dims, strides, box);
}
void encode_w2(EncodeFn fn, CUtensorMap* m, const void* ptr, int rows) {
    const cuuint64_t rb = DM * 2;
    const cuuint64_t dims[5] = {DM, 2, 4, 4, (cuuint64_t)rows / 32}, strides[4] = {rb, 8 * rb, 2 * rb, 32 * rb};
    const cuuint32_t box[5] = {64, 2, 4, 4, 2};
    encode(fn, m, ptr, 5, dims, strides, box);
}
void encode_wo(EncodeFn fn, CUtensorMap* m, const void* ptr) {
    const cuuint64_t rb = DM * 2;
    const cuuint64_t dims[5] = {DM, 4, DM / 32, 2, 4}, strides[4] = {8 * rb, 32 * rb, rb, 2 * rb};
    const cuuint32_t box[5] = {64, 4, 2, 2, 4};
    encode(fn, m, ptr, 5, dims, strides, box);
}

}

extern "C" void kernel_launch(void* const* d_in, const int* in_sizes, int n_in, void* d_out, int out_size) {
    (void)in_sizes; (void)n_in; (void)out_size;
    static EncodeFn fn = nullptr;
    static Params prm;
    if (!fn) {
        cudaDriverEntryPointQueryResult st;
        cudaGetDriverEntryPoint("cuTensorMapEncodeTiled", (void**)&fn, cudaEnableDefault, &st);
        cudaGetSymbolAddress((void**)&prm.pxn, g_xn);
        cudaGetSymbolAddress((void**)&prm.pa2, g_a2);
        cudaGetSymbolAddress((void**)&prm.tail, g_tail);
        cudaGetSymbolAddress((void**)&prm.halo, g_halo);
        cudaGetSymbolAddress((void**)&prm.stats, g_stats);
        cudaGetSymbolAddress((void**)&prm.colsum, g_colsum);
        cudaGetSymbolAddress((void**)&prm.flags, g_flags);
        cudaGetSymbolAddress((void**)&prm.epoch, g_epoch);
        cudaFuncSetAttribute(fused_kernel, cudaFuncAttributeMaxDynamicSharedMemorySize, SMEM_BYTES);
    }
    encode_rows(fn, &prm.x, d_in[0], DM, 64, 2);
    encode_rows(fn, &prm.xn, prm.pxn, DM, 64, 2);
    encode_rows(fn, &prm.a2, prm.pa2, K2, 64, 2);
    encode_rows(fn, &prm.out, d_out, DM, 16, 1);
    encode_w1(fn, &prm.wqkv, d_in[1], NQKV);
    encode_w1(fn, &prm.wg, d_in[4], DF);
    encode_w1(fn, &prm.wu, d_in[5], DF);
    encode_tail(fn, &prm.wu_tail, d_in[5], DM, DF, 8);
    encode_tail(fn, &prm.wd_tail, d_in[6], DF, DM, 2);
    encode_wo(fn, &prm.wo, d_in[2]);
    encode_w2(fn, &prm.wd, d_in[6], DF);
    prm.px = (const __nv_bfloat16*)d_in[0];
    prm.pout = (__nv_bfloat16*)d_out;
    fused_kernel<<<NCTA, 384, SMEM_BYTES>>>(prm);
}
```

```cpp
#include <cuda_runtime.h>
#include <cuda_bf16.h>
#include <cuda.h>
#include <stdint.h>
#include <type_traits>

#define LNS 3
#define FS 14
#define CA 0x87658765u
#define CB 0x65876587u
#define CST 10
#define CIDX nslot
#define PACE0 900
#define PACE 425
#define PACE3 1700
#define TAIL1 12
#define TAIL2 11
#define NAR0 19
#define NARS 2
#define MIXQ 8
#define MIXV 9
#define TLD2 7
#define XLD 7
#define VK 1
#define VN 2
#define KK 2
#define EREL 0
#define MEET 4
#define OVS 4
#define GV 3
#define TOP 16
#define SK2 5
#define PFK 60 + mblk
#define XK 66 + nslot
#define TSK 2
#define TW0 9000
#define TLD 12
#define SK4 2
#define GA 3
#define GB 4

namespace {

constexpr int SEQ = 2048, DM = 1024, DF = 3584, K2 = DM + DF, NQKV = 3 * DM;
constexpr int NGEMM = 128, NCTA = 132;
constexpr int G1_STAGES = 4, G1_STAGE_BYTES = 49152, G1_KSTEPS = 16, G1_TILES = 5;
constexpr int G2_STAGES = 6, G2_STAGE_BYTES = 32768, G2_KSTEPS = 72, G2_LATE = 40, G2_DSTEPS = 56;
constexpr int G2_HEAD = 17;
constexpr int LN_STEP = LNS, FOLD_STEP = FS;
constexpr int A_BYTES = 16384;
constexpr int AUX_OFF = G1_STAGES * G1_STAGE_BYTES;
constexpr int BAR_OFF = AUX_OFF + 32768;
constexpr int SMEM_BYTES = BAR_OFF + 2816;
constexpr int G1_SKEW = 2, G2_SKEW = SK2;
constexpr int CONSUMER_REGS = 224, AUX_REGS = 56;
constexpr int HALO_BYTES = 4096;
constexpr uint64_t narrow_steps() {
    uint64_t m = 0;
    for (int i = 0; i < TAIL2; i++) m |= 1ull << NAR0 + i * NARS;
    return m;
}
constexpr uint64_t G2_NARROW = narrow_steps();
static_assert(G2_NARROW >> G2_LATE == 0 && NAR0 >= 18 && NAR0 < 18 + NARS && 6 % NARS == 0, "narrow steps use early columns");

enum { F_LN = 0, F_LN2 = 1, F_FIRST = 2, F_EARLY = 3, F_LATE = 4, F_TAIL = 5, F_HALO = 6 };
constexpr unsigned CNT_LN = 8, CNT_FIRST = 8, CNT_EARLY = 16, CNT_LATE = 8;

__device__ __align__(1024) __nv_bfloat16 g_xn[SEQ * DM];
__device__ __align__(1024) __nv_bfloat16 g_a2[SEQ * K2];
__device__ __align__(128) uint4 g_tail[2 * NGEMM * 512];
__device__ __align__(128) uint8_t g_halo[(2 * NGEMM + 1) * HALO_BYTES];
__device__ __align__(128) float2 g_stats[SEQ];
__device__ __align__(128) float g_colsum[16 * 1024];
__device__ __align__(128) unsigned g_flags[(F_HALO + 8) * 16 * 32];
__device__ __align__(128) unsigned g_epoch[NCTA * 16];

struct Params {
    const __nv_bfloat16* px;
    __nv_bfloat16 *pxn, *pa2, *pout;
    uint4* tail;
    uint8_t* halo;
    float2* stats;
    float* colsum;
    unsigned *flags, *epoch;
    unsigned long long* trace;
    CUtensorMap x, wg, wu, xn, wqkv, a2, wu_tail, wd_tail, wo, wd, out;
};

extern __shared__ __align__(1024) uint8_t smem_raw[];

#define TRACE(slot) do {} while (0)
#define TRACE_GT(slot) do {} while (0)
#define TRACE_S(slot, v, want) do {} while (0)
#define TRACE_GET(v) do {} while (0)
#define TRACE_PUT(slot, v) do {} while (0)
#define TRACE_SLOT(v, slot) do {} while (0)
#define TRACE_NEXT(v) do {} while (0)
#define TRACE_DUMP() do {} while (0)
#define TRACE_CLEAR() do {} while (0)
#define STAGE_TRACE 0
#define TRACE_END() do {} while (0)
#define TRACE_LITE(i, c) do {} while (0)
#define TRACE_STEP(t, k, i) do {} while (0)

__device__ __forceinline__ uint32_t smem_u32(const void* p) { return (uint32_t)__cvta_generic_to_shared(p); }
__device__ __forceinline__ void mbar_init(uint32_t bar, uint32_t cnt) {
    asm volatile("mbarrier.init.shared::cta.b64 [%0], %1;" :: "r"(bar), "r"(cnt) : "memory");
}
__device__ __forceinline__ void mbar_expect_tx(uint32_t bar, uint32_t bytes) {
    asm volatile("mbarrier.arrive.expect_tx.shared::cta.b64 _, [%0], %1;" :: "r"(bar), "r"(bytes) : "memory");
}
__device__ __forceinline__ void mbar_arrive(uint32_t bar) {
    asm volatile("mbarrier.arrive.shared::cta.b64 _, [%0];" :: "r"(bar) : "memory");
}
__device__ __forceinline__ bool mbar_try_wait(uint32_t bar, uint32_t parity) {
    uint32_t ok;
    asm volatile("{\n.reg .pred p;\nmbarrier.try_wait.parity.shared::cta.b64 p, [%1], %2;\nselp.u32 %0, 1, 0, p;\n}"
                 : "=r"(ok) : "r"(bar), "r"(parity) : "memory");
    return ok;
}
__device__ __forceinline__ void mbar_wait(uint32_t bar, uint32_t parity) {
#pragma unroll 1
    for (int spins = 0; !mbar_try_wait(bar, parity) && spins < (1 << 17); spins++) {}
}
__device__ __forceinline__ void mbar_wait(uint32_t bar, uint32_t parity, int& spins) {
    asm volatile("{\n.reg .pred p;\nagain:\nmbarrier.try_wait.parity.shared::cta.b64 p, [%1], %2;\n@p bra done;\n"
                 "add.s32 %0, %0, -1;\nsetp.gt.s32 p, %0, 0;\n@p bra again;\ndone:\n}" : "+r"(spins) : "r"(bar), "r"(parity) : "memory");
}
template <bool WARP = false> __device__ __forceinline__ void flag_wait(const unsigned* p, unsigned target) {
#pragma unroll 1
    for (int spins = 0; spins < (1 << 19); spins++) {
        unsigned v;
        asm volatile("ld.acquire.gpu.global.u32 %0, [%1];" : "=r"(v) : "l"(p) : "memory");
        if (WARP ? __all_sync(0xffffffffu, (int)(v - target) >= 0) : (int)(v - target) >= 0) break;
        __nanosleep(64);
    }
}
__device__ __forceinline__ void mbar_wait_warp(uint32_t bar, uint32_t parity) {
#pragma unroll 1
    for (int spins = 0; !__all_sync(0xffffffffu, mbar_try_wait(bar, parity)) && spins < (1 << 17); spins++) {}
}
__device__ __forceinline__ void flag_add(unsigned* p) {
    asm volatile("red.release.gpu.global.add.u32 [%0], 1;" :: "l"(p) : "memory");
}
__device__ __forceinline__ bool elect_one() {
    uint32_t ok;
    asm volatile("{\n.reg .pred p;\nelect.sync _|p, 0xffffffff;\nselp.u32 %0, 1, 0, p;\n}" : "=r"(ok));
    return ok;
}
__device__ __forceinline__ uint32_t pick(bool c, uint32_t a, uint32_t b) {
    uint32_t r;
    asm("{\n.reg .pred p;\nsetp.ne.b32 p, %3, 0;\nselp.b32 %0, %1, %2, p;\n}" : "=r"(r) : "r"(a), "r"(b), "r"((uint32_t)c));
    return r;
}
__device__ __forceinline__ void fence_proxy_async() { asm volatile("fence.proxy.async.global;" ::: "memory"); }
__device__ __forceinline__ uint4 lds128(uint32_t addr) {
    uint4 v;
    asm volatile("ld.shared.v4.u32 {%0,%1,%2,%3}, [%4];" : "=r"(v.x), "=r"(v.y), "=r"(v.z), "=r"(v.w) : "r"(addr) : "memory");
    return v;
}
__device__ __forceinline__ float2 lds64f(uint32_t addr) {
    float2 v;
    asm volatile("ld.shared.v2.f32 {%0,%1}, [%2];" : "=f"(v.x), "=f"(v.y) : "r"(addr) : "memory");
    return v;
}
__device__ __forceinline__ void sts128(uint32_t addr, uint4 v) {
    asm volatile("st.shared.v4.u32 [%0], {%1,%2,%3,%4};" :: "r"(addr), "r"(v.x), "r"(v.y), "r"(v.z), "r"(v.w) : "memory");
}
__device__ __forceinline__ void sts64f(uint32_t addr, float a, float b) {
    asm volatile("st.shared.v2.f32 [%0], {%1,%2};" :: "r"(addr), "f"(a), "f"(b) : "memory");
}

__device__ __forceinline__ uint64_t stream_policy() { return 0x12F0000000000000ull; }
__device__ __forceinline__ void tma_3d(uint32_t dst, const CUtensorMap* m, uint32_t bar, int c0, int c1, int c2, uint64_t pol) {
    asm volatile("cp.async.bulk.tensor.3d.shared::cluster.global.mbarrier::complete_tx::bytes.L2::cache_hint"
                 " [%0], [%1, {%3, %4, %5}], [%2], %6;"
                 :: "r"(dst), "l"(m), "r"(bar), "r"(c0), "r"(c1), "r"(c2), "l"(pol) : "memory");
}
__device__ __forceinline__ void load_stage1(uint32_t dst, uint32_t dst_b, uint32_t bar, const CUtensorMap* ma, const CUtensorMap* mb0,
                                            const CUtensorMap* mb1, int k, int row, int col0, int col1, int keep_a, uint64_t pol) {
    asm volatile("{\n.reg .pred e, p, q;\nelect.sync _|e, 0xffffffff;\nsetp.ne.and.b32 p|q, %8, 0, e;\n"
        "@p cp.async.bulk.tensor.3d.shared::cluster.global.mbarrier::complete_tx::bytes [%0], [%3, {%5, %6, %10}], [%2];\n"
        "@q cp.async.bulk.tensor.3d.shared::cluster.global.mbarrier::complete_tx::bytes.L2::cache_hint [%0], [%3, {%5, %6, %10}], [%2], %9;\n"
        "@e cp.async.bulk.tensor.2d.shared::cluster.global.mbarrier::complete_tx::bytes.multicast::cluster.L2::cache_hint"
        " [%1], [%4, {%7, %5}], [%2], %11, %9;\n"
        "@e cp.async.bulk.tensor.2d.shared::cluster.global.mbarrier::complete_tx::bytes.multicast::cluster.L2::cache_hint"
        " [%1 + 8192], [%13, {%14, %5}], [%2], %11, %9;\n"
        "@e mbarrier.arrive.expect_tx.shared::cta.b64 _, [%2], %12;\n}"
        :: "r"(dst), "r"(dst_b), "r"(bar), "l"(ma), "l"(mb0), "r"(k), "r"(row), "r"(col0), "r"(keep_a), "l"(pol), "r"(0),
           "h"((uint16_t)3), "n"(G1_STAGE_BYTES), "l"(mb1), "r"(col1) : "memory");
}
__device__ __forceinline__ void load_stage2(uint32_t dst, uint32_t dst_b, uint32_t bar, const CUtensorMap* ma, const CUtensorMap* mb,
                                            int ka, int row, int col, int kb2, int kb4, uint64_t pol) {
    asm volatile("{\n.reg .pred e;\nelect.sync _|e, 0xffffffff;\n"
        "@e cp.async.bulk.tensor.3d.shared::cluster.global.mbarrier::complete_tx::bytes.L2::cache_hint [%0], [%3, {%5, %6, %10}], [%2], %9;\n"
        "@e cp.async.bulk.tensor.5d.shared::cluster.global.mbarrier::complete_tx::bytes.multicast::cluster.L2::cache_hint"
        " [%1], [%4, {%7, %10, %13, %10, %8}], [%2], %11, %9;\n"
        "@e mbarrier.arrive.expect_tx.shared::cta.b64 _, [%2], %12;\n}"
        :: "r"(dst), "r"(dst_b), "r"(bar), "l"(ma), "l"(mb), "r"(ka), "r"(row), "r"(col), "r"(kb4), "l"(pol), "r"(0),
           "h"((uint16_t)3), "n"(G2_STAGE_BYTES), "r"(kb2) : "memory");
}
__device__ __forceinline__ uint4 ldg_stream(const void* p, uint64_t pol) {
    uint4 v;
    asm volatile("ld.global.nc.L1::no_allocate.L2::cache_hint.v4.u32 {%0,%1,%2,%3}, [%4], %5;"
                 : "=r"(v.x), "=r"(v.y), "=r"(v.z), "=r"(v.w) : "l"(p), "l"(pol));
    return v;
}
__device__ __forceinline__ void st_tagged(void* p, float a, float b, uint32_t tag) {
    asm volatile("st.relaxed.gpu.global.v2.b32 [%0], {%1,%2};"
                 :: "l"(p), "r"((__float_as_uint(a) & ~3u) | tag), "r"((__float_as_uint(b) & ~3u) | tag) : "memory");
}
__device__ __forceinline__ bool untagged(const uint4& v, uint32_t tag) {
    return ((v.x ^ tag) | (v.y ^ tag) | (v.z ^ tag) | (v.w ^ tag)) & 3;
}
__device__ __forceinline__ uint4 ld_relaxed(const void* p) {
    uint4 v;
    asm volatile("ld.relaxed.gpu.global.v4.b32 {%0,%1,%2,%3}, [%4];" : "=r"(v.x), "=r"(v.y), "=r"(v.z), "=r"(v.w) : "l"(p) : "memory");
    return v;
}
__device__ __forceinline__ void prefetch_map(const CUtensorMap* m) {
    asm volatile("prefetch.tensormap [%0];" :: "l"(m) : "memory");
}
template <int N> __device__ __forceinline__ void wg_wait() { asm volatile("wgmma.wait_group.sync.aligned %0;" :: "n"(N) : "memory"); }

__device__ __forceinline__ uint32_t desc_a(uint32_t addr) { return (addr & 0x3FFFF) >> 4 | 1 << 16; }
__device__ __forceinline__ uint32_t desc_b(uint32_t addr) { return (addr & 0x3FFFF) >> 4 | 512 << 16; }

#define R8(d, o) "+f"(d[o]), "+f"(d[o+1]), "+f"(d[o+2]), "+f"(d[o+3]), "+f"(d[o+4]), "+f"(d[o+5]), "+f"(d[o+6]), "+f"(d[o+7])
#define R32(d, o) R8(d, o), R8(d, o+8), R8(d, o+16), R8(d, o+24)
#define R64(d, o) R32(d, o), R32(d, o+32)
#define ACC00 "%0,%1,%2,%3,%4,%5,%6,%7,%8,%9,%10,%11,%12,%13,%14,%15,%16,%17,%18,%19,%20,%21,%22,%23,%24,%25,%26,%27,%28,%29,%30,%31,"\
    "%32,%33,%34,%35,%36,%37,%38,%39,%40,%41,%42,%43,%44,%45,%46,%47"
#define ACC0 ACC00 ",%48,%49,%50,%51,%52,%53,%54,%55,%56,%57,%58,%59,%60,%61,%62,%63"
#define ACC1 "%64,%65,%66,%67,%68,%69,%70,%71,%72,%73,%74,%75,%76,%77,%78,%79,%80,%81,%82,%83,%84,%85,%86,%87,%88,%89,%90,%91,%92,%93,%94,%95,"\
    "%96,%97,%98,%99,%100,%101,%102,%103,%104,%105,%106,%107,%108,%109,%110,%111"
#define ACC48 "{" ACC00 "}"
#define ACC64 "{" ACC0 "}"
#define ACC112 "{" ACC0 "," ACC1 "}"
#define ACC128 "{" ACC0 "," ACC1 ",%112,%113,%114,%115,%116,%117,%118,%119,%120,%121,%122,%123,%124,%125,%126,%127}"
#define MMA_K16(shape, acc, a, b, keep, hb) \
    "mov.b64 da, {" a ", 0x40000040};\nmov.b64 db, {" b ", " hb "};\n" \
    "wgmma.mma_async.sync.aligned." shape ".f32.bf16.bf16 " acc ", da, db, " keep ", 1, 1, 0, 1;\n"
#define MMA_NEXT(op, a, b, sa, sb) op " " a ", " a ", " sa ";\n" op " " b ", " b ", " sb ";\n"
#define MMA_STEP_B(shape, acc, a, b, na, nb, keep, hb, sb) \
    "{\n.reg .pred p, q;\n.reg .b64 da, db;\nsetp.ne.b32 p, " keep ", 0;\nsetp.eq.b32 q, 0, 0;\nwgmma.fence.sync.aligned;\n" \
    MMA_K16(shape, acc, a, b, "p", hb) MMA_NEXT("xor.b32", a, b, "2", "128") MMA_K16(shape, acc, a, b, "q", hb) MMA_NEXT("add.s32", a, b, "2", sb) \
    MMA_K16(shape, acc, a, b, "q", hb) MMA_NEXT("xor.b32", a, b, "2", "128") MMA_K16(shape, acc, a, b, "q", hb) MMA_NEXT("add.s32", a, b, na, nb) \
    "wgmma.commit_group.sync.aligned;\n}"
#define MMA_STEP(shape, acc, a, b, na, nb, keep) MMA_STEP_B(shape, acc, a, b, na, nb, keep, "0x40000040", "128")
#define MMA_ARGS "+r"(da), "+r"(db) : "r"(next / 16 - 6), "r"(next / 16 - 384), "r"(keep) : "memory"

__device__ __forceinline__ void mma_step(float (&d)[128], uint32_t& da, uint32_t& db, int next, int keep) {
    asm volatile(MMA_STEP("m64n256k16", ACC128, "%128", "%129", "%130", "%131", "%132") : R64(d, 0), R64(d, 64), MMA_ARGS);
}
__device__ __forceinline__ void mma_rank(float (&d)[128], uint32_t a0, uint32_t a1, uint32_t db) {
    asm volatile("{\n.reg .pred q;\n.reg .b64 db;\nsetp.eq.b32 q, 0, 0;\nmov.b64 db, {%131, 0x40000040};\nwgmma.fence.sync.aligned;\n"
                 "wgmma.mma_async.sync.aligned.m64n256k16.f32.bf16.bf16 " ACC128 ", {%128, %129, %130, %130}, db, q, 1, 1, 1;\n}"
                 : R64(d, 0), R64(d, 64) : "r"(a0), "r"(a1), "r"(0), "r"(db) : "memory");
}
__device__ __forceinline__ void mma_step224(float (&d)[128], uint32_t& da, uint32_t& db, int next, int keep) {
    asm volatile(MMA_STEP("m64n224k16", ACC112, "%112", "%113", "%114", "%115", "%116")
                 : R64(d, 0), R32(d, 64), R8(d, 96), R8(d, 104), MMA_ARGS);
}
__device__ __forceinline__ void mma_step(float (&d)[64], uint32_t& da, uint32_t& db, int next, int keep) {
    asm volatile(MMA_STEP("m64n128k16", ACC64, "%64", "%65", "%66", "%67", "%68") : R64(d, 0), MMA_ARGS);
}
__device__ __forceinline__ void mma_step96(float (&d)[64], uint32_t& da, uint32_t& db, int next, int keep) {
    asm volatile(MMA_STEP("m64n96k16", ACC48, "%48", "%49", "%50", "%51", "%52") : R32(d, 0), R8(d, 32), R8(d, 40), MMA_ARGS);
}
__device__ __forceinline__ void mma_step_tail(float (&d)[128], uint32_t da, uint32_t b, int keep) {
    uint32_t db = (b & 0x3FFFF) >> 4 | 256 << 16;
    const int next = 0;
    asm volatile(MMA_STEP_B("m64n256k16", ACC128, "%128", "%129", "%130", "%131", "%132", "0x80000040", "-96")
                 : R64(d, 0), R64(d, 64), MMA_ARGS);
}

__device__ __forceinline__ uint32_t pack_bf16(float lo, float hi) {
    uint32_t r; asm("cvt.rn.bf16x2.f32 %0, %1, %2;" : "=r"(r) : "f"(hi), "f"(lo)); return r;
}
__device__ __forceinline__ float bf_lo(uint32_t v) { return __uint_as_float(v << 16); }
__device__ __forceinline__ float bf_hi(uint32_t v) { return __uint_as_float(v & 0xffff0000u); }
__device__ __forceinline__ float round_bf16(float v) { return bf_lo(pack_bf16(v, 0.f)); }
__device__ __forceinline__ uint32_t mul_bf16x2(uint32_t a, uint32_t b) {
    uint32_t r; asm("mul.rn.bf16x2 %0, %1, %2;" : "=r"(r) : "r"(a), "r"(b)); return r;
}
__device__ __forceinline__ uint32_t sub_bf16x2(uint32_t a, uint32_t b) {
    uint32_t r; asm("sub.rn.bf16x2 %0, %1, %2;" : "=r"(r) : "r"(a), "r"(b)); return r;
}
__device__ __forceinline__ uint32_t mul2_bf16x2(uint32_t a, uint32_t hi, uint32_t lo) {
    uint32_t r; asm("fma.rn.bf16x2 %0, %1, %2, %3;" : "=r"(r) : "r"(a), "r"(hi), "r"(mul_bf16x2(a, lo))); return r;
}
__device__ __forceinline__ float tanh_fast(float x) { float r; asm("tanh.approx.f32 %0, %1;" : "=f"(r) : "f"(x)); return r; }
__device__ __forceinline__ float gelu_twice(float g) {
    return fmaf(g, tanh_fast(fmaf(g * g, 0.044715f * 0.7978845608f, 0.7978845608f) * g), g);
}
__device__ __forceinline__ uint32_t geglu2(uint32_t g2, uint32_t u2) {
    return mul_bf16x2(pack_bf16(gelu_twice(bf_lo(g2)), gelu_twice(bf_hi(g2))), u2);
}
__device__ __forceinline__ uint32_t silu2(float lo, float hi) {
    const uint32_t h = mul_bf16x2(pack_bf16(lo, hi), 0x3e803e80u);
    return pack_bf16(fmaf(bf_lo(h), tanh_fast(bf_lo(h)), bf_lo(h)), fmaf(bf_hi(h), tanh_fast(bf_hi(h)), bf_hi(h)));
}
__device__ __forceinline__ float ex2_fast(float x) { float r; asm("ex2.approx.ftz.f32 %0, %1;" : "=f"(r) : "f"(x)); return r; }
__device__ __forceinline__ void unpack8(uint4 v, float (&f)[8]) {
    f[0] = bf_lo(v.x); f[1] = bf_hi(v.x); f[2] = bf_lo(v.y); f[3] = bf_hi(v.y);
    f[4] = bf_lo(v.z); f[5] = bf_hi(v.z); f[6] = bf_lo(v.w); f[7] = bf_hi(v.w);
}
template <int N> __device__ __forceinline__ void fence_regs(float (&d)[N]) {
#pragma unroll
    for (int i = 0; i < N; i++) asm volatile("" : "+f"(d[i]) :: "memory");
}

__device__ __forceinline__ float rcp_fast(float x) { float r; asm("rcp.approx.ftz.f32 %0, %1;" : "=f"(r) : "f"(x)); return r; }
__device__ __forceinline__ float sqrt_fast(float x) { float r; asm("sqrt.approx.ftz.f32 %0, %1;" : "=f"(r) : "f"(x)); return r; }
__device__ __forceinline__ uint32_t max_bf16x2(uint32_t a, uint32_t b) {
    uint32_t r; asm("max.bf16x2 %0, %1, %2;" : "=r"(r) : "r"(a), "r"(b)); return r;
}
__device__ __forceinline__ uint32_t transpose8(uint32_t a) {
    uint32_t r; asm volatile("movmatrix.sync.aligned.m8n8.trans.b16 %0, %1;" : "=r"(r) : "r"(a)); return r;
}
__device__ __forceinline__ void mma_sync(uint32_t* d, const uint32_t* a, uint32_t b0, uint32_t b1, const uint32_t* c) {
    asm volatile("mma.sync.aligned.m16n8k16.row.col.f32.bf16.bf16.f32 {%0,%1,%2,%3}, {%4,%5,%6,%7}, {%8,%9}, {%10,%11,%12,%13};"
        : "=r"(d[0]), "=r"(d[1]), "=r"(d[2]), "=r"(d[3])
        : "r"(a[0]), "r"(a[1]), "r"(a[2]), "r"(a[3]), "r"(b0), "r"(b1), "r"(c[0]), "r"(c[1]), "r"(c[2]), "r"(c[3]));
}
template <int N> struct Floats {
    float f[N];
    __device__ __forceinline__ Floats() {}
    __device__ __forceinline__ Floats(const uint32_t* p) {
#pragma unroll
        for (int i = 0; i < N; i++) asm("mov.b32 %0, %1;" : "=f"(f[i]) : "r"(p[i]));
    }
    __device__ __forceinline__ void put(uint32_t* p) const {
#pragma unroll
        for (int i = 0; i < N; i++) asm("mov.b32 %0, %1;" : "=r"(p[i]) : "f"(f[i]));
    }
    __device__ __forceinline__ float& operator[](int i) { return f[i]; }
};
__device__ __forceinline__ uint32_t fresh_tid() { uint32_t r; asm volatile("mov.u32 %0, %%tid.x;" : "=r"(r)); return r; }
template <typename T> __device__ __forceinline__ T uniform(T v) { return __shfl_sync(0xffffffffu, v, 0); }

__device__ __forceinline__ void tail_gemm(const Params& prm, uint32_t base, uint32_t t0, unsigned epoch, int grp, int warp, int lane) {
    const uint32_t full = base + BAR_OFF, empty = full + 320, sig = full + 192, dep = full + 256;
    unsigned* const flags = prm.flags + grp * 128;
    if (warp >= 8) asm volatile("setmaxnreg.dec.sync.aligned.u32 %0;" :: "n"(AUX_REGS));
    if (warp == 8) {
        if (elect_one()) { prefetch_map(&prm.xn); prefetch_map(&prm.wu_tail); prefetch_map(&prm.a2); prefetch_map(&prm.wd_tail); }
        auto load_w = [&](int i, const CUtensorMap* m, int k) {
            asm volatile("{\n.reg .pred e;\nelect.sync _|e, 0xffffffff;\n"
                "@e cp.async.bulk.tensor.5d.shared::cluster.global.mbarrier::complete_tx::bytes [%0], [%2, {%4, %4, %3, %4, %4}], [%1];\n"
                "@e mbarrier.arrive.expect_tx.shared::cta.b64 _, [%1], %5;\n}"
                :: "r"(base + (i & 3) * G1_STAGE_BYTES + A_BYTES), "r"(full + (i & 3) * 8), "l"(m), "r"(k), "r"(0),
                   "n"(G1_STAGE_BYTES) : "memory");
        };
        while ((uint32_t)clock() - t0 < TW0) {}
#pragma unroll 1
        for (int i = 0; i < 4; i++) load_w(i, &prm.wu_tail, i * 2);
        flag_wait<true>(flags + F_LN * 512 + (lane & 3) * 32, epoch * CNT_LN);
        fence_proxy_async();
        TRACE(62);
#pragma unroll 1
        for (int p = 0, i = 0; p < 8; p++) {
            const bool first = p < 4;
            if (p == 4) mbar_wait_warp(dep + 8, 0);
#pragma unroll 1
            for (int k = 0; k < (first ? TAIL1 : TAIL2); k++, i++) {
                if (i == 8) mbar_wait_warp(dep, 0);
                mbar_wait_warp(empty + (i & 3) * 8, ~i >> 2 & 1);
                asm volatile("{\n.reg .pred e;\nelect.sync _|e, 0xffffffff;\n"
                    "@e cp.async.bulk.tensor.3d.shared::cluster.global.mbarrier::complete_tx::bytes [%0], [%2, {%3, %4, %5}], [%1];\n}"
                    :: "r"(base + (i & 3) * G1_STAGE_BYTES), "r"(full + (i & 3) * 8), "l"(first ? &prm.xn : &prm.a2),
                       "r"((first ? 0 : DM) + k * 64), "r"(grp * 256 + (p & 3) * 64), "r"(0) : "memory");
                if (i >= 4) load_w(i, first ? &prm.wu_tail : &prm.wd_tail, first ? k * 2 : k * 8);
            }
        }
    } else if (warp == 9) {
#pragma unroll 1
        for (int j = 0; j < 2; j++) {
            flag_wait<true>(flags + (F_LN2 + j) * 512 + (lane & 3) * 32, epoch * CNT_LN);
            fence_proxy_async();
            __syncwarp();
            if (lane == 0) mbar_arrive(dep + j * 8);
        }
    } else if (warp == 10 && lane == 0) {
#pragma unroll 1
        for (int p = 0; p < 8; p++) {
            mbar_wait(sig + p * 8, 0);
            flag_add(flags + F_TAIL * 512 + (p & 3) * 32);
            TRACE_S(50, p, 3); TRACE_S(51, p, 7);
        }
        prm.epoch[blockIdx.x * 16] = epoch;
        TRACE_DUMP();
    }
    if (warp >= 8) return;
    asm volatile("setmaxnreg.inc.sync.aligned.u32 %0;" :: "n"(CONSUMER_REGS) : "memory");
    const uint32_t da = desc_a(base + (warp >> 2) * 8192);
    uint4* out = prm.tail;
    float acc[128];
    uint32_t pk[64];
    int i = 0;
    auto release = [&]() { if ((threadIdx.x & 127) == 0) mbar_arrive(empty + (i - 1 & 3) * 8); };
    auto store = [&](int j) {
        asm volatile("st.global.v4.u32 [%0], {%1,%2,%3,%4};" :: "l"(out + j / 2 * 8192 + j % 2 * 256),
                     "r"(pk[4 * j]), "r"(pk[4 * j + 1]), "r"(pk[4 * j + 2]), "r"(pk[4 * j + 3]) : "memory");
    };
    auto step = [&](int k, int left) {
        mbar_wait(full + (i & 3) * 8, i >> 2 & 1);
        TRACE_S(45, warp * 128 + i, 0);
        if (warp >= 4 && left == TSK) asm volatile("bar.sync 1, 256;" ::: "memory");
        mma_step_tail(acc, da + (i & 3) * (G1_STAGE_BYTES / 16), base + A_BYTES + (i & 3) * G1_STAGE_BYTES, k);
        if (warp < 4 && left == 1) asm volatile("bar.arrive 1, 256;" ::: "memory");
        wg_wait<1>();
        if (k) release();
        i++;
    };
#pragma unroll
    for (int j = 0; j < 128; j++) asm volatile("mov.b32 %0, 0;" : "=f"(acc[j]));
#pragma unroll
    for (int j = 0; j < 64; j++) asm volatile("mov.b32 %0, 0;" : "=r"(pk[j]));
#pragma unroll 1
    for (int p = 0; p < 8; p++) {
        step(0, 0);
#pragma unroll 1
        for (int left = (p < 4 ? TAIL1 : TAIL2) - 1, n = p ? 8 : 0; left > 0; left--) {
            if (n > 0) { store(0); store(1); }
#pragma unroll
            for (int j = 8; j < 64; j++) asm volatile("mov.b32 %0, %1;" : "=r"(pk[j - 8]) : "r"(pk[j]));
            out += 8192;
            __syncwarp();
            if (--n == 0 && lane == 0) mbar_arrive(sig + p * 8 - 8);
            step(1, left);
        }
        wg_wait<0>();
        fence_regs(acc);
        release();
        TRACE_S(46, p + warp * 8, 32); TRACE_S(47, p + warp * 8, 33); TRACE_S(48, p + warp * 8, 34); TRACE_S(49, p + warp * 8, 35);
        TRACE_S(53, p + warp * 8, 36); TRACE_S(54, p + warp * 8, 37); TRACE_S(55, p + warp * 8, 38); TRACE_S(56, p + warp * 8, 39);
#pragma unroll
        for (int j = 0; j < 64; j++) pk[j] = pack_bf16(acc[2 * j], acc[2 * j + 1]);
        out = prm.tail + p / 4 * NGEMM * 512 + (grp * 4 + p % 4) * 512 + threadIdx.x;
    }
#pragma unroll
    for (int j = 0; j < 16; j++) store(j);
    __syncwarp();
    TRACE_S(58, warp, 4);
    if (lane == 0) mbar_arrive(sig + 56);
}

__device__ __forceinline__ int gate_col(int t, int nslot) { return t == 2 ? 960 + nslot * 64 : max(t * 1024 - 1536, 0) + nslot * 128; }

struct Role {
    int rank, role, mblk, nslot;
    __device__ __forceinline__ Role() {
        uint32_t id;
        asm volatile("mov.u32 %0, %%ctaid.x;" : "=r"(id));
        const uint32_t cl = id / 2;
        rank = id & 1;
        role = pick(cl < 4, 32 + cl * 8, cl - 8 + max(4u, (cl - 1) * 37 >> 8)) * 2 + rank;
        mblk = role & 15; nslot = role >> 4;
    }
};

__global__ void __cluster_dims__(2, 1, 1) __launch_bounds__(384, 1)
fused_kernel(const __grid_constant__ Params prm) {
    TRACE_GET(c0);
    const uint32_t base = smem_u32(smem_raw) & ~1023u;
    const uint32_t bars = base + BAR_OFF;
    auto full1 = [&](int s) { return bars + s * 8; };
    auto empty1 = [&](int s) { return bars + 32 + s * 8; };
    auto full2 = [&](int s) { return bars + 64 + s * 8; };
    auto empty2 = [&](int s) { return bars + 128 + s * 8; };
    const uint32_t sig_bar = bars + 192, dep_bar = bars + 256, cs_bar = bars + 304, fold_bar = bars + 320, x_bar = bars + 352;
    const uint32_t halo_bar = dep_bar + 32;
    const uint32_t stats = bars + 1536;
    auto stage2 = [&](int q) { return base + q * G2_STAGE_BYTES; };
    const uint32_t aux = base + AUX_OFF;

    asm volatile("{\n.reg .pred p;\nsetp.eq.u32 p, %1, 0;\n@p mbarrier.init.shared::cta.b64 [%0], 1;\n"
        "fence.mbarrier_init.release.cluster;\nbarrier.cluster.arrive.relaxed.aligned;\n}" :: "r"(bars), "r"(threadIdx.x) : "memory");
    const int warp = __shfl_sync(0xffffffffu, threadIdx.x >> 5, 0);
    auto cluster_wait = []() { asm volatile("barrier.cluster.wait.acquire.aligned;" ::: "memory"); };
    if ((warp | (blockIdx.x & NGEMM)) == 8) {
        const Role r;
        asm volatile("{\n.reg .pred e;\nelect.sync _|e, 0xffffffff;\n"
            "@e prefetch.tensormap [%0];\n@e prefetch.tensormap [%1];\n}" :: "l"(&prm.x), "l"(&prm.wg + r.rank) : "memory");
        cluster_wait();
        load_stage1(base, base + A_BYTES + r.rank * 16384, full1(0), &prm.x, &prm.wg + r.rank, &prm.wg + r.rank, 0, r.mblk * 64,
                    r.nslot * 128, r.nslot * 128 + 64, 0, stream_policy());
    } else {
        cluster_wait();
    }
    const uint32_t t0 = clock();
    asm volatile("{\n.reg .pred e, q;\nelect.sync _|e, 0xffffffff;\nsetp.ne.and.u32 q, %2, 0, e;\n"
        "@q mbarrier.init.shared::cta.b64 [%0], %1;\n@e mbarrier.init.shared::cta.b64 [%0 + 8], %1;\n"
        "@e mbarrier.init.shared::cta.b64 [%0 + 16], %1;\n@e mbarrier.init.shared::cta.b64 [%0 + 24], %1;\n"
        "fence.mbarrier_init.release.cluster;\nbarrier.cluster.arrive.relaxed.aligned;\n}"
        :: "r"(bars + warp * 32), "r"(1 << (0x10fa08 >> warp * 2 & 3)), "r"(warp) : "memory");
    const int lane = threadIdx.x & 31;
    const Role me;
    const int rank = me.rank, role = me.role, mblk = me.mblk, nslot = me.nslot;
    const CUtensorMap* const w0 = &prm.wg + rank;

    if (blockIdx.x >= NGEMM) {
        if (warp == 9) { TRACE_CLEAR(); TRACE_GT(0); TRACE_PUT(1, c0); }
        cluster_wait();
        const uint32_t seen = __ldcg(prm.epoch + blockIdx.x * 16);
        tail_gemm(prm, base, t0, seen + 1, blockIdx.x - NGEMM, warp, lane);
    } else if (warp < 8) {
        asm volatile("setmaxnreg.inc.sync.aligned.u32 %0;" :: "n"(CONSUMER_REGS));
        const int wg = __shfl_sync(0xffffffffu, threadIdx.x >> 7, 0);
        const int cw = threadIdx.x >> 5;
        const int tid = threadIdx.x & 127;
        int spins = 1 << 18;
        float acc[128];
        uint32_t pk[64];
#pragma unroll
        for (int i = 0; i < 64; i++) asm volatile("mov.b32 %0, 0;" : "=r"(pk[i]));
#pragma unroll
        for (int i = 0; i < 128; i++) asm volatile("mov.b32 %0, 0;" : "=f"(acc[i]));
        cluster_wait();

        auto row0 = [&](uint32_t id) { return mblk * 128 + (id & 96) + wg; };
        __nv_bfloat16* optr = prm.pxn + (mblk * 128 + nslot * 16 + cw * 2) * DM + lane * 8;
        uint32_t da = desc_a(base + wg * 8192), db = desc_b(base + A_BYTES);
        auto next1 = [](int s) { return ((s + 1) % G1_STAGES - s) * G1_STAGE_BYTES; };
        auto next2 = [](int q) { return ((q + 1) % G2_STAGES - q) * G2_STAGE_BYTES; };
        uint32_t peer_bars;
        asm volatile("mapa.shared::cluster.u32 %0, %1, %2;" : "=r"(peer_bars) : "r"(bars), "r"(tid & 1));
        if (tid >= 2) peer_bars = 0;
        auto release = [&](uint32_t bar) {
            if (peer_bars) asm volatile("mbarrier.arrive.shared::cluster.b64 _, [%0];" :: "r"(peer_bars + (bar - bars)) : "memory");
        };
        auto up = [](int i) { return 32 + (i & 24) + (i & 3) * 2 + (i >> 2 & 1); };
        auto store_pk = [&](__nv_bfloat16* p, int j) {
            asm volatile("st.global.v4.u32 [%0], {%1,%2,%3,%4};"
                         :: "l"(p), "r"(pk[4 * j]), "r"(pk[4 * j + 1]), "r"(pk[4 * j + 2]), "r"(pk[4 * j + 3]) : "memory");
        };
        auto chunk_geglu = [&](int j) {
#pragma unroll
            for (int i = 4 * j; i < 4 * j + 4; i++) pk[i] = geglu2(pk[i], pk[up(i)]);
            store_pk(optr + (j & 1) * 16 * K2 + (j >> 1) * 32, j);
        };
        auto signal_stores = [&](int p) { __syncwarp(); if (lane == 0) mbar_arrive(sig_bar + p * 8); };

        auto chunk_ln = [&](int k) {
            Floats<6> mo(pk + 32);
            if (k == 0) {
                const uint4* xp = reinterpret_cast<const uint4*>(prm.px + (optr - prm.pxn));
                pk[38] = __ldcg(prm.epoch + blockIdx.x * 16 + 2);
#pragma unroll
                for (int i = 0; i < 8; i++) {
                    const uint4 v = ldg_stream(xp + i * 32, stream_policy());
                    pk[4 * i] = v.x; pk[4 * i + 1] = v.y; pk[4 * i + 2] = v.z; pk[4 * i + 3] = v.w;
                }
            } else if (k >= LN_STEP && k < LN_STEP + 3) {
                if (k == LN_STEP) {
                    mo[0] = bf_lo(uniform(pk[0])); mo[1] = bf_lo(uniform(pk[16]));
                    mo[2] = mo[3] = mo[4] = mo[5] = 0.f;
                }
#pragma unroll
                for (int i = (k - LN_STEP) * 11; i < (k - LN_STEP) * 11 + 11 && i < 32; i++) {
                    const int r = i & 1;
                    const uint32_t w = pk[r * 16 + i / 2];
                    const float lo = bf_lo(w) - mo[r], hi = bf_hi(w) - mo[r];
                    mo[2 + r] += lo + hi;
                    mo[4 + r] = fmaf(hi, hi, fmaf(lo, lo, mo[4 + r]));
                }
                mo.put(pk + 32);
            } else if (k == LN_STEP + 3) {
                const bool second = lane & 16;
                float m1 = (second ? mo[3] : mo[2]) + __shfl_xor_sync(0xffffffffu, second ? mo[2] : mo[3], 16);
                float m2 = (second ? mo[5] : mo[4]) + __shfl_xor_sync(0xffffffffu, second ? mo[4] : mo[5], 16);
#pragma unroll
                for (int o = 8; o > 0; o >>= 1) {
                    m1 += __shfl_xor_sync(0xffffffffu, m1, o);
                    m2 += __shfl_xor_sync(0xffffffffu, m2, o);
                }
                m1 *= 1.f / DM;
                const float var = fmaxf(fmaf(-m1, m1, m2 * (1.f / DM)), 0.f);
                const float mean = round_bf16((second ? mo[1] : mo[0]) + m1);
                const float inv = rcp_fast(round_bf16(sqrt_fast(round_bf16(round_bf16(var) + 1e-5f))));
                if ((lane & 15) == 0) st_tagged(prm.stats + (uint32_t)(optr - prm.pxn) / DM + second, -mean, inv, 2 - (pk[38] & 1));
                const uint32_t split = pack_bf16(inv - round_bf16(inv), inv);
#pragma unroll
                for (int r = 0; r < 2; r++) {
                    const uint32_t f = __shfl_sync(0xffffffffu, split, r * 16);
                    pk[32 + 3 * r] = __byte_perm(__shfl_sync(0xffffffffu, __float_as_uint(mean), r * 16), 0, 0x3232);
                    pk[33 + 3 * r] = __byte_perm(f, 0, 0x3232);
                    pk[34 + 3 * r] = __byte_perm(f, 0, 0x1010);
                }
            } else if (k >= LN_STEP + 4 && k < LN_STEP + 8) {
#pragma unroll
                for (int i = k - LN_STEP - 4; i < 8; i += 4) {
                    const uint32_t* n = pk + 32 + i / 4 * 3;
#pragma unroll
                    for (int j = 4 * i; j < 4 * i + 4; j++) pk[j] = mul2_bf16x2(sub_bf16x2(pk[j], n[0]), n[1], n[2]);
                    store_pk(optr + i * 256, i);
                }
                if (k == LN_STEP + 5 || k == LN_STEP + 7) signal_stores(k == LN_STEP + 5 ? 0 : 7);
            } else if (k == FOLD_STEP) {
                mbar_wait(fold_bar, 0, spins);
                const uint32_t id = fresh_tid(), sp = stats + (id & 96) * 8 + (id & 28) * 4 + wg * 8;
                const uint32_t sel = lane & 2 ? 0x4444 : (lane & 1 ? 0x4432 : 0x3232);
                const float2 sa = lds64f(sp), sb = lds64f(sp + 128);
                mma_rank(acc, __byte_perm(__float_as_uint(sa.x), 0, sel), __byte_perm(__float_as_uint(sb.x), 0, sel), desc_b(aux));
                mo[0] = sa.y; mo[1] = sb.y;
                mo.put(pk + 32);
            }
        };

        auto halo = [&]() { const uint32_t id = fresh_tid(); return aux + (id & 96) * 128 + (id & 128) * 16 + (id & 31) * 4; };
        auto put = [&](uint32_t a, uint32_t v0, uint32_t v1) {
            asm volatile("st.shared.u32 [%0], %1;\nst.shared.u32 [%0 + 128], %2;" :: "r"(a + HALO_BYTES), "r"(v0), "r"(v1) : "memory");
        };
        auto get = [&](uint32_t a, uint32_t& v0, uint32_t& v1) {
            asm volatile("ld.shared.u32 %0, [%2];\nld.shared.u32 %1, [%2 + 128];" : "=r"(v0), "=r"(v1) : "r"(a) : "memory");
        };
        auto publish = [&](int p) { asm volatile("fence.proxy.async.shared::cta;" ::: "memory"); signal_stores(p); };
        const uint32_t zero[4] = {0, 0, 0, 0};
        auto meet = [&](int n, int k, uint32_t id) {
            if (n == 15 - MEET)
                asm volatile("{\n.reg .b32 c;\nmov.u32 c, %%clock;\nbar.arrive %1, 256;\nlop3.b32 %0, %0, c, 1, 0x70;\n}"
                             : "+r"(peer_bars) : "r"(2 + id / 128) : "memory");
            if (n == 15) {
                asm volatile("{\n.reg .b32 c;\nmov.u32 c, %%clock;\nbar.sync %1, 256;\nlop3.b32 %0, %0, c, 1, 0x70;\n}"
                             : "+r"(peer_bars) : "r"(3 - id / 128) : "memory");
                mma_step(acc, da, db, next1(k & 3), k);
                asm volatile("// batch step");
            }
        };
        auto mix_qk = [&]() {
            uint32_t c[2][4];
            const uint32_t a = halo(), id = fresh_tid();
            if (EREL) { wg_wait<0>(); release(empty1((MIXQ - 1) & 3)); }
            mbar_wait(halo_bar, 0, spins);
#pragma unroll
            for (int n = 0; n < 16; n++) {
                const int b = 1 - n / 8, h = (n & 4) / 2 + n % 2, j = n / 2 % 2;
                uint32_t* const kq = pk + 32 + 8 * h + 4 * j;
                uint32_t* const q = pk + 8 * h + 4 * b;
                mma_sync(j ? q : c[n % 2], kq, q[2 * j], q[2 * j + 1], j ? c[n % 2] : zero);
                if (b) get(a + (h * 2 + j) * 256, kq[1], kq[3]);
                meet(n, MIXQ, id);
            }
        };
        auto chunk_qk = [&](int k) {
            constexpr float LOG2E = 1.4426950408889634f;
            uint32_t* const l = pk + 32;
            Floats<16> e(pk);
            if (k == KK) {
                const uint32_t a = halo();
#pragma unroll
                for (int i = 0; i < 8; i++) put(a + i * 256, pk[33 + 4 * i], pk[35 + 4 * i]);
                publish(1);
            } else if (k == MIXQ + 1) {
                const uint32_t id = fresh_tid();
                const bool u0 = id % 32 / 4 > id % 4 * 2, u1 = id % 32 / 4 > id % 4 * 2 + 1;
                const uint32_t gone = row0(id) < 2 ? (u0 ? 0xffffu : 0u) | (u1 ? 0xffff0000u : 0u) : 0u;
#pragma unroll
                for (int n = 0; n < 8; n++) {
                    const int b = n % 2;
                    const uint32_t* const c = pk + 4 * n;
                    uint32_t v = pack_bf16(__uint_as_float(pick(u0, c[2 - 2 * b], c[2 * b])), __uint_as_float(pick(u1, c[3 - 2 * b], c[1 + 2 * b])));
                    v = mul2_bf16x2(v, 0x3e353e35u, 0x379e379eu);
                    if (!b) v = v & ~gone | 0xce6ece6eu & gone;
                    l[n] = transpose8(v);
                }
            } else if (k == MIXQ + 2) {
#pragma unroll
                for (int h = 0; h < 4; h++) {
                    uint32_t m = max_bf16x2(__byte_perm(l[2 * h], l[2 * h + 1], 0x5410), __byte_perm(l[2 * h], l[2 * h + 1], 0x7632));
                    m = max_bf16x2(m, __shfl_xor_sync(0xffffffffu, m, 1));
                    m = max_bf16x2(m, __shfl_xor_sync(0xffffffffu, m, 2));
#pragma unroll
                    for (int n = 2 * h; n < 2 * h + 2; n++) {
                        const float f = -LOG2E * (n % 2 ? bf_hi(m) : bf_lo(m));
                        e[2 * n] = ex2_fast(fmaf(bf_lo(l[n]), LOG2E, f));
                        e[2 * n + 1] = ex2_fast(fmaf(bf_hi(l[n]), LOG2E, f));
                    }
                }
                e.put(pk);
            } else if (k == MIXQ + 3) {
                uint32_t p[8];
#pragma unroll
                for (int n = 0; n < 8; n++) {
                    float sum = e[2 * n] + e[2 * n + 1];
                    sum += __shfl_xor_sync(0xffffffffu, sum, 1);
                    sum += __shfl_xor_sync(0xffffffffu, sum, 2);
                    const float r = rcp_fast(sum);
                    p[n] = pack_bf16(e[2 * n] * r, e[2 * n + 1] * r);
                }
                const uint32_t a = aux + 5 * HALO_BYTES + fresh_tid() * 16;
                sts128(a, make_uint4(p[0], p[1], p[2], p[3]));
                sts128(a + 4096, make_uint4(p[4], p[5], p[6], p[7]));
            }
        };
        auto values = [&](int h) { return pk + (h & 2) * 16 + (h & 1) * 8; };
        auto mix_pv = [&]() {
            uint32_t lo[8], hi[8];
            const uint32_t id = fresh_tid();
            const uint32_t keep = (id % 4 * 2 > id % 32 / 4 ? 0xffffu : 0u) | (id % 4 * 2 + 1 > id % 32 / 4 ? 0xffff0000u : 0u);
            const uint4 p0 = lds128(aux + 5 * HALO_BYTES + id * 16), p1 = lds128(aux + 6 * HALO_BYTES + id * 16);
            const uint32_t p[8] = {p0.x, p0.y, p0.z, p0.w, p1.x, p1.y, p1.z, p1.w};
#pragma unroll
            for (int n = 0; n < 8; n++)
                asm volatile("and.b32 %0, %2, %3;\nand.b32 %1, %2, %4;" : "=r"(lo[n]), "=r"(hi[n])
                             : "r"(p[n]), "r"(n % 2 ? keep : ~keep), "r"(n % 2 ? ~keep : keep));
            if (EREL) { wg_wait<0>(); release(empty1((MIXV - 1) & 3)); }
            mbar_wait(halo_bar, 1, spins);
#pragma unroll
            for (int n = 0; n < 16; n++) {
                const int i = (n & 8) / 2 + (n & 2) + (n & 4) / 4;
                mma_sync(pk + 4 * (n ^ 4), pk + 4 * (n ^ 4), lo[i], hi[i], zero);
                meet(n, MIXV, id);
            }
        };
        auto chunk_pv = [&](int k) {
            if (k >= VK && k < VK + VN) {
                const uint32_t a = halo();
#pragma unroll
                for (int h = (k - VK) * 4 / VN; h < (k - VK + 1) * 4 / VN; h++) {
                    uint32_t* const w = values(h);
                    uint32_t v[8];
#pragma unroll
                    for (int i = 0; i < 8; i++) v[i] = transpose8(w[h < 2 ? (i & 1) + (i & 2) * 2 + (i & 4) / 2 : (i & 1) * 2 + (i & 2) / 2 + (i & 4)]);
#pragma unroll
                    for (int i = 0; i < 8; i++) w[i] = v[i];
                    put(a + h * 512, w[2], w[3]);
                    put(a + h * 512 + 256, w[6], w[7]);
                }
                if (k == VK + VN - 1) publish(3);
            } else if (k == MIXV - 1) {
                const uint32_t a = halo(), id = fresh_tid();
                optr = prm.pa2 + (size_t)(row0(id) + id % 4 * 4) * K2 + nslot * 128 + (id & 28) * 2;
                mbar_wait(halo_bar, 1, spins);
#pragma unroll
                for (int n = 0; n < 8; n++) {
                    uint32_t* const w = values(n / 2) + n % 2 * 4;
                    w[16] = w[0]; w[17] = w[1];
                    get(a + n * 256, w[18], w[19]);
                }
            } else if (k > MIXV && k <= MIXV + OVS) {
#pragma unroll
                for (int j = 0; j < 8; j++) {
                    if (j * OVS / 8 != k - MIXV - 1) continue;
                    Floats<15> c(pk + j / 2 * 16 + j % 2);
                    asm volatile("st.global.v4.u32 [%0], {%1,%2,%3,%4};"
                                 :: "l"(optr + ((~j & 2) * 8 + j % 2 * 2) * K2 + j / 4 * 64), "r"(pack_bf16(c[0], c[2])),
                                    "r"(pack_bf16(c[4], c[6])), "r"(pack_bf16(c[8], c[10])), "r"(pack_bf16(c[12], c[14])) : "memory");
                }
                if (k == MIXV + OVS) signal_stores(4);
            }
        };

        TRACE_SLOT(tile_slot, 16 + wg * 8);
#pragma unroll 1
        for (int t = 0; t < G1_TILES; t++) {
#pragma unroll
            for (int k = 0; k < G1_KSTEPS; k++) {
                const int s = k & 3;
                if (k % TOP == 0) asm volatile("" : "+r"(t));
                TRACE_STEP(t, k, 0);
                mbar_wait(full1(s), (k >> 2) & 1, spins);
                if (k == 0) TRACE_S(12, t, 0);
                TRACE_STEP(t, k, 1);
                if (wg == 1 && k == G1_KSTEPS - (t == 4 ? SK4 : G1_SKEW)) asm volatile("bar.sync 1, 256;" ::: "memory");
                if (k == MIXV && t == 3) mix_pv();
                else if (k == MIXQ && t == 2) mix_qk();
                else if (k >= G1_KSTEPS - TAIL1 && t == G1_TILES - 1) mma_step224(acc, da, db, next1(s), k);
                else mma_step(acc, da, db, next1(s), k);
                if (wg == 0 && k == G1_KSTEPS - 1) asm volatile("bar.arrive 1, 256;" ::: "memory");
                wg_wait<1>();
                if (k > 0 && !(EREL && (k == MIXV && t == 3 || k == MIXQ && t == 2))) release(empty1((k - 1) & 3));
                TRACE_STEP(t, k, 2);
                if (t == 0) chunk_ln(k);
                if (k >= 1 && k <= 8 && ((k < GV || k > GV + 3 ? 0x12 : 0x1a) >> t & 1)) {
                    chunk_geglu(k < GV ? k - 1 : (k > GV + 3 ? k - 5 : k - GV + 4));
                    if (k == 8 && t != 3) signal_stores(t + 1);
                }
                if (t == 2) chunk_qk(k);
                if (t == 3) chunk_pv(k);
                if (k == TLD && t == G1_TILES - 1) {
#pragma unroll
                    for (int i = 0; i < 2; i++) {
                        const uint4 v = ldg_stream(prm.tail + role * 512 + i * 256 + threadIdx.x, stream_policy());
                        pk[16 + 4 * i] = v.x; pk[17 + 4 * i] = v.y; pk[18 + 4 * i] = v.z; pk[19 + 4 * i] = v.w;
                    }
                }
                if (k == TLD + 3 && t == G1_TILES - 1) {
#pragma unroll
                    for (int i = 0; i < 8; i++)
                        asm volatile("shl.b32 %0, %2, 16;\nand.b32 %1, %2, 0xffff0000;" : "=r"(pk[2 * i]), "=r"(pk[2 * i + 1]) : "r"(pk[16 + i]));
                }
                if (k == 13) {
                    const uint32_t id = fresh_tid();
                    optr = prm.pa2 + (size_t)(row0(id) + (id & 28) / 2) * K2 + DM + gate_col(t, nslot) + id % 4 * 8;
                    asm volatile("" : "+l"(optr));
                }
            }
            wg_wait<0>();
            fence_regs(acc);
            release(empty1(3));
            if (t == 0) {
                Floats<2> inv(pk + 32);
#pragma unroll
                for (int i = 0; i < 128; i++) acc[i] *= inv[i / 2 % 2];
                fence_regs(acc);
            }
            if (t == G1_TILES - 1) {
                Floats<16> part(pk);
#pragma unroll
                for (int i = 0; i < 16; i++) acc[112 + i] += part[i];
                fence_regs(acc);
            }
#pragma unroll
            for (int i = 0; i < 64; i++) {
                const int e = i < 32 ? (i & ~7) * 2 + (i & 3) * 4 + (i & 4) / 2 : i * 2;
                pk[i] = pack_bf16(acc[e], acc[e + 1]);
            }
            TRACE_NEXT(tile_slot);
        }

        float accd[64], accs[64];
#pragma unroll
        for (int i = 0; i < 64; i++) accd[i] = 0.f;
#pragma unroll
        for (int u = 0; u < G2_HEAD; u++) {
            const int q = u % G2_STAGES;
            mbar_wait(full2(q), (u / G2_STAGES) & 1, spins);
            mma_step(accd, da, db, next2(q), u);
            wg_wait<1>();
            if (u > 0) release(empty2((u - 1) % G2_STAGES));
            if (u >= 1) {
                const int j = (u - 1) / 2;
#pragma unroll
                for (int i = 2 * u - 2; i < 2 * u; i++) pk[i] = geglu2(pk[i], pk[up(i)]);
                if (u % 2 == 0) store_pk(optr + (j & 1) * 16 * K2 + (j >> 1) * 32, j);
            }
            if (u == G2_HEAD - 1) signal_stores(6);
        }
        auto down = [&](int q, uint32_t phase, bool narrow) {
            mbar_wait(full2(q), phase, spins);
            if (narrow) mma_step96(accd, da, db, next2(q), 1);
            else mma_step(accd, da, db, next2(q), 1);
            wg_wait<1>();
            release(empty2((q + G2_STAGES - 1) % G2_STAGES));
        };
        down(5, 0, false);
#pragma unroll 1
        for (uint32_t r = 3; r < 9; r++) {
#pragma unroll
            for (int q = 0; q < G2_STAGES; q++) down(q, r & 1, (NAR0 - q) % NARS == 0 && r <= (NAR0 + TAIL2 * NARS - 1 - q) / G2_STAGES);
        }
        down(0, 1, false);
        down(1, 1, false);
        TRACE_NEXT(tile_slot);
#pragma unroll
        for (int i = 0; i < 64; i++) accs[i] = 0.f;
        uint32_t gk[32], xr[32];
        const uint32_t xs = aux + cw * 2048;
        const uint32_t xrow = xs + ((lane & 7) + ((lane >> 3) & 1) * 8) * 128;
        auto xaddr = [&](int j) { return xrow + (j >> 2) * 16384 + (((((j & 3) * 2) + (lane >> 4)) ^ (lane & 7)) << 4); };
#pragma unroll
        for (int u = G2_DSTEPS; u < G2_KSTEPS; u++) {
            const int q = u % G2_STAGES, v = u - G2_DSTEPS;
            mbar_wait(full2(q), (u / G2_STAGES) & 1, spins);
            if (G2_SKEW > 0 && wg == 1 && u == G2_KSTEPS - G2_SKEW) asm volatile("bar.sync 1, 256;" ::: "memory");
            mma_step(accs, da, db, next2(q), v);
            if (G2_SKEW > 0 && wg == 0 && u == G2_KSTEPS - 1) asm volatile("bar.arrive 1, 256;" ::: "memory");
            if (v == TLD2) {
                TRACE_S(32, wg, 0);
                mbar_wait(dep_bar + 24, 0, spins);
                TRACE_S(33, wg, 0);
#pragma unroll
                for (int i = 0; i < 2; i++) {
                    const uint4 w = ldg_stream(prm.tail + (NGEMM + role) * 512 + i * 256 + threadIdx.x, stream_policy());
                    gk[24 + 4 * i] = w.x; gk[25 + 4 * i] = w.y; gk[26 + 4 * i] = w.z; gk[27 + 4 * i] = w.w;
                }
            }
#pragma unroll
            for (int i = 0; i < 32; i++) {
                if (v == (i < 24 ? i / 4 + 1 : TLD2 + (i < 28 ? GA : GB)))
                    gk[i] = i < 24 ? silu2(accd[2 * i], accd[2 * i + 1])
                                   : silu2(accd[2 * i] + bf_lo(gk[i]), accd[2 * i + 1] + bf_hi(gk[i]));
            }
            if (v == XLD) mbar_wait(x_bar, 0, spins);
            if (v >= XLD && v < XLD + 4) {
#pragma unroll
                for (int j = 2 * (v - XLD); j < 2 * (v - XLD + 1); j++)
                    asm volatile("ldmatrix.sync.aligned.m8n8.x4.shared.b16 {%0,%1,%2,%3}, [%4];"
                                 : "=r"(xr[4 * j]), "=r"(xr[4 * j + 1]), "=r"(xr[4 * j + 2]), "=r"(xr[4 * j + 3])
                                 : "r"(xaddr(j)) : "memory");
            }
            wg_wait<1>();
            if (v == 0) fence_regs(accd);
            if (u - 1 + G2_STAGES < G2_KSTEPS) release(empty2((u - 1) % G2_STAGES));
        }
        __nv_bfloat16* po = prm.pout + (row0(fresh_tid()) + (lane >> 3) * 2) * DM + nslot * 128 + 64 + (lane & 7) * 8;
        uint32_t so = xs + 16384 + (lane >> 3) * 128 + (((lane & 7) ^ (lane >> 3)) << 4);
        const int c0 = uniform(nslot * 128), c1 = uniform(row0(fresh_tid()) >> 1);
        const uint32_t xu = uniform(xs);
        asm volatile("" : "+l"(po), "+r"(so));
        wg_wait<0>();
        fence_regs(accs);
        TRACE_NEXT(tile_slot);
        TRACE_END();
#pragma unroll
        for (int j = 0; j < 8; j++) {
            uint32_t r[4];
#pragma unroll
            for (int i = 0; i < 4; i++) {
                const int e = j * 4 + i;
                asm("fma.rn.bf16x2 %0, %1, %2, %3;" : "=r"(r[i]) : "r"(pack_bf16(accs[2 * e], accs[2 * e + 1])), "r"(gk[e]), "r"(xr[e]));
            }
            asm volatile("stmatrix.sync.aligned.m8n8.x4.shared.b16 [%0], {%1,%2,%3,%4};"
                         :: "r"(xaddr(j)), "r"(r[0]), "r"(r[1]), "r"(r[2]), "r"(r[3]) : "memory");
            if (j == 3)
                asm volatile("{\n.reg .pred e;\nfence.proxy.async.shared::cta;\nbar.warp.sync 0xffffffff;\nelect.sync _|e, 0xffffffff;\n"
                    "@e cp.async.bulk.tensor.3d.global.shared::cta.bulk_group [%0, {%2, %3, %4}], [%1];\n}"
                    :: "l"(&prm.out), "r"(xu), "r"(c0), "r"(c1), "r"(wg) : "memory");
        }
        __syncwarp();
#pragma unroll
        for (int i = 0; i < 4; i++) {
            const uint4 v = lds128((so ^ (i & 1) * 64) + i * 512);
            asm volatile("st.global.v4.u32 [%0], {%1,%2,%3,%4};" :: "l"(po + i * 8 * DM), "r"(v.x), "r"(v.y), "r"(v.z), "r"(v.w) : "memory");
        }
        asm volatile("cp.async.bulk.commit_group;\ncp.async.bulk.wait_group.read 0;" ::: "memory");
        TRACE_LITE(10, clock());
        if (tid == 0) { TRACE_NEXT(tile_slot); if (wg == 1) TRACE_GT(13); TRACE_DUMP(); }
    } else {
        asm volatile("setmaxnreg.dec.sync.aligned.u32 %0;" :: "n"(AUX_REGS));
        cluster_wait();
        unsigned* const flags = prm.flags + mblk * 32;
        if (warp == 9) {
            TRACE_CLEAR(); TRACE_GT(0); TRACE_LITE(8, t0);
            if (lane == 0) {
                const unsigned epoch = __ldcg(prm.epoch + blockIdx.x * 16 + 2) + 1;
                mbar_wait(sig_bar, 0);
                TRACE(11);
                flag_add(flags + F_LN * 512);
                TRACE(42);
                flag_wait(flags + F_LN * 512, epoch * CNT_LN);
                fence_proxy_async();
                mbar_arrive(dep_bar);
                mbar_wait(sig_bar + 56, 0);
                flag_add(flags + F_LN2 * 512);
                flag_wait(flags + F_LN2 * 512, epoch * CNT_LN);
                fence_proxy_async();
                mbar_arrive(dep_bar + 40);
                TRACE(59);
                prm.epoch[blockIdx.x * 16 + 2] = epoch;
#pragma unroll 1
                for (int p = 3; p < 7; p++) {
                    mbar_wait(sig_bar + (p == 3 ? 16 : p * 8), 0);
                    TRACE_S(37, p, 4);
                    flag_add(flags + (p / 2 + 1) * 512);
                    TRACE_S(43, p, 4);
                }
            }
        } else if (warp > 9) {
            const int w = warp - 10;
            const unsigned epoch = __ldcg(prm.epoch + blockIdx.x * 16 + w) + 1;
            const uint32_t tag = 1 + (epoch & 1);
            const uint32_t at = (w ? CB : CA) >> (CIDX) * 4 & 15;
            mbar_wait(empty1(at & 3), 0);
            mbar_wait(empty1(at & 3), at >> 3);
            if (elect_one()) {
                mbar_expect_tx(cs_bar + w * 8, 16384);
                asm volatile("cp.async.bulk.tensor.2d.shared::cluster.global.mbarrier::complete_tx::bytes [%0], [%1, {%3, %5}], [%2];\n"
                    "cp.async.bulk.tensor.2d.shared::cluster.global.mbarrier::complete_tx::bytes [%0 + 8192], [%1, {%4, %5}], [%2];"
                    :: "r"(aux + w * 16384), "l"(w0), "r"(cs_bar + w * 8), "r"(nslot * 128), "r"(nslot * 128 + 64),
                       "r"(((mblk & ~1) + w) * 64) : "memory");
            }
            float cs[8];
#pragma unroll
            for (int d = 0; d < 8; d++) cs[d] = 0.f;
            const uint32_t wa = aux + w * 8192 + (lane >> 3) * 128 + (((lane & 7) ^ (lane >> 3)) << 4);
            uint4 v[9];
            auto fetch = [&](int h, uint32_t off) {
#pragma unroll
                for (int j = 0; j < 4; j++) v[h * 4 + j] = lds128((wa ^ (j & 1) * 64) + off + h * 2048 + j * 512);
            };
            auto add = [&](int h) {
#pragma unroll
                for (int j = 0; j < 4; j++) {
                    float f[8];
                    unpack8(v[h * 4 + j], f);
#pragma unroll
                    for (int d = 0; d < 8; d++) cs[d] += f[d];
                }
            };
            if (CST) { mbar_wait(empty1(CST & 3), 0); mbar_wait(empty1(CST & 3), CST >> 3); }
            mbar_wait(cs_bar, 0);

            fetch(0, 0);
#pragma unroll 1
            for (int i = 0; i < 4; i++) {
                fetch(1, (i >> 1) * 16384 + (i & 1) * 4096);
                add(0);
                if (i == 1) mbar_wait(cs_bar + 8, 0);
                fetch(0, (i + 1 & 2) * 8192 + (~i & 1) * 4096);
                add(1);
            }
#pragma unroll
            for (int d = 0; d < 4; d++)
                cs[d] = (lane & 16 ? cs[d + 4] : cs[d]) + __shfl_xor_sync(0xffffffffu, lane & 16 ? cs[d] : cs[d + 4], 16);
#pragma unroll
            for (int d = 0; d < 2; d++)
                cs[d] = (lane & 8 ? cs[d + 2] : cs[d]) + __shfl_xor_sync(0xffffffffu, lane & 8 ? cs[d] : cs[d + 2], 8);
            st_tagged(prm.colsum + (nslot * 2 + rank) * 1024 + (mblk >> 1) * 128 + w * 64 + (lane & 7) * 8 + (lane >> 3) * 2,
                      cs[0], cs[1], tag);

#pragma unroll
            for (int m = 0; m < 9; m++) v[m] = make_uint4(0, 0, 0, 0);
            const float* parts = prm.colsum + (nslot * 2 + (lane >> 4)) * 1024 + w * 64 + (lane & 15) * 4;
            const float* const rows = &prm.stats[mblk * 128 + w * 64 + lane * 2].x;
#pragma unroll 1
            for (int spins = 0; spins < (1 << 16); spins++) {
                bool missing = false;
                asm volatile("" : "+l"(parts));
#pragma unroll
                for (int m = 0; m < 9; m++) {
                    if (untagged(v[m], tag)) {
                        missing = true;
                        v[m] = ld_relaxed(m < 8 ? parts + m * 128 : rows);
                    }
                }
                if (!missing) break;
            }
            float4 c = make_float4(0.f, 0.f, 0.f, 0.f);
#pragma unroll
            for (int m = 0; m < 8; m++) {
                c.x += __uint_as_float(v[m].x ^ tag); c.y += __uint_as_float(v[m].y ^ tag);
                c.z += __uint_as_float(v[m].z ^ tag); c.w += __uint_as_float(v[m].w ^ tag);
            }
            sts128(stats + w * 512 + lane * 16, make_uint4(v[8].x ^ tag, v[8].y ^ tag, v[8].z ^ tag, v[8].w ^ tag));
            const uint32_t ca = aux + w * 8192 + (lane >> 4) * 16384 + (lane & 15) * 8;
#pragma unroll
            for (int r = 0; r < 3; r++) {
                const uint32_t lo = pack_bf16(c.x, c.y), hi = pack_bf16(c.z, c.w);
                sts64f((ca ^ r * 16) + r * 128, __uint_as_float(lo), __uint_as_float(hi));
                c.x -= bf_lo(lo); c.y -= bf_hi(lo); c.z -= bf_lo(hi); c.w -= bf_hi(hi);
            }
            asm volatile("fence.proxy.async.shared::cta;" ::: "memory");
            __syncwarp();
            if (lane == 0) {
                mbar_arrive(fold_bar);
                prm.epoch[blockIdx.x * 16 + w] = epoch;
                if (w == 0) {
                    TRACE_S(35, w, 0);
                    flag_wait(flags + F_TAIL * 512, epoch * 2 - 1);
                    mbar_arrive(x_bar + 8);
                    flag_wait(flags + F_FIRST * 512, epoch * CNT_FIRST);
                    flag_wait(flags + F_EARLY * 512, epoch * CNT_EARLY);
                    fence_proxy_async(); mbar_arrive(dep_bar + 8);
                    flag_wait(flags + F_LATE * 512, epoch * CNT_LATE);
                    fence_proxy_async(); mbar_arrive(dep_bar + 16);
                    flag_wait(flags + F_TAIL * 512, epoch * 2);
                    mbar_arrive(dep_bar + 24);
                } else {
#pragma unroll 1
                    for (int j = 0; j < 2; j++) {
                        uint8_t* const h = prm.halo + (j * NGEMM + role) * HALO_BYTES;
                        unsigned* const f = prm.flags + F_HALO * 512 + role * 32;
                        mbar_wait(sig_bar + 8 + j * 16, 0);
                        TRACE_S(38, j, 0); TRACE_S(9, j, 1);
                        asm volatile("cp.async.bulk.global.shared::cta.bulk_group [%0], [%1], %2;\n"
                            "cp.async.bulk.commit_group;\ncp.async.bulk.wait_group 0;"
                            :: "l"(h + HALO_BYTES), "r"(aux + 4 * HALO_BYTES), "n"(HALO_BYTES) : "memory");
                        fence_proxy_async();
                        TRACE_S(39, j, 0); TRACE_S(10, j, 1);
                        flag_add(f);
                        TRACE_S(40, j, 0); TRACE_S(34, j, 1);
                        if (mblk) flag_wait(f - 32, epoch * 2 - 1 + j);
                        fence_proxy_async();
                        TRACE_S(41, j, 0); TRACE_S(36, j, 1);
                        mbar_expect_tx(halo_bar, HALO_BYTES);
                        asm volatile("cp.async.bulk.shared::cluster.global.mbarrier::complete_tx::bytes [%0], [%1], %2, [%3];"
                            :: "r"(aux), "l"(mblk ? h : prm.halo), "n"(HALO_BYTES), "r"(halo_bar) : "memory");
                    }
                }
            }
        } else {
#pragma unroll
            for (int k = 1; k < G1_STAGES; k++) {
                const uint32_t sa = base + k * G1_STAGE_BYTES;
                if (PACE0 + PACE) while ((uint32_t)clock() - t0 < (k == 3 ? PACE3 : PACE0 + (k - 1) * PACE)) {}
                load_stage1(sa, sa + A_BYTES + rank * 16384, full1(k), &prm.x, w0, w0, k * 64, mblk * 64, nslot * 128,
                            nslot * 128 + 64, 0, stream_policy());
            }
            if (elect_one()) {
                prefetch_map(&prm.xn); prefetch_map(&prm.wqkv);
                prefetch_map(&prm.a2); prefetch_map(&prm.wo); prefetch_map(&prm.wd); prefetch_map(&prm.out);
            }
            auto load_x = [&]() {
                if (elect_one()) {
                    mbar_expect_tx(x_bar, 32768);
                    tma_3d(aux, &prm.x, x_bar, nslot * 128, mblk * 64, 0, stream_policy());
                    tma_3d(aux + 16384, &prm.x, x_bar, nslot * 128 + 64, mblk * 64, 0, stream_policy());
                }
                __syncwarp();
            };
            uint32_t ph = 0;
#pragma unroll 1
            for (int t = 0; t < G1_TILES; t++) {
                const int col1 = (t == 1 ? rank * DM + nslot * 128 : gate_col(t, nslot)) + 64;
                const int col0 = t == 2 ? 2 * DM + nslot * 128 + rank * 64 : col1 - 64;
                if (t == 1) { TRACE_PUT(1, c0); TRACE_PUT(2, t0); TRACE(14); mbar_wait_warp(dep_bar, 0); TRACE(3); }
#pragma unroll 1
                for (int k = t ? 0 : G1_STAGES; k < G1_KSTEPS; k++) {
                    const int s = k & 3;
                    if (t == 1 && k == 8) mbar_wait_warp(dep_bar + 40, 0);
                    if (t * 16 + k == 64 + TLD) { TRACE(61); mbar_wait_warp(x_bar + 8, 0); TRACE(63); }
                    if (t * 16 + k == (PFK)) {
                        asm volatile("{\n.reg .pred e;\nelect.sync _|e, 0xffffffff;\n"
                            "@e cp.async.bulk.prefetch.tensor.5d.L2.global [%0, {%1, %4, %4, %4, %3}];\n"
                            "@e cp.async.bulk.prefetch.tensor.5d.L2.global [%0, {%2, %4, %4, %4, %3}];\n}"
                            :: "l"(&prm.wd), "r"(nslot * 128), "r"(nslot * 128 + 64), "r"((mblk + TAIL2) * 2), "r"(0) : "memory");
                    }
                    mbar_wait_warp(empty1(s), ph);
                    const uint32_t sa = base + s * G1_STAGE_BYTES;
                    load_stage1(sa, sa + A_BYTES + rank * 16384, full1(s), t ? &prm.xn : &prm.x, t == 1 || t == 2 ? &prm.wqkv : w0,
                                t == 1 ? &prm.wqkv : w0, (k + (t >> 2) * TAIL1 & 15) * 64, mblk * 64, col0, col1, t & 3,
                                stream_policy());
                    if (s == 3) ph ^= 1;
                    if (t * 16 + k == (XK)) load_x();
                }
            }
            TRACE(4);
            mbar_wait_warp(dep_bar + 8, 0);
            TRACE(5);
            int q = 0, narrow = 0; uint32_t ph2 = 1;
#pragma unroll 1
            for (int u = 0; u < G2_KSTEPS; u++) {
                if (u == G2_LATE) { TRACE(6); mbar_wait_warp(dep_bar + 16, 0); TRACE(7); }
                const uint32_t sa = stage2(q);
                const bool down = u < G2_DSTEPS;
                const int k = !down ? u - G2_DSTEPS : (G2_NARROW >> u & 1 ? narrow++ : u + TAIL2 - narrow);
                mbar_wait_warp(u < G2_STAGES ? empty1((u * 2 + 1) / 3) : empty2(q), u < G2_STAGES ? ph : ph2);
                load_stage2(sa, sa + A_BYTES + rank * 8192, full2(q), &prm.a2, down ? &prm.wd : &prm.wo, (down ? DM : 0) + k * 64,
                            mblk * 64, nslot * 128 + rank * 64, down ? 0 : k * 2, down ? k * 2 : 0, stream_policy());
                if (++q == G2_STAGES) { q = 0; ph2 ^= 1; }
            }
            TRACE(8);
        }
    }
}

typedef CUresult (*EncodeFn)(CUtensorMap*, CUtensorMapDataType, cuuint32_t, void*, const cuuint64_t*, const cuuint64_t*,
                             const cuuint32_t*, const cuuint32_t*, CUtensorMapInterleave, CUtensorMapSwizzle,
                             CUtensorMapL2promotion, CUtensorMapFloatOOBfill);

void encode(EncodeFn fn, CUtensorMap* m, const void* ptr, int rank, const cuuint64_t* dims, const cuuint64_t* strides,
            const cuuint32_t* box) {
    const cuuint32_t es[5] = {1, 1, 1, 1, 1};
    fn(m, CU_TENSOR_MAP_DATA_TYPE_BFLOAT16, rank, const_cast<void*>(ptr), dims, strides, box, es,
       CU_TENSOR_MAP_INTERLEAVE_NONE, box[0] == 32 ? CU_TENSOR_MAP_SWIZZLE_64B : CU_TENSOR_MAP_SWIZZLE_128B,
       CU_TENSOR_MAP_L2_PROMOTION_L2_128B, CU_TENSOR_MAP_FLOAT_OOB_FILL_NONE);
}
void encode_rows(EncodeFn fn, CUtensorMap* m, const void* ptr, int cols, int box_rows, int box_parity) {
    const cuuint64_t dims[3] = {(cuuint64_t)cols, SEQ / 2, 2}, strides[2] = {(cuuint64_t)cols * 4, (cuuint64_t)cols * 2};
    const cuuint32_t box[3] = {64, (cuuint32_t)box_rows, (cuuint32_t)box_parity};
    encode(fn, m, ptr, 3, dims, strides, box);
}
void encode_w1(EncodeFn fn, CUtensorMap* m, const void* ptr, int cols) {
    const cuuint64_t dims[2] = {(cuuint64_t)cols, DM}, strides[1] = {(cuuint64_t)cols * 2};
    const cuuint32_t box[2] = {64, 64};
    encode(fn, m, ptr, 2, dims, strides, box);
}
void encode_tail(EncodeFn fn, CUtensorMap* m, const void* ptr, int rows, int cols, int n) {
    const cuuint64_t rb = cols * 2;
    const cuuint64_t dims[5] = {32, (cuuint64_t)n, (cuuint64_t)rows / (4 * n), 4, 8}, strides[4] = {rb, 4 * n * rb, n * rb, 256};
    const cuuint32_t box[5] = {32, (cuuint32_t)n, 16 / (cuuint32_t)n, 4, 8};
    encode(fn, m, (const __nv_bfloat16*)ptr + cols - 1024 + 96, 5, dims, strides, box);
}
void encode_w2(EncodeFn fn, CUtensorMap* m, const void* ptr, int rows) {
    const cuuint64_t rb = DM * 2;
    const cuuint64_t dims[5] = {DM, 2, 4, 4, (cuuint64_t)rows / 32}, strides[4] = {rb, 8 * rb, 2 * rb, 32 * rb};
    const cuuint32_t box[5] = {64, 2, 4, 4, 2};
    encode(fn, m, ptr, 5, dims, strides, box);
}
void encode_wo(EncodeFn fn, CUtensorMap* m, const void* ptr) {
    const cuuint64_t rb = DM * 2;
    const cuuint64_t dims[5] = {DM, 4, DM / 32, 2, 4}, strides[4] = {8 * rb, 32 * rb, rb, 2 * rb};
    const cuuint32_t box[5] = {64, 4, 2, 2, 4};
    encode(fn, m, ptr, 5, dims, strides, box);
}

}

extern "C" void kernel_launch(void* const* d_in, const int* in_sizes, int n_in, void* d_out, int out_size) {
    (void)in_sizes; (void)n_in; (void)out_size;
    static EncodeFn fn = nullptr;
    static Params prm;
    if (!fn) {
        cudaDriverEntryPointQueryResult st;
        cudaGetDriverEntryPoint("cuTensorMapEncodeTiled", (void**)&fn, cudaEnableDefault, &st);
        cudaGetSymbolAddress((void**)&prm.pxn, g_xn);
        cudaGetSymbolAddress((void**)&prm.pa2, g_a2);
        cudaGetSymbolAddress((void**)&prm.tail, g_tail);
        cudaGetSymbolAddress((void**)&prm.halo, g_halo);
        cudaGetSymbolAddress((void**)&prm.stats, g_stats);
        cudaGetSymbolAddress((void**)&prm.colsum, g_colsum);
        cudaGetSymbolAddress((void**)&prm.flags, g_flags);
        cudaGetSymbolAddress((void**)&prm.epoch, g_epoch);
        cudaFuncSetAttribute(fused_kernel, cudaFuncAttributeMaxDynamicSharedMemorySize, SMEM_BYTES);
    }
    encode_rows(fn, &prm.x, d_in[0], DM, 64, 2);
    encode_rows(fn, &prm.xn, prm.pxn, DM, 64, 2);
    encode_rows(fn, &prm.a2, prm.pa2, K2, 64, 2);
    encode_rows(fn, &prm.out, d_out, DM, 16, 1);
    encode_w1(fn, &prm.wqkv, d_in[1], NQKV);
    encode_w1(fn, &prm.wg, d_in[4], DF);
    encode_w1(fn, &prm.wu, d_in[5], DF);
    encode_tail(fn, &prm.wu_tail, d_in[5], DM, DF, 8);
    encode_tail(fn, &prm.wd_tail, d_in[6], DF, DM, 2);
    encode_wo(fn, &prm.wo, d_in[2]);
    encode_w2(fn, &prm.wd, d_in[6], DF);
    prm.px = (const __nv_bfloat16*)d_in[0];
    prm.pout = (__nv_bfloat16*)d_out;
    fused_kernel<<<NCTA, 384, SMEM_BYTES>>>(prm);
}
```

```cpp
#include <cuda_runtime.h>
#include <cuda_bf16.h>
#include <cuda.h>
#include <stdint.h>
#include <type_traits>

#define LNS 3
#define FS 14
#define CA 0x87658765u
#define CB 0x65876587u
#define CST 10
#define CIDX nslot
#define PACE0 900
#define PACE 425
#define PACE3 1700
#define TAIL2 10
#define C2AT 2
#define TPACE 425
#define TEARLY 1
#define TEW 8
#define WDPF 1
#define TFOLD 1
#define NAR0 19
#define NARS 2
#define MIXQ 8
#define MIXV 9
#define TLD2 7
#define XLD 7
#define VK 1
#define VN 2
#define KK 2
#define EREL 0
#define MEET 4
#define OVS 4
#define GV 3
#define TOP 16
#define SK2 5
#define PFK 60 + mblk
#define XK 66 + nslot
#define TSK 2
#define TW0 600
#define TLD 2
#define SK4 2
#define GA 3
#define GB 4

namespace {

constexpr int SEQ = 2048, DM = 1024, DF = 3584, K2 = DM + DF, NQKV = 3 * DM;
constexpr int NGEMM = 128, NCTA = 132;
constexpr int G1_STAGES = 4, G1_STAGE_BYTES = 49152, G1_KSTEPS = 16, G1_TILES = 5;
constexpr int G2_STAGES = 6, G2_STAGE_BYTES = 32768, G2_KSTEPS = 72, G2_LATE = 40, G2_DSTEPS = 56;
constexpr int G2_HEAD = 17;
constexpr int LN_STEP = LNS, FOLD_STEP = FS;
constexpr int A_BYTES = 16384;
constexpr int AUX_OFF = G1_STAGES * G1_STAGE_BYTES;
constexpr int BAR_OFF = AUX_OFF + 32768;
constexpr int STAT_OFF = BAR_OFF + 1536;
constexpr int SMEM_BYTES = BAR_OFF + 2816;
constexpr int G1_SKEW = 2, G2_SKEW = SK2;
constexpr int CONSUMER_REGS = 224, AUX_REGS = 56;
constexpr int HALO_BYTES = 4096;
constexpr uint64_t narrow_steps() {
    uint64_t m = 0;
    for (int i = 0; i < TAIL2; i++) m |= 1ull << NAR0 + i * NARS;
    return m;
}
constexpr uint64_t G2_NARROW = narrow_steps();
static_assert(G2_NARROW >> G2_LATE == 0 && NAR0 >= 18 && NAR0 < 18 + NARS && 6 % NARS == 0, "narrow steps use early columns");

enum { F_LN = 0, F_LN2 = 1, F_FIRST = 2, F_EARLY = 3, F_LATE = 4, F_TAIL2 = 5, F_HALO = 6 };
constexpr unsigned CNT_LN = 8, CNT_EARLY = 17, CNT_LATE = 8;

__device__ __align__(1024) __nv_bfloat16 g_xn[SEQ * DM];
__device__ __align__(1024) __nv_bfloat16 g_a2[SEQ * K2];
__device__ __align__(128) uint4 g_tail[2 * NGEMM * 512];
__device__ __align__(128) uint8_t g_halo[(2 * NGEMM + 1) * HALO_BYTES];
__device__ __align__(128) float2 g_stats[SEQ];
__device__ __align__(128) float g_colsum[18 * 1024];
__device__ __align__(128) unsigned g_flags[(F_HALO + 8) * 16 * 32];
__device__ __align__(128) unsigned g_epoch[NCTA * 16];

struct Params {
    const __nv_bfloat16 *px, *pwu;
    __nv_bfloat16 *pxn, *pa2, *pout;
    uint4* tail;
    uint8_t* halo;
    float2* stats;
    float* colsum;
    unsigned *flags, *epoch;
    unsigned long long* trace;
    CUtensorMap x, wg, wu, xn, wqkv, a2, wu_tail, wd_tail, wo, wd, out;
};

extern __shared__ __align__(1024) uint8_t smem_raw[];

#define TRACE(slot) do {} while (0)
#define TRACE_GT(slot) do {} while (0)
#define TRACE_S(slot, v, want) do {} while (0)
#define TRACE_GET(v) do {} while (0)
#define TRACE_PUT(slot, v) do {} while (0)
#define TRACE_SLOT(v, slot) do {} while (0)
#define TRACE_NEXT(v) do {} while (0)
#define TRACE_DUMP() do {} while (0)
#define TRACE_CLEAR() do {} while (0)
#define STAGE_TRACE 0
#define TRACE_END() do {} while (0)
#define TRACE_LITE(i, c) do {} while (0)
#define TRACE_STEP(t, k, i) do {} while (0)

__device__ __forceinline__ uint32_t smem_u32(const void* p) { return (uint32_t)__cvta_generic_to_shared(p); }
__device__ __forceinline__ void mbar_init(uint32_t bar, uint32_t cnt) {
    asm volatile("mbarrier.init.shared::cta.b64 [%0], %1;" :: "r"(bar), "r"(cnt) : "memory");
}
__device__ __forceinline__ void mbar_expect_tx(uint32_t bar, uint32_t bytes) {
    asm volatile("mbarrier.arrive.expect_tx.shared::cta.b64 _, [%0], %1;" :: "r"(bar), "r"(bytes) : "memory");
}
__device__ __forceinline__ void mbar_arrive(uint32_t bar) {
    asm volatile("mbarrier.arrive.shared::cta.b64 _, [%0];" :: "r"(bar) : "memory");
}
__device__ __forceinline__ bool mbar_try_wait(uint32_t bar, uint32_t parity) {
    uint32_t ok;
    asm volatile("{\n.reg .pred p;\nmbarrier.try_wait.parity.shared::cta.b64 p, [%1], %2;\nselp.u32 %0, 1, 0, p;\n}"
                 : "=r"(ok) : "r"(bar), "r"(parity) : "memory");
    return ok;
}
__device__ __forceinline__ void mbar_wait(uint32_t bar, uint32_t parity) {
#pragma unroll 1
    for (int spins = 0; !mbar_try_wait(bar, parity) && spins < (1 << 17); spins++) {}
}
__device__ __forceinline__ void mbar_wait(uint32_t bar, uint32_t parity, int& spins) {
    asm volatile("{\n.reg .pred p;\nagain:\nmbarrier.try_wait.parity.shared::cta.b64 p, [%1], %2;\n@p bra done;\n"
                 "add.s32 %0, %0, -1;\nsetp.gt.s32 p, %0, 0;\n@p bra again;\ndone:\n}" : "+r"(spins) : "r"(bar), "r"(parity) : "memory");
}
template <bool WARP = false> __device__ __forceinline__ void flag_wait(const unsigned* p, unsigned target) {
#pragma unroll 1
    for (int spins = 0; spins < (1 << 19); spins++) {
        unsigned v;
        asm volatile("ld.acquire.gpu.global.u32 %0, [%1];" : "=r"(v) : "l"(p) : "memory");
        if (WARP ? __all_sync(0xffffffffu, (int)(v - target) >= 0) : (int)(v - target) >= 0) break;
        __nanosleep(64);
    }
}
__device__ __forceinline__ void mbar_wait_warp(uint32_t bar, uint32_t parity) {
#pragma unroll 1
    for (int spins = 0; !__all_sync(0xffffffffu, mbar_try_wait(bar, parity)) && spins < (1 << 17); spins++) {}
}
__device__ __forceinline__ void flag_add(unsigned* p) {
    asm volatile("red.release.gpu.global.add.u32 [%0], 1;" :: "l"(p) : "memory");
}
__device__ __forceinline__ bool elect_one() {
    uint32_t ok;
    asm volatile("{\n.reg .pred p;\nelect.sync _|p, 0xffffffff;\nselp.u32 %0, 1, 0, p;\n}" : "=r"(ok));
    return ok;
}
__device__ __forceinline__ uint32_t pick(bool c, uint32_t a, uint32_t b) {
    uint32_t r;
    asm("{\n.reg .pred p;\nsetp.ne.b32 p, %3, 0;\nselp.b32 %0, %1, %2, p;\n}" : "=r"(r) : "r"(a), "r"(b), "r"((uint32_t)c));
    return r;
}
__device__ __forceinline__ void fence_proxy_async() { asm volatile("fence.proxy.async.global;" ::: "memory"); }
__device__ __forceinline__ uint4 lds128(uint32_t addr) {
    uint4 v;
    asm volatile("ld.shared.v4.u32 {%0,%1,%2,%3}, [%4];" : "=r"(v.x), "=r"(v.y), "=r"(v.z), "=r"(v.w) : "r"(addr) : "memory");
    return v;
}
__device__ __forceinline__ float2 lds64f(uint32_t addr) {
    float2 v;
    asm volatile("ld.shared.v2.f32 {%0,%1}, [%2];" : "=f"(v.x), "=f"(v.y) : "r"(addr) : "memory");
    return v;
}
__device__ __forceinline__ void sts128(uint32_t addr, uint4 v) {
    asm volatile("st.shared.v4.u32 [%0], {%1,%2,%3,%4};" :: "r"(addr), "r"(v.x), "r"(v.y), "r"(v.z), "r"(v.w) : "memory");
}
__device__ __forceinline__ void sts64f(uint32_t addr, float a, float b) {
    asm volatile("st.shared.v2.f32 [%0], {%1,%2};" :: "r"(addr), "f"(a), "f"(b) : "memory");
}

__device__ __forceinline__ uint64_t stream_policy() { return 0x12F0000000000000ull; }
__device__ __forceinline__ void tma_3d(uint32_t dst, const CUtensorMap* m, uint32_t bar, int c0, int c1, int c2, uint64_t pol) {
    asm volatile("cp.async.bulk.tensor.3d.shared::cluster.global.mbarrier::complete_tx::bytes.L2::cache_hint"
                 " [%0], [%1, {%3, %4, %5}], [%2], %6;"
                 :: "r"(dst), "l"(m), "r"(bar), "r"(c0), "r"(c1), "r"(c2), "l"(pol) : "memory");
}
__device__ __forceinline__ void load_stage1(uint32_t dst, uint32_t dst_b, uint32_t bar, const CUtensorMap* ma, const CUtensorMap* mb0,
                                            const CUtensorMap* mb1, int k, int row, int col0, int col1, int keep_a, uint64_t pol) {
    asm volatile("{\n.reg .pred e, p, q;\nelect.sync _|e, 0xffffffff;\nsetp.ne.and.b32 p|q, %8, 0, e;\n"
        "@p cp.async.bulk.tensor.3d.shared::cluster.global.mbarrier::complete_tx::bytes [%0], [%3, {%5, %6, %10}], [%2];\n"
        "@q cp.async.bulk.tensor.3d.shared::cluster.global.mbarrier::complete_tx::bytes.L2::cache_hint [%0], [%3, {%5, %6, %10}], [%2], %9;\n"
        "@e cp.async.bulk.tensor.2d.shared::cluster.global.mbarrier::complete_tx::bytes.multicast::cluster.L2::cache_hint"
        " [%1], [%4, {%7, %5}], [%2], %11, %9;\n"
        "@e cp.async.bulk.tensor.2d.shared::cluster.global.mbarrier::complete_tx::bytes.multicast::cluster.L2::cache_hint"
        " [%1 + 8192], [%13, {%14, %5}], [%2], %11, %9;\n"
        "@e mbarrier.arrive.expect_tx.shared::cta.b64 _, [%2], %12;\n}"
        :: "r"(dst), "r"(dst_b), "r"(bar), "l"(ma), "l"(mb0), "r"(k), "r"(row), "r"(col0), "r"(keep_a), "l"(pol), "r"(0),
           "h"((uint16_t)3), "n"(G1_STAGE_BYTES), "l"(mb1), "r"(col1) : "memory");
}
__device__ __forceinline__ void load_stage2(uint32_t dst, uint32_t dst_b, uint32_t bar, const CUtensorMap* ma, const CUtensorMap* mb,
                                            int ka, int row, int col, int kb2, int kb4, uint64_t pol) {
    asm volatile("{\n.reg .pred e;\nelect.sync _|e, 0xffffffff;\n"
        "@e cp.async.bulk.tensor.3d.shared::cluster.global.mbarrier::complete_tx::bytes.L2::cache_hint [%0], [%3, {%5, %6, %10}], [%2], %9;\n"
        "@e cp.async.bulk.tensor.5d.shared::cluster.global.mbarrier::complete_tx::bytes.multicast::cluster.L2::cache_hint"
        " [%1], [%4, {%7, %10, %13, %10, %8}], [%2], %11, %9;\n"
        "@e mbarrier.arrive.expect_tx.shared::cta.b64 _, [%2], %12;\n}"
        :: "r"(dst), "r"(dst_b), "r"(bar), "l"(ma), "l"(mb), "r"(ka), "r"(row), "r"(col), "r"(kb4), "l"(pol), "r"(0),
           "h"((uint16_t)3), "n"(G2_STAGE_BYTES), "r"(kb2) : "memory");
}
__device__ __forceinline__ void load_tail(uint32_t dst, uint32_t bar, const CUtensorMap* ma, const CUtensorMap* mb, int ka, int grp,
                                          int p, int kb) {
    asm volatile("{\n.reg .pred e;\nelect.sync _|e, 0xffffffff;\n"
        "@e cp.async.bulk.tensor.3d.shared::cluster.global.mbarrier::complete_tx::bytes [%0], [%2, {%3, %4, %5}], [%1];\n"
        "@e cp.async.bulk.tensor.5d.shared::cluster.global.mbarrier::complete_tx::bytes.multicast::cluster"
        " [%9], [%6, {%5, %5, %7, %5, %10}], [%1], %11;\n"
        "@e mbarrier.arrive.expect_tx.shared::cta.b64 _, [%1], %8;\n}"
        :: "r"(dst), "r"(bar), "l"(ma), "r"(ka), "r"(grp * 256 + p * 64), "r"(0), "l"(mb), "r"(kb), "n"(G1_STAGE_BYTES),
           "r"(dst + A_BYTES + grp % 2 * 16384), "r"(grp % 2 * 4), "h"((uint16_t)3) : "memory");
}
__device__ __forceinline__ uint4 ldg_stream(const void* p, uint64_t pol) {
    uint4 v;
    asm volatile("ld.global.nc.L1::no_allocate.L2::cache_hint.v4.u32 {%0,%1,%2,%3}, [%4], %5;"
                 : "=r"(v.x), "=r"(v.y), "=r"(v.z), "=r"(v.w) : "l"(p), "l"(pol));
    return v;
}
__device__ __forceinline__ void st_tagged(void* p, float a, float b, uint32_t tag) {
    asm volatile("st.relaxed.gpu.global.v2.b32 [%0], {%1,%2};"
                 :: "l"(p), "r"((__float_as_uint(a) & ~3u) | tag), "r"((__float_as_uint(b) & ~3u) | tag) : "memory");
}
__device__ __forceinline__ bool untagged(const uint4& v, uint32_t tag) {
    return ((v.x ^ tag) | (v.y ^ tag) | (v.z ^ tag) | (v.w ^ tag)) & 3;
}
__device__ __forceinline__ uint4 ld_relaxed(const void* p) {
    uint4 v;
    asm volatile("ld.relaxed.gpu.global.v4.b32 {%0,%1,%2,%3}, [%4];" : "=r"(v.x), "=r"(v.y), "=r"(v.z), "=r"(v.w) : "l"(p) : "memory");
    return v;
}
__device__ __forceinline__ void prefetch_map(const CUtensorMap* m) {
    asm volatile("prefetch.tensormap [%0];" :: "l"(m) : "memory");
}
template <int N> __device__ __forceinline__ void wg_wait() { asm volatile("wgmma.wait_group.sync.aligned %0;" :: "n"(N) : "memory"); }

__device__ __forceinline__ uint32_t desc_a(uint32_t addr) { return (addr & 0x3FFFF) >> 4 | 1 << 16; }
__device__ __forceinline__ uint32_t desc_b(uint32_t addr) { return (addr & 0x3FFFF) >> 4 | 512 << 16; }

#define R8(d, o) "+f"(d[o]), "+f"(d[o+1]), "+f"(d[o+2]), "+f"(d[o+3]), "+f"(d[o+4]), "+f"(d[o+5]), "+f"(d[o+6]), "+f"(d[o+7])
#define R32(d, o) R8(d, o), R8(d, o+8), R8(d, o+16), R8(d, o+24)
#define R64(d, o) R32(d, o), R32(d, o+32)
#define ACC00 "%0,%1,%2,%3,%4,%5,%6,%7,%8,%9,%10,%11,%12,%13,%14,%15,%16,%17,%18,%19,%20,%21,%22,%23,%24,%25,%26,%27,%28,%29,%30,%31,"\
    "%32,%33,%34,%35,%36,%37,%38,%39,%40,%41,%42,%43,%44,%45,%46,%47"
#define ACC0 ACC00 ",%48,%49,%50,%51,%52,%53,%54,%55,%56,%57,%58,%59,%60,%61,%62,%63"
#define ACC1 "%64,%65,%66,%67,%68,%69,%70,%71,%72,%73,%74,%75,%76,%77,%78,%79,%80,%81,%82,%83,%84,%85,%86,%87,%88,%89,%90,%91,%92,%93,%94,%95,"\
    "%96,%97,%98,%99,%100,%101,%102,%103,%104,%105,%106,%107,%108,%109,%110,%111"
#define ACC48 "{" ACC00 "}"
#define ACC64 "{" ACC0 "}"
#define ACC112 "{" ACC0 "," ACC1 "}"
#define ACC128 "{" ACC0 "," ACC1 ",%112,%113,%114,%115,%116,%117,%118,%119,%120,%121,%122,%123,%124,%125,%126,%127}"
#define MMA_K16(shape, acc, a, b, keep, hb) \
    "mov.b64 da, {" a ", 0x40000040};\nmov.b64 db, {" b ", " hb "};\n" \
    "wgmma.mma_async.sync.aligned." shape ".f32.bf16.bf16 " acc ", da, db, " keep ", 1, 1, 0, 1;\n"
#define MMA_NEXT(op, a, b, sa, sb) op " " a ", " a ", " sa ";\n" op " " b ", " b ", " sb ";\n"
#define MMA_STEP_B(shape, acc, a, b, na, nb, keep, hb, sb) \
    "{\n.reg .pred p, q;\n.reg .b64 da, db;\nsetp.ne.b32 p, " keep ", 0;\nsetp.eq.b32 q, 0, 0;\nwgmma.fence.sync.aligned;\n" \
    MMA_K16(shape, acc, a, b, "p", hb) MMA_NEXT("xor.b32", a, b, "2", "128") MMA_K16(shape, acc, a, b, "q", hb) MMA_NEXT("add.s32", a, b, "2", sb) \
    MMA_K16(shape, acc, a, b, "q", hb) MMA_NEXT("xor.b32", a, b, "2", "128") MMA_K16(shape, acc, a, b, "q", hb) MMA_NEXT("add.s32", a, b, na, nb) \
    "wgmma.commit_group.sync.aligned;\n}"
#define MMA_STEP(shape, acc, a, b, na, nb, keep) MMA_STEP_B(shape, acc, a, b, na, nb, keep, "0x40000040", "128")
#define MMA_ARGS "+r"(da), "+r"(db) : "r"(next / 16 - 6), "r"(next / 16 - 384), "r"(keep) : "memory"

__device__ __forceinline__ void mma_step(float (&d)[128], uint32_t& da, uint32_t& db, int next, int keep) {
    asm volatile(MMA_STEP("m64n256k16", ACC128, "%128", "%129", "%130", "%131", "%132") : R64(d, 0), R64(d, 64), MMA_ARGS);
}
__device__ __forceinline__ void mma_rank(float (&d)[128], uint32_t a0, uint32_t a1, uint32_t db) {
    asm volatile("{\n.reg .pred q;\n.reg .b64 db;\nsetp.eq.b32 q, 0, 0;\nmov.b64 db, {%131, 0x40000040};\nwgmma.fence.sync.aligned;\n"
                 "wgmma.mma_async.sync.aligned.m64n256k16.f32.bf16.bf16 " ACC128 ", {%128, %129, %130, %130}, db, q, 1, 1, 1;\n}"
                 : R64(d, 0), R64(d, 64) : "r"(a0), "r"(a1), "r"(0), "r"(db) : "memory");
}
__device__ __forceinline__ void mma_step224(float (&d)[128], uint32_t& da, uint32_t& db, int next, int keep) {
    asm volatile(MMA_STEP("m64n224k16", ACC112, "%112", "%113", "%114", "%115", "%116")
                 : R64(d, 0), R32(d, 64), R8(d, 96), R8(d, 104), MMA_ARGS);
}
__device__ __forceinline__ void mma_step(float (&d)[64], uint32_t& da, uint32_t& db, int next, int keep) {
    asm volatile(MMA_STEP("m64n128k16", ACC64, "%64", "%65", "%66", "%67", "%68") : R64(d, 0), MMA_ARGS);
}
__device__ __forceinline__ void mma_step96(float (&d)[64], uint32_t& da, uint32_t& db, int next, int keep) {
    asm volatile(MMA_STEP("m64n96k16", ACC48, "%48", "%49", "%50", "%51", "%52") : R32(d, 0), R8(d, 32), R8(d, 40), MMA_ARGS);
}
__device__ __forceinline__ void mma_step_tail(float (&d)[128], uint32_t da, uint32_t b, int keep) {
    uint32_t db = (b & 0x3FFFF) >> 4 | 256 << 16;
    const int next = 0;
    asm volatile(MMA_STEP_B("m64n256k16", ACC128, "%128", "%129", "%130", "%131", "%132", "0x80000040", "-96")
                 : R64(d, 0), R64(d, 64), MMA_ARGS);
}

__device__ __forceinline__ uint32_t pack_bf16(float lo, float hi) {
    uint32_t r; asm("cvt.rn.bf16x2.f32 %0, %1, %2;" : "=r"(r) : "f"(hi), "f"(lo)); return r;
}
__device__ __forceinline__ float bf_lo(uint32_t v) { return __uint_as_float(v << 16); }
__device__ __forceinline__ float bf_hi(uint32_t v) { return __uint_as_float(v & 0xffff0000u); }
__device__ __forceinline__ float round_bf16(float v) { return bf_lo(pack_bf16(v, 0.f)); }
__device__ __forceinline__ uint32_t mul_bf16x2(uint32_t a, uint32_t b) {
    uint32_t r; asm("mul.rn.bf16x2 %0, %1, %2;" : "=r"(r) : "r"(a), "r"(b)); return r;
}
__device__ __forceinline__ uint32_t sub_bf16x2(uint32_t a, uint32_t b) {
    uint32_t r; asm("sub.rn.bf16x2 %0, %1, %2;" : "=r"(r) : "r"(a), "r"(b)); return r;
}
__device__ __forceinline__ uint32_t mul2_bf16x2(uint32_t a, uint32_t hi, uint32_t lo) {
    uint32_t r; asm("fma.rn.bf16x2 %0, %1, %2, %3;" : "=r"(r) : "r"(a), "r"(hi), "r"(mul_bf16x2(a, lo))); return r;
}
__device__ __forceinline__ float tanh_fast(float x) { float r; asm("tanh.approx.f32 %0, %1;" : "=f"(r) : "f"(x)); return r; }
__device__ __forceinline__ float gelu_twice(float g) {
    return fmaf(g, tanh_fast(fmaf(g * g, 0.044715f * 0.7978845608f, 0.7978845608f) * g), g);
}
__device__ __forceinline__ uint32_t geglu2(uint32_t g2, uint32_t u2) {
    return mul_bf16x2(pack_bf16(gelu_twice(bf_lo(g2)), gelu_twice(bf_hi(g2))), u2);
}
__device__ __forceinline__ uint32_t silu2(float lo, float hi) {
    const uint32_t h = mul_bf16x2(pack_bf16(lo, hi), 0x3e803e80u);
    return pack_bf16(fmaf(bf_lo(h), tanh_fast(bf_lo(h)), bf_lo(h)), fmaf(bf_hi(h), tanh_fast(bf_hi(h)), bf_hi(h)));
}
__device__ __forceinline__ float ex2_fast(float x) { float r; asm("ex2.approx.ftz.f32 %0, %1;" : "=f"(r) : "f"(x)); return r; }
__device__ __forceinline__ void unpack8(uint4 v, float (&f)[8]) {
    f[0] = bf_lo(v.x); f[1] = bf_hi(v.x); f[2] = bf_lo(v.y); f[3] = bf_hi(v.y);
    f[4] = bf_lo(v.z); f[5] = bf_hi(v.z); f[6] = bf_lo(v.w); f[7] = bf_hi(v.w);
}
template <int N> __device__ __forceinline__ void fence_regs(float (&d)[N]) {
#pragma unroll
    for (int i = 0; i < N; i++) asm volatile("" : "+f"(d[i]) :: "memory");
}

__device__ __forceinline__ float rcp_fast(float x) { float r; asm("rcp.approx.ftz.f32 %0, %1;" : "=f"(r) : "f"(x)); return r; }
__device__ __forceinline__ float sqrt_fast(float x) { float r; asm("sqrt.approx.ftz.f32 %0, %1;" : "=f"(r) : "f"(x)); return r; }
__device__ __forceinline__ uint32_t max_bf16x2(uint32_t a, uint32_t b) {
    uint32_t r; asm("max.bf16x2 %0, %1, %2;" : "=r"(r) : "r"(a), "r"(b)); return r;
}
__device__ __forceinline__ uint32_t transpose8(uint32_t a) {
    uint32_t r; asm volatile("movmatrix.sync.aligned.m8n8.trans.b16 %0, %1;" : "=r"(r) : "r"(a)); return r;
}
__device__ __forceinline__ void mma_sync(uint32_t* d, const uint32_t* a, uint32_t b0, uint32_t b1, const uint32_t* c) {
    asm volatile("mma.sync.aligned.m16n8k16.row.col.f32.bf16.bf16.f32 {%0,%1,%2,%3}, {%4,%5,%6,%7}, {%8,%9}, {%10,%11,%12,%13};"
        : "=r"(d[0]), "=r"(d[1]), "=r"(d[2]), "=r"(d[3])
        : "r"(a[0]), "r"(a[1]), "r"(a[2]), "r"(a[3]), "r"(b0), "r"(b1), "r"(c[0]), "r"(c[1]), "r"(c[2]), "r"(c[3]));
}
template <int N> struct Floats {
    float f[N];
    __device__ __forceinline__ Floats() {}
    __device__ __forceinline__ Floats(const uint32_t* p) {
#pragma unroll
        for (int i = 0; i < N; i++) asm("mov.b32 %0, %1;" : "=f"(f[i]) : "r"(p[i]));
    }
    __device__ __forceinline__ void put(uint32_t* p) const {
#pragma unroll
        for (int i = 0; i < N; i++) asm("mov.b32 %0, %1;" : "=r"(p[i]) : "f"(f[i]));
    }
    __device__ __forceinline__ float& operator[](int i) { return f[i]; }
};
__device__ __forceinline__ uint32_t fresh_tid() { uint32_t r; asm volatile("mov.u32 %0, %%tid.x;" : "=r"(r)); return r; }
template <typename T> __device__ __forceinline__ T uniform(T v) { return __shfl_sync(0xffffffffu, v, 0); }

__device__ __forceinline__ void fold_operands(const Params& prm, uint32_t base, int slot, int mblk, uint32_t tag, int w, int lane) {
    uint4 v[9];
#pragma unroll
    for (int m = 0; m < 9; m++) v[m] = make_uint4(0, 0, 0, 0);
    const float* parts = prm.colsum + (slot * 2 + (lane >> 4)) * 1024 + w * 64 + (lane & 15) * 4;
    const float* const rows = &prm.stats[mblk * 128 + w * 64 + lane * 2].x;
#pragma unroll 1
    for (int spins = 0; spins < (1 << 16); spins++) {
        bool missing = false;
        asm volatile("" : "+l"(parts));
#pragma unroll
        for (int m = 0; m < 9; m++) {
            if (untagged(v[m], tag)) {
                missing = true;
                v[m] = ld_relaxed(m < 8 ? parts + m * 128 : rows);
            }
        }
        if (!missing) break;
    }
    float4 c = make_float4(0.f, 0.f, 0.f, 0.f);
#pragma unroll
    for (int m = 0; m < 8; m++) {
        c.x += __uint_as_float(v[m].x ^ tag); c.y += __uint_as_float(v[m].y ^ tag);
        c.z += __uint_as_float(v[m].z ^ tag); c.w += __uint_as_float(v[m].w ^ tag);
    }
    sts128(base + STAT_OFF + w * 512 + lane * 16, make_uint4(v[8].x ^ tag, v[8].y ^ tag, v[8].z ^ tag, v[8].w ^ tag));
    const uint32_t ca = base + AUX_OFF + w * 8192 + (lane >> 4) * 16384 + (lane & 15) * 8;
#pragma unroll
    for (int r = 0; r < 3; r++) {
        const uint32_t lo = pack_bf16(c.x, c.y), hi = pack_bf16(c.z, c.w);
        sts64f((ca ^ r * 16) + r * 128, __uint_as_float(lo), __uint_as_float(hi));
        c.x -= bf_lo(lo); c.y -= bf_hi(lo); c.z -= bf_lo(hi); c.w -= bf_hi(hi);
    }
    asm volatile("fence.proxy.async.shared::cta;" ::: "memory");
    __syncwarp();
}
__device__ __forceinline__ float2 fold(float (&acc)[128], uint32_t base, int wg) {
    const uint32_t id = fresh_tid(), sp = base + STAT_OFF + (id & 96) * 8 + (id & 28) * 4 + wg * 8;
    const uint32_t sel = id & 2 ? 0x4444 : (id & 1 ? 0x4432 : 0x3232);
    const float2 sa = lds64f(sp), sb = lds64f(sp + 128);
    mma_rank(acc, __byte_perm(__float_as_uint(sa.x), 0, sel), __byte_perm(__float_as_uint(sb.x), 0, sel), desc_b(base + AUX_OFF));
    return make_float2(sa.y, sb.y);
}

__device__ __forceinline__ void tail_gemm(const Params& prm, uint32_t base, unsigned epoch, int grp, int warp, int lane) {
    constexpr int STEPS = 4 * (G1_KSTEPS + TAIL2);
    const uint32_t full = base + BAR_OFF, empty = full + 32, sig = full + 192, dep = full + 256, folded = full + 320;
    unsigned* const flags = prm.flags + grp * 128;
    if (warp == 8) {
        if (elect_one()) { prefetch_map(&prm.xn); prefetch_map(&prm.a2); prefetch_map(&prm.wd_tail); }
#pragma unroll 1
        for (int p = 0, i = G1_STAGES; p < 8; p++) {
            const bool first = p < 4;
#pragma unroll 1
            for (int k = p ? 0 : G1_STAGES; k < (first ? G1_KSTEPS : TAIL2); k++, i++) {
                if (WDPF && p == 3 && k % 2 == grp / 2 && k < TAIL2)
                    asm volatile("{\n.reg .pred e;\nelect.sync _|e, 0xffffffff;\n"
                        "@e cp.async.bulk.prefetch.tensor.5d.L2.global [%0, {%2, %2, %1, %2, %3}];\n}"
                        :: "l"(&prm.wd_tail), "r"(k * 8), "r"(0), "r"(grp % 2 * 4) : "memory");
                if (i == 16 || i == 24 || i == 64) mbar_wait_warp(dep + (i >> 2 & 16 | i & 8), 0);
                TRACE_S(62, i, 16); TRACE_S(63, i, 4);
                mbar_wait_warp(empty + (i & 3) * 8, ~i >> 2 & 1);
                load_tail(base + (i & 3) * G1_STAGE_BYTES, full + (i & 3) * 8, first ? (p ? &prm.xn : &prm.x) : &prm.a2,
                          first ? &prm.wu_tail : &prm.wd_tail, (first ? 0 : DM) + k * 64, grp, p & 3, first ? k * 2 : k * 8);
            }
        }
    } else if (warp == 9) {
#pragma unroll 1
        for (int j = 0; j < 3; j++) {
            flag_wait<true>(flags + (F_LN + j) * 512 + (lane & 3) * 32, epoch * CNT_LN);
            fence_proxy_async();
            __syncwarp();
            if (lane == 0) mbar_arrive(dep + j * 8);
        }
    } else if (warp > 9) {
#pragma unroll 1
        for (int j = 0; j < 8; j++) sts128(base + AUX_OFF + (warp - 10) * 8192 + (j & 4) * 4096 + (j & 3) * 512 + lane * 16, make_uint4(0, 0, 0, 0));
        mbar_wait_warp(empty + 8, 0);
        mbar_wait_warp(empty + 8, 1);
        fold_operands(prm, base, 8, grp * 4, 1 + (epoch & 1), warp - 10, lane);
        if (lane == 0) mbar_arrive(folded);
        TRACE_S(60, warp, 10);
    }
    if (warp == 10 && lane == 0) {
#pragma unroll 1
        for (int p = 0; p < 8; p++) {
            mbar_wait(sig + p * 8, 0);
            flag_add(flags + (p < 4 ? F_EARLY : F_TAIL2) * 512 + (p & 3) * 32);
            TRACE_S(50, p, 3); TRACE_S(51, p, 7);
        }
        prm.epoch[blockIdx.x * 16] = epoch;
        TRACE_DUMP();
    }
    if (warp >= 8) return;
    asm volatile("setmaxnreg.inc.sync.aligned.u32 %0;" :: "n"(CONSUMER_REGS) : "memory");
    const uint32_t da = desc_a(base + (warp >> 2) * 8192);
    uint4* out = prm.tail;
    float acc[128];
    uint32_t pk[64];
    float2 inv = make_float2(0.f, 0.f);
    int i = 0;
    uint32_t peer;
    asm volatile("mapa.shared::cluster.u32 %0, %1, %2;" : "=r"(peer) : "r"(empty), "r"(lane & 1));
    auto release = [&]() {
        if ((threadIdx.x & 126) == 0 && i <= STEPS - G1_STAGES)
            asm volatile("mbarrier.arrive.shared::cluster.b64 _, [%0];" :: "r"(peer + (i - 1 & 3) * 8) : "memory");
    };
    auto store = [&](int j) {
        asm volatile("st.global.v4.u32 [%0], {%1,%2,%3,%4};" :: "l"(out + j / 2 * 8192 + j % 2 * 256),
                     "r"(pk[4 * j]), "r"(pk[4 * j + 1]), "r"(pk[4 * j + 2]), "r"(pk[4 * j + 3]) : "memory");
    };
    auto step = [&](int k, int left) {
        TRACE_S(44, warp * 128 + i, 0);
        mbar_wait(full + (i & 3) * 8, i >> 2 & 1);
        TRACE_S(45, warp * 128 + i, 0); TRACE_S(52, warp * 128 + i, 4);
        if (warp >= 4 && left == TSK) asm volatile("bar.sync 1, 256;" ::: "memory");
        mma_step_tail(acc, da + (i & 3) * (G1_STAGE_BYTES / 16), base + A_BYTES + (i & 3) * G1_STAGE_BYTES, k);
        if (warp < 4 && left == 1) asm volatile("bar.arrive 1, 256;" ::: "memory");
        wg_wait<1>();
        if (k) release();
        i++;
    };
#pragma unroll
    for (int j = 0; j < 128; j++) asm volatile("mov.b32 %0, 0;" : "=f"(acc[j]));
#pragma unroll
    for (int j = 0; j < 64; j++) asm volatile("mov.b32 %0, 0;" : "=r"(pk[j]));
#pragma unroll 1
    for (int p = 0; p < 8; p++) {
        step(0, 0);
#pragma unroll 1
        for (int left = (p < 4 ? G1_KSTEPS : TAIL2) - 1, n = p ? 8 : 0; left > 0; left--) {
            if (i == G1_KSTEPS - TFOLD) { mbar_wait(folded, 0); inv = fold(acc, base, warp >> 2); }
            if (n > 0) { store(0); store(1); }
#pragma unroll
            for (int j = 8; j < 64; j++) asm volatile("mov.b32 %0, %1;" : "=r"(pk[j - 8]) : "r"(pk[j]));
            out += 8192;
            __syncwarp();
            if (--n == 0 && lane == 0) mbar_arrive(sig + p * 8 - 8);
            step(1, left);
        }
        wg_wait<0>();
        fence_regs(acc);
        release();
        if (p == 0) {
#pragma unroll
            for (int j = 0; j < 128; j++) acc[j] *= j & 2 ? inv.y : inv.x;
            fence_regs(acc);
        }
        TRACE_S(46, p + warp * 8, 32); TRACE_S(47, p + warp * 8, 33); TRACE_S(48, p + warp * 8, 34); TRACE_S(49, p + warp * 8, 35);
        TRACE_S(53, p + warp * 8, 36); TRACE_S(54, p + warp * 8, 37); TRACE_S(55, p + warp * 8, 38); TRACE_S(56, p + warp * 8, 39);
#pragma unroll
        for (int j = 0; j < 64; j++) pk[j] = pack_bf16(acc[2 * j], acc[2 * j + 1]);
        out = prm.tail + p / 4 * NGEMM * 512 + (grp * 4 + p % 4) * 512 + threadIdx.x;
    }
#pragma unroll
    for (int j = 0; j < 16; j++) store(j);
    __syncwarp();
    TRACE_S(58, warp, 4);
    if (lane == 0) mbar_arrive(sig + 56);
}

__device__ __forceinline__ int gate_col(int t, int nslot) { return t == 2 ? 960 + nslot * 64 : max(t * 1024 - 1536, 0) + nslot * 128; }

struct Role {
    int rank, role, mblk, nslot;
    __device__ __forceinline__ Role() {
        uint32_t id;
        asm volatile("mov.u32 %0, %%ctaid.x;" : "=r"(id));
        const uint32_t cl = id / 2;
        rank = id & 1;
        role = pick(cl < 4, 32 + cl * 8, cl - 8 + max(4u, (cl - 1) * 37 >> 8)) * 2 + rank;
        mblk = role & 15; nslot = role >> 4;
    }
};

__global__ void __cluster_dims__(2, 1, 1) __launch_bounds__(384, 1)
fused_kernel(const __grid_constant__ Params prm) {
    TRACE_GET(c0);
    const uint32_t base = smem_u32(smem_raw) & ~1023u;
    const uint32_t bars = base + BAR_OFF;
    auto full1 = [&](int s) { return bars + s * 8; };
    auto empty1 = [&](int s) { return bars + 32 + s * 8; };
    auto full2 = [&](int s) { return bars + 64 + s * 8; };
    auto empty2 = [&](int s) { return bars + 128 + s * 8; };
    const uint32_t sig_bar = bars + 192, dep_bar = bars + 256, cs_bar = bars + 304, fold_bar = bars + 320, x_bar = bars + 352;
    const uint32_t halo_bar = dep_bar + 32;
    auto stage2 = [&](int q) { return base + q * G2_STAGE_BYTES; };
    const uint32_t aux = base + AUX_OFF;

    asm volatile("{\n.reg .pred p;\nsetp.eq.u32 p, %1, 0;\n@p mbarrier.init.shared::cta.b64 [%0], 1;\n"
        "fence.mbarrier_init.release.cluster;\nbarrier.cluster.arrive.relaxed.aligned;\n}" :: "r"(bars), "r"(threadIdx.x) : "memory");
    const int warp = __shfl_sync(0xffffffffu, threadIdx.x >> 5, 0);
    auto cluster_wait = []() { asm volatile("barrier.cluster.wait.acquire.aligned;" ::: "memory"); };
    if ((warp | (blockIdx.x & NGEMM)) == 8) {
        const Role r;
        asm volatile("{\n.reg .pred e;\nelect.sync _|e, 0xffffffff;\n"
            "@e prefetch.tensormap [%0];\n@e prefetch.tensormap [%1];\n}" :: "l"(&prm.x), "l"(&prm.wg + r.rank) : "memory");
        cluster_wait();
        load_stage1(base, base + A_BYTES + r.rank * 16384, full1(0), &prm.x, &prm.wg + r.rank, &prm.wg + r.rank, 0, r.mblk * 64,
                    r.nslot * 128, r.nslot * 128 + 64, 0, stream_policy());
    } else {
        cluster_wait();
    }
    const uint32_t t0 = clock();
    if (TEARLY) {
        uint32_t cta;
        asm volatile("mov.u32 %0, %%ctaid.x;" : "=r"(cta));
        if ((warp | (~cta & NGEMM)) == TEW) load_tail(base, full1(0), &prm.x, &prm.wu_tail, 0, cta - NGEMM, 0, 0);
    }
    asm volatile("{\n.reg .pred e, q;\nelect.sync _|e, 0xffffffff;\nsetp.ne.and.u32 q, %2, 0, e;\n"
        "@q mbarrier.init.shared::cta.b64 [%0], %1;\n@e mbarrier.init.shared::cta.b64 [%0 + 8], %1;\n"
        "@e mbarrier.init.shared::cta.b64 [%0 + 16], %1;\n@e mbarrier.init.shared::cta.b64 [%0 + 24], %1;\n"
        "fence.mbarrier_init.release.cluster;\nbarrier.cluster.arrive.relaxed.aligned;\n}"
        :: "r"(bars + warp * 32), "r"(1 << (0x10fa08 >> warp * 2 & 3)), "r"(warp) : "memory");
    const int lane = threadIdx.x & 31;
    const Role me;
    const int rank = me.rank, role = me.role, mblk = me.mblk, nslot = me.nslot;
    const CUtensorMap* const w0 = &prm.wg + rank;

    unsigned* const flags = prm.flags + mblk * 32;
    if (warp >= 8) {
        asm volatile("setmaxnreg.dec.sync.aligned.u32 %0;" :: "n"(AUX_REGS));
        if (warp == 9) { TRACE_CLEAR(); TRACE_GT(0); TRACE_PUT(1, c0); }
        if ((warp | (~blockIdx.x & NGEMM)) == 8) {
#pragma unroll 1
            for (int i = TEARLY; i < G1_STAGES; i++) {
                if (i == 1) cluster_wait();
                TRACE_S(57, i, 1);
                load_tail(base + i * G1_STAGE_BYTES, full1(i), &prm.x, &prm.wu_tail, i * 64, blockIdx.x - NGEMM, 0, i * 2);
            }
        } else {
            cluster_wait();
        }
    }

    if (blockIdx.x >= NGEMM) {
        if (warp < 8) cluster_wait();
        const uint32_t seen = __ldcg(prm.epoch + blockIdx.x * 16);
        tail_gemm(prm, base, seen + 1, blockIdx.x - NGEMM, warp, lane);
    } else if (warp == 9) {
        const unsigned epoch = __ldcg(prm.epoch + blockIdx.x * 16 + 2) + 1;
        {
            const __nv_bfloat16* const w = prm.pwu + ((mblk >> 1) * 128 + lane / 2) * DF + gate_col(4, nslot) + 96 + rank * 16 + lane % 2 * 8;
            uint4 v[8];
            float cs[8], f[8];
            mbar_wait(empty1(C2AT & 3), 0);
            if (C2AT > 3) mbar_wait(empty1(C2AT & 3), 1);
#pragma unroll
            for (int j = 0; j < 8; j++) v[j] = __ldg(reinterpret_cast<const uint4*>(w + j * 16 * DF));
            unpack8(v[0], cs);
#pragma unroll
            for (int j = 1; j < 8; j++) {
                unpack8(v[j], f);
#pragma unroll
                for (int d = 0; d < 8; d++) cs[d] += f[d];
            }
#pragma unroll
            for (int d = 0; d < 4; d++)
                cs[d] = (lane & 16 ? cs[d + 4] : cs[d]) + __shfl_xor_sync(0xffffffffu, lane & 16 ? cs[d] : cs[d + 4], 16);
#pragma unroll
            for (int d = 0; d < 2; d++) {
                cs[d] = (lane & 8 ? cs[d + 2] : cs[d]) + __shfl_xor_sync(0xffffffffu, lane & 8 ? cs[d] : cs[d + 2], 8);
                cs[d] += __shfl_xor_sync(0xffffffffu, cs[d], 4);
                cs[d] += __shfl_xor_sync(0xffffffffu, cs[d], 2);
            }
            if (!(lane & 6))
                st_tagged(prm.colsum + (16 + nslot / 4) * 1024 + (mblk >> 1) * 128 + nslot % 4 * 32 + rank * 16 + lane % 2 * 8 + (lane >> 3) * 2,
                          cs[0], cs[1], 1 + (epoch & 1));
            TRACE(61);
        }
        if (lane == 0) {
            mbar_wait(sig_bar, 0);
            TRACE(11);
            flag_add(flags + F_LN * 512);
            TRACE(42);
            flag_wait(flags + F_LN * 512, epoch * CNT_LN);
            fence_proxy_async();
            mbar_arrive(dep_bar);
            mbar_wait(sig_bar + 56, 0);
            flag_add(flags + F_LN2 * 512);
            flag_wait(flags + F_LN2 * 512, epoch * CNT_LN);
            fence_proxy_async();
            mbar_arrive(dep_bar + 40);
            TRACE(59);
            prm.epoch[blockIdx.x * 16 + 2] = epoch;
#pragma unroll 1
            for (int p = 3; p < 7; p++) {
                mbar_wait(sig_bar + (p == 3 ? 16 : p * 8), 0);
                TRACE_S(37, p, 4);
                flag_add(flags + (p / 2 + 1) * 512);
                TRACE_S(43, p, 4);
            }
        }
    } else if (warp < 8) {
        asm volatile("setmaxnreg.inc.sync.aligned.u32 %0;" :: "n"(CONSUMER_REGS));
        const int wg = __shfl_sync(0xffffffffu, threadIdx.x >> 7, 0);
        const int cw = threadIdx.x >> 5;
        const int tid = threadIdx.x & 127;
        int spins = 1 << 18;
        float acc[128];
        uint32_t pk[64];
#pragma unroll
        for (int i = 0; i < 64; i++) asm volatile("mov.b32 %0, 0;" : "=r"(pk[i]));
#pragma unroll
        for (int i = 0; i < 128; i++) asm volatile("mov.b32 %0, 0;" : "=f"(acc[i]));
        cluster_wait();

        auto row0 = [&](uint32_t id) { return mblk * 128 + (id & 96) + wg; };
        __nv_bfloat16* optr = prm.pxn + (mblk * 128 + nslot * 16 + cw * 2) * DM + lane * 8;
        uint32_t da = desc_a(base + wg * 8192), db = desc_b(base + A_BYTES);
        auto next1 = [](int s) { return ((s + 1) % G1_STAGES - s) * G1_STAGE_BYTES; };
        auto next2 = [](int q) { return ((q + 1) % G2_STAGES - q) * G2_STAGE_BYTES; };
        uint32_t peer_bars;
        asm volatile("mapa.shared::cluster.u32 %0, %1, %2;" : "=r"(peer_bars) : "r"(bars), "r"(tid & 1));
        if (tid >= 2) peer_bars = 0;
        auto release = [&](uint32_t bar) {
            if (peer_bars) asm volatile("mbarrier.arrive.shared::cluster.b64 _, [%0];" :: "r"(peer_bars + (bar - bars)) : "memory");
        };
        auto up = [](int i) { return 32 + (i & 24) + (i & 3) * 2 + (i >> 2 & 1); };
        auto store_pk = [&](__nv_bfloat16* p, int j) {
            asm volatile("st.global.v4.u32 [%0], {%1,%2,%3,%4};"
                         :: "l"(p), "r"(pk[4 * j]), "r"(pk[4 * j + 1]), "r"(pk[4 * j + 2]), "r"(pk[4 * j + 3]) : "memory");
        };
        auto chunk_geglu = [&](int j) {
#pragma unroll
            for (int i = 4 * j; i < 4 * j + 4; i++) pk[i] = geglu2(pk[i], pk[up(i)]);
            store_pk(optr + (j & 1) * 16 * K2 + (j >> 1) * 32, j);
        };
        auto signal_stores = [&](int p) { __syncwarp(); if (lane == 0) mbar_arrive(sig_bar + p * 8); };

        auto chunk_ln = [&](int k) {
            Floats<6> mo(pk + 32);
            if (k == 0) {
                const uint4* xp = reinterpret_cast<const uint4*>(prm.px + (optr - prm.pxn));
                pk[38] = __ldcg(prm.epoch + blockIdx.x * 16 + 2);
#pragma unroll
                for (int i = 0; i < 8; i++) {
                    const uint4 v = ldg_stream(xp + i * 32, stream_policy());
                    pk[4 * i] = v.x; pk[4 * i + 1] = v.y; pk[4 * i + 2] = v.z; pk[4 * i + 3] = v.w;
                }
            } else if (k >= LN_STEP && k < LN_STEP + 3) {
                if (k == LN_STEP) {
                    mo[0] = bf_lo(uniform(pk[0])); mo[1] = bf_lo(uniform(pk[16]));
                    mo[2] = mo[3] = mo[4] = mo[5] = 0.f;
                }
#pragma unroll
                for (int i = (k - LN_STEP) * 11; i < (k - LN_STEP) * 11 + 11 && i < 32; i++) {
                    const int r = i & 1;
                    const uint32_t w = pk[r * 16 + i / 2];
                    const float lo = bf_lo(w) - mo[r], hi = bf_hi(w) - mo[r];
                    mo[2 + r] += lo + hi;
                    mo[4 + r] = fmaf(hi, hi, fmaf(lo, lo, mo[4 + r]));
                }
                mo.put(pk + 32);
            } else if (k == LN_STEP + 3) {
                const bool second = lane & 16;
                float m1 = (second ? mo[3] : mo[2]) + __shfl_xor_sync(0xffffffffu, second ? mo[2] : mo[3], 16);
                float m2 = (second ? mo[5] : mo[4]) + __shfl_xor_sync(0xffffffffu, second ? mo[4] : mo[5], 16);
#pragma unroll
                for (int o = 8; o > 0; o >>= 1) {
                    m1 += __shfl_xor_sync(0xffffffffu, m1, o);
                    m2 += __shfl_xor_sync(0xffffffffu, m2, o);
                }
                m1 *= 1.f / DM;
                const float var = fmaxf(fmaf(-m1, m1, m2 * (1.f / DM)), 0.f);
                const float mean = round_bf16((second ? mo[1] : mo[0]) + m1);
                const float inv = rcp_fast(round_bf16(sqrt_fast(round_bf16(round_bf16(var) + 1e-5f))));
                if ((lane & 15) == 0) st_tagged(prm.stats + (uint32_t)(optr - prm.pxn) / DM + second, -mean, inv, 2 - (pk[38] & 1));
                const uint32_t split = pack_bf16(inv - round_bf16(inv), inv);
#pragma unroll
                for (int r = 0; r < 2; r++) {
                    const uint32_t f = __shfl_sync(0xffffffffu, split, r * 16);
                    pk[32 + 3 * r] = __byte_perm(__shfl_sync(0xffffffffu, __float_as_uint(mean), r * 16), 0, 0x3232);
                    pk[33 + 3 * r] = __byte_perm(f, 0, 0x3232);
                    pk[34 + 3 * r] = __byte_perm(f, 0, 0x1010);
                }
            } else if (k >= LN_STEP + 4 && k < LN_STEP + 8) {
#pragma unroll
                for (int i = k - LN_STEP - 4; i < 8; i += 4) {
                    const uint32_t* n = pk + 32 + i / 4 * 3;
#pragma unroll
                    for (int j = 4 * i; j < 4 * i + 4; j++) pk[j] = mul2_bf16x2(sub_bf16x2(pk[j], n[0]), n[1], n[2]);
                    store_pk(optr + i * 256, i);
                }
                if (k == LN_STEP + 5 || k == LN_STEP + 7) signal_stores(k == LN_STEP + 5 ? 0 : 7);
            } else if (k == FOLD_STEP) {
                mbar_wait(fold_bar, 0, spins);
                const float2 inv = fold(acc, base, wg);
                mo[0] = inv.x; mo[1] = inv.y;
                mo.put(pk + 32);
            }
        };

        auto halo = [&]() { const uint32_t id = fresh_tid(); return aux + (id & 96) * 128 + (id & 128) * 16 + (id & 31) * 4; };
        auto put = [&](uint32_t a, uint32_t v0, uint32_t v1) {
            asm volatile("st.shared.u32 [%0], %1;\nst.shared.u32 [%0 + 128], %2;" :: "r"(a + HALO_BYTES), "r"(v0), "r"(v1) : "memory");
        };
        auto get = [&](uint32_t a, uint32_t& v0, uint32_t& v1) {
            asm volatile("ld.shared.u32 %0, [%2];\nld.shared.u32 %1, [%2 + 128];" : "=r"(v0), "=r"(v1) : "r"(a) : "memory");
        };
        auto publish = [&](int p) { asm volatile("fence.proxy.async.shared::cta;" ::: "memory"); signal_stores(p); };
        const uint32_t zero[4] = {0, 0, 0, 0};
        auto meet = [&](int n, int k, uint32_t id) {
            if (n == 15 - MEET)
                asm volatile("{\n.reg .b32 c;\nmov.u32 c, %%clock;\nbar.arrive %1, 256;\nlop3.b32 %0, %0, c, 1, 0x70;\n}"
                             : "+r"(peer_bars) : "r"(2 + id / 128) : "memory");
            if (n == 15) {
                asm volatile("{\n.reg .b32 c;\nmov.u32 c, %%clock;\nbar.sync %1, 256;\nlop3.b32 %0, %0, c, 1, 0x70;\n}"
                             : "+r"(peer_bars) : "r"(3 - id / 128) : "memory");
                mma_step(acc, da, db, next1(k & 3), k);
                asm volatile("// batch step");
            }
        };
        auto mix_qk = [&]() {
            uint32_t c[2][4];
            const uint32_t a = halo(), id = fresh_tid();
            if (EREL) { wg_wait<0>(); release(empty1((MIXQ - 1) & 3)); }
            mbar_wait(halo_bar, 0, spins);
#pragma unroll
            for (int n = 0; n < 16; n++) {
                const int b = 1 - n / 8, h = (n & 4) / 2 + n % 2, j = n / 2 % 2;
                uint32_t* const kq = pk + 32 + 8 * h + 4 * j;
                uint32_t* const q = pk + 8 * h + 4 * b;
                mma_sync(j ? q : c[n % 2], kq, q[2 * j], q[2 * j + 1], j ? c[n % 2] : zero);
                if (b) get(a + (h * 2 + j) * 256, kq[1], kq[3]);
                meet(n, MIXQ, id);
            }
        };
        auto chunk_qk = [&](int k) {
            constexpr float LOG2E = 1.4426950408889634f;
            uint32_t* const l = pk + 32;
            Floats<16> e(pk);
            if (k == KK) {
                const uint32_t a = halo();
#pragma unroll
                for (int i = 0; i < 8; i++) put(a + i * 256, pk[33 + 4 * i], pk[35 + 4 * i]);
                publish(1);
            } else if (k == MIXQ + 1) {
                const uint32_t id = fresh_tid();
                const bool u0 = id % 32 / 4 > id % 4 * 2, u1 = id % 32 / 4 > id % 4 * 2 + 1;
                const uint32_t gone = row0(id) < 2 ? (u0 ? 0xffffu : 0u) | (u1 ? 0xffff0000u : 0u) : 0u;
#pragma unroll
                for (int n = 0; n < 8; n++) {
                    const int b = n % 2;
                    const uint32_t* const c = pk + 4 * n;
                    uint32_t v = pack_bf16(__uint_as_float(pick(u0, c[2 - 2 * b], c[2 * b])), __uint_as_float(pick(u1, c[3 - 2 * b], c[1 + 2 * b])));
                    v = mul2_bf16x2(v, 0x3e353e35u, 0x379e379eu);
                    if (!b) v = v & ~gone | 0xce6ece6eu & gone;
                    l[n] = transpose8(v);
                }
            } else if (k == MIXQ + 2) {
#pragma unroll
                for (int h = 0; h < 4; h++) {
                    uint32_t m = max_bf16x2(__byte_perm(l[2 * h], l[2 * h + 1], 0x5410), __byte_perm(l[2 * h], l[2 * h + 1], 0x7632));
                    m = max_bf16x2(m, __shfl_xor_sync(0xffffffffu, m, 1));
                    m = max_bf16x2(m, __shfl_xor_sync(0xffffffffu, m, 2));
#pragma unroll
                    for (int n = 2 * h; n < 2 * h + 2; n++) {
                        const float f = -LOG2E * (n % 2 ? bf_hi(m) : bf_lo(m));
                        e[2 * n] = ex2_fast(fmaf(bf_lo(l[n]), LOG2E, f));
                        e[2 * n + 1] = ex2_fast(fmaf(bf_hi(l[n]), LOG2E, f));
                    }
                }
                e.put(pk);
            } else if (k == MIXQ + 3) {
                uint32_t p[8];
#pragma unroll
                for (int n = 0; n < 8; n++) {
                    float sum = e[2 * n] + e[2 * n + 1];
                    sum += __shfl_xor_sync(0xffffffffu, sum, 1);
                    sum += __shfl_xor_sync(0xffffffffu, sum, 2);
                    const float r = rcp_fast(sum);
                    p[n] = pack_bf16(e[2 * n] * r, e[2 * n + 1] * r);
                }
                const uint32_t a = aux + 5 * HALO_BYTES + fresh_tid() * 16;
                sts128(a, make_uint4(p[0], p[1], p[2], p[3]));
                sts128(a + 4096, make_uint4(p[4], p[5], p[6], p[7]));
            }
        };
        auto values = [&](int h) { return pk + (h & 2) * 16 + (h & 1) * 8; };
        auto mix_pv = [&]() {
            uint32_t lo[8], hi[8];
            const uint32_t id = fresh_tid();
            const uint32_t keep = (id % 4 * 2 > id % 32 / 4 ? 0xffffu : 0u) | (id % 4 * 2 + 1 > id % 32 / 4 ? 0xffff0000u : 0u);
            const uint4 p0 = lds128(aux + 5 * HALO_BYTES + id * 16), p1 = lds128(aux + 6 * HALO_BYTES + id * 16);
            const uint32_t p[8] = {p0.x, p0.y, p0.z, p0.w, p1.x, p1.y, p1.z, p1.w};
#pragma unroll
            for (int n = 0; n < 8; n++)
                asm volatile("and.b32 %0, %2, %3;\nand.b32 %1, %2, %4;" : "=r"(lo[n]), "=r"(hi[n])
                             : "r"(p[n]), "r"(n % 2 ? keep : ~keep), "r"(n % 2 ? ~keep : keep));
            if (EREL) { wg_wait<0>(); release(empty1((MIXV - 1) & 3)); }
            mbar_wait(halo_bar, 1, spins);
#pragma unroll
            for (int n = 0; n < 16; n++) {
                const int i = (n & 8) / 2 + (n & 2) + (n & 4) / 4;
                mma_sync(pk + 4 * (n ^ 4), pk + 4 * (n ^ 4), lo[i], hi[i], zero);
                meet(n, MIXV, id);
            }
        };
        auto chunk_pv = [&](int k) {
            if (k >= VK && k < VK + VN) {
                const uint32_t a = halo();
#pragma unroll
                for (int h = (k - VK) * 4 / VN; h < (k - VK + 1) * 4 / VN; h++) {
                    uint32_t* const w = values(h);
                    uint32_t v[8];
#pragma unroll
                    for (int i = 0; i < 8; i++) v[i] = transpose8(w[h < 2 ? (i & 1) + (i & 2) * 2 + (i & 4) / 2 : (i & 1) * 2 + (i & 2) / 2 + (i & 4)]);
#pragma unroll
                    for (int i = 0; i < 8; i++) w[i] = v[i];
                    put(a + h * 512, w[2], w[3]);
                    put(a + h * 512 + 256, w[6], w[7]);
                }
                if (k == VK + VN - 1) publish(3);
            } else if (k == MIXV - 1) {
                const uint32_t a = halo(), id = fresh_tid();
                optr = prm.pa2 + (size_t)(row0(id) + id % 4 * 4) * K2 + nslot * 128 + (id & 28) * 2;
                mbar_wait(halo_bar, 1, spins);
#pragma unroll
                for (int n = 0; n < 8; n++) {
                    uint32_t* const w = values(n / 2) + n % 2 * 4;
                    w[16] = w[0]; w[17] = w[1];
                    get(a + n * 256, w[18], w[19]);
                }
            } else if (k > MIXV && k <= MIXV + OVS) {
#pragma unroll
                for (int j = 0; j < 8; j++) {
                    if (j * OVS / 8 != k - MIXV - 1) continue;
                    Floats<15> c(pk + j / 2 * 16 + j % 2);
                    asm volatile("st.global.v4.u32 [%0], {%1,%2,%3,%4};"
                                 :: "l"(optr + ((~j & 2) * 8 + j % 2 * 2) * K2 + j / 4 * 64), "r"(pack_bf16(c[0], c[2])),
                                    "r"(pack_bf16(c[4], c[6])), "r"(pack_bf16(c[8], c[10])), "r"(pack_bf16(c[12], c[14])) : "memory");
                }
                if (k == MIXV + OVS) signal_stores(4);
            }
        };

        TRACE_SLOT(tile_slot, 16 + wg * 8);
#pragma unroll 1
        for (int t = 0; t < G1_TILES; t++) {
#pragma unroll
            for (int k = 0; k < G1_KSTEPS; k++) {
                const int s = k & 3;
                if (k % TOP == 0) asm volatile("" : "+r"(t));
                TRACE_STEP(t, k, 0);
                mbar_wait(full1(s), (k >> 2) & 1, spins);
                if (k == 0) TRACE_S(12, t, 0);
                TRACE_STEP(t, k, 1);
                if (wg == 1 && k == G1_KSTEPS - (t == 4 ? SK4 : G1_SKEW)) asm volatile("bar.sync 1, 256;" ::: "memory");
                if (k == MIXV && t == 3) mix_pv();
                else if (k == MIXQ && t == 2) mix_qk();
                else if (t == G1_TILES - 1) mma_step224(acc, da, db, next1(s), k);
                else mma_step(acc, da, db, next1(s), k);
                if (wg == 0 && k == G1_KSTEPS - 1) asm volatile("bar.arrive 1, 256;" ::: "memory");
                wg_wait<1>();
                if (k > 0 && !(EREL && (k == MIXV && t == 3 || k == MIXQ && t == 2))) release(empty1((k - 1) & 3));
                TRACE_STEP(t, k, 2);
                if (t == 0) chunk_ln(k);
                if (k >= 1 && k <= 8 && ((k < GV || k > GV + 3 ? 0x12 : 0x1a) >> t & 1)) {
                    chunk_geglu(k < GV ? k - 1 : (k > GV + 3 ? k - 5 : k - GV + 4));
                    if (k == 8 && t != 3) signal_stores(t + 1);
                }
                if (t == 2) chunk_qk(k);
                if (t == 3) chunk_pv(k);
                if (k == 13) {
                    const uint32_t id = fresh_tid();
                    optr = prm.pa2 + (size_t)(row0(id) + (id & 28) / 2) * K2 + DM + gate_col(t, nslot) + id % 4 * 8;
                    asm volatile("" : "+l"(optr));
                }
            }
            wg_wait<0>();
            fence_regs(acc);
            release(empty1(3));
            if (t == 0) {
                Floats<2> inv(pk + 32);
#pragma unroll
                for (int i = 0; i < 128; i++) acc[i] *= inv[i / 2 % 2];
                fence_regs(acc);
            }
#pragma unroll
            for (int i = 0; i < 64; i++) {
                const int e = i < 32 ? (i & ~7) * 2 + (i & 3) * 4 + (i & 4) / 2 : i * 2;
                pk[i] = pack_bf16(acc[e], acc[e + 1]);
            }
            TRACE_NEXT(tile_slot);
        }

        float accd[64], accs[64];
#pragma unroll
        for (int i = 0; i < 64; i++) accd[i] = 0.f;
#pragma unroll
        for (int u = 0; u < G2_HEAD; u++) {
            const int q = u % G2_STAGES;
            mbar_wait(full2(q), (u / G2_STAGES) & 1, spins);
            mma_step(accd, da, db, next2(q), u);
            wg_wait<1>();
            if (u > 0) release(empty2((u - 1) % G2_STAGES));
            if (u == TLD) {
#pragma unroll
                for (int i = 0; i < 2; i++) {
                    const uint4 v = ldg_stream(prm.tail + role * 512 + i * 256 + threadIdx.x, stream_policy());
                    pk[56 + 4 * i] = v.x; pk[57 + 4 * i] = v.y; pk[58 + 4 * i] = v.z; pk[59 + 4 * i] = v.w;
                }
            }
            if (u >= 1) {
                const int j = (u - 1) / 2;
#pragma unroll
                for (int i = 2 * u - 2; i < 2 * u; i++) pk[i] = geglu2(pk[i], pk[up(i)]);
                if (u % 2 == 0) store_pk(optr + (j & 1) * 16 * K2 + (j >> 1) * 32, j);
            }
            if (u == G2_HEAD - 1) signal_stores(6);
        }
        auto down = [&](int q, uint32_t phase, bool narrow) {
            mbar_wait(full2(q), phase, spins);
            if (narrow) mma_step96(accd, da, db, next2(q), 1);
            else mma_step(accd, da, db, next2(q), 1);
            wg_wait<1>();
            release(empty2((q + G2_STAGES - 1) % G2_STAGES));
        };
        down(5, 0, false);
#pragma unroll 1
        for (uint32_t r = 3; r < 9; r++) {
#pragma unroll
            for (int q = 0; q < G2_STAGES; q++) down(q, r & 1, (NAR0 - q) % NARS == 0 && r <= (NAR0 + TAIL2 * NARS - 1 - q) / G2_STAGES);
        }
        down(0, 1, false);
        down(1, 1, false);
        TRACE_NEXT(tile_slot);
#pragma unroll
        for (int i = 0; i < 64; i++) accs[i] = 0.f;
        uint32_t gk[32], xr[32];
        const uint32_t xs = aux + cw * 2048;
        const uint32_t xrow = xs + ((lane & 7) + ((lane >> 3) & 1) * 8) * 128;
        auto xaddr = [&](int j) { return xrow + (j >> 2) * 16384 + (((((j & 3) * 2) + (lane >> 4)) ^ (lane & 7)) << 4); };
#pragma unroll
        for (int u = G2_DSTEPS; u < G2_KSTEPS; u++) {
            const int q = u % G2_STAGES, v = u - G2_DSTEPS;
            mbar_wait(full2(q), (u / G2_STAGES) & 1, spins);
            if (G2_SKEW > 0 && wg == 1 && u == G2_KSTEPS - G2_SKEW) asm volatile("bar.sync 1, 256;" ::: "memory");
            mma_step(accs, da, db, next2(q), v);
            if (G2_SKEW > 0 && wg == 0 && u == G2_KSTEPS - 1) asm volatile("bar.arrive 1, 256;" ::: "memory");
            if (v == TLD2) {
                TRACE_S(32, wg, 0);
                mbar_wait(dep_bar + 24, 0, spins);
                TRACE_S(33, wg, 0);
#pragma unroll
                for (int i = 0; i < 2; i++) {
                    const uint4 w = ldg_stream(prm.tail + (NGEMM + role) * 512 + i * 256 + threadIdx.x, stream_policy());
                    gk[24 + 4 * i] = w.x; gk[25 + 4 * i] = w.y; gk[26 + 4 * i] = w.z; gk[27 + 4 * i] = w.w;
                }
            }
#pragma unroll
            for (int i = 0; i < 32; i++) {
                if (v == (i < 24 ? i / 4 + 1 : TLD2 + (i < 28 ? GA : GB)))
                    gk[i] = i < 24 ? silu2(accd[2 * i], accd[2 * i + 1])
                                   : silu2(accd[2 * i] + bf_lo(gk[i]), accd[2 * i + 1] + bf_hi(gk[i]));
            }
            if (v == XLD) mbar_wait(x_bar, 0, spins);
            if (v >= XLD && v < XLD + 4) {
#pragma unroll
                for (int j = 2 * (v - XLD); j < 2 * (v - XLD + 1); j++)
                    asm volatile("ldmatrix.sync.aligned.m8n8.x4.shared.b16 {%0,%1,%2,%3}, [%4];"
                                 : "=r"(xr[4 * j]), "=r"(xr[4 * j + 1]), "=r"(xr[4 * j + 2]), "=r"(xr[4 * j + 3])
                                 : "r"(xaddr(j)) : "memory");
            }
            wg_wait<1>();
            if (v == 0) fence_regs(accd);
            if (u - 1 + G2_STAGES < G2_KSTEPS) release(empty2((u - 1) % G2_STAGES));
        }
        __nv_bfloat16* po = prm.pout + (row0(fresh_tid()) + (lane >> 3) * 2) * DM + nslot * 128 + 64 + (lane & 7) * 8;
        uint32_t so = xs + 16384 + (lane >> 3) * 128 + (((lane & 7) ^ (lane >> 3)) << 4);
        const int c0 = uniform(nslot * 128), c1 = uniform(row0(fresh_tid()) >> 1);
        const uint32_t xu = uniform(xs);
        asm volatile("" : "+l"(po), "+r"(so));
        wg_wait<0>();
        fence_regs(accs);
        TRACE_NEXT(tile_slot);
        TRACE_END();
#pragma unroll
        for (int j = 0; j < 8; j++) {
            uint32_t r[4];
#pragma unroll
            for (int i = 0; i < 4; i++) {
                const int e = j * 4 + i;
                asm("fma.rn.bf16x2 %0, %1, %2, %3;" : "=r"(r[i]) : "r"(pack_bf16(accs[2 * e], accs[2 * e + 1])), "r"(gk[e]), "r"(xr[e]));
            }
            asm volatile("stmatrix.sync.aligned.m8n8.x4.shared.b16 [%0], {%1,%2,%3,%4};"
                         :: "r"(xaddr(j)), "r"(r[0]), "r"(r[1]), "r"(r[2]), "r"(r[3]) : "memory");
            if (j == 3)
                asm volatile("{\n.reg .pred e;\nfence.proxy.async.shared::cta;\nbar.warp.sync 0xffffffff;\nelect.sync _|e, 0xffffffff;\n"
                    "@e cp.async.bulk.tensor.3d.global.shared::cta.bulk_group [%0, {%2, %3, %4}], [%1];\n}"
                    :: "l"(&prm.out), "r"(xu), "r"(c0), "r"(c1), "r"(wg) : "memory");
        }
        __syncwarp();
#pragma unroll
        for (int i = 0; i < 4; i++) {
            const uint4 v = lds128((so ^ (i & 1) * 64) + i * 512);
            asm volatile("st.global.v4.u32 [%0], {%1,%2,%3,%4};" :: "l"(po + i * 8 * DM), "r"(v.x), "r"(v.y), "r"(v.z), "r"(v.w) : "memory");
        }
        asm volatile("cp.async.bulk.commit_group;\ncp.async.bulk.wait_group.read 0;" ::: "memory");
        TRACE_LITE(10, clock());
        if (tid == 0) { TRACE_NEXT(tile_slot); if (wg == 1) TRACE_GT(13); TRACE_DUMP(); }
    } else if (warp > 9) {
        const int w = warp - 10;
        const unsigned epoch = __ldcg(prm.epoch + blockIdx.x * 16 + w) + 1;
        const uint32_t tag = 1 + (epoch & 1);
        TRACE_LITE(8, t0);
        const uint32_t at = (w ? CB : CA) >> (CIDX) * 4 & 15;
        mbar_wait(empty1(at & 3), 0);
        mbar_wait(empty1(at & 3), at >> 3);
        if (elect_one()) {
            mbar_expect_tx(cs_bar + w * 8, 16384);
            asm volatile("cp.async.bulk.tensor.2d.shared::cluster.global.mbarrier::complete_tx::bytes [%0], [%1, {%3, %5}], [%2];\n"
                "cp.async.bulk.tensor.2d.shared::cluster.global.mbarrier::complete_tx::bytes [%0 + 8192], [%1, {%4, %5}], [%2];"
                :: "r"(aux + w * 16384), "l"(w0), "r"(cs_bar + w * 8), "r"(nslot * 128), "r"(nslot * 128 + 64),
                   "r"(((mblk & ~1) + w) * 64) : "memory");
        }
        float cs[8];
#pragma unroll
        for (int d = 0; d < 8; d++) cs[d] = 0.f;
        const uint32_t wa = aux + w * 8192 + (lane >> 3) * 128 + (((lane & 7) ^ (lane >> 3)) << 4);
        uint4 v[8];
        auto fetch = [&](int h, uint32_t off) {
#pragma unroll
            for (int j = 0; j < 4; j++) v[h * 4 + j] = lds128((wa ^ (j & 1) * 64) + off + h * 2048 + j * 512);
        };
        auto add = [&](int h) {
#pragma unroll
            for (int j = 0; j < 4; j++) {
                float f[8];
                unpack8(v[h * 4 + j], f);
#pragma unroll
                for (int d = 0; d < 8; d++) cs[d] += f[d];
            }
        };
        if (CST) { mbar_wait(empty1(CST & 3), 0); mbar_wait(empty1(CST & 3), CST >> 3); }
        mbar_wait(cs_bar, 0);

        fetch(0, 0);
#pragma unroll 1
        for (int i = 0; i < 4; i++) {
            fetch(1, (i >> 1) * 16384 + (i & 1) * 4096);
            add(0);
            if (i == 1) mbar_wait(cs_bar + 8, 0);
            fetch(0, (i + 1 & 2) * 8192 + (~i & 1) * 4096);
            add(1);
        }
#pragma unroll
        for (int d = 0; d < 4; d++)
            cs[d] = (lane & 16 ? cs[d + 4] : cs[d]) + __shfl_xor_sync(0xffffffffu, lane & 16 ? cs[d] : cs[d + 4], 16);
#pragma unroll
        for (int d = 0; d < 2; d++)
            cs[d] = (lane & 8 ? cs[d + 2] : cs[d]) + __shfl_xor_sync(0xffffffffu, lane & 8 ? cs[d] : cs[d + 2], 8);
        st_tagged(prm.colsum + (nslot * 2 + rank) * 1024 + (mblk >> 1) * 128 + w * 64 + (lane & 7) * 8 + (lane >> 3) * 2,
                  cs[0], cs[1], tag);

        fold_operands(prm, base, nslot, mblk, tag, w, lane);
        if (lane == 0) {
            mbar_arrive(fold_bar);
            prm.epoch[blockIdx.x * 16 + w] = epoch;
            if (w == 0) {
                TRACE(35);
#pragma unroll 1
                for (int j = F_FIRST; j <= F_TAIL2; j++) {
                    flag_wait(flags + j * 512, epoch * (j == F_EARLY ? CNT_EARLY : (j == F_TAIL2 ? 1 : CNT_LATE)));
                    fence_proxy_async();
                    if (j != F_FIRST) mbar_arrive(dep_bar + (j - F_FIRST) * 8);
                }
            } else {
#pragma unroll 1
                for (int j = 0; j < 2; j++) {
                    uint8_t* const h = prm.halo + (j * NGEMM + role) * HALO_BYTES;
                    unsigned* const f = prm.flags + F_HALO * 512 + role * 32;
                    mbar_wait(sig_bar + 8 + j * 16, 0);
                    TRACE_S(38, j, 0); TRACE_S(9, j, 1);
                    asm volatile("cp.async.bulk.global.shared::cta.bulk_group [%0], [%1], %2;\n"
                        "cp.async.bulk.commit_group;\ncp.async.bulk.wait_group 0;"
                        :: "l"(h + HALO_BYTES), "r"(aux + 4 * HALO_BYTES), "n"(HALO_BYTES) : "memory");
                    fence_proxy_async();
                    TRACE_S(39, j, 0); TRACE_S(10, j, 1);
                    flag_add(f);
                    TRACE_S(40, j, 0); TRACE_S(34, j, 1);
                    if (mblk) flag_wait(f - 32, epoch * 2 - 1 + j);
                    fence_proxy_async();
                    TRACE_S(41, j, 0); TRACE_S(36, j, 1);
                    mbar_expect_tx(halo_bar, HALO_BYTES);
                    asm volatile("cp.async.bulk.shared::cluster.global.mbarrier::complete_tx::bytes [%0], [%1], %2, [%3];"
                        :: "r"(aux), "l"(mblk ? h : prm.halo), "n"(HALO_BYTES), "r"(halo_bar) : "memory");
                }
            }
        }
    } else {
#pragma unroll
        for (int k = 1; k < G1_STAGES; k++) {
            const uint32_t sa = base + k * G1_STAGE_BYTES;
            if (PACE0 + PACE) while ((uint32_t)clock() - t0 < (k == 3 ? PACE3 : PACE0 + (k - 1) * PACE)) {}
            load_stage1(sa, sa + A_BYTES + rank * 16384, full1(k), &prm.x, w0, w0, k * 64, mblk * 64, nslot * 128,
                        nslot * 128 + 64, 0, stream_policy());
        }
        if (elect_one()) {
            prefetch_map(&prm.xn); prefetch_map(&prm.wqkv);
            prefetch_map(&prm.a2); prefetch_map(&prm.wo); prefetch_map(&prm.wd); prefetch_map(&prm.out);
        }
        auto load_x = [&]() {
            if (elect_one()) {
                mbar_expect_tx(x_bar, 32768);
                tma_3d(aux, &prm.x, x_bar, nslot * 128, mblk * 64, 0, stream_policy());
                tma_3d(aux + 16384, &prm.x, x_bar, nslot * 128 + 64, mblk * 64, 0, stream_policy());
            }
            __syncwarp();
        };
        uint32_t ph = 0;
#pragma unroll 1
        for (int t = 0; t < G1_TILES; t++) {
            const int col1 = (t == 1 ? rank * DM + nslot * 128 : gate_col(t, nslot)) + 64;
            const int col0 = t == 2 ? 2 * DM + nslot * 128 + rank * 64 : col1 - 64;
            if (t == 1) { TRACE_PUT(2, t0); TRACE(14); mbar_wait_warp(dep_bar, 0); TRACE(3); }
#pragma unroll 1
            for (int k = t ? 0 : G1_STAGES; k < G1_KSTEPS; k++) {
                const int s = k & 3;
                if (t == 1 && k == 8) mbar_wait_warp(dep_bar + 40, 0);
                if (t * 16 + k == (PFK)) {
                    asm volatile("{\n.reg .pred e;\nelect.sync _|e, 0xffffffff;\n"
                        "@e cp.async.bulk.prefetch.tensor.5d.L2.global [%0, {%1, %4, %4, %4, %3}];\n"
                        "@e cp.async.bulk.prefetch.tensor.5d.L2.global [%0, {%2, %4, %4, %4, %3}];\n}"
                        :: "l"(&prm.wd), "r"(nslot * 128), "r"(nslot * 128 + 64), "r"((mblk + TAIL2) * 2), "r"(0) : "memory");
                }
                mbar_wait_warp(empty1(s), ph);
                const uint32_t sa = base + s * G1_STAGE_BYTES;
                load_stage1(sa, sa + A_BYTES + rank * 16384, full1(s), t ? &prm.xn : &prm.x, t == 1 || t == 2 ? &prm.wqkv : w0,
                            t == 1 ? &prm.wqkv : w0, k * 64, mblk * 64, col0, col1, t & 3,
                            stream_policy());
                if (s == 3) ph ^= 1;
                if (t * 16 + k == (XK)) load_x();
            }
        }
        TRACE(4);
        mbar_wait_warp(dep_bar + 8, 0);
        TRACE(5);
        int q = 0, narrow = 0; uint32_t ph2 = 1;
#pragma unroll 1
        for (int u = 0; u < G2_KSTEPS; u++) {
            if (u == G2_LATE) { TRACE(6); mbar_wait_warp(dep_bar + 16, 0); TRACE(7); }
            const uint32_t sa = stage2(q);
            const bool down = u < G2_DSTEPS;
            const int k = !down ? u - G2_DSTEPS : (G2_NARROW >> u & 1 ? narrow++ : u + TAIL2 - narrow);
            mbar_wait_warp(u < G2_STAGES ? empty1((u * 2 + 1) / 3) : empty2(q), u < G2_STAGES ? ph : ph2);
            load_stage2(sa, sa + A_BYTES + rank * 8192, full2(q), &prm.a2, down ? &prm.wd : &prm.wo, (down ? DM : 0) + k * 64,
                        mblk * 64, nslot * 128 + rank * 64, down ? 0 : k * 2, down ? k * 2 : 0, stream_policy());
            if (++q == G2_STAGES) { q = 0; ph2 ^= 1; }
        }
        TRACE(8);
    }
}

typedef CUresult (*EncodeFn)(CUtensorMap*, CUtensorMapDataType, cuuint32_t, void*, const cuuint64_t*, const cuuint64_t*,
                             const cuuint32_t*, const cuuint32_t*, CUtensorMapInterleave, CUtensorMapSwizzle,
                             CUtensorMapL2promotion, CUtensorMapFloatOOBfill);

void encode(EncodeFn fn, CUtensorMap* m, const void* ptr, int rank, const cuuint64_t* dims, const cuuint64_t* strides,
            const cuuint32_t* box) {
    const cuuint32_t es[5] = {1, 1, 1, 1, 1};
    fn(m, CU_TENSOR_MAP_DATA_TYPE_BFLOAT16, rank, const_cast<void*>(ptr), dims, strides, box, es,
       CU_TENSOR_MAP_INTERLEAVE_NONE, box[0] == 32 ? CU_TENSOR_MAP_SWIZZLE_64B : CU_TENSOR_MAP_SWIZZLE_128B,
       CU_TENSOR_MAP_L2_PROMOTION_L2_128B, CU_TENSOR_MAP_FLOAT_OOB_FILL_NONE);
}
void encode_rows(EncodeFn fn, CUtensorMap* m, const void* ptr, int cols, int box_rows, int box_parity) {
    const cuuint64_t dims[3] = {(cuuint64_t)cols, SEQ / 2, 2}, strides[2] = {(cuuint64_t)cols * 4, (cuuint64_t)cols * 2};
    const cuuint32_t box[3] = {64, (cuuint32_t)box_rows, (cuuint32_t)box_parity};
    encode(fn, m, ptr, 3, dims, strides, box);
}
void encode_w1(EncodeFn fn, CUtensorMap* m, const void* ptr, int cols) {
    const cuuint64_t dims[2] = {(cuuint64_t)cols, DM}, strides[1] = {(cuuint64_t)cols * 2};
    const cuuint32_t box[2] = {64, 64};
    encode(fn, m, ptr, 2, dims, strides, box);
}
void encode_tail(EncodeFn fn, CUtensorMap* m, const void* ptr, int rows, int cols, int n) {
    const cuuint64_t rb = cols * 2;
    const cuuint64_t dims[5] = {32, (cuuint64_t)n, (cuuint64_t)rows / (4 * n), 4, 8}, strides[4] = {rb, 4 * n * rb, n * rb, 256};
    const cuuint32_t box[5] = {32, (cuuint32_t)n, 16 / (cuuint32_t)n, 4, 4};
    encode(fn, m, (const __nv_bfloat16*)ptr + cols - 1024 + 96, 5, dims, strides, box);
}
void encode_w2(EncodeFn fn, CUtensorMap* m, const void* ptr, int rows) {
    const cuuint64_t rb = DM * 2;
    const cuuint64_t dims[5] = {DM, 2, 4, 4, (cuuint64_t)rows / 32}, strides[4] = {rb, 8 * rb, 2 * rb, 32 * rb};
    const cuuint32_t box[5] = {64, 2, 4, 4, 2};
    encode(fn, m, ptr, 5, dims, strides, box);
}
void encode_wo(EncodeFn fn, CUtensorMap* m, const void* ptr) {
    const cuuint64_t rb = DM * 2;
    const cuuint64_t dims[5] = {DM, 4, DM / 32, 2, 4}, strides[4] = {8 * rb, 32 * rb, rb, 2 * rb};
    const cuuint32_t box[5] = {64, 4, 2, 2, 4};
    encode(fn, m, ptr, 5, dims, strides, box);
}

}

extern "C" void kernel_launch(void* const* d_in, const int* in_sizes, int n_in, void* d_out, int out_size) {
    (void)in_sizes; (void)n_in; (void)out_size;
    static EncodeFn fn = nullptr;
    static Params prm;
    if (!fn) {
        cudaDriverEntryPointQueryResult st;
        cudaGetDriverEntryPoint("cuTensorMapEncodeTiled", (void**)&fn, cudaEnableDefault, &st);
        cudaGetSymbolAddress((void**)&prm.pxn, g_xn);
        cudaGetSymbolAddress((void**)&prm.pa2, g_a2);
        cudaGetSymbolAddress((void**)&prm.tail, g_tail);
        cudaGetSymbolAddress((void**)&prm.halo, g_halo);
        cudaGetSymbolAddress((void**)&prm.stats, g_stats);
        cudaGetSymbolAddress((void**)&prm.colsum, g_colsum);
        cudaGetSymbolAddress((void**)&prm.flags, g_flags);
        cudaGetSymbolAddress((void**)&prm.epoch, g_epoch);
        cudaFuncSetAttribute(fused_kernel, cudaFuncAttributeMaxDynamicSharedMemorySize, SMEM_BYTES);
    }
    encode_rows(fn, &prm.x, d_in[0], DM, 64, 2);
    encode_rows(fn, &prm.xn, prm.pxn, DM, 64, 2);
    encode_rows(fn, &prm.a2, prm.pa2, K2, 64, 2);
    encode_rows(fn, &prm.out, d_out, DM, 16, 1);
    encode_w1(fn, &prm.wqkv, d_in[1], NQKV);
    encode_w1(fn, &prm.wg, d_in[4], DF);
    encode_w1(fn, &prm.wu, d_in[5], DF);
    encode_tail(fn, &prm.wu_tail, d_in[5], DM, DF, 8);
    encode_tail(fn, &prm.wd_tail, d_in[6], DF, DM, 2);
    encode_wo(fn, &prm.wo, d_in[2]);
    encode_w2(fn, &prm.wd, d_in[6], DF);
    prm.px = (const __nv_bfloat16*)d_in[0];
    prm.pwu = (const __nv_bfloat16*)d_in[5];
    prm.pout = (__nv_bfloat16*)d_out;
    fused_kernel<<<NCTA, 384, SMEM_BYTES>>>(prm);
}
```

```cpp
#include <cuda_runtime.h>
#include <cuda_bf16.h>
#include <cuda.h>
#include <stdint.h>
#include <limits.h>

#define LNS 3
#define FS 14
#define CA 0x87658765u
#define CB 0x65876587u
#define CST 10
#define CIDX nslot
#define PACE0 900
#define PACE 425
#define PACE3 1700
#define TSUM 39
#define STEPNS 79
#define REST 65000.f
#define ROLL 1
#define BAL 1
#define C2AT 2
#define TPACE 425
#define TEARLY 1
#define TEW 8
#define WDPF 1
#define TFOLD 1
#define MIXQ 8
#define MIXV 9
#define TLD2 7
#define XLD 7
#define VK 1
#define VN 2
#define KK 2
#define EREL 0
#define MEET 4
#define OVS 4
#define GV 3
#define TOP 16
#define SK2 5
#define PFK 60 + mblk
#define XK 66 + nslot
#define TSK 2
#define TW0 600
#define TLD 2
#define SK4 2
#define GA 3
#define GB 4

namespace {

constexpr int SEQ = 2048, DM = 1024, DF = 3584, K2 = DM + DF, NQKV = 3 * DM;
constexpr int NGEMM = 128, NCTA = 132;
constexpr int G1_STAGES = 4, G1_STAGE_BYTES = 49152, G1_KSTEPS = 16, G1_TILES = 5;
constexpr int G2_STAGES = 6, G2_STAGE_BYTES = 32768, G2_KSTEPS = 72, G2_LATE = 40, G2_DSTEPS = 56;
constexpr int G2_HEAD = 17;
constexpr int LN_STEP = LNS, FOLD_STEP = FS;
constexpr int A_BYTES = 16384;
constexpr int AUX_OFF = G1_STAGES * G1_STAGE_BYTES;
constexpr int BAR_OFF = AUX_OFF + 32768;
constexpr int PLAN_OFF = BAR_OFF + 384, STAT_OFF = BAR_OFF + 1536;
constexpr int SMEM_BYTES = BAR_OFF + 2816;
constexpr int G1_SKEW = 2, G2_SKEW = SK2;
constexpr int CONSUMER_REGS = 224, AUX_REGS = 56;
constexpr int HALO_BYTES = 4096;
constexpr int SHARE_MIN = 5, SHARE_MAX = 18, SHARE_SUM = TSUM;

enum { F_LN = 0, F_LN2 = 1, F_FIRST = 2, F_SECOND = 3, F_SHARE = 4, F_EARLY = 5, F_LATE = 6, F_TAIL2 = 7, F_PACE = 8, F_HALO = 9 };
constexpr unsigned CNT_LN = 8, CNT_EARLY = 9, CNT_LATE = 8;

__device__ __align__(1024) __nv_bfloat16 g_xn[SEQ * DM];
__device__ __align__(1024) __nv_bfloat16 g_a2[SEQ * K2];
__device__ __align__(128) uint4 g_tail[2 * NGEMM * 512];
__device__ __align__(128) uint8_t g_halo[(2 * NGEMM + 1) * HALO_BYTES];
__device__ __align__(128) float2 g_stats[SEQ];
__device__ __align__(128) float g_colsum[18 * 1024];
__device__ __align__(128) unsigned g_flags[(F_HALO + 8) * 16 * 32];
__device__ __align__(128) unsigned g_epoch[NCTA * 16];

struct Params {
    const __nv_bfloat16 *px, *pwu;
    __nv_bfloat16 *pxn, *pa2, *pout;
    uint4* tail;
    uint8_t* halo;
    float2* stats;
    float* colsum;
    unsigned *flags, *epoch;
    unsigned long long* trace;
    CUtensorMap x, wg, wu, xn, wqkv, a2, wu_tail, wd_tail, wo, wd, out;
};

extern __shared__ __align__(1024) uint8_t smem_raw[];

#define TRACE(slot) do {} while (0)
#define TRACE_GT(slot) do {} while (0)
#define TRACE_S(slot, v, want) do {} while (0)
#define TRACE_GET(v) do {} while (0)
#define TRACE_PUT(slot, v) do {} while (0)
#define TRACE_SLOT(v, slot) do {} while (0)
#define TRACE_NEXT(v) do {} while (0)
#define TRACE_DUMP() do {} while (0)
#define TRACE_CLEAR() do {} while (0)
#define STAGE_TRACE 0
#define TRACE_END() do {} while (0)
#define TRACE_LITE(i, c) do {} while (0)
#define TRACE_STEP(t, k, i) do {} while (0)

__device__ __forceinline__ uint32_t smem_u32(const void* p) { return (uint32_t)__cvta_generic_to_shared(p); }
__device__ __forceinline__ void mbar_init(uint32_t bar, uint32_t cnt) {
    asm volatile("mbarrier.init.shared::cta.b64 [%0], %1;" :: "r"(bar), "r"(cnt) : "memory");
}
__device__ __forceinline__ void mbar_expect_tx(uint32_t bar, uint32_t bytes) {
    asm volatile("mbarrier.arrive.expect_tx.shared::cta.b64 _, [%0], %1;" :: "r"(bar), "r"(bytes) : "memory");
}
__device__ __forceinline__ void mbar_arrive(uint32_t bar) {
    asm volatile("mbarrier.arrive.shared::cta.b64 _, [%0];" :: "r"(bar) : "memory");
}
__device__ __forceinline__ bool mbar_try_wait(uint32_t bar, uint32_t parity) {
    uint32_t ok;
    asm volatile("{\n.reg .pred p;\nmbarrier.try_wait.parity.shared::cta.b64 p, [%1], %2;\nselp.u32 %0, 1, 0, p;\n}"
                 : "=r"(ok) : "r"(bar), "r"(parity) : "memory");
    return ok;
}
__device__ __forceinline__ void mbar_wait(uint32_t bar, uint32_t parity) {
#pragma unroll 1
    for (int spins = 0; !mbar_try_wait(bar, parity) && spins < (1 << 17); spins++) {}
}
__device__ __forceinline__ void mbar_wait(uint32_t bar, uint32_t parity, int& spins) {
    asm volatile("{\n.reg .pred p;\nagain:\nmbarrier.try_wait.parity.shared::cta.b64 p, [%1], %2;\n@p bra done;\n"
                 "add.s32 %0, %0, -1;\nsetp.gt.s32 p, %0, 0;\n@p bra again;\ndone:\n}" : "+r"(spins) : "r"(bar), "r"(parity) : "memory");
}
template <bool WARP = false> __device__ __forceinline__ unsigned flag_wait(const unsigned* p, unsigned target) {
    unsigned v;
#pragma unroll 1
    for (int spins = 0; spins < (1 << 19); spins++) {
        asm volatile("ld.acquire.gpu.global.u32 %0, [%1];" : "=r"(v) : "l"(p) : "memory");
        if (WARP ? __all_sync(0xffffffffu, (int)(v - target) >= 0) : (int)(v - target) >= 0) break;
        __nanosleep(64);
    }
    return v;
}
__device__ __forceinline__ void mbar_wait_warp(uint32_t bar, uint32_t parity) {
#pragma unroll 1
    for (int spins = 0; !__all_sync(0xffffffffu, mbar_try_wait(bar, parity)) && spins < (1 << 17); spins++) {}
}
__device__ __forceinline__ void flag_add(unsigned* p) {
    asm volatile("red.release.gpu.global.add.u32 [%0], 1;" :: "l"(p) : "memory");
}
__device__ __forceinline__ bool elect_one() {
    uint32_t ok;
    asm volatile("{\n.reg .pred p;\nelect.sync _|p, 0xffffffff;\nselp.u32 %0, 1, 0, p;\n}" : "=r"(ok));
    return ok;
}
__device__ __forceinline__ uint32_t pick(bool c, uint32_t a, uint32_t b) {
    uint32_t r;
    asm("{\n.reg .pred p;\nsetp.ne.b32 p, %3, 0;\nselp.b32 %0, %1, %2, p;\n}" : "=r"(r) : "r"(a), "r"(b), "r"((uint32_t)c));
    return r;
}
__device__ __forceinline__ void fence_proxy_async() { asm volatile("fence.proxy.async.global;" ::: "memory"); }
__device__ __forceinline__ uint4 lds128(uint32_t addr) {
    uint4 v;
    asm volatile("ld.shared.v4.u32 {%0,%1,%2,%3}, [%4];" : "=r"(v.x), "=r"(v.y), "=r"(v.z), "=r"(v.w) : "r"(addr) : "memory");
    return v;
}
__device__ __forceinline__ uint32_t lds32(uint32_t addr) {
    uint32_t v;
    asm volatile("ld.shared.u32 %0, [%1];" : "=r"(v) : "r"(addr) : "memory");
    return v;
}
__device__ __forceinline__ void sts32(uint32_t addr, uint32_t v) { asm volatile("st.shared.u32 [%0], %1;" :: "r"(addr), "r"(v) : "memory"); }
__device__ __forceinline__ uint32_t nanos() { uint32_t t; asm volatile("mov.u32 %0, %%globaltimer_lo;" : "=r"(t)); return t; }
__device__ __forceinline__ float2 lds64f(uint32_t addr) {
    float2 v;
    asm volatile("ld.shared.v2.f32 {%0,%1}, [%2];" : "=f"(v.x), "=f"(v.y) : "r"(addr) : "memory");
    return v;
}
__device__ __forceinline__ void sts128(uint32_t addr, uint4 v) {
    asm volatile("st.shared.v4.u32 [%0], {%1,%2,%3,%4};" :: "r"(addr), "r"(v.x), "r"(v.y), "r"(v.z), "r"(v.w) : "memory");
}
__device__ __forceinline__ void sts64f(uint32_t addr, float a, float b) {
    asm volatile("st.shared.v2.f32 [%0], {%1,%2};" :: "r"(addr), "f"(a), "f"(b) : "memory");
}

__device__ __forceinline__ uint64_t stream_policy() { return 0x12F0000000000000ull; }
__device__ __forceinline__ void tma_3d(uint32_t dst, const CUtensorMap* m, uint32_t bar, int c0, int c1, int c2, uint64_t pol) {
    asm volatile("cp.async.bulk.tensor.3d.shared::cluster.global.mbarrier::complete_tx::bytes.L2::cache_hint"
                 " [%0], [%1, {%3, %4, %5}], [%2], %6;"
                 :: "r"(dst), "l"(m), "r"(bar), "r"(c0), "r"(c1), "r"(c2), "l"(pol) : "memory");
}
__device__ __forceinline__ void load_stage1(uint32_t dst, uint32_t dst_b, uint32_t bar, const CUtensorMap* ma, const CUtensorMap* mb0,
                                            const CUtensorMap* mb1, int k, int row, int col0, int col1, int keep_a, uint64_t pol) {
    asm volatile("{\n.reg .pred e, p, q;\nelect.sync _|e, 0xffffffff;\nsetp.ne.and.b32 p|q, %8, 0, e;\n"
        "@p cp.async.bulk.tensor.3d.shared::cluster.global.mbarrier::complete_tx::bytes [%0], [%3, {%5, %6, %10}], [%2];\n"
        "@q cp.async.bulk.tensor.3d.shared::cluster.global.mbarrier::complete_tx::bytes.L2::cache_hint [%0], [%3, {%5, %6, %10}], [%2], %9;\n"
        "@e cp.async.bulk.tensor.2d.shared::cluster.global.mbarrier::complete_tx::bytes.multicast::cluster.L2::cache_hint"
        " [%1], [%4, {%7, %5}], [%2], %11, %9;\n"
        "@e cp.async.bulk.tensor.2d.shared::cluster.global.mbarrier::complete_tx::bytes.multicast::cluster.L2::cache_hint"
        " [%1 + 8192], [%13, {%14, %5}], [%2], %11, %9;\n"
        "@e mbarrier.arrive.expect_tx.shared::cta.b64 _, [%2], %12;\n}"
        :: "r"(dst), "r"(dst_b), "r"(bar), "l"(ma), "l"(mb0), "r"(k), "r"(row), "r"(col0), "r"(keep_a), "l"(pol), "r"(0),
           "h"((uint16_t)3), "n"(G1_STAGE_BYTES), "l"(mb1), "r"(col1) : "memory");
}
__device__ __forceinline__ void load_stage2(uint32_t dst, uint32_t dst_b, uint32_t bar, const CUtensorMap* ma, const CUtensorMap* mb,
                                            int ka, int row, int col, int kb2, int kb4, uint64_t pol) {
    asm volatile("{\n.reg .pred e;\nelect.sync _|e, 0xffffffff;\n"
        "@e cp.async.bulk.tensor.3d.shared::cluster.global.mbarrier::complete_tx::bytes.L2::cache_hint [%0], [%3, {%5, %6, %10}], [%2], %9;\n"
        "@e cp.async.bulk.tensor.5d.shared::cluster.global.mbarrier::complete_tx::bytes.multicast::cluster.L2::cache_hint"
        " [%1], [%4, {%7, %10, %13, %10, %8}], [%2], %11, %9;\n"
        "@e mbarrier.arrive.expect_tx.shared::cta.b64 _, [%2], %12;\n}"
        :: "r"(dst), "r"(dst_b), "r"(bar), "l"(ma), "l"(mb), "r"(ka), "r"(row), "r"(col), "r"(kb4), "l"(pol), "r"(0),
           "h"((uint16_t)3), "n"(G2_STAGE_BYTES), "r"(kb2) : "memory");
}
__device__ __forceinline__ void load_tail(uint32_t dst, uint32_t bar, const CUtensorMap* ma, const CUtensorMap* mb, int ka, int mblk,
                                          int kb) {
    asm volatile("{\n.reg .pred e;\nelect.sync _|e, 0xffffffff;\n"
        "@e cp.async.bulk.tensor.3d.shared::cluster.global.mbarrier::complete_tx::bytes [%0], [%2, {%3, %4, %5}], [%1];\n"
        "@e cp.async.bulk.tensor.5d.shared::cluster.global.mbarrier::complete_tx::bytes.multicast::cluster"
        " [%9], [%6, {%5, %5, %7, %5, %10}], [%1], %11;\n"
        "@e mbarrier.arrive.expect_tx.shared::cta.b64 _, [%1], %8;\n}"
        :: "r"(dst), "r"(bar), "l"(ma), "r"(ka), "r"(mblk * 64), "r"(0), "l"(mb), "r"(kb), "n"(G1_STAGE_BYTES),
           "r"(dst + A_BYTES + (mblk & 1) * 16384), "r"((mblk & 1) * 4), "h"((uint16_t)3) : "memory");
}
__device__ __forceinline__ uint4 ldg_stream(const void* p, uint64_t pol) {
    uint4 v;
    asm volatile("ld.global.nc.L1::no_allocate.L2::cache_hint.v4.u32 {%0,%1,%2,%3}, [%4], %5;"
                 : "=r"(v.x), "=r"(v.y), "=r"(v.z), "=r"(v.w) : "l"(p), "l"(pol));
    return v;
}
__device__ __forceinline__ void st_tagged(void* p, float a, float b, uint32_t tag) {
    asm volatile("st.relaxed.gpu.global.v2.b32 [%0], {%1,%2};"
                 :: "l"(p), "r"((__float_as_uint(a) & ~3u) | tag), "r"((__float_as_uint(b) & ~3u) | tag) : "memory");
}
__device__ __forceinline__ void st_relaxed(unsigned* p, uint32_t v) {
    asm volatile("st.relaxed.gpu.global.b32 [%0], %1;" :: "l"(p), "r"(v) : "memory");
}
__device__ __forceinline__ bool untagged(const uint4& v, uint32_t tag) {
    return ((v.x ^ tag) | (v.y ^ tag) | (v.z ^ tag) | (v.w ^ tag)) & 3;
}
__device__ __forceinline__ uint4 ld_relaxed(const void* p) {
    uint4 v;
    asm volatile("ld.relaxed.gpu.global.v4.b32 {%0,%1,%2,%3}, [%4];" : "=r"(v.x), "=r"(v.y), "=r"(v.z), "=r"(v.w) : "l"(p) : "memory");
    return v;
}
__device__ __forceinline__ void prefetch_map(const CUtensorMap* m) {
    asm volatile("prefetch.tensormap [%0];" :: "l"(m) : "memory");
}
template <int N> __device__ __forceinline__ void wg_wait() { asm volatile("wgmma.wait_group.sync.aligned %0;" :: "n"(N) : "memory"); }

__device__ __forceinline__ uint32_t desc_a(uint32_t addr) { return (addr & 0x3FFFF) >> 4 | 1 << 16; }
__device__ __forceinline__ uint32_t desc_b(uint32_t addr) { return (addr & 0x3FFFF) >> 4 | 512 << 16; }

#define R8(d, o) "+f"(d[o]), "+f"(d[o+1]), "+f"(d[o+2]), "+f"(d[o+3]), "+f"(d[o+4]), "+f"(d[o+5]), "+f"(d[o+6]), "+f"(d[o+7])
#define R32(d, o) R8(d, o), R8(d, o+8), R8(d, o+16), R8(d, o+24)
#define R64(d, o) R32(d, o), R32(d, o+32)
#define ACC00 "%0,%1,%2,%3,%4,%5,%6,%7,%8,%9,%10,%11,%12,%13,%14,%15,%16,%17,%18,%19,%20,%21,%22,%23,%24,%25,%26,%27,%28,%29,%30,%31,"\
    "%32,%33,%34,%35,%36,%37,%38,%39,%40,%41,%42,%43,%44,%45,%46,%47"
#define ACC0 ACC00 ",%48,%49,%50,%51,%52,%53,%54,%55,%56,%57,%58,%59,%60,%61,%62,%63"
#define ACC1 "%64,%65,%66,%67,%68,%69,%70,%71,%72,%73,%74,%75,%76,%77,%78,%79,%80,%81,%82,%83,%84,%85,%86,%87,%88,%89,%90,%91,%92,%93,%94,%95,"\
    "%96,%97,%98,%99,%100,%101,%102,%103,%104,%105,%106,%107,%108,%109,%110,%111"
#define ACC48 "{" ACC00 "}"
#define ACC64 "{" ACC0 "}"
#define ACC112 "{" ACC0 "," ACC1 "}"
#define ACC128 "{" ACC0 "," ACC1 ",%112,%113,%114,%115,%116,%117,%118,%119,%120,%121,%122,%123,%124,%125,%126,%127}"
#define MMA_K16(shape, acc, a, b, keep, hb) \
    "mov.b64 da, {" a ", 0x40000040};\nmov.b64 db, {" b ", " hb "};\n" \
    "wgmma.mma_async.sync.aligned." shape ".f32.bf16.bf16 " acc ", da, db, " keep ", 1, 1, 0, 1;\n"
#define MMA_NEXT(op, a, b, sa, sb) op " " a ", " a ", " sa ";\n" op " " b ", " b ", " sb ";\n"
#define MMA_STEP_B(shape, acc, a, b, na, nb, keep, hb, sb) \
    "{\n.reg .pred p, q;\n.reg .b64 da, db;\nsetp.ne.b32 p, " keep ", 0;\nsetp.eq.b32 q, 0, 0;\nwgmma.fence.sync.aligned;\n" \
    MMA_K16(shape, acc, a, b, "p", hb) MMA_NEXT("xor.b32", a, b, "2", "128") MMA_K16(shape, acc, a, b, "q", hb) MMA_NEXT("add.s32", a, b, "2", sb) \
    MMA_K16(shape, acc, a, b, "q", hb) MMA_NEXT("xor.b32", a, b, "2", "128") MMA_K16(shape, acc, a, b, "q", hb) MMA_NEXT("add.s32", a, b, na, nb) \
    "wgmma.commit_group.sync.aligned;\n}"
#define MMA_STEP(shape, acc, a, b, na, nb, keep) MMA_STEP_B(shape, acc, a, b, na, nb, keep, "0x40000040", "128")
#define MMA_ARGS "+r"(da), "+r"(db) : "r"(next / 16 - 6), "r"(next / 16 - 384), "r"(keep) : "memory"

__device__ __forceinline__ void mma_step(float (&d)[128], uint32_t& da, uint32_t& db, int next, int keep) {
    asm volatile(MMA_STEP("m64n256k16", ACC128, "%128", "%129", "%130", "%131", "%132") : R64(d, 0), R64(d, 64), MMA_ARGS);
}
__device__ __forceinline__ void mma_rank(float (&d)[128], uint32_t a0, uint32_t a1, uint32_t db) {
    asm volatile("{\n.reg .pred q;\n.reg .b64 db;\nsetp.eq.b32 q, 0, 0;\nmov.b64 db, {%131, 0x40000040};\nwgmma.fence.sync.aligned;\n"
                 "wgmma.mma_async.sync.aligned.m64n256k16.f32.bf16.bf16 " ACC128 ", {%128, %129, %130, %130}, db, q, 1, 1, 1;\n}"
                 : R64(d, 0), R64(d, 64) : "r"(a0), "r"(a1), "r"(0), "r"(db) : "memory");
}
__device__ __forceinline__ void mma_step224(float (&d)[128], uint32_t& da, uint32_t& db, int next, int keep) {
    asm volatile(MMA_STEP("m64n224k16", ACC112, "%112", "%113", "%114", "%115", "%116")
                 : R64(d, 0), R32(d, 64), R8(d, 96), R8(d, 104), MMA_ARGS);
}
__device__ __forceinline__ void mma_step(float (&d)[64], uint32_t& da, uint32_t& db, int next, int keep) {
    asm volatile(MMA_STEP("m64n128k16", ACC64, "%64", "%65", "%66", "%67", "%68") : R64(d, 0), MMA_ARGS);
}
__device__ __forceinline__ void mma_step96(float (&d)[64], uint32_t& da, uint32_t& db, int next, int keep) {
    asm volatile(MMA_STEP("m64n96k16", ACC48, "%48", "%49", "%50", "%51", "%52") : R32(d, 0), R8(d, 32), R8(d, 40), MMA_ARGS);
}
__device__ __forceinline__ void mma_step_tail(float (&d)[128], uint32_t da, uint32_t b, int keep) {
    uint32_t db = (b & 0x3FFFF) >> 4 | 256 << 16;
    const int next = 0;
    asm volatile(MMA_STEP_B("m64n256k16", ACC128, "%128", "%129", "%130", "%131", "%132", "0x80000040", "-96")
                 : R64(d, 0), R64(d, 64), MMA_ARGS);
}

__device__ __forceinline__ uint32_t pack_bf16(float lo, float hi) {
    uint32_t r; asm("cvt.rn.bf16x2.f32 %0, %1, %2;" : "=r"(r) : "f"(hi), "f"(lo)); return r;
}
__device__ __forceinline__ float bf_lo(uint32_t v) { return __uint_as_float(v << 16); }
__device__ __forceinline__ float bf_hi(uint32_t v) { return __uint_as_float(v & 0xffff0000u); }
__device__ __forceinline__ float round_bf16(float v) { return bf_lo(pack_bf16(v, 0.f)); }
__device__ __forceinline__ uint32_t mul_bf16x2(uint32_t a, uint32_t b) {
    uint32_t r; asm("mul.rn.bf16x2 %0, %1, %2;" : "=r"(r) : "r"(a), "r"(b)); return r;
}
__device__ __forceinline__ uint32_t sub_bf16x2(uint32_t a, uint32_t b) {
    uint32_t r; asm("sub.rn.bf16x2 %0, %1, %2;" : "=r"(r) : "r"(a), "r"(b)); return r;
}
__device__ __forceinline__ uint32_t mul2_bf16x2(uint32_t a, uint32_t hi, uint32_t lo) {
    uint32_t r; asm("fma.rn.bf16x2 %0, %1, %2, %3;" : "=r"(r) : "r"(a), "r"(hi), "r"(mul_bf16x2(a, lo))); return r;
}
__device__ __forceinline__ float tanh_fast(float x) { float r; asm("tanh.approx.f32 %0, %1;" : "=f"(r) : "f"(x)); return r; }
__device__ __forceinline__ float gelu_twice(float g) {
    return fmaf(g, tanh_fast(fmaf(g * g, 0.044715f * 0.7978845608f, 0.7978845608f) * g), g);
}
__device__ __forceinline__ uint32_t geglu2(uint32_t g2, uint32_t u2) {
    return mul_bf16x2(pack_bf16(gelu_twice(bf_lo(g2)), gelu_twice(bf_hi(g2))), u2);
}
__device__ __forceinline__ uint32_t silu2(float lo, float hi) {
    const uint32_t h = mul_bf16x2(pack_bf16(lo, hi), 0x3e803e80u);
    return pack_bf16(fmaf(bf_lo(h), tanh_fast(bf_lo(h)), bf_lo(h)), fmaf(bf_hi(h), tanh_fast(bf_hi(h)), bf_hi(h)));
}
__device__ __forceinline__ float ex2_fast(float x) { float r; asm("ex2.approx.ftz.f32 %0, %1;" : "=f"(r) : "f"(x)); return r; }
__device__ __forceinline__ void unpack8(uint4 v, float (&f)[8]) {
    f[0] = bf_lo(v.x); f[1] = bf_hi(v.x); f[2] = bf_lo(v.y); f[3] = bf_hi(v.y);
    f[4] = bf_lo(v.z); f[5] = bf_hi(v.z); f[6] = bf_lo(v.w); f[7] = bf_hi(v.w);
}
template <int N> __device__ __forceinline__ void fence_regs(float (&d)[N]) {
#pragma unroll
    for (int i = 0; i < N; i++) asm volatile("" : "+f"(d[i]) :: "memory");
}

__device__ __forceinline__ float rcp_fast(float x) { float r; asm("rcp.approx.ftz.f32 %0, %1;" : "=f"(r) : "f"(x)); return r; }
__device__ __forceinline__ float sqrt_fast(float x) { float r; asm("sqrt.approx.ftz.f32 %0, %1;" : "=f"(r) : "f"(x)); return r; }
__device__ __forceinline__ uint32_t max_bf16x2(uint32_t a, uint32_t b) {
    uint32_t r; asm("max.bf16x2 %0, %1, %2;" : "=r"(r) : "r"(a), "r"(b)); return r;
}
__device__ __forceinline__ uint32_t transpose8(uint32_t a) {
    uint32_t r; asm volatile("movmatrix.sync.aligned.m8n8.trans.b16 %0, %1;" : "=r"(r) : "r"(a)); return r;
}
__device__ __forceinline__ void mma_sync(uint32_t* d, const uint32_t* a, uint32_t b0, uint32_t b1, const uint32_t* c) {
    asm volatile("mma.sync.aligned.m16n8k16.row.col.f32.bf16.bf16.f32 {%0,%1,%2,%3}, {%4,%5,%6,%7}, {%8,%9}, {%10,%11,%12,%13};"
        : "=r"(d[0]), "=r"(d[1]), "=r"(d[2]), "=r"(d[3])
        : "r"(a[0]), "r"(a[1]), "r"(a[2]), "r"(a[3]), "r"(b0), "r"(b1), "r"(c[0]), "r"(c[1]), "r"(c[2]), "r"(c[3]));
}
template <int N> struct Floats {
    float f[N];
    __device__ __forceinline__ Floats() {}
    __device__ __forceinline__ Floats(const uint32_t* p) {
#pragma unroll
        for (int i = 0; i < N; i++) asm("mov.b32 %0, %1;" : "=f"(f[i]) : "r"(p[i]));
    }
    __device__ __forceinline__ void put(uint32_t* p) const {
#pragma unroll
        for (int i = 0; i < N; i++) asm("mov.b32 %0, %1;" : "=r"(p[i]) : "f"(f[i]));
    }
    __device__ __forceinline__ float& operator[](int i) { return f[i]; }
};
__device__ __forceinline__ uint32_t fresh_tid() { uint32_t r; asm volatile("mov.u32 %0, %%tid.x;" : "=r"(r)); return r; }
template <typename T> __device__ __forceinline__ T uniform(T v) { return __shfl_sync(0xffffffffu, v, 0); }

__device__ __forceinline__ uint32_t plan_word(uint32_t base, int lane) { return uniform(lds32(base + PLAN_OFF + lane * 4)); }

__device__ __forceinline__ void fold_operands(const Params& prm, uint32_t base, int slot, int mblk, uint32_t tag, int w, int lane) {
    uint4 v[9];
#pragma unroll
    for (int m = 0; m < 9; m++) v[m] = make_uint4(0, 0, 0, 0);
    const float* parts = prm.colsum + (slot * 2 + (lane >> 4)) * 1024 + w * 64 + (lane & 15) * 4;
    const float* const rows = &prm.stats[mblk * 128 + w * 64 + lane * 2].x;
#pragma unroll 1
    for (int spins = 0; spins < (1 << 16); spins++) {
        bool missing = false;
        asm volatile("" : "+l"(parts));
#pragma unroll
        for (int m = 0; m < 9; m++) {
            if (untagged(v[m], tag)) {
                missing = true;
                v[m] = ld_relaxed(m < 8 ? parts + m * 128 : rows);
            }
        }
        if (!missing) break;
    }
    float4 c = make_float4(0.f, 0.f, 0.f, 0.f);
#pragma unroll
    for (int m = 0; m < 8; m++) {
        c.x += __uint_as_float(v[m].x ^ tag); c.y += __uint_as_float(v[m].y ^ tag);
        c.z += __uint_as_float(v[m].z ^ tag); c.w += __uint_as_float(v[m].w ^ tag);
    }
    sts128(base + STAT_OFF + w * 512 + lane * 16, make_uint4(v[8].x ^ tag, v[8].y ^ tag, v[8].z ^ tag, v[8].w ^ tag));
    const uint32_t ca = base + AUX_OFF + w * 8192 + (lane >> 4) * 16384 + (lane & 15) * 8;
#pragma unroll
    for (int r = 0; r < 3; r++) {
        const uint32_t lo = pack_bf16(c.x, c.y), hi = pack_bf16(c.z, c.w);
        sts64f((ca ^ r * 16) + r * 128, __uint_as_float(lo), __uint_as_float(hi));
        c.x -= bf_lo(lo); c.y -= bf_hi(lo); c.z -= bf_lo(hi); c.w -= bf_hi(hi);
    }
    asm volatile("fence.proxy.async.shared::cta;" ::: "memory");
    __syncwarp();
}
__device__ __forceinline__ float2 fold(float (&acc)[128], uint32_t base, int wg) {
    const uint32_t id = fresh_tid(), sp = base + STAT_OFF + (id & 96) * 8 + (id & 28) * 4 + wg * 8;
    const uint32_t sel = id & 2 ? 0x4444 : (id & 1 ? 0x4432 : 0x3232);
    const float2 sa = lds64f(sp), sb = lds64f(sp + 128);
    mma_rank(acc, __byte_perm(__float_as_uint(sa.x), 0, sel), __byte_perm(__float_as_uint(sb.x), 0, sel), desc_b(base + AUX_OFF));
    return make_float2(sa.y, sb.y);
}

__device__ __forceinline__ void tail_gemm(const Params& prm, uint32_t base, uint32_t t0, unsigned epoch, int grp, int warp, int lane) {
    constexpr int STEPS = 4 * G1_KSTEPS + SHARE_SUM;
    const uint32_t full = base + BAR_OFF, empty = full + 32, sig = full + 192, dep = full + 256, folded = full + 320;
    const uint32_t tag = 1 + (epoch & 1);
    auto plan = [&](uint32_t p, uint32_t word) { return p < 4 ? p * 64 + grp / 2 * 32 + 15 : word >> p % 4 * 8 & 255; };
    auto rows = [&](uint32_t job) { return job / 32 * 2 + grp % 2; };
    if (warp == 8) {
        if (elect_one()) { prefetch_map(&prm.xn); prefetch_map(&prm.a2); prefetch_map(&prm.wd_tail); }
#pragma unroll 1
        for (int p = 0, i = G1_STAGES; p < 8; p++) {
            const bool first = p < 4;
            if (p == 4) mbar_wait_warp(dep + 16, 0);
            const uint32_t job = plan(p, plan_word(base, lane));
#pragma unroll 1
            for (int k = p ? 0 : G1_STAGES; k <= job % 32; k++, i++) {
                if (WDPF && p == 3 && k % 2 == grp / 2)
                    asm volatile("{\n.reg .pred e;\nelect.sync _|e, 0xffffffff;\n"
                        "@e cp.async.bulk.prefetch.tensor.5d.L2.global [%0, {%2, %2, %1, %2, %3}];\n}"
                        :: "l"(&prm.wd_tail), "r"(k * 8), "r"(0), "r"(grp % 2 * 4) : "memory");
                if (i == 16 || i == 24 || k == 16) mbar_wait_warp(dep + (first ? i & 8 : 24), 0);
                TRACE_S(62, i, 16); TRACE_S(63, i, 4);
                mbar_wait_warp(empty + (i & 3) * 8, ~i >> 2 & 1);
                load_tail(base + (i & 3) * G1_STAGE_BYTES, full + (i & 3) * 8, first ? (p ? &prm.xn : &prm.x) : &prm.a2,
                          first ? &prm.wu_tail : &prm.wd_tail, (first ? 0 : DM) + k * 64, rows(job), first ? k * 2 : k * 8);
            }
        }
        return;
    }
    if (warp == 9) {
#pragma unroll 1
        for (int j = 0; j < 3; j++) {
            flag_wait<true>(prm.flags + (F_LN + j) * 512 + (j < 2 ? lane % 4 * 4 + grp : lane % 16) * 32, epoch * CNT_LN);
            fence_proxy_async();
            __syncwarp();
            if (lane == 0 && j < 2) mbar_arrive(dep + j * 8);
        }
        uint4 v;
#pragma unroll 1
        for (int spins = 0; spins < (1 << 19); spins++) {
            v = ld_relaxed(prm.flags + F_PACE * 512 + lane / 2 * 4);
            if (!__any_sync(0xffffffffu, untagged(v, tag))) break;
            __nanosleep(256);
        }
        const uint32_t ref = uniform(v.x);
        int late = max(max((int)(v.x - ref), (int)(v.y - ref)), max((int)(v.z - ref), (int)(v.w - ref)));
        late = min(max(max(late, __shfl_xor_sync(0xffffffffu, late, 2)), -100000), 100000) * 8 * BAL + lane / 4;
        TRACE_PUT(16 + lane / 4, late + (1 << 20));
        int place = 0, n = SHARE_MIN;
#pragma unroll 1
        for (int g = 0; g < 32; g += 4) place += __shfl_sync(0xffffffffu, late, g) > late;
        const bool mine = (place + 1 >> 1 & 1) == grp / 2;
#pragma unroll 1
        for (int j = 4 * SHARE_MIN; j < SHARE_SUM; j++) {
            if (__reduce_max_sync(0xffffffffu, mine && n < SHARE_MAX ? late : INT_MIN) == late) { n++; late -= STEPNS * 8; }
        }
        auto first = [](uint32_t bits, int n) { return bits & (1u << min(max(n, 0), 24)) - 1; };
        const uint32_t job = lane / 4 * 32 + n - 1;
        if (mine) st_relaxed(prm.flags + F_SHARE * 512 + rows(job) * 32,
                             epoch << 24 | first(0x2aaaaa, 2 * n) | first(0x104104, 6 * n - 66) | first(0x10410, 6 * n - 90));
        if (mine) TRACE_PUT(24 + lane / 4, n);
        sts32(base + PLAN_OFF, __reduce_or_sync(0xffffffffu, mine ? job << place / 2 * 8 : 0));
        if (lane == 0) mbar_arrive(dep + 16);
        flag_wait<true>(prm.flags + F_SECOND * 512 + lane % 16 * 32, epoch * CNT_LN);
        fence_proxy_async();
        __syncwarp();
        if (lane == 0) mbar_arrive(dep + 24);
        return;
    }
    if (warp > 9) {
#pragma unroll 1
        for (int j = 0; j < 8; j++) sts128(base + AUX_OFF + (warp - 10) * 8192 + (j & 4) * 4096 + (j & 3) * 512 + lane * 16, make_uint4(0, 0, 0, 0));
        while ((uint32_t)clock() - t0 < 9000) __nanosleep(256);
        fold_operands(prm, base, 8, grp, tag, warp - 10, lane);
        if (lane) return;
        mbar_arrive(folded);
        if (warp == 11) return;
        TRACE(60);
#pragma unroll 1
        for (int p = 0; p < 8; p++) {
            mbar_wait(sig + p * 8, 0);
            flag_add(prm.flags + (p < 4 ? F_EARLY : F_TAIL2) * 512 + rows(plan(p, lds32(base + PLAN_OFF))) * 32);
            TRACE_S(50, p, 3); TRACE_S(51, p, 7);
        }
        prm.epoch[blockIdx.x * 16] = epoch;
        TRACE_DUMP();
        return;
    }
    asm volatile("setmaxnreg.inc.sync.aligned.u32 %0;" :: "n"(CONSUMER_REGS) : "memory");
    const uint32_t da = desc_a(base + (warp >> 2) * 8192);
    uint4* out = prm.tail;
    float acc[128];
    uint32_t pk[64];
    float2 inv = make_float2(0.f, 0.f);
    int i = 0;
    uint32_t peer;
    asm volatile("mapa.shared::cluster.u32 %0, %1, %2;" : "=r"(peer) : "r"(empty), "r"(lane & 1));
    auto release = [&]() {
        if ((threadIdx.x & 126) == 0 && i <= STEPS - G1_STAGES)
            asm volatile("mbarrier.arrive.shared::cluster.b64 _, [%0];" :: "r"(peer + (i - 1 & 3) * 8) : "memory");
    };
    auto store = [&](int j) {
        asm volatile("st.global.v4.u32 [%0], {%1,%2,%3,%4};" :: "l"(out + j / 2 * 8192 + j % 2 * 256),
                     "r"(pk[4 * j]), "r"(pk[4 * j + 1]), "r"(pk[4 * j + 2]), "r"(pk[4 * j + 3]) : "memory");
    };
    auto step = [&](int k, int left) {
        mbar_wait(full + (i & 3) * 8, i >> 2 & 1);
        TRACE_S(45, warp * 128 + i, 0);
        if (warp >= 4 && left == TSK) asm volatile("bar.sync 1, 256;" ::: "memory");
        mma_step_tail(acc, da + (i & 3) * (G1_STAGE_BYTES / 16), base + A_BYTES + (i & 3) * G1_STAGE_BYTES, k);
        if (warp < 4 && left == 1) asm volatile("bar.arrive 1, 256;" ::: "memory");
    };
    auto drip = [&](int p, int& n) {
        if (n > 0) { store(0); store(1); }
#pragma unroll
        for (int j = 8; j < 64; j++) asm volatile("mov.b32 %0, %1;" : "=r"(pk[j - 8]) : "r"(pk[j]));
        out += 8192;
        __syncwarp();
        if (--n == 0 && lane == 0) mbar_arrive(sig + p * 8 - 8);
    };
#pragma unroll
    for (int j = 0; j < 128; j++) asm volatile("mov.b32 %0, 0;" : "=f"(acc[j]));
#pragma unroll
    for (int j = 0; j < 64; j++) asm volatile("mov.b32 %0, 0;" : "=r"(pk[j]));
#pragma unroll 1
    for (int p = 0; p < 8; p++) {
        step(0, 0);
        i++;
        const uint32_t job = plan(p, plan_word(base, lane));
#pragma unroll 1
        for (int left = job % 32, n = p ? 8 : 0; left > 0; left--) {
            if (i == G1_KSTEPS - TFOLD) { mbar_wait(folded, 0); inv = fold(acc, base, warp >> 2); }
#pragma unroll 1
            do drip(p, n); while (n & 1 && job % 32 < 8);
            step(1, left);
            wg_wait<1>();
            release();
            i++;
        }
        wg_wait<0>();
        fence_regs(acc);
        release();
        if (p == 0) {
#pragma unroll
            for (int j = 0; j < 128; j++) acc[j] *= j & 2 ? inv.y : inv.x;
            fence_regs(acc);
        }
        if (warp == 4) TRACE_PUT(46 + p + p / 4 * 3, (uint32_t)clock());
#pragma unroll
        for (int j = 0; j < 64; j++) pk[j] = pack_bf16(acc[2 * j], acc[2 * j + 1]);
        out = prm.tail + p / 4 * NGEMM * 512 + rows(job) * 512 + threadIdx.x;
    }
#pragma unroll
    for (int j = 0; j < 16; j++) store(j);
    __syncwarp();
    TRACE_S(58, warp, 4);
    if (lane == 0) mbar_arrive(sig + 56);
}

__device__ __forceinline__ int gate_col(int t, int nslot) { return t == 2 ? 960 + nslot * 64 : max(t * 1024 - 1536, 0) + nslot * 128; }

struct Role {
    int rank, role, mblk, nslot;
    __device__ __forceinline__ Role() {
        uint32_t id;
        asm volatile("mov.u32 %0, %%ctaid.x;" : "=r"(id));
        const uint32_t cl = id / 2;
        rank = id & 1;
        role = pick(cl < 4, 32 + cl * 8, cl - 8 + max(4u, (cl - 1) * 37 >> 8)) * 2 + rank;
        mblk = role & 15; nslot = role >> 4;
    }
};

__global__ void __cluster_dims__(2, 1, 1) __launch_bounds__(384, 1)
fused_kernel(const __grid_constant__ Params prm) {
    TRACE_GET(c0);
    const uint32_t base = smem_u32(smem_raw) & ~1023u;
    const uint32_t bars = base + BAR_OFF;
    auto full1 = [&](int s) { return bars + s * 8; };
    auto empty1 = [&](int s) { return bars + 32 + s * 8; };
    auto full2 = [&](int s) { return bars + 64 + s * 8; };
    auto empty2 = [&](int s) { return bars + 128 + s * 8; };
    const uint32_t sig_bar = bars + 192, dep_bar = bars + 256, cs_bar = bars + 304, fold_bar = bars + 320, x_bar = bars + 352;
    const uint32_t halo_bar = dep_bar + 32;
    auto stage2 = [&](int q) { return base + q * G2_STAGE_BYTES; };
    const uint32_t aux = base + AUX_OFF;

    asm volatile("{\n.reg .pred p;\nsetp.eq.u32 p, %1, 0;\n@p mbarrier.init.shared::cta.b64 [%0], 1;\n"
        "fence.mbarrier_init.release.cluster;\nbarrier.cluster.arrive.relaxed.aligned;\n}" :: "r"(bars), "r"(threadIdx.x) : "memory");
    const int warp = __shfl_sync(0xffffffffu, threadIdx.x >> 5, 0);
    auto cluster_wait = []() { asm volatile("barrier.cluster.wait.acquire.aligned;" ::: "memory"); };
    if ((warp | (blockIdx.x & NGEMM)) == 8) {
        const Role r;
        asm volatile("{\n.reg .pred e;\nelect.sync _|e, 0xffffffff;\n"
            "@e prefetch.tensormap [%0];\n@e prefetch.tensormap [%1];\n}" :: "l"(&prm.x), "l"(&prm.wg + r.rank) : "memory");
        cluster_wait();
        load_stage1(base, base + A_BYTES + r.rank * 16384, full1(0), &prm.x, &prm.wg + r.rank, &prm.wg + r.rank, 0, r.mblk * 64,
                    r.nslot * 128, r.nslot * 128 + 64, 0, stream_policy());
    } else {
        cluster_wait();
    }
    const uint32_t t0 = clock();
    if (TEARLY) {
        uint32_t cta;
        asm volatile("mov.u32 %0, %%ctaid.x;" : "=r"(cta));
        if ((warp | (~cta & NGEMM)) == TEW) load_tail(base, full1(0), &prm.x, &prm.wu_tail, 0, cta - NGEMM, 0);
    }
    asm volatile("{\n.reg .pred e, q;\nelect.sync _|e, 0xffffffff;\nsetp.ne.and.u32 q, %2, 0, e;\n"
        "@q mbarrier.init.shared::cta.b64 [%0], %1;\n@e mbarrier.init.shared::cta.b64 [%0 + 8], %1;\n"
        "@e mbarrier.init.shared::cta.b64 [%0 + 16], %1;\n@e mbarrier.init.shared::cta.b64 [%0 + 24], %1;\n"
        "fence.mbarrier_init.release.cluster;\nbarrier.cluster.arrive.relaxed.aligned;\n}"
        :: "r"(bars + warp * 32), "r"(1 << (0x10fa08 >> warp * 2 & 3)), "r"(warp) : "memory");
    const int lane = threadIdx.x & 31;
    const Role me;
    const int rank = me.rank, role = me.role, mblk = me.mblk, nslot = me.nslot;
    const CUtensorMap* const w0 = &prm.wg + rank;

    unsigned* const flags = prm.flags + mblk * 32;
    if (warp >= 8) {
        asm volatile("setmaxnreg.dec.sync.aligned.u32 %0;" :: "n"(AUX_REGS));
        if (warp == 9) { TRACE_CLEAR(); TRACE_GT(0); TRACE_PUT(1, c0); }
        if ((warp | (~blockIdx.x & NGEMM)) == 8) {
#pragma unroll 1
            for (int i = TEARLY; i < G1_STAGES; i++) {
                if (i == 1) cluster_wait();
                TRACE_S(57, i, 1);
                load_tail(base + i * G1_STAGE_BYTES, full1(i), &prm.x, &prm.wu_tail, i * 64, blockIdx.x - NGEMM, i * 2);
            }
        } else {
            cluster_wait();
        }
    }

    if (blockIdx.x >= NGEMM) {
        if (warp < 8) cluster_wait();
        const uint32_t seen = __ldcg(prm.epoch + blockIdx.x * 16);
        tail_gemm(prm, base, t0, seen + 1, blockIdx.x - NGEMM, warp, lane);
    } else if (warp == 9) {
        const unsigned epoch = __ldcg(prm.epoch + blockIdx.x * 16 + 2) + 1;
        const uint32_t n0 = nanos(), c1 = clock();
        {
            const __nv_bfloat16* const w = prm.pwu + ((mblk >> 1) * 128 + lane / 2) * DF + gate_col(4, nslot) + 96 + rank * 16 + lane % 2 * 8;
            uint4 v[8];
            float cs[8], f[8];
            mbar_wait(empty1(C2AT & 3), 0);
            if (C2AT > 3) mbar_wait(empty1(C2AT & 3), 1);
#pragma unroll
            for (int j = 0; j < 8; j++) v[j] = __ldg(reinterpret_cast<const uint4*>(w + j * 16 * DF));
            unpack8(v[0], cs);
#pragma unroll
            for (int j = 1; j < 8; j++) {
                unpack8(v[j], f);
#pragma unroll
                for (int d = 0; d < 8; d++) cs[d] += f[d];
            }
#pragma unroll
            for (int d = 0; d < 4; d++)
                cs[d] = (lane & 16 ? cs[d + 4] : cs[d]) + __shfl_xor_sync(0xffffffffu, lane & 16 ? cs[d] : cs[d + 4], 16);
#pragma unroll
            for (int d = 0; d < 2; d++) {
                cs[d] = (lane & 8 ? cs[d + 2] : cs[d]) + __shfl_xor_sync(0xffffffffu, lane & 8 ? cs[d] : cs[d + 2], 8);
                cs[d] += __shfl_xor_sync(0xffffffffu, cs[d], 4);
                cs[d] += __shfl_xor_sync(0xffffffffu, cs[d], 2);
            }
            if (!(lane & 6))
                st_tagged(prm.colsum + (16 + nslot / 4) * 1024 + (mblk >> 1) * 128 + nslot % 4 * 32 + rank * 16 + lane % 2 * 8 + (lane >> 3) * 2,
                          cs[0], cs[1], 1 + (epoch & 1));
            TRACE(61);
        }
        if (lane == 0) {
            mbar_wait(sig_bar, 0);
            TRACE(11);
            flag_add(flags + F_LN * 512);
            TRACE(42);
            flag_wait(flags + F_LN * 512, epoch * CNT_LN);
            fence_proxy_async();
            mbar_arrive(dep_bar);
            mbar_wait(sig_bar + 56, 0);
            flag_add(flags + F_LN2 * 512);
            flag_wait(flags + F_LN2 * 512, epoch * CNT_LN);
            fence_proxy_async();
            mbar_arrive(dep_bar + 40);
            TRACE(59);
            prm.epoch[blockIdx.x * 16 + 2] = epoch;
#pragma unroll 1
            for (int p = 3; p < 7; p++) {
                mbar_wait(sig_bar + (p == 3 ? 16 : p * 8), 0);
                TRACE_S(37, p, 4);
                flag_add(flags + (p - (p < F_EARLY)) * 512);
                TRACE_S(43, p, 4);
                if (p == 3 && rank == 0) {
                    mbar_wait(sig_bar + 24, 0);
                    const uint32_t n1 = nanos(), end = n1 + (int)((n1 - n0) * REST * rcp_fast((uint32_t)clock() - c1));
                    st_relaxed(prm.flags + F_PACE * 512 + mblk * 4 + nslot, end & ~3u | 1 + (epoch & 1));
                }
            }
        }
    } else if (warp < 8) {
        asm volatile("setmaxnreg.inc.sync.aligned.u32 %0;" :: "n"(CONSUMER_REGS));
        const int wg = __shfl_sync(0xffffffffu, threadIdx.x >> 7, 0);
        const int cw = threadIdx.x >> 5;
        const int tid = threadIdx.x & 127;
        int spins = 1 << 18;
        float acc[128];
        uint32_t pk[64];
#pragma unroll
        for (int i = 0; i < 64; i++) asm volatile("mov.b32 %0, 0;" : "=r"(pk[i]));
#pragma unroll
        for (int i = 0; i < 128; i++) asm volatile("mov.b32 %0, 0;" : "=f"(acc[i]));
        cluster_wait();

        auto row0 = [&](uint32_t id) { return mblk * 128 + (id & 96) + wg; };
        __nv_bfloat16* optr = prm.pxn + (mblk * 128 + nslot * 16 + cw * 2) * DM + lane * 8;
        uint32_t da = desc_a(base + wg * 8192), db = desc_b(base + A_BYTES);
        auto next1 = [](int s) { return ((s + 1) % G1_STAGES - s) * G1_STAGE_BYTES; };
        auto next2 = [](int q) { return ((q + 1) % G2_STAGES - q) * G2_STAGE_BYTES; };
        uint32_t peer_bars;
        asm volatile("mapa.shared::cluster.u32 %0, %1, %2;" : "=r"(peer_bars) : "r"(bars), "r"(tid & 1));
        if (tid >= 2) peer_bars = 0;
        auto release = [&](uint32_t bar) {
            if (peer_bars) asm volatile("mbarrier.arrive.shared::cluster.b64 _, [%0];" :: "r"(peer_bars + (bar - bars)) : "memory");
        };
        auto up = [](int i) { return 32 + (i & 24) + (i & 3) * 2 + (i >> 2 & 1); };
        auto store_pk = [&](__nv_bfloat16* p, int j) {
            asm volatile("st.global.v4.u32 [%0], {%1,%2,%3,%4};"
                         :: "l"(p), "r"(pk[4 * j]), "r"(pk[4 * j + 1]), "r"(pk[4 * j + 2]), "r"(pk[4 * j + 3]) : "memory");
        };
        auto chunk_geglu = [&](int j) {
#pragma unroll
            for (int i = 4 * j; i < 4 * j + 4; i++) pk[i] = geglu2(pk[i], pk[up(i)]);
            store_pk(optr + (j & 1) * 16 * K2 + (j >> 1) * 32, j);
        };
        auto signal_stores = [&](int p) { __syncwarp(); if (lane == 0) mbar_arrive(sig_bar + p * 8); };

        auto chunk_ln = [&](int k) {
            Floats<6> mo(pk + 32);
            if (k == 0) {
                const uint4* xp = reinterpret_cast<const uint4*>(prm.px + (optr - prm.pxn));
                pk[38] = __ldcg(prm.epoch + blockIdx.x * 16 + 2);
#pragma unroll
                for (int i = 0; i < 8; i++) {
                    const uint4 v = ldg_stream(xp + i * 32, stream_policy());
                    pk[4 * i] = v.x; pk[4 * i + 1] = v.y; pk[4 * i + 2] = v.z; pk[4 * i + 3] = v.w;
                }
            } else if (k >= LN_STEP && k < LN_STEP + 3) {
                if (k == LN_STEP) {
                    mo[0] = bf_lo(uniform(pk[0])); mo[1] = bf_lo(uniform(pk[16]));
                    mo[2] = mo[3] = mo[4] = mo[5] = 0.f;
                }
#pragma unroll
                for (int i = (k - LN_STEP) * 11; i < (k - LN_STEP) * 11 + 11 && i < 32; i++) {
                    const int r = i & 1;
                    const uint32_t w = pk[r * 16 + i / 2];
                    const float lo = bf_lo(w) - mo[r], hi = bf_hi(w) - mo[r];
                    mo[2 + r] += lo + hi;
                    mo[4 + r] = fmaf(hi, hi, fmaf(lo, lo, mo[4 + r]));
                }
                mo.put(pk + 32);
            } else if (k == LN_STEP + 3) {
                const bool second = lane & 16;
                float m1 = (second ? mo[3] : mo[2]) + __shfl_xor_sync(0xffffffffu, second ? mo[2] : mo[3], 16);
                float m2 = (second ? mo[5] : mo[4]) + __shfl_xor_sync(0xffffffffu, second ? mo[4] : mo[5], 16);
#pragma unroll
                for (int o = 8; o > 0; o >>= 1) {
                    m1 += __shfl_xor_sync(0xffffffffu, m1, o);
                    m2 += __shfl_xor_sync(0xffffffffu, m2, o);
                }
                m1 *= 1.f / DM;
                const float var = fmaxf(fmaf(-m1, m1, m2 * (1.f / DM)), 0.f);
                const float mean = round_bf16((second ? mo[1] : mo[0]) + m1);
                const float inv = rcp_fast(round_bf16(sqrt_fast(round_bf16(round_bf16(var) + 1e-5f))));
                if ((lane & 15) == 0) st_tagged(prm.stats + (uint32_t)(optr - prm.pxn) / DM + second, -mean, inv, 2 - (pk[38] & 1));
                const uint32_t split = pack_bf16(inv - round_bf16(inv), inv);
#pragma unroll
                for (int r = 0; r < 2; r++) {
                    const uint32_t f = __shfl_sync(0xffffffffu, split, r * 16);
                    pk[32 + 3 * r] = __byte_perm(__shfl_sync(0xffffffffu, __float_as_uint(mean), r * 16), 0, 0x3232);
                    pk[33 + 3 * r] = __byte_perm(f, 0, 0x3232);
                    pk[34 + 3 * r] = __byte_perm(f, 0, 0x1010);
                }
            } else if (k >= LN_STEP + 4 && k < LN_STEP + 8) {
#pragma unroll
                for (int i = k - LN_STEP - 4; i < 8; i += 4) {
                    const uint32_t* n = pk + 32 + i / 4 * 3;
#pragma unroll
                    for (int j = 4 * i; j < 4 * i + 4; j++) pk[j] = mul2_bf16x2(sub_bf16x2(pk[j], n[0]), n[1], n[2]);
                    store_pk(optr + i * 256, i);
                }
                if (k == LN_STEP + 5 || k == LN_STEP + 7) signal_stores(k == LN_STEP + 5 ? 0 : 7);
            } else if (k == FOLD_STEP) {
                mbar_wait(fold_bar, 0, spins);
                const float2 inv = fold(acc, base, wg);
                mo[0] = inv.x; mo[1] = inv.y;
                mo.put(pk + 32);
            }
        };

        auto halo = [&]() { const uint32_t id = fresh_tid(); return aux + (id & 96) * 128 + (id & 128) * 16 + (id & 31) * 4; };
        auto put = [&](uint32_t a, uint32_t v0, uint32_t v1) {
            asm volatile("st.shared.u32 [%0], %1;\nst.shared.u32 [%0 + 128], %2;" :: "r"(a + HALO_BYTES), "r"(v0), "r"(v1) : "memory");
        };
        auto get = [&](uint32_t a, uint32_t& v0, uint32_t& v1) {
            asm volatile("ld.shared.u32 %0, [%2];\nld.shared.u32 %1, [%2 + 128];" : "=r"(v0), "=r"(v1) : "r"(a) : "memory");
        };
        auto publish = [&](int p) { asm volatile("fence.proxy.async.shared::cta;" ::: "memory"); signal_stores(p); };
        const uint32_t zero[4] = {0, 0, 0, 0};
        auto meet = [&](int n, int k, uint32_t id) {
            if (n == 15 - MEET)
                asm volatile("{\n.reg .b32 c;\nmov.u32 c, %%clock;\nbar.arrive %1, 256;\nlop3.b32 %0, %0, c, 1, 0x70;\n}"
                             : "+r"(peer_bars) : "r"(2 + id / 128) : "memory");
            if (n == 15) {
                asm volatile("{\n.reg .b32 c;\nmov.u32 c, %%clock;\nbar.sync %1, 256;\nlop3.b32 %0, %0, c, 1, 0x70;\n}"
                             : "+r"(peer_bars) : "r"(3 - id / 128) : "memory");
                mma_step(acc, da, db, next1(k & 3), k);
                asm volatile("// batch step");
            }
        };
        auto mix_qk = [&]() {
            uint32_t c[2][4];
            const uint32_t a = halo(), id = fresh_tid();
            if (EREL) { wg_wait<0>(); release(empty1((MIXQ - 1) & 3)); }
            mbar_wait(halo_bar, 0, spins);
#pragma unroll
            for (int n = 0; n < 16; n++) {
                const int b = 1 - n / 8, h = (n & 4) / 2 + n % 2, j = n / 2 % 2;
                uint32_t* const kq = pk + 32 + 8 * h + 4 * j;
                uint32_t* const q = pk + 8 * h + 4 * b;
                mma_sync(j ? q : c[n % 2], kq, q[2 * j], q[2 * j + 1], j ? c[n % 2] : zero);
                if (b) get(a + (h * 2 + j) * 256, kq[1], kq[3]);
                meet(n, MIXQ, id);
            }
        };
        auto chunk_qk = [&](int k) {
            constexpr float LOG2E = 1.4426950408889634f;
            uint32_t* const l = pk + 32;
            Floats<16> e(pk);
            if (k == KK) {
                const uint32_t a = halo();
#pragma unroll
                for (int i = 0; i < 8; i++) put(a + i * 256, pk[33 + 4 * i], pk[35 + 4 * i]);
                publish(1);
            } else if (k == MIXQ + 1) {
                const uint32_t id = fresh_tid();
                const bool u0 = id % 32 / 4 > id % 4 * 2, u1 = id % 32 / 4 > id % 4 * 2 + 1;
                const uint32_t gone = row0(id) < 2 ? (u0 ? 0xffffu : 0u) | (u1 ? 0xffff0000u : 0u) : 0u;
#pragma unroll
                for (int n = 0; n < 8; n++) {
                    const int b = n % 2;
                    const uint32_t* const c = pk + 4 * n;
                    uint32_t v = pack_bf16(__uint_as_float(pick(u0, c[2 - 2 * b], c[2 * b])), __uint_as_float(pick(u1, c[3 - 2 * b], c[1 + 2 * b])));
                    v = mul2_bf16x2(v, 0x3e353e35u, 0x379e379eu);
                    if (!b) v = v & ~gone | 0xce6ece6eu & gone;
                    l[n] = transpose8(v);
                }
            } else if (k == MIXQ + 2) {
#pragma unroll
                for (int h = 0; h < 4; h++) {
                    uint32_t m = max_bf16x2(__byte_perm(l[2 * h], l[2 * h + 1], 0x5410), __byte_perm(l[2 * h], l[2 * h + 1], 0x7632));
                    m = max_bf16x2(m, __shfl_xor_sync(0xffffffffu, m, 1));
                    m = max_bf16x2(m, __shfl_xor_sync(0xffffffffu, m, 2));
#pragma unroll
                    for (int n = 2 * h; n < 2 * h + 2; n++) {
                        const float f = -LOG2E * (n % 2 ? bf_hi(m) : bf_lo(m));
                        e[2 * n] = ex2_fast(fmaf(bf_lo(l[n]), LOG2E, f));
                        e[2 * n + 1] = ex2_fast(fmaf(bf_hi(l[n]), LOG2E, f));
                    }
                }
                e.put(pk);
            } else if (k == MIXQ + 3) {
                uint32_t p[8];
#pragma unroll
                for (int n = 0; n < 8; n++) {
                    float sum = e[2 * n] + e[2 * n + 1];
                    sum += __shfl_xor_sync(0xffffffffu, sum, 1);
                    sum += __shfl_xor_sync(0xffffffffu, sum, 2);
                    const float r = rcp_fast(sum);
                    p[n] = pack_bf16(e[2 * n] * r, e[2 * n + 1] * r);
                }
                const uint32_t a = aux + 5 * HALO_BYTES + fresh_tid() * 16;
                sts128(a, make_uint4(p[0], p[1], p[2], p[3]));
                sts128(a + 4096, make_uint4(p[4], p[5], p[6], p[7]));
            }
        };
        auto values = [&](int h) { return pk + (h & 2) * 16 + (h & 1) * 8; };
        auto mix_pv = [&]() {
            uint32_t lo[8], hi[8];
            const uint32_t id = fresh_tid();
            const uint32_t keep = (id % 4 * 2 > id % 32 / 4 ? 0xffffu : 0u) | (id % 4 * 2 + 1 > id % 32 / 4 ? 0xffff0000u : 0u);
            const uint4 p0 = lds128(aux + 5 * HALO_BYTES + id * 16), p1 = lds128(aux + 6 * HALO_BYTES + id * 16);
            const uint32_t p[8] = {p0.x, p0.y, p0.z, p0.w, p1.x, p1.y, p1.z, p1.w};
#pragma unroll
            for (int n = 0; n < 8; n++)
                asm volatile("and.b32 %0, %2, %3;\nand.b32 %1, %2, %4;" : "=r"(lo[n]), "=r"(hi[n])
                             : "r"(p[n]), "r"(n % 2 ? keep : ~keep), "r"(n % 2 ? ~keep : keep));
            if (EREL) { wg_wait<0>(); release(empty1((MIXV - 1) & 3)); }
            mbar_wait(halo_bar, 1, spins);
#pragma unroll
            for (int n = 0; n < 16; n++) {
                const int i = (n & 8) / 2 + (n & 2) + (n & 4) / 4;
                mma_sync(pk + 4 * (n ^ 4), pk + 4 * (n ^ 4), lo[i], hi[i], zero);
                meet(n, MIXV, id);
            }
        };
        auto chunk_pv = [&](int k) {
            if (k >= VK && k < VK + VN) {
                const uint32_t a = halo();
#pragma unroll
                for (int h = (k - VK) * 4 / VN; h < (k - VK + 1) * 4 / VN; h++) {
                    uint32_t* const w = values(h);
                    uint32_t v[8];
#pragma unroll
                    for (int i = 0; i < 8; i++) v[i] = transpose8(w[h < 2 ? (i & 1) + (i & 2) * 2 + (i & 4) / 2 : (i & 1) * 2 + (i & 2) / 2 + (i & 4)]);
#pragma unroll
                    for (int i = 0; i < 8; i++) w[i] = v[i];
                    put(a + h * 512, w[2], w[3]);
                    put(a + h * 512 + 256, w[6], w[7]);
                }
                if (k == VK + VN - 1) publish(3);
            } else if (k == MIXV - 1) {
                const uint32_t a = halo(), id = fresh_tid();
                optr = prm.pa2 + (size_t)(row0(id) + id % 4 * 4) * K2 + nslot * 128 + (id & 28) * 2;
                mbar_wait(halo_bar, 1, spins);
#pragma unroll
                for (int n = 0; n < 8; n++) {
                    uint32_t* const w = values(n / 2) + n % 2 * 4;
                    w[16] = w[0]; w[17] = w[1];
                    get(a + n * 256, w[18], w[19]);
                }
            } else if (k > MIXV && k <= MIXV + OVS) {
#pragma unroll
                for (int j = 0; j < 8; j++) {
                    if (j * OVS / 8 != k - MIXV - 1) continue;
                    Floats<15> c(pk + j / 2 * 16 + j % 2);
                    asm volatile("st.global.v4.u32 [%0], {%1,%2,%3,%4};"
                                 :: "l"(optr + ((~j & 2) * 8 + j % 2 * 2) * K2 + j / 4 * 64), "r"(pack_bf16(c[0], c[2])),
                                    "r"(pack_bf16(c[4], c[6])), "r"(pack_bf16(c[8], c[10])), "r"(pack_bf16(c[12], c[14])) : "memory");
                }
                if (k == MIXV + OVS) signal_stores(4);
            }
        };

        TRACE_SLOT(tile_slot, 16 + wg * 8);
#pragma unroll 1
        for (int t = 0; t < G1_TILES; t++) {
#pragma unroll
            for (int k = 0; k < G1_KSTEPS; k++) {
                const int s = k & 3;
                if (k % TOP == 0) asm volatile("" : "+r"(t));
                TRACE_STEP(t, k, 0);
                mbar_wait(full1(s), (k >> 2) & 1, spins);
                if (k == 0) TRACE_S(12, t, 0);
                TRACE_STEP(t, k, 1);
                if (wg == 1 && k == G1_KSTEPS - (t == 4 ? SK4 : G1_SKEW)) asm volatile("bar.sync 1, 256;" ::: "memory");
                if (k == MIXV && t == 3) mix_pv();
                else if (k == MIXQ && t == 2) mix_qk();
                else if (t == G1_TILES - 1) mma_step224(acc, da, db, next1(s), k);
                else mma_step(acc, da, db, next1(s), k);
                if (wg == 0 && k == G1_KSTEPS - 1) asm volatile("bar.arrive 1, 256;" ::: "memory");
                wg_wait<1>();
                if (k > 0 && !(EREL && (k == MIXV && t == 3 || k == MIXQ && t == 2))) release(empty1((k - 1) & 3));
                TRACE_STEP(t, k, 2);
                if (t == 0) chunk_ln(k);
                if (k >= 1 && k <= 8 && ((k < GV || k > GV + 3 ? 0x12 : 0x1a) >> t & 1)) {
                    chunk_geglu(k < GV ? k - 1 : (k > GV + 3 ? k - 5 : k - GV + 4));
                    if (k == 8 && t != 3) signal_stores(t + 1);
                }
                if (t == 2) chunk_qk(k);
                if (t == 3) chunk_pv(k);
                if (k == 13) {
                    const uint32_t id = fresh_tid();
                    optr = prm.pa2 + (size_t)(row0(id) + (id & 28) / 2) * K2 + DM + gate_col(t, nslot) + id % 4 * 8;
                    asm volatile("" : "+l"(optr));
                }
            }
            wg_wait<0>();
            fence_regs(acc);
            release(empty1(3));
            if (t == 0) {
                Floats<2> inv(pk + 32);
#pragma unroll
                for (int i = 0; i < 128; i++) acc[i] *= inv[i / 2 % 2];
                fence_regs(acc);
            }
#pragma unroll
            for (int i = 0; i < 64; i++) {
                const int e = i < 32 ? (i & ~7) * 2 + (i & 3) * 4 + (i & 4) / 2 : i * 2;
                pk[i] = pack_bf16(acc[e], acc[e + 1]);
            }
            TRACE_NEXT(tile_slot);
        }

        float accd[64], accs[64];
#pragma unroll
        for (int i = 0; i < 64; i++) accd[i] = 0.f;
#pragma unroll
        for (int u = 0; u < G2_HEAD; u++) {
            const int q = u % G2_STAGES;
            mbar_wait(full2(q), (u / G2_STAGES) & 1, spins);
            mma_step(accd, da, db, next2(q), u);
            wg_wait<1>();
            if (u > 0) release(empty2((u - 1) % G2_STAGES));
            if (u == TLD) {
#pragma unroll
                for (int i = 0; i < 2; i++) {
                    const uint4 v = ldg_stream(prm.tail + role * 512 + i * 256 + threadIdx.x, stream_policy());
                    pk[56 + 4 * i] = v.x; pk[57 + 4 * i] = v.y; pk[58 + 4 * i] = v.z; pk[59 + 4 * i] = v.w;
                }
            }
            if (u >= 1) {
                const int j = (u - 1) / 2;
#pragma unroll
                for (int i = 2 * u - 2; i < 2 * u; i++) pk[i] = geglu2(pk[i], pk[up(i)]);
                if (u % 2 == 0) store_pk(optr + (j & 1) * 16 * K2 + (j >> 1) * 32, j);
            }
            if (u == G2_HEAD - 1) signal_stores(6);
        }
        auto down = [&](int q, uint32_t phase, bool narrow) {
            mbar_wait(full2(q), phase, spins);
            if (narrow) mma_step96(accd, da, db, next2(q), 1);
            else mma_step(accd, da, db, next2(q), 1);
            wg_wait<1>();
            release(empty2((q + G2_STAGES - 1) % G2_STAGES));
        };
        uint32_t shared_steps = plan_word(base, lane);
        down(5, 0, false);
#pragma unroll 1
        for (uint32_t r = 3; r < 9; r++, shared_steps >>= G2_STAGES) {
#pragma unroll
            for (int q = 0; q < G2_STAGES; q++) down(q, r & 1, q && shared_steps >> q & 1);
        }
        down(0, 1, false);
        down(1, 1, false);
        TRACE_NEXT(tile_slot);
#pragma unroll
        for (int i = 0; i < 64; i++) accs[i] = 0.f;
        uint32_t gk[32], xr[32];
        const uint32_t xs = aux + cw * 2048;
        const uint32_t xrow = xs + ((lane & 7) + ((lane >> 3) & 1) * 8) * 128;
        auto xaddr = [&](int j) { return xrow + (j >> 2) * 16384 + (((((j & 3) * 2) + (lane >> 4)) ^ (lane & 7)) << 4); };
#pragma unroll
        for (int u = G2_DSTEPS; u < G2_KSTEPS; u++) {
            const int q = u % G2_STAGES, v = u - G2_DSTEPS;
            mbar_wait(full2(q), (u / G2_STAGES) & 1, spins);
            if (G2_SKEW > 0 && wg == 1 && u == G2_KSTEPS - G2_SKEW) asm volatile("bar.sync 1, 256;" ::: "memory");
            mma_step(accs, da, db, next2(q), v);
            if (G2_SKEW > 0 && wg == 0 && u == G2_KSTEPS - 1) asm volatile("bar.arrive 1, 256;" ::: "memory");
            if (v == TLD2) {
                TRACE_S(32, wg, 0);
                mbar_wait(dep_bar + 24, 0, spins);
                TRACE_S(33, wg, 0);
#pragma unroll
                for (int i = 0; i < 2; i++) {
                    const uint4 w = ldg_stream(prm.tail + (NGEMM + role) * 512 + i * 256 + threadIdx.x, stream_policy());
                    gk[24 + 4 * i] = w.x; gk[25 + 4 * i] = w.y; gk[26 + 4 * i] = w.z; gk[27 + 4 * i] = w.w;
                }
            }
#pragma unroll
            for (int i = 0; i < 32; i++) {
                if (v == (i < 24 ? i / 4 + 1 : TLD2 + (i < 28 ? GA : GB)))
                    gk[i] = i < 24 ? silu2(accd[2 * i], accd[2 * i + 1])
                                   : silu2(accd[2 * i] + bf_lo(gk[i]), accd[2 * i + 1] + bf_hi(gk[i]));
            }
            if (v == XLD) mbar_wait(x_bar, 0, spins);
            if (v >= XLD && v < XLD + 4) {
#pragma unroll
                for (int j = 2 * (v - XLD); j < 2 * (v - XLD + 1); j++)
                    asm volatile("ldmatrix.sync.aligned.m8n8.x4.shared.b16 {%0,%1,%2,%3}, [%4];"
                                 : "=r"(xr[4 * j]), "=r"(xr[4 * j + 1]), "=r"(xr[4 * j + 2]), "=r"(xr[4 * j + 3])
                                 : "r"(xaddr(j)) : "memory");
            }
            wg_wait<1>();
            if (v == 0) fence_regs(accd);
            if (u - 1 + G2_STAGES < G2_KSTEPS) release(empty2((u - 1) % G2_STAGES));
        }
        __nv_bfloat16* po = prm.pout + (row0(fresh_tid()) + (lane >> 3) * 2) * DM + nslot * 128 + 64 + (lane & 7) * 8;
        uint32_t so = xs + 16384 + (lane >> 3) * 128 + (((lane & 7) ^ (lane >> 3)) << 4);
        const int c0 = uniform(nslot * 128), c1 = uniform(row0(fresh_tid()) >> 1);
        const uint32_t xu = uniform(xs);
        asm volatile("" : "+l"(po), "+r"(so));
        wg_wait<0>();
        fence_regs(accs);
        TRACE_NEXT(tile_slot);
        TRACE_END();
#pragma unroll
        for (int j = 0; j < 8; j++) {
            uint32_t r[4];
#pragma unroll
            for (int i = 0; i < 4; i++) {
                const int e = j * 4 + i;
                asm("fma.rn.bf16x2 %0, %1, %2, %3;" : "=r"(r[i]) : "r"(pack_bf16(accs[2 * e], accs[2 * e + 1])), "r"(gk[e]), "r"(xr[e]));
            }
            asm volatile("stmatrix.sync.aligned.m8n8.x4.shared.b16 [%0], {%1,%2,%3,%4};"
                         :: "r"(xaddr(j)), "r"(r[0]), "r"(r[1]), "r"(r[2]), "r"(r[3]) : "memory");
            if (j == 3)
                asm volatile("{\n.reg .pred e;\nfence.proxy.async.shared::cta;\nbar.warp.sync 0xffffffff;\nelect.sync _|e, 0xffffffff;\n"
                    "@e cp.async.bulk.tensor.3d.global.shared::cta.bulk_group [%0, {%2, %3, %4}], [%1];\n}"
                    :: "l"(&prm.out), "r"(xu), "r"(c0), "r"(c1), "r"(wg) : "memory");
        }
        __syncwarp();
#pragma unroll
        for (int i = 0; i < 4; i++) {
            const uint4 v = lds128((so ^ (i & 1) * 64) + i * 512);
            asm volatile("st.global.v4.u32 [%0], {%1,%2,%3,%4};" :: "l"(po + i * 8 * DM), "r"(v.x), "r"(v.y), "r"(v.z), "r"(v.w) : "memory");
        }
        asm volatile("cp.async.bulk.commit_group;\ncp.async.bulk.wait_group.read 0;" ::: "memory");
        TRACE_LITE(10, clock());
        if (tid == 0) { TRACE_NEXT(tile_slot); if (wg == 1) TRACE_GT(13); TRACE_DUMP(); }
    } else if (warp > 9) {
        const int w = warp - 10;
        const unsigned epoch = __ldcg(prm.epoch + blockIdx.x * 16 + w) + 1;
        const uint32_t tag = 1 + (epoch & 1);
        TRACE_LITE(8, t0);
        const uint32_t at = (w ? CB : CA) >> (CIDX) * 4 & 15;
        mbar_wait(empty1(at & 3), 0);
        mbar_wait(empty1(at & 3), at >> 3);
        if (elect_one()) {
            mbar_expect_tx(cs_bar + w * 8, 16384);
            asm volatile("cp.async.bulk.tensor.2d.shared::cluster.global.mbarrier::complete_tx::bytes [%0], [%1, {%3, %5}], [%2];\n"
                "cp.async.bulk.tensor.2d.shared::cluster.global.mbarrier::complete_tx::bytes [%0 + 8192], [%1, {%4, %5}], [%2];"
                :: "r"(aux + w * 16384), "l"(w0), "r"(cs_bar + w * 8), "r"(nslot * 128), "r"(nslot * 128 + 64),
                   "r"(((mblk & ~1) + w) * 64) : "memory");
        }
        float cs[8];
#pragma unroll
        for (int d = 0; d < 8; d++) cs[d] = 0.f;
        const uint32_t wa = aux + w * 8192 + (lane >> 3) * 128 + (((lane & 7) ^ (lane >> 3)) << 4);
        uint4 v[8];
        auto fetch = [&](int h, uint32_t off) {
#pragma unroll
            for (int j = 0; j < 4; j++) v[h * 4 + j] = lds128((wa ^ (j & 1) * 64) + off + h * 2048 + j * 512);
        };
        auto add = [&](int h) {
#pragma unroll
            for (int j = 0; j < 4; j++) {
                float f[8];
                unpack8(v[h * 4 + j], f);
#pragma unroll
                for (int d = 0; d < 8; d++) cs[d] += f[d];
            }
        };
        if (CST) { mbar_wait(empty1(CST & 3), 0); mbar_wait(empty1(CST & 3), CST >> 3); }
        mbar_wait(cs_bar, 0);

        fetch(0, 0);
#pragma unroll 1
        for (int i = 0; i < 4; i++) {
            fetch(1, (i >> 1) * 16384 + (i & 1) * 4096);
            add(0);
            if (i == 1) mbar_wait(cs_bar + 8, 0);
            fetch(0, (i + 1 & 2) * 8192 + (~i & 1) * 4096);
            add(1);
        }
#pragma unroll
        for (int d = 0; d < 4; d++)
            cs[d] = (lane & 16 ? cs[d + 4] : cs[d]) + __shfl_xor_sync(0xffffffffu, lane & 16 ? cs[d] : cs[d + 4], 16);
#pragma unroll
        for (int d = 0; d < 2; d++)
            cs[d] = (lane & 8 ? cs[d + 2] : cs[d]) + __shfl_xor_sync(0xffffffffu, lane & 8 ? cs[d] : cs[d + 2], 8);
        st_tagged(prm.colsum + (nslot * 2 + rank) * 1024 + (mblk >> 1) * 128 + w * 64 + (lane & 7) * 8 + (lane >> 3) * 2,
                  cs[0], cs[1], tag);

        fold_operands(prm, base, nslot, mblk, tag, w, lane);
        if (lane == 0) {
            mbar_arrive(fold_bar);
            prm.epoch[blockIdx.x * 16 + w] = epoch;
            if (w == 0) {
                TRACE(35);
#pragma unroll 1
                for (uint32_t j = 0, n = 1 << 24; j < 4; n = (CNT_EARLY | CNT_LATE << 8 | 1 << 16) >> j * 8 & 255, j++) {
                    const uint32_t v = flag_wait(flags + (F_SHARE + j) * 512, epoch * n);
                    fence_proxy_async();
                    if (j) mbar_arrive(dep_bar + j * 8);
                    else sts32(base + PLAN_OFF, v & 0xffffff);
                }
            } else {
#pragma unroll 1
                for (int j = 0; j < 2; j++) {
                    uint8_t* const h = prm.halo + (j * NGEMM + role) * HALO_BYTES;
                    unsigned* const f = prm.flags + F_HALO * 512 + role * 32;
                    mbar_wait(sig_bar + 8 + j * 16, 0);
                    TRACE_S(38, j, 0); TRACE_S(9, j, 1);
                    asm volatile("cp.async.bulk.global.shared::cta.bulk_group [%0], [%1], %2;\n"
                        "cp.async.bulk.commit_group;\ncp.async.bulk.wait_group 0;"
                        :: "l"(h + HALO_BYTES), "r"(aux + 4 * HALO_BYTES), "n"(HALO_BYTES) : "memory");
                    fence_proxy_async();
                    TRACE_S(39, j, 0); TRACE_S(10, j, 1);
                    flag_add(f);
                    TRACE_S(40, j, 0); TRACE_S(34, j, 1);
                    if (mblk) flag_wait(f - 32, epoch * 2 - 1 + j);
                    fence_proxy_async();
                    TRACE_S(41, j, 0); TRACE_S(36, j, 1);
                    mbar_expect_tx(halo_bar, HALO_BYTES);
                    asm volatile("cp.async.bulk.shared::cluster.global.mbarrier::complete_tx::bytes [%0], [%1], %2, [%3];"
                        :: "r"(aux), "l"(mblk ? h : prm.halo), "n"(HALO_BYTES), "r"(halo_bar) : "memory");
                }
            }
        }
    } else {
        constexpr int roll = ROLL;
#pragma unroll roll
        for (int k = 1; k < G1_STAGES; k++) {
            const uint32_t sa = base + k * G1_STAGE_BYTES;
            if (PACE0 + PACE) while ((uint32_t)clock() - t0 < (k == 3 ? PACE3 : PACE0 + (k - 1) * PACE)) {}
            load_stage1(sa, sa + A_BYTES + rank * 16384, full1(k), &prm.x, w0, w0, k * 64, mblk * 64, nslot * 128,
                        nslot * 128 + 64, 0, stream_policy());
        }
        if (elect_one()) {
            prefetch_map(&prm.xn); prefetch_map(&prm.wqkv);
            prefetch_map(&prm.a2); prefetch_map(&prm.wo); prefetch_map(&prm.wd); prefetch_map(&prm.out);
        }
        auto load_x = [&]() {
            if (elect_one()) {
                mbar_expect_tx(x_bar, 32768);
                tma_3d(aux, &prm.x, x_bar, nslot * 128, mblk * 64, 0, stream_policy());
                tma_3d(aux + 16384, &prm.x, x_bar, nslot * 128 + 64, mblk * 64, 0, stream_policy());
            }
            __syncwarp();
        };
        uint32_t ph = 0;
#pragma unroll 1
        for (int t = 0; t < G1_TILES; t++) {
            const int col1 = (t == 1 ? rank * DM + nslot * 128 : gate_col(t, nslot)) + 64;
            const int col0 = t == 2 ? 2 * DM + nslot * 128 + rank * 64 : col1 - 64;
            if (t == 1) { TRACE_PUT(2, t0); TRACE(14); mbar_wait_warp(dep_bar, 0); TRACE(3); }
#pragma unroll 1
            for (int k = t ? 0 : G1_STAGES; k < G1_KSTEPS; k++) {
                const int s = k & 3;
                if (t == 1 && k == 8) mbar_wait_warp(dep_bar + 40, 0);
                if (t * 16 + k == (PFK)) {
                    asm volatile("{\n.reg .pred e;\nelect.sync _|e, 0xffffffff;\n"
                        "@e cp.async.bulk.prefetch.tensor.5d.L2.global [%0, {%1, %4, %4, %4, %3}];\n"
                        "@e cp.async.bulk.prefetch.tensor.5d.L2.global [%0, {%2, %4, %4, %4, %3}];\n}"
                        :: "l"(&prm.wd), "r"(nslot * 128), "r"(nslot * 128 + 64), "r"((mblk + SHARE_MAX) * 2), "r"(0) : "memory");
                }
                mbar_wait_warp(empty1(s), ph);
                const uint32_t sa = base + s * G1_STAGE_BYTES;
                load_stage1(sa, sa + A_BYTES + rank * 16384, full1(s), t ? &prm.xn : &prm.x, t == 1 || t == 2 ? &prm.wqkv : w0,
                            t == 1 ? &prm.wqkv : w0, k * 64, mblk * 64, col0, col1, t & 3,
                            stream_policy());
                if (s == 3) ph ^= 1;
                if (t * 16 + k == (XK)) load_x();
            }
        }
        TRACE(4);
        mbar_wait_warp(dep_bar + 8, 0);
        TRACE(5);
        int q = 0, round = 4, own = SHARE_MAX; uint32_t ph2 = 1;
#pragma unroll 1
        for (int u = 0; u < G2_KSTEPS; u++) {
            if (u == G2_LATE) { TRACE(6); mbar_wait_warp(dep_bar + 16, 0); TRACE(7); }
            const uint32_t sa = stage2(q);
            const bool down = u < G2_DSTEPS;
            const int k = !down ? u - G2_DSTEPS : (u < 18 || u >= 40 || q == 0 ? own++ : (q & 1 ? u / 2 - 9 : round + q * 2));
            mbar_wait_warp(u < G2_STAGES ? empty1((u * 2 + 1) / 3) : empty2(q), u < G2_STAGES ? ph : ph2);
            load_stage2(sa, sa + A_BYTES + rank * 8192, full2(q), &prm.a2, down ? &prm.wd : &prm.wo, (down ? DM : 0) + k * 64,
                        mblk * 64, nslot * 128 + rank * 64, down ? 0 : k * 2, down ? k * 2 : 0, stream_policy());
            if (++q == G2_STAGES) { q = 0; ph2 ^= 1; round++; }
        }
        TRACE(8);
    }
}

typedef CUresult (*EncodeFn)(CUtensorMap*, CUtensorMapDataType, cuuint32_t, void*, const cuuint64_t*, const cuuint64_t*,
                             const cuuint32_t*, const cuuint32_t*, CUtensorMapInterleave, CUtensorMapSwizzle,
                             CUtensorMapL2promotion, CUtensorMapFloatOOBfill);

void encode(EncodeFn fn, CUtensorMap* m, const void* ptr, int rank, const cuuint64_t* dims, const cuuint64_t* strides,
            const cuuint32_t* box) {
    const cuuint32_t es[5] = {1, 1, 1, 1, 1};
    fn(m, CU_TENSOR_MAP_DATA_TYPE_BFLOAT16, rank, const_cast<void*>(ptr), dims, strides, box, es,
       CU_TENSOR_MAP_INTERLEAVE_NONE, box[0] == 32 ? CU_TENSOR_MAP_SWIZZLE_64B : CU_TENSOR_MAP_SWIZZLE_128B,
       CU_TENSOR_MAP_L2_PROMOTION_L2_128B, CU_TENSOR_MAP_FLOAT_OOB_FILL_NONE);
}
void encode_rows(EncodeFn fn, CUtensorMap* m, const void* ptr, int cols, int box_rows, int box_parity) {
    const cuuint64_t dims[3] = {(cuuint64_t)cols, SEQ / 2, 2}, strides[2] = {(cuuint64_t)cols * 4, (cuuint64_t)cols * 2};
    const cuuint32_t box[3] = {64, (cuuint32_t)box_rows, (cuuint32_t)box_parity};
    encode(fn, m, ptr, 3, dims, strides, box);
}
void encode_w1(EncodeFn fn, CUtensorMap* m, const void* ptr, int cols) {
    const cuuint64_t dims[2] = {(cuuint64_t)cols, DM}, strides[1] = {(cuuint64_t)cols * 2};
    const cuuint32_t box[2] = {64, 64};
    encode(fn, m, ptr, 2, dims, strides, box);
}
void encode_tail(EncodeFn fn, CUtensorMap* m, const void* ptr, int rows, int cols, int n) {
    const cuuint64_t rb = cols * 2;
    const cuuint64_t dims[5] = {32, (cuuint64_t)n, (cuuint64_t)rows / (4 * n), 4, 8}, strides[4] = {rb, 4 * n * rb, n * rb, 256};
    const cuuint32_t box[5] = {32, (cuuint32_t)n, 16 / (cuuint32_t)n, 4, 4};
    encode(fn, m, (const __nv_bfloat16*)ptr + cols - 1024 + 96, 5, dims, strides, box);
}
void encode_w2(EncodeFn fn, CUtensorMap* m, const void* ptr, int rows) {
    const cuuint64_t rb = DM * 2;
    const cuuint64_t dims[5] = {DM, 2, 4, 4, (cuuint64_t)rows / 32}, strides[4] = {rb, 8 * rb, 2 * rb, 32 * rb};
    const cuuint32_t box[5] = {64, 2, 4, 4, 2};
    encode(fn, m, ptr, 5, dims, strides, box);
}
void encode_wo(EncodeFn fn, CUtensorMap* m, const void* ptr) {
    const cuuint64_t rb = DM * 2;
    const cuuint64_t dims[5] = {DM, 4, DM / 32, 2, 4}, strides[4] = {8 * rb, 32 * rb, rb, 2 * rb};
    const cuuint32_t box[5] = {64, 4, 2, 2, 4};
    encode(fn, m, ptr, 5, dims, strides, box);
}

}

extern "C" void kernel_launch(void* const* d_in, const int* in_sizes, int n_in, void* d_out, int out_size) {
    (void)in_sizes; (void)n_in; (void)out_size;
    static EncodeFn fn = nullptr;
    static Params prm;
    if (!fn) {
        cudaDriverEntryPointQueryResult st;
        cudaGetDriverEntryPoint("cuTensorMapEncodeTiled", (void**)&fn, cudaEnableDefault, &st);
        cudaGetSymbolAddress((void**)&prm.pxn, g_xn);
        cudaGetSymbolAddress((void**)&prm.pa2, g_a2);
        cudaGetSymbolAddress((void**)&prm.tail, g_tail);
        cudaGetSymbolAddress((void**)&prm.halo, g_halo);
        cudaGetSymbolAddress((void**)&prm.stats, g_stats);
        cudaGetSymbolAddress((void**)&prm.colsum, g_colsum);
        cudaGetSymbolAddress((void**)&prm.flags, g_flags);
        cudaGetSymbolAddress((void**)&prm.epoch, g_epoch);
        cudaFuncSetAttribute(fused_kernel, cudaFuncAttributeMaxDynamicSharedMemorySize, SMEM_BYTES);
    }
    encode_rows(fn, &prm.x, d_in[0], DM, 64, 2);
    encode_rows(fn, &prm.xn, prm.pxn, DM, 64, 2);
    encode_rows(fn, &prm.a2, prm.pa2, K2, 64, 2);
    encode_rows(fn, &prm.out, d_out, DM, 16, 1);
    encode_w1(fn, &prm.wqkv, d_in[1], NQKV);
    encode_w1(fn, &prm.wg, d_in[4], DF);
    encode_w1(fn, &prm.wu, d_in[5], DF);
    encode_tail(fn, &prm.wu_tail, d_in[5], DM, DF, 8);
    encode_tail(fn, &prm.wd_tail, d_in[6], DF, DM, 2);
    encode_wo(fn, &prm.wo, d_in[2]);
    encode_w2(fn, &prm.wd, d_in[6], DF);
    prm.px = (const __nv_bfloat16*)d_in[0];
    prm.pwu = (const __nv_bfloat16*)d_in[5];
    prm.pout = (__nv_bfloat16*)d_out;
    fused_kernel<<<NCTA, 384, SMEM_BYTES>>>(prm);
}
```

```cpp
#include <cuda_runtime.h>
#include <cuda_bf16.h>
#include <cuda.h>
#include <stdint.h>
#include <limits.h>

#define LNS 3
#define FS 14
#define CA 0x87658765u
#define CB 0x65876587u
#define CST 10
#define CIDX nslot
#define PACE0 900
#define PACE 425
#define PACE3 1700
#define TSUM 43
#define SMIN 3
#define SMAX 22
#define BIAS 30
#define DUE 75300.f
#define TLO 36
#define SWAP 1
#define STEPNS 79
#define REST 65000.f
#define ROLL 1
#define BAL 1
#define C2AT 2
#define TPACE 425
#define TEARLY 1
#define TEW 8
#define WDPF 1
#define TFOLD 1
#define MIXQ 8
#define MIXV 9
#define TLD2 7
#define XLD 7
#define VK 1
#define VN 2
#define KK 2
#define EREL 0
#define MEET 4
#define OVS 4
#define GV 3
#define TOP 16
#define SK2 5
#define PFK 60 + mblk
#define XK 66 + nslot
#define TSK 2
#define TW0 600
#define TLD 2
#define SK4 2
#define GA 3
#define GB 4

namespace {

constexpr int SEQ = 2048, DM = 1024, DF = 3584, K2 = DM + DF, NQKV = 3 * DM;
constexpr int NGEMM = 128, NCTA = 132;
constexpr int G1_STAGES = 4, G1_STAGE_BYTES = 49152, G1_KSTEPS = 16, G1_TILES = 5;
constexpr int G2_STAGES = 6, G2_STAGE_BYTES = 32768, G2_KSTEPS = 72, G2_LATE = 40, G2_DSTEPS = 56;
constexpr int G2_HEAD = 17;
constexpr int LN_STEP = LNS, FOLD_STEP = FS;
constexpr int A_BYTES = 16384;
constexpr int AUX_OFF = G1_STAGES * G1_STAGE_BYTES;
constexpr int BAR_OFF = AUX_OFF + 32768;
constexpr int PLAN_OFF = BAR_OFF + 384, STAT_OFF = BAR_OFF + 1536;
constexpr int SMEM_BYTES = BAR_OFF + 2816;
constexpr int G1_SKEW = 2, G2_SKEW = SK2;
constexpr int CONSUMER_REGS = 224, AUX_REGS = 56;
constexpr int HALO_BYTES = 4096;
constexpr int SHARE_MIN = SMIN, SHARE_MAX = SMAX, SHARE_SUM = TSUM;

enum { F_LN = 0, F_LN2 = 1, F_FIRST = 2, F_SECOND = 3, F_SHARE = 4, F_EARLY = 5, F_LATE = 6, F_TAIL2 = 7, F_PACE = 8, F_HALO = 9 };
constexpr unsigned CNT_LN = 8, CNT_EARLY = 9, CNT_LATE = 8;

__device__ __align__(1024) __nv_bfloat16 g_xn[SEQ * DM];
__device__ __align__(1024) __nv_bfloat16 g_a2[SEQ * K2];
__device__ __align__(128) uint4 g_tail[2 * NGEMM * 512];
__device__ __align__(128) uint8_t g_halo[(2 * NGEMM + 1) * HALO_BYTES];
__device__ __align__(128) float2 g_stats[SEQ];
__device__ __align__(128) float g_colsum[18 * 1024];
__device__ __align__(128) unsigned g_flags[(F_HALO + 8) * 16 * 32];
__device__ __align__(128) unsigned g_epoch[NCTA * 16];

struct Params {
    const __nv_bfloat16 *px, *pwu;
    __nv_bfloat16 *pxn, *pa2, *pout;
    uint4* tail;
    uint8_t* halo;
    float2* stats;
    float* colsum;
    unsigned *flags, *epoch;
    unsigned long long* trace;
    uint32_t hi[2];
    CUtensorMap x, wg, wu, xn, wqkv, a2, wu_tail, wd_tail, wo, wd, out;
};

extern __shared__ __align__(1024) uint8_t smem_raw[];

#define TRACE(slot) do {} while (0)
#define TRACE_GT(slot) do {} while (0)
#define TRACE_S(slot, v, want) do {} while (0)
#define TRACE_GET(v) do {} while (0)
#define TRACE_PUT(slot, v) do {} while (0)
#define TRACE_SLOT(v, slot) do {} while (0)
#define TRACE_NEXT(v) do {} while (0)
#define TRACE_DUMP() do {} while (0)
#define TRACE_CLEAR() do {} while (0)
#define STAGE_TRACE 0
#define TRACE_END() do {} while (0)
#define TRACE_LITE(i, c) do {} while (0)
#define TRACE_STEP(t, k, i) do {} while (0)

__device__ __forceinline__ uint32_t smem_u32(const void* p) { return (uint32_t)__cvta_generic_to_shared(p); }
__device__ __forceinline__ void mbar_init(uint32_t bar, uint32_t cnt) {
    asm volatile("mbarrier.init.shared::cta.b64 [%0], %1;" :: "r"(bar), "r"(cnt) : "memory");
}
__device__ __forceinline__ void mbar_expect_tx(uint32_t bar, uint32_t bytes) {
    asm volatile("mbarrier.arrive.expect_tx.shared::cta.b64 _, [%0], %1;" :: "r"(bar), "r"(bytes) : "memory");
}
__device__ __forceinline__ void mbar_arrive(uint32_t bar) {
    asm volatile("mbarrier.arrive.shared::cta.b64 _, [%0];" :: "r"(bar) : "memory");
}
__device__ __forceinline__ bool mbar_try_wait(uint32_t bar, uint32_t parity) {
    uint32_t ok;
    asm volatile("{\n.reg .pred p;\nmbarrier.try_wait.parity.shared::cta.b64 p, [%1], %2;\nselp.u32 %0, 1, 0, p;\n}"
                 : "=r"(ok) : "r"(bar), "r"(parity) : "memory");
    return ok;
}
__device__ __forceinline__ void mbar_wait(uint32_t bar, uint32_t parity) {
#pragma unroll 1
    for (int spins = 0; !mbar_try_wait(bar, parity) && spins < (1 << 17); spins++) {}
}
__device__ __forceinline__ void mbar_wait(uint32_t bar, uint32_t parity, int& spins) {
    asm volatile("{\n.reg .pred p;\nagain:\nmbarrier.try_wait.parity.shared::cta.b64 p, [%1], %2;\n@p bra done;\n"
                 "add.s32 %0, %0, -1;\nsetp.gt.s32 p, %0, 0;\n@p bra again;\ndone:\n}" : "+r"(spins) : "r"(bar), "r"(parity) : "memory");
}
template <bool WARP = false> __device__ __forceinline__ unsigned flag_wait(const unsigned* p, unsigned target) {
    unsigned v;
#pragma unroll 1
    for (int spins = 0; spins < (1 << 19); spins++) {
        asm volatile("ld.acquire.gpu.global.u32 %0, [%1];" : "=r"(v) : "l"(p) : "memory");
        if (WARP ? __all_sync(0xffffffffu, (int)(v - target) >= 0) : (int)(v - target) >= 0) break;
        __nanosleep(64);
    }
    return v;
}
__device__ __forceinline__ void mbar_wait_warp(uint32_t bar, uint32_t parity) {
#pragma unroll 1
    for (int spins = 0; !__all_sync(0xffffffffu, mbar_try_wait(bar, parity)) && spins < (1 << 17); spins++) {}
}
__device__ __forceinline__ void flag_add(unsigned* p) {
    asm volatile("red.release.gpu.global.add.u32 [%0], 1;" :: "l"(p) : "memory");
}
__device__ __forceinline__ bool elect_one() {
    uint32_t ok;
    asm volatile("{\n.reg .pred p;\nelect.sync _|p, 0xffffffff;\nselp.u32 %0, 1, 0, p;\n}" : "=r"(ok));
    return ok;
}
__device__ __forceinline__ uint32_t pick(bool c, uint32_t a, uint32_t b) {
    uint32_t r;
    asm("{\n.reg .pred p;\nsetp.ne.b32 p, %3, 0;\nselp.b32 %0, %1, %2, p;\n}" : "=r"(r) : "r"(a), "r"(b), "r"((uint32_t)c));
    return r;
}
__device__ __forceinline__ void fence_proxy_async() { asm volatile("fence.proxy.async.global;" ::: "memory"); }
__device__ __forceinline__ uint4 lds128(uint32_t addr) {
    uint4 v;
    asm volatile("ld.shared.v4.u32 {%0,%1,%2,%3}, [%4];" : "=r"(v.x), "=r"(v.y), "=r"(v.z), "=r"(v.w) : "r"(addr) : "memory");
    return v;
}
__device__ __forceinline__ uint32_t lds32(uint32_t addr) {
    uint32_t v;
    asm volatile("ld.shared.u32 %0, [%1];" : "=r"(v) : "r"(addr) : "memory");
    return v;
}
__device__ __forceinline__ void sts32(uint32_t addr, uint32_t v) { asm volatile("st.shared.u32 [%0], %1;" :: "r"(addr), "r"(v) : "memory"); }
__device__ __forceinline__ uint32_t nanos() { uint32_t t; asm volatile("mov.u32 %0, %%globaltimer_lo;" : "=r"(t)); return t; }
__device__ __forceinline__ float2 lds64f(uint32_t addr) {
    float2 v;
    asm volatile("ld.shared.v2.f32 {%0,%1}, [%2];" : "=f"(v.x), "=f"(v.y) : "r"(addr) : "memory");
    return v;
}
__device__ __forceinline__ void sts128(uint32_t addr, uint4 v) {
    asm volatile("st.shared.v4.u32 [%0], {%1,%2,%3,%4};" :: "r"(addr), "r"(v.x), "r"(v.y), "r"(v.z), "r"(v.w) : "memory");
}
__device__ __forceinline__ void sts64f(uint32_t addr, float a, float b) {
    asm volatile("st.shared.v2.f32 [%0], {%1,%2};" :: "r"(addr), "f"(a), "f"(b) : "memory");
}

__device__ __forceinline__ uint64_t stream_policy() { return 0x12F0000000000000ull; }
__device__ __forceinline__ void tma_3d(uint32_t dst, const CUtensorMap* m, uint32_t bar, int c0, int c1, int c2, uint64_t pol) {
    asm volatile("cp.async.bulk.tensor.3d.shared::cluster.global.mbarrier::complete_tx::bytes.L2::cache_hint"
                 " [%0], [%1, {%3, %4, %5}], [%2], %6;"
                 :: "r"(dst), "l"(m), "r"(bar), "r"(c0), "r"(c1), "r"(c2), "l"(pol) : "memory");
}
__device__ __forceinline__ void load_stage1(uint32_t dst, uint32_t dst_b, uint32_t bar, const CUtensorMap* ma, const CUtensorMap* mb0,
                                            const CUtensorMap* mb1, int k, int row, int col0, int col1, int keep_a, uint64_t pol) {
    asm volatile("{\n.reg .pred e, p, q;\nelect.sync _|e, 0xffffffff;\nsetp.ne.and.b32 p|q, %8, 0, e;\n"
        "@p cp.async.bulk.tensor.3d.shared::cluster.global.mbarrier::complete_tx::bytes [%0], [%3, {%5, %6, %10}], [%2];\n"
        "@q cp.async.bulk.tensor.3d.shared::cluster.global.mbarrier::complete_tx::bytes.L2::cache_hint [%0], [%3, {%5, %6, %10}], [%2], %9;\n"
        "@e cp.async.bulk.tensor.2d.shared::cluster.global.mbarrier::complete_tx::bytes.multicast::cluster.L2::cache_hint"
        " [%1], [%4, {%7, %5}], [%2], %11, %9;\n"
        "@e cp.async.bulk.tensor.2d.shared::cluster.global.mbarrier::complete_tx::bytes.multicast::cluster.L2::cache_hint"
        " [%1 + 8192], [%13, {%14, %5}], [%2], %11, %9;\n"
        "@e mbarrier.arrive.expect_tx.shared::cta.b64 _, [%2], %12;\n}"
        :: "r"(dst), "r"(dst_b), "r"(bar), "l"(ma), "l"(mb0), "r"(k), "r"(row), "r"(col0), "r"(keep_a), "l"(pol), "r"(0),
           "h"((uint16_t)3), "n"(G1_STAGE_BYTES), "l"(mb1), "r"(col1) : "memory");
}
__device__ __forceinline__ void load_stage2(uint32_t dst, uint32_t dst_b, uint32_t bar, const CUtensorMap* ma, const CUtensorMap* mb,
                                            int ka, int row, int col, int kb2, int kb4, uint64_t pol) {
    asm volatile("{\n.reg .pred e;\nelect.sync _|e, 0xffffffff;\n"
        "@e cp.async.bulk.tensor.3d.shared::cluster.global.mbarrier::complete_tx::bytes.L2::cache_hint [%0], [%3, {%5, %6, %10}], [%2], %9;\n"
        "@e cp.async.bulk.tensor.5d.shared::cluster.global.mbarrier::complete_tx::bytes.multicast::cluster.L2::cache_hint"
        " [%1], [%4, {%7, %10, %13, %10, %8}], [%2], %11, %9;\n"
        "@e mbarrier.arrive.expect_tx.shared::cta.b64 _, [%2], %12;\n}"
        :: "r"(dst), "r"(dst_b), "r"(bar), "l"(ma), "l"(mb), "r"(ka), "r"(row), "r"(col), "r"(kb4), "l"(pol), "r"(0),
           "h"((uint16_t)3), "n"(G2_STAGE_BYTES), "r"(kb2) : "memory");
}
__device__ __forceinline__ void load_tail(uint32_t dst, uint32_t bar, const CUtensorMap* ma, const CUtensorMap* mb, int ka, int mblk,
                                          int kb) {
    asm volatile("{\n.reg .pred e;\nelect.sync _|e, 0xffffffff;\n"
        "@e cp.async.bulk.tensor.3d.shared::cluster.global.mbarrier::complete_tx::bytes [%0], [%2, {%3, %4, %5}], [%1];\n"
        "@e cp.async.bulk.tensor.5d.shared::cluster.global.mbarrier::complete_tx::bytes.multicast::cluster"
        " [%9], [%6, {%5, %5, %7, %5, %10}], [%1], %11;\n"
        "@e mbarrier.arrive.expect_tx.shared::cta.b64 _, [%1], %8;\n}"
        :: "r"(dst), "r"(bar), "l"(ma), "r"(ka), "r"(mblk * 64), "r"(0), "l"(mb), "r"(kb), "n"(G1_STAGE_BYTES),
           "r"(dst + A_BYTES + (mblk & 1) * 16384), "r"((mblk & 1) * 4), "h"((uint16_t)3) : "memory");
}
__device__ __forceinline__ uint4 ldg_stream(const void* p, uint64_t pol) {
    uint4 v;
    asm volatile("ld.global.nc.L1::no_allocate.L2::cache_hint.v4.u32 {%0,%1,%2,%3}, [%4], %5;"
                 : "=r"(v.x), "=r"(v.y), "=r"(v.z), "=r"(v.w) : "l"(p), "l"(pol));
    return v;
}
__device__ __forceinline__ void st_tagged(void* p, float a, float b, uint32_t tag) {
    asm volatile("st.relaxed.gpu.global.v2.b32 [%0], {%1,%2};"
                 :: "l"(p), "r"((__float_as_uint(a) & ~3u) | tag), "r"((__float_as_uint(b) & ~3u) | tag) : "memory");
}
__device__ __forceinline__ void st_relaxed(unsigned* p, uint32_t v) {
    asm volatile("st.relaxed.gpu.global.b32 [%0], %1;" :: "l"(p), "r"(v) : "memory");
}
__device__ __forceinline__ bool untagged(const uint4& v, uint32_t tag) {
    return ((v.x ^ tag) | (v.y ^ tag) | (v.z ^ tag) | (v.w ^ tag)) & 3;
}
__device__ __forceinline__ uint4 ld_relaxed(const void* p) {
    uint4 v;
    asm volatile("ld.relaxed.gpu.global.v4.b32 {%0,%1,%2,%3}, [%4];" : "=r"(v.x), "=r"(v.y), "=r"(v.z), "=r"(v.w) : "l"(p) : "memory");
    return v;
}
__device__ __forceinline__ void prefetch_map(const CUtensorMap* m) {
    asm volatile("prefetch.tensormap [%0];" :: "l"(m) : "memory");
}
template <int N> __device__ __forceinline__ void wg_wait() { asm volatile("wgmma.wait_group.sync.aligned %0;" :: "n"(N) : "memory"); }

__device__ __forceinline__ uint32_t desc_a(uint32_t addr) { return (addr & 0x3FFFF) >> 4 | 1 << 16; }
__device__ __forceinline__ uint32_t desc_b(uint32_t addr) { return (addr & 0x3FFFF) >> 4 | 512 << 16; }

#define R8(d, o) "+f"(d[o]), "+f"(d[o+1]), "+f"(d[o+2]), "+f"(d[o+3]), "+f"(d[o+4]), "+f"(d[o+5]), "+f"(d[o+6]), "+f"(d[o+7])
#define R32(d, o) R8(d, o), R8(d, o+8), R8(d, o+16), R8(d, o+24)
#define R64(d, o) R32(d, o), R32(d, o+32)
#define ACC00 "%0,%1,%2,%3,%4,%5,%6,%7,%8,%9,%10,%11,%12,%13,%14,%15,%16,%17,%18,%19,%20,%21,%22,%23,%24,%25,%26,%27,%28,%29,%30,%31,"\
    "%32,%33,%34,%35,%36,%37,%38,%39,%40,%41,%42,%43,%44,%45,%46,%47"
#define ACC0 ACC00 ",%48,%49,%50,%51,%52,%53,%54,%55,%56,%57,%58,%59,%60,%61,%62,%63"
#define ACC1 "%64,%65,%66,%67,%68,%69,%70,%71,%72,%73,%74,%75,%76,%77,%78,%79,%80,%81,%82,%83,%84,%85,%86,%87,%88,%89,%90,%91,%92,%93,%94,%95,"\
    "%96,%97,%98,%99,%100,%101,%102,%103,%104,%105,%106,%107,%108,%109,%110,%111"
#define ACC48 "{" ACC00 "}"
#define ACC64 "{" ACC0 "}"
#define ACC112 "{" ACC0 "," ACC1 "}"
#define ACC128 "{" ACC0 "," ACC1 ",%112,%113,%114,%115,%116,%117,%118,%119,%120,%121,%122,%123,%124,%125,%126,%127}"
#define MMA_K16(shape, acc, a, b, keep, hb) \
    "mov.b64 da, {" a ", 0x40000040};\nmov.b64 db, {" b ", " hb "};\n" \
    "wgmma.mma_async.sync.aligned." shape ".f32.bf16.bf16 " acc ", da, db, " keep ", 1, 1, 0, 1;\n"
#define MMA_NEXT(op, a, b, sa, sb) op " " a ", " a ", " sa ";\n" op " " b ", " b ", " sb ";\n"
#define MMA_STEP_B(shape, acc, a, b, na, nb, keep, hb, sb) \
    "{\n.reg .pred p, q;\n.reg .b64 da, db;\nsetp.ne.b32 p, " keep ", 0;\nsetp.eq.b32 q, 0, 0;\nwgmma.fence.sync.aligned;\n" \
    MMA_K16(shape, acc, a, b, "p", hb) MMA_NEXT("xor.b32", a, b, "2", "128") MMA_K16(shape, acc, a, b, "q", hb) MMA_NEXT("add.s32", a, b, "2", sb) \
    MMA_K16(shape, acc, a, b, "q", hb) MMA_NEXT("xor.b32", a, b, "2", "128") MMA_K16(shape, acc, a, b, "q", hb) MMA_NEXT("add.s32", a, b, na, nb) \
    "wgmma.commit_group.sync.aligned;\n}"
#define MMA64(shape, acc, a, b, keep) "wgmma.mma_async.sync.aligned." shape ".f32.bf16.bf16 " acc ", " a ", " b ", " keep ", 1, 1, 0, 1;\n"
#define NEXT64(op, a, b, sa, sb) "mov.b64 {lo, hi}, " a ";\n" op " lo, lo, " sa ";\nmov.b64 " a ", {lo, hi};\n" \
    "mov.b64 {lo, hi}, " b ";\n" op " lo, lo, " sb ";\nmov.b64 " b ", {lo, hi};\n"
#define MMA_STEP(shape, acc, a, b, na, nb, keep) \
    "{\n.reg .pred p, q;\n.reg .b32 lo, hi;\nsetp.ne.b32 p, " keep ", 0;\nsetp.eq.b32 q, 0, 0;\nwgmma.fence.sync.aligned;\n" \
    MMA64(shape, acc, a, b, "p") NEXT64("xor.b32", a, b, "2", "128") MMA64(shape, acc, a, b, "q") NEXT64("add.s32", a, b, "2", "128") \
    MMA64(shape, acc, a, b, "q") NEXT64("xor.b32", a, b, "2", "128") MMA64(shape, acc, a, b, "q") NEXT64("add.s32", a, b, na, nb) \
    "wgmma.commit_group.sync.aligned;\n}"
#define MMA_ARGS64 "+l"(da), "+l"(db) : "r"(next / 16 - 6), "r"(next / 16 - 384), "r"(keep) : "memory"
#define MMA_ARGS "+r"(da), "+r"(db) : "r"(next / 16 - 6), "r"(next / 16 - 384), "r"(keep) : "memory"

__device__ __forceinline__ void mma_step(float (&d)[128], uint64_t& da, uint64_t& db, int next, int keep) {
    asm volatile(MMA_STEP("m64n256k16", ACC128, "%128", "%129", "%130", "%131", "%132") : R64(d, 0), R64(d, 64), MMA_ARGS64);
}
__device__ __forceinline__ void mma_rank(float (&d)[128], uint32_t a0, uint32_t a1, uint32_t db) {
    asm volatile("{\n.reg .pred q;\n.reg .b64 db;\nsetp.eq.b32 q, 0, 0;\nmov.b64 db, {%131, 0x40000040};\nwgmma.fence.sync.aligned;\n"
                 "wgmma.mma_async.sync.aligned.m64n256k16.f32.bf16.bf16 " ACC128 ", {%128, %129, %130, %130}, db, q, 1, 1, 1;\n}"
                 : R64(d, 0), R64(d, 64) : "r"(a0), "r"(a1), "r"(0), "r"(db) : "memory");
}
__device__ __forceinline__ void mma_step224(float (&d)[128], uint64_t& da, uint64_t& db, int next, int keep) {
    asm volatile(MMA_STEP("m64n224k16", ACC112, "%112", "%113", "%114", "%115", "%116")
                 : R64(d, 0), R32(d, 64), R8(d, 96), R8(d, 104), MMA_ARGS64);
}
__device__ __forceinline__ void mma_step(float (&d)[64], uint64_t& da, uint64_t& db, int next, int keep) {
    asm volatile(MMA_STEP("m64n128k16", ACC64, "%64", "%65", "%66", "%67", "%68") : R64(d, 0), MMA_ARGS64);
}
__device__ __forceinline__ void mma_step96(float (&d)[64], uint64_t& da, uint64_t& db, int next, int keep) {
    asm volatile(MMA_STEP("m64n96k16", ACC48, "%48", "%49", "%50", "%51", "%52") : R32(d, 0), R8(d, 32), R8(d, 40), MMA_ARGS64);
}
__device__ __forceinline__ void mma_step_tail(float (&d)[128], uint32_t da, uint32_t b, int keep) {
    uint32_t db = (b & 0x3FFFF) >> 4 | 256 << 16;
    const int next = 0;
    asm volatile(MMA_STEP_B("m64n256k16", ACC128, "%128", "%129", "%130", "%131", "%132", "0x80000040", "-96")
                 : R64(d, 0), R64(d, 64), MMA_ARGS);
}

__device__ __forceinline__ uint32_t pack_bf16(float lo, float hi) {
    uint32_t r; asm("cvt.rn.bf16x2.f32 %0, %1, %2;" : "=r"(r) : "f"(hi), "f"(lo)); return r;
}
__device__ __forceinline__ float bf_lo(uint32_t v) { return __uint_as_float(v << 16); }
__device__ __forceinline__ float bf_hi(uint32_t v) { return __uint_as_float(v & 0xffff0000u); }
__device__ __forceinline__ float round_bf16(float v) { return bf_lo(pack_bf16(v, 0.f)); }
__device__ __forceinline__ uint32_t mul_bf16x2(uint32_t a, uint32_t b) {
    uint32_t r; asm("mul.rn.bf16x2 %0, %1, %2;" : "=r"(r) : "r"(a), "r"(b)); return r;
}
__device__ __forceinline__ uint32_t sub_bf16x2(uint32_t a, uint32_t b) {
    uint32_t r; asm("sub.rn.bf16x2 %0, %1, %2;" : "=r"(r) : "r"(a), "r"(b)); return r;
}
__device__ __forceinline__ uint32_t mul2_bf16x2(uint32_t a, uint32_t hi, uint32_t lo) {
    uint32_t r; asm("fma.rn.bf16x2 %0, %1, %2, %3;" : "=r"(r) : "r"(a), "r"(hi), "r"(mul_bf16x2(a, lo))); return r;
}
__device__ __forceinline__ float tanh_fast(float x) { float r; asm("tanh.approx.f32 %0, %1;" : "=f"(r) : "f"(x)); return r; }
__device__ __forceinline__ float gelu_twice(float g) {
    return fmaf(g, tanh_fast(fmaf(g * g, 0.044715f * 0.7978845608f, 0.7978845608f) * g), g);
}
__device__ __forceinline__ uint32_t geglu2(uint32_t g2, uint32_t u2) {
    return mul_bf16x2(pack_bf16(gelu_twice(bf_lo(g2)), gelu_twice(bf_hi(g2))), u2);
}
__device__ __forceinline__ uint32_t silu2(float lo, float hi) {
    const uint32_t h = mul_bf16x2(pack_bf16(lo, hi), 0x3e803e80u);
    return pack_bf16(fmaf(bf_lo(h), tanh_fast(bf_lo(h)), bf_lo(h)), fmaf(bf_hi(h), tanh_fast(bf_hi(h)), bf_hi(h)));
}
__device__ __forceinline__ float ex2_fast(float x) { float r; asm("ex2.approx.ftz.f32 %0, %1;" : "=f"(r) : "f"(x)); return r; }
__device__ __forceinline__ void unpack8(uint4 v, float (&f)[8]) {
    f[0] = bf_lo(v.x); f[1] = bf_hi(v.x); f[2] = bf_lo(v.y); f[3] = bf_hi(v.y);
    f[4] = bf_lo(v.z); f[5] = bf_hi(v.z); f[6] = bf_lo(v.w); f[7] = bf_hi(v.w);
}
template <int N> __device__ __forceinline__ void fence_regs(float (&d)[N]) {
#pragma unroll
    for (int i = 0; i < N; i++) asm volatile("" : "+f"(d[i]) :: "memory");
}

__device__ __forceinline__ float rcp_fast(float x) { float r; asm("rcp.approx.ftz.f32 %0, %1;" : "=f"(r) : "f"(x)); return r; }
__device__ __forceinline__ float sqrt_fast(float x) { float r; asm("sqrt.approx.ftz.f32 %0, %1;" : "=f"(r) : "f"(x)); return r; }
__device__ __forceinline__ uint32_t max_bf16x2(uint32_t a, uint32_t b) {
    uint32_t r; asm("max.bf16x2 %0, %1, %2;" : "=r"(r) : "r"(a), "r"(b)); return r;
}
__device__ __forceinline__ uint32_t transpose8(uint32_t a) {
    uint32_t r; asm volatile("movmatrix.sync.aligned.m8n8.trans.b16 %0, %1;" : "=r"(r) : "r"(a)); return r;
}
__device__ __forceinline__ void mma_sync(uint32_t* d, const uint32_t* a, uint32_t b0, uint32_t b1, const uint32_t* c) {
    asm volatile("mma.sync.aligned.m16n8k16.row.col.f32.bf16.bf16.f32 {%0,%1,%2,%3}, {%4,%5,%6,%7}, {%8,%9}, {%10,%11,%12,%13};"
        : "=r"(d[0]), "=r"(d[1]), "=r"(d[2]), "=r"(d[3])
        : "r"(a[0]), "r"(a[1]), "r"(a[2]), "r"(a[3]), "r"(b0), "r"(b1), "r"(c[0]), "r"(c[1]), "r"(c[2]), "r"(c[3]));
}
template <int N> struct Floats {
    float f[N];
    __device__ __forceinline__ Floats() {}
    __device__ __forceinline__ Floats(const uint32_t* p) {
#pragma unroll
        for (int i = 0; i < N; i++) asm("mov.b32 %0, %1;" : "=f"(f[i]) : "r"(p[i]));
    }
    __device__ __forceinline__ void put(uint32_t* p) const {
#pragma unroll
        for (int i = 0; i < N; i++) asm("mov.b32 %0, %1;" : "=r"(p[i]) : "f"(f[i]));
    }
    __device__ __forceinline__ float& operator[](int i) { return f[i]; }
};
__device__ __forceinline__ uint32_t fresh_tid() { uint32_t r; asm volatile("mov.u32 %0, %%tid.x;" : "=r"(r)); return r; }
template <typename T> __device__ __forceinline__ T uniform(T v) { return __shfl_sync(0xffffffffu, v, 0); }

__device__ __forceinline__ uint32_t forecast(uint32_t n0, uint32_t c0, float cycles, uint32_t tag) {
    const uint32_t n = nanos();
    return n + (int)((n - n0) * cycles * rcp_fast((uint32_t)clock() - c0)) & ~3u | tag;
}
__device__ __forceinline__ uint32_t plan_word(uint32_t base, int lane) { return uniform(lds32(base + PLAN_OFF + lane * 4)); }

__device__ __forceinline__ void fold_operands(const Params& prm, uint32_t base, int slot, int mblk, uint32_t tag, int w, int lane) {
    uint4 v[9];
#pragma unroll
    for (int m = 0; m < 9; m++) v[m] = make_uint4(0, 0, 0, 0);
    const float* parts = prm.colsum + (slot * 2 + (lane >> 4)) * 1024 + w * 64 + (lane & 15) * 4;
    const float* const rows = &prm.stats[mblk * 128 + w * 64 + lane * 2].x;
#pragma unroll 1
    for (int spins = 0; spins < (1 << 16); spins++) {
        bool missing = false;
        asm volatile("" : "+l"(parts));
#pragma unroll
        for (int m = 0; m < 9; m++) {
            if (untagged(v[m], tag)) {
                missing = true;
                v[m] = ld_relaxed(m < 8 ? parts + m * 128 : rows);
            }
        }
        if (!missing) break;
    }
    float4 c = make_float4(0.f, 0.f, 0.f, 0.f);
#pragma unroll
    for (int m = 0; m < 8; m++) {
        c.x += __uint_as_float(v[m].x ^ tag); c.y += __uint_as_float(v[m].y ^ tag);
        c.z += __uint_as_float(v[m].z ^ tag); c.w += __uint_as_float(v[m].w ^ tag);
    }
    sts128(base + STAT_OFF + w * 512 + lane * 16, make_uint4(v[8].x ^ tag, v[8].y ^ tag, v[8].z ^ tag, v[8].w ^ tag));
    const uint32_t ca = base + AUX_OFF + w * 8192 + (lane >> 4) * 16384 + (lane & 15) * 8;
#pragma unroll
    for (int r = 0; r < 3; r++) {
        const uint32_t lo = pack_bf16(c.x, c.y), hi = pack_bf16(c.z, c.w);
        sts64f((ca ^ r * 16) + r * 128, __uint_as_float(lo), __uint_as_float(hi));
        c.x -= bf_lo(lo); c.y -= bf_hi(lo); c.z -= bf_lo(hi); c.w -= bf_hi(hi);
    }
    asm volatile("fence.proxy.async.shared::cta;" ::: "memory");
    __syncwarp();
}
__device__ __forceinline__ float2 fold(float (&acc)[128], uint32_t base, int wg) {
    const uint32_t id = fresh_tid(), sp = base + STAT_OFF + (id & 96) * 8 + (id & 28) * 4 + wg * 8;
    const uint32_t sel = id & 2 ? 0x4444 : (id & 1 ? 0x4432 : 0x3232);
    const float2 sa = lds64f(sp), sb = lds64f(sp + 128);
    mma_rank(acc, __byte_perm(__float_as_uint(sa.x), 0, sel), __byte_perm(__float_as_uint(sb.x), 0, sel), desc_b(base + AUX_OFF));
    return make_float2(sa.y, sb.y);
}

__device__ __forceinline__ void tail_gemm(const Params& prm, uint32_t base, uint32_t t0, unsigned epoch, int grp, int warp, int lane) {
    const uint32_t full = base + BAR_OFF, empty = full + 32, sig = full + 192, dep = full + 256, folded = full + 320;
    const uint32_t tag = 1 + (epoch & 1);
    auto plan = [&](uint32_t p, uint32_t word) { return p < 4 ? p * 64 + grp / 2 * 32 + 15 : word >> p % 4 * 8 & 255; };
    auto rows = [&](uint32_t job) { return job / 32 * 2 + grp % 2; };
    if (warp == 8) {
        if (elect_one()) { prefetch_map(&prm.xn); prefetch_map(&prm.a2); prefetch_map(&prm.wd_tail); }
#pragma unroll 1
        for (int p = 0, i = G1_STAGES; p < 8; p++) {
            const bool first = p < 4;
            if (p == 4) mbar_wait_warp(dep + 16, 0);
            const uint32_t job = plan(p, plan_word(base, lane));
#pragma unroll 1
            for (int k = p ? 0 : G1_STAGES; k <= job % 32; k++, i++) {
                if (WDPF && p == 3 && k % 2 == grp / 2)
                    asm volatile("{\n.reg .pred e;\nelect.sync _|e, 0xffffffff;\n"
                        "@e cp.async.bulk.prefetch.tensor.5d.L2.global [%0, {%2, %2, %1, %2, %3}];\n}"
                        :: "l"(&prm.wd_tail), "r"(k * 8), "r"(0), "r"(grp % 2 * 4) : "memory");
                if (i == 16 || i == 24 || k == 16) mbar_wait_warp(dep + (first ? i & 8 : 24), 0);
                TRACE_S(62, i, 16); TRACE_S(63, i, 4);
                mbar_wait_warp(empty + (i & 3) * 8, ~i >> 2 & 1);
                load_tail(base + (i & 3) * G1_STAGE_BYTES, full + (i & 3) * 8, first ? (p ? &prm.xn : &prm.x) : &prm.a2,
                          first ? &prm.wu_tail : &prm.wd_tail, (first ? 0 : DM) + k * 64, rows(job), first ? k * 2 : k * 8);
            }
        }
        return;
    }
    if (warp == 9) {
        const uint32_t n0 = nanos(), c0 = clock();
#pragma unroll 1
        for (int j = 0; j < 3; j++) {
            flag_wait<true>(prm.flags + (F_LN + j) * 512 + (j < 2 ? lane % 4 * 4 + grp : lane % 16) * 32, epoch * CNT_LN);
            fence_proxy_async();
            __syncwarp();
            if (lane == 0 && j < 2) mbar_arrive(dep + j * 8);
        }
        mbar_wait_warp(sig + 8, 0);
        if (lane == 0) st_relaxed(prm.flags + F_PACE * 512 + 64 + grp, forecast(n0, c0, DUE, tag));
        uint4 v, w;
#pragma unroll 1
        for (int spins = 0; spins < (1 << 19); spins++) {
            v = ld_relaxed(prm.flags + F_PACE * 512 + lane / 2 * 4);
            w = ld_relaxed(prm.flags + F_PACE * 512 + 64);
            if (!__any_sync(0xffffffffu, untagged(v, tag) || untagged(w, tag))) break;
            __nanosleep(256);
        }
        const uint32_t ref = uniform(v.x);
        const int due = min(max((int)((grp & 2 ? w.z : w.x) - ref), -100000), 100000) * 8;
        int late = max(max((int)(v.x - ref), (int)(v.y - ref)), max((int)(v.z - ref), (int)(v.w - ref)));
        late = min(max(max(late, __shfl_xor_sync(0xffffffffu, late, 2)), -100000), 100000) * 8 * BAL + lane / 4 + lane / 24 * BIAS * 8;
        TRACE_PUT(16 + lane / 4, late + (1 << 20));
        int place = 0, n = SHARE_MIN;
#pragma unroll 1
        for (int g = 0; g < 32; g += 4) place += __shfl_sync(0xffffffffu, late, g) > late;
        const bool swap = SWAP && (__reduce_add_sync(0xffffffffu, place + 1 & 2 ? late : -late) ^ w.x - w.z) >> 31;
        const bool mine = (place + 1 >> 1 & 1 ^ swap) == grp / 2;
#pragma unroll 1
        for (int j = 4 * SHARE_MIN; j < SHARE_SUM; j++) {
            const int most = __reduce_max_sync(0xffffffffu, mine && n < SHARE_MAX ? late : INT_MIN);
            if (j >= TLO && due + (j - 38) * 640 * 8 > most) break;
            if (j == 38) TRACE_PUT(32, most - due + (1 << 20));
            if (most == late) { n++; late -= STEPNS * 8; }
        }
        auto first = [](uint32_t bits, int n) { return bits & (1u << min(max(n, 0), 24)) - 1; };
        const uint32_t job = lane / 4 * 32 + n - 1;
        if (mine) st_relaxed(prm.flags + F_SHARE * 512 + rows(job) * 32,
                             epoch << 24 | first(0x2aaaaa, 2 * n) | first(0x104104, 6 * n - 66) | first(0x10410, 6 * n - 90) |
                             first(0x41041, 6 * n - 108));
        if (mine) TRACE_PUT(24 + lane / 4, n);
        sts32(base + PLAN_OFF, __reduce_or_sync(0xffffffffu, mine ? job << place / 2 * 8 : 0));
        if (lane == 0) mbar_arrive(dep + 16);
        flag_wait<true>(prm.flags + F_SECOND * 512 + lane % 16 * 32, epoch * CNT_LN);
        fence_proxy_async();
        __syncwarp();
        if (lane == 0) mbar_arrive(dep + 24);
        return;
    }
    if (warp > 9) {
#pragma unroll 1
        for (int j = 0; j < 8; j++) sts128(base + AUX_OFF + (warp - 10) * 8192 + (j & 4) * 4096 + (j & 3) * 512 + lane * 16, make_uint4(0, 0, 0, 0));
        while ((uint32_t)clock() - t0 < 9000) __nanosleep(256);
        fold_operands(prm, base, 8, grp, tag, warp - 10, lane);
        if (lane) return;
        mbar_arrive(folded);
        if (warp == 11) return;
        TRACE(60);
#pragma unroll 1
        for (int p = 0; p < 8; p++) {
            mbar_wait(sig + p * 8, 0);
            flag_add(prm.flags + (p < 4 ? F_EARLY : F_TAIL2) * 512 + rows(plan(p, lds32(base + PLAN_OFF))) * 32);
            TRACE_S(50, p, 3); TRACE_S(51, p, 7);
        }
        prm.epoch[blockIdx.x * 16] = epoch;
        TRACE_DUMP();
        return;
    }
    asm volatile("setmaxnreg.inc.sync.aligned.u32 %0;" :: "n"(CONSUMER_REGS) : "memory");
    const uint32_t da = desc_a(base + (warp >> 2) * 8192);
    uint4* out = prm.tail;
    float acc[128];
    uint32_t pk[64];
    float2 inv = make_float2(0.f, 0.f);
    int i = 0, last;
    uint32_t peer;
    asm volatile("mapa.shared::cluster.u32 %0, %1, %2;" : "=r"(peer) : "r"(empty), "r"(lane & 1));
    auto release = [&]() {
        if ((threadIdx.x & 126) == 0 && i <= last)
            asm volatile("mbarrier.arrive.shared::cluster.b64 _, [%0];" :: "r"(peer + (i - 1 & 3) * 8) : "memory");
    };
    auto store = [&](int j) {
        asm volatile("st.global.v4.u32 [%0], {%1,%2,%3,%4};" :: "l"(out + j / 2 * 8192 + j % 2 * 256),
                     "r"(pk[4 * j]), "r"(pk[4 * j + 1]), "r"(pk[4 * j + 2]), "r"(pk[4 * j + 3]) : "memory");
    };
    auto step = [&](int k, int left, int most) {
        mbar_wait(full + (i & 3) * 8, i >> 2 & 1);
        TRACE_S(45, warp * 128 + i, 0);
        if (warp >= 4 && left == (SMIN < 3 ? min(TSK, most) : TSK)) asm volatile("bar.sync 1, 256;" ::: "memory");
        mma_step_tail(acc, da + (i & 3) * (G1_STAGE_BYTES / 16), base + A_BYTES + (i & 3) * G1_STAGE_BYTES, k);
        if (warp < 4 && left == 1) asm volatile("bar.arrive 1, 256;" ::: "memory");
    };
    auto drip = [&](int p, int& n) {
        if (n > 0) { store(0); store(1); }
#pragma unroll
        for (int j = 8; j < 64; j++) asm volatile("mov.b32 %0, %1;" : "=r"(pk[j - 8]) : "r"(pk[j]));
        out += 8192;
        __syncwarp();
        if (--n == 0 && lane == 0) mbar_arrive(sig + p * 8 - 8);
    };
#pragma unroll
    for (int j = 0; j < 128; j++) asm volatile("mov.b32 %0, 0;" : "=f"(acc[j]));
#pragma unroll
    for (int j = 0; j < 64; j++) asm volatile("mov.b32 %0, 0;" : "=r"(pk[j]));
#pragma unroll 1
    for (int p = 0; p < 8; p++) {
        step(0, 0, 1);
        i++;
        const uint32_t word = plan_word(base, lane), job = plan(p, word);
        last = __dp4a(word & 0x1f1f1f1fu, 0x01010101u, 4u * G1_KSTEPS);
#pragma unroll 1
        for (int left = job % 32, n = p ? 8 : 0; left > 0; left--) {
            if (i == G1_KSTEPS - TFOLD) { mbar_wait(folded, 0); inv = fold(acc, base, warp >> 2); }
#pragma unroll 1
            do drip(p, n); while (n & 7 >> 31 - __clz(job % 32));
            step(1, left, job % 32);
            wg_wait<1>();
            release();
            i++;
        }
        wg_wait<0>();
        fence_regs(acc);
        release();
        if (p == 0) {
#pragma unroll
            for (int j = 0; j < 128; j++) acc[j] *= j & 2 ? inv.y : inv.x;
            fence_regs(acc);
        }
        if (warp == 4) TRACE_PUT(46 + p + p / 4 * 3, (uint32_t)clock());
#pragma unroll
        for (int j = 0; j < 64; j++) pk[j] = pack_bf16(acc[2 * j], acc[2 * j + 1]);
        out = prm.tail + p / 4 * NGEMM * 512 + rows(job) * 512 + threadIdx.x;
    }
#pragma unroll
    for (int j = 0; j < 16; j++) store(j);
    __syncwarp();
    TRACE_S(58, warp, 4);
    if (lane == 0) mbar_arrive(sig + 56);
}

__device__ __forceinline__ int gate_col(int t, int nslot) { return t == 2 ? 960 + nslot * 64 : max(t * 1024 - 1536, 0) + nslot * 128; }

struct Role {
    int rank, role, mblk, nslot;
    __device__ __forceinline__ Role() {
        uint32_t id;
        asm volatile("mov.u32 %0, %%ctaid.x;" : "=r"(id));
        const uint32_t cl = id / 2;
        rank = id & 1;
        role = pick(cl < 4, 32 + cl * 8, cl - 8 + max(4u, (cl - 1) * 37 >> 8)) * 2 + rank;
        mblk = role & 15; nslot = role >> 4;
    }
};

__global__ void __cluster_dims__(2, 1, 1) __launch_bounds__(384, 1)
fused_kernel(const __grid_constant__ Params prm) {
    TRACE_GET(c0);
    const uint32_t base = smem_u32(smem_raw) & ~1023u;
    const uint32_t bars = base + BAR_OFF;
    auto full1 = [&](int s) { return bars + s * 8; };
    auto empty1 = [&](int s) { return bars + 32 + s * 8; };
    auto full2 = [&](int s) { return bars + 64 + s * 8; };
    auto empty2 = [&](int s) { return bars + 128 + s * 8; };
    const uint32_t sig_bar = bars + 192, dep_bar = bars + 256, cs_bar = bars + 304, fold_bar = bars + 320, x_bar = bars + 352;
    const uint32_t halo_bar = dep_bar + 32;
    auto stage2 = [&](int q) { return base + q * G2_STAGE_BYTES; };
    const uint32_t aux = base + AUX_OFF;

    asm volatile("{\n.reg .pred p;\nsetp.eq.u32 p, %1, 0;\n@p mbarrier.init.shared::cta.b64 [%0], 1;\n"
        "fence.mbarrier_init.release.cluster;\nbarrier.cluster.arrive.relaxed.aligned;\n}" :: "r"(bars), "r"(threadIdx.x) : "memory");
    const int warp = __shfl_sync(0xffffffffu, threadIdx.x >> 5, 0);
    auto cluster_wait = []() { asm volatile("barrier.cluster.wait.acquire.aligned;" ::: "memory"); };
    if ((warp | (blockIdx.x & NGEMM)) == 8) {
        const Role r;
        asm volatile("{\n.reg .pred e;\nelect.sync _|e, 0xffffffff;\n"
            "@e prefetch.tensormap [%0];\n@e prefetch.tensormap [%1];\n}" :: "l"(&prm.x), "l"(&prm.wg + r.rank) : "memory");
        cluster_wait();
        load_stage1(base, base + A_BYTES + r.rank * 16384, full1(0), &prm.x, &prm.wg + r.rank, &prm.wg + r.rank, 0, r.mblk * 64,
                    r.nslot * 128, r.nslot * 128 + 64, 0, stream_policy());
    } else {
        cluster_wait();
    }
    const uint32_t t0 = clock();
    if (TEARLY) {
        uint32_t cta;
        asm volatile("mov.u32 %0, %%ctaid.x;" : "=r"(cta));
        if ((warp | (~cta & NGEMM)) == TEW) load_tail(base, full1(0), &prm.x, &prm.wu_tail, 0, cta - NGEMM, 0);
    }
    asm volatile("{\n.reg .pred e, q;\nelect.sync _|e, 0xffffffff;\nsetp.ne.and.u32 q, %2, 0, e;\n"
        "@q mbarrier.init.shared::cta.b64 [%0], %1;\n@e mbarrier.init.shared::cta.b64 [%0 + 8], %1;\n"
        "@e mbarrier.init.shared::cta.b64 [%0 + 16], %1;\n@e mbarrier.init.shared::cta.b64 [%0 + 24], %1;\n"
        "fence.mbarrier_init.release.cluster;\nbarrier.cluster.arrive.relaxed.aligned;\n}"
        :: "r"(bars + warp * 32), "r"(1 << (0x10fa08 >> warp * 2 & 3)), "r"(warp) : "memory");
    const int lane = threadIdx.x & 31;
    const Role me;
    const int rank = me.rank, role = me.role, mblk = me.mblk, nslot = me.nslot;
    const CUtensorMap* const w0 = &prm.wg + rank;

    unsigned* const flags = prm.flags + mblk * 32;
    if (warp >= 8) {
        asm volatile("setmaxnreg.dec.sync.aligned.u32 %0;" :: "n"(AUX_REGS));
        if (warp == 9) { TRACE_CLEAR(); TRACE_GT(0); TRACE_PUT(1, c0); }
        if ((warp | (~blockIdx.x & NGEMM)) == 8) {
#pragma unroll 1
            for (int i = TEARLY; i < G1_STAGES; i++) {
                if (i == 1) cluster_wait();
                TRACE_S(57, i, 1);
                load_tail(base + i * G1_STAGE_BYTES, full1(i), &prm.x, &prm.wu_tail, i * 64, blockIdx.x - NGEMM, i * 2);
            }
        } else {
            cluster_wait();
        }
    }

    if (blockIdx.x >= NGEMM) {
        if (warp < 8) cluster_wait();
        const uint32_t seen = __ldcg(prm.epoch + blockIdx.x * 16);
        tail_gemm(prm, base, t0, seen + 1, blockIdx.x - NGEMM, warp, lane);
    } else if (warp == 9) {
        const unsigned epoch = __ldcg(prm.epoch + blockIdx.x * 16 + 2) + 1;
        const uint32_t n0 = nanos(), c1 = clock();
        {
            const __nv_bfloat16* const w = prm.pwu + ((mblk >> 1) * 128 + lane / 2) * DF + gate_col(4, nslot) + 96 + rank * 16 + lane % 2 * 8;
            uint4 v[8];
            float cs[8], f[8];
            mbar_wait(empty1(C2AT & 3), 0);
            if (C2AT > 3) mbar_wait(empty1(C2AT & 3), 1);
#pragma unroll
            for (int j = 0; j < 8; j++) v[j] = __ldg(reinterpret_cast<const uint4*>(w + j * 16 * DF));
            unpack8(v[0], cs);
#pragma unroll
            for (int j = 1; j < 8; j++) {
                unpack8(v[j], f);
#pragma unroll
                for (int d = 0; d < 8; d++) cs[d] += f[d];
            }
#pragma unroll
            for (int d = 0; d < 4; d++)
                cs[d] = (lane & 16 ? cs[d + 4] : cs[d]) + __shfl_xor_sync(0xffffffffu, lane & 16 ? cs[d] : cs[d + 4], 16);
#pragma unroll
            for (int d = 0; d < 2; d++) {
                cs[d] = (lane & 8 ? cs[d + 2] : cs[d]) + __shfl_xor_sync(0xffffffffu, lane & 8 ? cs[d] : cs[d + 2], 8);
                cs[d] += __shfl_xor_sync(0xffffffffu, cs[d], 4);
                cs[d] += __shfl_xor_sync(0xffffffffu, cs[d], 2);
            }
            if (!(lane & 6))
                st_tagged(prm.colsum + (16 + nslot / 4) * 1024 + (mblk >> 1) * 128 + nslot % 4 * 32 + rank * 16 + lane % 2 * 8 + (lane >> 3) * 2,
                          cs[0], cs[1], 1 + (epoch & 1));
            TRACE(61);
        }
        if (lane == 0) {
            mbar_wait(sig_bar, 0);
            TRACE(11);
            flag_add(flags + F_LN * 512);
            TRACE(42);
            flag_wait(flags + F_LN * 512, epoch * CNT_LN);
            fence_proxy_async();
            mbar_arrive(dep_bar);
            mbar_wait(sig_bar + 56, 0);
            flag_add(flags + F_LN2 * 512);
            flag_wait(flags + F_LN2 * 512, epoch * CNT_LN);
            fence_proxy_async();
            mbar_arrive(dep_bar + 40);
            TRACE(59);
            prm.epoch[blockIdx.x * 16 + 2] = epoch;
#pragma unroll 1
            for (int p = 3; p < 7; p++) {
                mbar_wait(sig_bar + (p == 3 ? 16 : p * 8), 0);
                TRACE_S(37, p, 4);
                flag_add(flags + (p - (p < F_EARLY)) * 512);
                TRACE_S(43, p, 4);
                if (p == 3 && rank == 0) {
                    mbar_wait(sig_bar + 24, 0);
                    st_relaxed(prm.flags + F_PACE * 512 + mblk * 4 + nslot, forecast(n0, c1, REST, 1 + (epoch & 1)));
                }
            }
        }
    } else if (warp < 8) {
        asm volatile("setmaxnreg.inc.sync.aligned.u32 %0;" :: "n"(CONSUMER_REGS));
        const int wg = __shfl_sync(0xffffffffu, threadIdx.x >> 7, 0);
        const int cw = threadIdx.x >> 5;
        const int tid = threadIdx.x & 127;
        int spins = 1 << 18;
        float acc[128];
        uint32_t pk[64];
#pragma unroll
        for (int i = 0; i < 64; i++) asm volatile("mov.b32 %0, 0;" : "=r"(pk[i]));
#pragma unroll
        for (int i = 0; i < 128; i++) asm volatile("mov.b32 %0, 0;" : "=f"(acc[i]));
        cluster_wait();

        auto row0 = [&](uint32_t id) { return mblk * 128 + (id & 96) + wg; };
        __nv_bfloat16* optr = prm.pxn + (mblk * 128 + nslot * 16 + cw * 2) * DM + lane * 8;
        uint64_t da = desc_a(base + wg * 8192) | (uint64_t)prm.hi[0] << 32, db = desc_b(base + A_BYTES) | (uint64_t)prm.hi[1] << 32;
        auto next1 = [](int s) { return ((s + 1) % G1_STAGES - s) * G1_STAGE_BYTES; };
        auto next2 = [](int q) { return ((q + 1) % G2_STAGES - q) * G2_STAGE_BYTES; };
        uint32_t peer_bars;
        asm volatile("mapa.shared::cluster.u32 %0, %1, %2;" : "=r"(peer_bars) : "r"(bars), "r"(tid & 1));
        if (tid >= 2) peer_bars = 0;
        auto release = [&](uint32_t bar) {
            if (peer_bars) asm volatile("mbarrier.arrive.shared::cluster.b64 _, [%0];" :: "r"(peer_bars + (bar - bars)) : "memory");
        };
        auto up = [](int i) { return 32 + (i & 24) + (i & 3) * 2 + (i >> 2 & 1); };
        auto store_pk = [&](__nv_bfloat16* p, int j) {
            asm volatile("st.global.v4.u32 [%0], {%1,%2,%3,%4};"
                         :: "l"(p), "r"(pk[4 * j]), "r"(pk[4 * j + 1]), "r"(pk[4 * j + 2]), "r"(pk[4 * j + 3]) : "memory");
        };
        auto chunk_geglu = [&](int j) {
#pragma unroll
            for (int i = 4 * j; i < 4 * j + 4; i++) pk[i] = geglu2(pk[i], pk[up(i)]);
            store_pk(optr + (j & 1) * 16 * K2 + (j >> 1) * 32, j);
        };
        auto signal_stores = [&](int p) { __syncwarp(); if (lane == 0) mbar_arrive(sig_bar + p * 8); };

        auto chunk_ln = [&](int k) {
            Floats<6> mo(pk + 32);
            if (k == 0) {
                const uint4* xp = reinterpret_cast<const uint4*>(prm.px + (optr - prm.pxn));
                pk[38] = __ldcg(prm.epoch + blockIdx.x * 16 + 2);
#pragma unroll
                for (int i = 0; i < 8; i++) {
                    const uint4 v = ldg_stream(xp + i * 32, stream_policy());
                    pk[4 * i] = v.x; pk[4 * i + 1] = v.y; pk[4 * i + 2] = v.z; pk[4 * i + 3] = v.w;
                }
            } else if (k >= LN_STEP && k < LN_STEP + 3) {
                if (k == LN_STEP) {
                    mo[0] = bf_lo(uniform(pk[0])); mo[1] = bf_lo(uniform(pk[16]));
                    mo[2] = mo[3] = mo[4] = mo[5] = 0.f;
                }
#pragma unroll
                for (int i = (k - LN_STEP) * 11; i < (k - LN_STEP) * 11 + 11 && i < 32; i++) {
                    const int r = i & 1;
                    const uint32_t w = pk[r * 16 + i / 2];
                    const float lo = bf_lo(w) - mo[r], hi = bf_hi(w) - mo[r];
                    mo[2 + r] += lo + hi;
                    mo[4 + r] = fmaf(hi, hi, fmaf(lo, lo, mo[4 + r]));
                }
                mo.put(pk + 32);
            } else if (k == LN_STEP + 3) {
                const bool second = lane & 16;
                float m1 = (second ? mo[3] : mo[2]) + __shfl_xor_sync(0xffffffffu, second ? mo[2] : mo[3], 16);
                float m2 = (second ? mo[5] : mo[4]) + __shfl_xor_sync(0xffffffffu, second ? mo[4] : mo[5], 16);
#pragma unroll
                for (int o = 8; o > 0; o >>= 1) {
                    m1 += __shfl_xor_sync(0xffffffffu, m1, o);
                    m2 += __shfl_xor_sync(0xffffffffu, m2, o);
                }
                m1 *= 1.f / DM;
                const float var = fmaxf(fmaf(-m1, m1, m2 * (1.f / DM)), 0.f);
                const float mean = round_bf16((second ? mo[1] : mo[0]) + m1);
                const float inv = rcp_fast(round_bf16(sqrt_fast(round_bf16(round_bf16(var) + 1e-5f))));
                if ((lane & 15) == 0) st_tagged(prm.stats + (uint32_t)(optr - prm.pxn) / DM + second, -mean, inv, 2 - (pk[38] & 1));
                const uint32_t split = pack_bf16(inv - round_bf16(inv), inv);
#pragma unroll
                for (int r = 0; r < 2; r++) {
                    const uint32_t f = __shfl_sync(0xffffffffu, split, r * 16);
                    pk[32 + 3 * r] = __byte_perm(__shfl_sync(0xffffffffu, __float_as_uint(mean), r * 16), 0, 0x3232);
                    pk[33 + 3 * r] = __byte_perm(f, 0, 0x3232);
                    pk[34 + 3 * r] = __byte_perm(f, 0, 0x1010);
                }
            } else if (k >= LN_STEP + 4 && k < LN_STEP + 8) {
#pragma unroll
                for (int i = k - LN_STEP - 4; i < 8; i += 4) {
                    const uint32_t* n = pk + 32 + i / 4 * 3;
#pragma unroll
                    for (int j = 4 * i; j < 4 * i + 4; j++) pk[j] = mul2_bf16x2(sub_bf16x2(pk[j], n[0]), n[1], n[2]);
                    store_pk(optr + i * 256, i);
                }
                if (k == LN_STEP + 5 || k == LN_STEP + 7) signal_stores(k == LN_STEP + 5 ? 0 : 7);
            } else if (k == FOLD_STEP) {
                mbar_wait(fold_bar, 0, spins);
                const float2 inv = fold(acc, base, wg);
                mo[0] = inv.x; mo[1] = inv.y;
                mo.put(pk + 32);
            }
        };

        auto halo = [&]() { const uint32_t id = fresh_tid(); return aux + (id & 96) * 128 + (id & 128) * 16 + (id & 31) * 4; };
        auto put = [&](uint32_t a, uint32_t v0, uint32_t v1) {
            asm volatile("st.shared.u32 [%0], %1;\nst.shared.u32 [%0 + 128], %2;" :: "r"(a + HALO_BYTES), "r"(v0), "r"(v1) : "memory");
        };
        auto get = [&](uint32_t a, uint32_t& v0, uint32_t& v1) {
            asm volatile("ld.shared.u32 %0, [%2];\nld.shared.u32 %1, [%2 + 128];" : "=r"(v0), "=r"(v1) : "r"(a) : "memory");
        };
        auto publish = [&](int p) { asm volatile("fence.proxy.async.shared::cta;" ::: "memory"); signal_stores(p); };
        const uint32_t zero[4] = {0, 0, 0, 0};
        auto meet = [&](int n, int k, uint32_t id) {
            if (n == 15 - MEET)
                asm volatile("{\n.reg .b32 c;\nmov.u32 c, %%clock;\nbar.arrive %1, 256;\nlop3.b32 %0, %0, c, 1, 0x70;\n}"
                             : "+r"(peer_bars) : "r"(2 + id / 128) : "memory");
            if (n == 15) {
                asm volatile("{\n.reg .b32 c;\nmov.u32 c, %%clock;\nbar.sync %1, 256;\nlop3.b32 %0, %0, c, 1, 0x70;\n}"
                             : "+r"(peer_bars) : "r"(3 - id / 128) : "memory");
                mma_step(acc, da, db, next1(k & 3), k);
                asm volatile("// batch step");
            }
        };
        auto mix_qk = [&]() {
            uint32_t c[2][4];
            const uint32_t a = halo(), id = fresh_tid();
            if (EREL) { wg_wait<0>(); release(empty1((MIXQ - 1) & 3)); }
            mbar_wait(halo_bar, 0, spins);
#pragma unroll
            for (int n = 0; n < 16; n++) {
                const int b = 1 - n / 8, h = (n & 4) / 2 + n % 2, j = n / 2 % 2;
                uint32_t* const kq = pk + 32 + 8 * h + 4 * j;
                uint32_t* const q = pk + 8 * h + 4 * b;
                mma_sync(j ? q : c[n % 2], kq, q[2 * j], q[2 * j + 1], j ? c[n % 2] : zero);
                if (b) get(a + (h * 2 + j) * 256, kq[1], kq[3]);
                meet(n, MIXQ, id);
            }
        };
        auto chunk_qk = [&](int k) {
            constexpr float LOG2E = 1.4426950408889634f;
            uint32_t* const l = pk + 32;
            Floats<16> e(pk);
            if (k == KK) {
                const uint32_t a = halo();
#pragma unroll
                for (int i = 0; i < 8; i++) put(a + i * 256, pk[33 + 4 * i], pk[35 + 4 * i]);
                publish(1);
            } else if (k == MIXQ + 1) {
                const uint32_t id = fresh_tid();
                const bool u0 = id % 32 / 4 > id % 4 * 2, u1 = id % 32 / 4 > id % 4 * 2 + 1;
                const uint32_t gone = row0(id) < 2 ? (u0 ? 0xffffu : 0u) | (u1 ? 0xffff0000u : 0u) : 0u;
#pragma unroll
                for (int n = 0; n < 8; n++) {
                    const int b = n % 2;
                    const uint32_t* const c = pk + 4 * n;
                    uint32_t v = pack_bf16(__uint_as_float(pick(u0, c[2 - 2 * b], c[2 * b])), __uint_as_float(pick(u1, c[3 - 2 * b], c[1 + 2 * b])));
                    v = mul2_bf16x2(v, 0x3e353e35u, 0x379e379eu);
                    if (!b) v = v & ~gone | 0xce6ece6eu & gone;
                    l[n] = transpose8(v);
                }
            } else if (k == MIXQ + 2) {
#pragma unroll
                for (int h = 0; h < 4; h++) {
                    uint32_t m = max_bf16x2(__byte_perm(l[2 * h], l[2 * h + 1], 0x5410), __byte_perm(l[2 * h], l[2 * h + 1], 0x7632));
                    m = max_bf16x2(m, __shfl_xor_sync(0xffffffffu, m, 1));
                    m = max_bf16x2(m, __shfl_xor_sync(0xffffffffu, m, 2));
#pragma unroll
                    for (int n = 2 * h; n < 2 * h + 2; n++) {
                        const float f = -LOG2E * (n % 2 ? bf_hi(m) : bf_lo(m));
                        e[2 * n] = ex2_fast(fmaf(bf_lo(l[n]), LOG2E, f));
                        e[2 * n + 1] = ex2_fast(fmaf(bf_hi(l[n]), LOG2E, f));
                    }
                }
                e.put(pk);
            } else if (k == MIXQ + 3) {
                uint32_t p[8];
#pragma unroll
                for (int n = 0; n < 8; n++) {
                    float sum = e[2 * n] + e[2 * n + 1];
                    sum += __shfl_xor_sync(0xffffffffu, sum, 1);
                    sum += __shfl_xor_sync(0xffffffffu, sum, 2);
                    const float r = rcp_fast(sum);
                    p[n] = pack_bf16(e[2 * n] * r, e[2 * n + 1] * r);
                }
                const uint32_t a = aux + 5 * HALO_BYTES + fresh_tid() * 16;
                sts128(a, make_uint4(p[0], p[1], p[2], p[3]));
                sts128(a + 4096, make_uint4(p[4], p[5], p[6], p[7]));
            }
        };
        auto values = [&](int h) { return pk + (h & 2) * 16 + (h & 1) * 8; };
        auto mix_pv = [&]() {
            uint32_t lo[8], hi[8];
            const uint32_t id = fresh_tid();
            const uint32_t keep = (id % 4 * 2 > id % 32 / 4 ? 0xffffu : 0u) | (id % 4 * 2 + 1 > id % 32 / 4 ? 0xffff0000u : 0u);
            const uint4 p0 = lds128(aux + 5 * HALO_BYTES + id * 16), p1 = lds128(aux + 6 * HALO_BYTES + id * 16);
            const uint32_t p[8] = {p0.x, p0.y, p0.z, p0.w, p1.x, p1.y, p1.z, p1.w};
#pragma unroll
            for (int n = 0; n < 8; n++)
                asm volatile("and.b32 %0, %2, %3;\nand.b32 %1, %2, %4;" : "=r"(lo[n]), "=r"(hi[n])
                             : "r"(p[n]), "r"(n % 2 ? keep : ~keep), "r"(n % 2 ? ~keep : keep));
            if (EREL) { wg_wait<0>(); release(empty1((MIXV - 1) & 3)); }
            mbar_wait(halo_bar, 1, spins);
#pragma unroll
            for (int n = 0; n < 16; n++) {
                const int i = (n & 8) / 2 + (n & 2) + (n & 4) / 4;
                mma_sync(pk + 4 * (n ^ 4), pk + 4 * (n ^ 4), lo[i], hi[i], zero);
                meet(n, MIXV, id);
            }
        };
        auto chunk_pv = [&](int k) {
            if (k >= VK && k < VK + VN) {
                const uint32_t a = halo();
#pragma unroll
                for (int h = (k - VK) * 4 / VN; h < (k - VK + 1) * 4 / VN; h++) {
                    uint32_t* const w = values(h);
                    uint32_t v[8];
#pragma unroll
                    for (int i = 0; i < 8; i++) v[i] = transpose8(w[h < 2 ? (i & 1) + (i & 2) * 2 + (i & 4) / 2 : (i & 1) * 2 + (i & 2) / 2 + (i & 4)]);
#pragma unroll
                    for (int i = 0; i < 8; i++) w[i] = v[i];
                    put(a + h * 512, w[2], w[3]);
                    put(a + h * 512 + 256, w[6], w[7]);
                }
                if (k == VK + VN - 1) publish(3);
            } else if (k == MIXV - 1) {
                const uint32_t a = halo(), id = fresh_tid();
                optr = prm.pa2 + (size_t)(row0(id) + id % 4 * 4) * K2 + nslot * 128 + (id & 28) * 2;
                mbar_wait(halo_bar, 1, spins);
#pragma unroll
                for (int n = 0; n < 8; n++) {
                    uint32_t* const w = values(n / 2) + n % 2 * 4;
                    w[16] = w[0]; w[17] = w[1];
                    get(a + n * 256, w[18], w[19]);
                }
            } else if (k > MIXV && k <= MIXV + OVS) {
#pragma unroll
                for (int j = 0; j < 8; j++) {
                    if (j * OVS / 8 != k - MIXV - 1) continue;
                    Floats<15> c(pk + j / 2 * 16 + j % 2);
                    asm volatile("st.global.v4.u32 [%0], {%1,%2,%3,%4};"
                                 :: "l"(optr + ((~j & 2) * 8 + j % 2 * 2) * K2 + j / 4 * 64), "r"(pack_bf16(c[0], c[2])),
                                    "r"(pack_bf16(c[4], c[6])), "r"(pack_bf16(c[8], c[10])), "r"(pack_bf16(c[12], c[14])) : "memory");
                }
                if (k == MIXV + OVS) signal_stores(4);
            }
        };

        TRACE_SLOT(tile_slot, 16 + wg * 8);
#pragma unroll 1
        for (int t = 0; t < G1_TILES; t++) {
#pragma unroll
            for (int k = 0; k < G1_KSTEPS; k++) {
                const int s = k & 3;
                if (k % TOP == 0) asm volatile("" : "+r"(t));
                TRACE_STEP(t, k, 0);
                mbar_wait(full1(s), (k >> 2) & 1, spins);
                if (k == 0) TRACE_S(12, t, 0);
                TRACE_STEP(t, k, 1);
                if (wg == 1 && k == G1_KSTEPS - (t == 4 ? SK4 : G1_SKEW)) asm volatile("bar.sync 1, 256;" ::: "memory");
                if (k == MIXV && t == 3) mix_pv();
                else if (k == MIXQ && t == 2) mix_qk();
                else if (t == G1_TILES - 1) mma_step224(acc, da, db, next1(s), k);
                else mma_step(acc, da, db, next1(s), k);
                if (wg == 0 && k == G1_KSTEPS - 1) asm volatile("bar.arrive 1, 256;" ::: "memory");
                wg_wait<1>();
                if (k > 0 && !(EREL && (k == MIXV && t == 3 || k == MIXQ && t == 2))) release(empty1((k - 1) & 3));
                TRACE_STEP(t, k, 2);
                if (t == 0) chunk_ln(k);
                if (k >= 1 && k <= 8 && ((k < GV || k > GV + 3 ? 0x12 : 0x1a) >> t & 1)) {
                    chunk_geglu(k < GV ? k - 1 : (k > GV + 3 ? k - 5 : k - GV + 4));
                    if (k == 8 && t != 3) signal_stores(t + 1);
                }
                if (t == 2) chunk_qk(k);
                if (t == 3) chunk_pv(k);
                if (k == 13) {
                    const uint32_t id = fresh_tid();
                    optr = prm.pa2 + (size_t)(row0(id) + (id & 28) / 2) * K2 + DM + gate_col(t, nslot) + id % 4 * 8;
                    asm volatile("" : "+l"(optr));
                }
            }
            wg_wait<0>();
            fence_regs(acc);
            release(empty1(3));
            if (t == 0) {
                Floats<2> inv(pk + 32);
#pragma unroll
                for (int i = 0; i < 128; i++) acc[i] *= inv[i / 2 % 2];
                fence_regs(acc);
            }
#pragma unroll
            for (int i = 0; i < 64; i++) {
                const int e = i < 32 ? (i & ~7) * 2 + (i & 3) * 4 + (i & 4) / 2 : i * 2;
                pk[i] = pack_bf16(acc[e], acc[e + 1]);
            }
            TRACE_NEXT(tile_slot);
        }

        float accd[64], accs[64];
#pragma unroll
        for (int i = 0; i < 64; i++) accd[i] = 0.f;
#pragma unroll
        for (int u = 0; u < G2_HEAD; u++) {
            const int q = u % G2_STAGES;
            mbar_wait(full2(q), (u / G2_STAGES) & 1, spins);
            mma_step(accd, da, db, next2(q), u);
            wg_wait<1>();
            if (u > 0) release(empty2((u - 1) % G2_STAGES));
            if (u == TLD) {
#pragma unroll
                for (int i = 0; i < 2; i++) {
                    const uint4 v = ldg_stream(prm.tail + role * 512 + i * 256 + threadIdx.x, stream_policy());
                    pk[56 + 4 * i] = v.x; pk[57 + 4 * i] = v.y; pk[58 + 4 * i] = v.z; pk[59 + 4 * i] = v.w;
                }
            }
            if (u >= 1) {
                const int j = (u - 1) / 2;
#pragma unroll
                for (int i = 2 * u - 2; i < 2 * u; i++) pk[i] = geglu2(pk[i], pk[up(i)]);
                if (u % 2 == 0) store_pk(optr + (j & 1) * 16 * K2 + (j >> 1) * 32, j);
            }
            if (u == G2_HEAD - 1) signal_stores(6);
        }
        auto down = [&](int q, uint32_t phase, bool narrow) {
            mbar_wait(full2(q), phase, spins);
            if (narrow) mma_step96(accd, da, db, next2(q), 1);
            else mma_step(accd, da, db, next2(q), 1);
            wg_wait<1>();
            release(empty2((q + G2_STAGES - 1) % G2_STAGES));
        };
        uint32_t shared_steps = plan_word(base, lane);
        down(5, 0, false);
#pragma unroll 1
        for (uint32_t r = 3; r < 9; r++, shared_steps >>= G2_STAGES) {
#pragma unroll
            for (int q = 0; q < G2_STAGES; q++) down(q, r & 1, (q || SMAX > 18) && shared_steps >> q & 1);
        }
        down(0, 1, false);
        down(1, 1, false);
        TRACE_NEXT(tile_slot);
#pragma unroll
        for (int i = 0; i < 64; i++) accs[i] = 0.f;
        uint32_t gk[32], xr[32];
        const uint32_t xs = aux + cw * 2048;
        const uint32_t xrow = xs + ((lane & 7) + ((lane >> 3) & 1) * 8) * 128;
        auto xaddr = [&](int j) { return xrow + (j >> 2) * 16384 + (((((j & 3) * 2) + (lane >> 4)) ^ (lane & 7)) << 4); };
#pragma unroll
        for (int u = G2_DSTEPS; u < G2_KSTEPS; u++) {
            const int q = u % G2_STAGES, v = u - G2_DSTEPS;
            mbar_wait(full2(q), (u / G2_STAGES) & 1, spins);
            if (G2_SKEW > 0 && wg == 1 && u == G2_KSTEPS - G2_SKEW) asm volatile("bar.sync 1, 256;" ::: "memory");
            mma_step(accs, da, db, next2(q), v);
            if (G2_SKEW > 0 && wg == 0 && u == G2_KSTEPS - 1) asm volatile("bar.arrive 1, 256;" ::: "memory");
            if (v == TLD2) {
                TRACE_S(32, wg, 0);
                mbar_wait(dep_bar + 24, 0, spins);
                TRACE_S(33, wg, 0);
#pragma unroll
                for (int i = 0; i < 2; i++) {
                    const uint4 w = ldg_stream(prm.tail + (NGEMM + role) * 512 + i * 256 + threadIdx.x, stream_policy());
                    gk[24 + 4 * i] = w.x; gk[25 + 4 * i] = w.y; gk[26 + 4 * i] = w.z; gk[27 + 4 * i] = w.w;
                }
            }
#pragma unroll
            for (int i = 0; i < 32; i++) {
                if (v == (i < 24 ? i / 4 + 1 : TLD2 + (i < 28 ? GA : GB)))
                    gk[i] = i < 24 ? silu2(accd[2 * i], accd[2 * i + 1])
                                   : silu2(accd[2 * i] + bf_lo(gk[i]), accd[2 * i + 1] + bf_hi(gk[i]));
            }
            if (v == XLD) mbar_wait(x_bar, 0, spins);
            if (v >= XLD && v < XLD + 4) {
#pragma unroll
                for (int j = 2 * (v - XLD); j < 2 * (v - XLD + 1); j++)
                    asm volatile("ldmatrix.sync.aligned.m8n8.x4.shared.b16 {%0,%1,%2,%3}, [%4];"
                                 : "=r"(xr[4 * j]), "=r"(xr[4 * j + 1]), "=r"(xr[4 * j + 2]), "=r"(xr[4 * j + 3])
                                 : "r"(xaddr(j)) : "memory");
            }
            wg_wait<1>();
            if (v == 0) fence_regs(accd);
            if (u - 1 + G2_STAGES < G2_KSTEPS) release(empty2((u - 1) % G2_STAGES));
        }
        __nv_bfloat16* po = prm.pout + (row0(fresh_tid()) + (lane >> 3) * 2) * DM + nslot * 128 + 64 + (lane & 7) * 8;
        uint32_t so = xs + 16384 + (lane >> 3) * 128 + (((lane & 7) ^ (lane >> 3)) << 4);
        const int c0 = uniform(nslot * 128), c1 = uniform(row0(fresh_tid()) >> 1);
        const uint32_t xu = uniform(xs);
        asm volatile("" : "+l"(po), "+r"(so));
        wg_wait<0>();
        fence_regs(accs);
        TRACE_NEXT(tile_slot);
        TRACE_END();
#pragma unroll
        for (int j = 0; j < 8; j++) {
            uint32_t r[4];
#pragma unroll
            for (int i = 0; i < 4; i++) {
                const int e = j * 4 + i;
                asm("fma.rn.bf16x2 %0, %1, %2, %3;" : "=r"(r[i]) : "r"(pack_bf16(accs[2 * e], accs[2 * e + 1])), "r"(gk[e]), "r"(xr[e]));
            }
            asm volatile("stmatrix.sync.aligned.m8n8.x4.shared.b16 [%0], {%1,%2,%3,%4};"
                         :: "r"(xaddr(j)), "r"(r[0]), "r"(r[1]), "r"(r[2]), "r"(r[3]) : "memory");
            if (j == 3)
                asm volatile("{\n.reg .pred e;\nfence.proxy.async.shared::cta;\nbar.warp.sync 0xffffffff;\nelect.sync _|e, 0xffffffff;\n"
                    "@e cp.async.bulk.tensor.3d.global.shared::cta.bulk_group [%0, {%2, %3, %4}], [%1];\n}"
                    :: "l"(&prm.out), "r"(xu), "r"(c0), "r"(c1), "r"(wg) : "memory");
        }
        __syncwarp();
#pragma unroll
        for (int i = 0; i < 4; i++) {
            const uint4 v = lds128((so ^ (i & 1) * 64) + i * 512);
            asm volatile("st.global.v4.u32 [%0], {%1,%2,%3,%4};" :: "l"(po + i * 8 * DM), "r"(v.x), "r"(v.y), "r"(v.z), "r"(v.w) : "memory");
        }
        asm volatile("cp.async.bulk.commit_group;\ncp.async.bulk.wait_group.read 0;" ::: "memory");
        TRACE_LITE(10, clock());
        if (tid == 0) { TRACE_NEXT(tile_slot); if (wg == 1) TRACE_GT(13); TRACE_DUMP(); }
    } else if (warp > 9) {
        const int w = warp - 10;
        const unsigned epoch = __ldcg(prm.epoch + blockIdx.x * 16 + w) + 1;
        const uint32_t tag = 1 + (epoch & 1);
        TRACE_LITE(8, t0);
        const uint32_t at = (w ? CB : CA) >> (CIDX) * 4 & 15;
        mbar_wait(empty1(at & 3), 0);
        mbar_wait(empty1(at & 3), at >> 3);
        if (elect_one()) {
            mbar_expect_tx(cs_bar + w * 8, 16384);
            asm volatile("cp.async.bulk.tensor.2d.shared::cluster.global.mbarrier::complete_tx::bytes [%0], [%1, {%3, %5}], [%2];\n"
                "cp.async.bulk.tensor.2d.shared::cluster.global.mbarrier::complete_tx::bytes [%0 + 8192], [%1, {%4, %5}], [%2];"
                :: "r"(aux + w * 16384), "l"(w0), "r"(cs_bar + w * 8), "r"(nslot * 128), "r"(nslot * 128 + 64),
                   "r"(((mblk & ~1) + w) * 64) : "memory");
        }
        float cs[8];
#pragma unroll
        for (int d = 0; d < 8; d++) cs[d] = 0.f;
        const uint32_t wa = aux + w * 8192 + (lane >> 3) * 128 + (((lane & 7) ^ (lane >> 3)) << 4);
        uint4 v[8];
        auto fetch = [&](int h, uint32_t off) {
#pragma unroll
            for (int j = 0; j < 4; j++) v[h * 4 + j] = lds128((wa ^ (j & 1) * 64) + off + h * 2048 + j * 512);
        };
        auto add = [&](int h) {
#pragma unroll
            for (int j = 0; j < 4; j++) {
                float f[8];
                unpack8(v[h * 4 + j], f);
#pragma unroll
                for (int d = 0; d < 8; d++) cs[d] += f[d];
            }
        };
        if (CST) { mbar_wait(empty1(CST & 3), 0); mbar_wait(empty1(CST & 3), CST >> 3); }
        mbar_wait(cs_bar, 0);

        fetch(0, 0);
#pragma unroll 1
        for (int i = 0; i < 4; i++) {
            fetch(1, (i >> 1) * 16384 + (i & 1) * 4096);
            add(0);
            if (i == 1) mbar_wait(cs_bar + 8, 0);
            fetch(0, (i + 1 & 2) * 8192 + (~i & 1) * 4096);
            add(1);
        }
#pragma unroll
        for (int d = 0; d < 4; d++)
            cs[d] = (lane & 16 ? cs[d + 4] : cs[d]) + __shfl_xor_sync(0xffffffffu, lane & 16 ? cs[d] : cs[d + 4], 16);
#pragma unroll
        for (int d = 0; d < 2; d++)
            cs[d] = (lane & 8 ? cs[d + 2] : cs[d]) + __shfl_xor_sync(0xffffffffu, lane & 8 ? cs[d] : cs[d + 2], 8);
        st_tagged(prm.colsum + (nslot * 2 + rank) * 1024 + (mblk >> 1) * 128 + w * 64 + (lane & 7) * 8 + (lane >> 3) * 2,
                  cs[0], cs[1], tag);

        fold_operands(prm, base, nslot, mblk, tag, w, lane);
        if (lane == 0) {
            mbar_arrive(fold_bar);
            prm.epoch[blockIdx.x * 16 + w] = epoch;
            if (w == 0) {
                TRACE(35);
#pragma unroll 1
                for (uint32_t j = 0, n = 1 << 24; j < 4; n = (CNT_EARLY | CNT_LATE << 8 | 1 << 16) >> j * 8 & 255, j++) {
                    const uint32_t v = flag_wait(flags + (F_SHARE + j) * 512, epoch * n);
                    fence_proxy_async();
                    if (j) mbar_arrive(dep_bar + j * 8);
                    else sts32(base + PLAN_OFF, v & 0xffffff);
                }
            } else {
#pragma unroll 1
                for (int j = 0; j < 2; j++) {
                    uint8_t* const h = prm.halo + (j * NGEMM + role) * HALO_BYTES;
                    unsigned* const f = prm.flags + F_HALO * 512 + role * 32;
                    mbar_wait(sig_bar + 8 + j * 16, 0);
                    TRACE_S(38, j, 0); TRACE_S(9, j, 1);
                    asm volatile("cp.async.bulk.global.shared::cta.bulk_group [%0], [%1], %2;\n"
                        "cp.async.bulk.commit_group;\ncp.async.bulk.wait_group 0;"
                        :: "l"(h + HALO_BYTES), "r"(aux + 4 * HALO_BYTES), "n"(HALO_BYTES) : "memory");
                    fence_proxy_async();
                    TRACE_S(39, j, 0); TRACE_S(10, j, 1);
                    flag_add(f);
                    TRACE_S(40, j, 0); TRACE_S(34, j, 1);
                    if (mblk) flag_wait(f - 32, epoch * 2 - 1 + j);
                    fence_proxy_async();
                    TRACE_S(41, j, 0); TRACE_S(36, j, 1);
                    mbar_expect_tx(halo_bar, HALO_BYTES);
                    asm volatile("cp.async.bulk.shared::cluster.global.mbarrier::complete_tx::bytes [%0], [%1], %2, [%3];"
                        :: "r"(aux), "l"(mblk ? h : prm.halo), "n"(HALO_BYTES), "r"(halo_bar) : "memory");
                }
            }
        }
    } else {
        constexpr int roll = ROLL;
#pragma unroll roll
        for (int k = 1; k < G1_STAGES; k++) {
            const uint32_t sa = base + k * G1_STAGE_BYTES;
            if (PACE0 + PACE) while ((uint32_t)clock() - t0 < (k == 3 ? PACE3 : PACE0 + (k - 1) * PACE)) {}
            load_stage1(sa, sa + A_BYTES + rank * 16384, full1(k), &prm.x, w0, w0, k * 64, mblk * 64, nslot * 128,
                        nslot * 128 + 64, 0, stream_policy());
        }
        if (elect_one()) {
            prefetch_map(&prm.xn); prefetch_map(&prm.wqkv);
            prefetch_map(&prm.a2); prefetch_map(&prm.wo); prefetch_map(&prm.wd); prefetch_map(&prm.out);
        }
        auto load_x = [&]() {
            if (elect_one()) {
                mbar_expect_tx(x_bar, 32768);
                tma_3d(aux, &prm.x, x_bar, nslot * 128, mblk * 64, 0, stream_policy());
                tma_3d(aux + 16384, &prm.x, x_bar, nslot * 128 + 64, mblk * 64, 0, stream_policy());
            }
            __syncwarp();
        };
        uint32_t ph = 0;
#pragma unroll 1
        for (int t = 0; t < G1_TILES; t++) {
            const int col1 = (t == 1 ? rank * DM + nslot * 128 : gate_col(t, nslot)) + 64;
            const int col0 = t == 2 ? 2 * DM + nslot * 128 + rank * 64 : col1 - 64;
            if (t == 1) { TRACE_PUT(2, t0); TRACE(14); mbar_wait_warp(dep_bar, 0); TRACE(3); }
#pragma unroll 1
            for (int k = t ? 0 : G1_STAGES; k < G1_KSTEPS; k++) {
                const int s = k & 3;
                if (t == 1 && k == 8) mbar_wait_warp(dep_bar + 40, 0);
                if (t * 16 + k == (PFK)) {
                    asm volatile("{\n.reg .pred e;\nelect.sync _|e, 0xffffffff;\n"
                        "@e cp.async.bulk.prefetch.tensor.5d.L2.global [%0, {%1, %4, %4, %4, %3}];\n"
                        "@e cp.async.bulk.prefetch.tensor.5d.L2.global [%0, {%2, %4, %4, %4, %3}];\n}"
                        :: "l"(&prm.wd), "r"(nslot * 128), "r"(nslot * 128 + 64), "r"((mblk + SHARE_MAX) * 2), "r"(0) : "memory");
                }
                mbar_wait_warp(empty1(s), ph);
                const uint32_t sa = base + s * G1_STAGE_BYTES;
                load_stage1(sa, sa + A_BYTES + rank * 16384, full1(s), t ? &prm.xn : &prm.x, t == 1 || t == 2 ? &prm.wqkv : w0,
                            t == 1 ? &prm.wqkv : w0, k * 64, mblk * 64, col0, col1, t & 3,
                            stream_policy());
                if (s == 3) ph ^= 1;
                if (t * 16 + k == (XK)) load_x();
            }
        }
        TRACE(4);
        mbar_wait_warp(dep_bar + 8, 0);
        TRACE(5);
        int q = 0, round = 4, own = SHARE_MAX; uint32_t ph2 = 1;
#pragma unroll 1
        for (int u = 0; u < G2_KSTEPS; u++) {
            if (u == G2_LATE) { TRACE(6); mbar_wait_warp(dep_bar + 16, 0); TRACE(7); }
            const uint32_t sa = stage2(q);
            const bool down = u < G2_DSTEPS;
            const int k = !down ? u - G2_DSTEPS : (u < 18 || u >= 40 || (SMAX == 18 && q == 0) ? own++ : (q & 1 ? u / 2 - 9 : round + (q ? q * 2 : 11)));
            mbar_wait_warp(u < G2_STAGES ? empty1((u * 2 + 1) / 3) : empty2(q), u < G2_STAGES ? ph : ph2);
            load_stage2(sa, sa + A_BYTES + rank * 8192, full2(q), &prm.a2, down ? &prm.wd : &prm.wo, (down ? DM : 0) + k * 64,
                        mblk * 64, nslot * 128 + rank * 64, down ? 0 : k * 2, down ? k * 2 : 0, stream_policy());
            if (++q == G2_STAGES) { q = 0; ph2 ^= 1; round++; }
        }
        TRACE(8);
    }
}

typedef CUresult (*EncodeFn)(CUtensorMap*, CUtensorMapDataType, cuuint32_t, void*, const cuuint64_t*, const cuuint64_t*,
                             const cuuint32_t*, const cuuint32_t*, CUtensorMapInterleave, CUtensorMapSwizzle,
                             CUtensorMapL2promotion, CUtensorMapFloatOOBfill);

void encode(EncodeFn fn, CUtensorMap* m, const void* ptr, int rank, const cuuint64_t* dims, const cuuint64_t* strides,
            const cuuint32_t* box) {
    const cuuint32_t es[5] = {1, 1, 1, 1, 1};
    fn(m, CU_TENSOR_MAP_DATA_TYPE_BFLOAT16, rank, const_cast<void*>(ptr), dims, strides, box, es,
       CU_TENSOR_MAP_INTERLEAVE_NONE, box[0] == 32 ? CU_TENSOR_MAP_SWIZZLE_64B : CU_TENSOR_MAP_SWIZZLE_128B,
       CU_TENSOR_MAP_L2_PROMOTION_L2_128B, CU_TENSOR_MAP_FLOAT_OOB_FILL_NONE);
}
void encode_rows(EncodeFn fn, CUtensorMap* m, const void* ptr, int cols, int box_rows, int box_parity) {
    const cuuint64_t dims[3] = {(cuuint64_t)cols, SEQ / 2, 2}, strides[2] = {(cuuint64_t)cols * 4, (cuuint64_t)cols * 2};
    const cuuint32_t box[3] = {64, (cuuint32_t)box_rows, (cuuint32_t)box_parity};
    encode(fn, m, ptr, 3, dims, strides, box);
}
void encode_w1(EncodeFn fn, CUtensorMap* m, const void* ptr, int cols) {
    const cuuint64_t dims[2] = {(cuuint64_t)cols, DM}, strides[1] = {(cuuint64_t)cols * 2};
    const cuuint32_t box[2] = {64, 64};
    encode(fn, m, ptr, 2, dims, strides, box);
}
void encode_tail(EncodeFn fn, CUtensorMap* m, const void* ptr, int rows, int cols, int n) {
    const cuuint64_t rb = cols * 2;
    const cuuint64_t dims[5] = {32, (cuuint64_t)n, (cuuint64_t)rows / (4 * n), 4, 8}, strides[4] = {rb, 4 * n * rb, n * rb, 256};
    const cuuint32_t box[5] = {32, (cuuint32_t)n, 16 / (cuuint32_t)n, 4, 4};
    encode(fn, m, (const __nv_bfloat16*)ptr + cols - 1024 + 96, 5, dims, strides, box);
}
void encode_w2(EncodeFn fn, CUtensorMap* m, const void* ptr, int rows) {
    const cuuint64_t rb = DM * 2;
    const cuuint64_t dims[5] = {DM, 2, 4, 4, (cuuint64_t)rows / 32}, strides[4] = {rb, 8 * rb, 2 * rb, 32 * rb};
    const cuuint32_t box[5] = {64, 2, 4, 4, 2};
    encode(fn, m, ptr, 5, dims, strides, box);
}
void encode_wo(EncodeFn fn, CUtensorMap* m, const void* ptr) {
    const cuuint64_t rb = DM * 2;
    const cuuint64_t dims[5] = {DM, 4, DM / 32, 2, 4}, strides[4] = {8 * rb, 32 * rb, rb, 2 * rb};
    const cuuint32_t box[5] = {64, 4, 2, 2, 4};
    encode(fn, m, ptr, 5, dims, strides, box);
}

}

extern "C" void kernel_launch(void* const* d_in, const int* in_sizes, int n_in, void* d_out, int out_size) {
    (void)in_sizes; (void)n_in; (void)out_size;
    static EncodeFn fn = nullptr;
    static Params prm;
    if (!fn) {
        cudaDriverEntryPointQueryResult st;
        cudaGetDriverEntryPoint("cuTensorMapEncodeTiled", (void**)&fn, cudaEnableDefault, &st);
        cudaGetSymbolAddress((void**)&prm.pxn, g_xn);
        cudaGetSymbolAddress((void**)&prm.pa2, g_a2);
        cudaGetSymbolAddress((void**)&prm.tail, g_tail);
        cudaGetSymbolAddress((void**)&prm.halo, g_halo);
        cudaGetSymbolAddress((void**)&prm.stats, g_stats);
        cudaGetSymbolAddress((void**)&prm.colsum, g_colsum);
        cudaGetSymbolAddress((void**)&prm.flags, g_flags);
        cudaGetSymbolAddress((void**)&prm.epoch, g_epoch);
        cudaFuncSetAttribute(fused_kernel, cudaFuncAttributeMaxDynamicSharedMemorySize, SMEM_BYTES);
    }
    encode_rows(fn, &prm.x, d_in[0], DM, 64, 2);
    encode_rows(fn, &prm.xn, prm.pxn, DM, 64, 2);
    encode_rows(fn, &prm.a2, prm.pa2, K2, 64, 2);
    encode_rows(fn, &prm.out, d_out, DM, 16, 1);
    encode_w1(fn, &prm.wqkv, d_in[1], NQKV);
    encode_w1(fn, &prm.wg, d_in[4], DF);
    encode_w1(fn, &prm.wu, d_in[5], DF);
    encode_tail(fn, &prm.wu_tail, d_in[5], DM, DF, 8);
    encode_tail(fn, &prm.wd_tail, d_in[6], DF, DM, 2);
    encode_wo(fn, &prm.wo, d_in[2]);
    encode_w2(fn, &prm.wd, d_in[6], DF);
    prm.hi[0] = prm.hi[1] = 0x40000040;
    prm.px = (const __nv_bfloat16*)d_in[0];
    prm.pwu = (const __nv_bfloat16*)d_in[5];
    prm.pout = (__nv_bfloat16*)d_out;
    fused_kernel<<<NCTA, 384, SMEM_BYTES>>>(prm);
}
```

```cpp
#include <cuda_runtime.h>
#include <cuda_bf16.h>
#include <cuda.h>
#include <stdint.h>
#include <limits.h>

#define LNS 3
#define FS 14
#define CA 0x87658765u
#define CB 0x65876587u
#define CST 10
#define CIDX nslot
#define PACE0 900
#define PACE 425
#define PACE3 1700
#define TSUM 43
#define SMIN 3
#define SMAX 22
#define BIAS 30
#define DUE 75300.f
#define TLO 36
#define SWAP 1
#define STEPNS 79
#define REST 65000.f
#define ROLL 1
#define BAL 1
#define C2AT 2
#define TPACE 425
#define TEARLY 1
#define TEW 8
#define WDPF 1
#define TFOLD 1
#define MIXQ 8
#define MIXV 9
#define TLD2 7
#define XLD 7
#define VK 1
#define VN 2
#define KK 2
#define EREL 0
#define MEET 4
#define OVS 4
#define GV 3
#define TOP 16
#define SK2 5
#define PFK 60 + mblk
#define XK 66 + nslot
#define TSK 2
#define TW0 600
#define TLD 2
#define SK4 2
#define GA 3
#define GB 4

namespace {

constexpr int SEQ = 2048, DM = 1024, DF = 3584, K2 = DM + DF, NQKV = 3 * DM;
constexpr int NGEMM = 128, NCTA = 132;
constexpr int G1_STAGES = 4, G1_STAGE_BYTES = 49152, G1_KSTEPS = 16, G1_TILES = 5;
constexpr int G2_STAGES = 6, G2_STAGE_BYTES = 32768, G2_KSTEPS = 72, G2_LATE = 40, G2_DSTEPS = 56;
constexpr int G2_HEAD = 17;
constexpr int LN_STEP = LNS, FOLD_STEP = FS;
constexpr int A_BYTES = 16384;
constexpr int AUX_OFF = G1_STAGES * G1_STAGE_BYTES;
constexpr int BAR_OFF = AUX_OFF + 32768;
constexpr int PLAN_OFF = BAR_OFF + 384, STAT_OFF = BAR_OFF + 1536;
constexpr int SMEM_BYTES = BAR_OFF + 2816;
constexpr int G1_SKEW = 2, G2_SKEW = SK2;
constexpr int CONSUMER_REGS = 224, AUX_REGS = 56;
constexpr int HALO_BYTES = 4096;
constexpr int SHARE_MIN = SMIN, SHARE_MAX = SMAX, SHARE_SUM = TSUM;

enum { F_LN = 0, F_LN2 = 1, F_FIRST = 2, F_SECOND = 3, F_SHARE = 4, F_EARLY = 5, F_LATE = 6, F_TAIL2 = 7, F_PACE = 8, F_HALO = 9 };
constexpr unsigned CNT_LN = 8, CNT_EARLY = 9, CNT_LATE = 8;

__device__ __align__(1024) __nv_bfloat16 g_xn[SEQ * DM];
__device__ __align__(1024) __nv_bfloat16 g_a2[SEQ * K2];
__device__ __align__(128) uint4 g_tail[2 * NGEMM * 512];
__device__ __align__(128) uint8_t g_halo[(2 * NGEMM + 1) * HALO_BYTES];
__device__ __align__(128) float2 g_stats[SEQ];
__device__ __align__(128) float g_colsum[18 * 1024];
__device__ __align__(128) unsigned g_flags[(F_HALO + 8) * 16 * 32];
__device__ __align__(128) unsigned g_epoch[NCTA * 16];

struct Params {
    const __nv_bfloat16 *px, *pwu;
    __nv_bfloat16 *pxn, *pa2, *pout;
    uint4* tail;
    uint8_t* halo;
    float2* stats;
    float* colsum;
    unsigned *flags, *epoch;
    unsigned long long* trace;
    uint32_t hi[2];
    CUtensorMap x, wg, wu, xn, wqkv, a2, wu_tail, wd_tail, wo, wd, out;
};

extern __shared__ __align__(1024) uint8_t smem_raw[];

#define TRACE(slot) do {} while (0)
#define TRACE_GT(slot) do {} while (0)
#define TRACE_S(slot, v, want) do {} while (0)
#define TRACE_GET(v) do {} while (0)
#define TRACE_PUT(slot, v) do {} while (0)
#define TRACE_SLOT(v, slot) do {} while (0)
#define TRACE_NEXT(v) do {} while (0)
#define TRACE_DUMP() do {} while (0)
#define TRACE_CLEAR() do {} while (0)
#define STAGE_TRACE 0
#define TRACE_END() do {} while (0)
#define TRACE_LITE(i, c) do {} while (0)
#define TRACE_STEP(t, k, i) do {} while (0)

__device__ __forceinline__ uint32_t smem_u32(const void* p) { return (uint32_t)__cvta_generic_to_shared(p); }
__device__ __forceinline__ void mbar_init(uint32_t bar, uint32_t cnt) {
    asm volatile("mbarrier.init.shared::cta.b64 [%0], %1;" :: "r"(bar), "r"(cnt) : "memory");
}
__device__ __forceinline__ void mbar_expect_tx(uint32_t bar, uint32_t bytes) {
    asm volatile("mbarrier.arrive.expect_tx.shared::cta.b64 _, [%0], %1;" :: "r"(bar), "r"(bytes) : "memory");
}
__device__ __forceinline__ void mbar_arrive(uint32_t bar) {
    asm volatile("mbarrier.arrive.shared::cta.b64 _, [%0];" :: "r"(bar) : "memory");
}
__device__ __forceinline__ bool mbar_try_wait(uint32_t bar, uint32_t parity) {
    uint32_t ok;
    asm volatile("{\n.reg .pred p;\nmbarrier.try_wait.parity.shared::cta.b64 p, [%1], %2;\nselp.u32 %0, 1, 0, p;\n}"
                 : "=r"(ok) : "r"(bar), "r"(parity) : "memory");
    return ok;
}
__device__ __forceinline__ void mbar_wait(uint32_t bar, uint32_t parity) {
#pragma unroll 1
    for (int spins = 0; !mbar_try_wait(bar, parity) && spins < (1 << 17); spins++) {}
}
__device__ __forceinline__ void mbar_wait(uint32_t bar, uint32_t parity, int& spins) {
    asm volatile("{\n.reg .pred p;\nagain:\nmbarrier.try_wait.parity.shared::cta.b64 p, [%1], %2;\n@p bra done;\n"
                 "add.s32 %0, %0, -1;\nsetp.gt.s32 p, %0, 0;\n@p bra again;\ndone:\n}" : "+r"(spins) : "r"(bar), "r"(parity) : "memory");
}
template <bool WARP = false> __device__ __forceinline__ unsigned flag_wait(const unsigned* p, unsigned target) {
    unsigned v;
#pragma unroll 1
    for (int spins = 0; spins < (1 << 19); spins++) {
        asm volatile("ld.acquire.gpu.global.u32 %0, [%1];" : "=r"(v) : "l"(p) : "memory");
        if (WARP ? __all_sync(0xffffffffu, (int)(v - target) >= 0) : (int)(v - target) >= 0) break;
        __nanosleep(64);
    }
    return v;
}
__device__ __forceinline__ void mbar_wait_warp(uint32_t bar, uint32_t parity) {
#pragma unroll 1
    for (int spins = 0; !__all_sync(0xffffffffu, mbar_try_wait(bar, parity)) && spins < (1 << 17); spins++) {}
}
__device__ __forceinline__ void flag_add(unsigned* p) {
    asm volatile("red.release.gpu.global.add.u32 [%0], 1;" :: "l"(p) : "memory");
}
__device__ __forceinline__ bool elect_one() {
    uint32_t ok;
    asm volatile("{\n.reg .pred p;\nelect.sync _|p, 0xffffffff;\nselp.u32 %0, 1, 0, p;\n}" : "=r"(ok));
    return ok;
}
__device__ __forceinline__ uint32_t pick(bool c, uint32_t a, uint32_t b) {
    uint32_t r;
    asm("{\n.reg .pred p;\nsetp.ne.b32 p, %3, 0;\nselp.b32 %0, %1, %2, p;\n}" : "=r"(r) : "r"(a), "r"(b), "r"((uint32_t)c));
    return r;
}
__device__ __forceinline__ void fence_proxy_async() { asm volatile("fence.proxy.async.global;" ::: "memory"); }
__device__ __forceinline__ uint4 lds128(uint32_t addr) {
    uint4 v;
    asm volatile("ld.shared.v4.u32 {%0,%1,%2,%3}, [%4];" : "=r"(v.x), "=r"(v.y), "=r"(v.z), "=r"(v.w) : "r"(addr) : "memory");
    return v;
}
__device__ __forceinline__ uint32_t lds32(uint32_t addr) {
    uint32_t v;
    asm volatile("ld.shared.u32 %0, [%1];" : "=r"(v) : "r"(addr) : "memory");
    return v;
}
__device__ __forceinline__ void sts32(uint32_t addr, uint32_t v) { asm volatile("st.shared.u32 [%0], %1;" :: "r"(addr), "r"(v) : "memory"); }
__device__ __forceinline__ uint32_t nanos() { uint32_t t; asm volatile("mov.u32 %0, %%globaltimer_lo;" : "=r"(t)); return t; }
__device__ __forceinline__ float2 lds64f(uint32_t addr) {
    float2 v;
    asm volatile("ld.shared.v2.f32 {%0,%1}, [%2];" : "=f"(v.x), "=f"(v.y) : "r"(addr) : "memory");
    return v;
}
__device__ __forceinline__ void sts128(uint32_t addr, uint4 v) {
    asm volatile("st.shared.v4.u32 [%0], {%1,%2,%3,%4};" :: "r"(addr), "r"(v.x), "r"(v.y), "r"(v.z), "r"(v.w) : "memory");
}
__device__ __forceinline__ void sts64f(uint32_t addr, float a, float b) {
    asm volatile("st.shared.v2.f32 [%0], {%1,%2};" :: "r"(addr), "f"(a), "f"(b) : "memory");
}

__device__ __forceinline__ uint64_t stream_policy() { return 0x12F0000000000000ull; }
__device__ __forceinline__ void tma_3d(uint32_t dst, const CUtensorMap* m, uint32_t bar, int c0, int c1, int c2, uint64_t pol) {
    asm volatile("cp.async.bulk.tensor.3d.shared::cluster.global.mbarrier::complete_tx::bytes.L2::cache_hint"
                 " [%0], [%1, {%3, %4, %5}], [%2], %6;"
                 :: "r"(dst), "l"(m), "r"(bar), "r"(c0), "r"(c1), "r"(c2), "l"(pol) : "memory");
}
__device__ __forceinline__ void load_stage1(uint32_t dst, uint32_t dst_b, uint32_t bar, const CUtensorMap* ma, const CUtensorMap* mb0,
                                            const CUtensorMap* mb1, int k, int row, int col0, int col1, int keep_a, uint64_t pol) {
    asm volatile("{\n.reg .pred e, p, q;\nelect.sync _|e, 0xffffffff;\nsetp.ne.and.b32 p|q, %8, 0, e;\n"
        "@p cp.async.bulk.tensor.3d.shared::cluster.global.mbarrier::complete_tx::bytes [%0], [%3, {%5, %6, %10}], [%2];\n"
        "@q cp.async.bulk.tensor.3d.shared::cluster.global.mbarrier::complete_tx::bytes.L2::cache_hint [%0], [%3, {%5, %6, %10}], [%2], %9;\n"
        "@e cp.async.bulk.tensor.2d.shared::cluster.global.mbarrier::complete_tx::bytes.multicast::cluster.L2::cache_hint"
        " [%1], [%4, {%7, %5}], [%2], %11, %9;\n"
        "@e cp.async.bulk.tensor.2d.shared::cluster.global.mbarrier::complete_tx::bytes.multicast::cluster.L2::cache_hint"
        " [%1 + 8192], [%13, {%14, %5}], [%2], %11, %9;\n"
        "@e mbarrier.arrive.expect_tx.shared::cta.b64 _, [%2], %12;\n}"
        :: "r"(dst), "r"(dst_b), "r"(bar), "l"(ma), "l"(mb0), "r"(k), "r"(row), "r"(col0), "r"(keep_a), "l"(pol), "r"(0),
           "h"((uint16_t)3), "n"(G1_STAGE_BYTES), "l"(mb1), "r"(col1) : "memory");
}
__device__ __forceinline__ void load_stage2(uint32_t dst, uint32_t dst_b, uint32_t bar, const CUtensorMap* ma, const CUtensorMap* mb,
                                            int ka, int row, int col, int kb2, int kb4, uint64_t pol) {
    asm volatile("{\n.reg .pred e;\nelect.sync _|e, 0xffffffff;\n"
        "@e cp.async.bulk.tensor.3d.shared::cluster.global.mbarrier::complete_tx::bytes.L2::cache_hint [%0], [%3, {%5, %6, %10}], [%2], %9;\n"
        "@e cp.async.bulk.tensor.5d.shared::cluster.global.mbarrier::complete_tx::bytes.multicast::cluster.L2::cache_hint"
        " [%1], [%4, {%7, %10, %13, %10, %8}], [%2], %11, %9;\n"
        "@e mbarrier.arrive.expect_tx.shared::cta.b64 _, [%2], %12;\n}"
        :: "r"(dst), "r"(dst_b), "r"(bar), "l"(ma), "l"(mb), "r"(ka), "r"(row), "r"(col), "r"(kb4), "l"(pol), "r"(0),
           "h"((uint16_t)3), "n"(G2_STAGE_BYTES), "r"(kb2) : "memory");
}
__device__ __forceinline__ void load_tail(uint32_t dst, uint32_t bar, const CUtensorMap* ma, const CUtensorMap* mb, int ka, int mblk,
                                          int kb) {
    asm volatile("{\n.reg .pred e;\nelect.sync _|e, 0xffffffff;\n"
        "@e cp.async.bulk.tensor.3d.shared::cluster.global.mbarrier::complete_tx::bytes [%0], [%2, {%3, %4, %5}], [%1];\n"
        "@e cp.async.bulk.tensor.5d.shared::cluster.global.mbarrier::complete_tx::bytes.multicast::cluster"
        " [%9], [%6, {%5, %5, %7, %5, %10}], [%1], %11;\n"
        "@e mbarrier.arrive.expect_tx.shared::cta.b64 _, [%1], %8;\n}"
        :: "r"(dst), "r"(bar), "l"(ma), "r"(ka), "r"(mblk * 64), "r"(0), "l"(mb), "r"(kb), "n"(G1_STAGE_BYTES),
           "r"(dst + A_BYTES + (mblk & 1) * 16384), "r"((mblk & 1) * 4), "h"((uint16_t)3) : "memory");
}
__device__ __forceinline__ uint4 ldg_stream(const void* p, uint64_t pol) {
    uint4 v;
    asm volatile("ld.global.nc.L1::no_allocate.L2::cache_hint.v4.u32 {%0,%1,%2,%3}, [%4], %5;"
                 : "=r"(v.x), "=r"(v.y), "=r"(v.z), "=r"(v.w) : "l"(p), "l"(pol));
    return v;
}
__device__ __forceinline__ void st_tagged(void* p, float a, float b, uint32_t tag) {
    asm volatile("st.relaxed.gpu.global.v2.b32 [%0], {%1,%2};"
                 :: "l"(p), "r"((__float_as_uint(a) & ~3u) | tag), "r"((__float_as_uint(b) & ~3u) | tag) : "memory");
}
__device__ __forceinline__ void st_relaxed(unsigned* p, uint32_t v) {
    asm volatile("st.relaxed.gpu.global.b32 [%0], %1;" :: "l"(p), "r"(v) : "memory");
}
__device__ __forceinline__ bool untagged(const uint4& v, uint32_t tag) {
    return ((v.x ^ tag) | (v.y ^ tag) | (v.z ^ tag) | (v.w ^ tag)) & 3;
}
__device__ __forceinline__ uint4 ld_relaxed(const void* p) {
    uint4 v;
    asm volatile("ld.relaxed.gpu.global.v4.b32 {%0,%1,%2,%3}, [%4];" : "=r"(v.x), "=r"(v.y), "=r"(v.z), "=r"(v.w) : "l"(p) : "memory");
    return v;
}
__device__ __forceinline__ void prefetch_map(const CUtensorMap* m) {
    asm volatile("prefetch.tensormap [%0];" :: "l"(m) : "memory");
}
template <int N> __device__ __forceinline__ void wg_wait() { asm volatile("wgmma.wait_group.sync.aligned %0;" :: "n"(N) : "memory"); }

__device__ __forceinline__ uint32_t desc_a(uint32_t addr) { return (addr & 0x3FFFF) >> 4 | 1 << 16; }
__device__ __forceinline__ uint32_t desc_b(uint32_t addr) { return (addr & 0x3FFFF) >> 4 | 512 << 16; }

#define R8(d, o) "+f"(d[o]), "+f"(d[o+1]), "+f"(d[o+2]), "+f"(d[o+3]), "+f"(d[o+4]), "+f"(d[o+5]), "+f"(d[o+6]), "+f"(d[o+7])
#define R32(d, o) R8(d, o), R8(d, o+8), R8(d, o+16), R8(d, o+24)
#define R64(d, o) R32(d, o), R32(d, o+32)
#define ACC00 "%0,%1,%2,%3,%4,%5,%6,%7,%8,%9,%10,%11,%12,%13,%14,%15,%16,%17,%18,%19,%20,%21,%22,%23,%24,%25,%26,%27,%28,%29,%30,%31,"\
    "%32,%33,%34,%35,%36,%37,%38,%39,%40,%41,%42,%43,%44,%45,%46,%47"
#define ACC0 ACC00 ",%48,%49,%50,%51,%52,%53,%54,%55,%56,%57,%58,%59,%60,%61,%62,%63"
#define ACC1 "%64,%65,%66,%67,%68,%69,%70,%71,%72,%73,%74,%75,%76,%77,%78,%79,%80,%81,%82,%83,%84,%85,%86,%87,%88,%89,%90,%91,%92,%93,%94,%95,"\
    "%96,%97,%98,%99,%100,%101,%102,%103,%104,%105,%106,%107,%108,%109,%110,%111"
#define ACC48 "{" ACC00 "}"
#define ACC64 "{" ACC0 "}"
#define ACC112 "{" ACC0 "," ACC1 "}"
#define ACC128 "{" ACC0 "," ACC1 ",%112,%113,%114,%115,%116,%117,%118,%119,%120,%121,%122,%123,%124,%125,%126,%127}"
#define MMA_K16(shape, acc, a, b, keep, hb) \
    "mov.b64 da, {" a ", 0x40000040};\nmov.b64 db, {" b ", " hb "};\n" \
    "wgmma.mma_async.sync.aligned." shape ".f32.bf16.bf16 " acc ", da, db, " keep ", 1, 1, 0, 1;\n"
#define MMA_NEXT(op, a, b, sa, sb) op " " a ", " a ", " sa ";\n" op " " b ", " b ", " sb ";\n"
#define MMA_STEP_B(shape, acc, a, b, na, nb, keep, hb, sb) \
    "{\n.reg .pred p, q;\n.reg .b64 da, db;\nsetp.ne.b32 p, " keep ", 0;\nsetp.eq.b32 q, 0, 0;\nwgmma.fence.sync.aligned;\n" \
    MMA_K16(shape, acc, a, b, "p", hb) MMA_NEXT("xor.b32", a, b, "2", "128") MMA_K16(shape, acc, a, b, "q", hb) MMA_NEXT("add.s32", a, b, "2", sb) \
    MMA_K16(shape, acc, a, b, "q", hb) MMA_NEXT("xor.b32", a, b, "2", "128") MMA_K16(shape, acc, a, b, "q", hb) MMA_NEXT("add.s32", a, b, na, nb) \
    "wgmma.commit_group.sync.aligned;\n}"
#define MMA64(shape, acc, a, b, keep) "wgmma.mma_async.sync.aligned." shape ".f32.bf16.bf16 " acc ", " a ", " b ", " keep ", 1, 1, 0, 1;\n"
#define NEXT64(op, a, b, sa, sb) "mov.b64 {lo, hi}, " a ";\n" op " lo, lo, " sa ";\nmov.b64 " a ", {lo, hi};\n" \
    "mov.b64 {lo, hi}, " b ";\n" op " lo, lo, " sb ";\nmov.b64 " b ", {lo, hi};\n"
#define ADD64(op, a, b, sa, sb) "cvt.s64.s32 w, " sa ";\nadd.s64 " a ", " a ", w;\ncvt.s64.s32 w, " sb ";\nadd.s64 " b ", " b ", w;\n"
#define MMA_STEP(shape, acc, a, b, na, nb, keep) MMA_STEP_N(shape, acc, a, b, na, nb, keep, NEXT64)
#define MMA_STEP_N(shape, acc, a, b, na, nb, keep, LAST) \
    "{\n.reg .pred p, q;\n.reg .b32 lo, hi;\n.reg .b64 w;\nsetp.ne.b32 p, " keep ", 0;\nsetp.eq.b32 q, 0, 0;\nwgmma.fence.sync.aligned;\n" \
    MMA64(shape, acc, a, b, "p") NEXT64("xor.b32", a, b, "2", "128") MMA64(shape, acc, a, b, "q") NEXT64("add.s32", a, b, "2", "128") \
    MMA64(shape, acc, a, b, "q") NEXT64("xor.b32", a, b, "2", "128") MMA64(shape, acc, a, b, "q") LAST("add.s32", a, b, na, nb) \
    "wgmma.commit_group.sync.aligned;\n}"
#define MMA_ARGS64 "+l"(da), "+l"(db) : "r"(next / 16 - 6), "r"(next / 16 - 384), "r"(keep) : "memory"
#define MMA_ARGS "+r"(da), "+r"(db) : "r"(next / 16 - 6), "r"(next / 16 - 384), "r"(keep) : "memory"

__device__ __forceinline__ void mma_step(float (&d)[128], uint64_t& da, uint64_t& db, int next, int keep) {
    asm volatile(MMA_STEP("m64n256k16", ACC128, "%128", "%129", "%130", "%131", "%132") : R64(d, 0), R64(d, 64), MMA_ARGS64);
}
__device__ __forceinline__ void mma_rank(float (&d)[128], uint32_t a0, uint32_t a1, uint32_t db) {
    asm volatile("{\n.reg .pred q;\n.reg .b64 db;\nsetp.eq.b32 q, 0, 0;\nmov.b64 db, {%131, 0x40000040};\nwgmma.fence.sync.aligned;\n"
                 "wgmma.mma_async.sync.aligned.m64n256k16.f32.bf16.bf16 " ACC128 ", {%128, %129, %130, %130}, db, q, 1, 1, 1;\n}"
                 : R64(d, 0), R64(d, 64) : "r"(a0), "r"(a1), "r"(0), "r"(db) : "memory");
}
__device__ __forceinline__ void mma_step224(float (&d)[128], uint64_t& da, uint64_t& db, int next, int keep) {
    asm volatile(MMA_STEP("m64n224k16", ACC112, "%112", "%113", "%114", "%115", "%116")
                 : R64(d, 0), R32(d, 64), R8(d, 96), R8(d, 104), MMA_ARGS64);
}
__device__ __forceinline__ void mma_step(float (&d)[64], uint64_t& da, uint64_t& db, int next, int keep) {
    asm volatile(MMA_STEP("m64n128k16", ACC64, "%64", "%65", "%66", "%67", "%68") : R64(d, 0), MMA_ARGS64);
}
__device__ __forceinline__ void mma_step_c(float (&d)[64], uint64_t& da, uint64_t& db, int next, int keep) {
    asm volatile(MMA_STEP_N("m64n128k16", ACC64, "%64", "%65", "%66", "%67", "%68", ADD64) : R64(d, 0), MMA_ARGS64);
}
__device__ __forceinline__ void mma_step96(float (&d)[64], uint64_t& da, uint64_t& db, int next, int keep) {
    asm volatile(MMA_STEP("m64n96k16", ACC48, "%48", "%49", "%50", "%51", "%52") : R32(d, 0), R8(d, 32), R8(d, 40), MMA_ARGS64);
}
__device__ __forceinline__ void mma_step_tail(float (&d)[128], uint32_t da, uint32_t b, int keep) {
    uint32_t db = (b & 0x3FFFF) >> 4 | 256 << 16;
    const int next = 0;
    asm volatile(MMA_STEP_B("m64n256k16", ACC128, "%128", "%129", "%130", "%131", "%132", "0x80000040", "-96")
                 : R64(d, 0), R64(d, 64), MMA_ARGS);
}

__device__ __forceinline__ uint32_t pack_bf16(float lo, float hi) {
    uint32_t r; asm("cvt.rn.bf16x2.f32 %0, %1, %2;" : "=r"(r) : "f"(hi), "f"(lo)); return r;
}
__device__ __forceinline__ float bf_lo(uint32_t v) { return __uint_as_float(v << 16); }
__device__ __forceinline__ float bf_hi(uint32_t v) { return __uint_as_float(v & 0xffff0000u); }
__device__ __forceinline__ float round_bf16(float v) { return bf_lo(pack_bf16(v, 0.f)); }
__device__ __forceinline__ uint32_t mul_bf16x2(uint32_t a, uint32_t b) {
    uint32_t r; asm("mul.rn.bf16x2 %0, %1, %2;" : "=r"(r) : "r"(a), "r"(b)); return r;
}
__device__ __forceinline__ uint32_t sub_bf16x2(uint32_t a, uint32_t b) {
    uint32_t r; asm("sub.rn.bf16x2 %0, %1, %2;" : "=r"(r) : "r"(a), "r"(b)); return r;
}
__device__ __forceinline__ uint32_t mul2_bf16x2(uint32_t a, uint32_t hi, uint32_t lo) {
    uint32_t r; asm("fma.rn.bf16x2 %0, %1, %2, %3;" : "=r"(r) : "r"(a), "r"(hi), "r"(mul_bf16x2(a, lo))); return r;
}
__device__ __forceinline__ float tanh_fast(float x) { float r; asm("tanh.approx.f32 %0, %1;" : "=f"(r) : "f"(x)); return r; }
__device__ __forceinline__ float gelu_twice(float g) {
    return fmaf(g, tanh_fast(fmaf(g * g, 0.044715f * 0.7978845608f, 0.7978845608f) * g), g);
}
__device__ __forceinline__ uint32_t geglu2(uint32_t g2, uint32_t u2) {
    return mul_bf16x2(pack_bf16(gelu_twice(bf_lo(g2)), gelu_twice(bf_hi(g2))), u2);
}
__device__ __forceinline__ uint32_t silu2(float lo, float hi) {
    const uint32_t h = mul_bf16x2(pack_bf16(lo, hi), 0x3e803e80u);
    return pack_bf16(fmaf(bf_lo(h), tanh_fast(bf_lo(h)), bf_lo(h)), fmaf(bf_hi(h), tanh_fast(bf_hi(h)), bf_hi(h)));
}
__device__ __forceinline__ float ex2_fast(float x) { float r; asm("ex2.approx.ftz.f32 %0, %1;" : "=f"(r) : "f"(x)); return r; }
__device__ __forceinline__ void unpack8(uint4 v, float (&f)[8]) {
    f[0] = bf_lo(v.x); f[1] = bf_hi(v.x); f[2] = bf_lo(v.y); f[3] = bf_hi(v.y);
    f[4] = bf_lo(v.z); f[5] = bf_hi(v.z); f[6] = bf_lo(v.w); f[7] = bf_hi(v.w);
}
template <int N> __device__ __forceinline__ void fence_regs(float (&d)[N]) {
#pragma unroll
    for (int i = 0; i < N; i++) asm volatile("" : "+f"(d[i]) :: "memory");
}

__device__ __forceinline__ float rcp_fast(float x) { float r; asm("rcp.approx.ftz.f32 %0, %1;" : "=f"(r) : "f"(x)); return r; }
__device__ __forceinline__ float sqrt_fast(float x) { float r; asm("sqrt.approx.ftz.f32 %0, %1;" : "=f"(r) : "f"(x)); return r; }
__device__ __forceinline__ uint32_t max_bf16x2(uint32_t a, uint32_t b) {
    uint32_t r; asm("max.bf16x2 %0, %1, %2;" : "=r"(r) : "r"(a), "r"(b)); return r;
}
__device__ __forceinline__ uint32_t transpose8(uint32_t a) {
    uint32_t r; asm volatile("movmatrix.sync.aligned.m8n8.trans.b16 %0, %1;" : "=r"(r) : "r"(a)); return r;
}
__device__ __forceinline__ void mma_sync(uint32_t* d, const uint32_t* a, uint32_t b0, uint32_t b1, const uint32_t* c) {
    asm volatile("mma.sync.aligned.m16n8k16.row.col.f32.bf16.bf16.f32 {%0,%1,%2,%3}, {%4,%5,%6,%7}, {%8,%9}, {%10,%11,%12,%13};"
        : "=r"(d[0]), "=r"(d[1]), "=r"(d[2]), "=r"(d[3])
        : "r"(a[0]), "r"(a[1]), "r"(a[2]), "r"(a[3]), "r"(b0), "r"(b1), "r"(c[0]), "r"(c[1]), "r"(c[2]), "r"(c[3]));
}
template <int N> struct Floats {
    float f[N];
    __device__ __forceinline__ Floats() {}
    __device__ __forceinline__ Floats(const uint32_t* p) {
#pragma unroll
        for (int i = 0; i < N; i++) asm("mov.b32 %0, %1;" : "=f"(f[i]) : "r"(p[i]));
    }
    __device__ __forceinline__ void put(uint32_t* p) const {
#pragma unroll
        for (int i = 0; i < N; i++) asm("mov.b32 %0, %1;" : "=r"(p[i]) : "f"(f[i]));
    }
    __device__ __forceinline__ float& operator[](int i) { return f[i]; }
};
__device__ __forceinline__ uint32_t fresh_tid() { uint32_t r; asm volatile("mov.u32 %0, %%tid.x;" : "=r"(r)); return r; }
template <typename T> __device__ __forceinline__ T uniform(T v) { return __shfl_sync(0xffffffffu, v, 0); }

__device__ __forceinline__ uint32_t forecast(uint32_t n0, uint32_t c0, float cycles, uint32_t tag) {
    const uint32_t n = nanos();
    return n + (int)((n - n0) * cycles * rcp_fast((uint32_t)clock() - c0)) & ~3u | tag;
}
__device__ __forceinline__ uint32_t plan_word(uint32_t base, int lane) { return uniform(lds32(base + PLAN_OFF + lane * 4)); }

__device__ __forceinline__ void fold_operands(const Params& prm, uint32_t base, int slot, int mblk, uint32_t tag, int w, int lane) {
    uint4 v[9];
#pragma unroll
    for (int m = 0; m < 9; m++) v[m] = make_uint4(0, 0, 0, 0);
    const float* parts = prm.colsum + (slot * 2 + (lane >> 4)) * 1024 + w * 64 + (lane & 15) * 4;
    const float* const rows = &prm.stats[mblk * 128 + w * 64 + lane * 2].x;
#pragma unroll 1
    for (int spins = 0; spins < (1 << 16); spins++) {
        bool missing = false;
        asm volatile("" : "+l"(parts));
#pragma unroll
        for (int m = 0; m < 9; m++) {
            if (untagged(v[m], tag)) {
                missing = true;
                v[m] = ld_relaxed(m < 8 ? parts + m * 128 : rows);
            }
        }
        if (!missing) break;
    }
    float4 c = make_float4(0.f, 0.f, 0.f, 0.f);
#pragma unroll
    for (int m = 0; m < 8; m++) {
        c.x += __uint_as_float(v[m].x ^ tag); c.y += __uint_as_float(v[m].y ^ tag);
        c.z += __uint_as_float(v[m].z ^ tag); c.w += __uint_as_float(v[m].w ^ tag);
    }
    sts128(base + STAT_OFF + w * 512 + lane * 16, make_uint4(v[8].x ^ tag, v[8].y ^ tag, v[8].z ^ tag, v[8].w ^ tag));
    const uint32_t ca = base + AUX_OFF + w * 8192 + (lane >> 4) * 16384 + (lane & 15) * 8;
#pragma unroll
    for (int r = 0; r < 3; r++) {
        const uint32_t lo = pack_bf16(c.x, c.y), hi = pack_bf16(c.z, c.w);
        sts64f((ca ^ r * 16) + r * 128, __uint_as_float(lo), __uint_as_float(hi));
        c.x -= bf_lo(lo); c.y -= bf_hi(lo); c.z -= bf_lo(hi); c.w -= bf_hi(hi);
    }
    asm volatile("fence.proxy.async.shared::cta;" ::: "memory");
    __syncwarp();
}
__device__ __forceinline__ float2 fold(float (&acc)[128], uint32_t base, int wg) {
    const uint32_t id = fresh_tid(), sp = base + STAT_OFF + (id & 96) * 8 + (id & 28) * 4 + wg * 8;
    const uint32_t sel = id & 2 ? 0x4444 : (id & 1 ? 0x4432 : 0x3232);
    const float2 sa = lds64f(sp), sb = lds64f(sp + 128);
    mma_rank(acc, __byte_perm(__float_as_uint(sa.x), 0, sel), __byte_perm(__float_as_uint(sb.x), 0, sel), desc_b(base + AUX_OFF));
    return make_float2(sa.y, sb.y);
}

__device__ __forceinline__ void tail_gemm(const Params& prm, uint32_t base, uint32_t t0, unsigned epoch, int grp, int warp, int lane) {
    const uint32_t full = base + BAR_OFF, empty = full + 32, sig = full + 192, dep = full + 256, folded = full + 320;
    const uint32_t tag = 1 + (epoch & 1);
    auto plan = [&](uint32_t p, uint32_t word) { return p < 4 ? p * 64 + grp / 2 * 32 + 15 : word >> p % 4 * 8 & 255; };
    auto rows = [&](uint32_t job) { return job / 32 * 2 + grp % 2; };
    if (warp == 8) {
        if (elect_one()) { prefetch_map(&prm.xn); prefetch_map(&prm.a2); prefetch_map(&prm.wd_tail); }
#pragma unroll 1
        for (int p = 0, i = G1_STAGES; p < 8; p++) {
            const bool first = p < 4;
            if (p == 4) mbar_wait_warp(dep + 16, 0);
            const uint32_t job = plan(p, plan_word(base, lane));
#pragma unroll 1
            for (int k = p ? 0 : G1_STAGES; k <= job % 32; k++, i++) {
                if (WDPF && p == 3 && k % 2 == grp / 2)
                    asm volatile("{\n.reg .pred e;\nelect.sync _|e, 0xffffffff;\n"
                        "@e cp.async.bulk.prefetch.tensor.5d.L2.global [%0, {%2, %2, %1, %2, %3}];\n}"
                        :: "l"(&prm.wd_tail), "r"(k * 8), "r"(0), "r"(grp % 2 * 4) : "memory");
                if (i == 16 || i == 24 || k == 16) mbar_wait_warp(dep + (first ? i & 8 : 24), 0);
                TRACE_S(62, i, 16); TRACE_S(63, i, 4);
                mbar_wait_warp(empty + (i & 3) * 8, ~i >> 2 & 1);
                load_tail(base + (i & 3) * G1_STAGE_BYTES, full + (i & 3) * 8, first ? (p ? &prm.xn : &prm.x) : &prm.a2,
                          first ? &prm.wu_tail : &prm.wd_tail, (first ? 0 : DM) + k * 64, rows(job), first ? k * 2 : k * 8);
            }
        }
        return;
    }
    if (warp == 9) {
        const uint32_t n0 = nanos(), c0 = clock();
#pragma unroll 1
        for (int j = 0; j < 3; j++) {
            flag_wait<true>(prm.flags + (F_LN + j) * 512 + (j < 2 ? lane % 4 * 4 + grp : lane % 16) * 32, epoch * CNT_LN);
            fence_proxy_async();
            __syncwarp();
            if (lane == 0 && j < 2) mbar_arrive(dep + j * 8);
        }
        mbar_wait_warp(sig + 8, 0);
        if (lane == 0) st_relaxed(prm.flags + F_PACE * 512 + 64 + grp, forecast(n0, c0, DUE, tag));
        uint4 v, w;
#pragma unroll 1
        for (int spins = 0; spins < (1 << 19); spins++) {
            v = ld_relaxed(prm.flags + F_PACE * 512 + lane / 2 * 4);
            w = ld_relaxed(prm.flags + F_PACE * 512 + 64);
            if (!__any_sync(0xffffffffu, untagged(v, tag) || untagged(w, tag))) break;
            __nanosleep(256);
        }
        const uint32_t ref = uniform(v.x);
        const int due = min(max((int)((grp & 2 ? w.z : w.x) - ref), -100000), 100000) * 8;
        int late = max(max((int)(v.x - ref), (int)(v.y - ref)), max((int)(v.z - ref), (int)(v.w - ref)));
        late = min(max(max(late, __shfl_xor_sync(0xffffffffu, late, 2)), -100000), 100000) * 8 * BAL + lane / 4 + lane / 24 * BIAS * 8;
        TRACE_PUT(16 + lane / 4, late + (1 << 20));
        int place = 0, n = SHARE_MIN;
#pragma unroll 1
        for (int g = 0; g < 32; g += 4) place += __shfl_sync(0xffffffffu, late, g) > late;
        const bool swap = SWAP && (__reduce_add_sync(0xffffffffu, place + 1 & 2 ? late : -late) ^ w.x - w.z) >> 31;
        const bool mine = (place + 1 >> 1 & 1 ^ swap) == grp / 2;
#pragma unroll 1
        for (int j = 4 * SHARE_MIN; j < SHARE_SUM; j++) {
            const int most = __reduce_max_sync(0xffffffffu, mine && n < SHARE_MAX ? late : INT_MIN);
            if (j >= TLO && due + (j - 38) * 640 * 8 > most) break;
            if (j == 38) TRACE_PUT(32, most - due + (1 << 20));
            if (most == late) { n++; late -= STEPNS * 8; }
        }
        auto first = [](uint32_t bits, int n) { return bits & (1u << min(max(n, 0), 24)) - 1; };
        const uint32_t job = lane / 4 * 32 + n - 1;
        if (mine) st_relaxed(prm.flags + F_SHARE * 512 + rows(job) * 32,
                             epoch << 24 | first(0x2aaaaa, 2 * n) | first(0x104104, 6 * n - 66) | first(0x10410, 6 * n - 90) |
                             first(0x41041, 6 * n - 108));
        if (mine) TRACE_PUT(24 + lane / 4, n);
        sts32(base + PLAN_OFF, __reduce_or_sync(0xffffffffu, mine ? job << place / 2 * 8 : 0));
        if (lane == 0) mbar_arrive(dep + 16);
        flag_wait<true>(prm.flags + F_SECOND * 512 + lane % 16 * 32, epoch * CNT_LN);
        fence_proxy_async();
        __syncwarp();
        if (lane == 0) mbar_arrive(dep + 24);
        return;
    }
    if (warp > 9) {
#pragma unroll 1
        for (int j = 0; j < 8; j++) sts128(base + AUX_OFF + (warp - 10) * 8192 + (j & 4) * 4096 + (j & 3) * 512 + lane * 16, make_uint4(0, 0, 0, 0));
        while ((uint32_t)clock() - t0 < 9000) __nanosleep(256);
        fold_operands(prm, base, 8, grp, tag, warp - 10, lane);
        if (lane) return;
        mbar_arrive(folded);
        if (warp == 11) return;
        TRACE(60);
#pragma unroll 1
        for (int p = 0; p < 8; p++) {
            mbar_wait(sig + p * 8, 0);
            flag_add(prm.flags + (p < 4 ? F_EARLY : F_TAIL2) * 512 + rows(plan(p, lds32(base + PLAN_OFF))) * 32);
            TRACE_S(50, p, 3); TRACE_S(51, p, 7);
        }
        prm.epoch[blockIdx.x * 16] = epoch;
        TRACE_DUMP();
        return;
    }
    asm volatile("setmaxnreg.inc.sync.aligned.u32 %0;" :: "n"(CONSUMER_REGS) : "memory");
    const uint32_t da = desc_a(base + (warp >> 2) * 8192);
    uint4* out = prm.tail;
    float acc[128];
    uint32_t pk[64];
    float2 inv = make_float2(0.f, 0.f);
    int i = 0, last;
    uint32_t peer;
    asm volatile("mapa.shared::cluster.u32 %0, %1, %2;" : "=r"(peer) : "r"(empty), "r"(lane & 1));
    auto release = [&]() {
        if ((threadIdx.x & 126) == 0 && i <= last)
            asm volatile("mbarrier.arrive.shared::cluster.b64 _, [%0];" :: "r"(peer + (i - 1 & 3) * 8) : "memory");
    };
    auto store = [&](int j) {
        asm volatile("st.global.v4.u32 [%0], {%1,%2,%3,%4};" :: "l"(out + j / 2 * 8192 + j % 2 * 256),
                     "r"(pk[4 * j]), "r"(pk[4 * j + 1]), "r"(pk[4 * j + 2]), "r"(pk[4 * j + 3]) : "memory");
    };
    auto step = [&](int k, int left, int most) {
        mbar_wait(full + (i & 3) * 8, i >> 2 & 1);
        TRACE_S(45, warp * 128 + i, 0);
        if (warp >= 4 && left == (SMIN < 3 ? min(TSK, most) : TSK)) asm volatile("bar.sync 1, 256;" ::: "memory");
        mma_step_tail(acc, da + (i & 3) * (G1_STAGE_BYTES / 16), base + A_BYTES + (i & 3) * G1_STAGE_BYTES, k);
        if (warp < 4 && left == 1) asm volatile("bar.arrive 1, 256;" ::: "memory");
    };
    auto drip = [&](int p, int& n) {
        if (n > 0) { store(0); store(1); }
#pragma unroll
        for (int j = 8; j < 64; j++) asm volatile("mov.b32 %0, %1;" : "=r"(pk[j - 8]) : "r"(pk[j]));
        out += 8192;
        __syncwarp();
        if (--n == 0 && lane == 0) mbar_arrive(sig + p * 8 - 8);
    };
#pragma unroll
    for (int j = 0; j < 128; j++) asm volatile("mov.b32 %0, 0;" : "=f"(acc[j]));
#pragma unroll
    for (int j = 0; j < 64; j++) asm volatile("mov.b32 %0, 0;" : "=r"(pk[j]));
#pragma unroll 1
    for (int p = 0; p < 8; p++) {
        step(0, 0, 1);
        i++;
        const uint32_t word = plan_word(base, lane), job = plan(p, word);
        last = __dp4a(word & 0x1f1f1f1fu, 0x01010101u, 4u * G1_KSTEPS);
#pragma unroll 1
        for (int left = job % 32, n = p ? 8 : 0; left > 0; left--) {
            if (i == G1_KSTEPS - TFOLD) { mbar_wait(folded, 0); inv = fold(acc, base, warp >> 2); }
#pragma unroll 1
            do drip(p, n); while (n & 7 >> 31 - __clz(job % 32));
            step(1, left, job % 32);
            wg_wait<1>();
            release();
            i++;
        }
        wg_wait<0>();
        fence_regs(acc);
        release();
        if (p == 0) {
#pragma unroll
            for (int j = 0; j < 128; j++) acc[j] *= j & 2 ? inv.y : inv.x;
            fence_regs(acc);
        }
        if (warp == 4) TRACE_PUT(46 + p + p / 4 * 3, (uint32_t)clock());
#pragma unroll
        for (int j = 0; j < 64; j++) pk[j] = pack_bf16(acc[2 * j], acc[2 * j + 1]);
        out = prm.tail + p / 4 * NGEMM * 512 + rows(job) * 512 + threadIdx.x;
    }
#pragma unroll
    for (int j = 0; j < 16; j++) store(j);
    __syncwarp();
    TRACE_S(58, warp, 4);
    if (lane == 0) mbar_arrive(sig + 56);
}

__device__ __forceinline__ int gate_col(int t, int nslot) { return t == 2 ? 960 + nslot * 64 : max(t * 1024 - 1536, 0) + nslot * 128; }

struct Role {
    int rank, role, mblk, nslot;
    __device__ __forceinline__ Role() {
        uint32_t id;
        asm volatile("mov.u32 %0, %%ctaid.x;" : "=r"(id));
        const uint32_t cl = id / 2;
        rank = id & 1;
        role = pick(cl < 4, 32 + cl * 8, cl - 8 + max(4u, (cl - 1) * 37 >> 8)) * 2 + rank;
        mblk = role & 15; nslot = role >> 4;
    }
};

__global__ void __cluster_dims__(2, 1, 1) __launch_bounds__(384, 1)
fused_kernel(const __grid_constant__ Params prm) {
    TRACE_GET(c0);
    const uint32_t base = smem_u32(smem_raw) & ~1023u;
    const uint32_t bars = base + BAR_OFF;
    auto full1 = [&](int s) { return bars + s * 8; };
    auto empty1 = [&](int s) { return bars + 32 + s * 8; };
    auto full2 = [&](int s) { return bars + 64 + s * 8; };
    auto empty2 = [&](int s) { return bars + 128 + s * 8; };
    const uint32_t sig_bar = bars + 192, dep_bar = bars + 256, cs_bar = bars + 304, fold_bar = bars + 320, x_bar = bars + 352;
    const uint32_t halo_bar = dep_bar + 32;
    auto stage2 = [&](int q) { return base + q * G2_STAGE_BYTES; };
    const uint32_t aux = base + AUX_OFF;

    asm volatile("{\n.reg .pred p;\nsetp.eq.u32 p, %1, 0;\n@p mbarrier.init.shared::cta.b64 [%0], 1;\n"
        "fence.mbarrier_init.release.cluster;\nbarrier.cluster.arrive.relaxed.aligned;\n}" :: "r"(bars), "r"(threadIdx.x) : "memory");
    const int warp = __shfl_sync(0xffffffffu, threadIdx.x >> 5, 0);
    auto cluster_wait = []() { asm volatile("barrier.cluster.wait.acquire.aligned;" ::: "memory"); };
    if ((warp | (blockIdx.x & NGEMM)) == 8) {
        const Role r;
        asm volatile("{\n.reg .pred e;\nelect.sync _|e, 0xffffffff;\n"
            "@e prefetch.tensormap [%0];\n@e prefetch.tensormap [%1];\n}" :: "l"(&prm.x), "l"(&prm.wg + r.rank) : "memory");
        cluster_wait();
        load_stage1(base, base + A_BYTES + r.rank * 16384, full1(0), &prm.x, &prm.wg + r.rank, &prm.wg + r.rank, 0, r.mblk * 64,
                    r.nslot * 128, r.nslot * 128 + 64, 0, stream_policy());
    } else {
        cluster_wait();
    }
    const uint32_t t0 = clock();
    if (TEARLY) {
        uint32_t cta;
        asm volatile("mov.u32 %0, %%ctaid.x;" : "=r"(cta));
        if ((warp | (~cta & NGEMM)) == TEW) load_tail(base, full1(0), &prm.x, &prm.wu_tail, 0, cta - NGEMM, 0);
    }
    asm volatile("{\n.reg .pred e, q;\nelect.sync _|e, 0xffffffff;\nsetp.ne.and.u32 q, %2, 0, e;\n"
        "@q mbarrier.init.shared::cta.b64 [%0], %1;\n@e mbarrier.init.shared::cta.b64 [%0 + 8], %1;\n"
        "@e mbarrier.init.shared::cta.b64 [%0 + 16], %1;\n@e mbarrier.init.shared::cta.b64 [%0 + 24], %1;\n"
        "fence.mbarrier_init.release.cluster;\nbarrier.cluster.arrive.relaxed.aligned;\n}"
        :: "r"(bars + warp * 32), "r"(1 << (0x10fa08 >> warp * 2 & 3)), "r"(warp) : "memory");
    const int lane = threadIdx.x & 31;
    const Role me;
    const int rank = me.rank, role = me.role, mblk = me.mblk, nslot = me.nslot;
    const CUtensorMap* const w0 = &prm.wg + rank;

    unsigned* const flags = prm.flags + mblk * 32;
    if (warp >= 8) {
        asm volatile("setmaxnreg.dec.sync.aligned.u32 %0;" :: "n"(AUX_REGS));
        if (warp == 9) { TRACE_CLEAR(); TRACE_GT(0); TRACE_PUT(1, c0); }
        if ((warp | (~blockIdx.x & NGEMM)) == 8) {
#pragma unroll 1
            for (int i = TEARLY; i < G1_STAGES; i++) {
                if (i == 1) cluster_wait();
                TRACE_S(57, i, 1);
                load_tail(base + i * G1_STAGE_BYTES, full1(i), &prm.x, &prm.wu_tail, i * 64, blockIdx.x - NGEMM, i * 2);
            }
        } else {
            cluster_wait();
        }
    }

    if (blockIdx.x >= NGEMM) {
        if (warp < 8) cluster_wait();
        const uint32_t seen = __ldcg(prm.epoch + blockIdx.x * 16);
        tail_gemm(prm, base, t0, seen + 1, blockIdx.x - NGEMM, warp, lane);
    } else if (warp == 9) {
        const unsigned epoch = __ldcg(prm.epoch + blockIdx.x * 16 + 2) + 1;
        const uint32_t n0 = nanos(), c1 = clock();
        {
            const __nv_bfloat16* const w = prm.pwu + ((mblk >> 1) * 128 + lane / 2) * DF + gate_col(4, nslot) + 96 + rank * 16 + lane % 2 * 8;
            uint4 v[8];
            float cs[8], f[8];
            mbar_wait(empty1(C2AT & 3), 0);
            if (C2AT > 3) mbar_wait(empty1(C2AT & 3), 1);
#pragma unroll
            for (int j = 0; j < 8; j++) v[j] = __ldg(reinterpret_cast<const uint4*>(w + j * 16 * DF));
            unpack8(v[0], cs);
#pragma unroll
            for (int j = 1; j < 8; j++) {
                unpack8(v[j], f);
#pragma unroll
                for (int d = 0; d < 8; d++) cs[d] += f[d];
            }
#pragma unroll
            for (int d = 0; d < 4; d++)
                cs[d] = (lane & 16 ? cs[d + 4] : cs[d]) + __shfl_xor_sync(0xffffffffu, lane & 16 ? cs[d] : cs[d + 4], 16);
#pragma unroll
            for (int d = 0; d < 2; d++) {
                cs[d] = (lane & 8 ? cs[d + 2] : cs[d]) + __shfl_xor_sync(0xffffffffu, lane & 8 ? cs[d] : cs[d + 2], 8);
                cs[d] += __shfl_xor_sync(0xffffffffu, cs[d], 4);
                cs[d] += __shfl_xor_sync(0xffffffffu, cs[d], 2);
            }
            if (!(lane & 6))
                st_tagged(prm.colsum + (16 + nslot / 4) * 1024 + (mblk >> 1) * 128 + nslot % 4 * 32 + rank * 16 + lane % 2 * 8 + (lane >> 3) * 2,
                          cs[0], cs[1], 1 + (epoch & 1));
            TRACE(61);
        }
        if (lane == 0) {
            mbar_wait(sig_bar, 0);
            TRACE(11);
            flag_add(flags + F_LN * 512);
            TRACE(42);
            flag_wait(flags + F_LN * 512, epoch * CNT_LN);
            fence_proxy_async();
            mbar_arrive(dep_bar);
            mbar_wait(sig_bar + 56, 0);
            flag_add(flags + F_LN2 * 512);
            flag_wait(flags + F_LN2 * 512, epoch * CNT_LN);
            fence_proxy_async();
            mbar_arrive(dep_bar + 40);
            TRACE(59);
            prm.epoch[blockIdx.x * 16 + 2] = epoch;
#pragma unroll 1
            for (int p = 3; p < 7; p++) {
                mbar_wait(sig_bar + (p == 3 ? 16 : p * 8), 0);
                TRACE_S(37, p, 4);
                flag_add(flags + (p - (p < F_EARLY)) * 512);
                TRACE_S(43, p, 4);
                if (p == 3 && rank == 0) {
                    mbar_wait(sig_bar + 24, 0);
                    st_relaxed(prm.flags + F_PACE * 512 + mblk * 4 + nslot, forecast(n0, c1, REST, 1 + (epoch & 1)));
                }
            }
        }
    } else if (warp < 8) {
        asm volatile("setmaxnreg.inc.sync.aligned.u32 %0;" :: "n"(CONSUMER_REGS));
        const int wg = __shfl_sync(0xffffffffu, threadIdx.x >> 7, 0);
        const int cw = threadIdx.x >> 5;
        const int tid = threadIdx.x & 127;
        int spins = 1 << 18;
        float acc[128];
        uint32_t pk[64];
#pragma unroll
        for (int i = 0; i < 64; i++) asm volatile("mov.b32 %0, 0;" : "=r"(pk[i]));
#pragma unroll
        for (int i = 0; i < 128; i++) asm volatile("mov.b32 %0, 0;" : "=f"(acc[i]));
        cluster_wait();

        auto row0 = [&](uint32_t id) { return mblk * 128 + (id & 96) + wg; };
        __nv_bfloat16* optr = prm.pxn + (mblk * 128 + nslot * 16 + cw * 2) * DM + lane * 8;
        uint64_t da = desc_a(base + wg * 8192) | (uint64_t)prm.hi[0] << 32, db = desc_b(base + A_BYTES) | (uint64_t)prm.hi[1] << 32;
        auto next1 = [](int s) { return ((s + 1) % G1_STAGES - s) * G1_STAGE_BYTES; };
        auto next2 = [](int q) { return ((q + 1) % G2_STAGES - q) * G2_STAGE_BYTES; };
        uint32_t peer_bars;
        asm volatile("mapa.shared::cluster.u32 %0, %1, %2;" : "=r"(peer_bars) : "r"(bars), "r"(tid & 1));
        if (tid >= 2) peer_bars = 0;
        auto release = [&](uint32_t bar) {
            if (peer_bars) asm volatile("mbarrier.arrive.shared::cluster.b64 _, [%0];" :: "r"(peer_bars + (bar - bars)) : "memory");
        };
        auto up = [](int i) { return 32 + (i & 24) + (i & 3) * 2 + (i >> 2 & 1); };
        auto store_pk = [&](__nv_bfloat16* p, int j) {
            asm volatile("st.global.v4.u32 [%0], {%1,%2,%3,%4};"
                         :: "l"(p), "r"(pk[4 * j]), "r"(pk[4 * j + 1]), "r"(pk[4 * j + 2]), "r"(pk[4 * j + 3]) : "memory");
        };
        auto chunk_geglu = [&](int j) {
#pragma unroll
            for (int i = 4 * j; i < 4 * j + 4; i++) pk[i] = geglu2(pk[i], pk[up(i)]);
            store_pk(optr + (j & 1) * 16 * K2 + (j >> 1) * 32, j);
        };
        auto signal_stores = [&](int p) { __syncwarp(); if (lane == 0) mbar_arrive(sig_bar + p * 8); };

        auto chunk_ln = [&](int k) {
            Floats<6> mo(pk + 32);
            if (k == 0) {
                const uint4* xp = reinterpret_cast<const uint4*>(prm.px + (optr - prm.pxn));
                pk[38] = __ldcg(prm.epoch + blockIdx.x * 16 + 2);
#pragma unroll
                for (int i = 0; i < 8; i++) {
                    const uint4 v = ldg_stream(xp + i * 32, stream_policy());
                    pk[4 * i] = v.x; pk[4 * i + 1] = v.y; pk[4 * i + 2] = v.z; pk[4 * i + 3] = v.w;
                }
            } else if (k >= LN_STEP && k < LN_STEP + 3) {
                if (k == LN_STEP) {
                    mo[0] = bf_lo(uniform(pk[0])); mo[1] = bf_lo(uniform(pk[16]));
                    mo[2] = mo[3] = mo[4] = mo[5] = 0.f;
                }
#pragma unroll
                for (int i = (k - LN_STEP) * 11; i < (k - LN_STEP) * 11 + 11 && i < 32; i++) {
                    const int r = i & 1;
                    const uint32_t w = pk[r * 16 + i / 2];
                    const float lo = bf_lo(w) - mo[r], hi = bf_hi(w) - mo[r];
                    mo[2 + r] += lo + hi;
                    mo[4 + r] = fmaf(hi, hi, fmaf(lo, lo, mo[4 + r]));
                }
                mo.put(pk + 32);
            } else if (k == LN_STEP + 3) {
                const bool second = lane & 16;
                float m1 = (second ? mo[3] : mo[2]) + __shfl_xor_sync(0xffffffffu, second ? mo[2] : mo[3], 16);
                float m2 = (second ? mo[5] : mo[4]) + __shfl_xor_sync(0xffffffffu, second ? mo[4] : mo[5], 16);
#pragma unroll
                for (int o = 8; o > 0; o >>= 1) {
                    m1 += __shfl_xor_sync(0xffffffffu, m1, o);
                    m2 += __shfl_xor_sync(0xffffffffu, m2, o);
                }
                m1 *= 1.f / DM;
                const float var = fmaxf(fmaf(-m1, m1, m2 * (1.f / DM)), 0.f);
                const float mean = round_bf16((second ? mo[1] : mo[0]) + m1);
                const float inv = rcp_fast(round_bf16(sqrt_fast(round_bf16(round_bf16(var) + 1e-5f))));
                if ((lane & 15) == 0) st_tagged(prm.stats + (uint32_t)(optr - prm.pxn) / DM + second, -mean, inv, 2 - (pk[38] & 1));
                const uint32_t split = pack_bf16(inv - round_bf16(inv), inv);
#pragma unroll
                for (int r = 0; r < 2; r++) {
                    const uint32_t f = __shfl_sync(0xffffffffu, split, r * 16);
                    pk[32 + 3 * r] = __byte_perm(__shfl_sync(0xffffffffu, __float_as_uint(mean), r * 16), 0, 0x3232);
                    pk[33 + 3 * r] = __byte_perm(f, 0, 0x3232);
                    pk[34 + 3 * r] = __byte_perm(f, 0, 0x1010);
                }
            } else if (k >= LN_STEP + 4 && k < LN_STEP + 8) {
#pragma unroll
                for (int i = k - LN_STEP - 4; i < 8; i += 4) {
                    const uint32_t* n = pk + 32 + i / 4 * 3;
#pragma unroll
                    for (int j = 4 * i; j < 4 * i + 4; j++) pk[j] = mul2_bf16x2(sub_bf16x2(pk[j], n[0]), n[1], n[2]);
                    store_pk(optr + i * 256, i);
                }
                if (k == LN_STEP + 5 || k == LN_STEP + 7) signal_stores(k == LN_STEP + 5 ? 0 : 7);
            } else if (k == FOLD_STEP) {
                mbar_wait(fold_bar, 0, spins);
                const float2 inv = fold(acc, base, wg);
                mo[0] = inv.x; mo[1] = inv.y;
                mo.put(pk + 32);
            }
        };

        auto halo = [&]() { const uint32_t id = fresh_tid(); return aux + (id & 96) * 128 + (id & 128) * 16 + (id & 31) * 4; };
        auto put = [&](uint32_t a, uint32_t v0, uint32_t v1) {
            asm volatile("st.shared.u32 [%0], %1;\nst.shared.u32 [%0 + 128], %2;" :: "r"(a + HALO_BYTES), "r"(v0), "r"(v1) : "memory");
        };
        auto get = [&](uint32_t a, uint32_t& v0, uint32_t& v1) {
            asm volatile("ld.shared.u32 %0, [%2];\nld.shared.u32 %1, [%2 + 128];" : "=r"(v0), "=r"(v1) : "r"(a) : "memory");
        };
        auto publish = [&](int p) { asm volatile("fence.proxy.async.shared::cta;" ::: "memory"); signal_stores(p); };
        const uint32_t zero[4] = {0, 0, 0, 0};
        auto meet = [&](int n, int k, uint32_t id) {
            if (n == 15 - MEET)
                asm volatile("{\n.reg .b32 c;\nmov.u32 c, %%clock;\nbar.arrive %1, 256;\nlop3.b32 %0, %0, c, 1, 0x70;\n}"
                             : "+r"(peer_bars) : "r"(2 + id / 128) : "memory");
            if (n == 15) {
                asm volatile("{\n.reg .b32 c;\nmov.u32 c, %%clock;\nbar.sync %1, 256;\nlop3.b32 %0, %0, c, 1, 0x70;\n}"
                             : "+r"(peer_bars) : "r"(3 - id / 128) : "memory");
                mma_step(acc, da, db, next1(k & 3), k);
                asm volatile("// batch step");
            }
        };
        auto mix_qk = [&]() {
            uint32_t c[2][4];
            const uint32_t a = halo(), id = fresh_tid();
            if (EREL) { wg_wait<0>(); release(empty1((MIXQ - 1) & 3)); }
            mbar_wait(halo_bar, 0, spins);
#pragma unroll
            for (int n = 0; n < 16; n++) {
                const int b = 1 - n / 8, h = (n & 4) / 2 + n % 2, j = n / 2 % 2;
                uint32_t* const kq = pk + 32 + 8 * h + 4 * j;
                uint32_t* const q = pk + 8 * h + 4 * b;
                mma_sync(j ? q : c[n % 2], kq, q[2 * j], q[2 * j + 1], j ? c[n % 2] : zero);
                if (b) get(a + (h * 2 + j) * 256, kq[1], kq[3]);
                meet(n, MIXQ, id);
            }
        };
        auto chunk_qk = [&](int k) {
            constexpr float LOG2E = 1.4426950408889634f;
            uint32_t* const l = pk + 32;
            Floats<16> e(pk);
            if (k == KK) {
                const uint32_t a = halo();
#pragma unroll
                for (int i = 0; i < 8; i++) put(a + i * 256, pk[33 + 4 * i], pk[35 + 4 * i]);
                publish(1);
            } else if (k == MIXQ + 1) {
                const uint32_t id = fresh_tid();
                const bool u0 = id % 32 / 4 > id % 4 * 2, u1 = id % 32 / 4 > id % 4 * 2 + 1;
                const uint32_t gone = row0(id) < 2 ? (u0 ? 0xffffu : 0u) | (u1 ? 0xffff0000u : 0u) : 0u;
#pragma unroll
                for (int n = 0; n < 8; n++) {
                    const int b = n % 2;
                    const uint32_t* const c = pk + 4 * n;
                    uint32_t v = pack_bf16(__uint_as_float(pick(u0, c[2 - 2 * b], c[2 * b])), __uint_as_float(pick(u1, c[3 - 2 * b], c[1 + 2 * b])));
                    v = mul2_bf16x2(v, 0x3e353e35u, 0x379e379eu);
                    if (!b) v = v & ~gone | 0xce6ece6eu & gone;
                    l[n] = transpose8(v);
                }
            } else if (k == MIXQ + 2) {
#pragma unroll
                for (int h = 0; h < 4; h++) {
                    uint32_t m = max_bf16x2(__byte_perm(l[2 * h], l[2 * h + 1], 0x5410), __byte_perm(l[2 * h], l[2 * h + 1], 0x7632));
                    m = max_bf16x2(m, __shfl_xor_sync(0xffffffffu, m, 1));
                    m = max_bf16x2(m, __shfl_xor_sync(0xffffffffu, m, 2));
#pragma unroll
                    for (int n = 2 * h; n < 2 * h + 2; n++) {
                        const float f = -LOG2E * (n % 2 ? bf_hi(m) : bf_lo(m));
                        e[2 * n] = ex2_fast(fmaf(bf_lo(l[n]), LOG2E, f));
                        e[2 * n + 1] = ex2_fast(fmaf(bf_hi(l[n]), LOG2E, f));
                    }
                }
                e.put(pk);
            } else if (k == MIXQ + 3) {
                uint32_t p[8];
#pragma unroll
                for (int n = 0; n < 8; n++) {
                    float sum = e[2 * n] + e[2 * n + 1];
                    sum += __shfl_xor_sync(0xffffffffu, sum, 1);
                    sum += __shfl_xor_sync(0xffffffffu, sum, 2);
                    const float r = rcp_fast(sum);
                    p[n] = pack_bf16(e[2 * n] * r, e[2 * n + 1] * r);
                }
                const uint32_t a = aux + 5 * HALO_BYTES + fresh_tid() * 16;
                sts128(a, make_uint4(p[0], p[1], p[2], p[3]));
                sts128(a + 4096, make_uint4(p[4], p[5], p[6], p[7]));
            }
        };
        auto values = [&](int h) { return pk + (h & 2) * 16 + (h & 1) * 8; };
        auto mix_pv = [&]() {
            uint32_t lo[8], hi[8];
            const uint32_t id = fresh_tid();
            const uint32_t keep = (id % 4 * 2 > id % 32 / 4 ? 0xffffu : 0u) | (id % 4 * 2 + 1 > id % 32 / 4 ? 0xffff0000u : 0u);
            const uint4 p0 = lds128(aux + 5 * HALO_BYTES + id * 16), p1 = lds128(aux + 6 * HALO_BYTES + id * 16);
            const uint32_t p[8] = {p0.x, p0.y, p0.z, p0.w, p1.x, p1.y, p1.z, p1.w};
#pragma unroll
            for (int n = 0; n < 8; n++)
                asm volatile("and.b32 %0, %2, %3;\nand.b32 %1, %2, %4;" : "=r"(lo[n]), "=r"(hi[n])
                             : "r"(p[n]), "r"(n % 2 ? keep : ~keep), "r"(n % 2 ? ~keep : keep));
            if (EREL) { wg_wait<0>(); release(empty1((MIXV - 1) & 3)); }
            mbar_wait(halo_bar, 1, spins);
#pragma unroll
            for (int n = 0; n < 16; n++) {
                const int i = (n & 8) / 2 + (n & 2) + (n & 4) / 4;
                mma_sync(pk + 4 * (n ^ 4), pk + 4 * (n ^ 4), lo[i], hi[i], zero);
                meet(n, MIXV, id);
            }
        };
        auto chunk_pv = [&](int k) {
            if (k >= VK && k < VK + VN) {
                const uint32_t a = halo();
#pragma unroll
                for (int h = (k - VK) * 4 / VN; h < (k - VK + 1) * 4 / VN; h++) {
                    uint32_t* const w = values(h);
                    uint32_t v[8];
#pragma unroll
                    for (int i = 0; i < 8; i++) v[i] = transpose8(w[h < 2 ? (i & 1) + (i & 2) * 2 + (i & 4) / 2 : (i & 1) * 2 + (i & 2) / 2 + (i & 4)]);
#pragma unroll
                    for (int i = 0; i < 8; i++) w[i] = v[i];
                    put(a + h * 512, w[2], w[3]);
                    put(a + h * 512 + 256, w[6], w[7]);
                }
                if (k == VK + VN - 1) publish(3);
            } else if (k == MIXV - 1) {
                const uint32_t a = halo(), id = fresh_tid();
                optr = prm.pa2 + (size_t)(row0(id) + id % 4 * 4) * K2 + nslot * 128 + (id & 28) * 2;
                mbar_wait(halo_bar, 1, spins);
#pragma unroll
                for (int n = 0; n < 8; n++) {
                    uint32_t* const w = values(n / 2) + n % 2 * 4;
                    w[16] = w[0]; w[17] = w[1];
                    get(a + n * 256, w[18], w[19]);
                }
            } else if (k > MIXV && k <= MIXV + OVS) {
#pragma unroll
                for (int j = 0; j < 8; j++) {
                    if (j * OVS / 8 != k - MIXV - 1) continue;
                    Floats<15> c(pk + j / 2 * 16 + j % 2);
                    asm volatile("st.global.v4.u32 [%0], {%1,%2,%3,%4};"
                                 :: "l"(optr + ((~j & 2) * 8 + j % 2 * 2) * K2 + j / 4 * 64), "r"(pack_bf16(c[0], c[2])),
                                    "r"(pack_bf16(c[4], c[6])), "r"(pack_bf16(c[8], c[10])), "r"(pack_bf16(c[12], c[14])) : "memory");
                }
                if (k == MIXV + OVS) signal_stores(4);
            }
        };

        TRACE_SLOT(tile_slot, 16 + wg * 8);
#pragma unroll 1
        for (int t = 0; t < G1_TILES; t++) {
#pragma unroll
            for (int k = 0; k < G1_KSTEPS; k++) {
                const int s = k & 3;
                if (k % TOP == 0) asm volatile("" : "+r"(t));
                TRACE_STEP(t, k, 0);
                mbar_wait(full1(s), (k >> 2) & 1, spins);
                if (k == 0) TRACE_S(12, t, 0);
                TRACE_STEP(t, k, 1);
                if (wg == 1 && k == G1_KSTEPS - (t == 4 ? SK4 : G1_SKEW)) asm volatile("bar.sync 1, 256;" ::: "memory");
                if (k == MIXV && t == 3) mix_pv();
                else if (k == MIXQ && t == 2) mix_qk();
                else if (t == G1_TILES - 1) mma_step224(acc, da, db, next1(s), k);
                else mma_step(acc, da, db, next1(s), k);
                if (wg == 0 && k == G1_KSTEPS - 1) asm volatile("bar.arrive 1, 256;" ::: "memory");
                wg_wait<1>();
                if (k > 0 && !(EREL && (k == MIXV && t == 3 || k == MIXQ && t == 2))) release(empty1((k - 1) & 3));
                TRACE_STEP(t, k, 2);
                if (t == 0) chunk_ln(k);
                if (k >= 1 && k <= 8 && ((k < GV || k > GV + 3 ? 0x12 : 0x1a) >> t & 1)) {
                    chunk_geglu(k < GV ? k - 1 : (k > GV + 3 ? k - 5 : k - GV + 4));
                    if (k == 8 && t != 3) signal_stores(t + 1);
                }
                if (t == 2) chunk_qk(k);
                if (t == 3) chunk_pv(k);
                if (k == 13) {
                    const uint32_t id = fresh_tid();
                    optr = prm.pa2 + (size_t)(row0(id) + (id & 28) / 2) * K2 + DM + gate_col(t, nslot) + id % 4 * 8;
                    asm volatile("" : "+l"(optr));
                }
            }
            wg_wait<0>();
            fence_regs(acc);
            release(empty1(3));
            if (t == 0) {
                Floats<2> inv(pk + 32);
#pragma unroll
                for (int i = 0; i < 128; i++) acc[i] *= inv[i / 2 % 2];
                fence_regs(acc);
            }
#pragma unroll
            for (int i = 0; i < 64; i++) {
                const int e = i < 32 ? (i & ~7) * 2 + (i & 3) * 4 + (i & 4) / 2 : i * 2;
                pk[i] = pack_bf16(acc[e], acc[e + 1]);
            }
            TRACE_NEXT(tile_slot);
        }

        float accd[64], accs[64];
#pragma unroll
        for (int i = 0; i < 64; i++) accd[i] = 0.f;
#pragma unroll
        for (int u = 0; u < G2_HEAD; u++) {
            const int q = u % G2_STAGES;
            mbar_wait(full2(q), (u / G2_STAGES) & 1, spins);
            if (u % 2) mma_step_c(accd, da, db, next2(q), u);
            else mma_step(accd, da, db, next2(q), u);
            wg_wait<1>();
            if (u > 0) release(empty2((u - 1) % G2_STAGES));
            if (u == TLD) {
#pragma unroll
                for (int i = 0; i < 2; i++) {
                    const uint4 v = ldg_stream(prm.tail + role * 512 + i * 256 + threadIdx.x, stream_policy());
                    pk[56 + 4 * i] = v.x; pk[57 + 4 * i] = v.y; pk[58 + 4 * i] = v.z; pk[59 + 4 * i] = v.w;
                }
            }
            if (u >= 1) {
                const int j = (u - 1) / 2;
#pragma unroll
                for (int i = 2 * u - 2; i < 2 * u; i++) pk[i] = geglu2(pk[i], pk[up(i)]);
                if (u % 2 == 0) store_pk(optr + (j & 1) * 16 * K2 + (j >> 1) * 32, j);
            }
            if (u == G2_HEAD - 1) signal_stores(6);
        }
        auto down = [&](int q, uint32_t phase, bool narrow, bool busy = false) {
            mbar_wait(full2(q), phase, spins);
            if (narrow) mma_step96(accd, da, db, next2(q), 1);
            else if (busy) mma_step_c(accd, da, db, next2(q), 1);
            else mma_step(accd, da, db, next2(q), 1);
            wg_wait<1>();
            release(empty2((q + G2_STAGES - 1) % G2_STAGES));
        };
        uint32_t shared_steps = plan_word(base, lane);
        down(5, 0, false);
#pragma unroll 1
        for (uint32_t r = 3; r < 9; r++, shared_steps >>= G2_STAGES) {
#pragma unroll
            for (int q = 0; q < G2_STAGES; q++) down(q, r & 1, (q || SMAX > 18) && shared_steps >> q & 1);
        }
        down(0, 1, false);
        down(1, 1, false, true);
        TRACE_NEXT(tile_slot);
#pragma unroll
        for (int i = 0; i < 64; i++) accs[i] = 0.f;
        uint32_t gk[32], xr[32];
        const uint32_t xs = aux + cw * 2048;
        const uint32_t xrow = xs + ((lane & 7) + ((lane >> 3) & 1) * 8) * 128;
        auto xaddr = [&](int j) { return xrow + (j >> 2) * 16384 + (((((j & 3) * 2) + (lane >> 4)) ^ (lane & 7)) << 4); };
#pragma unroll
        for (int u = G2_DSTEPS; u < G2_KSTEPS; u++) {
            const int q = u % G2_STAGES, v = u - G2_DSTEPS;
            mbar_wait(full2(q), (u / G2_STAGES) & 1, spins);
            if (G2_SKEW > 0 && wg == 1 && u == G2_KSTEPS - G2_SKEW) asm volatile("bar.sync 1, 256;" ::: "memory");
            if (u % 2) mma_step_c(accs, da, db, next2(q), v);
            else mma_step(accs, da, db, next2(q), v);
            if (G2_SKEW > 0 && wg == 0 && u == G2_KSTEPS - 1) asm volatile("bar.arrive 1, 256;" ::: "memory");
            if (v == TLD2) {
                TRACE_S(32, wg, 0);
                mbar_wait(dep_bar + 24, 0, spins);
                TRACE_S(33, wg, 0);
#pragma unroll
                for (int i = 0; i < 2; i++) {
                    const uint4 w = ldg_stream(prm.tail + (NGEMM + role) * 512 + i * 256 + threadIdx.x, stream_policy());
                    gk[24 + 4 * i] = w.x; gk[25 + 4 * i] = w.y; gk[26 + 4 * i] = w.z; gk[27 + 4 * i] = w.w;
                }
            }
#pragma unroll
            for (int i = 0; i < 32; i++) {
                if (v == (i < 24 ? i / 4 + 1 : TLD2 + (i < 28 ? GA : GB)))
                    gk[i] = i < 24 ? silu2(accd[2 * i], accd[2 * i + 1])
                                   : silu2(accd[2 * i] + bf_lo(gk[i]), accd[2 * i + 1] + bf_hi(gk[i]));
            }
            if (v == XLD) mbar_wait(x_bar, 0, spins);
            if (v >= XLD && v < XLD + 4) {
#pragma unroll
                for (int j = 2 * (v - XLD); j < 2 * (v - XLD + 1); j++)
                    asm volatile("ldmatrix.sync.aligned.m8n8.x4.shared.b16 {%0,%1,%2,%3}, [%4];"
                                 : "=r"(xr[4 * j]), "=r"(xr[4 * j + 1]), "=r"(xr[4 * j + 2]), "=r"(xr[4 * j + 3])
                                 : "r"(xaddr(j)) : "memory");
            }
            wg_wait<1>();
            if (v == 0) fence_regs(accd);
            if (u - 1 + G2_STAGES < G2_KSTEPS) release(empty2((u - 1) % G2_STAGES));
        }
        __nv_bfloat16* po = prm.pout + (row0(fresh_tid()) + (lane >> 3) * 2) * DM + nslot * 128 + 64 + (lane & 7) * 8;
        uint32_t so = xs + 16384 + (lane >> 3) * 128 + (((lane & 7) ^ (lane >> 3)) << 4);
        const int c0 = uniform(nslot * 128), c1 = uniform(row0(fresh_tid()) >> 1);
        const uint32_t xu = uniform(xs);
        asm volatile("" : "+l"(po), "+r"(so));
        wg_wait<0>();
        fence_regs(accs);
        TRACE_NEXT(tile_slot);
        TRACE_END();
#pragma unroll
        for (int j = 0; j < 8; j++) {
            uint32_t r[4];
#pragma unroll
            for (int i = 0; i < 4; i++) {
                const int e = j * 4 + i;
                asm("fma.rn.bf16x2 %0, %1, %2, %3;" : "=r"(r[i]) : "r"(pack_bf16(accs[2 * e], accs[2 * e + 1])), "r"(gk[e]), "r"(xr[e]));
            }
            asm volatile("stmatrix.sync.aligned.m8n8.x4.shared.b16 [%0], {%1,%2,%3,%4};"
                         :: "r"(xaddr(j)), "r"(r[0]), "r"(r[1]), "r"(r[2]), "r"(r[3]) : "memory");
            if (j == 3)
                asm volatile("{\n.reg .pred e;\nfence.proxy.async.shared::cta;\nbar.warp.sync 0xffffffff;\nelect.sync _|e, 0xffffffff;\n"
                    "@e cp.async.bulk.tensor.3d.global.shared::cta.bulk_group [%0, {%2, %3, %4}], [%1];\n}"
                    :: "l"(&prm.out), "r"(xu), "r"(c0), "r"(c1), "r"(wg) : "memory");
        }
        __syncwarp();
#pragma unroll
        for (int i = 0; i < 4; i++) {
            const uint4 v = lds128((so ^ (i & 1) * 64) + i * 512);
            asm volatile("st.global.v4.u32 [%0], {%1,%2,%3,%4};" :: "l"(po + i * 8 * DM), "r"(v.x), "r"(v.y), "r"(v.z), "r"(v.w) : "memory");
        }
        asm volatile("cp.async.bulk.commit_group;\ncp.async.bulk.wait_group.read 0;" ::: "memory");
        TRACE_LITE(10, clock());
        if (tid == 0) { TRACE_NEXT(tile_slot); if (wg == 1) TRACE_GT(13); TRACE_DUMP(); }
    } else if (warp > 9) {
        const int w = warp - 10;
        const unsigned epoch = __ldcg(prm.epoch + blockIdx.x * 16 + w) + 1;
        const uint32_t tag = 1 + (epoch & 1);
        TRACE_LITE(8, t0);
        const uint32_t at = (w ? CB : CA) >> (CIDX) * 4 & 15;
        mbar_wait(empty1(at & 3), 0);
        mbar_wait(empty1(at & 3), at >> 3);
        if (elect_one()) {
            mbar_expect_tx(cs_bar + w * 8, 16384);
            asm volatile("cp.async.bulk.tensor.2d.shared::cluster.global.mbarrier::complete_tx::bytes [%0], [%1, {%3, %5}], [%2];\n"
                "cp.async.bulk.tensor.2d.shared::cluster.global.mbarrier::complete_tx::bytes [%0 + 8192], [%1, {%4, %5}], [%2];"
                :: "r"(aux + w * 16384), "l"(w0), "r"(cs_bar + w * 8), "r"(nslot * 128), "r"(nslot * 128 + 64),
                   "r"(((mblk & ~1) + w) * 64) : "memory");
        }
        float cs[8];
#pragma unroll
        for (int d = 0; d < 8; d++) cs[d] = 0.f;
        const uint32_t wa = aux + w * 8192 + (lane >> 3) * 128 + (((lane & 7) ^ (lane >> 3)) << 4);
        uint4 v[8];
        auto fetch = [&](int h, uint32_t off) {
#pragma unroll
            for (int j = 0; j < 4; j++) v[h * 4 + j] = lds128((wa ^ (j & 1) * 64) + off + h * 2048 + j * 512);
        };
        auto add = [&](int h) {
#pragma unroll
            for (int j = 0; j < 4; j++) {
                float f[8];
                unpack8(v[h * 4 + j], f);
#pragma unroll
                for (int d = 0; d < 8; d++) cs[d] += f[d];
            }
        };
        if (CST) { mbar_wait(empty1(CST & 3), 0); mbar_wait(empty1(CST & 3), CST >> 3); }
        mbar_wait(cs_bar, 0);

        fetch(0, 0);
#pragma unroll 1
        for (int i = 0; i < 4; i++) {
            fetch(1, (i >> 1) * 16384 + (i & 1) * 4096);
            add(0);
            if (i == 1) mbar_wait(cs_bar + 8, 0);
            fetch(0, (i + 1 & 2) * 8192 + (~i & 1) * 4096);
            add(1);
        }
#pragma unroll
        for (int d = 0; d < 4; d++)
            cs[d] = (lane & 16 ? cs[d + 4] : cs[d]) + __shfl_xor_sync(0xffffffffu, lane & 16 ? cs[d] : cs[d + 4], 16);
#pragma unroll
        for (int d = 0; d < 2; d++)
            cs[d] = (lane & 8 ? cs[d + 2] : cs[d]) + __shfl_xor_sync(0xffffffffu, lane & 8 ? cs[d] : cs[d + 2], 8);
        st_tagged(prm.colsum + (nslot * 2 + rank) * 1024 + (mblk >> 1) * 128 + w * 64 + (lane & 7) * 8 + (lane >> 3) * 2,
                  cs[0], cs[1], tag);

        fold_operands(prm, base, nslot, mblk, tag, w, lane);
        if (lane == 0) {
            mbar_arrive(fold_bar);
            prm.epoch[blockIdx.x * 16 + w] = epoch;
            if (w == 0) {
                TRACE(35);
#pragma unroll 1
                for (uint32_t j = 0, n = 1 << 24; j < 4; n = (CNT_EARLY | CNT_LATE << 8 | 1 << 16) >> j * 8 & 255, j++) {
                    const uint32_t v = flag_wait(flags + (F_SHARE + j) * 512, epoch * n);
                    fence_proxy_async();
                    if (j) mbar_arrive(dep_bar + j * 8);
                    else sts32(base + PLAN_OFF, v & 0xffffff);
                }
            } else {
#pragma unroll 1
                for (int j = 0; j < 2; j++) {
                    uint8_t* const h = prm.halo + (j * NGEMM + role) * HALO_BYTES;
                    unsigned* const f = prm.flags + F_HALO * 512 + role * 32;
                    mbar_wait(sig_bar + 8 + j * 16, 0);
                    TRACE_S(38, j, 0); TRACE_S(9, j, 1);
                    asm volatile("cp.async.bulk.global.shared::cta.bulk_group [%0], [%1], %2;\n"
                        "cp.async.bulk.commit_group;\ncp.async.bulk.wait_group 0;"
                        :: "l"(h + HALO_BYTES), "r"(aux + 4 * HALO_BYTES), "n"(HALO_BYTES) : "memory");
                    fence_proxy_async();
                    TRACE_S(39, j, 0); TRACE_S(10, j, 1);
                    flag_add(f);
                    TRACE_S(40, j, 0); TRACE_S(34, j, 1);
                    if (mblk) flag_wait(f - 32, epoch * 2 - 1 + j);
                    fence_proxy_async();
                    TRACE_S(41, j, 0); TRACE_S(36, j, 1);
                    mbar_expect_tx(halo_bar, HALO_BYTES);
                    asm volatile("cp.async.bulk.shared::cluster.global.mbarrier::complete_tx::bytes [%0], [%1], %2, [%3];"
                        :: "r"(aux), "l"(mblk ? h : prm.halo), "n"(HALO_BYTES), "r"(halo_bar) : "memory");
                }
            }
        }
    } else {
        constexpr int roll = ROLL;
#pragma unroll roll
        for (int k = 1; k < G1_STAGES; k++) {
            const uint32_t sa = base + k * G1_STAGE_BYTES;
            if (PACE0 + PACE) while ((uint32_t)clock() - t0 < (k == 3 ? PACE3 : PACE0 + (k - 1) * PACE)) {}
            load_stage1(sa, sa + A_BYTES + rank * 16384, full1(k), &prm.x, w0, w0, k * 64, mblk * 64, nslot * 128,
                        nslot * 128 + 64, 0, stream_policy());
        }
        if (elect_one()) {
            prefetch_map(&prm.xn); prefetch_map(&prm.wqkv);
            prefetch_map(&prm.a2); prefetch_map(&prm.wo); prefetch_map(&prm.wd); prefetch_map(&prm.out);
        }
        auto load_x = [&]() {
            if (elect_one()) {
                mbar_expect_tx(x_bar, 32768);
                tma_3d(aux, &prm.x, x_bar, nslot * 128, mblk * 64, 0, stream_policy());
                tma_3d(aux + 16384, &prm.x, x_bar, nslot * 128 + 64, mblk * 64, 0, stream_policy());
            }
            __syncwarp();
        };
        uint32_t ph = 0;
#pragma unroll 1
        for (int t = 0; t < G1_TILES; t++) {
            const int col1 = (t == 1 ? rank * DM + nslot * 128 : gate_col(t, nslot)) + 64;
            const int col0 = t == 2 ? 2 * DM + nslot * 128 + rank * 64 : col1 - 64;
            if (t == 1) { TRACE_PUT(2, t0); TRACE(14); mbar_wait_warp(dep_bar, 0); TRACE(3); }
#pragma unroll 1
            for (int k = t ? 0 : G1_STAGES; k < G1_KSTEPS; k++) {
                const int s = k & 3;
                if (t == 1 && k == 8) mbar_wait_warp(dep_bar + 40, 0);
                if (t * 16 + k == (PFK)) {
                    asm volatile("{\n.reg .pred e;\nelect.sync _|e, 0xffffffff;\n"
                        "@e cp.async.bulk.prefetch.tensor.5d.L2.global [%0, {%1, %4, %4, %4, %3}];\n"
                        "@e cp.async.bulk.prefetch.tensor.5d.L2.global [%0, {%2, %4, %4, %4, %3}];\n}"
                        :: "l"(&prm.wd), "r"(nslot * 128), "r"(nslot * 128 + 64), "r"((mblk + SHARE_MAX) * 2), "r"(0) : "memory");
                }
                mbar_wait_warp(empty1(s), ph);
                const uint32_t sa = base + s * G1_STAGE_BYTES;
                load_stage1(sa, sa + A_BYTES + rank * 16384, full1(s), t ? &prm.xn : &prm.x, t == 1 || t == 2 ? &prm.wqkv : w0,
                            t == 1 ? &prm.wqkv : w0, k * 64, mblk * 64, col0, col1, t & 3,
                            stream_policy());
                if (s == 3) ph ^= 1;
                if (t * 16 + k == (XK)) load_x();
            }
        }
        TRACE(4);
        mbar_wait_warp(dep_bar + 8, 0);
        TRACE(5);
        int q = 0, round = 4, own = SHARE_MAX; uint32_t ph2 = 1;
#pragma unroll 1
        for (int u = 0; u < G2_KSTEPS; u++) {
            if (u == G2_LATE) { TRACE(6); mbar_wait_warp(dep_bar + 16, 0); TRACE(7); }
            const uint32_t sa = stage2(q);
            const bool down = u < G2_DSTEPS;
            const int k = !down ? u - G2_DSTEPS : (u < 18 || u >= 40 || (SMAX == 18 && q == 0) ? own++ : (q & 1 ? u / 2 - 9 : round + (q ? q * 2 : 11)));
            mbar_wait_warp(u < G2_STAGES ? empty1((u * 2 + 1) / 3) : empty2(q), u < G2_STAGES ? ph : ph2);
            load_stage2(sa, sa + A_BYTES + rank * 8192, full2(q), &prm.a2, down ? &prm.wd : &prm.wo, (down ? DM : 0) + k * 64,
                        mblk * 64, nslot * 128 + rank * 64, down ? 0 : k * 2, down ? k * 2 : 0, stream_policy());
            if (++q == G2_STAGES) { q = 0; ph2 ^= 1; round++; }
        }
        TRACE(8);
    }
}

typedef CUresult (*EncodeFn)(CUtensorMap*, CUtensorMapDataType, cuuint32_t, void*, const cuuint64_t*, const cuuint64_t*,
                             const cuuint32_t*, const cuuint32_t*, CUtensorMapInterleave, CUtensorMapSwizzle,
                             CUtensorMapL2promotion, CUtensorMapFloatOOBfill);

void encode(EncodeFn fn, CUtensorMap* m, const void* ptr, int rank, const cuuint64_t* dims, const cuuint64_t* strides,
            const cuuint32_t* box) {
    const cuuint32_t es[5] = {1, 1, 1, 1, 1};
    fn(m, CU_TENSOR_MAP_DATA_TYPE_BFLOAT16, rank, const_cast<void*>(ptr), dims, strides, box, es,
       CU_TENSOR_MAP_INTERLEAVE_NONE, box[0] == 32 ? CU_TENSOR_MAP_SWIZZLE_64B : CU_TENSOR_MAP_SWIZZLE_128B,
       CU_TENSOR_MAP_L2_PROMOTION_L2_128B, CU_TENSOR_MAP_FLOAT_OOB_FILL_NONE);
}
void encode_rows(EncodeFn fn, CUtensorMap* m, const void* ptr, int cols, int box_rows, int box_parity) {
    const cuuint64_t dims[3] = {(cuuint64_t)cols, SEQ / 2, 2}, strides[2] = {(cuuint64_t)cols * 4, (cuuint64_t)cols * 2};
    const cuuint32_t box[3] = {64, (cuuint32_t)box_rows, (cuuint32_t)box_parity};
    encode(fn, m, ptr, 3, dims, strides, box);
}
void encode_w1(EncodeFn fn, CUtensorMap* m, const void* ptr, int cols) {
    const cuuint64_t dims[2] = {(cuuint64_t)cols, DM}, strides[1] = {(cuuint64_t)cols * 2};
    const cuuint32_t box[2] = {64, 64};
    encode(fn, m, ptr, 2, dims, strides, box);
}
void encode_tail(EncodeFn fn, CUtensorMap* m, const void* ptr, int rows, int cols, int n) {
    const cuuint64_t rb = cols * 2;
    const cuuint64_t dims[5] = {32, (cuuint64_t)n, (cuuint64_t)rows / (4 * n), 4, 8}, strides[4] = {rb, 4 * n * rb, n * rb, 256};
    const cuuint32_t box[5] = {32, (cuuint32_t)n, 16 / (cuuint32_t)n, 4, 4};
    encode(fn, m, (const __nv_bfloat16*)ptr + cols - 1024 + 96, 5, dims, strides, box);
}
void encode_w2(EncodeFn fn, CUtensorMap* m, const void* ptr, int rows) {
    const cuuint64_t rb = DM * 2;
    const cuuint64_t dims[5] = {DM, 2, 4, 4, (cuuint64_t)rows / 32}, strides[4] = {rb, 8 * rb, 2 * rb, 32 * rb};
    const cuuint32_t box[5] = {64, 2, 4, 4, 2};
    encode(fn, m, ptr, 5, dims, strides, box);
}
void encode_wo(EncodeFn fn, CUtensorMap* m, const void* ptr) {
    const cuuint64_t rb = DM * 2;
    const cuuint64_t dims[5] = {DM, 4, DM / 32, 2, 4}, strides[4] = {8 * rb, 32 * rb, rb, 2 * rb};
    const cuuint32_t box[5] = {64, 4, 2, 2, 4};
    encode(fn, m, ptr, 5, dims, strides, box);
}

}

extern "C" void kernel_launch(void* const* d_in, const int* in_sizes, int n_in, void* d_out, int out_size) {
    (void)in_sizes; (void)n_in; (void)out_size;
    static EncodeFn fn = nullptr;
    static Params prm;
    if (!fn) {
        cudaDriverEntryPointQueryResult st;
        cudaGetDriverEntryPoint("cuTensorMapEncodeTiled", (void**)&fn, cudaEnableDefault, &st);
        cudaGetSymbolAddress((void**)&prm.pxn, g_xn);
        cudaGetSymbolAddress((void**)&prm.pa2, g_a2);
        cudaGetSymbolAddress((void**)&prm.tail, g_tail);
        cudaGetSymbolAddress((void**)&prm.halo, g_halo);
        cudaGetSymbolAddress((void**)&prm.stats, g_stats);
        cudaGetSymbolAddress((void**)&prm.colsum, g_colsum);
        cudaGetSymbolAddress((void**)&prm.flags, g_flags);
        cudaGetSymbolAddress((void**)&prm.epoch, g_epoch);
        cudaFuncSetAttribute(fused_kernel, cudaFuncAttributeMaxDynamicSharedMemorySize, SMEM_BYTES);
    }
    encode_rows(fn, &prm.x, d_in[0], DM, 64, 2);
    encode_rows(fn, &prm.xn, prm.pxn, DM, 64, 2);
    encode_rows(fn, &prm.a2, prm.pa2, K2, 64, 2);
    encode_rows(fn, &prm.out, d_out, DM, 16, 1);
    encode_w1(fn, &prm.wqkv, d_in[1], NQKV);
    encode_w1(fn, &prm.wg, d_in[4], DF);
    encode_w1(fn, &prm.wu, d_in[5], DF);
    encode_tail(fn, &prm.wu_tail, d_in[5], DM, DF, 8);
    encode_tail(fn, &prm.wd_tail, d_in[6], DF, DM, 2);
    encode_wo(fn, &prm.wo, d_in[2]);
    encode_w2(fn, &prm.wd, d_in[6], DF);
    prm.hi[0] = prm.hi[1] = 0x40000040;
    prm.px = (const __nv_bfloat16*)d_in[0];
    prm.pwu = (const __nv_bfloat16*)d_in[5];
    prm.pout = (__nv_bfloat16*)d_out;
    fused_kernel<<<NCTA, 384, SMEM_BYTES>>>(prm);
}
```

```cpp
#include <cuda_runtime.h>
#include <cuda_bf16.h>
#include <cuda.h>
#include <stdint.h>
#include <limits.h>

#define LNS 3
#define FS 14
#define CA 0x87658765u
#define CB 0x65876587u
#define CST 11
#define CIDX nslot
#define PACE0 800
#define PACE 525
#define PACE3 1700
#define TSUM 43
#define SMIN 3
#define SMAX 22
#define DUE 75100.f
#define TLO 36
#define SWAP 1
#define STEPNS 79
#define REST 65000.f
#define ROLL 1
#define BAL 1
#define C2AT 2
#define TPACE 425
#define TEARLY 1
#define TEW 8
#define WDPF 1
#define TFOLD 1
#define MIXQ 8
#define MIXV 9
#define TLD2 7
#define XLD 5
#define VK 1
#define VN 2
#define KK 2
#define EREL 0
#define MEET 4
#define OVS 4
#define GV 3
#define TOP 16
#define SK2 5
#define XK 40 + nslot * 2
#define TSK 2
#define TW0 600
#define TLD 2
#define SK4 2
#define PB 0xa0302820u
#define GA 3
#define GB 4

namespace {

constexpr int SEQ = 2048, DM = 1024, DF = 3584, K2 = DM + DF, NQKV = 3 * DM;
constexpr int NGEMM = 128, NCTA = 132;
constexpr int G1_STAGES = 4, G1_STAGE_BYTES = 49152, G1_KSTEPS = 16, G1_TILES = 5;
constexpr int G2_STAGES = 6, G2_STAGE_BYTES = 32768, G2_KSTEPS = 72, G2_LATE = 40, G2_DSTEPS = 56;
constexpr int G2_HEAD = 17;
constexpr int LN_STEP = LNS, FOLD_STEP = FS;
constexpr int A_BYTES = 16384;
constexpr int AUX_OFF = G1_STAGES * G1_STAGE_BYTES;
constexpr int BAR_OFF = AUX_OFF + 32768;
constexpr int PLAN_OFF = BAR_OFF + 384, STAT_OFF = BAR_OFF + 1536;
constexpr int SMEM_BYTES = BAR_OFF + 2816;
constexpr int G1_SKEW = 2, G2_SKEW = SK2;
constexpr int CONSUMER_REGS = 224, AUX_REGS = 56;
constexpr int HALO_BYTES = 4096;
constexpr int SHARE_MIN = SMIN, SHARE_MAX = SMAX, SHARE_SUM = TSUM;

enum { F_LN = 0, F_LN2 = 1, F_FIRST = 2, F_SECOND = 3, F_SHARE = 4, F_EARLY = 5, F_LATE = 6, F_TAIL2 = 7, F_PACE = 8, F_HALO = 9 };
constexpr unsigned CNT_LN = 8, CNT_EARLY = 9, CNT_LATE = 8;

__device__ __align__(1024) __nv_bfloat16 g_xn[SEQ * DM];
__device__ __align__(1024) __nv_bfloat16 g_a2[SEQ * K2];
__device__ __align__(128) uint4 g_tail[2 * NGEMM * 512];
__device__ __align__(128) uint8_t g_halo[(2 * NGEMM + 1) * HALO_BYTES];
__device__ __align__(128) float2 g_stats[SEQ];
__device__ __align__(128) float g_colsum[18 * 1024];
__device__ __align__(128) unsigned g_flags[(F_HALO + 8) * 16 * 32];
__device__ __align__(128) unsigned g_epoch[NCTA * 16];

struct Params {
    const __nv_bfloat16 *px, *pwu;
    __nv_bfloat16 *pxn, *pa2, *pout;
    uint4* tail;
    uint8_t* halo;
    float2* stats;
    float* colsum;
    unsigned *flags, *epoch;
    unsigned long long* trace;
    uint32_t hi[2];
    CUtensorMap x, wg, wu, xn, wqkv, a2, wu_tail, wd_tail, wo, wd, out;
};

extern __shared__ __align__(1024) uint8_t smem_raw[];

#define TRACE(slot) do {} while (0)
#define TRACE_GT(slot) do {} while (0)
#define TRACE_S(slot, v, want) do {} while (0)
#define TRACE_GET(v) do {} while (0)
#define TRACE_PUT(slot, v) do {} while (0)
#define TRACE_SLOT(v, slot) do {} while (0)
#define TRACE_NEXT(v) do {} while (0)
#define TRACE_DUMP() do {} while (0)
#define TRACE_CLEAR() do {} while (0)
#define STAGE_TRACE 0
#define TRACE_END() do {} while (0)
#define TRACE_LITE(i, c) do {} while (0)
#define TRACE_STEP(t, k, i) do {} while (0)

__device__ __forceinline__ uint32_t smem_u32(const void* p) { return (uint32_t)__cvta_generic_to_shared(p); }
__device__ __forceinline__ void mbar_init(uint32_t bar, uint32_t cnt) {
    asm volatile("mbarrier.init.shared::cta.b64 [%0], %1;" :: "r"(bar), "r"(cnt) : "memory");
}
__device__ __forceinline__ void mbar_expect_tx(uint32_t bar, uint32_t bytes) {
    asm volatile("mbarrier.arrive.expect_tx.shared::cta.b64 _, [%0], %1;" :: "r"(bar), "r"(bytes) : "memory");
}
__device__ __forceinline__ void mbar_arrive(uint32_t bar) {
    asm volatile("mbarrier.arrive.shared::cta.b64 _, [%0];" :: "r"(bar) : "memory");
}
__device__ __forceinline__ bool mbar_try_wait(uint32_t bar, uint32_t parity) {
    uint32_t ok;
    asm volatile("{\n.reg .pred p;\nmbarrier.try_wait.parity.shared::cta.b64 p, [%1], %2;\nselp.u32 %0, 1, 0, p;\n}"
                 : "=r"(ok) : "r"(bar), "r"(parity) : "memory");
    return ok;
}
__device__ __forceinline__ void mbar_wait(uint32_t bar, uint32_t parity) {
#pragma unroll 1
    for (int spins = 0; !mbar_try_wait(bar, parity) && spins < (1 << 17); spins++) {}
}
__device__ __forceinline__ void mbar_wait(uint32_t bar, uint32_t parity, int& spins) {
    asm volatile("{\n.reg .pred p;\nagain:\nmbarrier.try_wait.parity.shared::cta.b64 p, [%1], %2;\n@p bra done;\n"
                 "add.s32 %0, %0, -1;\nsetp.gt.s32 p, %0, 0;\n@p bra again;\ndone:\n}" : "+r"(spins) : "r"(bar), "r"(parity) : "memory");
}
template <bool WARP = false> __device__ __forceinline__ unsigned flag_wait(const unsigned* p, unsigned target) {
    unsigned v;
#pragma unroll 1
    for (int spins = 0; spins < (1 << 19); spins++) {
        asm volatile("ld.acquire.gpu.global.u32 %0, [%1];" : "=r"(v) : "l"(p) : "memory");
        if (WARP ? __all_sync(0xffffffffu, (int)(v - target) >= 0) : (int)(v - target) >= 0) break;
        __nanosleep(64);
    }
    return v;
}
__device__ __forceinline__ void mbar_wait_warp(uint32_t bar, uint32_t parity) {
#pragma unroll 1
    for (int spins = 0; !__all_sync(0xffffffffu, mbar_try_wait(bar, parity)) && spins < (1 << 17); spins++) {}
}
__device__ __forceinline__ void flag_add(unsigned* p) {
    asm volatile("red.release.gpu.global.add.u32 [%0], 1;" :: "l"(p) : "memory");
}
__device__ __forceinline__ bool elect_one() {
    uint32_t ok;
    asm volatile("{\n.reg .pred p;\nelect.sync _|p, 0xffffffff;\nselp.u32 %0, 1, 0, p;\n}" : "=r"(ok));
    return ok;
}
__device__ __forceinline__ uint32_t pick(bool c, uint32_t a, uint32_t b) {
    uint32_t r;
    asm("{\n.reg .pred p;\nsetp.ne.b32 p, %3, 0;\nselp.b32 %0, %1, %2, p;\n}" : "=r"(r) : "r"(a), "r"(b), "r"((uint32_t)c));
    return r;
}
__device__ __forceinline__ void fence_proxy_async() { asm volatile("fence.proxy.async.global;" ::: "memory"); }
__device__ __forceinline__ uint4 lds128(uint32_t addr) {
    uint4 v;
    asm volatile("ld.shared.v4.u32 {%0,%1,%2,%3}, [%4];" : "=r"(v.x), "=r"(v.y), "=r"(v.z), "=r"(v.w) : "r"(addr) : "memory");
    return v;
}
__device__ __forceinline__ uint32_t lds32(uint32_t addr) {
    uint32_t v;
    asm volatile("ld.shared.u32 %0, [%1];" : "=r"(v) : "r"(addr) : "memory");
    return v;
}
__device__ __forceinline__ void sts32(uint32_t addr, uint32_t v) { asm volatile("st.shared.u32 [%0], %1;" :: "r"(addr), "r"(v) : "memory"); }
__device__ __forceinline__ uint32_t nanos() { uint32_t t; asm volatile("mov.u32 %0, %%globaltimer_lo;" : "=r"(t)); return t; }
__device__ __forceinline__ float2 lds64f(uint32_t addr) {
    float2 v;
    asm volatile("ld.shared.v2.f32 {%0,%1}, [%2];" : "=f"(v.x), "=f"(v.y) : "r"(addr) : "memory");
    return v;
}
__device__ __forceinline__ void sts128(uint32_t addr, uint4 v) {
    asm volatile("st.shared.v4.u32 [%0], {%1,%2,%3,%4};" :: "r"(addr), "r"(v.x), "r"(v.y), "r"(v.z), "r"(v.w) : "memory");
}
__device__ __forceinline__ void sts64f(uint32_t addr, float a, float b) {
    asm volatile("st.shared.v2.f32 [%0], {%1,%2};" :: "r"(addr), "f"(a), "f"(b) : "memory");
}

__device__ __forceinline__ uint64_t stream_policy() { return 0x12F0000000000000ull; }
__device__ __forceinline__ void tma_3d(uint32_t dst, const CUtensorMap* m, uint32_t bar, int c0, int c1, int c2, uint64_t pol) {
    asm volatile("cp.async.bulk.tensor.3d.shared::cluster.global.mbarrier::complete_tx::bytes.L2::cache_hint"
                 " [%0], [%1, {%3, %4, %5}], [%2], %6;"
                 :: "r"(dst), "l"(m), "r"(bar), "r"(c0), "r"(c1), "r"(c2), "l"(pol) : "memory");
}
__device__ __forceinline__ void load_stage1(uint32_t dst, uint32_t dst_b, uint32_t bar, const CUtensorMap* ma, const CUtensorMap* mb0,
                                            const CUtensorMap* mb1, int k, int row, int col0, int col1, int keep_a, uint64_t pol) {
    asm volatile("{\n.reg .pred e, p, q;\nelect.sync _|e, 0xffffffff;\nsetp.ne.and.b32 p|q, %8, 0, e;\n"
        "@p cp.async.bulk.tensor.3d.shared::cluster.global.mbarrier::complete_tx::bytes [%0], [%3, {%5, %6, %10}], [%2];\n"
        "@q cp.async.bulk.tensor.3d.shared::cluster.global.mbarrier::complete_tx::bytes.L2::cache_hint [%0], [%3, {%5, %6, %10}], [%2], %9;\n"
        "@e cp.async.bulk.tensor.2d.shared::cluster.global.mbarrier::complete_tx::bytes.multicast::cluster.L2::cache_hint"
        " [%1], [%4, {%7, %5}], [%2], %11, %9;\n"
        "@e cp.async.bulk.tensor.2d.shared::cluster.global.mbarrier::complete_tx::bytes.multicast::cluster.L2::cache_hint"
        " [%1 + 8192], [%13, {%14, %5}], [%2], %11, %9;\n"
        "@e mbarrier.arrive.expect_tx.shared::cta.b64 _, [%2], %12;\n}"
        :: "r"(dst), "r"(dst_b), "r"(bar), "l"(ma), "l"(mb0), "r"(k), "r"(row), "r"(col0), "r"(keep_a), "l"(pol), "r"(0),
           "h"((uint16_t)3), "n"(G1_STAGE_BYTES), "l"(mb1), "r"(col1) : "memory");
}
__device__ __forceinline__ void load_stage2(uint32_t dst, uint32_t dst_b, uint32_t bar, const CUtensorMap* ma, const CUtensorMap* mb,
                                            int ka, int row, int col, int kb2, int kb4, uint64_t pol) {
    asm volatile("{\n.reg .pred e;\nelect.sync _|e, 0xffffffff;\n"
        "@e cp.async.bulk.tensor.3d.shared::cluster.global.mbarrier::complete_tx::bytes.L2::cache_hint [%0], [%3, {%5, %6, %10}], [%2], %9;\n"
        "@e cp.async.bulk.tensor.5d.shared::cluster.global.mbarrier::complete_tx::bytes.multicast::cluster.L2::cache_hint"
        " [%1], [%4, {%7, %10, %13, %10, %8}], [%2], %11, %9;\n"
        "@e mbarrier.arrive.expect_tx.shared::cta.b64 _, [%2], %12;\n}"
        :: "r"(dst), "r"(dst_b), "r"(bar), "l"(ma), "l"(mb), "r"(ka), "r"(row), "r"(col), "r"(kb4), "l"(pol), "r"(0),
           "h"((uint16_t)3), "n"(G2_STAGE_BYTES), "r"(kb2) : "memory");
}
__device__ __forceinline__ void load_tail(uint32_t dst, uint32_t bar, const CUtensorMap* ma, const CUtensorMap* mb, int ka, int mblk,
                                          int kb) {
    asm volatile("{\n.reg .pred e;\nelect.sync _|e, 0xffffffff;\n"
        "@e cp.async.bulk.tensor.3d.shared::cluster.global.mbarrier::complete_tx::bytes [%0], [%2, {%3, %4, %5}], [%1];\n"
        "@e cp.async.bulk.tensor.5d.shared::cluster.global.mbarrier::complete_tx::bytes.multicast::cluster"
        " [%9], [%6, {%5, %5, %7, %5, %10}], [%1], %11;\n"
        "@e mbarrier.arrive.expect_tx.shared::cta.b64 _, [%1], %8;\n}"
        :: "r"(dst), "r"(bar), "l"(ma), "r"(ka), "r"(mblk * 64), "r"(0), "l"(mb), "r"(kb), "n"(G1_STAGE_BYTES),
           "r"(dst + A_BYTES + (mblk & 1) * 16384), "r"((mblk & 1) * 4), "h"((uint16_t)3) : "memory");
}
__device__ __forceinline__ uint4 ldg_stream(const void* p, uint64_t pol) {
    uint4 v;
    asm volatile("ld.global.nc.L1::no_allocate.L2::cache_hint.v4.u32 {%0,%1,%2,%3}, [%4], %5;"
                 : "=r"(v.x), "=r"(v.y), "=r"(v.z), "=r"(v.w) : "l"(p), "l"(pol));
    return v;
}
__device__ __forceinline__ void st_tagged(void* p, float a, float b, uint32_t tag) {
    asm volatile("st.relaxed.gpu.global.v2.b32 [%0], {%1,%2};"
                 :: "l"(p), "r"((__float_as_uint(a) & ~3u) | tag), "r"((__float_as_uint(b) & ~3u) | tag) : "memory");
}
__device__ __forceinline__ void st_relaxed(unsigned* p, uint32_t v) {
    asm volatile("st.relaxed.gpu.global.b32 [%0], %1;" :: "l"(p), "r"(v) : "memory");
}
__device__ __forceinline__ bool untagged(const uint4& v, uint32_t tag) {
    return ((v.x ^ tag) | (v.y ^ tag) | (v.z ^ tag) | (v.w ^ tag)) & 3;
}
__device__ __forceinline__ uint4 ld_relaxed(const void* p) {
    uint4 v;
    asm volatile("ld.relaxed.gpu.global.v4.b32 {%0,%1,%2,%3}, [%4];" : "=r"(v.x), "=r"(v.y), "=r"(v.z), "=r"(v.w) : "l"(p) : "memory");
    return v;
}
__device__ __forceinline__ void prefetch_map(const CUtensorMap* m) {
    asm volatile("prefetch.tensormap [%0];" :: "l"(m) : "memory");
}
template <int N> __device__ __forceinline__ void wg_wait() { asm volatile("wgmma.wait_group.sync.aligned %0;" :: "n"(N) : "memory"); }

__device__ __forceinline__ uint32_t desc_a(uint32_t addr) { return (addr & 0x3FFFF) >> 4 | 1 << 16; }
__device__ __forceinline__ uint32_t desc_b(uint32_t addr) { return (addr & 0x3FFFF) >> 4 | 512 << 16; }

#define R8(d, o) "+f"(d[o]), "+f"(d[o+1]), "+f"(d[o+2]), "+f"(d[o+3]), "+f"(d[o+4]), "+f"(d[o+5]), "+f"(d[o+6]), "+f"(d[o+7])
#define R32(d, o) R8(d, o), R8(d, o+8), R8(d, o+16), R8(d, o+24)
#define R64(d, o) R32(d, o), R32(d, o+32)
#define ACC00 "%0,%1,%2,%3,%4,%5,%6,%7,%8,%9,%10,%11,%12,%13,%14,%15,%16,%17,%18,%19,%20,%21,%22,%23,%24,%25,%26,%27,%28,%29,%30,%31,"\
    "%32,%33,%34,%35,%36,%37,%38,%39,%40,%41,%42,%43,%44,%45,%46,%47"
#define ACC0 ACC00 ",%48,%49,%50,%51,%52,%53,%54,%55,%56,%57,%58,%59,%60,%61,%62,%63"
#define ACC1 "%64,%65,%66,%67,%68,%69,%70,%71,%72,%73,%74,%75,%76,%77,%78,%79,%80,%81,%82,%83,%84,%85,%86,%87,%88,%89,%90,%91,%92,%93,%94,%95,"\
    "%96,%97,%98,%99,%100,%101,%102,%103,%104,%105,%106,%107,%108,%109,%110,%111"
#define ACC48 "{" ACC00 "}"
#define ACC64 "{" ACC0 "}"
#define ACC112 "{" ACC0 "," ACC1 "}"
#define ACC128 "{" ACC0 "," ACC1 ",%112,%113,%114,%115,%116,%117,%118,%119,%120,%121,%122,%123,%124,%125,%126,%127}"
#define MMA_K16(shape, acc, a, b, keep, hb) \
    "mov.b64 da, {" a ", 0x40000040};\nmov.b64 db, {" b ", " hb "};\n" \
    "wgmma.mma_async.sync.aligned." shape ".f32.bf16.bf16 " acc ", da, db, " keep ", 1, 1, 0, 1;\n"
#define MMA_NEXT(op, a, b, sa, sb) op " " a ", " a ", " sa ";\n" op " " b ", " b ", " sb ";\n"
#define MMA_STEP_B(shape, acc, a, b, na, nb, keep, hb, sb) \
    "{\n.reg .pred p, q;\n.reg .b64 da, db;\nsetp.ne.b32 p, " keep ", 0;\nsetp.eq.b32 q, 0, 0;\nwgmma.fence.sync.aligned;\n" \
    MMA_K16(shape, acc, a, b, "p", hb) MMA_NEXT("xor.b32", a, b, "2", "128") MMA_K16(shape, acc, a, b, "q", hb) MMA_NEXT("add.s32", a, b, "2", sb) \
    MMA_K16(shape, acc, a, b, "q", hb) MMA_NEXT("xor.b32", a, b, "2", "128") MMA_K16(shape, acc, a, b, "q", hb) MMA_NEXT("add.s32", a, b, na, nb) \
    "wgmma.commit_group.sync.aligned;\n}"
#define MMA64(shape, acc, a, b, keep) "wgmma.mma_async.sync.aligned." shape ".f32.bf16.bf16 " acc ", " a ", " b ", " keep ", 1, 1, 0, 1;\n"
#define NEXT64(op, a, b, sa, sb) "mov.b64 {lo, hi}, " a ";\n" op " lo, lo, " sa ";\nmov.b64 " a ", {lo, hi};\n" \
    "mov.b64 {lo, hi}, " b ";\n" op " lo, lo, " sb ";\nmov.b64 " b ", {lo, hi};\n"
#define ADD64(op, a, b, sa, sb) "cvt.s64.s32 w, " sa ";\nadd.s64 " a ", " a ", w;\ncvt.s64.s32 w, " sb ";\nadd.s64 " b ", " b ", w;\n"
#define MMA_STEP(shape, acc, a, b, na, nb, keep) MMA_STEP_N(shape, acc, a, b, na, nb, keep, NEXT64)
#define MMA_STEP_N(shape, acc, a, b, na, nb, keep, LAST) \
    "{\n.reg .pred p, q;\n.reg .b32 lo, hi;\n.reg .b64 w;\nsetp.ne.b32 p, " keep ", 0;\nsetp.eq.b32 q, 0, 0;\nwgmma.fence.sync.aligned;\n" \
    MMA64(shape, acc, a, b, "p") NEXT64("xor.b32", a, b, "2", "128") MMA64(shape, acc, a, b, "q") NEXT64("add.s32", a, b, "2", "128") \
    MMA64(shape, acc, a, b, "q") NEXT64("xor.b32", a, b, "2", "128") MMA64(shape, acc, a, b, "q") LAST("add.s32", a, b, na, nb) \
    "wgmma.commit_group.sync.aligned;\n}"
#define MMA_ARGS64 "+l"(da), "+l"(db) : "r"(next / 16 - 6), "r"(next / 16 - 384), "r"(keep) : "memory"
#define MMA_ARGS "+r"(da), "+r"(db) : "r"(next / 16 - 6), "r"(next / 16 - 384), "r"(keep) : "memory"

__device__ __forceinline__ void mma_step(float (&d)[128], uint64_t& da, uint64_t& db, int next, int keep) {
    asm volatile(MMA_STEP("m64n256k16", ACC128, "%128", "%129", "%130", "%131", "%132") : R64(d, 0), R64(d, 64), MMA_ARGS64);
}
__device__ __forceinline__ void mma_rank(float (&d)[128], uint32_t a0, uint32_t a1, uint32_t db) {
    asm volatile("{\n.reg .pred q;\n.reg .b64 db;\nsetp.eq.b32 q, 0, 0;\nmov.b64 db, {%131, 0x40000040};\nwgmma.fence.sync.aligned;\n"
                 "wgmma.mma_async.sync.aligned.m64n256k16.f32.bf16.bf16 " ACC128 ", {%128, %129, %130, %130}, db, q, 1, 1, 1;\n}"
                 : R64(d, 0), R64(d, 64) : "r"(a0), "r"(a1), "r"(0), "r"(db) : "memory");
}
__device__ __forceinline__ void mma_step224(float (&d)[128], uint64_t& da, uint64_t& db, int next, int keep) {
    asm volatile(MMA_STEP("m64n224k16", ACC112, "%112", "%113", "%114", "%115", "%116")
                 : R64(d, 0), R32(d, 64), R8(d, 96), R8(d, 104), MMA_ARGS64);
}
__device__ __forceinline__ void mma_step(float (&d)[64], uint64_t& da, uint64_t& db, int next, int keep) {
    asm volatile(MMA_STEP("m64n128k16", ACC64, "%64", "%65", "%66", "%67", "%68") : R64(d, 0), MMA_ARGS64);
}
__device__ __forceinline__ void mma_step_c(float (&d)[64], uint64_t& da, uint64_t& db, int next, int keep) {
    asm volatile(MMA_STEP_N("m64n128k16", ACC64, "%64", "%65", "%66", "%67", "%68", ADD64) : R64(d, 0), MMA_ARGS64);
}
__device__ __forceinline__ void mma_step96(float (&d)[64], uint64_t& da, uint64_t& db, int next, int keep) {
    asm volatile(MMA_STEP("m64n96k16", ACC48, "%48", "%49", "%50", "%51", "%52") : R32(d, 0), R8(d, 32), R8(d, 40), MMA_ARGS64);
}
__device__ __forceinline__ void mma_step_tail(float (&d)[128], uint32_t da, uint32_t b, int keep) {
    uint32_t db = (b & 0x3FFFF) >> 4 | 256 << 16;
    const int next = 0;
    asm volatile(MMA_STEP_B("m64n256k16", ACC128, "%128", "%129", "%130", "%131", "%132", "0x80000040", "-96")
                 : R64(d, 0), R64(d, 64), MMA_ARGS);
}

__device__ __forceinline__ uint32_t pack_bf16(float lo, float hi) {
    uint32_t r; asm("cvt.rn.bf16x2.f32 %0, %1, %2;" : "=r"(r) : "f"(hi), "f"(lo)); return r;
}
__device__ __forceinline__ float bf_lo(uint32_t v) { return __uint_as_float(v << 16); }
__device__ __forceinline__ float bf_hi(uint32_t v) { return __uint_as_float(v & 0xffff0000u); }
__device__ __forceinline__ float round_bf16(float v) { return bf_lo(pack_bf16(v, 0.f)); }
__device__ __forceinline__ uint32_t mul_bf16x2(uint32_t a, uint32_t b) {
    uint32_t r; asm("mul.rn.bf16x2 %0, %1, %2;" : "=r"(r) : "r"(a), "r"(b)); return r;
}
__device__ __forceinline__ uint32_t sub_bf16x2(uint32_t a, uint32_t b) {
    uint32_t r; asm("sub.rn.bf16x2 %0, %1, %2;" : "=r"(r) : "r"(a), "r"(b)); return r;
}
__device__ __forceinline__ uint32_t mul2_bf16x2(uint32_t a, uint32_t hi, uint32_t lo) {
    uint32_t r; asm("fma.rn.bf16x2 %0, %1, %2, %3;" : "=r"(r) : "r"(a), "r"(hi), "r"(mul_bf16x2(a, lo))); return r;
}
__device__ __forceinline__ float tanh_fast(float x) { float r; asm("tanh.approx.f32 %0, %1;" : "=f"(r) : "f"(x)); return r; }
__device__ __forceinline__ float gelu_twice(float g) {
    return fmaf(g, tanh_fast(fmaf(g * g, 0.044715f * 0.7978845608f, 0.7978845608f) * g), g);
}
__device__ __forceinline__ uint32_t geglu2(uint32_t g2, uint32_t u2) {
    return mul_bf16x2(pack_bf16(gelu_twice(bf_lo(g2)), gelu_twice(bf_hi(g2))), u2);
}
__device__ __forceinline__ uint32_t silu2(float lo, float hi) {
    const uint32_t h = mul_bf16x2(pack_bf16(lo, hi), 0x3e803e80u);
    return pack_bf16(fmaf(bf_lo(h), tanh_fast(bf_lo(h)), bf_lo(h)), fmaf(bf_hi(h), tanh_fast(bf_hi(h)), bf_hi(h)));
}
__device__ __forceinline__ float ex2_fast(float x) { float r; asm("ex2.approx.ftz.f32 %0, %1;" : "=f"(r) : "f"(x)); return r; }
__device__ __forceinline__ void unpack8(uint4 v, float (&f)[8]) {
    f[0] = bf_lo(v.x); f[1] = bf_hi(v.x); f[2] = bf_lo(v.y); f[3] = bf_hi(v.y);
    f[4] = bf_lo(v.z); f[5] = bf_hi(v.z); f[6] = bf_lo(v.w); f[7] = bf_hi(v.w);
}
template <int N> __device__ __forceinline__ void fence_regs(float (&d)[N]) {
#pragma unroll
    for (int i = 0; i < N; i++) asm volatile("" : "+f"(d[i]) :: "memory");
}

__device__ __forceinline__ float rcp_fast(float x) { float r; asm("rcp.approx.ftz.f32 %0, %1;" : "=f"(r) : "f"(x)); return r; }
__device__ __forceinline__ float sqrt_fast(float x) { float r; asm("sqrt.approx.ftz.f32 %0, %1;" : "=f"(r) : "f"(x)); return r; }
__device__ __forceinline__ uint32_t max_bf16x2(uint32_t a, uint32_t b) {
    uint32_t r; asm("max.bf16x2 %0, %1, %2;" : "=r"(r) : "r"(a), "r"(b)); return r;
}
__device__ __forceinline__ uint32_t transpose8(uint32_t a) {
    uint32_t r; asm volatile("movmatrix.sync.aligned.m8n8.trans.b16 %0, %1;" : "=r"(r) : "r"(a)); return r;
}
__device__ __forceinline__ void mma_sync(uint32_t* d, const uint32_t* a, uint32_t b0, uint32_t b1, const uint32_t* c) {
    asm volatile("mma.sync.aligned.m16n8k16.row.col.f32.bf16.bf16.f32 {%0,%1,%2,%3}, {%4,%5,%6,%7}, {%8,%9}, {%10,%11,%12,%13};"
        : "=r"(d[0]), "=r"(d[1]), "=r"(d[2]), "=r"(d[3])
        : "r"(a[0]), "r"(a[1]), "r"(a[2]), "r"(a[3]), "r"(b0), "r"(b1), "r"(c[0]), "r"(c[1]), "r"(c[2]), "r"(c[3]));
}
template <int N> struct Floats {
    float f[N];
    __device__ __forceinline__ Floats() {}
    __device__ __forceinline__ Floats(const uint32_t* p) {
#pragma unroll
        for (int i = 0; i < N; i++) asm("mov.b32 %0, %1;" : "=f"(f[i]) : "r"(p[i]));
    }
    __device__ __forceinline__ void put(uint32_t* p) const {
#pragma unroll
        for (int i = 0; i < N; i++) asm("mov.b32 %0, %1;" : "=r"(p[i]) : "f"(f[i]));
    }
    __device__ __forceinline__ float& operator[](int i) { return f[i]; }
};
__device__ __forceinline__ uint32_t fresh_tid() { uint32_t r; asm volatile("mov.u32 %0, %%tid.x;" : "=r"(r)); return r; }
template <typename T> __device__ __forceinline__ T uniform(T v) { return __shfl_sync(0xffffffffu, v, 0); }

__device__ __forceinline__ uint32_t forecast(uint32_t n0, uint32_t c0, float cycles, uint32_t tag) {
    const uint32_t n = nanos();
    return n + (int)((n - n0) * cycles * rcp_fast((uint32_t)clock() - c0)) & ~3u | tag;
}
__device__ __forceinline__ uint32_t plan_word(uint32_t base, int lane) { return uniform(lds32(base + PLAN_OFF + lane * 4)); }

__device__ __forceinline__ void fold_operands(const Params& prm, uint32_t base, int slot, int mblk, uint32_t tag, int w, int lane) {
    uint4 v[9];
#pragma unroll
    for (int m = 0; m < 9; m++) v[m] = make_uint4(0, 0, 0, 0);
    const float* parts = prm.colsum + (slot * 2 + (lane >> 4)) * 1024 + w * 64 + (lane & 15) * 4;
    const float* const rows = &prm.stats[mblk * 128 + w * 64 + lane * 2].x;
#pragma unroll 1
    for (int spins = 0; spins < (1 << 16); spins++) {
        bool missing = false;
        asm volatile("" : "+l"(parts));
#pragma unroll
        for (int m = 0; m < 9; m++) {
            if (untagged(v[m], tag)) {
                missing = true;
                v[m] = ld_relaxed(m < 8 ? parts + m * 128 : rows);
            }
        }
        if (!missing) break;
    }
    float4 c = make_float4(0.f, 0.f, 0.f, 0.f);
#pragma unroll
    for (int m = 0; m < 8; m++) {
        c.x += __uint_as_float(v[m].x ^ tag); c.y += __uint_as_float(v[m].y ^ tag);
        c.z += __uint_as_float(v[m].z ^ tag); c.w += __uint_as_float(v[m].w ^ tag);
    }
    sts128(base + STAT_OFF + w * 512 + lane * 16, make_uint4(v[8].x ^ tag, v[8].y ^ tag, v[8].z ^ tag, v[8].w ^ tag));
    const uint32_t ca = base + AUX_OFF + w * 8192 + (lane >> 4) * 16384 + (lane & 15) * 8;
#pragma unroll
    for (int r = 0; r < 3; r++) {
        const uint32_t lo = pack_bf16(c.x, c.y), hi = pack_bf16(c.z, c.w);
        sts64f((ca ^ r * 16) + r * 128, __uint_as_float(lo), __uint_as_float(hi));
        c.x -= bf_lo(lo); c.y -= bf_hi(lo); c.z -= bf_lo(hi); c.w -= bf_hi(hi);
    }
    asm volatile("fence.proxy.async.shared::cta;" ::: "memory");
    __syncwarp();
}
__device__ __forceinline__ float2 fold(float (&acc)[128], uint32_t base, int wg) {
    const uint32_t id = fresh_tid(), sp = base + STAT_OFF + (id & 96) * 8 + (id & 28) * 4 + wg * 8;
    const uint32_t sel = id & 2 ? 0x4444 : (id & 1 ? 0x4432 : 0x3232);
    const float2 sa = lds64f(sp), sb = lds64f(sp + 128);
    mma_rank(acc, __byte_perm(__float_as_uint(sa.x), 0, sel), __byte_perm(__float_as_uint(sb.x), 0, sel), desc_b(base + AUX_OFF));
    return make_float2(sa.y, sb.y);
}

__device__ __forceinline__ void tail_gemm(const Params& prm, uint32_t base, uint32_t t0, unsigned epoch, int grp, int warp, int lane) {
    const uint32_t full = base + BAR_OFF, empty = full + 32, sig = full + 192, dep = full + 256, folded = full + 320;
    const uint32_t tag = 1 + (epoch & 1);
    auto plan = [&](uint32_t p, uint32_t word) { return p < 4 ? p * 64 + grp / 2 * 32 + 15 : word >> p % 4 * 8 & 255; };
    auto rows = [&](uint32_t job) { return job / 32 * 2 + grp % 2; };
    if (warp == 8) {
        if (elect_one()) { prefetch_map(&prm.xn); prefetch_map(&prm.a2); prefetch_map(&prm.wd_tail); }
#pragma unroll 1
        for (int p = 0, i = G1_STAGES; p < 8; p++) {
            const bool first = p < 4;
            if (p == 4) mbar_wait_warp(dep + 16, 0);
            const uint32_t job = plan(p, plan_word(base, lane));
#pragma unroll 1
            for (int k = p ? 0 : G1_STAGES; k <= job % 32; k++, i++) {
                if (WDPF && p == 3 && k % 2 == grp / 2)
                    asm volatile("{\n.reg .pred e;\nelect.sync _|e, 0xffffffff;\n"
                        "@e cp.async.bulk.prefetch.tensor.5d.L2.global [%0, {%2, %2, %1, %2, %3}];\n}"
                        :: "l"(&prm.wd_tail), "r"(k * 8), "r"(0), "r"(grp % 2 * 4) : "memory");
                if (i == 16 || i == 24 || k == 16) mbar_wait_warp(dep + (first ? i & 8 : 24), 0);
                TRACE_S(62, i, 16); TRACE_S(63, i, 4);
                mbar_wait_warp(empty + (i & 3) * 8, ~i >> 2 & 1);
                load_tail(base + (i & 3) * G1_STAGE_BYTES, full + (i & 3) * 8, first ? (p ? &prm.xn : &prm.x) : &prm.a2,
                          first ? &prm.wu_tail : &prm.wd_tail, (first ? 0 : DM) + k * 64, rows(job), first ? k * 2 : k * 8);
            }
        }
        return;
    }
    if (warp == 9) {
        const uint32_t n0 = nanos(), c0 = clock();
#pragma unroll 1
        for (int j = 0; j < 3; j++) {
            flag_wait<true>(prm.flags + (F_LN + j) * 512 + (j < 2 ? lane % 4 * 4 + grp : lane % 16) * 32, epoch * CNT_LN);
            fence_proxy_async();
            __syncwarp();
            if (lane == 0 && j < 2) mbar_arrive(dep + j * 8);
        }
        mbar_wait_warp(sig + 8, 0);
        if (lane == 0) st_relaxed(prm.flags + F_PACE * 512 + 64 + grp, forecast(n0, c0, DUE, tag));
        uint4 v, w;
#pragma unroll 1
        for (int spins = 0; spins < (1 << 19); spins++) {
            v = ld_relaxed(prm.flags + F_PACE * 512 + lane / 2 * 4);
            w = ld_relaxed(prm.flags + F_PACE * 512 + 64);
            if (!__any_sync(0xffffffffu, untagged(v, tag) || untagged(w, tag))) break;
            __nanosleep(256);
        }
        const uint32_t ref = uniform(v.x);
        const int due = min(max((int)((grp & 2 ? w.z : w.x) - ref), -100000), 100000) * 8;
        int late = max(max((int)(v.x - ref), (int)(v.y - ref)), max((int)(v.z - ref), (int)(v.w - ref)));
        late = min(max(max(late, __shfl_xor_sync(0xffffffffu, late, 2)), -100000), 100000) * 8 * BAL + lane / 4;
        TRACE_PUT(16 + lane / 4, late + (1 << 20));
        int place = 0, n = SHARE_MIN;
#pragma unroll 1
        for (int g = 0; g < 32; g += 4) place += __shfl_sync(0xffffffffu, late, g) > late;
        const bool swap = SWAP && (__reduce_add_sync(0xffffffffu, place + 1 & 2 ? late : -late) ^ w.x - w.z) >> 31;
        const bool mine = (place + 1 >> 1 & 1 ^ swap) == grp / 2;
#pragma unroll 1
        for (int j = 4 * SHARE_MIN; j < SHARE_SUM; j++) {
            const int most = __reduce_max_sync(0xffffffffu, mine && n < SHARE_MAX ? late : INT_MIN);
            if (j >= TLO && due + (j - 38) * 640 * 8 > most) break;
            if (j == 38) TRACE_PUT(32, most - due + (1 << 20));
            if (most == late) { n++; late -= STEPNS * 8; }
        }
        auto first = [](uint32_t bits, int n) { return bits & (1u << min(max(n, 0), 24)) - 1; };
        const uint32_t job = lane / 4 * 32 + n - 1;
        if (mine) st_relaxed(prm.flags + F_SHARE * 512 + rows(job) * 32,
                             epoch << 24 | first(0x2aaaaa, 2 * n) | first(0x104104, 6 * n - 66) | first(0x10410, 6 * n - 90) |
                             first(0x41041, 6 * n - 108));
        if (mine) TRACE_PUT(24 + lane / 4, n);
        sts32(base + PLAN_OFF, __reduce_or_sync(0xffffffffu, mine ? job << place / 2 * 8 : 0));
        if (lane == 0) mbar_arrive(dep + 16);
        flag_wait<true>(prm.flags + F_SECOND * 512 + lane % 16 * 32, epoch * CNT_LN);
        fence_proxy_async();
        __syncwarp();
        if (lane == 0) mbar_arrive(dep + 24);
        return;
    }
    if (warp > 9) {
#pragma unroll 1
        for (int j = 0; j < 8; j++) sts128(base + AUX_OFF + (warp - 10) * 8192 + (j & 4) * 4096 + (j & 3) * 512 + lane * 16, make_uint4(0, 0, 0, 0));
        while ((uint32_t)clock() - t0 < 9000) __nanosleep(256);
        fold_operands(prm, base, 8, grp, tag, warp - 10, lane);
        if (lane) return;
        mbar_arrive(folded);
        if (warp == 11) return;
        TRACE(60);
#pragma unroll 1
        for (int p = 0; p < 8; p++) {
            mbar_wait(sig + p * 8, 0);
            flag_add(prm.flags + (p < 4 ? F_EARLY : F_TAIL2) * 512 + rows(plan(p, lds32(base + PLAN_OFF))) * 32);
            TRACE_S(50, p, 3); TRACE_S(51, p, 7);
        }
        prm.epoch[blockIdx.x * 16] = epoch;
        TRACE_DUMP();
        return;
    }
    asm volatile("setmaxnreg.inc.sync.aligned.u32 %0;" :: "n"(CONSUMER_REGS) : "memory");
    const uint32_t da = desc_a(base + (warp >> 2) * 8192);
    uint4* out = prm.tail;
    float acc[128];
    uint32_t pk[64];
    float2 inv = make_float2(0.f, 0.f);
    int i = 0, last;
    uint32_t peer;
    asm volatile("mapa.shared::cluster.u32 %0, %1, %2;" : "=r"(peer) : "r"(empty), "r"(lane & 1));
    auto release = [&]() {
        if ((threadIdx.x & 126) == 0 && i <= last)
            asm volatile("mbarrier.arrive.shared::cluster.b64 _, [%0];" :: "r"(peer + (i - 1 & 3) * 8) : "memory");
    };
    auto store = [&](int j) {
        asm volatile("st.global.v4.u32 [%0], {%1,%2,%3,%4};" :: "l"(out + j / 2 * 8192 + j % 2 * 256),
                     "r"(pk[4 * j]), "r"(pk[4 * j + 1]), "r"(pk[4 * j + 2]), "r"(pk[4 * j + 3]) : "memory");
    };
    auto step = [&](int k, int left, int most) {
        mbar_wait(full + (i & 3) * 8, i >> 2 & 1);
        TRACE_S(45, warp * 128 + i, 0);
        if (warp >= 4 && left == (SMIN < 3 ? min(TSK, most) : TSK)) asm volatile("bar.sync 1, 256;" ::: "memory");
        mma_step_tail(acc, da + (i & 3) * (G1_STAGE_BYTES / 16), base + A_BYTES + (i & 3) * G1_STAGE_BYTES, k);
        if (warp < 4 && left == 1) asm volatile("bar.arrive 1, 256;" ::: "memory");
    };
    auto drip = [&](int p, int& n) {
        if (n > 0) { store(0); store(1); }
#pragma unroll
        for (int j = 8; j < 64; j++) asm volatile("mov.b32 %0, %1;" : "=r"(pk[j - 8]) : "r"(pk[j]));
        out += 8192;
        __syncwarp();
        if (--n == 0 && lane == 0) mbar_arrive(sig + p * 8 - 8);
    };
#pragma unroll
    for (int j = 0; j < 128; j++) asm volatile("mov.b32 %0, 0;" : "=f"(acc[j]));
#pragma unroll
    for (int j = 0; j < 64; j++) asm volatile("mov.b32 %0, 0;" : "=r"(pk[j]));
#pragma unroll 1
    for (int p = 0; p < 8; p++) {
        step(0, 0, 1);
        i++;
        const uint32_t word = plan_word(base, lane), job = plan(p, word);
        last = __dp4a(word & 0x1f1f1f1fu, 0x01010101u, 4u * G1_KSTEPS);
#pragma unroll 1
        for (int left = job % 32, n = p ? 8 : 0; left > 0; left--) {
            if (i == G1_KSTEPS - TFOLD) { mbar_wait(folded, 0); inv = fold(acc, base, warp >> 2); }
#pragma unroll 1
            do drip(p, n); while (n & 7 >> 31 - __clz(job % 32));
            step(1, left, job % 32);
            wg_wait<1>();
            release();
            i++;
        }
        wg_wait<0>();
        fence_regs(acc);
        release();
        if (p == 0) {
#pragma unroll
            for (int j = 0; j < 128; j++) acc[j] *= j & 2 ? inv.y : inv.x;
            fence_regs(acc);
        }
        if (warp == 4) TRACE_PUT(46 + p + p / 4 * 3, (uint32_t)clock());
#pragma unroll
        for (int j = 0; j < 64; j++) pk[j] = pack_bf16(acc[2 * j], acc[2 * j + 1]);
        out = prm.tail + p / 4 * NGEMM * 512 + rows(job) * 512 + threadIdx.x;
    }
#pragma unroll
    for (int j = 0; j < 16; j++) store(j);
    __syncwarp();
    TRACE_S(58, warp, 4);
    if (lane == 0) mbar_arrive(sig + 56);
}

__device__ __forceinline__ int gate_col(int t, int nslot) { return t == 2 ? 960 + nslot * 64 : max(t * 1024 - 1536, 0) + nslot * 128; }

struct Role {
    int rank, role, mblk, nslot;
    __device__ __forceinline__ Role() {
        uint32_t id;
        asm volatile("mov.u32 %0, %%ctaid.x;" : "=r"(id));
        const uint32_t cl = id / 2;
        rank = id & 1;
        role = pick(cl < 4, 32 + cl * 8, cl - 8 + max(4u, (cl - 1) * 37 >> 8)) * 2 + rank;
        mblk = role & 15; nslot = role >> 4;
    }
};

__global__ void __cluster_dims__(2, 1, 1) __launch_bounds__(384, 1)
fused_kernel(const __grid_constant__ Params prm) {
    TRACE_GET(c0);
    const uint32_t base = smem_u32(smem_raw) & ~1023u;
    const uint32_t bars = base + BAR_OFF;
    auto full1 = [&](int s) { return bars + s * 8; };
    auto empty1 = [&](int s) { return bars + 32 + s * 8; };
    auto full2 = [&](int s) { return bars + 64 + s * 8; };
    auto empty2 = [&](int s) { return bars + 128 + s * 8; };
    const uint32_t sig_bar = bars + 192, dep_bar = bars + 256, cs_bar = bars + 304, fold_bar = bars + 320, x_bar = bars + 352;
    const uint32_t halo_bar = dep_bar + 32;
    auto stage2 = [&](int q) { return base + q * G2_STAGE_BYTES; };
    const uint32_t aux = base + AUX_OFF;

    asm volatile("{\n.reg .pred p;\nsetp.eq.u32 p, %1, 0;\n@p mbarrier.init.shared::cta.b64 [%0], 1;\n"
        "fence.mbarrier_init.release.cluster;\nbarrier.cluster.arrive.relaxed.aligned;\n}" :: "r"(bars), "r"(threadIdx.x) : "memory");
    const int warp = __shfl_sync(0xffffffffu, threadIdx.x >> 5, 0);
    auto cluster_wait = []() { asm volatile("barrier.cluster.wait.acquire.aligned;" ::: "memory"); };
    if ((warp | (blockIdx.x & NGEMM)) == 8) {
        const Role r;
        asm volatile("{\n.reg .pred e;\nelect.sync _|e, 0xffffffff;\n"
            "@e prefetch.tensormap [%0];\n@e prefetch.tensormap [%1];\n}" :: "l"(&prm.x), "l"(&prm.wg + r.rank) : "memory");
        cluster_wait();
        load_stage1(base, base + A_BYTES + r.rank * 16384, full1(0), &prm.x, &prm.wg + r.rank, &prm.wg + r.rank, 0, r.mblk * 64,
                    r.nslot * 128, r.nslot * 128 + 64, 0, stream_policy());
    } else {
        cluster_wait();
    }
    const uint32_t t0 = clock();
    if (TEARLY) {
        uint32_t cta;
        asm volatile("mov.u32 %0, %%ctaid.x;" : "=r"(cta));
        if ((warp | (~cta & NGEMM)) == TEW) load_tail(base, full1(0), &prm.x, &prm.wu_tail, 0, cta - NGEMM, 0);
    }
    asm volatile("{\n.reg .pred e, q;\nelect.sync _|e, 0xffffffff;\nsetp.ne.and.u32 q, %2, 0, e;\n"
        "@q mbarrier.init.shared::cta.b64 [%0], %1;\n@e mbarrier.init.shared::cta.b64 [%0 + 8], %1;\n"
        "@e mbarrier.init.shared::cta.b64 [%0 + 16], %1;\n@e mbarrier.init.shared::cta.b64 [%0 + 24], %1;\n"
        "fence.mbarrier_init.release.cluster;\nbarrier.cluster.arrive.relaxed.aligned;\n}"
        :: "r"(bars + warp * 32), "r"(1 << (0x10fa08 >> warp * 2 & 3)), "r"(warp) : "memory");
    const int lane = threadIdx.x & 31;
    const Role me;
    const int rank = me.rank, role = me.role, mblk = me.mblk, nslot = me.nslot;
    const CUtensorMap* const w0 = &prm.wg + rank;

    unsigned* const flags = prm.flags + mblk * 32;
    if (warp >= 8) {
        asm volatile("setmaxnreg.dec.sync.aligned.u32 %0;" :: "n"(AUX_REGS));
        if (warp == 9) { TRACE_CLEAR(); TRACE_GT(0); TRACE_PUT(1, c0); }
        if ((warp | (~blockIdx.x & NGEMM)) == 8) {
#pragma unroll 1
            for (int i = TEARLY; i < G1_STAGES; i++) {
                if (i == 1) cluster_wait();
                TRACE_S(57, i, 1);
                load_tail(base + i * G1_STAGE_BYTES, full1(i), &prm.x, &prm.wu_tail, i * 64, blockIdx.x - NGEMM, i * 2);
            }
        } else {
            cluster_wait();
        }
    }

    if (blockIdx.x >= NGEMM) {
        if (warp < 8) cluster_wait();
        const uint32_t seen = __ldcg(prm.epoch + blockIdx.x * 16);
        tail_gemm(prm, base, t0, seen + 1, blockIdx.x - NGEMM, warp, lane);
    } else if (warp == 9) {
        const unsigned epoch = __ldcg(prm.epoch + blockIdx.x * 16 + 2) + 1;
        const uint32_t n0 = nanos(), c1 = clock();
        {
            const __nv_bfloat16* const w = prm.pwu + ((mblk >> 1) * 128 + lane / 2) * DF + gate_col(4, nslot) + 96 + rank * 16 + lane % 2 * 8;
            uint4 v[8];
            float cs[8], f[8];
            mbar_wait(empty1(C2AT & 3), 0);
            if (C2AT > 3) mbar_wait(empty1(C2AT & 3), 1);
#pragma unroll
            for (int j = 0; j < 8; j++) v[j] = __ldg(reinterpret_cast<const uint4*>(w + j * 16 * DF));
            unpack8(v[0], cs);
#pragma unroll
            for (int j = 1; j < 8; j++) {
                unpack8(v[j], f);
#pragma unroll
                for (int d = 0; d < 8; d++) cs[d] += f[d];
            }
#pragma unroll
            for (int d = 0; d < 4; d++)
                cs[d] = (lane & 16 ? cs[d + 4] : cs[d]) + __shfl_xor_sync(0xffffffffu, lane & 16 ? cs[d] : cs[d + 4], 16);
#pragma unroll
            for (int d = 0; d < 2; d++) {
                cs[d] = (lane & 8 ? cs[d + 2] : cs[d]) + __shfl_xor_sync(0xffffffffu, lane & 8 ? cs[d] : cs[d + 2], 8);
                cs[d] += __shfl_xor_sync(0xffffffffu, cs[d], 4);
                cs[d] += __shfl_xor_sync(0xffffffffu, cs[d], 2);
            }
            if (!(lane & 6))
                st_tagged(prm.colsum + (16 + nslot / 4) * 1024 + (mblk >> 1) * 128 + nslot % 4 * 32 + rank * 16 + lane % 2 * 8 + (lane >> 3) * 2,
                          cs[0], cs[1], 1 + (epoch & 1));
            TRACE(61);
        }
        if (lane == 0) {
            mbar_wait(sig_bar, 0);
            TRACE(11);
            flag_add(flags + F_LN * 512);
            TRACE(42);
            flag_wait(flags + F_LN * 512, epoch * CNT_LN);
            fence_proxy_async();
            mbar_arrive(dep_bar);
            mbar_wait(sig_bar + 56, 0);
            flag_add(flags + F_LN2 * 512);
            flag_wait(flags + F_LN2 * 512, epoch * CNT_LN);
            fence_proxy_async();
            mbar_arrive(dep_bar + 40);
            TRACE(59);
            prm.epoch[blockIdx.x * 16 + 2] = epoch;
#pragma unroll 1
            for (int p = 3; p < 7; p++) {
                mbar_wait(sig_bar + (p == 3 ? 16 : p * 8), 0);
                TRACE_S(37, p, 4);
                flag_add(flags + (p - (p < F_EARLY)) * 512);
                TRACE_S(43, p, 4);
                if (p == 3 && rank == 0) {
                    mbar_wait(sig_bar + 24, 0);
                    st_relaxed(prm.flags + F_PACE * 512 + mblk * 4 + nslot, forecast(n0, c1, REST, 1 + (epoch & 1)));
                }
            }
        }
    } else if (warp < 8) {
        asm volatile("setmaxnreg.inc.sync.aligned.u32 %0;" :: "n"(CONSUMER_REGS));
        const int wg = __shfl_sync(0xffffffffu, threadIdx.x >> 7, 0);
        const int cw = threadIdx.x >> 5;
        const int tid = threadIdx.x & 127;
        int spins = 1 << 18;
        float acc[128];
        uint32_t pk[64];
#pragma unroll
        for (int i = 0; i < 64; i++) asm volatile("mov.b32 %0, 0;" : "=r"(pk[i]));
#pragma unroll
        for (int i = 0; i < 128; i++) asm volatile("mov.b32 %0, 0;" : "=f"(acc[i]));
        cluster_wait();

        auto row0 = [&](uint32_t id) { return mblk * 128 + (id & 96) + wg; };
        __nv_bfloat16* optr = prm.pxn + (mblk * 128 + nslot * 16 + cw * 2) * DM + lane * 8;
        uint64_t da = desc_a(base + wg * 8192) | (uint64_t)prm.hi[0] << 32, db = desc_b(base + A_BYTES) | (uint64_t)prm.hi[1] << 32;
        auto next1 = [](int s) { return ((s + 1) % G1_STAGES - s) * G1_STAGE_BYTES; };
        auto next2 = [](int q) { return ((q + 1) % G2_STAGES - q) * G2_STAGE_BYTES; };
        uint32_t peer_bars;
        asm volatile("mapa.shared::cluster.u32 %0, %1, %2;" : "=r"(peer_bars) : "r"(bars), "r"(tid & 1));
        if (tid >= 2) peer_bars = 0;
        auto release = [&](uint32_t bar) {
            if (peer_bars) asm volatile("mbarrier.arrive.shared::cluster.b64 _, [%0];" :: "r"(peer_bars + (bar - bars)) : "memory");
        };
        auto up = [](int i) { return 32 + (i & 24) + (i & 3) * 2 + (i >> 2 & 1); };
        auto store_pk = [&](__nv_bfloat16* p, int j) {
            asm volatile("st.global.v4.u32 [%0], {%1,%2,%3,%4};"
                         :: "l"(p), "r"(pk[4 * j]), "r"(pk[4 * j + 1]), "r"(pk[4 * j + 2]), "r"(pk[4 * j + 3]) : "memory");
        };
        auto chunk_geglu = [&](int j) {
#pragma unroll
            for (int i = 4 * j; i < 4 * j + 4; i++) pk[i] = geglu2(pk[i], pk[up(i)]);
            store_pk(optr + (j & 1) * 16 * K2 + (j >> 1) * 32, j);
        };
        auto signal_stores = [&](int p) { __syncwarp(); if (lane == 0) mbar_arrive(sig_bar + p * 8); };

        auto chunk_ln = [&](int k) {
            Floats<6> mo(pk + 32);
            if (k == 0) {
                const uint4* xp = reinterpret_cast<const uint4*>(prm.px + (optr - prm.pxn));
                pk[38] = __ldcg(prm.epoch + blockIdx.x * 16 + 2);
#pragma unroll
                for (int i = 0; i < 8; i++) {
                    const uint4 v = ldg_stream(xp + i * 32, stream_policy());
                    pk[4 * i] = v.x; pk[4 * i + 1] = v.y; pk[4 * i + 2] = v.z; pk[4 * i + 3] = v.w;
                }
            } else if (k >= LN_STEP && k < LN_STEP + 3) {
                if (k == LN_STEP) {
                    mo[0] = bf_lo(uniform(pk[0])); mo[1] = bf_lo(uniform(pk[16]));
                    mo[2] = mo[3] = mo[4] = mo[5] = 0.f;
                }
#pragma unroll
                for (int i = (k - LN_STEP) * 11; i < (k - LN_STEP) * 11 + 11 && i < 32; i++) {
                    const int r = i & 1;
                    const uint32_t w = pk[r * 16 + i / 2];
                    const float lo = bf_lo(w) - mo[r], hi = bf_hi(w) - mo[r];
                    mo[2 + r] += lo + hi;
                    mo[4 + r] = fmaf(hi, hi, fmaf(lo, lo, mo[4 + r]));
                }
                mo.put(pk + 32);
            } else if (k == LN_STEP + 3) {
                const bool second = lane & 16;
                float m1 = (second ? mo[3] : mo[2]) + __shfl_xor_sync(0xffffffffu, second ? mo[2] : mo[3], 16);
                float m2 = (second ? mo[5] : mo[4]) + __shfl_xor_sync(0xffffffffu, second ? mo[4] : mo[5], 16);
#pragma unroll
                for (int o = 8; o > 0; o >>= 1) {
                    m1 += __shfl_xor_sync(0xffffffffu, m1, o);
                    m2 += __shfl_xor_sync(0xffffffffu, m2, o);
                }
                m1 *= 1.f / DM;
                const float var = fmaxf(fmaf(-m1, m1, m2 * (1.f / DM)), 0.f);
                const float mean = round_bf16((second ? mo[1] : mo[0]) + m1);
                const float inv = rcp_fast(round_bf16(sqrt_fast(round_bf16(round_bf16(var) + 1e-5f))));
                if ((lane & 15) == 0) st_tagged(prm.stats + (uint32_t)(optr - prm.pxn) / DM + second, -mean, inv, 2 - (pk[38] & 1));
                const uint32_t split = pack_bf16(inv - round_bf16(inv), inv);
#pragma unroll
                for (int r = 0; r < 2; r++) {
                    const uint32_t f = __shfl_sync(0xffffffffu, split, r * 16);
                    pk[32 + 3 * r] = __byte_perm(__shfl_sync(0xffffffffu, __float_as_uint(mean), r * 16), 0, 0x3232);
                    pk[33 + 3 * r] = __byte_perm(f, 0, 0x3232);
                    pk[34 + 3 * r] = __byte_perm(f, 0, 0x1010);
                }
            } else if (k >= LN_STEP + 4 && k < LN_STEP + 8) {
#pragma unroll
                for (int i = k - LN_STEP - 4; i < 8; i += 4) {
                    const uint32_t* n = pk + 32 + i / 4 * 3;
#pragma unroll
                    for (int j = 4 * i; j < 4 * i + 4; j++) pk[j] = mul2_bf16x2(sub_bf16x2(pk[j], n[0]), n[1], n[2]);
                    store_pk(optr + i * 256, i);
                }
                if (k == LN_STEP + 5 || k == LN_STEP + 7) signal_stores(k == LN_STEP + 5 ? 0 : 7);
            } else if (k == FOLD_STEP) {
                mbar_wait(fold_bar, 0, spins);
                const float2 inv = fold(acc, base, wg);
                mo[0] = inv.x; mo[1] = inv.y;
                mo.put(pk + 32);
            }
        };

        auto halo = [&]() { const uint32_t id = fresh_tid(); return aux + (id & 96) * 128 + (id & 128) * 16 + (id & 31) * 4; };
        auto put = [&](uint32_t a, uint32_t v0, uint32_t v1) {
            asm volatile("st.shared.u32 [%0], %1;\nst.shared.u32 [%0 + 128], %2;" :: "r"(a + HALO_BYTES), "r"(v0), "r"(v1) : "memory");
        };
        auto get = [&](uint32_t a, uint32_t& v0, uint32_t& v1) {
            asm volatile("ld.shared.u32 %0, [%2];\nld.shared.u32 %1, [%2 + 128];" : "=r"(v0), "=r"(v1) : "r"(a) : "memory");
        };
        auto publish = [&](int p) { asm volatile("fence.proxy.async.shared::cta;" ::: "memory"); signal_stores(p); };
        const uint32_t zero[4] = {0, 0, 0, 0};
        auto meet = [&](int n, int k, uint32_t id) {
            if (n == 15 - MEET)
                asm volatile("{\n.reg .b32 c;\nmov.u32 c, %%clock;\nbar.arrive %1, 256;\nlop3.b32 %0, %0, c, 1, 0x70;\n}"
                             : "+r"(peer_bars) : "r"(2 + id / 128) : "memory");
            if (n == 15) {
                asm volatile("{\n.reg .b32 c;\nmov.u32 c, %%clock;\nbar.sync %1, 256;\nlop3.b32 %0, %0, c, 1, 0x70;\n}"
                             : "+r"(peer_bars) : "r"(3 - id / 128) : "memory");
                mma_step(acc, da, db, next1(k & 3), k);
                asm volatile("// batch step");
            }
        };
        auto mix_qk = [&]() {
            uint32_t c[2][4];
            const uint32_t a = halo(), id = fresh_tid();
            if (EREL) { wg_wait<0>(); release(empty1((MIXQ - 1) & 3)); }
            mbar_wait(halo_bar, 0, spins);
#pragma unroll
            for (int n = 0; n < 16; n++) {
                const int b = 1 - n / 8, h = (n & 4) / 2 + n % 2, j = n / 2 % 2;
                uint32_t* const kq = pk + 32 + 8 * h + 4 * j;
                uint32_t* const q = pk + 8 * h + 4 * b;
                mma_sync(j ? q : c[n % 2], kq, q[2 * j], q[2 * j + 1], j ? c[n % 2] : zero);
                if (b) get(a + (h * 2 + j) * 256, kq[1], kq[3]);
                meet(n, MIXQ, id);
            }
        };
        auto chunk_qk = [&](int k) {
            constexpr float LOG2E = 1.4426950408889634f;
            uint32_t* const l = pk + 32;
            Floats<16> e(pk);
            if (k == KK) {
                const uint32_t a = halo();
#pragma unroll
                for (int i = 0; i < 8; i++) put(a + i * 256, pk[33 + 4 * i], pk[35 + 4 * i]);
                publish(1);
            } else if (k == MIXQ + 1) {
                const uint32_t id = fresh_tid();
                const bool u0 = id % 32 / 4 > id % 4 * 2, u1 = id % 32 / 4 > id % 4 * 2 + 1;
                const uint32_t gone = row0(id) < 2 ? (u0 ? 0xffffu : 0u) | (u1 ? 0xffff0000u : 0u) : 0u;
#pragma unroll
                for (int n = 0; n < 8; n++) {
                    const int b = n % 2;
                    const uint32_t* const c = pk + 4 * n;
                    uint32_t v = pack_bf16(__uint_as_float(pick(u0, c[2 - 2 * b], c[2 * b])), __uint_as_float(pick(u1, c[3 - 2 * b], c[1 + 2 * b])));
                    v = mul2_bf16x2(v, 0x3e353e35u, 0x379e379eu);
                    if (!b) v = v & ~gone | 0xce6ece6eu & gone;
                    l[n] = transpose8(v);
                }
            } else if (k == MIXQ + 2) {
#pragma unroll
                for (int h = 0; h < 4; h++) {
                    uint32_t m = max_bf16x2(__byte_perm(l[2 * h], l[2 * h + 1], 0x5410), __byte_perm(l[2 * h], l[2 * h + 1], 0x7632));
                    m = max_bf16x2(m, __shfl_xor_sync(0xffffffffu, m, 1));
                    m = max_bf16x2(m, __shfl_xor_sync(0xffffffffu, m, 2));
#pragma unroll
                    for (int n = 2 * h; n < 2 * h + 2; n++) {
                        const float f = -LOG2E * (n % 2 ? bf_hi(m) : bf_lo(m));
                        e[2 * n] = ex2_fast(fmaf(bf_lo(l[n]), LOG2E, f));
                        e[2 * n + 1] = ex2_fast(fmaf(bf_hi(l[n]), LOG2E, f));
                    }
                }
                e.put(pk);
            } else if (k == MIXQ + 3) {
                uint32_t p[8];
#pragma unroll
                for (int n = 0; n < 8; n++) {
                    float sum = e[2 * n] + e[2 * n + 1];
                    sum += __shfl_xor_sync(0xffffffffu, sum, 1);
                    sum += __shfl_xor_sync(0xffffffffu, sum, 2);
                    const float r = rcp_fast(sum);
                    p[n] = pack_bf16(e[2 * n] * r, e[2 * n + 1] * r);
                }
                const uint32_t a = aux + 5 * HALO_BYTES + fresh_tid() * 16;
                sts128(a, make_uint4(p[0], p[1], p[2], p[3]));
                sts128(a + 4096, make_uint4(p[4], p[5], p[6], p[7]));
            }
        };
        auto values = [&](int h) { return pk + (h & 2) * 16 + (h & 1) * 8; };
        auto mix_pv = [&]() {
            uint32_t lo[8], hi[8];
            const uint32_t id = fresh_tid();
            const uint32_t keep = (id % 4 * 2 > id % 32 / 4 ? 0xffffu : 0u) | (id % 4 * 2 + 1 > id % 32 / 4 ? 0xffff0000u : 0u);
            const uint4 p0 = lds128(aux + 5 * HALO_BYTES + id * 16), p1 = lds128(aux + 6 * HALO_BYTES + id * 16);
            const uint32_t p[8] = {p0.x, p0.y, p0.z, p0.w, p1.x, p1.y, p1.z, p1.w};
#pragma unroll
            for (int n = 0; n < 8; n++)
                asm volatile("and.b32 %0, %2, %3;\nand.b32 %1, %2, %4;" : "=r"(lo[n]), "=r"(hi[n])
                             : "r"(p[n]), "r"(n % 2 ? keep : ~keep), "r"(n % 2 ? ~keep : keep));
            if (EREL) { wg_wait<0>(); release(empty1((MIXV - 1) & 3)); }
            mbar_wait(halo_bar, 1, spins);
#pragma unroll
            for (int n = 0; n < 16; n++) {
                const int i = (n & 8) / 2 + (n & 2) + (n & 4) / 4;
                mma_sync(pk + 4 * (n ^ 4), pk + 4 * (n ^ 4), lo[i], hi[i], zero);
                meet(n, MIXV, id);
            }
        };
        auto chunk_pv = [&](int k) {
            if (k >= VK && k < VK + VN) {
                const uint32_t a = halo();
#pragma unroll
                for (int h = (k - VK) * 4 / VN; h < (k - VK + 1) * 4 / VN; h++) {
                    uint32_t* const w = values(h);
                    uint32_t v[8];
#pragma unroll
                    for (int i = 0; i < 8; i++) v[i] = transpose8(w[h < 2 ? (i & 1) + (i & 2) * 2 + (i & 4) / 2 : (i & 1) * 2 + (i & 2) / 2 + (i & 4)]);
#pragma unroll
                    for (int i = 0; i < 8; i++) w[i] = v[i];
                    put(a + h * 512, w[2], w[3]);
                    put(a + h * 512 + 256, w[6], w[7]);
                }
                if (k == VK + VN - 1) publish(3);
            } else if (k == MIXV - 1) {
                const uint32_t a = halo(), id = fresh_tid();
                optr = prm.pa2 + (size_t)(row0(id) + id % 4 * 4) * K2 + nslot * 128 + (id & 28) * 2;
                mbar_wait(halo_bar, 1, spins);
#pragma unroll
                for (int n = 0; n < 8; n++) {
                    uint32_t* const w = values(n / 2) + n % 2 * 4;
                    w[16] = w[0]; w[17] = w[1];
                    get(a + n * 256, w[18], w[19]);
                }
            } else if (k > MIXV && k <= MIXV + OVS) {
#pragma unroll
                for (int j = 0; j < 8; j++) {
                    if (j * OVS / 8 != k - MIXV - 1) continue;
                    Floats<15> c(pk + j / 2 * 16 + j % 2);
                    asm volatile("st.global.v4.u32 [%0], {%1,%2,%3,%4};"
                                 :: "l"(optr + ((~j & 2) * 8 + j % 2 * 2) * K2 + j / 4 * 64), "r"(pack_bf16(c[0], c[2])),
                                    "r"(pack_bf16(c[4], c[6])), "r"(pack_bf16(c[8], c[10])), "r"(pack_bf16(c[12], c[14])) : "memory");
                }
                if (k == MIXV + OVS) signal_stores(4);
            }
        };

        TRACE_SLOT(tile_slot, 16 + wg * 8);
#pragma unroll 1
        for (int t = 0; t < G1_TILES; t++) {
#pragma unroll
            for (int k = 0; k < G1_KSTEPS; k++) {
                const int s = k & 3;
                if (k % TOP == 0) asm volatile("" : "+r"(t));
                TRACE_STEP(t, k, 0);
                mbar_wait(full1(s), (k >> 2) & 1, spins);
                if (k == 0) TRACE_S(12, t, 0);
                TRACE_STEP(t, k, 1);
                if (wg == 1 && k == G1_KSTEPS - (t == 4 ? SK4 : G1_SKEW)) asm volatile("bar.sync 1, 256;" ::: "memory");
                if (k == MIXV && t == 3) mix_pv();
                else if (k == MIXQ && t == 2) mix_qk();
                else if (t == G1_TILES - 1) mma_step224(acc, da, db, next1(s), k);
                else mma_step(acc, da, db, next1(s), k);
                if (wg == 0 && k == G1_KSTEPS - 1) asm volatile("bar.arrive 1, 256;" ::: "memory");
                wg_wait<1>();
                if (k > 0 && !(EREL && (k == MIXV && t == 3 || k == MIXQ && t == 2))) release(empty1((k - 1) & 3));
                TRACE_STEP(t, k, 2);
                if (t == 0) chunk_ln(k);
                if (k >= 1 && k <= 8 && ((k < GV || k > GV + 3 ? 0x12 : 0x1a) >> t & 1)) {
                    chunk_geglu(k < GV ? k - 1 : (k > GV + 3 ? k - 5 : k - GV + 4));
                    if (k == 8 && t != 3) signal_stores(t + 1);
                }
                if (t == 2) chunk_qk(k);
                if (t == 3) chunk_pv(k);
                if (k == (MIXV + OVS > 13 ? MIXV + OVS : 13)) {
                    const uint32_t id = fresh_tid();
                    optr = prm.pa2 + (size_t)(row0(id) + (id & 28) / 2) * K2 + DM + gate_col(t, nslot) + id % 4 * 8;
                    asm volatile("" : "+l"(optr));
                }
            }
            wg_wait<0>();
            fence_regs(acc);
            release(empty1(3));
            if (t == 0) {
                Floats<2> inv(pk + 32);
#pragma unroll
                for (int i = 0; i < 128; i++) acc[i] *= inv[i / 2 % 2];
                fence_regs(acc);
            }
#pragma unroll
            for (int i = 0; i < 64; i++) {
                const int e = i < 32 ? (i & ~7) * 2 + (i & 3) * 4 + (i & 4) / 2 : i * 2;
                pk[i] = pack_bf16(acc[e], acc[e + 1]);
            }
            TRACE_NEXT(tile_slot);
        }

        float accd[64], accs[64];
#pragma unroll
        for (int i = 0; i < 64; i++) accd[i] = 0.f;
#pragma unroll
        for (int u = 0; u < G2_HEAD; u++) {
            const int q = u % G2_STAGES;
            mbar_wait(full2(q), (u / G2_STAGES) & 1, spins);
            if (u % 2) mma_step_c(accd, da, db, next2(q), u);
            else mma_step(accd, da, db, next2(q), u);
            wg_wait<1>();
            if (u > 0) release(empty2((u - 1) % G2_STAGES));
            if (u == TLD) {
#pragma unroll
                for (int i = 0; i < 2; i++) {
                    const uint4 v = ldg_stream(prm.tail + role * 512 + i * 256 + threadIdx.x, stream_policy());
                    pk[56 + 4 * i] = v.x; pk[57 + 4 * i] = v.y; pk[58 + 4 * i] = v.z; pk[59 + 4 * i] = v.w;
                }
            }
            if (u >= 1) {
                const int j = (u - 1) / 2;
#pragma unroll
                for (int i = 2 * u - 2; i < 2 * u; i++) pk[i] = geglu2(pk[i], pk[up(i)]);
                if (u % 2 == 0) store_pk(optr + (j & 1) * 16 * K2 + (j >> 1) * 32, j);
            }
            if (u == G2_HEAD - 1) signal_stores(6);
        }
        auto down = [&](int q, uint32_t phase, bool narrow, bool busy = false) {
            mbar_wait(full2(q), phase, spins);
            if (narrow) mma_step96(accd, da, db, next2(q), 1);
            else if (busy) mma_step_c(accd, da, db, next2(q), 1);
            else mma_step(accd, da, db, next2(q), 1);
            wg_wait<1>();
            release(empty2((q + G2_STAGES - 1) % G2_STAGES));
        };
        uint32_t shared_steps = plan_word(base, lane);
        down(5, 0, false);
#pragma unroll 1
        for (uint32_t r = 3; r < 9; r++, shared_steps >>= G2_STAGES) {
#pragma unroll
            for (int q = 0; q < G2_STAGES; q++) down(q, r & 1, (q || SMAX > 18) && shared_steps >> q & 1);
        }
        down(0, 1, false);
        down(1, 1, false, true);
        TRACE_NEXT(tile_slot);
#pragma unroll
        for (int i = 0; i < 64; i++) accs[i] = 0.f;
        uint32_t gk[32], xr[32];
        const uint32_t xs = aux + cw * 2048;
        const uint32_t xrow = xs + ((lane & 7) + ((lane >> 3) & 1) * 8) * 128;
        auto xaddr = [&](int j) { return xrow + (j >> 2) * 16384 + (((((j & 3) * 2) + (lane >> 4)) ^ (lane & 7)) << 4); };
#pragma unroll
        for (int u = G2_DSTEPS; u < G2_KSTEPS; u++) {
            const int q = u % G2_STAGES, v = u - G2_DSTEPS;
            mbar_wait(full2(q), (u / G2_STAGES) & 1, spins);
            if (wg == 1 && u == G2_KSTEPS - G2_SKEW) {
                if (G2_SKEW == G2_STAGES) { wg_wait<0>(); release(empty2((u - 1) % G2_STAGES)); peer_bars = 0; }
                asm volatile("bar.sync 1, 256;" ::: "memory");
            }
            if (u % 2) mma_step_c(accs, da, db, next2(q), v);
            else mma_step(accs, da, db, next2(q), v);
            if (G2_SKEW > 0 && wg == 0 && u == G2_KSTEPS - 1) asm volatile("bar.arrive 1, 256;" ::: "memory");
            if (v == TLD2) {
                TRACE_S(32, wg, 0);
                mbar_wait(dep_bar + 24, 0, spins);
                TRACE_S(33, wg, 0);
#pragma unroll
                for (int i = 0; i < 2; i++) {
                    const uint4 w = ldg_stream(prm.tail + (NGEMM + role) * 512 + i * 256 + threadIdx.x, stream_policy());
                    gk[24 + 4 * i] = w.x; gk[25 + 4 * i] = w.y; gk[26 + 4 * i] = w.z; gk[27 + 4 * i] = w.w;
                }
            }
#pragma unroll
            for (int i = 0; i < 32; i++) {
                if (v == (i < 24 ? i / 4 + 1 : TLD2 + (i < 28 ? GA : GB)))
                    gk[i] = i < 24 ? silu2(accd[2 * i], accd[2 * i + 1])
                                   : silu2(accd[2 * i] + bf_lo(gk[i]), accd[2 * i + 1] + bf_hi(gk[i]));
            }
            if (v == XLD) mbar_wait(x_bar, 0, spins);
            if (v >= XLD && v < XLD + 4) {
#pragma unroll
                for (int j = 2 * (v - XLD); j < 2 * (v - XLD + 1); j++)
                    asm volatile("ldmatrix.sync.aligned.m8n8.x4.shared.b16 {%0,%1,%2,%3}, [%4];"
                                 : "=r"(xr[4 * j]), "=r"(xr[4 * j + 1]), "=r"(xr[4 * j + 2]), "=r"(xr[4 * j + 3])
                                 : "r"(xaddr(j)) : "memory");
            }
            wg_wait<1>();
            if (v == 0) fence_regs(accd);
            if (u - 1 + G2_STAGES < G2_KSTEPS) release(empty2((u - 1) % G2_STAGES));
        }
        __nv_bfloat16* po = prm.pout + (row0(fresh_tid()) + (lane >> 3) * 2) * DM + nslot * 128 + 64 + (lane & 7) * 8;
        uint32_t so = xs + 16384 + (lane >> 3) * 128 + (((lane & 7) ^ (lane >> 3)) << 4);
        const int c0 = uniform(nslot * 128), c1 = uniform(row0(fresh_tid()) >> 1);
        const uint32_t xu = uniform(xs);
        asm volatile("" : "+l"(po), "+r"(so));
        wg_wait<0>();
        fence_regs(accs);
        TRACE_NEXT(tile_slot);
        TRACE_END();
#pragma unroll
        for (int j = 0; j < 8; j++) {
            uint32_t r[4];
#pragma unroll
            for (int i = 0; i < 4; i++) {
                const int e = j * 4 + i;
                asm("fma.rn.bf16x2 %0, %1, %2, %3;" : "=r"(r[i]) : "r"(pack_bf16(accs[2 * e], accs[2 * e + 1])), "r"(gk[e]), "r"(xr[e]));
            }
            asm volatile("stmatrix.sync.aligned.m8n8.x4.shared.b16 [%0], {%1,%2,%3,%4};"
                         :: "r"(xaddr(j)), "r"(r[0]), "r"(r[1]), "r"(r[2]), "r"(r[3]) : "memory");
            if (j == 3)
                asm volatile("{\n.reg .pred e;\nfence.proxy.async.shared::cta;\nbar.warp.sync 0xffffffff;\nelect.sync _|e, 0xffffffff;\n"
                    "@e cp.async.bulk.tensor.3d.global.shared::cta.bulk_group [%0, {%2, %3, %4}], [%1];\n}"
                    :: "l"(&prm.out), "r"(xu), "r"(c0), "r"(c1), "r"(wg) : "memory");
        }
        __syncwarp();
#pragma unroll
        for (int i = 0; i < 4; i++) {
            const uint4 v = lds128((so ^ (i & 1) * 64) + i * 512);
            asm volatile("st.global.v4.u32 [%0], {%1,%2,%3,%4};" :: "l"(po + i * 8 * DM), "r"(v.x), "r"(v.y), "r"(v.z), "r"(v.w) : "memory");
        }
        asm volatile("cp.async.bulk.commit_group;\ncp.async.bulk.wait_group.read 0;" ::: "memory");
        TRACE_LITE(10, clock());
        if (tid == 0) { TRACE_NEXT(tile_slot); if (wg == 1) TRACE_GT(13); TRACE_DUMP(); }
    } else if (warp > 9) {
        const int w = warp - 10;
        const unsigned epoch = __ldcg(prm.epoch + blockIdx.x * 16 + w) + 1;
        const uint32_t tag = 1 + (epoch & 1);
        TRACE_LITE(8, t0);
        const uint32_t at = (w ? CB : CA) >> (CIDX) * 4 & 15;
        mbar_wait(empty1(at & 3), 0);
        mbar_wait(empty1(at & 3), at >> 3);
        if (elect_one()) {
            mbar_expect_tx(cs_bar + w * 8, 16384);
            asm volatile("cp.async.bulk.tensor.2d.shared::cluster.global.mbarrier::complete_tx::bytes [%0], [%1, {%3, %5}], [%2];\n"
                "cp.async.bulk.tensor.2d.shared::cluster.global.mbarrier::complete_tx::bytes [%0 + 8192], [%1, {%4, %5}], [%2];"
                :: "r"(aux + w * 16384), "l"(w0), "r"(cs_bar + w * 8), "r"(nslot * 128), "r"(nslot * 128 + 64),
                   "r"(((mblk & ~1) + w) * 64) : "memory");
        }
        float cs[8];
#pragma unroll
        for (int d = 0; d < 8; d++) cs[d] = 0.f;
        const uint32_t wa = aux + w * 8192 + (lane >> 3) * 128 + (((lane & 7) ^ (lane >> 3)) << 4);
        uint4 v[8];
        auto fetch = [&](int h, uint32_t off) {
#pragma unroll
            for (int j = 0; j < 4; j++) v[h * 4 + j] = lds128((wa ^ (j & 1) * 64) + off + h * 2048 + j * 512);
        };
        auto add = [&](int h) {
#pragma unroll
            for (int j = 0; j < 4; j++) {
                float f[8];
                unpack8(v[h * 4 + j], f);
#pragma unroll
                for (int d = 0; d < 8; d++) cs[d] += f[d];
            }
        };
        if (CST) { mbar_wait(empty1(CST & 3), 0); mbar_wait(empty1(CST & 3), CST >> 3); }
        mbar_wait(cs_bar, 0);

        fetch(0, 0);
#pragma unroll 1
        for (int i = 0; i < 4; i++) {
            fetch(1, (i >> 1) * 16384 + (i & 1) * 4096);
            add(0);
            if (i == 1) mbar_wait(cs_bar + 8, 0);
            fetch(0, (i + 1 & 2) * 8192 + (~i & 1) * 4096);
            add(1);
        }
#pragma unroll
        for (int d = 0; d < 4; d++)
            cs[d] = (lane & 16 ? cs[d + 4] : cs[d]) + __shfl_xor_sync(0xffffffffu, lane & 16 ? cs[d] : cs[d + 4], 16);
#pragma unroll
        for (int d = 0; d < 2; d++)
            cs[d] = (lane & 8 ? cs[d + 2] : cs[d]) + __shfl_xor_sync(0xffffffffu, lane & 8 ? cs[d] : cs[d + 2], 8);
        st_tagged(prm.colsum + (nslot * 2 + rank) * 1024 + (mblk >> 1) * 128 + w * 64 + (lane & 7) * 8 + (lane >> 3) * 2,
                  cs[0], cs[1], tag);

        fold_operands(prm, base, nslot, mblk, tag, w, lane);
        if (lane == 0) {
            mbar_arrive(fold_bar);
            prm.epoch[blockIdx.x * 16 + w] = epoch;
            if (w == 0) {
                TRACE(35);
#pragma unroll 1
                for (uint32_t j = 0, n = 1 << 24; j < 4; n = (CNT_EARLY | CNT_LATE << 8 | 1 << 16) >> j * 8 & 255, j++) {
                    mbar_wait(sig_bar + (PB >> j * 8 & 255), 0);
                    const uint32_t v = flag_wait(flags + (F_SHARE + j) * 512, epoch * n);
                    fence_proxy_async();
                    if (j) mbar_arrive(dep_bar + j * 8);
                    else sts32(base + PLAN_OFF, v & 0xffffff);
                }
            } else {
#pragma unroll 1
                for (int j = 0; j < 2; j++) {
                    uint8_t* const h = prm.halo + (j * NGEMM + role) * HALO_BYTES;
                    unsigned* const f = prm.flags + F_HALO * 512 + role * 32;
                    mbar_wait(sig_bar + 8 + j * 16, 0);
                    TRACE_S(38, j, 0); TRACE_S(9, j, 1);
                    asm volatile("cp.async.bulk.global.shared::cta.bulk_group [%0], [%1], %2;\n"
                        "cp.async.bulk.commit_group;\ncp.async.bulk.wait_group 0;"
                        :: "l"(h + HALO_BYTES), "r"(aux + 4 * HALO_BYTES), "n"(HALO_BYTES) : "memory");
                    fence_proxy_async();
                    TRACE_S(39, j, 0); TRACE_S(10, j, 1);
                    flag_add(f);
                    TRACE_S(40, j, 0); TRACE_S(34, j, 1);
                    if (mblk) flag_wait(f - 32, epoch * 2 - 1 + j);
                    fence_proxy_async();
                    TRACE_S(41, j, 0); TRACE_S(36, j, 1);
                    mbar_expect_tx(halo_bar, HALO_BYTES);
                    asm volatile("cp.async.bulk.shared::cluster.global.mbarrier::complete_tx::bytes [%0], [%1], %2, [%3];"
                        :: "r"(aux), "l"(mblk ? h : prm.halo), "n"(HALO_BYTES), "r"(halo_bar) : "memory");
                }
            }
        }
    } else {
        constexpr int roll = ROLL;
#pragma unroll roll
        for (int k = 1; k < G1_STAGES; k++) {
            const uint32_t sa = base + k * G1_STAGE_BYTES;
            if (PACE0 + PACE) while ((uint32_t)clock() - t0 < (k == 3 ? PACE3 : PACE0 + (k - 1) * PACE)) {}
            load_stage1(sa, sa + A_BYTES + rank * 16384, full1(k), &prm.x, w0, w0, k * 64, mblk * 64, nslot * 128,
                        nslot * 128 + 64, 0, stream_policy());
        }
        if (elect_one()) {
            prefetch_map(&prm.xn); prefetch_map(&prm.wqkv);
            prefetch_map(&prm.a2); prefetch_map(&prm.wo); prefetch_map(&prm.wd); prefetch_map(&prm.out);
        }
        uint32_t ph = 0;
#pragma unroll 1
        for (int t = 0; t < G1_TILES; t++) {
            const int col1 = (t == 1 ? rank * DM + nslot * 128 : gate_col(t, nslot)) + 64;
            const int col0 = t == 2 ? 2 * DM + nslot * 128 + rank * 64 : col1 - 64;
            if (t == 1) { TRACE_PUT(2, t0); TRACE(14); mbar_wait_warp(dep_bar, 0); TRACE(3); }
#pragma unroll 1
            for (int k = t ? 0 : G1_STAGES; k < G1_KSTEPS; k++) {
                const int s = k & 3;
                if (t == 1 && k == 8) mbar_wait_warp(dep_bar + 40, 0);
                mbar_wait_warp(empty1(s), ph);
                const uint32_t sa = base + s * G1_STAGE_BYTES;
                load_stage1(sa, sa + A_BYTES + rank * 16384, full1(s), t ? &prm.xn : &prm.x, t == 1 || t == 2 ? &prm.wqkv : w0,
                            t == 1 ? &prm.wqkv : w0, k * 64, mblk * 64, col0, col1, t & 3,
                            stream_policy());
                if (s == 3) ph ^= 1;
            }
        }
        TRACE(4);
        mbar_wait_warp(dep_bar + 8, 0);
        TRACE(5);
        int q = 0, round = 4, own = SHARE_MAX; uint32_t ph2 = 1;
#pragma unroll 1
        for (int u = 0; u < G2_KSTEPS; u++) {
            if (u == G2_LATE) { TRACE(6); mbar_wait_warp(dep_bar + 16, 0); TRACE(7); }
            const uint32_t sa = stage2(q);
            const bool down = u < G2_DSTEPS;
            const int k = !down ? u - G2_DSTEPS : (u < 18 || u >= 40 || (SMAX == 18 && q == 0) ? own++ : (q & 1 ? u / 2 - 9 : round + (q ? q * 2 : 11)));
            mbar_wait_warp(u < G2_STAGES ? empty1((u * 2 + 1) / 3) : empty2(q), u < G2_STAGES ? ph : ph2);
            load_stage2(sa, sa + A_BYTES + rank * 8192, full2(q), &prm.a2, down ? &prm.wd : &prm.wo, (down ? DM : 0) + k * 64,
                        mblk * 64, nslot * 128 + rank * 64, down ? 0 : k * 2, down ? k * 2 : 0, stream_policy());
            if (u == (XK)) {
                if (elect_one()) {
                    mbar_expect_tx(x_bar, 32768);
                    tma_3d(aux, &prm.x, x_bar, nslot * 128, mblk * 64, 0, stream_policy());
                    tma_3d(aux + 16384, &prm.x, x_bar, nslot * 128 + 64, mblk * 64, 0, stream_policy());
                }
                __syncwarp();
            }
            if (++q == G2_STAGES) { q = 0; ph2 ^= 1; round++; }
        }
        TRACE(8);
    }
}

typedef CUresult (*EncodeFn)(CUtensorMap*, CUtensorMapDataType, cuuint32_t, void*, const cuuint64_t*, const cuuint64_t*,
                             const cuuint32_t*, const cuuint32_t*, CUtensorMapInterleave, CUtensorMapSwizzle,
                             CUtensorMapL2promotion, CUtensorMapFloatOOBfill);

void encode(EncodeFn fn, CUtensorMap* m, const void* ptr, int rank, const cuuint64_t* dims, const cuuint64_t* strides,
            const cuuint32_t* box) {
    const cuuint32_t es[5] = {1, 1, 1, 1, 1};
    fn(m, CU_TENSOR_MAP_DATA_TYPE_BFLOAT16, rank, const_cast<void*>(ptr), dims, strides, box, es,
       CU_TENSOR_MAP_INTERLEAVE_NONE, box[0] == 32 ? CU_TENSOR_MAP_SWIZZLE_64B : CU_TENSOR_MAP_SWIZZLE_128B,
       CU_TENSOR_MAP_L2_PROMOTION_L2_128B, CU_TENSOR_MAP_FLOAT_OOB_FILL_NONE);
}
void encode_rows(EncodeFn fn, CUtensorMap* m, const void* ptr, int cols, int box_rows, int box_parity) {
    const cuuint64_t dims[3] = {(cuuint64_t)cols, SEQ / 2, 2}, strides[2] = {(cuuint64_t)cols * 4, (cuuint64_t)cols * 2};
    const cuuint32_t box[3] = {64, (cuuint32_t)box_rows, (cuuint32_t)box_parity};
    encode(fn, m, ptr, 3, dims, strides, box);
}
void encode_w1(EncodeFn fn, CUtensorMap* m, const void* ptr, int cols) {
    const cuuint64_t dims[2] = {(cuuint64_t)cols, DM}, strides[1] = {(cuuint64_t)cols * 2};
    const cuuint32_t box[2] = {64, 64};
    encode(fn, m, ptr, 2, dims, strides, box);
}
void encode_tail(EncodeFn fn, CUtensorMap* m, const void* ptr, int rows, int cols, int n) {
    const cuuint64_t rb = cols * 2;
    const cuuint64_t dims[5] = {32, (cuuint64_t)n, (cuuint64_t)rows / (4 * n), 4, 8}, strides[4] = {rb, 4 * n * rb, n * rb, 256};
    const cuuint32_t box[5] = {32, (cuuint32_t)n, 16 / (cuuint32_t)n, 4, 4};
    encode(fn, m, (const __nv_bfloat16*)ptr + cols - 1024 + 96, 5, dims, strides, box);
}
void encode_w2(EncodeFn fn, CUtensorMap* m, const void* ptr, int rows) {
    const cuuint64_t rb = DM * 2;
    const cuuint64_t dims[5] = {DM, 2, 4, 4, (cuuint64_t)rows / 32}, strides[4] = {rb, 8 * rb, 2 * rb, 32 * rb};
    const cuuint32_t box[5] = {64, 2, 4, 4, 2};
    encode(fn, m, ptr, 5, dims, strides, box);
}
void encode_wo(EncodeFn fn, CUtensorMap* m, const void* ptr) {
    const cuuint64_t rb = DM * 2;
    const cuuint64_t dims[5] = {DM, 4, DM / 32, 2, 4}, strides[4] = {8 * rb, 32 * rb, rb, 2 * rb};
    const cuuint32_t box[5] = {64, 4, 2, 2, 4};
    encode(fn, m, ptr, 5, dims, strides, box);
}

}

extern "C" void kernel_launch(void* const* d_in, const int* in_sizes, int n_in, void* d_out, int out_size) {
    (void)in_sizes; (void)n_in; (void)out_size;
    static EncodeFn fn = nullptr;
    static Params prm;
    if (!fn) {
        cudaDriverEntryPointQueryResult st;
        cudaGetDriverEntryPoint("cuTensorMapEncodeTiled", (void**)&fn, cudaEnableDefault, &st);
        cudaGetSymbolAddress((void**)&prm.pxn, g_xn);
        cudaGetSymbolAddress((void**)&prm.pa2, g_a2);
        cudaGetSymbolAddress((void**)&prm.tail, g_tail);
        cudaGetSymbolAddress((void**)&prm.halo, g_halo);
        cudaGetSymbolAddress((void**)&prm.stats, g_stats);
        cudaGetSymbolAddress((void**)&prm.colsum, g_colsum);
        cudaGetSymbolAddress((void**)&prm.flags, g_flags);
        cudaGetSymbolAddress((void**)&prm.epoch, g_epoch);
        cudaFuncSetAttribute(fused_kernel, cudaFuncAttributeMaxDynamicSharedMemorySize, SMEM_BYTES);
    }
    encode_rows(fn, &prm.x, d_in[0], DM, 64, 2);
    encode_rows(fn, &prm.xn, prm.pxn, DM, 64, 2);
    encode_rows(fn, &prm.a2, prm.pa2, K2, 64, 2);
    encode_rows(fn, &prm.out, d_out, DM, 16, 1);
    encode_w1(fn, &prm.wqkv, d_in[1], NQKV);
    encode_w1(fn, &prm.wg, d_in[4], DF);
    encode_w1(fn, &prm.wu, d_in[5], DF);
    encode_tail(fn, &prm.wu_tail, d_in[5], DM, DF, 8);
    encode_tail(fn, &prm.wd_tail, d_in[6], DF, DM, 2);
    encode_wo(fn, &prm.wo, d_in[2]);
    encode_w2(fn, &prm.wd, d_in[6], DF);
    prm.hi[0] = prm.hi[1] = 0x40000040;
    prm.px = (const __nv_bfloat16*)d_in[0];
    prm.pwu = (const __nv_bfloat16*)d_in[5];
    prm.pout = (__nv_bfloat16*)d_out;
    fused_kernel<<<NCTA, 384, SMEM_BYTES>>>(prm);
}
```

```cpp
#include <cuda_runtime.h>
#include <cuda_bf16.h>
#include <cuda.h>
#include <stdint.h>
#include <limits.h>

namespace {

constexpr int SEQ = 2048, DM = 1024, DF = 3584, K2 = DM + DF, NQKV = 3 * DM;
constexpr int NGEMM = 128, NCTA = 132;
constexpr int G1_STAGES = 4, G1_STAGE_BYTES = 49152, G1_KSTEPS = 16, G1_TILES = 5;
constexpr int G2_STAGES = 6, G2_STAGE_BYTES = 32768, G2_KSTEPS = 72, G2_LATE = 40, G2_DSTEPS = 56;
constexpr int G2_HEAD = 17;
constexpr int A_BYTES = 16384;
constexpr int AUX_OFF = G1_STAGES * G1_STAGE_BYTES;
constexpr int BAR_OFF = AUX_OFF + 32768;
constexpr int PLAN_OFF = BAR_OFF + 384, STAT_OFF = BAR_OFF + 1536;
constexpr int SMEM_BYTES = BAR_OFF + 2816;
constexpr int G1_SKEW = 2, G2_SKEW = 5;
constexpr int CONSUMER_REGS = 224, AUX_REGS = 56;
constexpr int HALO_BYTES = 4096;
constexpr int LN_STEP = 3, FOLD_STEP = 14, SUM_STEP = 11, SUM2_STEP = 2;
constexpr uint32_t SUM_LOAD0 = 0x87658765u, SUM_LOAD1 = 0x65876587u;
constexpr int KEY_STEP = 2, QK_STEP = 8;
constexpr int VAL_STEP = 1, HALF_STEP = 3, PV_STEP = 9, OUT_STEPS = 4;
constexpr int UP_STEP = 2, XLOAD_STEP = 44;
constexpr int XREAD_STEP = 5, TAIL_STEP = 7;
constexpr int MEET = 4;
constexpr int PACE1 = 800, PACE2 = 1325, PACE3 = 1700;
constexpr int SHARE_MIN = 3, SHARE_MAX = 22, SHARE_LOW = 36, SHARE_SUM = 43;
constexpr int SHARE_NS = 79, SPARE_NS = 640, LATE_SCALE = 8;
constexpr float REST = 65000.f, DUE = 75100.f;

enum { F_LN = 0, F_LN2 = 1, F_FIRST = 2, F_SECOND = 3, F_SHARE = 4, F_EARLY = 5, F_LATE = 6, F_TAIL2 = 7, F_PACE = 8, F_HALO = 9 };
constexpr unsigned CNT_LN = 8, CNT_EARLY = 9, CNT_LATE = 8;

__device__ __align__(1024) __nv_bfloat16 g_xn[SEQ * DM];
__device__ __align__(1024) __nv_bfloat16 g_a2[SEQ * K2];
__device__ __align__(128) uint4 g_tail[2 * NGEMM * 512];
__device__ __align__(128) uint8_t g_halo[(2 * NGEMM + 1) * HALO_BYTES];
__device__ __align__(128) float2 g_stats[SEQ];
__device__ __align__(128) float g_colsum[18 * 1024];
__device__ __align__(128) unsigned g_flags[(F_HALO + 8) * 16 * 32];
__device__ __align__(128) unsigned g_epoch[NCTA * 16];

struct Params {
    const __nv_bfloat16 *px, *pwu;
    __nv_bfloat16 *pxn, *pa2, *pout;
    uint4* tail;
    uint8_t* halo;
    float2* stats;
    float* colsum;
    unsigned *flags, *epoch;
    unsigned long long* trace;
    uint32_t hi[2];
    CUtensorMap x, wg, wu, xn, wqkv, a2, wu_tail, wd_tail, wo, wd, out;
};

extern __shared__ __align__(1024) uint8_t smem_raw[];

#define TRACE(slot) do {} while (0)
#define TRACE_GT(slot) do {} while (0)
#define TRACE_S(slot, v, want) do {} while (0)
#define TRACE_GET(v) do {} while (0)
#define TRACE_PUT(slot, v) do {} while (0)
#define TRACE_SLOT(v, slot) do {} while (0)
#define TRACE_NEXT(v) do {} while (0)
#define TRACE_DUMP() do {} while (0)
#define TRACE_CLEAR() do {} while (0)
#define STAGE_TRACE 0
#define TRACE_END() do {} while (0)
#define TRACE_LITE(i, c) do {} while (0)
#define TRACE_STEP(t, k, i) do {} while (0)

__device__ __forceinline__ uint32_t smem_u32(const void* p) { return (uint32_t)__cvta_generic_to_shared(p); }
__device__ __forceinline__ void mbar_init(uint32_t bar, uint32_t cnt) {
    asm volatile("mbarrier.init.shared::cta.b64 [%0], %1;" :: "r"(bar), "r"(cnt) : "memory");
}
__device__ __forceinline__ void mbar_expect_tx(uint32_t bar, uint32_t bytes) {
    asm volatile("mbarrier.arrive.expect_tx.shared::cta.b64 _, [%0], %1;" :: "r"(bar), "r"(bytes) : "memory");
}
__device__ __forceinline__ void mbar_arrive(uint32_t bar) {
    asm volatile("mbarrier.arrive.shared::cta.b64 _, [%0];" :: "r"(bar) : "memory");
}
__device__ __forceinline__ bool mbar_try_wait(uint32_t bar, uint32_t parity) {
    uint32_t ok;
    asm volatile("{\n.reg .pred p;\nmbarrier.try_wait.parity.shared::cta.b64 p, [%1], %2;\nselp.u32 %0, 1, 0, p;\n}"
                 : "=r"(ok) : "r"(bar), "r"(parity) : "memory");
    return ok;
}
__device__ __forceinline__ void mbar_wait(uint32_t bar, uint32_t parity) {
#pragma unroll 1
    for (int spins = 0; !mbar_try_wait(bar, parity) && spins < (1 << 17); spins++) {}
}
__device__ __forceinline__ void mbar_wait(uint32_t bar, uint32_t parity, int& spins) {
    asm volatile("{\n.reg .pred p;\nagain:\nmbarrier.try_wait.parity.shared::cta.b64 p, [%1], %2;\n@p bra done;\n"
                 "add.s32 %0, %0, -1;\nsetp.gt.s32 p, %0, 0;\n@p bra again;\ndone:\n}" : "+r"(spins) : "r"(bar), "r"(parity) : "memory");
}
template <bool WARP = false> __device__ __forceinline__ unsigned flag_wait(const unsigned* p, unsigned target) {
    unsigned v;
#pragma unroll 1
    for (int spins = 0; spins < (1 << 19); spins++) {
        asm volatile("ld.acquire.gpu.global.u32 %0, [%1];" : "=r"(v) : "l"(p) : "memory");
        if (WARP ? __all_sync(0xffffffffu, (int)(v - target) >= 0) : (int)(v - target) >= 0) break;
        __nanosleep(64);
    }
    return v;
}
__device__ __forceinline__ void mbar_wait_warp(uint32_t bar, uint32_t parity) {
#pragma unroll 1
    for (int spins = 0; !__all_sync(0xffffffffu, mbar_try_wait(bar, parity)) && spins < (1 << 17); spins++) {}
}
__device__ __forceinline__ void flag_add(unsigned* p) {
    asm volatile("red.release.gpu.global.add.u32 [%0], 1;" :: "l"(p) : "memory");
}
__device__ __forceinline__ bool elect_one() {
    uint32_t ok;
    asm volatile("{\n.reg .pred p;\nelect.sync _|p, 0xffffffff;\nselp.u32 %0, 1, 0, p;\n}" : "=r"(ok));
    return ok;
}
__device__ __forceinline__ uint32_t pick(bool c, uint32_t a, uint32_t b) {
    uint32_t r;
    asm("{\n.reg .pred p;\nsetp.ne.b32 p, %3, 0;\nselp.b32 %0, %1, %2, p;\n}" : "=r"(r) : "r"(a), "r"(b), "r"((uint32_t)c));
    return r;
}
__device__ __forceinline__ void fence_proxy_async() { asm volatile("fence.proxy.async.global;" ::: "memory"); }
__device__ __forceinline__ uint4 lds128(uint32_t addr) {
    uint4 v;
    asm volatile("ld.shared.v4.u32 {%0,%1,%2,%3}, [%4];" : "=r"(v.x), "=r"(v.y), "=r"(v.z), "=r"(v.w) : "r"(addr) : "memory");
    return v;
}
__device__ __forceinline__ uint32_t lds32(uint32_t addr) {
    uint32_t v;
    asm volatile("ld.shared.u32 %0, [%1];" : "=r"(v) : "r"(addr) : "memory");
    return v;
}
__device__ __forceinline__ void sts32(uint32_t addr, uint32_t v) { asm volatile("st.shared.u32 [%0], %1;" :: "r"(addr), "r"(v) : "memory"); }
__device__ __forceinline__ uint32_t nanos() { uint32_t t; asm volatile("mov.u32 %0, %%globaltimer_lo;" : "=r"(t)); return t; }
__device__ __forceinline__ float2 lds64f(uint32_t addr) {
    float2 v;
    asm volatile("ld.shared.v2.f32 {%0,%1}, [%2];" : "=f"(v.x), "=f"(v.y) : "r"(addr) : "memory");
    return v;
}
__device__ __forceinline__ void sts128(uint32_t addr, uint4 v) {
    asm volatile("st.shared.v4.u32 [%0], {%1,%2,%3,%4};" :: "r"(addr), "r"(v.x), "r"(v.y), "r"(v.z), "r"(v.w) : "memory");
}
__device__ __forceinline__ void sts64f(uint32_t addr, float a, float b) {
    asm volatile("st.shared.v2.f32 [%0], {%1,%2};" :: "r"(addr), "f"(a), "f"(b) : "memory");
}

__device__ __forceinline__ uint64_t stream_policy() { return 0x12F0000000000000ull; }
__device__ __forceinline__ void tma_3d(uint32_t dst, const CUtensorMap* m, uint32_t bar, int c0, int c1, int c2, uint64_t pol) {
    asm volatile("cp.async.bulk.tensor.3d.shared::cluster.global.mbarrier::complete_tx::bytes.L2::cache_hint"
                 " [%0], [%1, {%3, %4, %5}], [%2], %6;"
                 :: "r"(dst), "l"(m), "r"(bar), "r"(c0), "r"(c1), "r"(c2), "l"(pol) : "memory");
}
__device__ __forceinline__ void load_stage1(uint32_t dst, uint32_t dst_b, uint32_t bar, const CUtensorMap* ma, const CUtensorMap* mb0,
                                            const CUtensorMap* mb1, int k, int row, int col0, int col1, int keep_a, uint64_t pol) {
    asm volatile("{\n.reg .pred e, p, q;\nelect.sync _|e, 0xffffffff;\nsetp.ne.and.b32 p|q, %8, 0, e;\n"
        "@p cp.async.bulk.tensor.3d.shared::cluster.global.mbarrier::complete_tx::bytes [%0], [%3, {%5, %6, %10}], [%2];\n"
        "@q cp.async.bulk.tensor.3d.shared::cluster.global.mbarrier::complete_tx::bytes.L2::cache_hint [%0], [%3, {%5, %6, %10}], [%2], %9;\n"
        "@e cp.async.bulk.tensor.2d.shared::cluster.global.mbarrier::complete_tx::bytes.multicast::cluster.L2::cache_hint"
        " [%1], [%4, {%7, %5}], [%2], %11, %9;\n"
        "@e cp.async.bulk.tensor.2d.shared::cluster.global.mbarrier::complete_tx::bytes.multicast::cluster.L2::cache_hint"
        " [%1 + 8192], [%13, {%14, %5}], [%2], %11, %9;\n"
        "@e mbarrier.arrive.expect_tx.shared::cta.b64 _, [%2], %12;\n}"
        :: "r"(dst), "r"(dst_b), "r"(bar), "l"(ma), "l"(mb0), "r"(k), "r"(row), "r"(col0), "r"(keep_a), "l"(pol), "r"(0),
           "h"((uint16_t)3), "n"(G1_STAGE_BYTES), "l"(mb1), "r"(col1) : "memory");
}
__device__ __forceinline__ void load_stage2(uint32_t dst, uint32_t dst_b, uint32_t bar, const CUtensorMap* ma, const CUtensorMap* mb,
                                            int ka, int row, int col, int kb2, int kb4, uint64_t pol) {
    asm volatile("{\n.reg .pred e;\nelect.sync _|e, 0xffffffff;\n"
        "@e cp.async.bulk.tensor.3d.shared::cluster.global.mbarrier::complete_tx::bytes.L2::cache_hint [%0], [%3, {%5, %6, %10}], [%2], %9;\n"
        "@e cp.async.bulk.tensor.5d.shared::cluster.global.mbarrier::complete_tx::bytes.multicast::cluster.L2::cache_hint"
        " [%1], [%4, {%7, %10, %13, %10, %8}], [%2], %11, %9;\n"
        "@e mbarrier.arrive.expect_tx.shared::cta.b64 _, [%2], %12;\n}"
        :: "r"(dst), "r"(dst_b), "r"(bar), "l"(ma), "l"(mb), "r"(ka), "r"(row), "r"(col), "r"(kb4), "l"(pol), "r"(0),
           "h"((uint16_t)3), "n"(G2_STAGE_BYTES), "r"(kb2) : "memory");
}
__device__ __forceinline__ void load_tail(uint32_t dst, uint32_t bar, const CUtensorMap* ma, const CUtensorMap* mb, int ka, int mblk,
                                          int kb) {
    asm volatile("{\n.reg .pred e;\nelect.sync _|e, 0xffffffff;\n"
        "@e cp.async.bulk.tensor.3d.shared::cluster.global.mbarrier::complete_tx::bytes [%0], [%2, {%3, %4, %5}], [%1];\n"
        "@e cp.async.bulk.tensor.5d.shared::cluster.global.mbarrier::complete_tx::bytes.multicast::cluster"
        " [%9], [%6, {%5, %5, %7, %5, %10}], [%1], %11;\n"
        "@e mbarrier.arrive.expect_tx.shared::cta.b64 _, [%1], %8;\n}"
        :: "r"(dst), "r"(bar), "l"(ma), "r"(ka), "r"(mblk * 64), "r"(0), "l"(mb), "r"(kb), "n"(G1_STAGE_BYTES),
           "r"(dst + A_BYTES + (mblk & 1) * 16384), "r"((mblk & 1) * 4), "h"((uint16_t)3) : "memory");
}
__device__ __forceinline__ uint4 ldg_stream(const void* p, uint64_t pol) {
    uint4 v;
    asm volatile("ld.global.nc.L1::no_allocate.L2::cache_hint.v4.u32 {%0,%1,%2,%3}, [%4], %5;"
                 : "=r"(v.x), "=r"(v.y), "=r"(v.z), "=r"(v.w) : "l"(p), "l"(pol));
    return v;
}
__device__ __forceinline__ void st_tagged(void* p, float a, float b, uint32_t tag) {
    asm volatile("st.relaxed.gpu.global.v2.b32 [%0], {%1,%2};"
                 :: "l"(p), "r"((__float_as_uint(a) & ~3u) | tag), "r"((__float_as_uint(b) & ~3u) | tag) : "memory");
}
__device__ __forceinline__ void st_relaxed(unsigned* p, uint32_t v) {
    asm volatile("st.relaxed.gpu.global.b32 [%0], %1;" :: "l"(p), "r"(v) : "memory");
}
__device__ __forceinline__ bool untagged(const uint4& v, uint32_t tag) {
    return ((v.x ^ tag) | (v.y ^ tag) | (v.z ^ tag) | (v.w ^ tag)) & 3;
}
__device__ __forceinline__ uint4 ld_relaxed(const void* p) {
    uint4 v;
    asm volatile("ld.relaxed.gpu.global.v4.b32 {%0,%1,%2,%3}, [%4];" : "=r"(v.x), "=r"(v.y), "=r"(v.z), "=r"(v.w) : "l"(p) : "memory");
    return v;
}
__device__ __forceinline__ void prefetch_map(const CUtensorMap* m) {
    asm volatile("prefetch.tensormap [%0];" :: "l"(m) : "memory");
}
template <int N> __device__ __forceinline__ void wg_wait() { asm volatile("wgmma.wait_group.sync.aligned %0;" :: "n"(N) : "memory"); }

__device__ __forceinline__ uint32_t desc_a(uint32_t addr) { return (addr & 0x3FFFF) >> 4 | 1 << 16; }
__device__ __forceinline__ uint32_t desc_b(uint32_t addr) { return (addr & 0x3FFFF) >> 4 | 512 << 16; }

#define R8(d, o) "+f"(d[o]), "+f"(d[o+1]), "+f"(d[o+2]), "+f"(d[o+3]), "+f"(d[o+4]), "+f"(d[o+5]), "+f"(d[o+6]), "+f"(d[o+7])
#define R32(d, o) R8(d, o), R8(d, o+8), R8(d, o+16), R8(d, o+24)
#define R64(d, o) R32(d, o), R32(d, o+32)
#define ACC00 "%0,%1,%2,%3,%4,%5,%6,%7,%8,%9,%10,%11,%12,%13,%14,%15,%16,%17,%18,%19,%20,%21,%22,%23,%24,%25,%26,%27,%28,%29,%30,%31,"\
    "%32,%33,%34,%35,%36,%37,%38,%39,%40,%41,%42,%43,%44,%45,%46,%47"
#define ACC0 ACC00 ",%48,%49,%50,%51,%52,%53,%54,%55,%56,%57,%58,%59,%60,%61,%62,%63"
#define ACC1 "%64,%65,%66,%67,%68,%69,%70,%71,%72,%73,%74,%75,%76,%77,%78,%79,%80,%81,%82,%83,%84,%85,%86,%87,%88,%89,%90,%91,%92,%93,%94,%95,"\
    "%96,%97,%98,%99,%100,%101,%102,%103,%104,%105,%106,%107,%108,%109,%110,%111"
#define ACC48 "{" ACC00 "}"
#define ACC64 "{" ACC0 "}"
#define ACC112 "{" ACC0 "," ACC1 "}"
#define ACC128 "{" ACC0 "," ACC1 ",%112,%113,%114,%115,%116,%117,%118,%119,%120,%121,%122,%123,%124,%125,%126,%127}"
#define MMA_K16(shape, acc, a, b, keep, hb) \
    "mov.b64 da, {" a ", 0x40000040};\nmov.b64 db, {" b ", " hb "};\n" \
    "wgmma.mma_async.sync.aligned." shape ".f32.bf16.bf16 " acc ", da, db, " keep ", 1, 1, 0, 1;\n"
#define MMA_NEXT(op, a, b, sa, sb) op " " a ", " a ", " sa ";\n" op " " b ", " b ", " sb ";\n"
#define MMA_STEP_B(shape, acc, a, b, na, nb, keep, hb, sb) \
    "{\n.reg .pred p, q;\n.reg .b64 da, db;\nsetp.ne.b32 p, " keep ", 0;\nsetp.eq.b32 q, 0, 0;\nwgmma.fence.sync.aligned;\n" \
    MMA_K16(shape, acc, a, b, "p", hb) MMA_NEXT("xor.b32", a, b, "2", "128") MMA_K16(shape, acc, a, b, "q", hb) MMA_NEXT("add.s32", a, b, "2", sb) \
    MMA_K16(shape, acc, a, b, "q", hb) MMA_NEXT("xor.b32", a, b, "2", "128") MMA_K16(shape, acc, a, b, "q", hb) MMA_NEXT("add.s32", a, b, na, nb) \
    "wgmma.commit_group.sync.aligned;\n}"
#define MMA64(shape, acc, a, b, keep) "wgmma.mma_async.sync.aligned." shape ".f32.bf16.bf16 " acc ", " a ", " b ", " keep ", 1, 1, 0, 1;\n"
#define NEXT64(op, a, b, sa, sb) "mov.b64 {lo, hi}, " a ";\n" op " lo, lo, " sa ";\nmov.b64 " a ", {lo, hi};\n" \
    "mov.b64 {lo, hi}, " b ";\n" op " lo, lo, " sb ";\nmov.b64 " b ", {lo, hi};\n"
#define ADD64(op, a, b, sa, sb) "cvt.s64.s32 w, " sa ";\nadd.s64 " a ", " a ", w;\ncvt.s64.s32 w, " sb ";\nadd.s64 " b ", " b ", w;\n"
#define MMA_STEP(shape, acc, a, b, na, nb, keep) MMA_STEP_N(shape, acc, a, b, na, nb, keep, NEXT64)
#define MMA_STEP_N(shape, acc, a, b, na, nb, keep, LAST) \
    "{\n.reg .pred p, q;\n.reg .b32 lo, hi;\n.reg .b64 w;\nsetp.ne.b32 p, " keep ", 0;\nsetp.eq.b32 q, 0, 0;\nwgmma.fence.sync.aligned;\n" \
    MMA64(shape, acc, a, b, "p") NEXT64("xor.b32", a, b, "2", "128") MMA64(shape, acc, a, b, "q") NEXT64("add.s32", a, b, "2", "128") \
    MMA64(shape, acc, a, b, "q") NEXT64("xor.b32", a, b, "2", "128") MMA64(shape, acc, a, b, "q") LAST("add.s32", a, b, na, nb) \
    "wgmma.commit_group.sync.aligned;\n}"
#define MMA_ARGS64 "+l"(da), "+l"(db) : "r"(next / 16 - 6), "r"(next / 16 - 384), "r"(keep) : "memory"
#define MMA_ARGS "+r"(da), "+r"(db) : "r"(next / 16 - 6), "r"(next / 16 - 384), "r"(keep) : "memory"

__device__ __forceinline__ void mma_step(float (&d)[128], uint64_t& da, uint64_t& db, int next, int keep) {
    asm volatile(MMA_STEP("m64n256k16", ACC128, "%128", "%129", "%130", "%131", "%132") : R64(d, 0), R64(d, 64), MMA_ARGS64);
}
__device__ __forceinline__ void mma_rank(float (&d)[128], uint32_t a0, uint32_t a1, uint32_t db) {
    asm volatile("{\n.reg .pred q;\n.reg .b64 db;\nsetp.eq.b32 q, 0, 0;\nmov.b64 db, {%131, 0x40000040};\nwgmma.fence.sync.aligned;\n"
                 "wgmma.mma_async.sync.aligned.m64n256k16.f32.bf16.bf16 " ACC128 ", {%128, %129, %130, %130}, db, q, 1, 1, 1;\n}"
                 : R64(d, 0), R64(d, 64) : "r"(a0), "r"(a1), "r"(0), "r"(db) : "memory");
}
__device__ __forceinline__ void mma_step224(float (&d)[128], uint64_t& da, uint64_t& db, int next, int keep) {
    asm volatile(MMA_STEP("m64n224k16", ACC112, "%112", "%113", "%114", "%115", "%116")
                 : R64(d, 0), R32(d, 64), R8(d, 96), R8(d, 104), MMA_ARGS64);
}
__device__ __forceinline__ void mma_step(float (&d)[64], uint64_t& da, uint64_t& db, int next, int keep) {
    asm volatile(MMA_STEP("m64n128k16", ACC64, "%64", "%65", "%66", "%67", "%68") : R64(d, 0), MMA_ARGS64);
}
__device__ __forceinline__ void mma_step_c(float (&d)[64], uint64_t& da, uint64_t& db, int next, int keep) {
    asm volatile(MMA_STEP_N("m64n128k16", ACC64, "%64", "%65", "%66", "%67", "%68", ADD64) : R64(d, 0), MMA_ARGS64);
}
__device__ __forceinline__ void mma_step96(float (&d)[64], uint64_t& da, uint64_t& db, int next, int keep) {
    asm volatile(MMA_STEP("m64n96k16", ACC48, "%48", "%49", "%50", "%51", "%52") : R32(d, 0), R8(d, 32), R8(d, 40), MMA_ARGS64);
}
__device__ __forceinline__ void mma_step_tail(float (&d)[128], uint32_t da, uint32_t b, int keep) {
    uint32_t db = (b & 0x3FFFF) >> 4 | 256 << 16;
    const int next = 0;
    asm volatile(MMA_STEP_B("m64n256k16", ACC128, "%128", "%129", "%130", "%131", "%132", "0x80000040", "-96")
                 : R64(d, 0), R64(d, 64), MMA_ARGS);
}

__device__ __forceinline__ uint32_t pack_bf16(float lo, float hi) {
    uint32_t r; asm("cvt.rn.bf16x2.f32 %0, %1, %2;" : "=r"(r) : "f"(hi), "f"(lo)); return r;
}
__device__ __forceinline__ float bf_lo(uint32_t v) { return __uint_as_float(v << 16); }
__device__ __forceinline__ float bf_hi(uint32_t v) { return __uint_as_float(v & 0xffff0000u); }
__device__ __forceinline__ float round_bf16(float v) { return bf_lo(pack_bf16(v, 0.f)); }
__device__ __forceinline__ uint32_t mul_bf16x2(uint32_t a, uint32_t b) {
    uint32_t r; asm("mul.rn.bf16x2 %0, %1, %2;" : "=r"(r) : "r"(a), "r"(b)); return r;
}
__device__ __forceinline__ uint32_t sub_bf16x2(uint32_t a, uint32_t b) {
    uint32_t r; asm("sub.rn.bf16x2 %0, %1, %2;" : "=r"(r) : "r"(a), "r"(b)); return r;
}
__device__ __forceinline__ uint32_t mul2_bf16x2(uint32_t a, uint32_t hi, uint32_t lo) {
    uint32_t r; asm("fma.rn.bf16x2 %0, %1, %2, %3;" : "=r"(r) : "r"(a), "r"(hi), "r"(mul_bf16x2(a, lo))); return r;
}
__device__ __forceinline__ float tanh_fast(float x) { float r; asm("tanh.approx.f32 %0, %1;" : "=f"(r) : "f"(x)); return r; }
__device__ __forceinline__ float gelu_twice(float g) {
    return fmaf(g, tanh_fast(fmaf(g * g, 0.044715f * 0.7978845608f, 0.7978845608f) * g), g);
}
__device__ __forceinline__ uint32_t geglu2(uint32_t g2, uint32_t u2) {
    return mul_bf16x2(pack_bf16(gelu_twice(bf_lo(g2)), gelu_twice(bf_hi(g2))), u2);
}
__device__ __forceinline__ uint32_t silu2(float lo, float hi) {
    const uint32_t h = mul_bf16x2(pack_bf16(lo, hi), 0x3e803e80u);
    return pack_bf16(fmaf(bf_lo(h), tanh_fast(bf_lo(h)), bf_lo(h)), fmaf(bf_hi(h), tanh_fast(bf_hi(h)), bf_hi(h)));
}
__device__ __forceinline__ float ex2_fast(float x) { float r; asm("ex2.approx.ftz.f32 %0, %1;" : "=f"(r) : "f"(x)); return r; }
__device__ __forceinline__ void unpack8(uint4 v, float (&f)[8]) {
    f[0] = bf_lo(v.x); f[1] = bf_hi(v.x); f[2] = bf_lo(v.y); f[3] = bf_hi(v.y);
    f[4] = bf_lo(v.z); f[5] = bf_hi(v.z); f[6] = bf_lo(v.w); f[7] = bf_hi(v.w);
}
template <int N> __device__ __forceinline__ void fence_regs(float (&d)[N]) {
#pragma unroll
    for (int i = 0; i < N; i++) asm volatile("" : "+f"(d[i]) :: "memory");
}

__device__ __forceinline__ float rcp_fast(float x) { float r; asm("rcp.approx.ftz.f32 %0, %1;" : "=f"(r) : "f"(x)); return r; }
__device__ __forceinline__ float sqrt_fast(float x) { float r; asm("sqrt.approx.ftz.f32 %0, %1;" : "=f"(r) : "f"(x)); return r; }
__device__ __forceinline__ uint32_t max_bf16x2(uint32_t a, uint32_t b) {
    uint32_t r; asm("max.bf16x2 %0, %1, %2;" : "=r"(r) : "r"(a), "r"(b)); return r;
}
__device__ __forceinline__ uint32_t transpose8(uint32_t a) {
    uint32_t r; asm volatile("movmatrix.sync.aligned.m8n8.trans.b16 %0, %1;" : "=r"(r) : "r"(a)); return r;
}
__device__ __forceinline__ void mma_sync(uint32_t* d, const uint32_t* a, uint32_t b0, uint32_t b1, const uint32_t* c) {
    asm volatile("mma.sync.aligned.m16n8k16.row.col.f32.bf16.bf16.f32 {%0,%1,%2,%3}, {%4,%5,%6,%7}, {%8,%9}, {%10,%11,%12,%13};"
        : "=r"(d[0]), "=r"(d[1]), "=r"(d[2]), "=r"(d[3])
        : "r"(a[0]), "r"(a[1]), "r"(a[2]), "r"(a[3]), "r"(b0), "r"(b1), "r"(c[0]), "r"(c[1]), "r"(c[2]), "r"(c[3]));
}
template <int N> struct Floats {
    float f[N];
    __device__ __forceinline__ Floats() {}
    __device__ __forceinline__ Floats(const uint32_t* p) {
#pragma unroll
        for (int i = 0; i < N; i++) asm("mov.b32 %0, %1;" : "=f"(f[i]) : "r"(p[i]));
    }
    __device__ __forceinline__ void put(uint32_t* p) const {
#pragma unroll
        for (int i = 0; i < N; i++) asm("mov.b32 %0, %1;" : "=r"(p[i]) : "f"(f[i]));
    }
    __device__ __forceinline__ float& operator[](int i) { return f[i]; }
};
__device__ __forceinline__ uint32_t fresh_tid() { uint32_t r; asm volatile("mov.u32 %0, %%tid.x;" : "=r"(r)); return r; }
template <typename T> __device__ __forceinline__ T uniform(T v) { return __shfl_sync(0xffffffffu, v, 0); }

__device__ __forceinline__ uint32_t forecast(uint32_t n0, uint32_t c0, float cycles, uint32_t tag) {
    const uint32_t n = nanos();
    return n + (int)((n - n0) * cycles * rcp_fast((uint32_t)clock() - c0)) & ~3u | tag;
}
__device__ __forceinline__ uint32_t plan_word(uint32_t base, int lane) { return uniform(lds32(base + PLAN_OFF + lane * 4)); }

__device__ __forceinline__ void fold_operands(const Params& prm, uint32_t base, int slot, int mblk, uint32_t tag, int w, int lane) {
    uint4 v[9];
#pragma unroll
    for (int m = 0; m < 9; m++) v[m] = make_uint4(0, 0, 0, 0);
    const float* parts = prm.colsum + (slot * 2 + (lane >> 4)) * 1024 + w * 64 + (lane & 15) * 4;
    const float* const rows = &prm.stats[mblk * 128 + w * 64 + lane * 2].x;
#pragma unroll 1
    for (int spins = 0; spins < (1 << 16); spins++) {
        bool missing = false;
        asm volatile("" : "+l"(parts));
#pragma unroll
        for (int m = 0; m < 9; m++) {
            if (untagged(v[m], tag)) {
                missing = true;
                v[m] = ld_relaxed(m < 8 ? parts + m * 128 : rows);
            }
        }
        if (!missing) break;
    }
    float4 c = make_float4(0.f, 0.f, 0.f, 0.f);
#pragma unroll
    for (int m = 0; m < 8; m++) {
        c.x += __uint_as_float(v[m].x ^ tag); c.y += __uint_as_float(v[m].y ^ tag);
        c.z += __uint_as_float(v[m].z ^ tag); c.w += __uint_as_float(v[m].w ^ tag);
    }
    sts128(base + STAT_OFF + w * 512 + lane * 16, make_uint4(v[8].x ^ tag, v[8].y ^ tag, v[8].z ^ tag, v[8].w ^ tag));
    const uint32_t ca = base + AUX_OFF + w * 8192 + (lane >> 4) * 16384 + (lane & 15) * 8;
#pragma unroll
    for (int r = 0; r < 3; r++) {
        const uint32_t lo = pack_bf16(c.x, c.y), hi = pack_bf16(c.z, c.w);
        sts64f((ca ^ r * 16) + r * 128, __uint_as_float(lo), __uint_as_float(hi));
        c.x -= bf_lo(lo); c.y -= bf_hi(lo); c.z -= bf_lo(hi); c.w -= bf_hi(hi);
    }
    asm volatile("fence.proxy.async.shared::cta;" ::: "memory");
    __syncwarp();
}
__device__ __forceinline__ float2 fold(float (&acc)[128], uint32_t base, int wg) {
    const uint32_t id = fresh_tid(), sp = base + STAT_OFF + (id & 96) * 8 + (id & 28) * 4 + wg * 8;
    const uint32_t sel = id & 2 ? 0x4444 : (id & 1 ? 0x4432 : 0x3232);
    const float2 sa = lds64f(sp), sb = lds64f(sp + 128);
    mma_rank(acc, __byte_perm(__float_as_uint(sa.x), 0, sel), __byte_perm(__float_as_uint(sb.x), 0, sel), desc_b(base + AUX_OFF));
    return make_float2(sa.y, sb.y);
}

__device__ __forceinline__ void tail_gemm(const Params& prm, uint32_t base, uint32_t t0, unsigned epoch, int grp, int warp, int lane) {
    const uint32_t full = base + BAR_OFF, empty = full + 32, sig = full + 192, dep = full + 256, folded = full + 320;
    const uint32_t tag = 1 + (epoch & 1);
    auto plan = [&](uint32_t p, uint32_t word) { return p < 4 ? p * 64 + grp / 2 * 32 + 15 : word >> p % 4 * 8 & 255; };
    auto rows = [&](uint32_t job) { return job / 32 * 2 + grp % 2; };
    if (warp == 8) {
        if (elect_one()) { prefetch_map(&prm.xn); prefetch_map(&prm.a2); prefetch_map(&prm.wd_tail); }
#pragma unroll 1
        for (int p = 0, i = G1_STAGES; p < 8; p++) {
            const bool first = p < 4;
            if (p == 4) mbar_wait_warp(dep + 16, 0);
            const uint32_t job = plan(p, plan_word(base, lane));
#pragma unroll 1
            for (int k = p ? 0 : G1_STAGES; k <= job % 32; k++, i++) {
                if (p == 3 && k % 2 == grp / 2)
                    asm volatile("{\n.reg .pred e;\nelect.sync _|e, 0xffffffff;\n"
                        "@e cp.async.bulk.prefetch.tensor.5d.L2.global [%0, {%2, %2, %1, %2, %3}];\n}"
                        :: "l"(&prm.wd_tail), "r"(k * 8), "r"(0), "r"(grp % 2 * 4) : "memory");
                if (i == 16 || i == 24 || k == 16) mbar_wait_warp(dep + (first ? i & 8 : 24), 0);
                TRACE_S(62, i, 16); TRACE_S(63, i, 4);
                mbar_wait_warp(empty + (i & 3) * 8, ~i >> 2 & 1);
                load_tail(base + (i & 3) * G1_STAGE_BYTES, full + (i & 3) * 8, first ? (p ? &prm.xn : &prm.x) : &prm.a2,
                          first ? &prm.wu_tail : &prm.wd_tail, (first ? 0 : DM) + k * 64, rows(job), first ? k * 2 : k * 8);
            }
        }
        return;
    }
    if (warp == 9) {
        const uint32_t n0 = nanos(), c0 = clock();
#pragma unroll 1
        for (int j = 0; j < 3; j++) {
            flag_wait<true>(prm.flags + (F_LN + j) * 512 + (j < 2 ? lane % 4 * 4 + grp : lane % 16) * 32, epoch * CNT_LN);
            fence_proxy_async();
            __syncwarp();
            if (lane == 0 && j < 2) mbar_arrive(dep + j * 8);
        }
        mbar_wait_warp(sig + 8, 0);
        if (lane == 0) st_relaxed(prm.flags + F_PACE * 512 + 64 + grp, forecast(n0, c0, DUE, tag));
        uint4 v, w;
#pragma unroll 1
        for (int spins = 0; spins < (1 << 19); spins++) {
            v = ld_relaxed(prm.flags + F_PACE * 512 + lane / 2 * 4);
            w = ld_relaxed(prm.flags + F_PACE * 512 + 64);
            if (!__any_sync(0xffffffffu, untagged(v, tag) || untagged(w, tag))) break;
            __nanosleep(256);
        }
        const uint32_t ref = uniform(v.x);
        const int due = min(max((int)((grp & 2 ? w.z : w.x) - ref), -100000), 100000) * 8;
        int late = max(max((int)(v.x - ref), (int)(v.y - ref)), max((int)(v.z - ref), (int)(v.w - ref)));
        late = min(max(max(late, __shfl_xor_sync(0xffffffffu, late, 2)), -100000), 100000) * LATE_SCALE + lane / 4;
        TRACE_PUT(16 + lane / 4, late + (1 << 20));
        int place = 0, n = SHARE_MIN;
#pragma unroll 1
        for (int g = 0; g < 32; g += 4) place += __shfl_sync(0xffffffffu, late, g) > late;
        const bool swap = (__reduce_add_sync(0xffffffffu, place + 1 & 2 ? late : -late) ^ w.x - w.z) >> 31;
        const bool mine = (place + 1 >> 1 & 1 ^ swap) == grp / 2;
#pragma unroll 1
        for (int j = 4 * SHARE_MIN; j < SHARE_SUM; j++) {
            const int most = __reduce_max_sync(0xffffffffu, mine && n < SHARE_MAX ? late : INT_MIN);
            if (j >= SHARE_LOW && due + (j - 38) * SPARE_NS * 8 > most) break;
            if (j == 38) TRACE_PUT(32, most - due + (1 << 20));
            if (most == late) { n++; late -= SHARE_NS * 8; }
        }
        auto first = [](uint32_t bits, int n) { return bits & (1u << min(max(n, 0), 24)) - 1; };
        const uint32_t job = lane / 4 * 32 + n - 1;
        if (mine) st_relaxed(prm.flags + F_SHARE * 512 + rows(job) * 32,
                             epoch << 24 | first(0x2aaaaa, 2 * n) | first(0x104104, 6 * n - 66) | first(0x10410, 6 * n - 90) |
                             first(0x41041, 6 * n - 108));
        if (mine) TRACE_PUT(24 + lane / 4, n);
        sts32(base + PLAN_OFF, __reduce_or_sync(0xffffffffu, mine ? job << place / 2 * 8 : 0));
        if (lane == 0) mbar_arrive(dep + 16);
        flag_wait<true>(prm.flags + F_SECOND * 512 + lane % 16 * 32, epoch * CNT_LN);
        fence_proxy_async();
        __syncwarp();
        if (lane == 0) mbar_arrive(dep + 24);
        return;
    }
    if (warp > 9) {
#pragma unroll 1
        for (int j = 0; j < 8; j++) sts128(base + AUX_OFF + (warp - 10) * 8192 + (j & 4) * 4096 + (j & 3) * 512 + lane * 16, make_uint4(0, 0, 0, 0));
        while ((uint32_t)clock() - t0 < 9000) __nanosleep(256);
        fold_operands(prm, base, 8, grp, tag, warp - 10, lane);
        if (lane) return;
        mbar_arrive(folded);
        if (warp == 11) return;
        TRACE(60);
#pragma unroll 1
        for (int p = 0; p < 8; p++) {
            mbar_wait(sig + p * 8, 0);
            flag_add(prm.flags + (p < 4 ? F_EARLY : F_TAIL2) * 512 + rows(plan(p, lds32(base + PLAN_OFF))) * 32);
            TRACE_S(50, p, 3); TRACE_S(51, p, 7);
        }
        prm.epoch[blockIdx.x * 16] = epoch;
        TRACE_DUMP();
        return;
    }
    asm volatile("setmaxnreg.inc.sync.aligned.u32 %0;" :: "n"(CONSUMER_REGS) : "memory");
    const uint32_t da = desc_a(base + (warp >> 2) * 8192);
    uint4* out = prm.tail;
    float acc[128];
    uint32_t pk[64];
    float2 inv = make_float2(0.f, 0.f);
    int i = 0, last;
    uint32_t peer;
    asm volatile("mapa.shared::cluster.u32 %0, %1, %2;" : "=r"(peer) : "r"(empty), "r"(lane & 1));
    auto release = [&]() {
        if ((threadIdx.x & 126) == 0 && i <= last)
            asm volatile("mbarrier.arrive.shared::cluster.b64 _, [%0];" :: "r"(peer + (i - 1 & 3) * 8) : "memory");
    };
    auto store = [&](int j) {
        asm volatile("st.global.v4.u32 [%0], {%1,%2,%3,%4};" :: "l"(out + j / 2 * 8192 + j % 2 * 256),
                     "r"(pk[4 * j]), "r"(pk[4 * j + 1]), "r"(pk[4 * j + 2]), "r"(pk[4 * j + 3]) : "memory");
    };
    auto step = [&](int k, int left) {
        mbar_wait(full + (i & 3) * 8, i >> 2 & 1);
        TRACE_S(45, warp * 128 + i, 0);
        if (warp >= 4 && left == G1_SKEW) asm volatile("bar.sync 1, 256;" ::: "memory");
        mma_step_tail(acc, da + (i & 3) * (G1_STAGE_BYTES / 16), base + A_BYTES + (i & 3) * G1_STAGE_BYTES, k);
        if (warp < 4 && left == 1) asm volatile("bar.arrive 1, 256;" ::: "memory");
    };
    auto drip = [&](int p, int& n) {
        if (n > 0) { store(0); store(1); }
#pragma unroll
        for (int j = 8; j < 64; j++) asm volatile("mov.b32 %0, %1;" : "=r"(pk[j - 8]) : "r"(pk[j]));
        out += 8192;
        __syncwarp();
        if (--n == 0 && lane == 0) mbar_arrive(sig + p * 8 - 8);
    };
#pragma unroll
    for (int j = 0; j < 128; j++) asm volatile("mov.b32 %0, 0;" : "=f"(acc[j]));
#pragma unroll
    for (int j = 0; j < 64; j++) asm volatile("mov.b32 %0, 0;" : "=r"(pk[j]));
#pragma unroll 1
    for (int p = 0; p < 8; p++) {
        step(0, 0);
        i++;
        const uint32_t word = plan_word(base, lane), job = plan(p, word);
        last = __dp4a(word & 0x1f1f1f1fu, 0x01010101u, 4u * G1_KSTEPS);
#pragma unroll 1
        for (int left = job % 32, n = p ? 8 : 0; left > 0; left--) {
            if (i == G1_KSTEPS - 1) { mbar_wait(folded, 0); inv = fold(acc, base, warp >> 2); }
#pragma unroll 1
            do drip(p, n); while (n & 7 >> 31 - __clz(job % 32));
            step(1, left);
            wg_wait<1>();
            release();
            i++;
        }
        wg_wait<0>();
        fence_regs(acc);
        release();
        if (p == 0) {
#pragma unroll
            for (int j = 0; j < 128; j++) acc[j] *= j & 2 ? inv.y : inv.x;
            fence_regs(acc);
        }
        if (warp == 4) TRACE_PUT(46 + p + p / 4 * 3, (uint32_t)clock());
#pragma unroll
        for (int j = 0; j < 64; j++) pk[j] = pack_bf16(acc[2 * j], acc[2 * j + 1]);
        out = prm.tail + p / 4 * NGEMM * 512 + rows(job) * 512 + threadIdx.x;
    }
#pragma unroll
    for (int j = 0; j < 16; j++) store(j);
    __syncwarp();
    TRACE_S(58, warp, 4);
    if (lane == 0) mbar_arrive(sig + 56);
}

__device__ __forceinline__ int gate_col(int t, int nslot) { return t == 2 ? 960 + nslot * 64 : max(t * 1024 - 1536, 0) + nslot * 128; }

struct Role {
    int rank, role, mblk, nslot;
    __device__ __forceinline__ Role() {
        uint32_t id;
        asm volatile("mov.u32 %0, %%ctaid.x;" : "=r"(id));
        const uint32_t cl = id / 2;
        rank = id & 1;
        role = pick(cl < 4, 32 + cl * 8, cl - 8 + max(4u, (cl - 1) * 37 >> 8)) * 2 + rank;
        mblk = role & 15; nslot = role >> 4;
    }
};

__global__ void __cluster_dims__(2, 1, 1) __launch_bounds__(384, 1)
fused_kernel(const __grid_constant__ Params prm) {
    TRACE_GET(c0);
    const uint32_t base = smem_u32(smem_raw) & ~1023u;
    const uint32_t bars = base + BAR_OFF;
    auto full1 = [&](int s) { return bars + s * 8; };
    auto empty1 = [&](int s) { return bars + 32 + s * 8; };
    auto full2 = [&](int s) { return bars + 64 + s * 8; };
    auto empty2 = [&](int s) { return bars + 128 + s * 8; };
    const uint32_t sig_bar = bars + 192, dep_bar = bars + 256, cs_bar = bars + 304, fold_bar = bars + 320, x_bar = bars + 352;
    const uint32_t halo_bar = dep_bar + 32;
    auto stage2 = [&](int q) { return base + q * G2_STAGE_BYTES; };
    const uint32_t aux = base + AUX_OFF;

    asm volatile("{\n.reg .pred p;\nsetp.eq.u32 p, %1, 0;\n@p mbarrier.init.shared::cta.b64 [%0], 1;\n"
        "fence.mbarrier_init.release.cluster;\nbarrier.cluster.arrive.relaxed.aligned;\n}" :: "r"(bars), "r"(threadIdx.x) : "memory");
    const int warp = __shfl_sync(0xffffffffu, threadIdx.x >> 5, 0);
    auto cluster_wait = []() { asm volatile("barrier.cluster.wait.acquire.aligned;" ::: "memory"); };
    if ((warp | (blockIdx.x & NGEMM)) == 8) {
        const Role r;
        asm volatile("{\n.reg .pred e;\nelect.sync _|e, 0xffffffff;\n"
            "@e prefetch.tensormap [%0];\n@e prefetch.tensormap [%1];\n}" :: "l"(&prm.x), "l"(&prm.wg + r.rank) : "memory");
        cluster_wait();
        load_stage1(base, base + A_BYTES + r.rank * 16384, full1(0), &prm.x, &prm.wg + r.rank, &prm.wg + r.rank, 0, r.mblk * 64,
                    r.nslot * 128, r.nslot * 128 + 64, 0, stream_policy());
    } else {
        cluster_wait();
    }
    const uint32_t t0 = clock();
    {
        uint32_t cta;
        asm volatile("mov.u32 %0, %%ctaid.x;" : "=r"(cta));
        if ((warp | (~cta & NGEMM)) == 8) load_tail(base, full1(0), &prm.x, &prm.wu_tail, 0, cta - NGEMM, 0);
    }
    asm volatile("{\n.reg .pred e, q;\nelect.sync _|e, 0xffffffff;\nsetp.ne.and.u32 q, %2, 0, e;\n"
        "@q mbarrier.init.shared::cta.b64 [%0], %1;\n@e mbarrier.init.shared::cta.b64 [%0 + 8], %1;\n"
        "@e mbarrier.init.shared::cta.b64 [%0 + 16], %1;\n@e mbarrier.init.shared::cta.b64 [%0 + 24], %1;\n"
        "fence.mbarrier_init.release.cluster;\nbarrier.cluster.arrive.relaxed.aligned;\n}"
        :: "r"(bars + warp * 32), "r"(1 << (0x10fa08 >> warp * 2 & 3)), "r"(warp) : "memory");
    const int lane = threadIdx.x & 31;
    const Role me;
    const int rank = me.rank, role = me.role, mblk = me.mblk, nslot = me.nslot;
    const CUtensorMap* const w0 = &prm.wg + rank;

    unsigned* const flags = prm.flags + mblk * 32;
    if (warp >= 8) {
        asm volatile("setmaxnreg.dec.sync.aligned.u32 %0;" :: "n"(AUX_REGS));
        if (warp == 9) { TRACE_CLEAR(); TRACE_GT(0); TRACE_PUT(1, c0); }
        if ((warp | (~blockIdx.x & NGEMM)) == 8) {
#pragma unroll 1
            for (int i = 1; i < G1_STAGES; i++) {
                if (i == 1) cluster_wait();
                TRACE_S(57, i, 1);
                load_tail(base + i * G1_STAGE_BYTES, full1(i), &prm.x, &prm.wu_tail, i * 64, blockIdx.x - NGEMM, i * 2);
            }
        } else {
            cluster_wait();
        }
    }

    if (blockIdx.x >= NGEMM) {
        if (warp < 8) cluster_wait();
        const uint32_t seen = __ldcg(prm.epoch + blockIdx.x * 16);
        tail_gemm(prm, base, t0, seen + 1, blockIdx.x - NGEMM, warp, lane);
    } else if (warp == 9) {
        const unsigned epoch = __ldcg(prm.epoch + blockIdx.x * 16 + 2) + 1;
        const uint32_t n0 = nanos(), c1 = clock();
        {
            const __nv_bfloat16* const w = prm.pwu + ((mblk >> 1) * 128 + lane / 2) * DF + gate_col(4, nslot) + 96 + rank * 16 + lane % 2 * 8;
            uint4 v[8];
            float cs[8], f[8];
            mbar_wait(empty1(SUM2_STEP), 0);
#pragma unroll
            for (int j = 0; j < 8; j++) v[j] = __ldg(reinterpret_cast<const uint4*>(w + j * 16 * DF));
            unpack8(v[0], cs);
#pragma unroll
            for (int j = 1; j < 8; j++) {
                unpack8(v[j], f);
#pragma unroll
                for (int d = 0; d < 8; d++) cs[d] += f[d];
            }
#pragma unroll
            for (int d = 0; d < 4; d++)
                cs[d] = (lane & 16 ? cs[d + 4] : cs[d]) + __shfl_xor_sync(0xffffffffu, lane & 16 ? cs[d] : cs[d + 4], 16);
#pragma unroll
            for (int d = 0; d < 2; d++) {
                cs[d] = (lane & 8 ? cs[d + 2] : cs[d]) + __shfl_xor_sync(0xffffffffu, lane & 8 ? cs[d] : cs[d + 2], 8);
                cs[d] += __shfl_xor_sync(0xffffffffu, cs[d], 4);
                cs[d] += __shfl_xor_sync(0xffffffffu, cs[d], 2);
            }
            if (!(lane & 6))
                st_tagged(prm.colsum + (16 + nslot / 4) * 1024 + (mblk >> 1) * 128 + nslot % 4 * 32 + rank * 16 + lane % 2 * 8 + (lane >> 3) * 2,
                          cs[0], cs[1], 1 + (epoch & 1));
            TRACE(61);
        }
        if (lane == 0) {
            mbar_wait(sig_bar, 0);
            TRACE(11);
            flag_add(flags + F_LN * 512);
            TRACE(42);
            flag_wait(flags + F_LN * 512, epoch * CNT_LN);
            fence_proxy_async();
            mbar_arrive(dep_bar);
            mbar_wait(sig_bar + 56, 0);
            flag_add(flags + F_LN2 * 512);
            flag_wait(flags + F_LN2 * 512, epoch * CNT_LN);
            fence_proxy_async();
            mbar_arrive(dep_bar + 40);
            TRACE(59);
            prm.epoch[blockIdx.x * 16 + 2] = epoch;
#pragma unroll 1
            for (int p = 3; p < 7; p++) {
                mbar_wait(sig_bar + (p == 3 ? 16 : p * 8), 0);
                TRACE_S(37, p, 4);
                flag_add(flags + (p - (p < F_EARLY)) * 512);
                TRACE_S(43, p, 4);
                if (p == 3 && rank == 0) {
                    mbar_wait(sig_bar + 24, 0);
                    st_relaxed(prm.flags + F_PACE * 512 + mblk * 4 + nslot, forecast(n0, c1, REST, 1 + (epoch & 1)));
                }
            }
        }
    } else if (warp < 8) {
        asm volatile("setmaxnreg.inc.sync.aligned.u32 %0;" :: "n"(CONSUMER_REGS));
        const int wg = __shfl_sync(0xffffffffu, threadIdx.x >> 7, 0);
        const int cw = threadIdx.x >> 5;
        const int tid = threadIdx.x & 127;
        int spins = 1 << 18;
        float acc[128];
        uint32_t pk[64];
#pragma unroll
        for (int i = 0; i < 64; i++) asm volatile("mov.b32 %0, 0;" : "=r"(pk[i]));
#pragma unroll
        for (int i = 0; i < 128; i++) asm volatile("mov.b32 %0, 0;" : "=f"(acc[i]));
        cluster_wait();

        auto row0 = [&](uint32_t id) { return mblk * 128 + (id & 96) + wg; };
        __nv_bfloat16* optr = prm.pxn + (mblk * 128 + nslot * 16 + cw * 2) * DM + lane * 8;
        uint64_t da = desc_a(base + wg * 8192) | (uint64_t)prm.hi[0] << 32, db = desc_b(base + A_BYTES) | (uint64_t)prm.hi[1] << 32;
        auto next1 = [](int s) { return ((s + 1) % G1_STAGES - s) * G1_STAGE_BYTES; };
        auto next2 = [](int q) { return ((q + 1) % G2_STAGES - q) * G2_STAGE_BYTES; };
        uint32_t peer_bars;
        asm volatile("mapa.shared::cluster.u32 %0, %1, %2;" : "=r"(peer_bars) : "r"(bars), "r"(tid & 1));
        if (tid >= 2) peer_bars = 0;
        auto release = [&](uint32_t bar) {
            if (peer_bars) asm volatile("mbarrier.arrive.shared::cluster.b64 _, [%0];" :: "r"(peer_bars + (bar - bars)) : "memory");
        };
        auto up = [](int i) { return 32 + (i & 24) + (i & 3) * 2 + (i >> 2 & 1); };
        auto store_pk = [&](__nv_bfloat16* p, int j) {
            asm volatile("st.global.v4.u32 [%0], {%1,%2,%3,%4};"
                         :: "l"(p), "r"(pk[4 * j]), "r"(pk[4 * j + 1]), "r"(pk[4 * j + 2]), "r"(pk[4 * j + 3]) : "memory");
        };
        auto chunk_geglu = [&](int j) {
#pragma unroll
            for (int i = 4 * j; i < 4 * j + 4; i++) pk[i] = geglu2(pk[i], pk[up(i)]);
            store_pk(optr + (j & 1) * 16 * K2 + (j >> 1) * 32, j);
        };
        auto signal_stores = [&](int p) { __syncwarp(); if (lane == 0) mbar_arrive(sig_bar + p * 8); };

        auto chunk_ln = [&](int k) {
            Floats<6> mo(pk + 32);
            if (k == 0) {
                const uint4* xp = reinterpret_cast<const uint4*>(prm.px + (optr - prm.pxn));
                pk[38] = __ldcg(prm.epoch + blockIdx.x * 16 + 2);
#pragma unroll
                for (int i = 0; i < 8; i++) {
                    const uint4 v = ldg_stream(xp + i * 32, stream_policy());
                    pk[4 * i] = v.x; pk[4 * i + 1] = v.y; pk[4 * i + 2] = v.z; pk[4 * i + 3] = v.w;
                }
            } else if (k >= LN_STEP && k < LN_STEP + 3) {
                if (k == LN_STEP) {
                    mo[0] = bf_lo(uniform(pk[0])); mo[1] = bf_lo(uniform(pk[16]));
                    mo[2] = mo[3] = mo[4] = mo[5] = 0.f;
                }
#pragma unroll
                for (int i = (k - LN_STEP) * 11; i < (k - LN_STEP) * 11 + 11 && i < 32; i++) {
                    const int r = i & 1;
                    const uint32_t w = pk[r * 16 + i / 2];
                    const float lo = bf_lo(w) - mo[r], hi = bf_hi(w) - mo[r];
                    mo[2 + r] += lo + hi;
                    mo[4 + r] = fmaf(hi, hi, fmaf(lo, lo, mo[4 + r]));
                }
                mo.put(pk + 32);
            } else if (k == LN_STEP + 3) {
                const bool second = lane & 16;
                float m1 = (second ? mo[3] : mo[2]) + __shfl_xor_sync(0xffffffffu, second ? mo[2] : mo[3], 16);
                float m2 = (second ? mo[5] : mo[4]) + __shfl_xor_sync(0xffffffffu, second ? mo[4] : mo[5], 16);
#pragma unroll
                for (int o = 8; o > 0; o >>= 1) {
                    m1 += __shfl_xor_sync(0xffffffffu, m1, o);
                    m2 += __shfl_xor_sync(0xffffffffu, m2, o);
                }
                m1 *= 1.f / DM;
                const float var = fmaxf(fmaf(-m1, m1, m2 * (1.f / DM)), 0.f);
                const float mean = round_bf16((second ? mo[1] : mo[0]) + m1);
                const float inv = rcp_fast(round_bf16(sqrt_fast(round_bf16(round_bf16(var) + 1e-5f))));
                if ((lane & 15) == 0) st_tagged(prm.stats + (uint32_t)(optr - prm.pxn) / DM + second, -mean, inv, 2 - (pk[38] & 1));
                const uint32_t split = pack_bf16(inv - round_bf16(inv), inv);
#pragma unroll
                for (int r = 0; r < 2; r++) {
                    const uint32_t f = __shfl_sync(0xffffffffu, split, r * 16);
                    pk[32 + 3 * r] = __byte_perm(__shfl_sync(0xffffffffu, __float_as_uint(mean), r * 16), 0, 0x3232);
                    pk[33 + 3 * r] = __byte_perm(f, 0, 0x3232);
                    pk[34 + 3 * r] = __byte_perm(f, 0, 0x1010);
                }
            } else if (k >= LN_STEP + 4 && k < LN_STEP + 8) {
#pragma unroll
                for (int i = k - LN_STEP - 4; i < 8; i += 4) {
                    const uint32_t* n = pk + 32 + i / 4 * 3;
#pragma unroll
                    for (int j = 4 * i; j < 4 * i + 4; j++) pk[j] = mul2_bf16x2(sub_bf16x2(pk[j], n[0]), n[1], n[2]);
                    store_pk(optr + i * 256, i);
                }
                if (k == LN_STEP + 5 || k == LN_STEP + 7) signal_stores(k == LN_STEP + 5 ? 0 : 7);
            } else if (k == FOLD_STEP) {
                mbar_wait(fold_bar, 0, spins);
                const float2 inv = fold(acc, base, wg);
                mo[0] = inv.x; mo[1] = inv.y;
                mo.put(pk + 32);
            }
        };

        auto halo = [&]() { const uint32_t id = fresh_tid(); return aux + (id & 96) * 128 + (id & 128) * 16 + (id & 31) * 4; };
        auto put = [&](uint32_t a, uint32_t v0, uint32_t v1) {
            asm volatile("st.shared.u32 [%0], %1;\nst.shared.u32 [%0 + 128], %2;" :: "r"(a + HALO_BYTES), "r"(v0), "r"(v1) : "memory");
        };
        auto get = [&](uint32_t a, uint32_t& v0, uint32_t& v1) {
            asm volatile("ld.shared.u32 %0, [%2];\nld.shared.u32 %1, [%2 + 128];" : "=r"(v0), "=r"(v1) : "r"(a) : "memory");
        };
        auto publish = [&](int p) { asm volatile("fence.proxy.async.shared::cta;" ::: "memory"); signal_stores(p); };
        const uint32_t zero[4] = {0, 0, 0, 0};
        auto meet = [&](int n, int k, uint32_t id) {
            if (n == 15 - MEET)
                asm volatile("{\n.reg .b32 c;\nmov.u32 c, %%clock;\nbar.arrive %1, 256;\nlop3.b32 %0, %0, c, 1, 0x70;\n}"
                             : "+r"(peer_bars) : "r"(2 + id / 128) : "memory");
            if (n == 15) {
                asm volatile("{\n.reg .b32 c;\nmov.u32 c, %%clock;\nbar.sync %1, 256;\nlop3.b32 %0, %0, c, 1, 0x70;\n}"
                             : "+r"(peer_bars) : "r"(3 - id / 128) : "memory");
                mma_step(acc, da, db, next1(k & 3), k);
                asm volatile("// batch step");
            }
        };
        auto mix_qk = [&]() {
            uint32_t c[2][4];
            const uint32_t a = halo(), id = fresh_tid();
            mbar_wait(halo_bar, 0, spins);
#pragma unroll
            for (int n = 0; n < 16; n++) {
                const int b = 1 - n / 8, h = (n & 4) / 2 + n % 2, j = n / 2 % 2;
                uint32_t* const kq = pk + 32 + 8 * h + 4 * j;
                uint32_t* const q = pk + 8 * h + 4 * b;
                mma_sync(j ? q : c[n % 2], kq, q[2 * j], q[2 * j + 1], j ? c[n % 2] : zero);
                if (b) get(a + (h * 2 + j) * 256, kq[1], kq[3]);
                meet(n, QK_STEP, id);
            }
        };
        auto chunk_qk = [&](int k) {
            constexpr float LOG2E = 1.4426950408889634f;
            uint32_t* const l = pk + 32;
            Floats<16> e(pk);
            if (k == KEY_STEP) {
                const uint32_t a = halo();
#pragma unroll
                for (int i = 0; i < 8; i++) put(a + i * 256, pk[33 + 4 * i], pk[35 + 4 * i]);
                publish(1);
            } else if (k == QK_STEP + 1) {
                const uint32_t id = fresh_tid();
                const bool u0 = id % 32 / 4 > id % 4 * 2, u1 = id % 32 / 4 > id % 4 * 2 + 1;
                const uint32_t gone = row0(id) < 2 ? (u0 ? 0xffffu : 0u) | (u1 ? 0xffff0000u : 0u) : 0u;
#pragma unroll
                for (int n = 0; n < 8; n++) {
                    const int b = n % 2;
                    const uint32_t* const c = pk + 4 * n;
                    uint32_t v = pack_bf16(__uint_as_float(pick(u0, c[2 - 2 * b], c[2 * b])), __uint_as_float(pick(u1, c[3 - 2 * b], c[1 + 2 * b])));
                    v = mul2_bf16x2(v, 0x3e353e35u, 0x379e379eu);
                    if (!b) v = v & ~gone | 0xce6ece6eu & gone;
                    l[n] = transpose8(v);
                }
            } else if (k == QK_STEP + 2) {
#pragma unroll
                for (int h = 0; h < 4; h++) {
                    uint32_t m = max_bf16x2(__byte_perm(l[2 * h], l[2 * h + 1], 0x5410), __byte_perm(l[2 * h], l[2 * h + 1], 0x7632));
                    m = max_bf16x2(m, __shfl_xor_sync(0xffffffffu, m, 1));
                    m = max_bf16x2(m, __shfl_xor_sync(0xffffffffu, m, 2));
#pragma unroll
                    for (int n = 2 * h; n < 2 * h + 2; n++) {
                        const float f = -LOG2E * (n % 2 ? bf_hi(m) : bf_lo(m));
                        e[2 * n] = ex2_fast(fmaf(bf_lo(l[n]), LOG2E, f));
                        e[2 * n + 1] = ex2_fast(fmaf(bf_hi(l[n]), LOG2E, f));
                    }
                }
                e.put(pk);
            } else if (k == QK_STEP + 3) {
                uint32_t p[8];
#pragma unroll
                for (int n = 0; n < 8; n++) {
                    float sum = e[2 * n] + e[2 * n + 1];
                    sum += __shfl_xor_sync(0xffffffffu, sum, 1);
                    sum += __shfl_xor_sync(0xffffffffu, sum, 2);
                    const float r = rcp_fast(sum);
                    p[n] = pack_bf16(e[2 * n] * r, e[2 * n + 1] * r);
                }
                const uint32_t a = aux + 5 * HALO_BYTES + fresh_tid() * 16;
                sts128(a, make_uint4(p[0], p[1], p[2], p[3]));
                sts128(a + 4096, make_uint4(p[4], p[5], p[6], p[7]));
            }
        };
        auto values = [&](int h) { return pk + (h & 2) * 16 + (h & 1) * 8; };
        auto mix_pv = [&]() {
            uint32_t lo[8], hi[8];
            const uint32_t id = fresh_tid();
            const uint32_t keep = (id % 4 * 2 > id % 32 / 4 ? 0xffffu : 0u) | (id % 4 * 2 + 1 > id % 32 / 4 ? 0xffff0000u : 0u);
            const uint4 p0 = lds128(aux + 5 * HALO_BYTES + id * 16), p1 = lds128(aux + 6 * HALO_BYTES + id * 16);
            const uint32_t p[8] = {p0.x, p0.y, p0.z, p0.w, p1.x, p1.y, p1.z, p1.w};
#pragma unroll
            for (int n = 0; n < 8; n++)
                asm volatile("and.b32 %0, %2, %3;\nand.b32 %1, %2, %4;" : "=r"(lo[n]), "=r"(hi[n])
                             : "r"(p[n]), "r"(n % 2 ? keep : ~keep), "r"(n % 2 ? ~keep : keep));
            mbar_wait(halo_bar, 1, spins);
#pragma unroll
            for (int n = 0; n < 16; n++) {
                const int i = (n & 8) / 2 + (n & 2) + (n & 4) / 4;
                mma_sync(pk + 4 * (n ^ 4), pk + 4 * (n ^ 4), lo[i], hi[i], zero);
                meet(n, PV_STEP, id);
            }
        };
        auto chunk_pv = [&](int k) {
            if (k == VAL_STEP || k == VAL_STEP + 1) {
                const uint32_t a = halo();
#pragma unroll
                for (int h = (k - VAL_STEP) * 2; h < (k - VAL_STEP + 1) * 2; h++) {
                    uint32_t* const w = values(h);
                    uint32_t v[8];
#pragma unroll
                    for (int i = 0; i < 8; i++) v[i] = transpose8(w[h < 2 ? (i & 1) + (i & 2) * 2 + (i & 4) / 2 : (i & 1) * 2 + (i & 2) / 2 + (i & 4)]);
#pragma unroll
                    for (int i = 0; i < 8; i++) w[i] = v[i];
                    put(a + h * 512, w[2], w[3]);
                    put(a + h * 512 + 256, w[6], w[7]);
                }
                if (k > VAL_STEP) publish(3);
            } else if (k == PV_STEP - 1) {
                const uint32_t a = halo(), id = fresh_tid();
                optr = prm.pa2 + (size_t)(row0(id) + id % 4 * 4) * K2 + nslot * 128 + (id & 28) * 2;
                mbar_wait(halo_bar, 1, spins);
#pragma unroll
                for (int n = 0; n < 8; n++) {
                    uint32_t* const w = values(n / 2) + n % 2 * 4;
                    w[16] = w[0]; w[17] = w[1];
                    get(a + n * 256, w[18], w[19]);
                }
            } else if (k > PV_STEP && k <= PV_STEP + OUT_STEPS) {
#pragma unroll
                for (int j = 0; j < 8; j++) {
                    if (j * OUT_STEPS / 8 != k - PV_STEP - 1) continue;
                    Floats<15> c(pk + j / 2 * 16 + j % 2);
                    asm volatile("st.global.v4.u32 [%0], {%1,%2,%3,%4};"
                                 :: "l"(optr + ((~j & 2) * 8 + j % 2 * 2) * K2 + j / 4 * 64), "r"(pack_bf16(c[0], c[2])),
                                    "r"(pack_bf16(c[4], c[6])), "r"(pack_bf16(c[8], c[10])), "r"(pack_bf16(c[12], c[14])) : "memory");
                }
                if (k == PV_STEP + OUT_STEPS) signal_stores(4);
            }
        };

        TRACE_SLOT(tile_slot, 16 + wg * 8);
#pragma unroll 1
        for (int t = 0; t < G1_TILES; t++) {
#pragma unroll
            for (int k = 0; k < G1_KSTEPS; k++) {
                const int s = k & 3;
                if (k == 0) asm volatile("" : "+r"(t));
                TRACE_STEP(t, k, 0);
                mbar_wait(full1(s), (k >> 2) & 1, spins);
                if (k == 0) TRACE_S(12, t, 0);
                TRACE_STEP(t, k, 1);
                if (wg == 1 && k == G1_KSTEPS - G1_SKEW) asm volatile("bar.sync 1, 256;" ::: "memory");
                if (k == PV_STEP && t == 3) mix_pv();
                else if (k == QK_STEP && t == 2) mix_qk();
                else if (t == G1_TILES - 1) mma_step224(acc, da, db, next1(s), k);
                else mma_step(acc, da, db, next1(s), k);
                if (wg == 0 && k == G1_KSTEPS - 1) asm volatile("bar.arrive 1, 256;" ::: "memory");
                wg_wait<1>();
                if (k > 0) release(empty1((k - 1) & 3));
                TRACE_STEP(t, k, 2);
                if (t == 0) chunk_ln(k);
                if (k >= 1 && k <= 8 && ((k < HALF_STEP || k > HALF_STEP + 3 ? 0x12 : 0x1a) >> t & 1)) {
                    chunk_geglu(k < HALF_STEP ? k - 1 : (k > HALF_STEP + 3 ? k - 5 : k - HALF_STEP + 4));
                    if (k == 8 && t != 3) signal_stores(t + 1);
                }
                if (t == 2) chunk_qk(k);
                if (t == 3) chunk_pv(k);
                if (k == PV_STEP + OUT_STEPS) {
                    const uint32_t id = fresh_tid();
                    optr = prm.pa2 + (size_t)(row0(id) + (id & 28) / 2) * K2 + DM + gate_col(t, nslot) + id % 4 * 8;
                    asm volatile("" : "+l"(optr));
                }
            }
            wg_wait<0>();
            fence_regs(acc);
            release(empty1(3));
            if (t == 0) {
                Floats<2> inv(pk + 32);
#pragma unroll
                for (int i = 0; i < 128; i++) acc[i] *= inv[i / 2 % 2];
                fence_regs(acc);
            }
#pragma unroll
            for (int i = 0; i < 64; i++) {
                const int e = i < 32 ? (i & ~7) * 2 + (i & 3) * 4 + (i & 4) / 2 : i * 2;
                pk[i] = pack_bf16(acc[e], acc[e + 1]);
            }
            TRACE_NEXT(tile_slot);
        }

        float accd[64], accs[64];
#pragma unroll
        for (int i = 0; i < 64; i++) accd[i] = 0.f;
#pragma unroll
        for (int u = 0; u < G2_HEAD; u++) {
            const int q = u % G2_STAGES;
            mbar_wait(full2(q), (u / G2_STAGES) & 1, spins);
            if (u % 2) mma_step_c(accd, da, db, next2(q), u);
            else mma_step(accd, da, db, next2(q), u);
            wg_wait<1>();
            if (u > 0) release(empty2((u - 1) % G2_STAGES));
            if (u == UP_STEP) {
#pragma unroll
                for (int i = 0; i < 2; i++) {
                    const uint4 v = ldg_stream(prm.tail + role * 512 + i * 256 + threadIdx.x, stream_policy());
                    pk[56 + 4 * i] = v.x; pk[57 + 4 * i] = v.y; pk[58 + 4 * i] = v.z; pk[59 + 4 * i] = v.w;
                }
            }
            if (u >= 1) {
                const int j = (u - 1) / 2;
#pragma unroll
                for (int i = 2 * u - 2; i < 2 * u; i++) pk[i] = geglu2(pk[i], pk[up(i)]);
                if (u % 2 == 0) store_pk(optr + (j & 1) * 16 * K2 + (j >> 1) * 32, j);
            }
            if (u == G2_HEAD - 1) signal_stores(6);
        }
        auto down = [&](int q, uint32_t phase, bool narrow, bool busy = false) {
            mbar_wait(full2(q), phase, spins);
            if (narrow) mma_step96(accd, da, db, next2(q), 1);
            else if (busy) mma_step_c(accd, da, db, next2(q), 1);
            else mma_step(accd, da, db, next2(q), 1);
            wg_wait<1>();
            release(empty2((q + G2_STAGES - 1) % G2_STAGES));
        };
        uint32_t shared_steps = plan_word(base, lane);
        down(5, 0, false);
#pragma unroll 1
        for (uint32_t r = 3; r < 9; r++, shared_steps >>= G2_STAGES) {
#pragma unroll
            for (int q = 0; q < G2_STAGES; q++) down(q, r & 1, shared_steps >> q & 1);
        }
        down(0, 1, false);
        down(1, 1, false, true);
        TRACE_NEXT(tile_slot);
#pragma unroll
        for (int i = 0; i < 64; i++) accs[i] = 0.f;
        uint32_t gk[32], xr[32];
        const uint32_t xs = aux + cw * 2048;
        const uint32_t xrow = xs + ((lane & 7) + ((lane >> 3) & 1) * 8) * 128;
        auto xaddr = [&](int j) { return xrow + (j >> 2) * 16384 + (((((j & 3) * 2) + (lane >> 4)) ^ (lane & 7)) << 4); };
#pragma unroll
        for (int u = G2_DSTEPS; u < G2_KSTEPS; u++) {
            const int q = u % G2_STAGES, v = u - G2_DSTEPS;
            mbar_wait(full2(q), (u / G2_STAGES) & 1, spins);
            if (wg == 1 && u == G2_KSTEPS - G2_SKEW) asm volatile("bar.sync 1, 256;" ::: "memory");
            if (u % 2) mma_step_c(accs, da, db, next2(q), v);
            else mma_step(accs, da, db, next2(q), v);
            if (wg == 0 && u == G2_KSTEPS - 1) asm volatile("bar.arrive 1, 256;" ::: "memory");
            if (v == TAIL_STEP) {
                TRACE_S(32, wg, 0);
                mbar_wait(dep_bar + 24, 0, spins);
                TRACE_S(33, wg, 0);
#pragma unroll
                for (int i = 0; i < 2; i++) {
                    const uint4 w = ldg_stream(prm.tail + (NGEMM + role) * 512 + i * 256 + threadIdx.x, stream_policy());
                    gk[24 + 4 * i] = w.x; gk[25 + 4 * i] = w.y; gk[26 + 4 * i] = w.z; gk[27 + 4 * i] = w.w;
                }
            }
#pragma unroll
            for (int i = 0; i < 32; i++) {
                if (v == (i < 24 ? i / 4 + 1 : TAIL_STEP + i / 4 - 3))
                    gk[i] = i < 24 ? silu2(accd[2 * i], accd[2 * i + 1])
                                   : silu2(accd[2 * i] + bf_lo(gk[i]), accd[2 * i + 1] + bf_hi(gk[i]));
            }
            if (v == XREAD_STEP) mbar_wait(x_bar, 0, spins);
            if (v >= XREAD_STEP && v < XREAD_STEP + 4) {
#pragma unroll
                for (int j = 2 * (v - XREAD_STEP); j < 2 * (v - XREAD_STEP + 1); j++)
                    asm volatile("ldmatrix.sync.aligned.m8n8.x4.shared.b16 {%0,%1,%2,%3}, [%4];"
                                 : "=r"(xr[4 * j]), "=r"(xr[4 * j + 1]), "=r"(xr[4 * j + 2]), "=r"(xr[4 * j + 3])
                                 : "r"(xaddr(j)) : "memory");
            }
            wg_wait<1>();
            if (v == 0) fence_regs(accd);
            if (u - 1 + G2_STAGES < G2_KSTEPS) release(empty2((u - 1) % G2_STAGES));
        }
        __nv_bfloat16* po = prm.pout + (row0(fresh_tid()) + (lane >> 3) * 2) * DM + nslot * 128 + 64 + (lane & 7) * 8;
        uint32_t so = xs + 16384 + (lane >> 3) * 128 + (((lane & 7) ^ (lane >> 3)) << 4);
        const int c0 = uniform(nslot * 128), c1 = uniform(row0(fresh_tid()) >> 1);
        const uint32_t xu = uniform(xs);
        asm volatile("" : "+l"(po), "+r"(so));
        wg_wait<0>();
        fence_regs(accs);
        TRACE_NEXT(tile_slot);
        TRACE_END();
#pragma unroll
        for (int j = 0; j < 8; j++) {
            uint32_t r[4];
#pragma unroll
            for (int i = 0; i < 4; i++) {
                const int e = j * 4 + i;
                asm("fma.rn.bf16x2 %0, %1, %2, %3;" : "=r"(r[i]) : "r"(pack_bf16(accs[2 * e], accs[2 * e + 1])), "r"(gk[e]), "r"(xr[e]));
            }
            asm volatile("stmatrix.sync.aligned.m8n8.x4.shared.b16 [%0], {%1,%2,%3,%4};"
                         :: "r"(xaddr(j)), "r"(r[0]), "r"(r[1]), "r"(r[2]), "r"(r[3]) : "memory");
            if (j == 3)
                asm volatile("{\n.reg .pred e;\nfence.proxy.async.shared::cta;\nbar.warp.sync 0xffffffff;\nelect.sync _|e, 0xffffffff;\n"
                    "@e cp.async.bulk.tensor.3d.global.shared::cta.bulk_group [%0, {%2, %3, %4}], [%1];\n}"
                    :: "l"(&prm.out), "r"(xu), "r"(c0), "r"(c1), "r"(wg) : "memory");
        }
        __syncwarp();
#pragma unroll
        for (int i = 0; i < 4; i++) {
            const uint4 v = lds128((so ^ (i & 1) * 64) + i * 512);
            asm volatile("st.global.v4.u32 [%0], {%1,%2,%3,%4};" :: "l"(po + i * 8 * DM), "r"(v.x), "r"(v.y), "r"(v.z), "r"(v.w) : "memory");
        }
        asm volatile("cp.async.bulk.commit_group;\ncp.async.bulk.wait_group.read 0;" ::: "memory");
        TRACE_LITE(10, clock());
        if (tid == 0) { TRACE_NEXT(tile_slot); if (wg == 1) TRACE_GT(13); TRACE_DUMP(); }
    } else if (warp > 9) {
        const int w = warp - 10;
        const unsigned epoch = __ldcg(prm.epoch + blockIdx.x * 16 + w) + 1;
        const uint32_t tag = 1 + (epoch & 1);
        TRACE_LITE(8, t0);
        const uint32_t at = (w ? SUM_LOAD1 : SUM_LOAD0) >> nslot * 4 & 15;
        mbar_wait(empty1(at & 3), 0);
        mbar_wait(empty1(at & 3), at >> 3);
        if (elect_one()) {
            mbar_expect_tx(cs_bar + w * 8, 16384);
            asm volatile("cp.async.bulk.tensor.2d.shared::cluster.global.mbarrier::complete_tx::bytes [%0], [%1, {%3, %5}], [%2];\n"
                "cp.async.bulk.tensor.2d.shared::cluster.global.mbarrier::complete_tx::bytes [%0 + 8192], [%1, {%4, %5}], [%2];"
                :: "r"(aux + w * 16384), "l"(w0), "r"(cs_bar + w * 8), "r"(nslot * 128), "r"(nslot * 128 + 64),
                   "r"(((mblk & ~1) + w) * 64) : "memory");
        }
        float cs[8];
#pragma unroll
        for (int d = 0; d < 8; d++) cs[d] = 0.f;
        const uint32_t wa = aux + w * 8192 + (lane >> 3) * 128 + (((lane & 7) ^ (lane >> 3)) << 4);
        uint4 v[8];
        auto fetch = [&](int h, uint32_t off) {
#pragma unroll
            for (int j = 0; j < 4; j++) v[h * 4 + j] = lds128((wa ^ (j & 1) * 64) + off + h * 2048 + j * 512);
        };
        auto add = [&](int h) {
#pragma unroll
            for (int j = 0; j < 4; j++) {
                float f[8];
                unpack8(v[h * 4 + j], f);
#pragma unroll
                for (int d = 0; d < 8; d++) cs[d] += f[d];
            }
        };
        mbar_wait(empty1(SUM_STEP & 3), 0);
        mbar_wait(empty1(SUM_STEP & 3), SUM_STEP >> 3);
        mbar_wait(cs_bar, 0);
        fetch(0, 0);
#pragma unroll 1
        for (int i = 0; i < 4; i++) {
            fetch(1, (i >> 1) * 16384 + (i & 1) * 4096);
            add(0);
            if (i == 1) mbar_wait(cs_bar + 8, 0);
            fetch(0, (i + 1 & 2) * 8192 + (~i & 1) * 4096);
            add(1);
        }
#pragma unroll
        for (int d = 0; d < 4; d++)
            cs[d] = (lane & 16 ? cs[d + 4] : cs[d]) + __shfl_xor_sync(0xffffffffu, lane & 16 ? cs[d] : cs[d + 4], 16);
#pragma unroll
        for (int d = 0; d < 2; d++)
            cs[d] = (lane & 8 ? cs[d + 2] : cs[d]) + __shfl_xor_sync(0xffffffffu, lane & 8 ? cs[d] : cs[d + 2], 8);
        st_tagged(prm.colsum + (nslot * 2 + rank) * 1024 + (mblk >> 1) * 128 + w * 64 + (lane & 7) * 8 + (lane >> 3) * 2,
                  cs[0], cs[1], tag);

        fold_operands(prm, base, nslot, mblk, tag, w, lane);
        if (lane == 0) {
            mbar_arrive(fold_bar);
            prm.epoch[blockIdx.x * 16 + w] = epoch;
            if (w == 0) {
                TRACE(35);
#pragma unroll 1
                for (uint32_t j = 0, n = 1 << 24; j < 4; n = (CNT_EARLY | CNT_LATE << 8 | 1 << 16) >> j * 8 & 255, j++) {
                    mbar_wait(sig_bar + (0xa0302820u >> j * 8 & 255), 0);
                    const uint32_t v = flag_wait(flags + (F_SHARE + j) * 512, epoch * n);
                    fence_proxy_async();
                    if (j) mbar_arrive(dep_bar + j * 8);
                    else sts32(base + PLAN_OFF, v & 0xffffff);
                }
            } else {
#pragma unroll 1
                for (int j = 0; j < 2; j++) {
                    uint8_t* const h = prm.halo + (j * NGEMM + role) * HALO_BYTES;
                    unsigned* const f = prm.flags + F_HALO * 512 + role * 32;
                    mbar_wait(sig_bar + 8 + j * 16, 0);
                    TRACE_S(38, j, 0); TRACE_S(9, j, 1);
                    asm volatile("cp.async.bulk.global.shared::cta.bulk_group [%0], [%1], %2;\n"
                        "cp.async.bulk.commit_group;\ncp.async.bulk.wait_group 0;"
                        :: "l"(h + HALO_BYTES), "r"(aux + 4 * HALO_BYTES), "n"(HALO_BYTES) : "memory");
                    fence_proxy_async();
                    TRACE_S(39, j, 0); TRACE_S(10, j, 1);
                    flag_add(f);
                    TRACE_S(40, j, 0); TRACE_S(34, j, 1);
                    if (mblk) flag_wait(f - 32, epoch * 2 - 1 + j);
                    fence_proxy_async();
                    TRACE_S(41, j, 0); TRACE_S(36, j, 1);
                    mbar_expect_tx(halo_bar, HALO_BYTES);
                    asm volatile("cp.async.bulk.shared::cluster.global.mbarrier::complete_tx::bytes [%0], [%1], %2, [%3];"
                        :: "r"(aux), "l"(mblk ? h : prm.halo), "n"(HALO_BYTES), "r"(halo_bar) : "memory");
                }
            }
        }
    } else {
#pragma unroll 1
        for (int k = 1; k < G1_STAGES; k++) {
            const uint32_t sa = base + k * G1_STAGE_BYTES;
            while ((uint32_t)clock() - t0 < (k == 3 ? PACE3 : PACE1 + (k - 1) * (PACE2 - PACE1))) {}
            load_stage1(sa, sa + A_BYTES + rank * 16384, full1(k), &prm.x, w0, w0, k * 64, mblk * 64, nslot * 128,
                        nslot * 128 + 64, 0, stream_policy());
        }
        if (elect_one()) {
            prefetch_map(&prm.xn); prefetch_map(&prm.wqkv);
            prefetch_map(&prm.a2); prefetch_map(&prm.wo); prefetch_map(&prm.wd); prefetch_map(&prm.out);
        }
        uint32_t ph = 0;
#pragma unroll 1
        for (int t = 0; t < G1_TILES; t++) {
            const int col1 = (t == 1 ? rank * DM + nslot * 128 : gate_col(t, nslot)) + 64;
            const int col0 = t == 2 ? 2 * DM + nslot * 128 + rank * 64 : col1 - 64;
            if (t == 1) { TRACE_PUT(2, t0); TRACE(14); mbar_wait_warp(dep_bar, 0); TRACE(3); }
#pragma unroll 1
            for (int k = t ? 0 : G1_STAGES; k < G1_KSTEPS; k++) {
                const int s = k & 3;
                if (t == 1 && k == 8) mbar_wait_warp(dep_bar + 40, 0);
                mbar_wait_warp(empty1(s), ph);
                const uint32_t sa = base + s * G1_STAGE_BYTES;
                load_stage1(sa, sa + A_BYTES + rank * 16384, full1(s), t ? &prm.xn : &prm.x, t == 1 || t == 2 ? &prm.wqkv : w0,
                            t == 1 ? &prm.wqkv : w0, k * 64, mblk * 64, col0, col1, t & 3,
                            stream_policy());
                if (s == 3) ph ^= 1;
            }
        }
        TRACE(4);
        mbar_wait_warp(dep_bar + 8, 0);
        TRACE(5);
        int q = 0, round = 4, own = SHARE_MAX; uint32_t ph2 = 1;
#pragma unroll 1
        for (int u = 0; u < G2_KSTEPS; u++) {
            if (u == G2_LATE) { TRACE(6); mbar_wait_warp(dep_bar + 16, 0); TRACE(7); }
            const uint32_t sa = stage2(q);
            const bool down = u < G2_DSTEPS;
            const int k = !down ? u - G2_DSTEPS : (u < 18 || u >= 40 ? own++ : (q & 1 ? u / 2 - 9 : round + (q ? q * 2 : 11)));
            mbar_wait_warp(u < G2_STAGES ? empty1((u * 2 + 1) / 3) : empty2(q), u < G2_STAGES ? ph : ph2);
            load_stage2(sa, sa + A_BYTES + rank * 8192, full2(q), &prm.a2, down ? &prm.wd : &prm.wo, (down ? DM : 0) + k * 64,
                        mblk * 64, nslot * 128 + rank * 64, down ? 0 : k * 2, down ? k * 2 : 0, stream_policy());
            if (u == XLOAD_STEP + nslot * 2) {
                if (elect_one()) {
                    mbar_expect_tx(x_bar, 32768);
                    tma_3d(aux, &prm.x, x_bar, nslot * 128, mblk * 64, 0, stream_policy());
                    tma_3d(aux + 16384, &prm.x, x_bar, nslot * 128 + 64, mblk * 64, 0, stream_policy());
                }
                __syncwarp();
            }
            if (++q == G2_STAGES) { q = 0; ph2 ^= 1; round++; }
        }
        TRACE(8);
    }
}

typedef CUresult (*EncodeFn)(CUtensorMap*, CUtensorMapDataType, cuuint32_t, void*, const cuuint64_t*, const cuuint64_t*,
                             const cuuint32_t*, const cuuint32_t*, CUtensorMapInterleave, CUtensorMapSwizzle,
                             CUtensorMapL2promotion, CUtensorMapFloatOOBfill);

void encode(EncodeFn fn, CUtensorMap* m, const void* ptr, int rank, const cuuint64_t* dims, const cuuint64_t* strides,
            const cuuint32_t* box) {
    const cuuint32_t es[5] = {1, 1, 1, 1, 1};
    fn(m, CU_TENSOR_MAP_DATA_TYPE_BFLOAT16, rank, const_cast<void*>(ptr), dims, strides, box, es,
       CU_TENSOR_MAP_INTERLEAVE_NONE, box[0] == 32 ? CU_TENSOR_MAP_SWIZZLE_64B : CU_TENSOR_MAP_SWIZZLE_128B,
       CU_TENSOR_MAP_L2_PROMOTION_L2_128B, CU_TENSOR_MAP_FLOAT_OOB_FILL_NONE);
}
void encode_rows(EncodeFn fn, CUtensorMap* m, const void* ptr, int cols, int box_rows, int box_parity) {
    const cuuint64_t dims[3] = {(cuuint64_t)cols, SEQ / 2, 2}, strides[2] = {(cuuint64_t)cols * 4, (cuuint64_t)cols * 2};
    const cuuint32_t box[3] = {64, (cuuint32_t)box_rows, (cuuint32_t)box_parity};
    encode(fn, m, ptr, 3, dims, strides, box);
}
void encode_w1(EncodeFn fn, CUtensorMap* m, const void* ptr, int cols) {
    const cuuint64_t dims[2] = {(cuuint64_t)cols, DM}, strides[1] = {(cuuint64_t)cols * 2};
    const cuuint32_t box[2] = {64, 64};
    encode(fn, m, ptr, 2, dims, strides, box);
}
void encode_tail(EncodeFn fn, CUtensorMap* m, const void* ptr, int rows, int cols, int n) {
    const cuuint64_t rb = cols * 2;
    const cuuint64_t dims[5] = {32, (cuuint64_t)n, (cuuint64_t)rows / (4 * n), 4, 8}, strides[4] = {rb, 4 * n * rb, n * rb, 256};
    const cuuint32_t box[5] = {32, (cuuint32_t)n, 16 / (cuuint32_t)n, 4, 4};
    encode(fn, m, (const __nv_bfloat16*)ptr + cols - 1024 + 96, 5, dims, strides, box);
}
void encode_w2(EncodeFn fn, CUtensorMap* m, const void* ptr, int rows) {
    const cuuint64_t rb = DM * 2;
    const cuuint64_t dims[5] = {DM, 2, 4, 4, (cuuint64_t)rows / 32}, strides[4] = {rb, 8 * rb, 2 * rb, 32 * rb};
    const cuuint32_t box[5] = {64, 2, 4, 4, 2};
    encode(fn, m, ptr, 5, dims, strides, box);
}
void encode_wo(EncodeFn fn, CUtensorMap* m, const void* ptr) {
    const cuuint64_t rb = DM * 2;
    const cuuint64_t dims[5] = {DM, 4, DM / 32, 2, 4}, strides[4] = {8 * rb, 32 * rb, rb, 2 * rb};
    const cuuint32_t box[5] = {64, 4, 2, 2, 4};
    encode(fn, m, ptr, 5, dims, strides, box);
}

}

extern "C" void kernel_launch(void* const* d_in, const int* in_sizes, int n_in, void* d_out, int out_size) {
    (void)in_sizes; (void)n_in; (void)out_size;
    static EncodeFn fn = nullptr;
    static Params prm;
    if (!fn) {
        cudaDriverEntryPointQueryResult st;
        cudaGetDriverEntryPoint("cuTensorMapEncodeTiled", (void**)&fn, cudaEnableDefault, &st);
        cudaGetSymbolAddress((void**)&prm.pxn, g_xn);
        cudaGetSymbolAddress((void**)&prm.pa2, g_a2);
        cudaGetSymbolAddress((void**)&prm.tail, g_tail);
        cudaGetSymbolAddress((void**)&prm.halo, g_halo);
        cudaGetSymbolAddress((void**)&prm.stats, g_stats);
        cudaGetSymbolAddress((void**)&prm.colsum, g_colsum);
        cudaGetSymbolAddress((void**)&prm.flags, g_flags);
        cudaGetSymbolAddress((void**)&prm.epoch, g_epoch);
        cudaFuncSetAttribute(fused_kernel, cudaFuncAttributeMaxDynamicSharedMemorySize, SMEM_BYTES);
    }
    encode_rows(fn, &prm.x, d_in[0], DM, 64, 2);
    encode_rows(fn, &prm.xn, prm.pxn, DM, 64, 2);
    encode_rows(fn, &prm.a2, prm.pa2, K2, 64, 2);
    encode_rows(fn, &prm.out, d_out, DM, 16, 1);
    encode_w1(fn, &prm.wqkv, d_in[1], NQKV);
    encode_w1(fn, &prm.wg, d_in[4], DF);
    encode_w1(fn, &prm.wu, d_in[5], DF);
    encode_tail(fn, &prm.wu_tail, d_in[5], DM, DF, 8);
    encode_tail(fn, &prm.wd_tail, d_in[6], DF, DM, 2);
    encode_wo(fn, &prm.wo, d_in[2]);
    encode_w2(fn, &prm.wd, d_in[6], DF);
    prm.hi[0] = prm.hi[1] = 0x40000040;
    prm.px = (const __nv_bfloat16*)d_in[0];
    prm.pwu = (const __nv_bfloat16*)d_in[5];
    prm.pout = (__nv_bfloat16*)d_out;
    fused_kernel<<<NCTA, 384, SMEM_BYTES>>>(prm);
}
```

```cpp
#include <cuda_runtime.h>
#include <cuda_bf16.h>
#include <cuda.h>
#include <stdint.h>
#include <limits.h>

namespace {

constexpr int SEQ = 2048, DM = 1024, DF = 3584, K2 = DM + DF, NQKV = 3 * DM;
constexpr int NGEMM = 128, NCTA = 132;
constexpr int G1_STAGES = 4, G1_STAGE_BYTES = 49152, G1_KSTEPS = 16, G1_TILES = 5;
constexpr int G2_STAGES = 6, G2_STAGE_BYTES = 32768, G2_KSTEPS = 72, G2_LATE = 40, G2_DSTEPS = 56;
constexpr int G2_HEAD = 17;
constexpr int A_BYTES = 16384;
constexpr int AUX_OFF = G1_STAGES * G1_STAGE_BYTES;
constexpr int BAR_OFF = AUX_OFF + 32768;
constexpr int PLAN_OFF = BAR_OFF + 384, STAT_OFF = BAR_OFF + 1536;
constexpr int SMEM_BYTES = BAR_OFF + 2816;
constexpr int G1_SKEW = 2, G2_SKEW = 5;
constexpr int CONSUMER_REGS = 224, AUX_REGS = 56;
constexpr int HALO_BYTES = 4096;
constexpr int LN_STEP = 3, FOLD_STEP = 14, SUM_STEP = 11, SUM2_STEP = 2;
constexpr uint32_t SUM_LOAD0 = 0x87658765u, SUM_LOAD1 = 0x65876587u;
constexpr int KEY_STEP = 2, QK_STEP = 8;
constexpr int VAL_STEP = 1, HALF_STEP = 3, PV_STEP = 9, OUT_STEPS = 4;
constexpr int UP_STEP = 2, XLOAD_STEP = 44;
constexpr int XREAD_STEP = 5, TAIL_STEP = 7;
constexpr int MEET = 4;
constexpr int PACE1 = 800, PACE2 = 1325, PACE3 = 1700;
constexpr int SHARE_MIN = 3, SHARE_MAX = 22, SHARE_LOW = 36, SHARE_SUM = 43;
constexpr int SHARE_NS = 79, SPARE_NS = 640, LATE_SCALE = 8;
constexpr float REST = 65000.f, DUE = 75100.f;

enum { F_LN = 0, F_LN2 = 1, F_FIRST = 2, F_SECOND = 3, F_SHARE = 4, F_EARLY = 5, F_LATE = 6, F_TAIL2 = 7, F_PACE = 8, F_HALO = 9 };
constexpr unsigned CNT_LN = 8, CNT_EARLY = 9, CNT_LATE = 8;

__device__ __align__(1024) __nv_bfloat16 g_xn[SEQ * DM];
__device__ __align__(1024) __nv_bfloat16 g_a2[SEQ * K2];
__device__ __align__(128) uint4 g_tail[2 * NGEMM * 512];
__device__ __align__(128) uint8_t g_halo[(2 * NGEMM + 1) * HALO_BYTES];
__device__ __align__(128) float2 g_stats[SEQ];
__device__ __align__(128) float g_colsum[18 * 1024];
__device__ __align__(128) unsigned g_flags[(F_HALO + 8) * 16 * 32];
__device__ __align__(128) unsigned g_epoch[NCTA * 16];

struct Params {
    const __nv_bfloat16 *px, *pwu;
    __nv_bfloat16 *pxn, *pa2, *pout;
    uint4* tail;
    uint8_t* halo;
    float2* stats;
    float* colsum;
    unsigned *flags, *epoch;
    unsigned long long* trace;
    uint32_t hi[2];
    CUtensorMap x, wg, wu, xn, wqkv, a2, wu_tail, wd_tail, wo, wd, out;
};

extern __shared__ __align__(1024) uint8_t smem_raw[];

#define TRACE(slot) do {} while (0)
#define TRACE_GT(slot) do {} while (0)
#define TRACE_S(slot, v, want) do {} while (0)
#define TRACE_GET(v) do {} while (0)
#define TRACE_PUT(slot, v) do {} while (0)
#define TRACE_SLOT(v, slot) do {} while (0)
#define TRACE_NEXT(v) do {} while (0)
#define TRACE_DUMP() do {} while (0)
#define TRACE_CLEAR() do {} while (0)
#define STAGE_TRACE 0
#define TRACE_END() do {} while (0)
#define TRACE_LITE(i, c) do {} while (0)
#define TRACE_RING(i) do {} while (0)
#define TRACE_STEP(t, k, i) do {} while (0)

__device__ __forceinline__ uint32_t smem_u32(const void* p) { return (uint32_t)__cvta_generic_to_shared(p); }
__device__ __forceinline__ void mbar_expect_tx(uint32_t bar, uint32_t bytes) {
    asm volatile("mbarrier.arrive.expect_tx.shared::cta.b64 _, [%0], %1;" :: "r"(bar), "r"(bytes) : "memory");
}
__device__ __forceinline__ void mbar_arrive(uint32_t bar) {
    asm volatile("mbarrier.arrive.shared::cta.b64 _, [%0];" :: "r"(bar) : "memory");
}
__device__ __forceinline__ bool mbar_try_wait(uint32_t bar, uint32_t parity) {
    uint32_t ok;
    asm volatile("{\n.reg .pred p;\nmbarrier.try_wait.parity.shared::cta.b64 p, [%1], %2;\nselp.u32 %0, 1, 0, p;\n}"
                 : "=r"(ok) : "r"(bar), "r"(parity) : "memory");
    return ok;
}
__device__ __forceinline__ void mbar_wait(uint32_t bar, uint32_t parity) {
#pragma unroll 1
    for (int spins = 0; !mbar_try_wait(bar, parity) && spins < (1 << 17); spins++) {}
}
__device__ __forceinline__ void mbar_wait(uint32_t bar, uint32_t parity, int& spins) {
    asm volatile("{\n.reg .pred p;\nagain:\nmbarrier.try_wait.parity.shared::cta.b64 p, [%1], %2;\n@p bra done;\n"
                 "add.s32 %0, %0, -1;\nsetp.gt.s32 p, %0, 0;\n@p bra again;\ndone:\n}" : "+r"(spins) : "r"(bar), "r"(parity) : "memory");
}
template <bool WARP = false> __device__ __forceinline__ unsigned flag_wait(const unsigned* p, unsigned target) {
    unsigned v;
#pragma unroll 1
    for (int spins = 0; spins < (1 << 19); spins++) {
        asm volatile("ld.acquire.gpu.global.u32 %0, [%1];" : "=r"(v) : "l"(p) : "memory");
        if (WARP ? __all_sync(0xffffffffu, (int)(v - target) >= 0) : (int)(v - target) >= 0) break;
        __nanosleep(64);
    }
    return v;
}
__device__ __forceinline__ void mbar_wait_warp(uint32_t bar, uint32_t parity) {
#pragma unroll 1
    for (int spins = 0; !__all_sync(0xffffffffu, mbar_try_wait(bar, parity)) && spins < (1 << 17); spins++) {}
}
__device__ __forceinline__ void flag_add(unsigned* p) {
    asm volatile("red.release.gpu.global.add.u32 [%0], 1;" :: "l"(p) : "memory");
}
__device__ __forceinline__ bool elect_one() {
    uint32_t ok;
    asm volatile("{\n.reg .pred p;\nelect.sync _|p, 0xffffffff;\nselp.u32 %0, 1, 0, p;\n}" : "=r"(ok));
    return ok;
}
__device__ __forceinline__ uint32_t pick(bool c, uint32_t a, uint32_t b) {
    uint32_t r;
    asm("{\n.reg .pred p;\nsetp.ne.b32 p, %3, 0;\nselp.b32 %0, %1, %2, p;\n}" : "=r"(r) : "r"(a), "r"(b), "r"((uint32_t)c));
    return r;
}
__device__ __forceinline__ void fence_proxy_async() { asm volatile("fence.proxy.async.global;" ::: "memory"); }
__device__ __forceinline__ uint4 lds128(uint32_t addr) {
    uint4 v;
    asm volatile("ld.shared.v4.u32 {%0,%1,%2,%3}, [%4];" : "=r"(v.x), "=r"(v.y), "=r"(v.z), "=r"(v.w) : "r"(addr) : "memory");
    return v;
}
__device__ __forceinline__ uint32_t lds32(uint32_t addr) {
    uint32_t v;
    asm volatile("ld.shared.u32 %0, [%1];" : "=r"(v) : "r"(addr) : "memory");
    return v;
}
__device__ __forceinline__ void sts32(uint32_t addr, uint32_t v) { asm volatile("st.shared.u32 [%0], %1;" :: "r"(addr), "r"(v) : "memory"); }
__device__ __forceinline__ uint32_t nanos() { uint32_t t; asm volatile("mov.u32 %0, %%globaltimer_lo;" : "=r"(t)); return t; }
__device__ __forceinline__ float2 lds64f(uint32_t addr) {
    float2 v;
    asm volatile("ld.shared.v2.f32 {%0,%1}, [%2];" : "=f"(v.x), "=f"(v.y) : "r"(addr) : "memory");
    return v;
}
__device__ __forceinline__ void sts128(uint32_t addr, uint4 v) {
    asm volatile("st.shared.v4.u32 [%0], {%1,%2,%3,%4};" :: "r"(addr), "r"(v.x), "r"(v.y), "r"(v.z), "r"(v.w) : "memory");
}
__device__ __forceinline__ void sts64f(uint32_t addr, float a, float b) {
    asm volatile("st.shared.v2.f32 [%0], {%1,%2};" :: "r"(addr), "f"(a), "f"(b) : "memory");
}

__device__ __forceinline__ uint64_t stream_policy() { return 0x12F0000000000000ull; }
__device__ __forceinline__ void tma_3d(uint32_t dst, const CUtensorMap* m, uint32_t bar, int c0, int c1, int c2, uint64_t pol) {
    asm volatile("cp.async.bulk.tensor.3d.shared::cluster.global.mbarrier::complete_tx::bytes.L2::cache_hint"
                 " [%0], [%1, {%3, %4, %5}], [%2], %6;"
                 :: "r"(dst), "l"(m), "r"(bar), "r"(c0), "r"(c1), "r"(c2), "l"(pol) : "memory");
}
__device__ __forceinline__ void load_stage1(uint32_t dst, uint32_t dst_b, uint32_t bar, const CUtensorMap* ma, const CUtensorMap* mb0,
                                            const CUtensorMap* mb1, int k, int row, int col0, int col1, int keep_a, uint64_t pol) {
    asm volatile("{\n.reg .pred e, p, q;\nelect.sync _|e, 0xffffffff;\nsetp.ne.and.b32 p|q, %8, 0, e;\n"
        "@p cp.async.bulk.tensor.3d.shared::cluster.global.mbarrier::complete_tx::bytes [%0], [%3, {%5, %6, %10}], [%2];\n"
        "@q cp.async.bulk.tensor.3d.shared::cluster.global.mbarrier::complete_tx::bytes.L2::cache_hint [%0], [%3, {%5, %6, %10}], [%2], %9;\n"
        "@e cp.async.bulk.tensor.2d.shared::cluster.global.mbarrier::complete_tx::bytes.multicast::cluster.L2::cache_hint"
        " [%1], [%4, {%7, %5}], [%2], %11, %9;\n"
        "@e cp.async.bulk.tensor.2d.shared::cluster.global.mbarrier::complete_tx::bytes.multicast::cluster.L2::cache_hint"
        " [%1 + 8192], [%13, {%14, %5}], [%2], %11, %9;\n"
        "@e mbarrier.arrive.expect_tx.shared::cta.b64 _, [%2], %12;\n}"
        :: "r"(dst), "r"(dst_b), "r"(bar), "l"(ma), "l"(mb0), "r"(k), "r"(row), "r"(col0), "r"(keep_a), "l"(pol), "r"(0),
           "h"((uint16_t)3), "n"(G1_STAGE_BYTES), "l"(mb1), "r"(col1) : "memory");
}
__device__ __forceinline__ void load_stage2(uint32_t dst, uint32_t dst_b, uint32_t bar, const CUtensorMap* ma, const CUtensorMap* mb,
                                            int ka, int row, int col, int kb2, int kb4, uint64_t pol) {
    asm volatile("{\n.reg .pred e;\nelect.sync _|e, 0xffffffff;\n"
        "@e cp.async.bulk.tensor.3d.shared::cluster.global.mbarrier::complete_tx::bytes.L2::cache_hint [%0], [%3, {%5, %6, %10}], [%2], %9;\n"
        "@e cp.async.bulk.tensor.5d.shared::cluster.global.mbarrier::complete_tx::bytes.multicast::cluster.L2::cache_hint"
        " [%1], [%4, {%7, %10, %13, %10, %8}], [%2], %11, %9;\n"
        "@e mbarrier.arrive.expect_tx.shared::cta.b64 _, [%2], %12;\n}"
        :: "r"(dst), "r"(dst_b), "r"(bar), "l"(ma), "l"(mb), "r"(ka), "r"(row), "r"(col), "r"(kb4), "l"(pol), "r"(0),
           "h"((uint16_t)3), "n"(G2_STAGE_BYTES), "r"(kb2) : "memory");
}
__device__ __forceinline__ void load_tail(uint32_t dst, uint32_t bar, const CUtensorMap* ma, const CUtensorMap* mb, int ka, int mblk,
                                          int kb) {
    asm volatile("{\n.reg .pred e;\nelect.sync _|e, 0xffffffff;\n"
        "@e cp.async.bulk.tensor.3d.shared::cluster.global.mbarrier::complete_tx::bytes [%0], [%2, {%3, %4, %5}], [%1];\n"
        "@e cp.async.bulk.tensor.5d.shared::cluster.global.mbarrier::complete_tx::bytes.multicast::cluster"
        " [%9], [%6, {%5, %5, %7, %5, %10}], [%1], %11;\n"
        "@e mbarrier.arrive.expect_tx.shared::cta.b64 _, [%1], %8;\n}"
        :: "r"(dst), "r"(bar), "l"(ma), "r"(ka), "r"(mblk * 64), "r"(0), "l"(mb), "r"(kb), "n"(G1_STAGE_BYTES),
           "r"(dst + A_BYTES + (mblk & 1) * 16384), "r"((mblk & 1) * 4), "h"((uint16_t)3) : "memory");
}
__device__ __forceinline__ uint4 ldg_stream(const void* p, uint64_t pol) {
    uint4 v;
    asm volatile("ld.global.nc.L1::no_allocate.L2::cache_hint.v4.u32 {%0,%1,%2,%3}, [%4], %5;"
                 : "=r"(v.x), "=r"(v.y), "=r"(v.z), "=r"(v.w) : "l"(p), "l"(pol));
    return v;
}
__device__ __forceinline__ void st_tagged(void* p, float a, float b, uint32_t tag) {
    asm volatile("st.relaxed.gpu.global.v2.b32 [%0], {%1,%2};"
                 :: "l"(p), "r"((__float_as_uint(a) & ~3u) | tag), "r"((__float_as_uint(b) & ~3u) | tag) : "memory");
}
__device__ __forceinline__ void st_relaxed(unsigned* p, uint32_t v) {
    asm volatile("st.relaxed.gpu.global.b32 [%0], %1;" :: "l"(p), "r"(v) : "memory");
}
__device__ __forceinline__ bool untagged(const uint4& v, uint32_t tag) {
    return ((v.x ^ tag) | (v.y ^ tag) | (v.z ^ tag) | (v.w ^ tag)) & 3;
}
__device__ __forceinline__ uint4 ld_relaxed(const void* p) {
    uint4 v;
    asm volatile("ld.relaxed.gpu.global.v4.b32 {%0,%1,%2,%3}, [%4];" : "=r"(v.x), "=r"(v.y), "=r"(v.z), "=r"(v.w) : "l"(p) : "memory");
    return v;
}
__device__ __forceinline__ void prefetch_map(const CUtensorMap* m) {
    asm volatile("prefetch.tensormap [%0];" :: "l"(m) : "memory");
}
template <int N> __device__ __forceinline__ void wg_wait() { asm volatile("wgmma.wait_group.sync.aligned %0;" :: "n"(N) : "memory"); }

__device__ __forceinline__ uint32_t desc_a(uint32_t addr) { return (addr & 0x3FFFF) >> 4 | 1 << 16; }
__device__ __forceinline__ uint32_t desc_b(uint32_t addr) { return (addr & 0x3FFFF) >> 4 | 512 << 16; }

#define R8(d, o) "+f"(d[o]), "+f"(d[o+1]), "+f"(d[o+2]), "+f"(d[o+3]), "+f"(d[o+4]), "+f"(d[o+5]), "+f"(d[o+6]), "+f"(d[o+7])
#define R32(d, o) R8(d, o), R8(d, o+8), R8(d, o+16), R8(d, o+24)
#define R64(d, o) R32(d, o), R32(d, o+32)
#define ACC00 "%0,%1,%2,%3,%4,%5,%6,%7,%8,%9,%10,%11,%12,%13,%14,%15,%16,%17,%18,%19,%20,%21,%22,%23,%24,%25,%26,%27,%28,%29,%30,%31,"\
    "%32,%33,%34,%35,%36,%37,%38,%39,%40,%41,%42,%43,%44,%45,%46,%47"
#define ACC0 ACC00 ",%48,%49,%50,%51,%52,%53,%54,%55,%56,%57,%58,%59,%60,%61,%62,%63"
#define ACC1 "%64,%65,%66,%67,%68,%69,%70,%71,%72,%73,%74,%75,%76,%77,%78,%79,%80,%81,%82,%83,%84,%85,%86,%87,%88,%89,%90,%91,%92,%93,%94,%95,"\
    "%96,%97,%98,%99,%100,%101,%102,%103,%104,%105,%106,%107,%108,%109,%110,%111"
#define ACC48 "{" ACC00 "}"
#define ACC64 "{" ACC0 "}"
#define ACC112 "{" ACC0 "," ACC1 "}"
#define ACC128 "{" ACC0 "," ACC1 ",%112,%113,%114,%115,%116,%117,%118,%119,%120,%121,%122,%123,%124,%125,%126,%127}"
#define MMA_K16(shape, acc, a, b, keep, hb) \
    "mov.b64 da, {" a ", 0x40000040};\nmov.b64 db, {" b ", " hb "};\n" \
    "wgmma.mma_async.sync.aligned." shape ".f32.bf16.bf16 " acc ", da, db, " keep ", 1, 1, 0, 1;\n"
#define MMA_NEXT(op, a, b, sa, sb) op " " a ", " a ", " sa ";\n" op " " b ", " b ", " sb ";\n"
#define MMA_STEP_B(shape, acc, a, b, na, nb, keep, hb, sb) \
    "{\n.reg .pred p, q;\n.reg .b64 da, db;\nsetp.ne.b32 p, " keep ", 0;\nsetp.eq.b32 q, 0, 0;\nwgmma.fence.sync.aligned;\n" \
    MMA_K16(shape, acc, a, b, "p", hb) MMA_NEXT("xor.b32", a, b, "2", "128") MMA_K16(shape, acc, a, b, "q", hb) MMA_NEXT("add.s32", a, b, "2", sb) \
    MMA_K16(shape, acc, a, b, "q", hb) MMA_NEXT("xor.b32", a, b, "2", "128") MMA_K16(shape, acc, a, b, "q", hb) MMA_NEXT("add.s32", a, b, na, nb) \
    "wgmma.commit_group.sync.aligned;\n}"
#define MMA64(shape, acc, a, b, keep) "wgmma.mma_async.sync.aligned." shape ".f32.bf16.bf16 " acc ", " a ", " b ", " keep ", 1, 1, 0, 1;\n"
#define NEXT64(op, a, b, sa, sb) "mov.b64 {lo, hi}, " a ";\n" op " lo, lo, " sa ";\nmov.b64 " a ", {lo, hi};\n" \
    "mov.b64 {lo, hi}, " b ";\n" op " lo, lo, " sb ";\nmov.b64 " b ", {lo, hi};\n"
#define ADD64(op, a, b, sa, sb) "cvt.s64.s32 w, " sa ";\nadd.s64 " a ", " a ", w;\ncvt.s64.s32 w, " sb ";\nadd.s64 " b ", " b ", w;\n"
#define MMA_STEP(shape, acc, a, b, na, nb, keep) MMA_STEP_N(shape, acc, a, b, na, nb, keep, NEXT64)
#define MMA_STEP_N(shape, acc, a, b, na, nb, keep, LAST) \
    "{\n.reg .pred p, q;\n.reg .b32 lo, hi;\n.reg .b64 w;\nsetp.ne.b32 p, " keep ", 0;\nsetp.eq.b32 q, 0, 0;\nwgmma.fence.sync.aligned;\n" \
    MMA64(shape, acc, a, b, "p") NEXT64("xor.b32", a, b, "2", "128") MMA64(shape, acc, a, b, "q") NEXT64("add.s32", a, b, "2", "128") \
    MMA64(shape, acc, a, b, "q") NEXT64("xor.b32", a, b, "2", "128") MMA64(shape, acc, a, b, "q") LAST("add.s32", a, b, na, nb) \
    "wgmma.commit_group.sync.aligned;\n}"
#define MMA_ARGS64 "+l"(da), "+l"(db) : "r"(next / 16 - 6), "r"(next / 16 - 384), "r"(keep) : "memory"
#define MMA_ARGS "+r"(da), "+r"(db) : "r"(next / 16 - 6), "r"(next / 16 - 384), "r"(keep) : "memory"

__device__ __forceinline__ void mma_step(float (&d)[128], uint64_t& da, uint64_t& db, int next, int keep) {
    asm volatile(MMA_STEP("m64n256k16", ACC128, "%128", "%129", "%130", "%131", "%132") : R64(d, 0), R64(d, 64), MMA_ARGS64);
}
__device__ __forceinline__ void mma_rank(float (&d)[128], uint32_t a0, uint32_t a1, uint32_t db) {
    asm volatile("{\n.reg .pred q;\n.reg .b64 db;\nsetp.eq.b32 q, 0, 0;\nmov.b64 db, {%131, 0x40000040};\nwgmma.fence.sync.aligned;\n"
                 "wgmma.mma_async.sync.aligned.m64n256k16.f32.bf16.bf16 " ACC128 ", {%128, %129, %130, %130}, db, q, 1, 1, 1;\n}"
                 : R64(d, 0), R64(d, 64) : "r"(a0), "r"(a1), "r"(0), "r"(db) : "memory");
}
__device__ __forceinline__ void mma_step224(float (&d)[128], uint64_t& da, uint64_t& db, int next, int keep) {
    asm volatile(MMA_STEP("m64n224k16", ACC112, "%112", "%113", "%114", "%115", "%116")
                 : R64(d, 0), R32(d, 64), R8(d, 96), R8(d, 104), MMA_ARGS64);
}
__device__ __forceinline__ void mma_step(float (&d)[64], uint64_t& da, uint64_t& db, int next, int keep) {
    asm volatile(MMA_STEP("m64n128k16", ACC64, "%64", "%65", "%66", "%67", "%68") : R64(d, 0), MMA_ARGS64);
}
__device__ __forceinline__ void mma_step_c(float (&d)[64], uint64_t& da, uint64_t& db, int next, int keep) {
    asm volatile(MMA_STEP_N("m64n128k16", ACC64, "%64", "%65", "%66", "%67", "%68", ADD64) : R64(d, 0), MMA_ARGS64);
}
__device__ __forceinline__ void mma_step96(float (&d)[64], uint64_t& da, uint64_t& db, int next, int keep) {
    asm volatile(MMA_STEP("m64n96k16", ACC48, "%48", "%49", "%50", "%51", "%52") : R32(d, 0), R8(d, 32), R8(d, 40), MMA_ARGS64);
}
__device__ __forceinline__ void mma_step_tail(float (&d)[128], uint32_t da, uint32_t b, int keep) {
    uint32_t db = (b & 0x3FFFF) >> 4 | 256 << 16;
    const int next = 0;
    asm volatile(MMA_STEP_B("m64n256k16", ACC128, "%128", "%129", "%130", "%131", "%132", "0x80000040", "-96")
                 : R64(d, 0), R64(d, 64), MMA_ARGS);
}

__device__ __forceinline__ uint32_t pack_bf16(float lo, float hi) {
    uint32_t r; asm("cvt.rn.bf16x2.f32 %0, %1, %2;" : "=r"(r) : "f"(hi), "f"(lo)); return r;
}
__device__ __forceinline__ float bf_lo(uint32_t v) { return __uint_as_float(v << 16); }
__device__ __forceinline__ float bf_hi(uint32_t v) { return __uint_as_float(v & 0xffff0000u); }
__device__ __forceinline__ float round_bf16(float v) { return bf_lo(pack_bf16(v, 0.f)); }
__device__ __forceinline__ uint32_t mul_bf16x2(uint32_t a, uint32_t b) {
    uint32_t r; asm("mul.rn.bf16x2 %0, %1, %2;" : "=r"(r) : "r"(a), "r"(b)); return r;
}
__device__ __forceinline__ uint32_t sub_bf16x2(uint32_t a, uint32_t b) {
    uint32_t r; asm("sub.rn.bf16x2 %0, %1, %2;" : "=r"(r) : "r"(a), "r"(b)); return r;
}
__device__ __forceinline__ uint32_t mul2_bf16x2(uint32_t a, uint32_t hi, uint32_t lo) {
    uint32_t r; asm("fma.rn.bf16x2 %0, %1, %2, %3;" : "=r"(r) : "r"(a), "r"(hi), "r"(mul_bf16x2(a, lo))); return r;
}
__device__ __forceinline__ float tanh_fast(float x) { float r; asm("tanh.approx.f32 %0, %1;" : "=f"(r) : "f"(x)); return r; }
__device__ __forceinline__ float gelu_twice(float g) {
    return fmaf(g, tanh_fast(fmaf(g * g, 0.044715f * 0.7978845608f, 0.7978845608f) * g), g);
}
__device__ __forceinline__ uint32_t geglu2(uint32_t g2, uint32_t u2) {
    return mul_bf16x2(pack_bf16(gelu_twice(bf_lo(g2)), gelu_twice(bf_hi(g2))), u2);
}
__device__ __forceinline__ uint32_t silu2(float lo, float hi) {
    const uint32_t h = mul_bf16x2(pack_bf16(lo, hi), 0x3e803e80u);
    return pack_bf16(fmaf(bf_lo(h), tanh_fast(bf_lo(h)), bf_lo(h)), fmaf(bf_hi(h), tanh_fast(bf_hi(h)), bf_hi(h)));
}
__device__ __forceinline__ float ex2_fast(float x) { float r; asm("ex2.approx.ftz.f32 %0, %1;" : "=f"(r) : "f"(x)); return r; }
__device__ __forceinline__ void unpack8(uint4 v, float (&f)[8]) {
    f[0] = bf_lo(v.x); f[1] = bf_hi(v.x); f[2] = bf_lo(v.y); f[3] = bf_hi(v.y);
    f[4] = bf_lo(v.z); f[5] = bf_hi(v.z); f[6] = bf_lo(v.w); f[7] = bf_hi(v.w);
}
template <int N> __device__ __forceinline__ void fence_regs(float (&d)[N]) {
#pragma unroll
    for (int i = 0; i < N; i++) asm volatile("" : "+f"(d[i]) :: "memory");
}

__device__ __forceinline__ float rcp_fast(float x) { float r; asm("rcp.approx.ftz.f32 %0, %1;" : "=f"(r) : "f"(x)); return r; }
__device__ __forceinline__ float sqrt_fast(float x) { float r; asm("sqrt.approx.ftz.f32 %0, %1;" : "=f"(r) : "f"(x)); return r; }
__device__ __forceinline__ uint32_t max_bf16x2(uint32_t a, uint32_t b) {
    uint32_t r; asm("max.bf16x2 %0, %1, %2;" : "=r"(r) : "r"(a), "r"(b)); return r;
}
__device__ __forceinline__ uint32_t transpose8(uint32_t a) {
    uint32_t r; asm volatile("movmatrix.sync.aligned.m8n8.trans.b16 %0, %1;" : "=r"(r) : "r"(a)); return r;
}
__device__ __forceinline__ void mma_sync(uint32_t* d, const uint32_t* a, uint32_t b0, uint32_t b1, const uint32_t* c) {
    asm volatile("mma.sync.aligned.m16n8k16.row.col.f32.bf16.bf16.f32 {%0,%1,%2,%3}, {%4,%5,%6,%7}, {%8,%9}, {%10,%11,%12,%13};"
        : "=r"(d[0]), "=r"(d[1]), "=r"(d[2]), "=r"(d[3])
        : "r"(a[0]), "r"(a[1]), "r"(a[2]), "r"(a[3]), "r"(b0), "r"(b1), "r"(c[0]), "r"(c[1]), "r"(c[2]), "r"(c[3]));
}
template <int N> struct Floats {
    float f[N];
    __device__ __forceinline__ Floats() {}
    __device__ __forceinline__ Floats(const uint32_t* p) {
#pragma unroll
        for (int i = 0; i < N; i++) asm("mov.b32 %0, %1;" : "=f"(f[i]) : "r"(p[i]));
    }
    __device__ __forceinline__ void put(uint32_t* p) const {
#pragma unroll
        for (int i = 0; i < N; i++) asm("mov.b32 %0, %1;" : "=r"(p[i]) : "f"(f[i]));
    }
    __device__ __forceinline__ float& operator[](int i) { return f[i]; }
};
__device__ __forceinline__ uint32_t fresh_tid() { uint32_t r; asm volatile("mov.u32 %0, %%tid.x;" : "=r"(r)); return r; }
template <typename T> __device__ __forceinline__ T uniform(T v) { return __shfl_sync(0xffffffffu, v, 0); }

__device__ __forceinline__ uint32_t forecast(uint32_t n0, uint32_t c0, float cycles, uint32_t tag) {
    const uint32_t n = nanos();
    return n + (int)((n - n0) * cycles * rcp_fast((uint32_t)clock() - c0)) & ~3u | tag;
}
__device__ __forceinline__ uint32_t plan_word(uint32_t base, int lane) { return uniform(lds32(base + PLAN_OFF + lane * 4)); }

__device__ __forceinline__ void fold_operands(const Params& prm, uint32_t base, int slot, int mblk, uint32_t tag, int w, int lane) {
    uint4 v[9];
#pragma unroll
    for (int m = 0; m < 9; m++) v[m] = make_uint4(0, 0, 0, 0);
    const float* parts = prm.colsum + (slot * 2 + (lane >> 4)) * 1024 + w * 64 + (lane & 15) * 4;
    const float* const rows = &prm.stats[mblk * 128 + w * 64 + lane * 2].x;
#pragma unroll 1
    for (int spins = 0; spins < (1 << 16); spins++) {
        bool missing = false;
        asm volatile("" : "+l"(parts));
#pragma unroll
        for (int m = 0; m < 9; m++) {
            if (untagged(v[m], tag)) {
                missing = true;
                v[m] = ld_relaxed(m < 8 ? parts + m * 128 : rows);
            }
        }
        if (!missing) break;
    }
    float4 c = make_float4(0.f, 0.f, 0.f, 0.f);
#pragma unroll
    for (int m = 0; m < 8; m++) {
        c.x += __uint_as_float(v[m].x ^ tag); c.y += __uint_as_float(v[m].y ^ tag);
        c.z += __uint_as_float(v[m].z ^ tag); c.w += __uint_as_float(v[m].w ^ tag);
    }
    sts128(base + STAT_OFF + w * 512 + lane * 16, make_uint4(v[8].x ^ tag, v[8].y ^ tag, v[8].z ^ tag, v[8].w ^ tag));
    const uint32_t ca = base + AUX_OFF + w * 8192 + (lane >> 4) * 16384 + (lane & 15) * 8;
#pragma unroll
    for (int r = 0; r < 3; r++) {
        const uint32_t lo = pack_bf16(c.x, c.y), hi = pack_bf16(c.z, c.w);
        sts64f((ca ^ r * 16) + r * 128, __uint_as_float(lo), __uint_as_float(hi));
        c.x -= bf_lo(lo); c.y -= bf_hi(lo); c.z -= bf_lo(hi); c.w -= bf_hi(hi);
    }
    asm volatile("fence.proxy.async.shared::cta;" ::: "memory");
    __syncwarp();
}
__device__ __forceinline__ float2 fold(float (&acc)[128], uint32_t base, int wg) {
    const uint32_t id = fresh_tid(), sp = base + STAT_OFF + (id & 96) * 8 + (id & 28) * 4 + wg * 8;
    const uint32_t sel = id & 2 ? 0x4444 : (id & 1 ? 0x4432 : 0x3232);
    const float2 sa = lds64f(sp), sb = lds64f(sp + 128);
    mma_rank(acc, __byte_perm(__float_as_uint(sa.x), 0, sel), __byte_perm(__float_as_uint(sb.x), 0, sel), desc_b(base + AUX_OFF));
    return make_float2(sa.y, sb.y);
}

__device__ __forceinline__ void tail_gemm(const Params& prm, uint32_t base, uint32_t t0, unsigned epoch, int grp, int warp, int lane) {
    const uint32_t full = base + BAR_OFF, empty = full + 32, sig = full + 192, dep = full + 256, folded = full + 320;
    const uint32_t tag = 1 + (epoch & 1);
    auto plan = [&](uint32_t p, uint32_t word) { return p < 4 ? p * 64 + grp / 2 * 32 + 15 : word >> p % 4 * 8 & 255; };
    auto rows = [&](uint32_t job) { return job / 32 * 2 + grp % 2; };
    if (warp == 8) {
        if (elect_one()) { prefetch_map(&prm.xn); prefetch_map(&prm.a2); prefetch_map(&prm.wd_tail); }
#pragma unroll 1
        for (int p = 0, i = G1_STAGES; p < 8; p++) {
            const bool first = p < 4;
            if (p == 4) mbar_wait_warp(dep + 16, 0);
            const uint32_t job = plan(p, plan_word(base, lane));
#pragma unroll 1
            for (int k = p ? 0 : G1_STAGES; k <= job % 32; k++, i++) {
                if (p == 3 && k % 2 == grp / 2)
                    asm volatile("{\n.reg .pred e;\nelect.sync _|e, 0xffffffff;\n"
                        "@e cp.async.bulk.prefetch.tensor.5d.L2.global [%0, {%2, %2, %1, %2, %3}];\n}"
                        :: "l"(&prm.wd_tail), "r"(k * 8), "r"(0), "r"(grp % 2 * 4) : "memory");
                if (i == 16 || i == 24 || k == 16) mbar_wait_warp(dep + (first ? i & 8 : 24), 0);
                TRACE_S(62, i, 16); TRACE_S(63, i, 4);
                mbar_wait_warp(empty + (i & 3) * 8, ~i >> 2 & 1);
                load_tail(base + (i & 3) * G1_STAGE_BYTES, full + (i & 3) * 8, first ? (p ? &prm.xn : &prm.x) : &prm.a2,
                          first ? &prm.wu_tail : &prm.wd_tail, (first ? 0 : DM) + k * 64, rows(job), first ? k * 2 : k * 8);
            }
        }
        return;
    }
    if (warp == 9) {
        const uint32_t n0 = nanos(), c0 = clock();
#pragma unroll 1
        for (int j = 0; j < 3; j++) {
            flag_wait<true>(prm.flags + (F_LN + j) * 512 + (j < 2 ? lane % 4 * 4 + grp : lane % 16) * 32, epoch * CNT_LN);
            fence_proxy_async();
            __syncwarp();
            if (lane == 0 && j < 2) mbar_arrive(dep + j * 8);
        }
        mbar_wait_warp(sig + 8, 0);
        if (lane == 0) st_relaxed(prm.flags + F_PACE * 512 + 64 + grp, forecast(n0, c0, DUE, tag));
        uint4 v, w;
#pragma unroll 1
        for (int spins = 0; spins < (1 << 19); spins++) {
            v = ld_relaxed(prm.flags + F_PACE * 512 + lane / 2 * 4);
            w = ld_relaxed(prm.flags + F_PACE * 512 + 64);
            if (!__any_sync(0xffffffffu, untagged(v, tag) || untagged(w, tag))) break;
            __nanosleep(256);
        }
        const uint32_t ref = uniform(v.x);
        const int due = min(max((int)((grp & 2 ? w.z : w.x) - ref), -100000), 100000) * 8;
        int late = max(max((int)(v.x - ref), (int)(v.y - ref)), max((int)(v.z - ref), (int)(v.w - ref)));
        late = min(max(max(late, __shfl_xor_sync(0xffffffffu, late, 2)), -100000), 100000) * LATE_SCALE + lane / 4;
        TRACE_PUT(16 + lane / 4, late + (1 << 20));
        int place = 0, n = SHARE_MIN;
#pragma unroll 1
        for (int g = 0; g < 32; g += 4) place += __shfl_sync(0xffffffffu, late, g) > late;
        const bool swap = (__reduce_add_sync(0xffffffffu, place + 1 & 2 ? late : -late) ^ w.x - w.z) >> 31;
        const bool mine = (place + 1 >> 1 & 1 ^ swap) == grp / 2;
#pragma unroll 1
        for (int j = 4 * SHARE_MIN; j < SHARE_SUM; j++) {
            const int most = __reduce_max_sync(0xffffffffu, mine && n < SHARE_MAX ? late : INT_MIN);
            if (j >= SHARE_LOW && due + (j - 38) * SPARE_NS * 8 > most) break;
            if (j == 38) TRACE_PUT(32, most - due + (1 << 20));
            if (most == late) { n++; late -= SHARE_NS * 8; }
        }
        auto first = [](uint32_t bits, int n) { return bits & (1u << min(max(n, 0), 24)) - 1; };
        const uint32_t job = lane / 4 * 32 + n - 1;
        if (mine) st_relaxed(prm.flags + F_SHARE * 512 + rows(job) * 32,
                             epoch << 24 | first(0x2aaaaa, 2 * n) | first(0x104104, 6 * n - 66) | first(0x10410, 6 * n - 90) |
                             first(0x41041, 6 * n - 108));
        if (mine) TRACE_PUT(24 + lane / 4, n);
        sts32(base + PLAN_OFF, __reduce_or_sync(0xffffffffu, mine ? job << place / 2 * 8 : 0));
        if (lane == 0) mbar_arrive(dep + 16);
        flag_wait<true>(prm.flags + F_SECOND * 512 + lane % 16 * 32, epoch * CNT_LN);
        fence_proxy_async();
        __syncwarp();
        if (lane == 0) mbar_arrive(dep + 24);
        return;
    }
    if (warp > 9) {
#pragma unroll 1
        for (int j = 0; j < 8; j++) sts128(base + AUX_OFF + (warp - 10) * 8192 + (j & 4) * 4096 + (j & 3) * 512 + lane * 16, make_uint4(0, 0, 0, 0));
        while ((uint32_t)clock() - t0 < 9000) __nanosleep(256);
        fold_operands(prm, base, 8, grp, tag, warp - 10, lane);
        if (lane) return;
        mbar_arrive(folded);
        if (warp == 11) return;
        TRACE(60);
#pragma unroll 1
        for (int p = 0; p < 8; p++) {
            mbar_wait(sig + p * 8, 0);
            flag_add(prm.flags + (p < 4 ? F_EARLY : F_TAIL2) * 512 + rows(plan(p, lds32(base + PLAN_OFF))) * 32);
            TRACE_S(50, p, 3); TRACE_S(51, p, 7);
        }
        prm.epoch[blockIdx.x * 16] = epoch;
        TRACE_DUMP();
        return;
    }
    asm volatile("setmaxnreg.inc.sync.aligned.u32 %0;" :: "n"(CONSUMER_REGS) : "memory");
    const uint32_t da = desc_a(base + (warp >> 2) * 8192);
    uint4* out = prm.tail;
    float acc[128];
    uint32_t pk[64];
    float2 inv = make_float2(0.f, 0.f);
    int i = 0, last;
    uint32_t peer;
    asm volatile("mapa.shared::cluster.u32 %0, %1, %2;" : "=r"(peer) : "r"(empty), "r"(lane & 1));
    auto release = [&]() {
        if ((threadIdx.x & 126) == 0 && i <= last)
            asm volatile("mbarrier.arrive.shared::cluster.b64 _, [%0];" :: "r"(peer + (i - 1 & 3) * 8) : "memory");
    };
    auto store = [&](int j) {
        asm volatile("st.global.v4.u32 [%0], {%1,%2,%3,%4};" :: "l"(out + j / 2 * 8192 + j % 2 * 256),
                     "r"(pk[4 * j]), "r"(pk[4 * j + 1]), "r"(pk[4 * j + 2]), "r"(pk[4 * j + 3]) : "memory");
    };
    auto step = [&](int k, int left) {
        mbar_wait(full + (i & 3) * 8, i >> 2 & 1);
        TRACE_S(45, warp * 128 + i, 0);
        if (warp >= 4 && left == G1_SKEW) asm volatile("bar.sync 1, 256;" ::: "memory");
        mma_step_tail(acc, da + (i & 3) * (G1_STAGE_BYTES / 16), base + A_BYTES + (i & 3) * G1_STAGE_BYTES, k);
        if (warp < 4 && left == 1) asm volatile("bar.arrive 1, 256;" ::: "memory");
    };
    auto drip = [&](int p, int& n) {
        if (n > 0) { store(0); store(1); }
#pragma unroll
        for (int j = 8; j < 64; j++) asm volatile("mov.b32 %0, %1;" : "=r"(pk[j - 8]) : "r"(pk[j]));
        out += 8192;
        __syncwarp();
        if (--n == 0 && lane == 0) mbar_arrive(sig + p * 8 - 8);
    };
#pragma unroll
    for (int j = 0; j < 128; j++) asm volatile("mov.b32 %0, 0;" : "=f"(acc[j]));
#pragma unroll
    for (int j = 0; j < 64; j++) asm volatile("mov.b32 %0, 0;" : "=r"(pk[j]));
#pragma unroll 1
    for (int p = 0; p < 8; p++) {
        step(0, 0);
        i++;
        const uint32_t word = plan_word(base, lane), job = plan(p, word);
        last = __dp4a(word & 0x1f1f1f1fu, 0x01010101u, 4u * G1_KSTEPS);
#pragma unroll 1
        for (int left = job % 32, n = p ? 8 : 0; left > 0; left--) {
            if (i == G1_KSTEPS - 1) { mbar_wait(folded, 0); inv = fold(acc, base, warp >> 2); }
#pragma unroll 1
            do drip(p, n); while (n & 7 >> 31 - __clz(job % 32));
            step(1, left);
            wg_wait<1>();
            release();
            i++;
        }
        wg_wait<0>();
        fence_regs(acc);
        release();
        if (p == 0) {
#pragma unroll
            for (int j = 0; j < 128; j++) acc[j] *= j & 2 ? inv.y : inv.x;
            fence_regs(acc);
        }
        if (warp == 4) TRACE_PUT(46 + p + p / 4 * 3, (uint32_t)clock());
#pragma unroll
        for (int j = 0; j < 64; j++) pk[j] = pack_bf16(acc[2 * j], acc[2 * j + 1]);
        out = prm.tail + p / 4 * NGEMM * 512 + rows(job) * 512 + threadIdx.x;
    }
#pragma unroll
    for (int j = 0; j < 16; j++) store(j);
    __syncwarp();
    TRACE_S(58, warp, 4);
    if (lane == 0) mbar_arrive(sig + 56);
}

__device__ __forceinline__ int gate_col(int t, int nslot) { return t == 2 ? 960 + nslot * 64 : max(t * 1024 - 1536, 0) + nslot * 128; }

struct Role {
    int rank, role, mblk, nslot;
    __device__ __forceinline__ Role() {
        uint32_t id;
        asm volatile("mov.u32 %0, %%ctaid.x;" : "=r"(id));
        const uint32_t cl = id / 2;
        rank = id & 1;
        role = pick(cl < 4, 32 + cl * 8, cl - 8 + max(4u, (cl - 1) * 37 >> 8)) * 2 + rank;
        mblk = role & 15; nslot = role >> 4;
    }
};

__global__ void __cluster_dims__(2, 1, 1) __launch_bounds__(384, 1)
fused_kernel(const __grid_constant__ Params prm) {
    TRACE_GET(c0);
    const uint32_t base = smem_u32(smem_raw) & ~1023u;
    const uint32_t bars = base + BAR_OFF;
    auto full1 = [&](int s) { return bars + s * 8; };
    auto empty1 = [&](int s) { return bars + 32 + s * 8; };
    auto full2 = [&](int s) { return bars + 64 + s * 8; };
    auto empty2 = [&](int s) { return bars + 128 + s * 8; };
    const uint32_t sig_bar = bars + 192, dep_bar = bars + 256, cs_bar = bars + 304, fold_bar = bars + 320, x_bar = bars + 352;
    const uint32_t halo_bar = dep_bar + 32;
    auto stage2 = [&](int q) { return base + q * G2_STAGE_BYTES; };
    const uint32_t aux = base + AUX_OFF;

    asm volatile("{\n.reg .pred p;\nsetp.eq.u32 p, %1, 0;\n@p mbarrier.init.shared::cta.b64 [%0], 1;\n"
        "fence.mbarrier_init.release.cluster;\nbarrier.cluster.arrive.relaxed.aligned;\n}" :: "r"(bars), "r"(threadIdx.x) : "memory");
    const int warp = __shfl_sync(0xffffffffu, threadIdx.x >> 5, 0);
    auto cluster_wait = []() { asm volatile("barrier.cluster.wait.acquire.aligned;" ::: "memory"); };
    if ((warp | (blockIdx.x & NGEMM)) == 8) {
        const Role r;
        asm volatile("{\n.reg .pred e;\nelect.sync _|e, 0xffffffff;\n"
            "@e prefetch.tensormap [%0];\n@e prefetch.tensormap [%1];\n}" :: "l"(&prm.x), "l"(&prm.wg + r.rank) : "memory");
        cluster_wait();
        load_stage1(base, base + A_BYTES + r.rank * 16384, full1(0), &prm.x, &prm.wg + r.rank, &prm.wg + r.rank, 0, r.mblk * 64,
                    r.nslot * 128, r.nslot * 128 + 64, 0, stream_policy());
    } else {
        cluster_wait();
    }
    const uint32_t t0 = clock();
    {
        uint32_t cta;
        asm volatile("mov.u32 %0, %%ctaid.x;" : "=r"(cta));
        if ((warp | (~cta & NGEMM)) == 8) load_tail(base, full1(0), &prm.x, &prm.wu_tail, 0, cta - NGEMM, 0);
    }
    asm volatile("{\n.reg .pred e, q;\nelect.sync _|e, 0xffffffff;\nsetp.ne.and.u32 q, %2, 0, e;\n"
        "@q mbarrier.init.shared::cta.b64 [%0], %1;\n@e mbarrier.init.shared::cta.b64 [%0 + 8], %1;\n"
        "@e mbarrier.init.shared::cta.b64 [%0 + 16], %1;\n@e mbarrier.init.shared::cta.b64 [%0 + 24], %1;\n"
        "fence.mbarrier_init.release.cluster;\nbarrier.cluster.arrive.relaxed.aligned;\n}"
        :: "r"(bars + warp * 32), "r"(1 << (0x10fa08 >> warp * 2 & 3)), "r"(warp) : "memory");
    const int lane = threadIdx.x & 31;
    const Role me;
    const int rank = me.rank, role = me.role, mblk = me.mblk, nslot = me.nslot;
    const CUtensorMap* const w0 = &prm.wg + rank;

    unsigned* const flags = prm.flags + mblk * 32;
    if (warp >= 8) {
        asm volatile("setmaxnreg.dec.sync.aligned.u32 %0;" :: "n"(AUX_REGS));
        if (warp == 9) { TRACE_CLEAR(); TRACE_GT(0); TRACE_PUT(1, c0); }
        if ((warp | (~blockIdx.x & NGEMM)) == 8) {
#pragma unroll 1
            for (int i = 1; i < G1_STAGES; i++) {
                if (i == 1) cluster_wait();
                TRACE_S(57, i, 1);
                load_tail(base + i * G1_STAGE_BYTES, full1(i), &prm.x, &prm.wu_tail, i * 64, blockIdx.x - NGEMM, i * 2);
            }
        } else {
            cluster_wait();
        }
    }

    if (blockIdx.x >= NGEMM) {
        if (warp < 8) cluster_wait();
        const uint32_t seen = __ldcg(prm.epoch + blockIdx.x * 16);
        tail_gemm(prm, base, t0, seen + 1, blockIdx.x - NGEMM, warp, lane);
    } else if (warp == 9) {
        const unsigned epoch = __ldcg(prm.epoch + blockIdx.x * 16 + 2) + 1;
        const uint32_t n0 = nanos(), c1 = clock();
        {
            const __nv_bfloat16* const w = prm.pwu + ((mblk >> 1) * 128 + lane / 2) * DF + gate_col(4, nslot) + 96 + rank * 16 + lane % 2 * 8;
            uint4 v[8];
            float cs[8], f[8];
            mbar_wait(empty1(SUM2_STEP), 0);
#pragma unroll
            for (int j = 0; j < 8; j++) v[j] = __ldg(reinterpret_cast<const uint4*>(w + j * 16 * DF));
            unpack8(v[0], cs);
#pragma unroll
            for (int j = 1; j < 8; j++) {
                unpack8(v[j], f);
#pragma unroll
                for (int d = 0; d < 8; d++) cs[d] += f[d];
            }
#pragma unroll
            for (int d = 0; d < 4; d++)
                cs[d] = (lane & 16 ? cs[d + 4] : cs[d]) + __shfl_xor_sync(0xffffffffu, lane & 16 ? cs[d] : cs[d + 4], 16);
#pragma unroll
            for (int d = 0; d < 2; d++) {
                cs[d] = (lane & 8 ? cs[d + 2] : cs[d]) + __shfl_xor_sync(0xffffffffu, lane & 8 ? cs[d] : cs[d + 2], 8);
                cs[d] += __shfl_xor_sync(0xffffffffu, cs[d], 4);
                cs[d] += __shfl_xor_sync(0xffffffffu, cs[d], 2);
            }
            if (!(lane & 6))
                st_tagged(prm.colsum + (16 + nslot / 4) * 1024 + (mblk >> 1) * 128 + nslot % 4 * 32 + rank * 16 + lane % 2 * 8 + (lane >> 3) * 2,
                          cs[0], cs[1], 1 + (epoch & 1));
            TRACE(61);
        }
        if (lane == 0) {
            mbar_wait(sig_bar, 0);
            TRACE(11);
            flag_add(flags + F_LN * 512);
            TRACE(42);
            flag_wait(flags + F_LN * 512, epoch * CNT_LN);
            fence_proxy_async();
            mbar_arrive(dep_bar);
            mbar_wait(sig_bar + 56, 0);
            flag_add(flags + F_LN2 * 512);
            flag_wait(flags + F_LN2 * 512, epoch * CNT_LN);
            fence_proxy_async();
            mbar_arrive(dep_bar + 40);
            TRACE(59);
            prm.epoch[blockIdx.x * 16 + 2] = epoch;
#pragma unroll 1
            for (int p = 3; p < 7; p++) {
                mbar_wait(sig_bar + (p == 3 ? 16 : p * 8), 0);
                TRACE_S(37, p, 4);
                flag_add(flags + (p - (p < F_EARLY)) * 512);
                TRACE_S(43, p, 4);
                if (p == 3 && rank == 0) {
                    mbar_wait(sig_bar + 24, 0);
                    st_relaxed(prm.flags + F_PACE * 512 + mblk * 4 + nslot, forecast(n0, c1, REST, 1 + (epoch & 1)));
                }
            }
        }
    } else if (warp < 8) {
        asm volatile("setmaxnreg.inc.sync.aligned.u32 %0;" :: "n"(CONSUMER_REGS));
        const int wg = __shfl_sync(0xffffffffu, threadIdx.x >> 7, 0);
        const int cw = threadIdx.x >> 5;
        const int tid = threadIdx.x & 127;
        int spins = 1 << 18;
        float acc[128];
        uint32_t pk[64];
#pragma unroll
        for (int i = 0; i < 64; i++) asm volatile("mov.b32 %0, 0;" : "=r"(pk[i]));
#pragma unroll
        for (int i = 0; i < 128; i++) asm volatile("mov.b32 %0, 0;" : "=f"(acc[i]));
        cluster_wait();

        auto row0 = [&](uint32_t id) { return mblk * 128 + (id & 96) + wg; };
        __nv_bfloat16* optr = prm.pxn + (mblk * 128 + nslot * 16 + cw * 2) * DM + lane * 8;
        uint64_t da = desc_a(base + wg * 8192) | (uint64_t)prm.hi[0] << 32, db = desc_b(base + A_BYTES) | (uint64_t)prm.hi[1] << 32;
        auto next1 = [](int s) { return ((s + 1) % G1_STAGES - s) * G1_STAGE_BYTES; };
        auto next2 = [](int q) { return ((q + 1) % G2_STAGES - q) * G2_STAGE_BYTES; };
        uint32_t peer_bars;
        asm volatile("mapa.shared::cluster.u32 %0, %1, %2;" : "=r"(peer_bars) : "r"(bars), "r"(tid & 1));
        if (tid >= 2) peer_bars = 0;
        auto release = [&](uint32_t bar) {
            if (peer_bars) asm volatile("mbarrier.arrive.shared::cluster.b64 _, [%0];" :: "r"(peer_bars + (bar - bars)) : "memory");
        };
        auto up = [](int i) { return 32 + (i & 24) + (i & 3) * 2 + (i >> 2 & 1); };
        auto store_pk = [&](__nv_bfloat16* p, int j) {
            asm volatile("st.global.v4.u32 [%0], {%1,%2,%3,%4};"
                         :: "l"(p), "r"(pk[4 * j]), "r"(pk[4 * j + 1]), "r"(pk[4 * j + 2]), "r"(pk[4 * j + 3]) : "memory");
        };
        auto chunk_geglu = [&](int j) {
#pragma unroll
            for (int i = 4 * j; i < 4 * j + 4; i++) pk[i] = geglu2(pk[i], pk[up(i)]);
            store_pk(optr + (j & 1) * 16 * K2 + (j >> 1) * 32, j);
        };
        auto signal_stores = [&](int p) { __syncwarp(); if (lane == 0) mbar_arrive(sig_bar + p * 8); };

        auto chunk_ln = [&](int k) {
            Floats<6> mo(pk + 32);
            if (k == 0) {
                const uint4* xp = reinterpret_cast<const uint4*>(prm.px + (optr - prm.pxn));
                pk[38] = __ldcg(prm.epoch + blockIdx.x * 16 + 2);
#pragma unroll
                for (int i = 0; i < 8; i++) {
                    const uint4 v = ldg_stream(xp + i * 32, stream_policy());
                    pk[4 * i] = v.x; pk[4 * i + 1] = v.y; pk[4 * i + 2] = v.z; pk[4 * i + 3] = v.w;
                }
            } else if (k >= LN_STEP && k < LN_STEP + 3) {
                if (k == LN_STEP) {
                    mo[0] = bf_lo(uniform(pk[0])); mo[1] = bf_lo(uniform(pk[16]));
                    mo[2] = mo[3] = mo[4] = mo[5] = 0.f;
                }
#pragma unroll
                for (int i = (k - LN_STEP) * 11; i < (k - LN_STEP) * 11 + 11 && i < 32; i++) {
                    const int r = i & 1;
                    const uint32_t w = pk[r * 16 + i / 2];
                    const float lo = bf_lo(w) - mo[r], hi = bf_hi(w) - mo[r];
                    mo[2 + r] += lo + hi;
                    mo[4 + r] = fmaf(hi, hi, fmaf(lo, lo, mo[4 + r]));
                }
                mo.put(pk + 32);
            } else if (k == LN_STEP + 3) {
                const bool second = lane & 16;
                float m1 = (second ? mo[3] : mo[2]) + __shfl_xor_sync(0xffffffffu, second ? mo[2] : mo[3], 16);
                float m2 = (second ? mo[5] : mo[4]) + __shfl_xor_sync(0xffffffffu, second ? mo[4] : mo[5], 16);
#pragma unroll
                for (int o = 8; o > 0; o >>= 1) {
                    m1 += __shfl_xor_sync(0xffffffffu, m1, o);
                    m2 += __shfl_xor_sync(0xffffffffu, m2, o);
                }
                m1 *= 1.f / DM;
                const float var = fmaxf(fmaf(-m1, m1, m2 * (1.f / DM)), 0.f);
                const float mean = round_bf16((second ? mo[1] : mo[0]) + m1);
                const float inv = rcp_fast(round_bf16(sqrt_fast(round_bf16(round_bf16(var) + 1e-5f))));
                if ((lane & 15) == 0) st_tagged(prm.stats + (uint32_t)(optr - prm.pxn) / DM + second, -mean, inv, 2 - (pk[38] & 1));
                const uint32_t split = pack_bf16(inv - round_bf16(inv), inv);
#pragma unroll
                for (int r = 0; r < 2; r++) {
                    const uint32_t f = __shfl_sync(0xffffffffu, split, r * 16);
                    pk[32 + 3 * r] = __byte_perm(__shfl_sync(0xffffffffu, __float_as_uint(mean), r * 16), 0, 0x3232);
                    pk[33 + 3 * r] = __byte_perm(f, 0, 0x3232);
                    pk[34 + 3 * r] = __byte_perm(f, 0, 0x1010);
                }
            } else if (k >= LN_STEP + 4 && k < LN_STEP + 8) {
#pragma unroll
                for (int i = k - LN_STEP - 4; i < 8; i += 4) {
                    const uint32_t* n = pk + 32 + i / 4 * 3;
#pragma unroll
                    for (int j = 4 * i; j < 4 * i + 4; j++) pk[j] = mul2_bf16x2(sub_bf16x2(pk[j], n[0]), n[1], n[2]);
                    store_pk(optr + i * 256, i);
                }
                if (k == LN_STEP + 5 || k == LN_STEP + 7) signal_stores(k == LN_STEP + 5 ? 0 : 7);
            } else if (k == FOLD_STEP) {
                mbar_wait(fold_bar, 0, spins);
                const float2 inv = fold(acc, base, wg);
                mo[0] = inv.x; mo[1] = inv.y;
                mo.put(pk + 32);
            }
        };

        auto halo = [&]() { const uint32_t id = fresh_tid(); return aux + (id & 96) * 128 + (id & 128) * 16 + (id & 31) * 4; };
        auto put = [&](uint32_t a, uint32_t v0, uint32_t v1) {
            asm volatile("st.shared.u32 [%0], %1;\nst.shared.u32 [%0 + 128], %2;" :: "r"(a + HALO_BYTES), "r"(v0), "r"(v1) : "memory");
        };
        auto get = [&](uint32_t a, uint32_t& v0, uint32_t& v1) {
            asm volatile("ld.shared.u32 %0, [%2];\nld.shared.u32 %1, [%2 + 128];" : "=r"(v0), "=r"(v1) : "r"(a) : "memory");
        };
        auto publish = [&](int p) { asm volatile("fence.proxy.async.shared::cta;" ::: "memory"); signal_stores(p); };
        const uint32_t zero[4] = {0, 0, 0, 0};
        auto meet = [&](int n, int k, uint32_t id) {
            if (n == 15 - MEET)
                asm volatile("{\n.reg .b32 c;\nmov.u32 c, %%clock;\nbar.arrive %1, 256;\nlop3.b32 %0, %0, c, 1, 0x70;\n}"
                             : "+r"(peer_bars) : "r"(2 + id / 128) : "memory");
            if (n == 15) {
                asm volatile("{\n.reg .b32 c;\nmov.u32 c, %%clock;\nbar.sync %1, 256;\nlop3.b32 %0, %0, c, 1, 0x70;\n}"
                             : "+r"(peer_bars) : "r"(3 - id / 128) : "memory");
                mma_step(acc, da, db, next1(k & 3), k);
                asm volatile("// batch step");
            }
        };
        auto mix_qk = [&]() {
            uint32_t c[2][4];
            const uint32_t a = halo(), id = fresh_tid();
            mbar_wait(halo_bar, 0, spins);
#pragma unroll
            for (int n = 0; n < 16; n++) {
                const int b = 1 - n / 8, h = (n & 4) / 2 + n % 2, j = n / 2 % 2;
                uint32_t* const kq = pk + 32 + 8 * h + 4 * j;
                uint32_t* const q = pk + 8 * h + 4 * b;
                mma_sync(j ? q : c[n % 2], kq, q[2 * j], q[2 * j + 1], j ? c[n % 2] : zero);
                if (b) get(a + (h * 2 + j) * 256, kq[1], kq[3]);
                meet(n, QK_STEP, id);
            }
        };
        auto chunk_qk = [&](int k) {
            constexpr float LOG2E = 1.4426950408889634f;
            uint32_t* const l = pk + 32;
            Floats<16> e(pk);
            if (k == KEY_STEP) {
                const uint32_t a = halo();
#pragma unroll
                for (int i = 0; i < 8; i++) put(a + i * 256, pk[33 + 4 * i], pk[35 + 4 * i]);
                publish(1);
            } else if (k == QK_STEP + 1) {
                const uint32_t id = fresh_tid();
                const bool u0 = id % 32 / 4 > id % 4 * 2, u1 = id % 32 / 4 > id % 4 * 2 + 1;
                const uint32_t gone = row0(id) < 2 ? (u0 ? 0xffffu : 0u) | (u1 ? 0xffff0000u : 0u) : 0u;
#pragma unroll
                for (int n = 0; n < 8; n++) {
                    const int b = n % 2;
                    const uint32_t* const c = pk + 4 * n;
                    uint32_t v = pack_bf16(__uint_as_float(pick(u0, c[2 - 2 * b], c[2 * b])), __uint_as_float(pick(u1, c[3 - 2 * b], c[1 + 2 * b])));
                    v = mul2_bf16x2(v, 0x3e353e35u, 0x379e379eu);
                    if (!b) v = v & ~gone | 0xce6ece6eu & gone;
                    l[n] = transpose8(v);
                }
            } else if (k == QK_STEP + 2) {
#pragma unroll
                for (int h = 0; h < 4; h++) {
                    uint32_t m = max_bf16x2(__byte_perm(l[2 * h], l[2 * h + 1], 0x5410), __byte_perm(l[2 * h], l[2 * h + 1], 0x7632));
                    m = max_bf16x2(m, __shfl_xor_sync(0xffffffffu, m, 1));
                    m = max_bf16x2(m, __shfl_xor_sync(0xffffffffu, m, 2));
#pragma unroll
                    for (int n = 2 * h; n < 2 * h + 2; n++) {
                        const float f = -LOG2E * (n % 2 ? bf_hi(m) : bf_lo(m));
                        e[2 * n] = ex2_fast(fmaf(bf_lo(l[n]), LOG2E, f));
                        e[2 * n + 1] = ex2_fast(fmaf(bf_hi(l[n]), LOG2E, f));
                    }
                }
                e.put(pk);
            } else if (k == QK_STEP + 3) {
                uint32_t p[8];
#pragma unroll
                for (int n = 0; n < 8; n++) {
                    float sum = e[2 * n] + e[2 * n + 1];
                    sum += __shfl_xor_sync(0xffffffffu, sum, 1);
                    sum += __shfl_xor_sync(0xffffffffu, sum, 2);
                    const float r = rcp_fast(sum);
                    p[n] = pack_bf16(e[2 * n] * r, e[2 * n + 1] * r);
                }
                const uint32_t a = aux + 5 * HALO_BYTES + fresh_tid() * 16;
                sts128(a, make_uint4(p[0], p[1], p[2], p[3]));
                sts128(a + 4096, make_uint4(p[4], p[5], p[6], p[7]));
            }
        };
        auto values = [&](int h) { return pk + (h & 2) * 16 + (h & 1) * 8; };
        auto mix_pv = [&]() {
            uint32_t lo[8], hi[8];
            const uint32_t id = fresh_tid();
            const uint32_t keep = (id % 4 * 2 > id % 32 / 4 ? 0xffffu : 0u) | (id % 4 * 2 + 1 > id % 32 / 4 ? 0xffff0000u : 0u);
            const uint4 p0 = lds128(aux + 5 * HALO_BYTES + id * 16), p1 = lds128(aux + 6 * HALO_BYTES + id * 16);
            const uint32_t p[8] = {p0.x, p0.y, p0.z, p0.w, p1.x, p1.y, p1.z, p1.w};
#pragma unroll
            for (int n = 0; n < 8; n++)
                asm volatile("and.b32 %0, %2, %3;\nand.b32 %1, %2, %4;" : "=r"(lo[n]), "=r"(hi[n])
                             : "r"(p[n]), "r"(n % 2 ? keep : ~keep), "r"(n % 2 ? ~keep : keep));
            mbar_wait(halo_bar, 1, spins);
#pragma unroll
            for (int n = 0; n < 16; n++) {
                const int i = (n & 8) / 2 + (n & 2) + (n & 4) / 4;
                mma_sync(pk + 4 * (n ^ 4), pk + 4 * (n ^ 4), lo[i], hi[i], zero);
                meet(n, PV_STEP, id);
            }
        };
        auto chunk_pv = [&](int k) {
            if (k == VAL_STEP || k == VAL_STEP + 1) {
                const uint32_t a = halo();
#pragma unroll
                for (int h = (k - VAL_STEP) * 2; h < (k - VAL_STEP + 1) * 2; h++) {
                    uint32_t* const w = values(h);
                    uint32_t v[8];
#pragma unroll
                    for (int i = 0; i < 8; i++) v[i] = transpose8(w[h < 2 ? (i & 1) + (i & 2) * 2 + (i & 4) / 2 : (i & 1) * 2 + (i & 2) / 2 + (i & 4)]);
#pragma unroll
                    for (int i = 0; i < 8; i++) w[i] = v[i];
                    put(a + h * 512, w[2], w[3]);
                    put(a + h * 512 + 256, w[6], w[7]);
                }
                if (k > VAL_STEP) publish(3);
            } else if (k == PV_STEP - 1) {
                const uint32_t a = halo(), id = fresh_tid();
                optr = prm.pa2 + (size_t)(row0(id) + id % 4 * 4) * K2 + nslot * 128 + (id & 28) * 2;
                mbar_wait(halo_bar, 1, spins);
#pragma unroll
                for (int n = 0; n < 8; n++) {
                    uint32_t* const w = values(n / 2) + n % 2 * 4;
                    w[16] = w[0]; w[17] = w[1];
                    get(a + n * 256, w[18], w[19]);
                }
            } else if (k > PV_STEP && k <= PV_STEP + OUT_STEPS) {
#pragma unroll
                for (int j = 0; j < 8; j++) {
                    if (j * OUT_STEPS / 8 != k - PV_STEP - 1) continue;
                    Floats<15> c(pk + j / 2 * 16 + j % 2);
                    asm volatile("st.global.v4.u32 [%0], {%1,%2,%3,%4};"
                                 :: "l"(optr + ((~j & 2) * 8 + j % 2 * 2) * K2 + j / 4 * 64), "r"(pack_bf16(c[0], c[2])),
                                    "r"(pack_bf16(c[4], c[6])), "r"(pack_bf16(c[8], c[10])), "r"(pack_bf16(c[12], c[14])) : "memory");
                }
                if (k == PV_STEP + OUT_STEPS) signal_stores(4);
            }
        };

        TRACE_SLOT(tile_slot, 16 + wg * 8);
#pragma unroll 1
        for (int t = 0; t < G1_TILES; t++) {
#pragma unroll
            for (int k = 0; k < G1_KSTEPS; k++) {
                const int s = k & 3;
                if (k == 0) asm volatile("" : "+r"(t));
                TRACE_STEP(t, k, 0);
                mbar_wait(full1(s), (k >> 2) & 1, spins);
                if (k == 0) TRACE_S(12, t, 0);
                TRACE_STEP(t, k, 1);
                if (wg == 1 && k == G1_KSTEPS - G1_SKEW) asm volatile("bar.sync 1, 256;" ::: "memory");
                if (k == PV_STEP && t == 3) mix_pv();
                else if (k == QK_STEP && t == 2) mix_qk();
                else if (t == G1_TILES - 1) mma_step224(acc, da, db, next1(s), k);
                else mma_step(acc, da, db, next1(s), k);
                if (wg == 0 && k == G1_KSTEPS - 1) asm volatile("bar.arrive 1, 256;" ::: "memory");
                wg_wait<1>();
                if (k > 0) release(empty1((k - 1) & 3));
                TRACE_STEP(t, k, 2);
                if (t == 0) chunk_ln(k);
                if (k >= 1 && k <= 8 && ((k < HALF_STEP || k > HALF_STEP + 3 ? 0x12 : 0x1a) >> t & 1)) {
                    chunk_geglu(k < HALF_STEP ? k - 1 : (k > HALF_STEP + 3 ? k - 5 : k - HALF_STEP + 4));
                    if (k == 8 && t != 3) signal_stores(t + 1);
                }
                if (t == 2) chunk_qk(k);
                if (t == 3) chunk_pv(k);
                if (k == PV_STEP + OUT_STEPS) {
                    const uint32_t id = fresh_tid();
                    optr = prm.pa2 + (size_t)(row0(id) + (id & 28) / 2) * K2 + DM + gate_col(t, nslot) + id % 4 * 8;
                    asm volatile("" : "+l"(optr));
                }
            }
            wg_wait<0>();
            fence_regs(acc);
            release(empty1(3));
            if (t == 0) {
                Floats<2> inv(pk + 32);
#pragma unroll
                for (int i = 0; i < 128; i++) acc[i] *= inv[i / 2 % 2];
                fence_regs(acc);
            }
#pragma unroll
            for (int i = 0; i < 64; i++) {
                const int e = i < 32 ? (i & ~7) * 2 + (i & 3) * 4 + (i & 4) / 2 : i * 2;
                pk[i] = pack_bf16(acc[e], acc[e + 1]);
            }
            TRACE_NEXT(tile_slot);
        }

        float accd[64], accs[64];
#pragma unroll
        for (int i = 0; i < 64; i++) accd[i] = 0.f;
#pragma unroll
        for (int u = 0; u < G2_HEAD; u++) {
            const int q = u % G2_STAGES;
            TRACE_STEP(5, u, 0);
            mbar_wait(full2(q), (u / G2_STAGES) & 1, spins);
            TRACE_STEP(5, u, 1);
            if (u % 2) mma_step_c(accd, da, db, next2(q), u);
            else mma_step(accd, da, db, next2(q), u);
            wg_wait<1>();
            if (u > 0) release(empty2((u - 1) % G2_STAGES));
            TRACE_STEP(5, u, 2);
            if (u == UP_STEP) {
#pragma unroll
                for (int i = 0; i < 2; i++) {
                    const uint4 v = ldg_stream(prm.tail + role * 512 + i * 256 + threadIdx.x, stream_policy());
                    pk[56 + 4 * i] = v.x; pk[57 + 4 * i] = v.y; pk[58 + 4 * i] = v.z; pk[59 + 4 * i] = v.w;
                }
            }
            if (u >= 1) {
                const int j = (u - 1) / 2;
#pragma unroll
                for (int i = 2 * u - 2; i < 2 * u; i++) pk[i] = geglu2(pk[i], pk[up(i)]);
                if (u % 2 == 0) store_pk(optr + (j & 1) * 16 * K2 + (j >> 1) * 32, j);
            }
            if (u == G2_HEAD - 1) signal_stores(6);
        }
        auto down = [&](int q, uint32_t phase, bool narrow, bool busy = false) {
            mbar_wait(full2(q), phase, spins);
            if (narrow) mma_step96(accd, da, db, next2(q), 1);
            else if (busy) mma_step_c(accd, da, db, next2(q), 1);
            else mma_step(accd, da, db, next2(q), 1);
            wg_wait<1>();
            release(empty2((q + G2_STAGES - 1) % G2_STAGES));
        };
        uint32_t shared_steps = plan_word(base, lane);
        down(5, 0, false);
#pragma unroll 1
        for (uint32_t r = 3; r < 9; r++, shared_steps >>= G2_STAGES) {
#pragma unroll
            for (int q = 0; q < G2_STAGES; q++) down(q, r & 1, shared_steps >> q & 1);
        }
        down(0, 1, false);
        down(1, 1, false, true);
        TRACE_NEXT(tile_slot);
#pragma unroll
        for (int i = 0; i < 64; i++) accs[i] = 0.f;
        uint32_t gk[32], xr[32];
        const uint32_t xs = aux + cw * 2048;
        const uint32_t xrow = xs + ((lane & 7) + ((lane >> 3) & 1) * 8) * 128;
        auto xaddr = [&](int j) { return xrow + (j >> 2) * 16384 + (((((j & 3) * 2) + (lane >> 4)) ^ (lane & 7)) << 4); };
#pragma unroll
        for (int u = G2_DSTEPS; u < G2_KSTEPS; u++) {
            const int q = u % G2_STAGES, v = u - G2_DSTEPS;
            mbar_wait(full2(q), (u / G2_STAGES) & 1, spins);
            if (wg == 1 && u == G2_KSTEPS - G2_SKEW) asm volatile("bar.sync 1, 256;" ::: "memory");
            if (u % 2) mma_step_c(accs, da, db, next2(q), v);
            else mma_step(accs, da, db, next2(q), v);
            if (wg == 0 && u == G2_KSTEPS - 1) asm volatile("bar.arrive 1, 256;" ::: "memory");
            if (v == TAIL_STEP) {
                TRACE_S(32, wg, 0);
                mbar_wait(dep_bar + 24, 0, spins);
                TRACE_S(33, wg, 0);
#pragma unroll
                for (int i = 0; i < 2; i++) {
                    const uint4 w = ldg_stream(prm.tail + (NGEMM + role) * 512 + i * 256 + threadIdx.x, stream_policy());
                    gk[24 + 4 * i] = w.x; gk[25 + 4 * i] = w.y; gk[26 + 4 * i] = w.z; gk[27 + 4 * i] = w.w;
                }
            }
#pragma unroll
            for (int i = 0; i < 32; i++) {
                if (v == (i < 24 ? i / 4 + 1 : TAIL_STEP + i / 4 - 3))
                    gk[i] = i < 24 ? silu2(accd[2 * i], accd[2 * i + 1])
                                   : silu2(accd[2 * i] + bf_lo(gk[i]), accd[2 * i + 1] + bf_hi(gk[i]));
            }
            if (v == XREAD_STEP) mbar_wait(x_bar, 0, spins);
            if (v >= XREAD_STEP && v < XREAD_STEP + 4) {
#pragma unroll
                for (int j = 2 * (v - XREAD_STEP); j < 2 * (v - XREAD_STEP + 1); j++)
                    asm volatile("ldmatrix.sync.aligned.m8n8.x4.shared.b16 {%0,%1,%2,%3}, [%4];"
                                 : "=r"(xr[4 * j]), "=r"(xr[4 * j + 1]), "=r"(xr[4 * j + 2]), "=r"(xr[4 * j + 3])
                                 : "r"(xaddr(j)) : "memory");
            }
            wg_wait<1>();
            if (v == 0) fence_regs(accd);
            if (u - 1 + G2_STAGES < G2_KSTEPS) release(empty2((u - 1) % G2_STAGES));
        }
        __nv_bfloat16* po = prm.pout + (row0(fresh_tid()) + (lane >> 3) * 2) * DM + nslot * 128 + 64 + (lane & 7) * 8;
        uint32_t so = xs + 16384 + (lane >> 3) * 128 + (((lane & 7) ^ (lane >> 3)) << 4);
        const int c0 = uniform(nslot * 128), c1 = uniform(row0(fresh_tid()) >> 1);
        const uint32_t xu = uniform(xs);
        asm volatile("" : "+l"(po), "+r"(so));
        wg_wait<0>();
        fence_regs(accs);
        TRACE_NEXT(tile_slot);
        TRACE_END();
#pragma unroll
        for (int j = 0; j < 8; j++) {
            uint32_t r[4];
#pragma unroll
            for (int i = 0; i < 4; i++) {
                const int e = j * 4 + i;
                asm("fma.rn.bf16x2 %0, %1, %2, %3;" : "=r"(r[i]) : "r"(pack_bf16(accs[2 * e], accs[2 * e + 1])), "r"(gk[e]), "r"(xr[e]));
            }
            asm volatile("stmatrix.sync.aligned.m8n8.x4.shared.b16 [%0], {%1,%2,%3,%4};"
                         :: "r"(xaddr(j)), "r"(r[0]), "r"(r[1]), "r"(r[2]), "r"(r[3]) : "memory");
            if (j == 3)
                asm volatile("{\n.reg .pred e;\nfence.proxy.async.shared::cta;\nbar.warp.sync 0xffffffff;\nelect.sync _|e, 0xffffffff;\n"
                    "@e cp.async.bulk.tensor.3d.global.shared::cta.bulk_group [%0, {%2, %3, %4}], [%1];\n}"
                    :: "l"(&prm.out), "r"(xu), "r"(c0), "r"(c1), "r"(wg) : "memory");
        }
        __syncwarp();
#pragma unroll
        for (int i = 0; i < 4; i++) {
            const uint4 v = lds128((so ^ (i & 1) * 64) + i * 512);
            asm volatile("st.global.v4.u32 [%0], {%1,%2,%3,%4};" :: "l"(po + i * 8 * DM), "r"(v.x), "r"(v.y), "r"(v.z), "r"(v.w) : "memory");
        }
        asm volatile("cp.async.bulk.commit_group;\ncp.async.bulk.wait_group.read 0;" ::: "memory");
        TRACE_LITE(10, clock());
        if (tid == 0) { TRACE_NEXT(tile_slot); if (wg == 1) TRACE_GT(13); TRACE_DUMP(); }
    } else if (warp > 9) {
        const int w = warp - 10;
        const unsigned epoch = __ldcg(prm.epoch + blockIdx.x * 16 + w) + 1;
        const uint32_t tag = 1 + (epoch & 1);
        TRACE_LITE(8, t0);
        const uint32_t at = (w ? SUM_LOAD1 : SUM_LOAD0) >> nslot * 4 & 15;
        mbar_wait(empty1(at & 3), 0);
        mbar_wait(empty1(at & 3), at >> 3);
        if (elect_one()) {
            mbar_expect_tx(cs_bar + w * 8, 16384);
            asm volatile("cp.async.bulk.tensor.2d.shared::cluster.global.mbarrier::complete_tx::bytes [%0], [%1, {%3, %5}], [%2];\n"
                "cp.async.bulk.tensor.2d.shared::cluster.global.mbarrier::complete_tx::bytes [%0 + 8192], [%1, {%4, %5}], [%2];"
                :: "r"(aux + w * 16384), "l"(w0), "r"(cs_bar + w * 8), "r"(nslot * 128), "r"(nslot * 128 + 64),
                   "r"(((mblk & ~1) + w) * 64) : "memory");
        }
        float cs[8];
#pragma unroll
        for (int d = 0; d < 8; d++) cs[d] = 0.f;
        const uint32_t wa = aux + w * 8192 + (lane >> 3) * 128 + (((lane & 7) ^ (lane >> 3)) << 4);
        uint4 v[8];
        auto fetch = [&](int h, uint32_t off) {
#pragma unroll
            for (int j = 0; j < 4; j++) v[h * 4 + j] = lds128((wa ^ (j & 1) * 64) + off + h * 2048 + j * 512);
        };
        auto add = [&](int h) {
#pragma unroll
            for (int j = 0; j < 4; j++) {
                float f[8];
                unpack8(v[h * 4 + j], f);
#pragma unroll
                for (int d = 0; d < 8; d++) cs[d] += f[d];
            }
        };
        mbar_wait(empty1(SUM_STEP & 3), 0);
        mbar_wait(empty1(SUM_STEP & 3), SUM_STEP >> 3);
        mbar_wait(cs_bar, 0);
        fetch(0, 0);
#pragma unroll 1
        for (int i = 0; i < 4; i++) {
            fetch(1, (i >> 1) * 16384 + (i & 1) * 4096);
            add(0);
            if (i == 1) mbar_wait(cs_bar + 8, 0);
            fetch(0, (i + 1 & 2) * 8192 + (~i & 1) * 4096);
            add(1);
        }
#pragma unroll
        for (int d = 0; d < 4; d++)
            cs[d] = (lane & 16 ? cs[d + 4] : cs[d]) + __shfl_xor_sync(0xffffffffu, lane & 16 ? cs[d] : cs[d + 4], 16);
#pragma unroll
        for (int d = 0; d < 2; d++)
            cs[d] = (lane & 8 ? cs[d + 2] : cs[d]) + __shfl_xor_sync(0xffffffffu, lane & 8 ? cs[d] : cs[d + 2], 8);
        st_tagged(prm.colsum + (nslot * 2 + rank) * 1024 + (mblk >> 1) * 128 + w * 64 + (lane & 7) * 8 + (lane >> 3) * 2,
                  cs[0], cs[1], tag);

        fold_operands(prm, base, nslot, mblk, tag, w, lane);
        if (lane == 0) {
            mbar_arrive(fold_bar);
            prm.epoch[blockIdx.x * 16 + w] = epoch;
            if (w == 0) {
                TRACE(35);
#pragma unroll 1
                for (uint32_t j = 0, n = 1 << 24; j < 4; n = (CNT_EARLY | CNT_LATE << 8 | 1 << 16) >> j * 8 & 255, j++) {
                    mbar_wait(sig_bar + (0xa0302820u >> j * 8 & 255), 0);
                    const uint32_t v = flag_wait(flags + (F_SHARE + j) * 512, epoch * n);
                    fence_proxy_async();
                    if (j) mbar_arrive(dep_bar + j * 8);
                    else sts32(base + PLAN_OFF, v & 0xffffff);
                }
            } else {
#pragma unroll 1
                for (int j = 0; j < 2; j++) {
                    uint8_t* const h = prm.halo + (j * NGEMM + role) * HALO_BYTES;
                    unsigned* const f = prm.flags + F_HALO * 512 + role * 32;
                    mbar_wait(sig_bar + 8 + j * 16, 0);
                    TRACE_S(38, j, 0); TRACE_S(9, j, 1);
                    asm volatile("cp.async.bulk.global.shared::cta.bulk_group [%0], [%1], %2;\n"
                        "cp.async.bulk.commit_group;\ncp.async.bulk.wait_group 0;"
                        :: "l"(h + HALO_BYTES), "r"(aux + 4 * HALO_BYTES), "n"(HALO_BYTES) : "memory");
                    fence_proxy_async();
                    TRACE_S(39, j, 0); TRACE_S(10, j, 1);
                    flag_add(f);
                    TRACE_S(40, j, 0); TRACE_S(34, j, 1);
                    if (mblk) flag_wait(f - 32, epoch * 2 - 1 + j);
                    fence_proxy_async();
                    TRACE_S(41, j, 0); TRACE_S(36, j, 1);
                    mbar_expect_tx(halo_bar, HALO_BYTES);
                    asm volatile("cp.async.bulk.shared::cluster.global.mbarrier::complete_tx::bytes [%0], [%1], %2, [%3];"
                        :: "r"(aux), "l"(mblk ? h : prm.halo), "n"(HALO_BYTES), "r"(halo_bar) : "memory");
                }
            }
        }
    } else {
#pragma unroll 1
        for (int k = 1; k < G1_STAGES; k++) {
            const uint32_t sa = base + k * G1_STAGE_BYTES;
            while ((uint32_t)clock() - t0 < (k == 3 ? PACE3 : PACE1 + (k - 1) * (PACE2 - PACE1))) {}
            load_stage1(sa, sa + A_BYTES + rank * 16384, full1(k), &prm.x, w0, w0, k * 64, mblk * 64, nslot * 128,
                        nslot * 128 + 64, 0, stream_policy());
        }
        if (elect_one()) {
            prefetch_map(&prm.xn); prefetch_map(&prm.wqkv);
            prefetch_map(&prm.a2); prefetch_map(&prm.wo); prefetch_map(&prm.wd); prefetch_map(&prm.out);
        }
        uint32_t ph = 0;
#pragma unroll 1
        for (int t = 0; t < G1_TILES; t++) {
            const int col1 = (t == 1 ? rank * DM + nslot * 128 : gate_col(t, nslot)) + 64;
            const int col0 = t == 2 ? 2 * DM + nslot * 128 + rank * 64 : col1 - 64;
            if (t == 1) { TRACE_PUT(2, t0); TRACE(14); mbar_wait_warp(dep_bar, 0); TRACE(3); }
#pragma unroll 1
            for (int k = t ? 0 : G1_STAGES; k < G1_KSTEPS; k++) {
                const int s = k & 3;
                if (t == 1 && k == 8) mbar_wait_warp(dep_bar + 40, 0);
                mbar_wait_warp(empty1(s), ph);
                const uint32_t sa = base + s * G1_STAGE_BYTES;
                load_stage1(sa, sa + A_BYTES + rank * 16384, full1(s), t ? &prm.xn : &prm.x, t == 1 || t == 2 ? &prm.wqkv : w0,
                            t == 1 ? &prm.wqkv : w0, k * 64, mblk * 64, col0, col1, t & 3,
                            stream_policy());
                TRACE_RING(t * 16 + k);
                if (s == 3) ph ^= 1;
            }
        }
        TRACE(4);
        mbar_wait_warp(dep_bar + 8, 0);
        TRACE(5);
        int q = 0, round = 4, own = SHARE_MAX; uint32_t ph2 = 1;
#pragma unroll 1
        for (int u = 0; u < G2_KSTEPS; u++) {
            if (u == G2_LATE) { TRACE(6); mbar_wait_warp(dep_bar + 16, 0); TRACE(7); }
            const uint32_t sa = stage2(q);
            const bool down = u < G2_DSTEPS;
            const int k = !down ? u - G2_DSTEPS : (u < 18 || u >= 40 ? own++ : (q & 1 ? u / 2 - 9 : round + (q ? q * 2 : 11)));
            mbar_wait_warp(u < G2_STAGES ? empty1((u * 2 + 1) / 3) : empty2(q), u < G2_STAGES ? ph : ph2);
            load_stage2(sa, sa + A_BYTES + rank * 8192, full2(q), &prm.a2, down ? &prm.wd : &prm.wo, (down ? DM : 0) + k * 64,
                        mblk * 64, nslot * 128 + rank * 64, down ? 0 : k * 2, down ? k * 2 : 0, stream_policy());
            if (u == XLOAD_STEP + nslot * 2) {
                if (elect_one()) {
                    mbar_expect_tx(x_bar, 32768);
                    tma_3d(aux, &prm.x, x_bar, nslot * 128, mblk * 64, 0, stream_policy());
                    tma_3d(aux + 16384, &prm.x, x_bar, nslot * 128 + 64, mblk * 64, 0, stream_policy());
                }
                __syncwarp();
            }
            TRACE_RING(80 + u);
            if (++q == G2_STAGES) { q = 0; ph2 ^= 1; round++; }
        }
        TRACE(8);
    }
}

typedef CUresult (*EncodeFn)(CUtensorMap*, CUtensorMapDataType, cuuint32_t, void*, const cuuint64_t*, const cuuint64_t*,
                             const cuuint32_t*, const cuuint32_t*, CUtensorMapInterleave, CUtensorMapSwizzle,
                             CUtensorMapL2promotion, CUtensorMapFloatOOBfill);

void encode(EncodeFn fn, CUtensorMap* m, const void* ptr, int rank, const cuuint64_t* dims, const cuuint64_t* strides,
            const cuuint32_t* box) {
    const cuuint32_t es[5] = {1, 1, 1, 1, 1};
    fn(m, CU_TENSOR_MAP_DATA_TYPE_BFLOAT16, rank, const_cast<void*>(ptr), dims, strides, box, es,
       CU_TENSOR_MAP_INTERLEAVE_NONE, box[0] == 32 ? CU_TENSOR_MAP_SWIZZLE_64B : CU_TENSOR_MAP_SWIZZLE_128B,
       CU_TENSOR_MAP_L2_PROMOTION_L2_128B, CU_TENSOR_MAP_FLOAT_OOB_FILL_NONE);
}
void encode_rows(EncodeFn fn, CUtensorMap* m, const void* ptr, int cols, int box_rows, int box_parity) {
    const cuuint64_t dims[3] = {(cuuint64_t)cols, SEQ / 2, 2}, strides[2] = {(cuuint64_t)cols * 4, (cuuint64_t)cols * 2};
    const cuuint32_t box[3] = {64, (cuuint32_t)box_rows, (cuuint32_t)box_parity};
    encode(fn, m, ptr, 3, dims, strides, box);
}
void encode_w1(EncodeFn fn, CUtensorMap* m, const void* ptr, int cols) {
    const cuuint64_t dims[2] = {(cuuint64_t)cols, DM}, strides[1] = {(cuuint64_t)cols * 2};
    const cuuint32_t box[2] = {64, 64};
    encode(fn, m, ptr, 2, dims, strides, box);
}
void encode_tail(EncodeFn fn, CUtensorMap* m, const void* ptr, int rows, int cols, int n) {
    const cuuint64_t rb = cols * 2;
    const cuuint64_t dims[5] = {32, (cuuint64_t)n, (cuuint64_t)rows / (4 * n), 4, 8}, strides[4] = {rb, 4 * n * rb, n * rb, 256};
    const cuuint32_t box[5] = {32, (cuuint32_t)n, 16 / (cuuint32_t)n, 4, 4};
    encode(fn, m, (const __nv_bfloat16*)ptr + cols - 1024 + 96, 5, dims, strides, box);
}
void encode_w2(EncodeFn fn, CUtensorMap* m, const void* ptr, int rows) {
    const cuuint64_t rb = DM * 2;
    const cuuint64_t dims[5] = {DM, 2, 4, 4, (cuuint64_t)rows / 32}, strides[4] = {rb, 8 * rb, 2 * rb, 32 * rb};
    const cuuint32_t box[5] = {64, 2, 4, 4, 2};
    encode(fn, m, ptr, 5, dims, strides, box);
}
void encode_wo(EncodeFn fn, CUtensorMap* m, const void* ptr) {
    const cuuint64_t rb = DM * 2;
    const cuuint64_t dims[5] = {DM, 4, DM / 32, 2, 4}, strides[4] = {8 * rb, 32 * rb, rb, 2 * rb};
    const cuuint32_t box[5] = {64, 4, 2, 2, 4};
    encode(fn, m, ptr, 5, dims, strides, box);
}

}

extern "C" void kernel_launch(void* const* d_in, const int* in_sizes, int n_in, void* d_out, int out_size) {
    (void)in_sizes; (void)n_in; (void)out_size;
    static EncodeFn fn = nullptr;
    static Params prm;
    if (!fn) {
        cudaDriverEntryPointQueryResult st;
        cudaGetDriverEntryPoint("cuTensorMapEncodeTiled", (void**)&fn, cudaEnableDefault, &st);
        cudaGetSymbolAddress((void**)&prm.pxn, g_xn);
        cudaGetSymbolAddress((void**)&prm.pa2, g_a2);
        cudaGetSymbolAddress((void**)&prm.tail, g_tail);
        cudaGetSymbolAddress((void**)&prm.halo, g_halo);
        cudaGetSymbolAddress((void**)&prm.stats, g_stats);
        cudaGetSymbolAddress((void**)&prm.colsum, g_colsum);
        cudaGetSymbolAddress((void**)&prm.flags, g_flags);
        cudaGetSymbolAddress((void**)&prm.epoch, g_epoch);
        cudaFuncSetAttribute(fused_kernel, cudaFuncAttributeMaxDynamicSharedMemorySize, SMEM_BYTES);
    }
    encode_rows(fn, &prm.x, d_in[0], DM, 64, 2);
    encode_rows(fn, &prm.xn, prm.pxn, DM, 64, 2);
    encode_rows(fn, &prm.a2, prm.pa2, K2, 64, 2);
    encode_rows(fn, &prm.out, d_out, DM, 16, 1);
    encode_w1(fn, &prm.wqkv, d_in[1], NQKV);
    encode_w1(fn, &prm.wg, d_in[4], DF);
    encode_w1(fn, &prm.wu, d_in[5], DF);
    encode_tail(fn, &prm.wu_tail, d_in[5], DM, DF, 8);
    encode_tail(fn, &prm.wd_tail, d_in[6], DF, DM, 2);
    encode_wo(fn, &prm.wo, d_in[2]);
    encode_w2(fn, &prm.wd, d_in[6], DF);
    prm.hi[0] = prm.hi[1] = 0x40000040;
    prm.px = (const __nv_bfloat16*)d_in[0];
    prm.pwu = (const __nv_bfloat16*)d_in[5];
    prm.pout = (__nv_bfloat16*)d_out;
    fused_kernel<<<NCTA, 384, SMEM_BYTES>>>(prm);
}
```

```cpp
#include <cuda_runtime.h>
#include <cuda_bf16.h>
#include <cuda.h>
#include <stdint.h>
#include <limits.h>

namespace {

constexpr int SEQ = 2048, DM = 1024, DF = 3584, K2 = DM + DF, NQKV = 3 * DM;
constexpr int NGEMM = 128, NCTA = 132;
constexpr int G1_STAGES = 4, G1_STAGE_BYTES = 49152, G1_KSTEPS = 16, G1_TILES = 5;
constexpr int G2_STAGES = 6, G2_STAGE_BYTES = 32768, G2_KSTEPS = 72, G2_LATE = 40, G2_DSTEPS = 56;
constexpr int G2_HEAD = 17;
constexpr int A_BYTES = 16384;
constexpr int AUX_OFF = G1_STAGES * G1_STAGE_BYTES;
constexpr int BAR_OFF = AUX_OFF + 32768;
constexpr int PLAN_OFF = BAR_OFF + 384, STAT_OFF = BAR_OFF + 1536;
constexpr int SMEM_BYTES = BAR_OFF + 2816;
constexpr int G1_SKEW = 2, G2_SKEW = 5;
constexpr int CONSUMER_REGS = 224, AUX_REGS = 56;
constexpr int HALO_BYTES = 4096;
constexpr int LN_STEP = 3, FOLD_STEP = 14, SUM_STEP = 11, SUM2_STEP = 2;
constexpr uint32_t SUM_LOAD0 = 0x87658765u, SUM_LOAD1 = 0x65876587u;
constexpr int KEY_STEP = 2, QK_STEP = 8;
constexpr int VAL_STEP = 1, HALF_STEP = 3, PV_STEP = 9, OUT_STEPS = 4;
constexpr int UP_STEP = 2, XLOAD_STEP = 44;
constexpr int XREAD_STEP = 5, TAIL_STEP = 7;
constexpr int MEET = 4;
constexpr int PACE1 = 800, PACE2 = 1325, PACE3 = 1700;
constexpr int SHARE_MIN = 3, SHARE_MAX = 22, SHARE_LOW = 36, SHARE_SUM = 43;
constexpr int SHARE_NS = 79, SPARE_NS = 640, LATE_SCALE = 8;
constexpr float REST = 65000.f, DUE = 75100.f;

enum { F_LN = 0, F_LN2 = 1, F_FIRST = 2, F_SECOND = 3, F_SHARE = 4, F_EARLY = 5, F_LATE = 6, F_TAIL2 = 7, F_PACE = 8, F_HALO = 9 };
constexpr unsigned CNT_LN = 8, CNT_EARLY = 9, CNT_LATE = 8;

__device__ __align__(1024) __nv_bfloat16 g_xn[SEQ * DM];
__device__ __align__(1024) __nv_bfloat16 g_a2[SEQ * K2];
__device__ __align__(128) uint4 g_tail[2 * NGEMM * 512];
__device__ __align__(128) uint8_t g_halo[(2 * NGEMM + 1) * HALO_BYTES];
__device__ __align__(128) float2 g_stats[SEQ];
__device__ __align__(128) float g_colsum[18 * 1024];
__device__ __align__(128) unsigned g_flags[(F_HALO + 8) * 16 * 32];
__device__ __align__(128) unsigned g_epoch[NCTA * 16];

struct Params {
    const __nv_bfloat16 *px, *pwu;
    __nv_bfloat16 *pxn, *pa2, *pout;
    uint4* tail;
    uint8_t* halo;
    float2* stats;
    float* colsum;
    unsigned *flags, *epoch;
    unsigned long long* trace;
    uint32_t hi[4];
    CUtensorMap x, wg, wu, xn, wqkv, a2, wu_tail, wd_tail, wo, wd, out;
};

extern __shared__ __align__(1024) uint8_t smem_raw[];

#define TRACE(slot) do {} while (0)
#define TRACE_GT(slot) do {} while (0)
#define TRACE_S(slot, v, want) do {} while (0)
#define TRACE_GET(v) do {} while (0)
#define TRACE_PUT(slot, v) do {} while (0)
#define TRACE_SLOT(v, slot) do {} while (0)
#define TRACE_NEXT(v) do {} while (0)
#define TRACE_DUMP() do {} while (0)
#define TRACE_CLEAR() do {} while (0)
#define STAGE_TRACE 0
#define TRACE_END() do {} while (0)
#define TRACE_LITE(i, c) do {} while (0)
#define TRACE_RING(i) do {} while (0)
#define TRACE_STEP(t, k, i) do {} while (0)

__device__ __forceinline__ uint32_t smem_u32(const void* p) { return (uint32_t)__cvta_generic_to_shared(p); }
__device__ __forceinline__ void mbar_expect_tx(uint32_t bar, uint32_t bytes) {
    asm volatile("mbarrier.arrive.expect_tx.shared::cta.b64 _, [%0], %1;" :: "r"(bar), "r"(bytes) : "memory");
}
__device__ __forceinline__ void mbar_arrive(uint32_t bar) {
    asm volatile("mbarrier.arrive.shared::cta.b64 _, [%0];" :: "r"(bar) : "memory");
}
__device__ __forceinline__ bool mbar_try_wait(uint32_t bar, uint32_t parity) {
    uint32_t ok;
    asm volatile("{\n.reg .pred p;\nmbarrier.try_wait.parity.shared::cta.b64 p, [%1], %2;\nselp.u32 %0, 1, 0, p;\n}"
                 : "=r"(ok) : "r"(bar), "r"(parity) : "memory");
    return ok;
}
__device__ __forceinline__ void mbar_wait(uint32_t bar, uint32_t parity) {
#pragma unroll 1
    for (int spins = 0; !mbar_try_wait(bar, parity) && spins < (1 << 17); spins++) {}
}
__device__ __forceinline__ void mbar_wait(uint32_t bar, uint32_t parity, int& spins) {
    asm volatile("{\n.reg .pred p;\nagain:\nmbarrier.try_wait.parity.shared::cta.b64 p, [%1], %2;\n@p bra done;\n"
                 "add.s32 %0, %0, -1;\nsetp.gt.s32 p, %0, 0;\n@p bra again;\ndone:\n}" : "+r"(spins) : "r"(bar), "r"(parity) : "memory");
}
template <bool WARP = false> __device__ __forceinline__ unsigned flag_wait(const unsigned* p, unsigned target) {
    unsigned v;
#pragma unroll 1
    for (int spins = 0; spins < (1 << 19); spins++) {
        asm volatile("ld.acquire.gpu.global.u32 %0, [%1];" : "=r"(v) : "l"(p) : "memory");
        if (WARP ? __all_sync(0xffffffffu, (int)(v - target) >= 0) : (int)(v - target) >= 0) break;
        __nanosleep(64);
    }
    return v;
}
__device__ __forceinline__ void mbar_wait_warp(uint32_t bar, uint32_t parity) {
#pragma unroll 1
    for (int spins = 0; !__all_sync(0xffffffffu, mbar_try_wait(bar, parity)) && spins < (1 << 17); spins++) {}
}
__device__ __forceinline__ void flag_add(unsigned* p) {
    asm volatile("red.release.gpu.global.add.u32 [%0], 1;" :: "l"(p) : "memory");
}
__device__ __forceinline__ bool elect_one() {
    uint32_t ok;
    asm volatile("{\n.reg .pred p;\nelect.sync _|p, 0xffffffff;\nselp.u32 %0, 1, 0, p;\n}" : "=r"(ok));
    return ok;
}
__device__ __forceinline__ uint32_t pick(bool c, uint32_t a, uint32_t b) {
    uint32_t r;
    asm("{\n.reg .pred p;\nsetp.ne.b32 p, %3, 0;\nselp.b32 %0, %1, %2, p;\n}" : "=r"(r) : "r"(a), "r"(b), "r"((uint32_t)c));
    return r;
}
__device__ __forceinline__ void fence_proxy_async() { asm volatile("fence.proxy.async.global;" ::: "memory"); }
__device__ __forceinline__ uint4 lds128(uint32_t addr) {
    uint4 v;
    asm volatile("ld.shared.v4.u32 {%0,%1,%2,%3}, [%4];" : "=r"(v.x), "=r"(v.y), "=r"(v.z), "=r"(v.w) : "r"(addr) : "memory");
    return v;
}
__device__ __forceinline__ uint32_t lds32(uint32_t addr) {
    uint32_t v;
    asm volatile("ld.shared.u32 %0, [%1];" : "=r"(v) : "r"(addr) : "memory");
    return v;
}
__device__ __forceinline__ void sts32(uint32_t addr, uint32_t v) { asm volatile("st.shared.u32 [%0], %1;" :: "r"(addr), "r"(v) : "memory"); }
__device__ __forceinline__ uint32_t nanos() { uint32_t t; asm volatile("mov.u32 %0, %%globaltimer_lo;" : "=r"(t)); return t; }
__device__ __forceinline__ float2 lds64f(uint32_t addr) {
    float2 v;
    asm volatile("ld.shared.v2.f32 {%0,%1}, [%2];" : "=f"(v.x), "=f"(v.y) : "r"(addr) : "memory");
    return v;
}
__device__ __forceinline__ void sts128(uint32_t addr, uint4 v) {
    asm volatile("st.shared.v4.u32 [%0], {%1,%2,%3,%4};" :: "r"(addr), "r"(v.x), "r"(v.y), "r"(v.z), "r"(v.w) : "memory");
}
__device__ __forceinline__ void sts64f(uint32_t addr, float a, float b) {
    asm volatile("st.shared.v2.f32 [%0], {%1,%2};" :: "r"(addr), "f"(a), "f"(b) : "memory");
}

__device__ __forceinline__ uint64_t stream_policy() { return 0x12F0000000000000ull; }
__device__ __forceinline__ void tma_3d(uint32_t dst, const CUtensorMap* m, uint32_t bar, int c0, int c1, int c2, uint64_t pol) {
    asm volatile("cp.async.bulk.tensor.3d.shared::cluster.global.mbarrier::complete_tx::bytes.L2::cache_hint"
                 " [%0], [%1, {%3, %4, %5}], [%2], %6;"
                 :: "r"(dst), "l"(m), "r"(bar), "r"(c0), "r"(c1), "r"(c2), "l"(pol) : "memory");
}
__device__ __forceinline__ void load_stage1(uint32_t dst, uint32_t dst_b, uint32_t bar, const CUtensorMap* ma, const CUtensorMap* mb0,
                                            const CUtensorMap* mb1, int k, int row, int col0, int col1, int keep_a, uint64_t pol) {
    asm volatile("{\n.reg .pred e, p, q;\nelect.sync _|e, 0xffffffff;\nsetp.ne.and.b32 p|q, %8, 0, e;\n"
        "@p cp.async.bulk.tensor.3d.shared::cluster.global.mbarrier::complete_tx::bytes [%0], [%3, {%5, %6, %10}], [%2];\n"
        "@q cp.async.bulk.tensor.3d.shared::cluster.global.mbarrier::complete_tx::bytes.L2::cache_hint [%0], [%3, {%5, %6, %10}], [%2], %9;\n"
        "@e cp.async.bulk.tensor.2d.shared::cluster.global.mbarrier::complete_tx::bytes.multicast::cluster.L2::cache_hint"
        " [%1], [%4, {%7, %5}], [%2], %11, %9;\n"
        "@e cp.async.bulk.tensor.2d.shared::cluster.global.mbarrier::complete_tx::bytes.multicast::cluster.L2::cache_hint"
        " [%1 + 8192], [%13, {%14, %5}], [%2], %11, %9;\n"
        "@e mbarrier.arrive.expect_tx.shared::cta.b64 _, [%2], %12;\n}"
        :: "r"(dst), "r"(dst_b), "r"(bar), "l"(ma), "l"(mb0), "r"(k), "r"(row), "r"(col0), "r"(keep_a), "l"(pol), "r"(0),
           "h"((uint16_t)3), "n"(G1_STAGE_BYTES), "l"(mb1), "r"(col1) : "memory");
}
__device__ __forceinline__ void load_stage2(uint32_t dst, uint32_t dst_b, uint32_t bar, const CUtensorMap* ma, const CUtensorMap* mb,
                                            int ka, int row, int col, int kb2, int kb4, uint64_t pol) {
    asm volatile("{\n.reg .pred e;\nelect.sync _|e, 0xffffffff;\n"
        "@e cp.async.bulk.tensor.3d.shared::cluster.global.mbarrier::complete_tx::bytes.L2::cache_hint [%0], [%3, {%5, %6, %10}], [%2], %9;\n"
        "@e cp.async.bulk.tensor.5d.shared::cluster.global.mbarrier::complete_tx::bytes.multicast::cluster.L2::cache_hint"
        " [%1], [%4, {%7, %10, %13, %10, %8}], [%2], %11, %9;\n"
        "@e mbarrier.arrive.expect_tx.shared::cta.b64 _, [%2], %12;\n}"
        :: "r"(dst), "r"(dst_b), "r"(bar), "l"(ma), "l"(mb), "r"(ka), "r"(row), "r"(col), "r"(kb4), "l"(pol), "r"(0),
           "h"((uint16_t)3), "n"(G2_STAGE_BYTES), "r"(kb2) : "memory");
}
__device__ __forceinline__ void load_tail(uint32_t dst, uint32_t bar, const CUtensorMap* ma, const CUtensorMap* mb, int ka, int row,
                                          int rank, int kb) {
    asm volatile("{\n.reg .pred e;\nelect.sync _|e, 0xffffffff;\n"
        "@e cp.async.bulk.tensor.3d.shared::cluster.global.mbarrier::complete_tx::bytes [%0], [%2, {%3, %4, %5}], [%1];\n"
        "@e cp.async.bulk.tensor.5d.shared::cluster.global.mbarrier::complete_tx::bytes.multicast::cluster"
        " [%9], [%6, {%5, %5, %7, %5, %10}], [%1], %11;\n"
        "@e mbarrier.arrive.expect_tx.shared::cta.b64 _, [%1], %8;\n}"
        :: "r"(dst), "r"(bar), "l"(ma), "r"(ka), "r"(row), "r"(0), "l"(mb), "r"(kb), "n"(G1_STAGE_BYTES),
           "r"(dst + A_BYTES + rank * 16384), "r"(rank * 4), "h"((uint16_t)3) : "memory");
}
__device__ __forceinline__ uint4 ldg_stream(const void* p, uint64_t pol) {
    uint4 v;
    asm volatile("ld.global.nc.L1::no_allocate.L2::cache_hint.v4.u32 {%0,%1,%2,%3}, [%4], %5;"
                 : "=r"(v.x), "=r"(v.y), "=r"(v.z), "=r"(v.w) : "l"(p), "l"(pol));
    return v;
}
__device__ __forceinline__ void st_tagged(void* p, float a, float b, uint32_t tag) {
    asm volatile("st.relaxed.gpu.global.v2.b32 [%0], {%1,%2};"
                 :: "l"(p), "r"((__float_as_uint(a) & ~3u) | tag), "r"((__float_as_uint(b) & ~3u) | tag) : "memory");
}
__device__ __forceinline__ void st_relaxed(unsigned* p, uint32_t v) {
    asm volatile("st.relaxed.gpu.global.b32 [%0], %1;" :: "l"(p), "r"(v) : "memory");
}
__device__ __forceinline__ bool untagged(const uint4& v, uint32_t tag) {
    return ((v.x ^ tag) | (v.y ^ tag) | (v.z ^ tag) | (v.w ^ tag)) & 3;
}
__device__ __forceinline__ uint4 ld_relaxed(const void* p) {
    uint4 v;
    asm volatile("ld.relaxed.gpu.global.v4.b32 {%0,%1,%2,%3}, [%4];" : "=r"(v.x), "=r"(v.y), "=r"(v.z), "=r"(v.w) : "l"(p) : "memory");
    return v;
}
__device__ __forceinline__ void prefetch_map(const CUtensorMap* m) {
    asm volatile("prefetch.tensormap [%0];" :: "l"(m) : "memory");
}
template <int N> __device__ __forceinline__ void wg_wait() { asm volatile("wgmma.wait_group.sync.aligned %0;" :: "n"(N) : "memory"); }

constexpr uint32_t HI_128B = 0x40000040, HI_64B = 0x80000020;
__device__ __forceinline__ uint32_t desc_a(uint32_t addr) { return (addr & 0x3FFFF) >> 4 | 1 << 16; }
__device__ __forceinline__ uint32_t desc_b(uint32_t addr) { return (addr & 0x3FFFF) >> 4 | 512 << 16; }

#define R8(d, o) "+f"(d[o]), "+f"(d[o+1]), "+f"(d[o+2]), "+f"(d[o+3]), "+f"(d[o+4]), "+f"(d[o+5]), "+f"(d[o+6]), "+f"(d[o+7])
#define R32(d, o) R8(d, o), R8(d, o+8), R8(d, o+16), R8(d, o+24)
#define R64(d, o) R32(d, o), R32(d, o+32)
#define ACC00 "%0,%1,%2,%3,%4,%5,%6,%7,%8,%9,%10,%11,%12,%13,%14,%15,%16,%17,%18,%19,%20,%21,%22,%23,%24,%25,%26,%27,%28,%29,%30,%31,"\
    "%32,%33,%34,%35,%36,%37,%38,%39,%40,%41,%42,%43,%44,%45,%46,%47"
#define ACC0 ACC00 ",%48,%49,%50,%51,%52,%53,%54,%55,%56,%57,%58,%59,%60,%61,%62,%63"
#define ACC1 "%64,%65,%66,%67,%68,%69,%70,%71,%72,%73,%74,%75,%76,%77,%78,%79,%80,%81,%82,%83,%84,%85,%86,%87,%88,%89,%90,%91,%92,%93,%94,%95,"\
    "%96,%97,%98,%99,%100,%101,%102,%103,%104,%105,%106,%107,%108,%109,%110,%111"
#define ACC48 "{" ACC00 "}"
#define ACC64 "{" ACC0 "}"
#define ACC112 "{" ACC0 "," ACC1 "}"
#define ACC128 "{" ACC0 "," ACC1 ",%112,%113,%114,%115,%116,%117,%118,%119,%120,%121,%122,%123,%124,%125,%126,%127}"
#define MMA_K16(shape, acc, a, b, keep, ha, hb) \
    "mov.b64 da, {" a ", " ha "};\nmov.b64 db, {" b ", " hb "};\n" \
    "wgmma.mma_async.sync.aligned." shape ".f32.bf16.bf16 " acc ", da, db, " keep ", 1, 1, 0, 1;\n"
#define MMA_NEXT(op, a, b, sa, sb) op " " a ", " a ", " sa ";\n" op " " b ", " b ", " sb ";\n"
#define MMA_STEP_B(shape, acc, a, b, keep, ha, hb, sa, sb) \
    "{\n.reg .pred p, q;\n.reg .b64 da, db;\nsetp.ne.b32 p, " keep ", 0;\nsetp.eq.b32 q, 0, 0;\nwgmma.fence.sync.aligned;\n" \
    MMA_K16(shape, acc, a, b, "p", ha, hb) MMA_NEXT("xor.b32", a, b, "2", "128") MMA_K16(shape, acc, a, b, "q", ha, hb) MMA_NEXT("add.s32", a, b, sa, sb) \
    MMA_K16(shape, acc, a, b, "q", ha, hb) MMA_NEXT("xor.b32", a, b, "2", "128") MMA_K16(shape, acc, a, b, "q", ha, hb) \
    "wgmma.commit_group.sync.aligned;\n}"
#define MMA64(shape, acc, a, b, keep) "wgmma.mma_async.sync.aligned." shape ".f32.bf16.bf16 " acc ", " a ", " b ", " keep ", 1, 1, 0, 1;\n"
#define NEXT64(op, a, b, sa, sb) "mov.b64 {lo, hi}, " a ";\n" op " lo, lo, " sa ";\nmov.b64 " a ", {lo, hi};\n" \
    "mov.b64 {lo, hi}, " b ";\n" op " lo, lo, " sb ";\nmov.b64 " b ", {lo, hi};\n"
#define ADD64(op, a, b, sa, sb) "cvt.s64.s32 w, " sa ";\nadd.s64 " a ", " a ", w;\ncvt.s64.s32 w, " sb ";\nadd.s64 " b ", " b ", w;\n"
#define MMA_STEP(shape, acc, a, b, na, nb, keep, sa) MMA_STEP_N(shape, acc, a, b, na, nb, keep, sa, NEXT64)
#define MMA_STEP_N(shape, acc, a, b, na, nb, keep, sa, LAST) \
    "{\n.reg .pred p, q;\n.reg .b32 lo, hi;\n.reg .b64 w;\nsetp.ne.b32 p, " keep ", 0;\nsetp.eq.b32 q, 0, 0;\nwgmma.fence.sync.aligned;\n" \
    MMA64(shape, acc, a, b, "p") NEXT64("xor.b32", a, b, "2", "128") MMA64(shape, acc, a, b, "q") NEXT64("add.s32", a, b, sa, "128") \
    MMA64(shape, acc, a, b, "q") NEXT64("xor.b32", a, b, "2", "128") MMA64(shape, acc, a, b, "q") LAST("add.s32", a, b, na, nb) \
    "wgmma.commit_group.sync.aligned;\n}"
#define MMA_ARGS64(sa) "+l"(da), "+l"(db) : "r"(next / 16 - 4 - sa), "r"(next / 16 - 384), "r"(keep), "n"(sa) : "memory"

__device__ __forceinline__ void mma_step(float (&d)[128], uint64_t& da, uint64_t& db, int next, int keep) {
    asm volatile(MMA_STEP("m64n256k16", ACC128, "%128", "%129", "%130", "%131", "%132", "%133") : R64(d, 0), R64(d, 64), MMA_ARGS64(2));
}
__device__ __forceinline__ void mma_rank(float (&d)[128], uint32_t a0, uint32_t a1, uint32_t db) {
    asm volatile("{\n.reg .pred q;\n.reg .b64 db;\nsetp.eq.b32 q, 0, 0;\nmov.b64 db, {%131, 0x40000040};\nwgmma.fence.sync.aligned;\n"
                 "wgmma.mma_async.sync.aligned.m64n256k16.f32.bf16.bf16 " ACC128 ", {%128, %129, %130, %130}, db, q, 1, 1, 1;\n}"
                 : R64(d, 0), R64(d, 64) : "r"(a0), "r"(a1), "r"(0), "r"(db) : "memory");
}
__device__ __forceinline__ void mma_step224(float (&d)[128], uint64_t& da, uint64_t& db, int next, int keep) {
    asm volatile(MMA_STEP("m64n224k16", ACC112, "%112", "%113", "%114", "%115", "%116", "%117")
                 : R64(d, 0), R32(d, 64), R8(d, 96), R8(d, 104), MMA_ARGS64(2));
}
template <int SA> __device__ __forceinline__ void mma_step(float (&d)[64], uint64_t& da, uint64_t& db, int next, int keep) {
    asm volatile(MMA_STEP("m64n128k16", ACC64, "%64", "%65", "%66", "%67", "%68", "%69") : R64(d, 0), MMA_ARGS64(SA));
}
template <int SA> __device__ __forceinline__ void mma_step_c(float (&d)[64], uint64_t& da, uint64_t& db, int next, int keep) {
    asm volatile(MMA_STEP_N("m64n128k16", ACC64, "%64", "%65", "%66", "%67", "%68", "%69", ADD64) : R64(d, 0), MMA_ARGS64(SA));
}
__device__ __forceinline__ void mma_step96(float (&d)[64], uint64_t& da, uint64_t& db, int next, int keep) {
    asm volatile(MMA_STEP("m64n96k16", ACC48, "%48", "%49", "%50", "%51", "%52", "%53") : R32(d, 0), R8(d, 32), R8(d, 40), MMA_ARGS64(254));
}
__device__ __forceinline__ void mma_step_tail(float (&d)[128], uint32_t da, uint32_t b, int keep, bool down) {
    uint32_t db = (b & 0x3FFFF) >> 4 | 256 << 16;
    asm volatile(MMA_STEP_B("m64n256k16", ACC128, "%128", "%129", "%130", "%131", "0x80000040", "%132", "-96")
                 : R64(d, 0), R64(d, 64), "+r"(da), "+r"(db) : "r"(keep), "r"(down ? HI_64B : HI_128B), "r"(down ? 254 : 2) : "memory");
}

__device__ __forceinline__ uint32_t pack_bf16(float lo, float hi) {
    uint32_t r; asm("cvt.rn.bf16x2.f32 %0, %1, %2;" : "=r"(r) : "f"(hi), "f"(lo)); return r;
}
__device__ __forceinline__ float bf_lo(uint32_t v) { return __uint_as_float(v << 16); }
__device__ __forceinline__ float bf_hi(uint32_t v) { return __uint_as_float(v & 0xffff0000u); }
__device__ __forceinline__ float round_bf16(float v) { return bf_lo(pack_bf16(v, 0.f)); }
__device__ __forceinline__ uint32_t mul_bf16x2(uint32_t a, uint32_t b) {
    uint32_t r; asm("mul.rn.bf16x2 %0, %1, %2;" : "=r"(r) : "r"(a), "r"(b)); return r;
}
__device__ __forceinline__ uint32_t sub_bf16x2(uint32_t a, uint32_t b) {
    uint32_t r; asm("sub.rn.bf16x2 %0, %1, %2;" : "=r"(r) : "r"(a), "r"(b)); return r;
}
__device__ __forceinline__ uint32_t mul2_bf16x2(uint32_t a, uint32_t hi, uint32_t lo) {
    uint32_t r; asm("fma.rn.bf16x2 %0, %1, %2, %3;" : "=r"(r) : "r"(a), "r"(hi), "r"(mul_bf16x2(a, lo))); return r;
}
__device__ __forceinline__ float tanh_fast(float x) { float r; asm("tanh.approx.f32 %0, %1;" : "=f"(r) : "f"(x)); return r; }
__device__ __forceinline__ float gelu_twice(float g) {
    return fmaf(g, tanh_fast(fmaf(g * g, 0.044715f * 0.7978845608f, 0.7978845608f) * g), g);
}
__device__ __forceinline__ uint32_t geglu2(uint32_t g2, uint32_t u2) {
    return mul_bf16x2(pack_bf16(gelu_twice(bf_lo(g2)), gelu_twice(bf_hi(g2))), u2);
}
__device__ __forceinline__ uint32_t silu2(float lo, float hi) {
    const uint32_t h = mul_bf16x2(pack_bf16(lo, hi), 0x3e803e80u);
    return pack_bf16(fmaf(bf_lo(h), tanh_fast(bf_lo(h)), bf_lo(h)), fmaf(bf_hi(h), tanh_fast(bf_hi(h)), bf_hi(h)));
}
__device__ __forceinline__ float ex2_fast(float x) { float r; asm("ex2.approx.ftz.f32 %0, %1;" : "=f"(r) : "f"(x)); return r; }
__device__ __forceinline__ void unpack8(uint4 v, float (&f)[8]) {
    f[0] = bf_lo(v.x); f[1] = bf_hi(v.x); f[2] = bf_lo(v.y); f[3] = bf_hi(v.y);
    f[4] = bf_lo(v.z); f[5] = bf_hi(v.z); f[6] = bf_lo(v.w); f[7] = bf_hi(v.w);
}
template <int N> __device__ __forceinline__ void fence_regs(float (&d)[N]) {
#pragma unroll
    for (int i = 0; i < N; i++) asm volatile("" : "+f"(d[i]) :: "memory");
}

__device__ __forceinline__ float rcp_fast(float x) { float r; asm("rcp.approx.ftz.f32 %0, %1;" : "=f"(r) : "f"(x)); return r; }
__device__ __forceinline__ float sqrt_fast(float x) { float r; asm("sqrt.approx.ftz.f32 %0, %1;" : "=f"(r) : "f"(x)); return r; }
__device__ __forceinline__ uint32_t max_bf16x2(uint32_t a, uint32_t b) {
    uint32_t r; asm("max.bf16x2 %0, %1, %2;" : "=r"(r) : "r"(a), "r"(b)); return r;
}
__device__ __forceinline__ uint32_t transpose8(uint32_t a) {
    uint32_t r; asm volatile("movmatrix.sync.aligned.m8n8.trans.b16 %0, %1;" : "=r"(r) : "r"(a)); return r;
}
__device__ __forceinline__ void mma_sync(uint32_t* d, const uint32_t* a, uint32_t b0, uint32_t b1, const uint32_t* c) {
    asm volatile("mma.sync.aligned.m16n8k16.row.col.f32.bf16.bf16.f32 {%0,%1,%2,%3}, {%4,%5,%6,%7}, {%8,%9}, {%10,%11,%12,%13};"
        : "=r"(d[0]), "=r"(d[1]), "=r"(d[2]), "=r"(d[3])
        : "r"(a[0]), "r"(a[1]), "r"(a[2]), "r"(a[3]), "r"(b0), "r"(b1), "r"(c[0]), "r"(c[1]), "r"(c[2]), "r"(c[3]));
}
template <int N> struct Floats {
    float f[N];
    __device__ __forceinline__ Floats() {}
    __device__ __forceinline__ Floats(const uint32_t* p) {
#pragma unroll
        for (int i = 0; i < N; i++) asm("mov.b32 %0, %1;" : "=f"(f[i]) : "r"(p[i]));
    }
    __device__ __forceinline__ void put(uint32_t* p) const {
#pragma unroll
        for (int i = 0; i < N; i++) asm("mov.b32 %0, %1;" : "=r"(p[i]) : "f"(f[i]));
    }
    __device__ __forceinline__ float& operator[](int i) { return f[i]; }
};
__device__ __forceinline__ uint32_t fresh_tid() { uint32_t r; asm volatile("mov.u32 %0, %%tid.x;" : "=r"(r)); return r; }
template <typename T> __device__ __forceinline__ T uniform(T v) { return __shfl_sync(0xffffffffu, v, 0); }

__device__ __forceinline__ uint32_t forecast(uint32_t n0, uint32_t c0, float cycles, uint32_t tag) {
    const uint32_t n = nanos();
    return n + (int)((n - n0) * cycles * rcp_fast((uint32_t)clock() - c0)) & ~3u | tag;
}
__device__ __forceinline__ uint32_t plan_word(uint32_t base, int lane) { return uniform(lds32(base + PLAN_OFF + lane * 4)); }

__device__ __forceinline__ void fold_operands(const Params& prm, uint32_t base, int slot, int mblk, uint32_t tag, int w, int lane) {
    uint4 v[9];
#pragma unroll
    for (int m = 0; m < 9; m++) v[m] = make_uint4(0, 0, 0, 0);
    const float* parts = prm.colsum + (slot * 2 + (lane >> 4)) * 1024 + w * 64 + (lane & 15) * 4;
    const float* const rows = &prm.stats[mblk * 128 + w * 64 + lane * 2].x;
#pragma unroll 1
    for (int spins = 0; spins < (1 << 16); spins++) {
        bool missing = false;
        asm volatile("" : "+l"(parts));
#pragma unroll
        for (int m = 0; m < 9; m++) {
            if (untagged(v[m], tag)) {
                missing = true;
                v[m] = ld_relaxed(m < 8 ? parts + m * 128 : rows);
            }
        }
        if (!missing) break;
    }
    float4 c = make_float4(0.f, 0.f, 0.f, 0.f);
#pragma unroll
    for (int m = 0; m < 8; m++) {
        c.x += __uint_as_float(v[m].x ^ tag); c.y += __uint_as_float(v[m].y ^ tag);
        c.z += __uint_as_float(v[m].z ^ tag); c.w += __uint_as_float(v[m].w ^ tag);
    }
    sts128(base + STAT_OFF + w * 512 + lane * 16, make_uint4(v[8].x ^ tag, v[8].y ^ tag, v[8].z ^ tag, v[8].w ^ tag));
    const uint32_t ca = base + AUX_OFF + w * 8192 + (lane >> 4) * 16384 + (lane & 15) * 8;
#pragma unroll
    for (int r = 0; r < 3; r++) {
        const uint32_t lo = pack_bf16(c.x, c.y), hi = pack_bf16(c.z, c.w);
        sts64f((ca ^ r * 16) + r * 128, __uint_as_float(lo), __uint_as_float(hi));
        c.x -= bf_lo(lo); c.y -= bf_hi(lo); c.z -= bf_lo(hi); c.w -= bf_hi(hi);
    }
    asm volatile("fence.proxy.async.shared::cta;" ::: "memory");
    __syncwarp();
}
__device__ __forceinline__ float2 fold(float (&acc)[128], uint32_t base, int wg) {
    const uint32_t id = fresh_tid(), sp = base + STAT_OFF + (id & 96) * 8 + (id & 28) * 4 + wg * 8;
    const uint32_t sel = id & 2 ? 0x4444 : (id & 1 ? 0x4432 : 0x3232);
    const float2 sa = lds64f(sp), sb = lds64f(sp + 128);
    mma_rank(acc, __byte_perm(__float_as_uint(sa.x), 0, sel), __byte_perm(__float_as_uint(sb.x), 0, sel), desc_b(base + AUX_OFF));
    return make_float2(sa.y, sb.y);
}

__device__ __forceinline__ void tail_gemm(const Params& prm, uint32_t base, uint32_t t0, unsigned epoch, int grp, int warp, int lane) {
    const uint32_t full = base + BAR_OFF, empty = full + 32, sig = full + 192, dep = full + 256, folded = full + 320;
    const uint32_t tag = 1 + (epoch & 1);
    auto plan = [&](uint32_t p, uint32_t word) { return p < 4 ? p * 64 + grp / 2 * 32 + 15 : word >> p % 4 * 8 & 255; };
    auto rows = [&](uint32_t job) { return job / 32 * 2 + grp % 2; };
    if (warp == 8) {
        if (elect_one()) { prefetch_map(&prm.xn); prefetch_map(&prm.a2); prefetch_map(&prm.wd_tail); }
#pragma unroll 1
        for (int p = 0, i = G1_STAGES; p < 8; p++) {
            const bool first = p < 4;
            if (p == 4) mbar_wait_warp(dep + 16, 0);
            const uint32_t job = plan(p, plan_word(base, lane));
#pragma unroll 1
            for (int k = p ? 0 : G1_STAGES; k <= job % 32; k++, i++) {
                if (p == 3 && k % 2 == grp / 2)
                    asm volatile("{\n.reg .pred e;\nelect.sync _|e, 0xffffffff;\n"
                        "@e cp.async.bulk.prefetch.tensor.5d.L2.global [%0, {%2, %2, %1, %2, %3}];\n}"
                        :: "l"(&prm.wd_tail), "r"(k * 8), "r"(0), "r"(grp % 2 * 4) : "memory");
                if (i == 16 || i == 24 || k == 16) mbar_wait_warp(dep + (first ? i & 8 : 24), 0);
                TRACE_S(62, i, 16); TRACE_S(63, i, 4);
                mbar_wait_warp(empty + (i & 3) * 8, ~i >> 2 & 1);
                load_tail(base + (i & 3) * G1_STAGE_BYTES, full + (i & 3) * 8, first ? (p ? &prm.xn : &prm.x) : &prm.a2,
                          first ? &prm.wu_tail : &prm.wd_tail, first ? k * 64 : 0,
                          first ? rows(job) * 64 : (rows(job) * G2_KSTEPS + 16 + k) * 128, grp % 2, first ? k * 2 : k * 8);
            }
        }
        return;
    }
    if (warp == 9) {
        const uint32_t n0 = nanos(), c0 = clock();
#pragma unroll 1
        for (int j = 0; j < 3; j++) {
            flag_wait<true>(prm.flags + (F_LN + j) * 512 + (j < 2 ? lane % 4 * 4 + grp : lane % 16) * 32, epoch * CNT_LN);
            fence_proxy_async();
            __syncwarp();
            if (lane == 0 && j < 2) mbar_arrive(dep + j * 8);
        }
        mbar_wait_warp(sig + 8, 0);
        if (lane == 0) st_relaxed(prm.flags + F_PACE * 512 + 64 + grp, forecast(n0, c0, DUE, tag));
        uint4 v, w;
#pragma unroll 1
        for (int spins = 0; spins < (1 << 19); spins++) {
            v = ld_relaxed(prm.flags + F_PACE * 512 + lane / 2 * 4);
            w = ld_relaxed(prm.flags + F_PACE * 512 + 64);
            if (!__any_sync(0xffffffffu, untagged(v, tag) || untagged(w, tag))) break;
            __nanosleep(256);
        }
        const uint32_t ref = uniform(v.x);
        const int due = min(max((int)((grp & 2 ? w.z : w.x) - ref), -100000), 100000) * 8;
        int late = max(max((int)(v.x - ref), (int)(v.y - ref)), max((int)(v.z - ref), (int)(v.w - ref)));
        late = min(max(max(late, __shfl_xor_sync(0xffffffffu, late, 2)), -100000), 100000) * LATE_SCALE + lane / 4;
        TRACE_PUT(16 + lane / 4, late + (1 << 20));
        int place = 0, n = SHARE_MIN;
#pragma unroll 1
        for (int g = 0; g < 32; g += 4) place += __shfl_sync(0xffffffffu, late, g) > late;
        const bool swap = (__reduce_add_sync(0xffffffffu, place + 1 & 2 ? late : -late) ^ w.x - w.z) >> 31;
        const bool mine = (place + 1 >> 1 & 1 ^ swap) == grp / 2;
#pragma unroll 1
        for (int j = 4 * SHARE_MIN; j < SHARE_SUM; j++) {
            const int most = __reduce_max_sync(0xffffffffu, mine && n < SHARE_MAX ? late : INT_MIN);
            if (j >= SHARE_LOW && due + (j - 38) * SPARE_NS * 8 > most) break;
            if (j == 38) TRACE_PUT(32, most - due + (1 << 20));
            if (most == late) { n++; late -= SHARE_NS * 8; }
        }
        auto first = [](uint32_t bits, int n) { return bits & (1u << min(max(n, 0), 24)) - 1; };
        const uint32_t job = lane / 4 * 32 + n - 1;
        if (mine) st_relaxed(prm.flags + F_SHARE * 512 + rows(job) * 32,
                             epoch << 24 | first(0x2aaaaa, 2 * n) | first(0x104104, 6 * n - 66) | first(0x10410, 6 * n - 90) |
                             first(0x41041, 6 * n - 108));
        if (mine) TRACE_PUT(24 + lane / 4, n);
        sts32(base + PLAN_OFF, __reduce_or_sync(0xffffffffu, mine ? job << place / 2 * 8 : 0));
        if (lane == 0) mbar_arrive(dep + 16);
        flag_wait<true>(prm.flags + F_SECOND * 512 + lane % 16 * 32, epoch * CNT_LN);
        fence_proxy_async();
        __syncwarp();
        if (lane == 0) mbar_arrive(dep + 24);
        return;
    }
    if (warp > 9) {
#pragma unroll 1
        for (int j = 0; j < 8; j++) sts128(base + AUX_OFF + (warp - 10) * 8192 + (j & 4) * 4096 + (j & 3) * 512 + lane * 16, make_uint4(0, 0, 0, 0));
        while ((uint32_t)clock() - t0 < 9000) __nanosleep(256);
        fold_operands(prm, base, 8, grp, tag, warp - 10, lane);
        if (lane) return;
        mbar_arrive(folded);
        if (warp == 11) return;
        TRACE(60);
#pragma unroll 1
        for (int p = 0; p < 8; p++) {
            mbar_wait(sig + p * 8, 0);
            flag_add(prm.flags + (p < 4 ? F_EARLY : F_TAIL2) * 512 + rows(plan(p, lds32(base + PLAN_OFF))) * 32);
            TRACE_S(50, p, 3); TRACE_S(51, p, 7);
        }
        prm.epoch[blockIdx.x * 16] = epoch;
        TRACE_DUMP();
        return;
    }
    asm volatile("setmaxnreg.inc.sync.aligned.u32 %0;" :: "n"(CONSUMER_REGS) : "memory");
    const uint32_t da = desc_a(base + (warp >> 2) * 8192);
    uint4* out = prm.tail;
    float acc[128];
    uint32_t pk[64];
    float2 inv = make_float2(0.f, 0.f);
    int i = 0, last;
    uint32_t peer;
    asm volatile("mapa.shared::cluster.u32 %0, %1, %2;" : "=r"(peer) : "r"(empty), "r"(lane & 1));
    auto release = [&]() {
        if ((threadIdx.x & 126) == 0 && i <= last)
            asm volatile("mbarrier.arrive.shared::cluster.b64 _, [%0];" :: "r"(peer + (i - 1 & 3) * 8) : "memory");
    };
    auto store = [&](int j) {
        asm volatile("st.global.v4.u32 [%0], {%1,%2,%3,%4};" :: "l"(out + j / 2 * 8192 + j % 2 * 256),
                     "r"(pk[4 * j]), "r"(pk[4 * j + 1]), "r"(pk[4 * j + 2]), "r"(pk[4 * j + 3]) : "memory");
    };
    auto step = [&](int k, int left) {
        mbar_wait(full + (i & 3) * 8, i >> 2 & 1);
        TRACE_S(45, warp * 128 + i, 0);
        if (warp >= 4 && left == G1_SKEW) asm volatile("bar.sync 1, 256;" ::: "memory");
        mma_step_tail(acc, da + (i & 3) * (G1_STAGE_BYTES / 16), base + A_BYTES + (i & 3) * G1_STAGE_BYTES, k, i >= 4 * G1_KSTEPS);
        if (warp < 4 && left == 1) asm volatile("bar.arrive 1, 256;" ::: "memory");
    };
    auto drip = [&](int p, int& n) {
        if (n > 0) { store(0); store(1); }
#pragma unroll
        for (int j = 8; j < 64; j++) asm volatile("mov.b32 %0, %1;" : "=r"(pk[j - 8]) : "r"(pk[j]));
        out += 8192;
        __syncwarp();
        if (--n == 0 && lane == 0) mbar_arrive(sig + p * 8 - 8);
    };
#pragma unroll
    for (int j = 0; j < 128; j++) asm volatile("mov.b32 %0, 0;" : "=f"(acc[j]));
#pragma unroll
    for (int j = 0; j < 64; j++) asm volatile("mov.b32 %0, 0;" : "=r"(pk[j]));
#pragma unroll 1
    for (int p = 0; p < 8; p++) {
        step(0, 0);
        i++;
        const uint32_t word = plan_word(base, lane), job = plan(p, word);
        last = __dp4a(word & 0x1f1f1f1fu, 0x01010101u, 4u * G1_KSTEPS);
#pragma unroll 1
        for (int left = job % 32, n = p ? 8 : 0; left > 0; left--) {
            if (i == G1_KSTEPS - 1) { mbar_wait(folded, 0); inv = fold(acc, base, warp >> 2); }
#pragma unroll 1
            do drip(p, n); while (n & 7 >> 31 - __clz(job % 32));
            step(1, left);
            wg_wait<1>();
            release();
            i++;
        }
        wg_wait<0>();
        fence_regs(acc);
        release();
        if (p == 0) {
#pragma unroll
            for (int j = 0; j < 128; j++) acc[j] *= j & 2 ? inv.y : inv.x;
            fence_regs(acc);
        }
        if (warp == 4) TRACE_PUT(46 + p + p / 4 * 3, (uint32_t)clock());
#pragma unroll
        for (int j = 0; j < 64; j++) pk[j] = pack_bf16(acc[2 * j], acc[2 * j + 1]);
        out = prm.tail + p / 4 * NGEMM * 512 + rows(job) * 512 + threadIdx.x;
    }
#pragma unroll
    for (int j = 0; j < 16; j++) store(j);
    __syncwarp();
    TRACE_S(58, warp, 4);
    if (lane == 0) mbar_arrive(sig + 56);
}

__device__ __forceinline__ int gate_col(int t, int nslot) { return t == 2 ? 960 + nslot * 64 : max(t * 1024 - 1536, 0) + nslot * 128; }

struct Role {
    int rank, role, mblk, nslot;
    __device__ __forceinline__ Role() {
        uint32_t id;
        asm volatile("mov.u32 %0, %%ctaid.x;" : "=r"(id));
        const uint32_t cl = id / 2;
        rank = id & 1;
        role = pick(cl < 4, 32 + cl * 8, cl - 8 + max(4u, (cl - 1) * 37 >> 8)) * 2 + rank;
        mblk = role & 15; nslot = role >> 4;
    }
};

__global__ void __cluster_dims__(2, 1, 1) __launch_bounds__(384, 1)
fused_kernel(const __grid_constant__ Params prm) {
    TRACE_GET(c0);
    const uint32_t base = smem_u32(smem_raw) & ~1023u;
    const uint32_t bars = base + BAR_OFF;
    auto full1 = [&](int s) { return bars + s * 8; };
    auto empty1 = [&](int s) { return bars + 32 + s * 8; };
    auto full2 = [&](int s) { return bars + 64 + s * 8; };
    auto empty2 = [&](int s) { return bars + 128 + s * 8; };
    const uint32_t sig_bar = bars + 192, dep_bar = bars + 256, cs_bar = bars + 304, fold_bar = bars + 320, x_bar = bars + 352;
    const uint32_t halo_bar = dep_bar + 32;
    auto stage2 = [&](int q) { return base + q * G2_STAGE_BYTES; };
    const uint32_t aux = base + AUX_OFF;

    asm volatile("{\n.reg .pred p;\nsetp.eq.u32 p, %1, 0;\n@p mbarrier.init.shared::cta.b64 [%0], 1;\n"
        "fence.mbarrier_init.release.cluster;\nbarrier.cluster.arrive.relaxed.aligned;\n}" :: "r"(bars), "r"(threadIdx.x) : "memory");
    const int warp = __shfl_sync(0xffffffffu, threadIdx.x >> 5, 0);
    auto cluster_wait = []() { asm volatile("barrier.cluster.wait.acquire.aligned;" ::: "memory"); };
    if ((warp | (blockIdx.x & NGEMM)) == 8) {
        const Role r;
        asm volatile("{\n.reg .pred e;\nelect.sync _|e, 0xffffffff;\n"
            "@e prefetch.tensormap [%0];\n@e prefetch.tensormap [%1];\n}" :: "l"(&prm.x), "l"(&prm.wg + r.rank) : "memory");
        cluster_wait();
        load_stage1(base, base + A_BYTES + r.rank * 16384, full1(0), &prm.x, &prm.wg + r.rank, &prm.wg + r.rank, 0, r.mblk * 64,
                    r.nslot * 128, r.nslot * 128 + 64, 0, stream_policy());
    } else {
        cluster_wait();
    }
    const uint32_t t0 = clock();
    {
        uint32_t cta;
        asm volatile("mov.u32 %0, %%ctaid.x;" : "=r"(cta));
        if ((warp | (~cta & NGEMM)) == 8) load_tail(base, full1(0), &prm.x, &prm.wu_tail, 0, (cta - NGEMM) * 64, cta & 1, 0);
    }
    asm volatile("{\n.reg .pred e, q;\nelect.sync _|e, 0xffffffff;\nsetp.ne.and.u32 q, %2, 0, e;\n"
        "@q mbarrier.init.shared::cta.b64 [%0], %1;\n@e mbarrier.init.shared::cta.b64 [%0 + 8], %1;\n"
        "@e mbarrier.init.shared::cta.b64 [%0 + 16], %1;\n@e mbarrier.init.shared::cta.b64 [%0 + 24], %1;\n"
        "fence.mbarrier_init.release.cluster;\nbarrier.cluster.arrive.relaxed.aligned;\n}"
        :: "r"(bars + warp * 32), "r"(1 << (0x10fa08 >> warp * 2 & 3)), "r"(warp) : "memory");
    const int lane = threadIdx.x & 31;
    const Role me;
    const int rank = me.rank, role = me.role, mblk = me.mblk, nslot = me.nslot;
    const CUtensorMap* const w0 = &prm.wg + rank;

    unsigned* const flags = prm.flags + mblk * 32;
    if (warp >= 8) {
        asm volatile("setmaxnreg.dec.sync.aligned.u32 %0;" :: "n"(AUX_REGS));
        if (warp == 9) { TRACE_CLEAR(); TRACE_GT(0); TRACE_PUT(1, c0); }
        if ((warp | (~blockIdx.x & NGEMM)) == 8) {
#pragma unroll 1
            for (int i = 1; i < G1_STAGES; i++) {
                if (i == 1) cluster_wait();
                TRACE_S(57, i, 1);
                load_tail(base + i * G1_STAGE_BYTES, full1(i), &prm.x, &prm.wu_tail, i * 64, (blockIdx.x - NGEMM) * 64, blockIdx.x & 1, i * 2);
            }
        } else {
            cluster_wait();
        }
    }

    if (blockIdx.x >= NGEMM) {
        if (warp < 8) cluster_wait();
        const uint32_t seen = __ldcg(prm.epoch + blockIdx.x * 16);
        tail_gemm(prm, base, t0, seen + 1, blockIdx.x - NGEMM, warp, lane);
    } else if (warp == 9) {
        const unsigned epoch = __ldcg(prm.epoch + blockIdx.x * 16 + 2) + 1;
        const uint32_t n0 = nanos(), c1 = clock();
        {
            const __nv_bfloat16* const w = prm.pwu + ((mblk >> 1) * 128 + lane / 2) * DF + gate_col(4, nslot) + 96 + rank * 16 + lane % 2 * 8;
            uint4 v[8];
            float cs[8], f[8];
            mbar_wait(empty1(SUM2_STEP), 0);
#pragma unroll
            for (int j = 0; j < 8; j++) v[j] = __ldg(reinterpret_cast<const uint4*>(w + j * 16 * DF));
            unpack8(v[0], cs);
#pragma unroll
            for (int j = 1; j < 8; j++) {
                unpack8(v[j], f);
#pragma unroll
                for (int d = 0; d < 8; d++) cs[d] += f[d];
            }
#pragma unroll
            for (int d = 0; d < 4; d++)
                cs[d] = (lane & 16 ? cs[d + 4] : cs[d]) + __shfl_xor_sync(0xffffffffu, lane & 16 ? cs[d] : cs[d + 4], 16);
#pragma unroll
            for (int d = 0; d < 2; d++) {
                cs[d] = (lane & 8 ? cs[d + 2] : cs[d]) + __shfl_xor_sync(0xffffffffu, lane & 8 ? cs[d] : cs[d + 2], 8);
                cs[d] += __shfl_xor_sync(0xffffffffu, cs[d], 4);
                cs[d] += __shfl_xor_sync(0xffffffffu, cs[d], 2);
            }
            if (!(lane & 6))
                st_tagged(prm.colsum + (16 + nslot / 4) * 1024 + (mblk >> 1) * 128 + nslot % 4 * 32 + rank * 16 + lane % 2 * 8 + (lane >> 3) * 2,
                          cs[0], cs[1], 1 + (epoch & 1));
            TRACE(61);
        }
        if (lane == 0) {
            mbar_wait(sig_bar, 0);
            TRACE(11);
            flag_add(flags + F_LN * 512);
            TRACE(42);
            flag_wait(flags + F_LN * 512, epoch * CNT_LN);
            fence_proxy_async();
            mbar_arrive(dep_bar);
            mbar_wait(sig_bar + 56, 0);
            flag_add(flags + F_LN2 * 512);
            flag_wait(flags + F_LN2 * 512, epoch * CNT_LN);
            fence_proxy_async();
            mbar_arrive(dep_bar + 40);
            TRACE(59);
            prm.epoch[blockIdx.x * 16 + 2] = epoch;
#pragma unroll 1
            for (int p = 3; p < 7; p++) {
                mbar_wait(sig_bar + (p == 3 ? 16 : p * 8), 0);
                TRACE_S(37, p, 4);
                flag_add(flags + (p - (p < F_EARLY)) * 512);
                TRACE_S(43, p, 4);
                if (p == 3 && rank == 0) {
                    mbar_wait(sig_bar + 24, 0);
                    st_relaxed(prm.flags + F_PACE * 512 + mblk * 4 + nslot, forecast(n0, c1, REST, 1 + (epoch & 1)));
                }
            }
        }
    } else if (warp < 8) {
        asm volatile("setmaxnreg.inc.sync.aligned.u32 %0;" :: "n"(CONSUMER_REGS));
        const int wg = __shfl_sync(0xffffffffu, threadIdx.x >> 7, 0);
        const int cw = threadIdx.x >> 5;
        const int tid = threadIdx.x & 127;
        int spins = 1 << 18;
        float acc[128];
        uint32_t pk[64];
#pragma unroll
        for (int i = 0; i < 64; i++) asm volatile("mov.b32 %0, 0;" : "=r"(pk[i]));
#pragma unroll
        for (int i = 0; i < 128; i++) asm volatile("mov.b32 %0, 0;" : "=f"(acc[i]));
        cluster_wait();

        auto row0 = [&](uint32_t id) { return mblk * 128 + (id & 96) + wg; };
        __nv_bfloat16* optr = prm.pxn + (mblk * 128 + nslot * 16 + cw * 2) * DM + lane * 8;
        uint64_t da = desc_a(base + wg * 8192) | (uint64_t)prm.hi[0] << 32, db = desc_b(base + A_BYTES) | (uint64_t)prm.hi[1] << 32;
        auto next1 = [](int s) { return ((s + 1) % G1_STAGES - s) * G1_STAGE_BYTES; };
        auto next2 = [](int q) { return ((q + 1) % G2_STAGES - q) * G2_STAGE_BYTES; };
        uint32_t peer_bars;
        asm volatile("mapa.shared::cluster.u32 %0, %1, %2;" : "=r"(peer_bars) : "r"(bars), "r"(tid & 1));
        if (tid >= 2) peer_bars = 0;
        auto release = [&](uint32_t bar) {
            if (peer_bars) asm volatile("mbarrier.arrive.shared::cluster.b64 _, [%0];" :: "r"(peer_bars + (bar - bars)) : "memory");
        };
        auto up = [](int i) { return 32 + (i & 24) + (i & 3) * 2 + (i >> 2 & 1); };
        auto store_pk = [&](__nv_bfloat16* p, int j) {
            asm volatile("st.global.v4.u32 [%0], {%1,%2,%3,%4};"
                         :: "l"(p), "r"(pk[4 * j]), "r"(pk[4 * j + 1]), "r"(pk[4 * j + 2]), "r"(pk[4 * j + 3]) : "memory");
        };
        auto chunk_geglu = [&](int j) {
#pragma unroll
            for (int i = 4 * j; i < 4 * j + 4; i++) pk[i] = geglu2(pk[i], pk[up(i)]);
            store_pk(optr + (j & 1) * 256 + (j & 2) * 1024 + (j & 4) * 2048, j);
        };
        auto signal_stores = [&](int p) { __syncwarp(); if (lane == 0) mbar_arrive(sig_bar + p * 8); };

        auto chunk_ln = [&](int k) {
            Floats<6> mo(pk + 32);
            if (k == 0) {
                const uint4* xp = reinterpret_cast<const uint4*>(prm.px + (optr - prm.pxn));
                pk[38] = __ldcg(prm.epoch + blockIdx.x * 16 + 2);
#pragma unroll
                for (int i = 0; i < 8; i++) {
                    const uint4 v = ldg_stream(xp + i * 32, stream_policy());
                    pk[4 * i] = v.x; pk[4 * i + 1] = v.y; pk[4 * i + 2] = v.z; pk[4 * i + 3] = v.w;
                }
            } else if (k >= LN_STEP && k < LN_STEP + 3) {
                if (k == LN_STEP) {
                    mo[0] = bf_lo(uniform(pk[0])); mo[1] = bf_lo(uniform(pk[16]));
                    mo[2] = mo[3] = mo[4] = mo[5] = 0.f;
                }
#pragma unroll
                for (int i = (k - LN_STEP) * 11; i < (k - LN_STEP) * 11 + 11 && i < 32; i++) {
                    const int r = i & 1;
                    const uint32_t w = pk[r * 16 + i / 2];
                    const float lo = bf_lo(w) - mo[r], hi = bf_hi(w) - mo[r];
                    mo[2 + r] += lo + hi;
                    mo[4 + r] = fmaf(hi, hi, fmaf(lo, lo, mo[4 + r]));
                }
                mo.put(pk + 32);
            } else if (k == LN_STEP + 3) {
                const bool second = lane & 16;
                float m1 = (second ? mo[3] : mo[2]) + __shfl_xor_sync(0xffffffffu, second ? mo[2] : mo[3], 16);
                float m2 = (second ? mo[5] : mo[4]) + __shfl_xor_sync(0xffffffffu, second ? mo[4] : mo[5], 16);
#pragma unroll
                for (int o = 8; o > 0; o >>= 1) {
                    m1 += __shfl_xor_sync(0xffffffffu, m1, o);
                    m2 += __shfl_xor_sync(0xffffffffu, m2, o);
                }
                m1 *= 1.f / DM;
                const float var = fmaxf(fmaf(-m1, m1, m2 * (1.f / DM)), 0.f);
                const float mean = round_bf16((second ? mo[1] : mo[0]) + m1);
                const float inv = rcp_fast(round_bf16(sqrt_fast(round_bf16(round_bf16(var) + 1e-5f))));
                if ((lane & 15) == 0) st_tagged(prm.stats + (uint32_t)(optr - prm.pxn) / DM + second, -mean, inv, 2 - (pk[38] & 1));
                const uint32_t split = pack_bf16(inv - round_bf16(inv), inv);
#pragma unroll
                for (int r = 0; r < 2; r++) {
                    const uint32_t f = __shfl_sync(0xffffffffu, split, r * 16);
                    pk[32 + 3 * r] = __byte_perm(__shfl_sync(0xffffffffu, __float_as_uint(mean), r * 16), 0, 0x3232);
                    pk[33 + 3 * r] = __byte_perm(f, 0, 0x3232);
                    pk[34 + 3 * r] = __byte_perm(f, 0, 0x1010);
                }
            } else if (k >= LN_STEP + 4 && k < LN_STEP + 8) {
#pragma unroll
                for (int i = k - LN_STEP - 4; i < 8; i += 4) {
                    const uint32_t* n = pk + 32 + i / 4 * 3;
#pragma unroll
                    for (int j = 4 * i; j < 4 * i + 4; j++) pk[j] = mul2_bf16x2(sub_bf16x2(pk[j], n[0]), n[1], n[2]);
                    store_pk(optr + i * 256, i);
                }
                if (k == LN_STEP + 5 || k == LN_STEP + 7) signal_stores(k == LN_STEP + 5 ? 0 : 7);
            } else if (k == FOLD_STEP) {
                mbar_wait(fold_bar, 0, spins);
                const float2 inv = fold(acc, base, wg);
                mo[0] = inv.x; mo[1] = inv.y;
                mo.put(pk + 32);
            }
        };

        auto halo = [&]() { const uint32_t id = fresh_tid(); return aux + (id & 96) * 128 + (id & 128) * 16 + (id & 31) * 4; };
        auto put = [&](uint32_t a, uint32_t v0, uint32_t v1) {
            asm volatile("st.shared.u32 [%0], %1;\nst.shared.u32 [%0 + 128], %2;" :: "r"(a + HALO_BYTES), "r"(v0), "r"(v1) : "memory");
        };
        auto get = [&](uint32_t a, uint32_t& v0, uint32_t& v1) {
            asm volatile("ld.shared.u32 %0, [%2];\nld.shared.u32 %1, [%2 + 128];" : "=r"(v0), "=r"(v1) : "r"(a) : "memory");
        };
        auto publish = [&](int p) { asm volatile("fence.proxy.async.shared::cta;" ::: "memory"); signal_stores(p); };
        const uint32_t zero[4] = {0, 0, 0, 0};
        auto meet = [&](int n, int k, uint32_t id) {
            if (n == 15 - MEET)
                asm volatile("{\n.reg .b32 c;\nmov.u32 c, %%clock;\nbar.arrive %1, 256;\nlop3.b32 %0, %0, c, 1, 0x70;\n}"
                             : "+r"(peer_bars) : "r"(2 + id / 128) : "memory");
            if (n == 15) {
                asm volatile("{\n.reg .b32 c;\nmov.u32 c, %%clock;\nbar.sync %1, 256;\nlop3.b32 %0, %0, c, 1, 0x70;\n}"
                             : "+r"(peer_bars) : "r"(3 - id / 128) : "memory");
                mma_step(acc, da, db, next1(k & 3), k);
                asm volatile("// batch step");
            }
        };
        auto mix_qk = [&]() {
            uint32_t c[2][4];
            const uint32_t a = halo(), id = fresh_tid();
            mbar_wait(halo_bar, 0, spins);
#pragma unroll
            for (int n = 0; n < 16; n++) {
                const int b = 1 - n / 8, h = (n & 4) / 2 + n % 2, j = n / 2 % 2;
                uint32_t* const kq = pk + 32 + 8 * h + 4 * j;
                uint32_t* const q = pk + 8 * h + 4 * b;
                mma_sync(j ? q : c[n % 2], kq, q[2 * j], q[2 * j + 1], j ? c[n % 2] : zero);
                if (b) get(a + (h * 2 + j) * 256, kq[1], kq[3]);
                meet(n, QK_STEP, id);
            }
        };
        auto chunk_qk = [&](int k) {
            constexpr float LOG2E = 1.4426950408889634f;
            uint32_t* const l = pk + 32;
            Floats<16> e(pk);
            if (k == KEY_STEP) {
                const uint32_t a = halo();
#pragma unroll
                for (int i = 0; i < 8; i++) put(a + i * 256, pk[33 + 4 * i], pk[35 + 4 * i]);
                publish(1);
            } else if (k == QK_STEP + 1) {
                const uint32_t id = fresh_tid();
                const bool u0 = id % 32 / 4 > id % 4 * 2, u1 = id % 32 / 4 > id % 4 * 2 + 1;
                const uint32_t gone = row0(id) < 2 ? (u0 ? 0xffffu : 0u) | (u1 ? 0xffff0000u : 0u) : 0u;
#pragma unroll
                for (int n = 0; n < 8; n++) {
                    const int b = n % 2;
                    const uint32_t* const c = pk + 4 * n;
                    uint32_t v = pack_bf16(__uint_as_float(pick(u0, c[2 - 2 * b], c[2 * b])), __uint_as_float(pick(u1, c[3 - 2 * b], c[1 + 2 * b])));
                    v = mul2_bf16x2(v, 0x3e353e35u, 0x379e379eu);
                    if (!b) v = v & ~gone | 0xce6ece6eu & gone;
                    l[n] = transpose8(v);
                }
            } else if (k == QK_STEP + 2) {
#pragma unroll
                for (int h = 0; h < 4; h++) {
                    uint32_t m = max_bf16x2(__byte_perm(l[2 * h], l[2 * h + 1], 0x5410), __byte_perm(l[2 * h], l[2 * h + 1], 0x7632));
                    m = max_bf16x2(m, __shfl_xor_sync(0xffffffffu, m, 1));
                    m = max_bf16x2(m, __shfl_xor_sync(0xffffffffu, m, 2));
#pragma unroll
                    for (int n = 2 * h; n < 2 * h + 2; n++) {
                        const float f = -LOG2E * (n % 2 ? bf_hi(m) : bf_lo(m));
                        e[2 * n] = ex2_fast(fmaf(bf_lo(l[n]), LOG2E, f));
                        e[2 * n + 1] = ex2_fast(fmaf(bf_hi(l[n]), LOG2E, f));
                    }
                }
                e.put(pk);
            } else if (k == QK_STEP + 3) {
                uint32_t p[8];
#pragma unroll
                for (int n = 0; n < 8; n++) {
                    float sum = e[2 * n] + e[2 * n + 1];
                    sum += __shfl_xor_sync(0xffffffffu, sum, 1);
                    sum += __shfl_xor_sync(0xffffffffu, sum, 2);
                    const float r = rcp_fast(sum);
                    p[n] = pack_bf16(e[2 * n] * r, e[2 * n + 1] * r);
                }
                const uint32_t a = aux + 5 * HALO_BYTES + fresh_tid() * 16;
                sts128(a, make_uint4(p[0], p[1], p[2], p[3]));
                sts128(a + 4096, make_uint4(p[4], p[5], p[6], p[7]));
            }
        };
        auto values = [&](int h) { return pk + (h & 2) * 16 + (h & 1) * 8; };
        auto mix_pv = [&]() {
            uint32_t lo[8], hi[8];
            const uint32_t id = fresh_tid();
            const uint32_t keep = (id % 4 * 2 > id % 32 / 4 ? 0xffffu : 0u) | (id % 4 * 2 + 1 > id % 32 / 4 ? 0xffff0000u : 0u);
            const uint4 p0 = lds128(aux + 5 * HALO_BYTES + id * 16), p1 = lds128(aux + 6 * HALO_BYTES + id * 16);
            const uint32_t p[8] = {p0.x, p0.y, p0.z, p0.w, p1.x, p1.y, p1.z, p1.w};
#pragma unroll
            for (int n = 0; n < 8; n++)
                asm volatile("and.b32 %0, %2, %3;\nand.b32 %1, %2, %4;" : "=r"(lo[n]), "=r"(hi[n])
                             : "r"(p[n]), "r"(n % 2 ? keep : ~keep), "r"(n % 2 ? ~keep : keep));
            mbar_wait(halo_bar, 1, spins);
#pragma unroll
            for (int n = 0; n < 16; n++) {
                const int i = (n & 8) / 2 + (n & 2) + (n & 4) / 4;
                mma_sync(pk + 4 * (n ^ 4), pk + 4 * (n ^ 4), lo[i], hi[i], zero);
                meet(n, PV_STEP, id);
            }
        };
        auto chunk_pv = [&](int k) {
            if (k == VAL_STEP || k == VAL_STEP + 1) {
                const uint32_t a = halo();
#pragma unroll
                for (int h = (k - VAL_STEP) * 2; h < (k - VAL_STEP + 1) * 2; h++) {
                    uint32_t* const w = values(h);
                    uint32_t v[8];
#pragma unroll
                    for (int i = 0; i < 8; i++) v[i] = transpose8(w[h < 2 ? (i & 1) + (i & 2) * 2 + (i & 4) / 2 : (i & 1) * 2 + (i & 2) / 2 + (i & 4)]);
#pragma unroll
                    for (int i = 0; i < 8; i++) w[i] = v[i];
                    put(a + h * 512, w[2], w[3]);
                    put(a + h * 512 + 256, w[6], w[7]);
                }
                if (k > VAL_STEP) publish(3);
            } else if (k == PV_STEP - 1) {
                const uint32_t a = halo(), id = fresh_tid();
                optr = prm.pa2 + (mblk * K2 + nslot * 128) * 128 + (id & 224) * 32 + id % 4 * 128 + (id >> 2 & 7 ^ id % 4 * 2) * 8;
                mbar_wait(halo_bar, 1, spins);
#pragma unroll
                for (int n = 0; n < 8; n++) {
                    uint32_t* const w = values(n / 2) + n % 2 * 4;
                    w[16] = w[0]; w[17] = w[1];
                    get(a + n * 256, w[18], w[19]);
                }
            } else if (k > PV_STEP && k <= PV_STEP + OUT_STEPS) {
#pragma unroll
                for (int n = 0; n < 8; n++) {
                    if (n * OUT_STEPS / 8 != k - PV_STEP - 1) continue;
                    const int j = n ^ n >> 1 & 1;
                    if (n % 2) optr = reinterpret_cast<__nv_bfloat16*>(reinterpret_cast<uintptr_t>(optr) ^ 16);
                    Floats<15> c(pk + j / 2 * 16 + j % 2);
                    asm volatile("st.global.v4.u32 [%0], {%1,%2,%3,%4};"
                                 :: "l"(optr + (~j & 2) * 256 + j % 2 * 64 + j / 4 * 8192), "r"(pack_bf16(c[0], c[2])),
                                    "r"(pack_bf16(c[4], c[6])), "r"(pack_bf16(c[8], c[10])), "r"(pack_bf16(c[12], c[14])) : "memory");
                }
                if (k == PV_STEP + OUT_STEPS) signal_stores(4);
            }
        };

        TRACE_SLOT(tile_slot, 16 + wg * 8);
#pragma unroll 1
        for (int t = 0; t < G1_TILES; t++) {
#pragma unroll
            for (int k = 0; k < G1_KSTEPS; k++) {
                const int s = k & 3;
                if (k == 0) asm volatile("" : "+r"(t));
                TRACE_STEP(t, k, 0);
                mbar_wait(full1(s), (k >> 2) & 1, spins);
                if (k == 0) TRACE_S(12, t, 0);
                TRACE_STEP(t, k, 1);
                if (wg == 1 && k == G1_KSTEPS - G1_SKEW) asm volatile("bar.sync 1, 256;" ::: "memory");
                if (k == PV_STEP && t == 3) mix_pv();
                else if (k == QK_STEP && t == 2) mix_qk();
                else if (t == G1_TILES - 1) mma_step224(acc, da, db, next1(s), k);
                else mma_step(acc, da, db, next1(s), k);
                if (wg == 0 && k == G1_KSTEPS - 1) asm volatile("bar.arrive 1, 256;" ::: "memory");
                wg_wait<1>();
                if (k > 0) release(empty1((k - 1) & 3));
                TRACE_STEP(t, k, 2);
                if (t == 0) chunk_ln(k);
                if (k >= 1 && k <= 8 && ((k < HALF_STEP || k > HALF_STEP + 3 ? 0x12 : 0x1a) >> t & 1)) {
                    chunk_geglu(k < HALF_STEP ? k - 1 : (k > HALF_STEP + 3 ? k - 5 : k - HALF_STEP + 4));
                    if (k == 8 && t != 3) signal_stores(t + 1);
                }
                if (t == 2) chunk_qk(k);
                if (t == 3) chunk_pv(k);
                if (k == PV_STEP + OUT_STEPS) {
                    const uint32_t id = fresh_tid();
                    optr = prm.pa2 + (mblk * K2 + DM + gate_col(t, nslot)) * 128 + (id & 128) * 32 + (id & 96) * 16 + (id & 31 ^ id >> 3 & 3) * 8;
                    asm volatile("" : "+l"(optr));
                }
            }
            wg_wait<0>();
            fence_regs(acc);
            release(empty1(3));
            if (t == 0) {
                Floats<2> inv(pk + 32);
#pragma unroll
                for (int i = 0; i < 128; i++) acc[i] *= inv[i / 2 % 2];
                fence_regs(acc);
            }
#pragma unroll
            for (int i = 0; i < 64; i++) {
                const int e = i < 32 ? (i & ~7) * 2 + (i & 3) * 4 + (i & 4) / 2 : i * 2;
                pk[i] = pack_bf16(acc[e], acc[e + 1]);
            }
            TRACE_NEXT(tile_slot);
        }

        float accd[64], accs[64];
        da = (uint32_t)da | (uint64_t)prm.hi[2] << 32;
#pragma unroll
        for (int i = 0; i < 64; i++) accd[i] = 0.f;
#pragma unroll
        for (int u = 0; u < G2_HEAD; u++) {
            const int q = u % G2_STAGES;
            TRACE_STEP(5, u, 0);
            mbar_wait(full2(q), (u / G2_STAGES) & 1, spins);
            TRACE_STEP(5, u, 1);
            if (u % 2) mma_step_c<254>(accd, da, db, next2(q), u);
            else mma_step<254>(accd, da, db, next2(q), u);
            wg_wait<1>();
            if (u > 0) release(empty2((u - 1) % G2_STAGES));
            TRACE_STEP(5, u, 2);
            if (u == UP_STEP) {
#pragma unroll
                for (int i = 0; i < 2; i++) {
                    const uint4 v = ldg_stream(prm.tail + role * 512 + i * 256 + threadIdx.x, stream_policy());
                    pk[56 + 4 * i] = v.x; pk[57 + 4 * i] = v.y; pk[58 + 4 * i] = v.z; pk[59 + 4 * i] = v.w;
                }
            }
            if (u >= 1) {
                const int j = (u - 1) / 2;
#pragma unroll
                for (int i = 2 * u - 2; i < 2 * u; i++) pk[i] = geglu2(pk[i], pk[up(i)]);
                if (u % 2 == 0) store_pk(optr + (j & 1) * 256 + (j & 2) * 1024 + (j & 4) * 2048, j);
            }
            if (u == G2_HEAD - 1) signal_stores(6);
        }
        auto down = [&](int q, uint32_t phase, bool narrow, bool busy = false) {
            mbar_wait(full2(q), phase, spins);
            if (narrow) mma_step96(accd, da, db, next2(q), 1);
            else if (busy) mma_step_c<254>(accd, da, db, next2(q), 1);
            else mma_step<254>(accd, da, db, next2(q), 1);
            wg_wait<1>();
            release(empty2((q + G2_STAGES - 1) % G2_STAGES));
        };
        uint32_t shared_steps = plan_word(base, lane);
        down(5, 0, false);
#pragma unroll 1
        for (uint32_t r = 3; r < 9; r++, shared_steps >>= G2_STAGES) {
#pragma unroll
            for (int q = 0; q < G2_STAGES; q++) down(q, r & 1, shared_steps >> q & 1);
        }
        down(0, 1, false);
        down(1, 1, false, true);
        TRACE_NEXT(tile_slot);
#pragma unroll
        for (int i = 0; i < 64; i++) accs[i] = 0.f;
        da = (uint32_t)da | (uint64_t)prm.hi[3] << 32;
        uint32_t gk[32], xr[32];
        const uint32_t xs = aux + cw * 2048;
        const uint32_t xrow = xs + ((lane & 7) + ((lane >> 3) & 1) * 8) * 128;
        auto xaddr = [&](int j) { return xrow + (j >> 2) * 16384 + (((((j & 3) * 2) + (lane >> 4)) ^ (lane & 7)) << 4); };
#pragma unroll
        for (int u = G2_DSTEPS; u < G2_KSTEPS; u++) {
            const int q = u % G2_STAGES, v = u - G2_DSTEPS;
            mbar_wait(full2(q), (u / G2_STAGES) & 1, spins);
            if (wg == 1 && u == G2_KSTEPS - G2_SKEW) asm volatile("bar.sync 1, 256;" ::: "memory");
            if (u % 2) mma_step_c<2>(accs, da, db, next2(q), v);
            else mma_step<2>(accs, da, db, next2(q), v);
            if (wg == 0 && u == G2_KSTEPS - 1) asm volatile("bar.arrive 1, 256;" ::: "memory");
            if (v == TAIL_STEP) {
                TRACE_S(32, wg, 0);
                mbar_wait(dep_bar + 24, 0, spins);
                TRACE_S(33, wg, 0);
#pragma unroll
                for (int i = 0; i < 2; i++) {
                    const uint4 w = ldg_stream(prm.tail + (NGEMM + role) * 512 + i * 256 + threadIdx.x, stream_policy());
                    gk[24 + 4 * i] = w.x; gk[25 + 4 * i] = w.y; gk[26 + 4 * i] = w.z; gk[27 + 4 * i] = w.w;
                }
            }
#pragma unroll
            for (int i = 0; i < 32; i++) {
                if (v == (i < 24 ? i / 4 + 1 : TAIL_STEP + i / 4 - 3))
                    gk[i] = i < 24 ? silu2(accd[2 * i], accd[2 * i + 1])
                                   : silu2(accd[2 * i] + bf_lo(gk[i]), accd[2 * i + 1] + bf_hi(gk[i]));
            }
            if (v == XREAD_STEP) mbar_wait(x_bar, 0, spins);
            if (v >= XREAD_STEP && v < XREAD_STEP + 4) {
#pragma unroll
                for (int j = 2 * (v - XREAD_STEP); j < 2 * (v - XREAD_STEP + 1); j++)
                    asm volatile("ldmatrix.sync.aligned.m8n8.x4.shared.b16 {%0,%1,%2,%3}, [%4];"
                                 : "=r"(xr[4 * j]), "=r"(xr[4 * j + 1]), "=r"(xr[4 * j + 2]), "=r"(xr[4 * j + 3])
                                 : "r"(xaddr(j)) : "memory");
            }
            wg_wait<1>();
            if (v == 0) fence_regs(accd);
            if (u - 1 + G2_STAGES < G2_KSTEPS) release(empty2((u - 1) % G2_STAGES));
        }
        __nv_bfloat16* po = prm.pout + (row0(fresh_tid()) + (lane >> 3) * 2) * DM + nslot * 128 + 64 + (lane & 7) * 8;
        uint32_t so = xs + 16384 + (lane >> 3) * 128 + (((lane & 7) ^ (lane >> 3)) << 4);
        const int c0 = uniform(nslot * 128), c1 = uniform(row0(fresh_tid()) >> 1);
        const uint32_t xu = uniform(xs);
        asm volatile("" : "+l"(po), "+r"(so));
        wg_wait<0>();
        fence_regs(accs);
        TRACE_NEXT(tile_slot);
        TRACE_END();
#pragma unroll
        for (int j = 0; j < 8; j++) {
            uint32_t r[4];
#pragma unroll
            for (int i = 0; i < 4; i++) {
                const int e = j * 4 + i;
                asm("fma.rn.bf16x2 %0, %1, %2, %3;" : "=r"(r[i]) : "r"(pack_bf16(accs[2 * e], accs[2 * e + 1])), "r"(gk[e]), "r"(xr[e]));
            }
            asm volatile("stmatrix.sync.aligned.m8n8.x4.shared.b16 [%0], {%1,%2,%3,%4};"
                         :: "r"(xaddr(j)), "r"(r[0]), "r"(r[1]), "r"(r[2]), "r"(r[3]) : "memory");
            if (j == 3)
                asm volatile("{\n.reg .pred e;\nfence.proxy.async.shared::cta;\nbar.warp.sync 0xffffffff;\nelect.sync _|e, 0xffffffff;\n"
                    "@e cp.async.bulk.tensor.3d.global.shared::cta.bulk_group [%0, {%2, %3, %4}], [%1];\n}"
                    :: "l"(&prm.out), "r"(xu), "r"(c0), "r"(c1), "r"(wg) : "memory");
        }
        __syncwarp();
#pragma unroll
        for (int i = 0; i < 4; i++) {
            const uint4 v = lds128((so ^ (i & 1) * 64) + i * 512);
            asm volatile("st.global.v4.u32 [%0], {%1,%2,%3,%4};" :: "l"(po + i * 8 * DM), "r"(v.x), "r"(v.y), "r"(v.z), "r"(v.w) : "memory");
        }
        asm volatile("cp.async.bulk.commit_group;\ncp.async.bulk.wait_group.read 0;" ::: "memory");
        TRACE_LITE(10, clock());
        if (tid == 0) { TRACE_NEXT(tile_slot); if (wg == 1) TRACE_GT(13); TRACE_DUMP(); }
    } else if (warp > 9) {
        const int w = warp - 10;
        const unsigned epoch = __ldcg(prm.epoch + blockIdx.x * 16 + w) + 1;
        const uint32_t tag = 1 + (epoch & 1);
        TRACE_LITE(8, t0);
        const uint32_t at = (w ? SUM_LOAD1 : SUM_LOAD0) >> nslot * 4 & 15;
        mbar_wait(empty1(at & 3), 0);
        mbar_wait(empty1(at & 3), at >> 3);
        if (elect_one()) {
            mbar_expect_tx(cs_bar + w * 8, 16384);
            asm volatile("cp.async.bulk.tensor.2d.shared::cluster.global.mbarrier::complete_tx::bytes [%0], [%1, {%3, %5}], [%2];\n"
                "cp.async.bulk.tensor.2d.shared::cluster.global.mbarrier::complete_tx::bytes [%0 + 8192], [%1, {%4, %5}], [%2];"
                :: "r"(aux + w * 16384), "l"(w0), "r"(cs_bar + w * 8), "r"(nslot * 128), "r"(nslot * 128 + 64),
                   "r"(((mblk & ~1) + w) * 64) : "memory");
        }
        float cs[8];
#pragma unroll
        for (int d = 0; d < 8; d++) cs[d] = 0.f;
        const uint32_t wa = aux + w * 8192 + (lane >> 3) * 128 + (((lane & 7) ^ (lane >> 3)) << 4);
        uint4 v[8];
        auto fetch = [&](int h, uint32_t off) {
#pragma unroll
            for (int j = 0; j < 4; j++) v[h * 4 + j] = lds128((wa ^ (j & 1) * 64) + off + h * 2048 + j * 512);
        };
        auto add = [&](int h) {
#pragma unroll
            for (int j = 0; j < 4; j++) {
                float f[8];
                unpack8(v[h * 4 + j], f);
#pragma unroll
                for (int d = 0; d < 8; d++) cs[d] += f[d];
            }
        };
        mbar_wait(empty1(SUM_STEP & 3), 0);
        mbar_wait(empty1(SUM_STEP & 3), SUM_STEP >> 3);
        mbar_wait(cs_bar, 0);
        fetch(0, 0);
#pragma unroll 1
        for (int i = 0; i < 4; i++) {
            fetch(1, (i >> 1) * 16384 + (i & 1) * 4096);
            add(0);
            if (i == 1) mbar_wait(cs_bar + 8, 0);
            fetch(0, (i + 1 & 2) * 8192 + (~i & 1) * 4096);
            add(1);
        }
#pragma unroll
        for (int d = 0; d < 4; d++)
            cs[d] = (lane & 16 ? cs[d + 4] : cs[d]) + __shfl_xor_sync(0xffffffffu, lane & 16 ? cs[d] : cs[d + 4], 16);
#pragma unroll
        for (int d = 0; d < 2; d++)
            cs[d] = (lane & 8 ? cs[d + 2] : cs[d]) + __shfl_xor_sync(0xffffffffu, lane & 8 ? cs[d] : cs[d + 2], 8);
        st_tagged(prm.colsum + (nslot * 2 + rank) * 1024 + (mblk >> 1) * 128 + w * 64 + (lane & 7) * 8 + (lane >> 3) * 2,
                  cs[0], cs[1], tag);

        fold_operands(prm, base, nslot, mblk, tag, w, lane);
        if (lane == 0) {
            mbar_arrive(fold_bar);
            prm.epoch[blockIdx.x * 16 + w] = epoch;
            if (w == 0) {
                TRACE(35);
#pragma unroll 1
                for (uint32_t j = 0, n = 1 << 24; j < 4; n = (CNT_EARLY | CNT_LATE << 8 | 1 << 16) >> j * 8 & 255, j++) {
                    mbar_wait(sig_bar + (0xa0302820u >> j * 8 & 255), 0);
                    const uint32_t v = flag_wait(flags + (F_SHARE + j) * 512, epoch * n);
                    fence_proxy_async();
                    if (j) mbar_arrive(dep_bar + j * 8);
                    else sts32(base + PLAN_OFF, v & 0xffffff);
                }
            } else {
#pragma unroll 1
                for (int j = 0; j < 2; j++) {
                    uint8_t* const h = prm.halo + (j * NGEMM + role) * HALO_BYTES;
                    unsigned* const f = prm.flags + F_HALO * 512 + role * 32;
                    mbar_wait(sig_bar + 8 + j * 16, 0);
                    TRACE_S(38, j, 0); TRACE_S(9, j, 1);
                    asm volatile("cp.async.bulk.global.shared::cta.bulk_group [%0], [%1], %2;\n"
                        "cp.async.bulk.commit_group;\ncp.async.bulk.wait_group 0;"
                        :: "l"(h + HALO_BYTES), "r"(aux + 4 * HALO_BYTES), "n"(HALO_BYTES) : "memory");
                    fence_proxy_async();
                    TRACE_S(39, j, 0); TRACE_S(10, j, 1);
                    flag_add(f);
                    TRACE_S(40, j, 0); TRACE_S(34, j, 1);
                    if (mblk) flag_wait(f - 32, epoch * 2 - 1 + j);
                    fence_proxy_async();
                    TRACE_S(41, j, 0); TRACE_S(36, j, 1);
                    mbar_expect_tx(halo_bar, HALO_BYTES);
                    asm volatile("cp.async.bulk.shared::cluster.global.mbarrier::complete_tx::bytes [%0], [%1], %2, [%3];"
                        :: "r"(aux), "l"(mblk ? h : prm.halo), "n"(HALO_BYTES), "r"(halo_bar) : "memory");
                }
            }
        }
    } else {
#pragma unroll 1
        for (int k = 1; k < G1_STAGES; k++) {
            const uint32_t sa = base + k * G1_STAGE_BYTES;
            while ((uint32_t)clock() - t0 < (k == 3 ? PACE3 : PACE1 + (k - 1) * (PACE2 - PACE1))) {}
            load_stage1(sa, sa + A_BYTES + rank * 16384, full1(k), &prm.x, w0, w0, k * 64, mblk * 64, nslot * 128,
                        nslot * 128 + 64, 0, stream_policy());
        }
        if (elect_one()) {
            prefetch_map(&prm.xn); prefetch_map(&prm.wqkv);
            prefetch_map(&prm.a2); prefetch_map(&prm.wo); prefetch_map(&prm.wd); prefetch_map(&prm.out);
        }
        uint32_t ph = 0;
#pragma unroll 1
        for (int t = 0; t < G1_TILES; t++) {
            const int col1 = (t == 1 ? rank * DM + nslot * 128 : gate_col(t, nslot)) + 64;
            const int col0 = t == 2 ? 2 * DM + nslot * 128 + rank * 64 : col1 - 64;
            if (t == 1) { TRACE_PUT(2, t0); TRACE(14); mbar_wait_warp(dep_bar, 0); TRACE(3); }
#pragma unroll 1
            for (int k = t ? 0 : G1_STAGES; k < G1_KSTEPS; k++) {
                const int s = k & 3;
                if (t == 1 && k == 8) mbar_wait_warp(dep_bar + 40, 0);
                mbar_wait_warp(empty1(s), ph);
                const uint32_t sa = base + s * G1_STAGE_BYTES;
                load_stage1(sa, sa + A_BYTES + rank * 16384, full1(s), t ? &prm.xn : &prm.x, t == 1 || t == 2 ? &prm.wqkv : w0,
                            t == 1 ? &prm.wqkv : w0, k * 64, mblk * 64, col0, col1, t & 3,
                            stream_policy());
                TRACE_RING(t * 16 + k);
                if (s == 3) ph ^= 1;
            }
        }
        TRACE(4);
        mbar_wait_warp(dep_bar + 8, 0);
        TRACE(5);
        int q = 0, round = 4, own = SHARE_MAX; uint32_t ph2 = 1;
#pragma unroll 1
        for (int u = 0; u < G2_KSTEPS; u++) {
            if (u == G2_LATE) { TRACE(6); mbar_wait_warp(dep_bar + 16, 0); TRACE(7); }
            const uint32_t sa = stage2(q);
            const bool down = u < G2_DSTEPS;
            const int k = !down ? u - G2_DSTEPS : (u < 18 || u >= 40 ? own++ : (q & 1 ? u / 2 - 9 : round + (q ? q * 2 : 11)));
            mbar_wait_warp(u < G2_STAGES ? empty1((u * 2 + 1) / 3) : empty2(q), u < G2_STAGES ? ph : ph2);
            load_stage2(sa, sa + A_BYTES + rank * 8192, full2(q), &prm.a2, down ? &prm.wd : &prm.wo, 0,
                        (mblk * G2_KSTEPS + (down ? 16 : 0) + k) * 128, nslot * 128 + rank * 64, down ? 0 : k * 2, down ? k * 2 : 0, stream_policy());
            if (u == XLOAD_STEP + nslot * 2) {
                if (elect_one()) {
                    mbar_expect_tx(x_bar, 32768);
                    tma_3d(aux, &prm.x, x_bar, nslot * 128, mblk * 64, 0, stream_policy());
                    tma_3d(aux + 16384, &prm.x, x_bar, nslot * 128 + 64, mblk * 64, 0, stream_policy());
                }
                __syncwarp();
            }
            TRACE_RING(80 + u);
            if (++q == G2_STAGES) { q = 0; ph2 ^= 1; round++; }
        }
        TRACE(8);
    }
}

typedef CUresult (*EncodeFn)(CUtensorMap*, CUtensorMapDataType, cuuint32_t, void*, const cuuint64_t*, const cuuint64_t*,
                             const cuuint32_t*, const cuuint32_t*, CUtensorMapInterleave, CUtensorMapSwizzle,
                             CUtensorMapL2promotion, CUtensorMapFloatOOBfill);

void encode(EncodeFn fn, CUtensorMap* m, const void* ptr, int rank, const cuuint64_t* dims, const cuuint64_t* strides,
            const cuuint32_t* box, bool swizzle = true) {
    const cuuint32_t es[5] = {1, 1, 1, 1, 1};
    fn(m, CU_TENSOR_MAP_DATA_TYPE_BFLOAT16, rank, const_cast<void*>(ptr), dims, strides, box, es,
       CU_TENSOR_MAP_INTERLEAVE_NONE, !swizzle ? CU_TENSOR_MAP_SWIZZLE_NONE : box[0] == 32 ? CU_TENSOR_MAP_SWIZZLE_64B : CU_TENSOR_MAP_SWIZZLE_128B,
       CU_TENSOR_MAP_L2_PROMOTION_L2_128B, CU_TENSOR_MAP_FLOAT_OOB_FILL_NONE);
}
void encode_rows(EncodeFn fn, CUtensorMap* m, const void* ptr, int cols, int box_rows, int box_parity) {
    const cuuint64_t dims[3] = {(cuuint64_t)cols, SEQ / 2, 2}, strides[2] = {(cuuint64_t)cols * 4, (cuuint64_t)cols * 2};
    const cuuint32_t box[3] = {64, (cuuint32_t)box_rows, (cuuint32_t)box_parity};
    encode(fn, m, ptr, 3, dims, strides, box);
}
void encode_images(EncodeFn fn, CUtensorMap* m, const void* ptr) {
    const cuuint64_t dims[3] = {64, (cuuint64_t)SEQ * K2 / 64 - 64, 2}, strides[2] = {128, 8192};
    const cuuint32_t box[3] = {64, 64, 2};
    encode(fn, m, ptr, 3, dims, strides, box, false);
}
void encode_w1(EncodeFn fn, CUtensorMap* m, const void* ptr, int cols) {
    const cuuint64_t dims[2] = {(cuuint64_t)cols, DM}, strides[1] = {(cuuint64_t)cols * 2};
    const cuuint32_t box[2] = {64, 64};
    encode(fn, m, ptr, 2, dims, strides, box);
}
void encode_tail(EncodeFn fn, CUtensorMap* m, const void* ptr, int rows, int cols, int n) {
    const cuuint64_t rb = cols * 2;
    const cuuint64_t dims[5] = {32, (cuuint64_t)n, (cuuint64_t)rows / (4 * n), 4, 8}, strides[4] = {rb, 4 * n * rb, n * rb, 256};
    const cuuint32_t box[5] = {32, (cuuint32_t)n, 16 / (cuuint32_t)n, 4, 4};
    encode(fn, m, (const __nv_bfloat16*)ptr + cols - 1024 + 96, 5, dims, strides, box);
}
void encode_w2(EncodeFn fn, CUtensorMap* m, const void* ptr, int rows) {
    const cuuint64_t rb = DM * 2;
    const cuuint64_t dims[5] = {DM, 2, 4, 4, (cuuint64_t)rows / 32}, strides[4] = {rb, 8 * rb, 2 * rb, 32 * rb};
    const cuuint32_t box[5] = {64, 2, 4, 4, 2};
    encode(fn, m, ptr, 5, dims, strides, box);
}
void encode_wo(EncodeFn fn, CUtensorMap* m, const void* ptr) {
    const cuuint64_t rb = DM * 2;
    const cuuint64_t dims[5] = {DM, 4, DM / 32, 2, 4}, strides[4] = {8 * rb, 32 * rb, rb, 2 * rb};
    const cuuint32_t box[5] = {64, 4, 2, 2, 4};
    encode(fn, m, ptr, 5, dims, strides, box);
}

}

extern "C" void kernel_launch(void* const* d_in, const int* in_sizes, int n_in, void* d_out, int out_size) {
    (void)in_sizes; (void)n_in; (void)out_size;
    static EncodeFn fn = nullptr;
    static Params prm;
    if (!fn) {
        cudaDriverEntryPointQueryResult st;
        cudaGetDriverEntryPoint("cuTensorMapEncodeTiled", (void**)&fn, cudaEnableDefault, &st);
        cudaGetSymbolAddress((void**)&prm.pxn, g_xn);
        cudaGetSymbolAddress((void**)&prm.pa2, g_a2);
        cudaGetSymbolAddress((void**)&prm.tail, g_tail);
        cudaGetSymbolAddress((void**)&prm.halo, g_halo);
        cudaGetSymbolAddress((void**)&prm.stats, g_stats);
        cudaGetSymbolAddress((void**)&prm.colsum, g_colsum);
        cudaGetSymbolAddress((void**)&prm.flags, g_flags);
        cudaGetSymbolAddress((void**)&prm.epoch, g_epoch);
        cudaFuncSetAttribute(fused_kernel, cudaFuncAttributeMaxDynamicSharedMemorySize, SMEM_BYTES);
    }
    encode_rows(fn, &prm.x, d_in[0], DM, 64, 2);
    encode_rows(fn, &prm.xn, prm.pxn, DM, 64, 2);
    encode_images(fn, &prm.a2, prm.pa2);
    encode_rows(fn, &prm.out, d_out, DM, 16, 1);
    encode_w1(fn, &prm.wqkv, d_in[1], NQKV);
    encode_w1(fn, &prm.wg, d_in[4], DF);
    encode_w1(fn, &prm.wu, d_in[5], DF);
    encode_tail(fn, &prm.wu_tail, d_in[5], DM, DF, 8);
    encode_tail(fn, &prm.wd_tail, d_in[6], DF, DM, 2);
    encode_wo(fn, &prm.wo, d_in[2]);
    encode_w2(fn, &prm.wd, d_in[6], DF);
    prm.hi[0] = prm.hi[1] = prm.hi[3] = HI_128B;
    prm.hi[2] = HI_64B;
    prm.px = (const __nv_bfloat16*)d_in[0];
    prm.pwu = (const __nv_bfloat16*)d_in[5];
    prm.pout = (__nv_bfloat16*)d_out;
    fused_kernel<<<NCTA, 384, SMEM_BYTES>>>(prm);
}
```

```cpp
#include <cuda_runtime.h>
#include <cuda_bf16.h>
#include <cuda.h>
#include <stdint.h>
#include <limits.h>

namespace {

constexpr int SEQ = 2048, DM = 1024, DF = 3584, K2 = DM + DF, NQKV = 3 * DM;
constexpr int NGEMM = 128, NCTA = 132;
constexpr int G1_STAGES = 4, G1_STAGE_BYTES = 49152, G1_KSTEPS = 16, G1_TILES = 5;
constexpr int G2_STAGES = 6, G2_STAGE_BYTES = 32768, G2_KSTEPS = 72, G2_LATE = 40, G2_DSTEPS = 56;
constexpr int G2_HEAD = 17;
constexpr int A_BYTES = 16384;
constexpr int AUX_OFF = G1_STAGES * G1_STAGE_BYTES;
constexpr int BAR_OFF = AUX_OFF + 32768;
constexpr int PLAN_OFF = BAR_OFF + 384, STAT_OFF = BAR_OFF + 1536;
constexpr int SMEM_BYTES = BAR_OFF + 2816;
constexpr int G1_SKEW = 2, G2_SKEW = 5;
constexpr int CONSUMER_REGS = 224, AUX_REGS = 56;
constexpr int HALO_BYTES = 4096;
constexpr int LN_STEP = 3, FOLD_STEP = 14, SUM_STEP = 11, SUM2_STEP = 2;
constexpr uint32_t SUM_LOAD0 = 0x87658765u, SUM_LOAD1 = 0x65876587u;
constexpr int KEY_STEP = 2, QK_STEP = 8;
constexpr int VAL_STEP = 1, HALF_STEP = 3, PV_STEP = 9, OUT_STEPS = 4;
constexpr int UP_STEP = 2, XLOAD_STEP = 44;
constexpr int XREAD_STEP = 5, TAIL_STEP = 7;
constexpr int MEET = 4;
constexpr int PACE1 = 800, PACE2 = 1325, PACE3 = 1700;
constexpr int SHARE_MIN = 3, SHARE_MAX = 22, SHARE_LOW = 36, SHARE_SUM = 43;
constexpr int SHARE_NS = 79, SPARE_NS = 640, LATE_SCALE = 8;
constexpr float REST = 65000.f, DUE = 75100.f;

enum { F_LN = 0, F_LN2 = 1, F_FIRST = 2, F_SECOND = 3, F_SHARE = 4, F_EARLY = 5, F_LATE = 6, F_TAIL2 = 7, F_PACE = 8, F_HALO = 9 };
constexpr unsigned CNT_LN = 8, CNT_EARLY = 9, CNT_LATE = 8;

__device__ __align__(1024) __nv_bfloat16 g_xn[SEQ * DM];
__device__ __align__(1024) __nv_bfloat16 g_a2[SEQ * K2];
__device__ __align__(128) uint4 g_tail[2 * NGEMM * 512];
__device__ __align__(128) uint8_t g_halo[(2 * NGEMM + 1) * HALO_BYTES];
__device__ __align__(128) float2 g_stats[SEQ];
__device__ __align__(128) float g_colsum[18 * 1024];
__device__ __align__(128) unsigned g_flags[(F_HALO + 8) * 16 * 32];
__device__ __align__(128) unsigned g_epoch[NCTA * 16];

struct Params {
    const __nv_bfloat16 *px, *pwu;
    __nv_bfloat16 *pxn, *pa2, *pout;
    uint4* tail;
    uint8_t* halo;
    float2* stats;
    float* colsum;
    unsigned *flags, *epoch;
    unsigned long long* trace;
    uint32_t hi[2];
    CUtensorMap x, wg, wu, xn, wqkv, a2, wu_tail, wd_tail, wo, wd, out;
};

extern __shared__ __align__(1024) uint8_t smem_raw[];

#define TRACE(slot) do {} while (0)
#define TRACE_GT(slot) do {} while (0)
#define TRACE_S(slot, v, want) do {} while (0)
#define TRACE_GET(v) do {} while (0)
#define TRACE_PUT(slot, v) do {} while (0)
#define TRACE_SLOT(v, slot) do {} while (0)
#define TRACE_NEXT(v) do {} while (0)
#define TRACE_DUMP() do {} while (0)
#define TRACE_CLEAR() do {} while (0)
#define STAGE_TRACE 0
#define TRACE_END() do {} while (0)
#define TRACE_LITE(i, c) do {} while (0)
#define TRACE_RING(i) do {} while (0)
#define TRACE_STEP(t, k, i) do {} while (0)

__device__ __forceinline__ uint32_t smem_u32(const void* p) { return (uint32_t)__cvta_generic_to_shared(p); }
__device__ __forceinline__ void mbar_expect_tx(uint32_t bar, uint32_t bytes) {
    asm volatile("mbarrier.arrive.expect_tx.shared::cta.b64 _, [%0], %1;" :: "r"(bar), "r"(bytes) : "memory");
}
__device__ __forceinline__ void mbar_arrive(uint32_t bar) {
    asm volatile("mbarrier.arrive.shared::cta.b64 _, [%0];" :: "r"(bar) : "memory");
}
__device__ __forceinline__ bool mbar_try_wait(uint32_t bar, uint32_t parity) {
    uint32_t ok;
    asm volatile("{\n.reg .pred p;\nmbarrier.try_wait.parity.shared::cta.b64 p, [%1], %2;\nselp.u32 %0, 1, 0, p;\n}"
                 : "=r"(ok) : "r"(bar), "r"(parity) : "memory");
    return ok;
}
__device__ __forceinline__ void mbar_wait(uint32_t bar, uint32_t parity) {
#pragma unroll 1
    for (int spins = 0; !mbar_try_wait(bar, parity) && spins < (1 << 17); spins++) {}
}
__device__ __forceinline__ void mbar_wait(uint32_t bar, uint32_t parity, int& spins) {
    asm volatile("{\n.reg .pred p;\nagain:\nmbarrier.try_wait.parity.shared::cta.b64 p, [%1], %2;\n@p bra done;\n"
                 "add.s32 %0, %0, -1;\nsetp.gt.s32 p, %0, 0;\n@p bra again;\ndone:\n}" : "+r"(spins) : "r"(bar), "r"(parity) : "memory");
}
template <bool WARP = false> __device__ __forceinline__ unsigned flag_wait(const unsigned* p, unsigned target) {
    unsigned v;
#pragma unroll 1
    for (int spins = 0; spins < (1 << 19); spins++) {
        asm volatile("ld.acquire.gpu.global.u32 %0, [%1];" : "=r"(v) : "l"(p) : "memory");
        if (WARP ? __all_sync(0xffffffffu, (int)(v - target) >= 0) : (int)(v - target) >= 0) break;
        __nanosleep(64);
    }
    return v;
}
__device__ __forceinline__ void mbar_wait_warp(uint32_t bar, uint32_t parity) {
#pragma unroll 1
    for (int spins = 0; !__all_sync(0xffffffffu, mbar_try_wait(bar, parity)) && spins < (1 << 17); spins++) {}
}
__device__ __forceinline__ void flag_add(unsigned* p) {
    asm volatile("red.release.gpu.global.add.u32 [%0], 1;" :: "l"(p) : "memory");
}
__device__ __forceinline__ bool elect_one() {
    uint32_t ok;
    asm volatile("{\n.reg .pred p;\nelect.sync _|p, 0xffffffff;\nselp.u32 %0, 1, 0, p;\n}" : "=r"(ok));
    return ok;
}
__device__ __forceinline__ uint32_t pick(bool c, uint32_t a, uint32_t b) {
    uint32_t r;
    asm("{\n.reg .pred p;\nsetp.ne.b32 p, %3, 0;\nselp.b32 %0, %1, %2, p;\n}" : "=r"(r) : "r"(a), "r"(b), "r"((uint32_t)c));
    return r;
}
__device__ __forceinline__ void fence_proxy_async() { asm volatile("fence.proxy.async.global;" ::: "memory"); }
__device__ __forceinline__ uint4 lds128(uint32_t addr) {
    uint4 v;
    asm volatile("ld.shared.v4.u32 {%0,%1,%2,%3}, [%4];" : "=r"(v.x), "=r"(v.y), "=r"(v.z), "=r"(v.w) : "r"(addr) : "memory");
    return v;
}
__device__ __forceinline__ uint32_t lds32(uint32_t addr) {
    uint32_t v;
    asm volatile("ld.shared.u32 %0, [%1];" : "=r"(v) : "r"(addr) : "memory");
    return v;
}
__device__ __forceinline__ void sts32(uint32_t addr, uint32_t v) { asm volatile("st.shared.u32 [%0], %1;" :: "r"(addr), "r"(v) : "memory"); }
__device__ __forceinline__ uint32_t nanos() { uint32_t t; asm volatile("mov.u32 %0, %%globaltimer_lo;" : "=r"(t)); return t; }
__device__ __forceinline__ float2 lds64f(uint32_t addr) {
    float2 v;
    asm volatile("ld.shared.v2.f32 {%0,%1}, [%2];" : "=f"(v.x), "=f"(v.y) : "r"(addr) : "memory");
    return v;
}
__device__ __forceinline__ void sts128(uint32_t addr, uint4 v) {
    asm volatile("st.shared.v4.u32 [%0], {%1,%2,%3,%4};" :: "r"(addr), "r"(v.x), "r"(v.y), "r"(v.z), "r"(v.w) : "memory");
}
__device__ __forceinline__ void sts64f(uint32_t addr, float a, float b) {
    asm volatile("st.shared.v2.f32 [%0], {%1,%2};" :: "r"(addr), "f"(a), "f"(b) : "memory");
}

__device__ __forceinline__ uint64_t stream_policy() { return 0x12F0000000000000ull; }
__device__ __forceinline__ void tma_3d(uint32_t dst, const CUtensorMap* m, uint32_t bar, int c0, int c1, int c2, uint64_t pol) {
    asm volatile("cp.async.bulk.tensor.3d.shared::cluster.global.mbarrier::complete_tx::bytes.L2::cache_hint"
                 " [%0], [%1, {%3, %4, %5}], [%2], %6;"
                 :: "r"(dst), "l"(m), "r"(bar), "r"(c0), "r"(c1), "r"(c2), "l"(pol) : "memory");
}
__device__ __forceinline__ void load_stage1(uint32_t dst, uint32_t dst_b, uint32_t bar, const CUtensorMap* ma, const CUtensorMap* mb0,
                                            const CUtensorMap* mb1, int k, int ka, int row, int col0, int col1, int keep_a, uint64_t pol) {
    asm volatile("{\n.reg .pred e, p, q;\nelect.sync _|e, 0xffffffff;\nsetp.ne.and.b32 p|q, %8, 0, e;\n"
        "@p cp.async.bulk.tensor.3d.shared::cluster.global.mbarrier::complete_tx::bytes [%0], [%3, {%15, %6, %10}], [%2];\n"
        "@q cp.async.bulk.tensor.3d.shared::cluster.global.mbarrier::complete_tx::bytes.L2::cache_hint [%0], [%3, {%15, %6, %10}], [%2], %9;\n"
        "@e cp.async.bulk.tensor.2d.shared::cluster.global.mbarrier::complete_tx::bytes.multicast::cluster.L2::cache_hint"
        " [%1], [%4, {%7, %5}], [%2], %11, %9;\n"
        "@e cp.async.bulk.tensor.2d.shared::cluster.global.mbarrier::complete_tx::bytes.multicast::cluster.L2::cache_hint"
        " [%1 + 8192], [%13, {%14, %5}], [%2], %11, %9;\n"
        "@e mbarrier.arrive.expect_tx.shared::cta.b64 _, [%2], %12;\n}"
        :: "r"(dst), "r"(dst_b), "r"(bar), "l"(ma), "l"(mb0), "r"(k), "r"(row), "r"(col0), "r"(keep_a), "l"(pol), "r"(0),
           "h"((uint16_t)3), "n"(G1_STAGE_BYTES), "l"(mb1), "r"(col1), "r"(ka) : "memory");
}
__device__ __forceinline__ void load_stage2(uint32_t dst, uint32_t dst_b, uint32_t bar, const CUtensorMap* ma, const CUtensorMap* mb,
                                            int ka, int row, int col, int kb2, int kb4, uint64_t pol) {
    asm volatile("{\n.reg .pred e;\nelect.sync _|e, 0xffffffff;\n"
        "@e cp.async.bulk.tensor.3d.shared::cluster.global.mbarrier::complete_tx::bytes.L2::cache_hint [%0], [%3, {%5, %6, %10}], [%2], %9;\n"
        "@e cp.async.bulk.tensor.5d.shared::cluster.global.mbarrier::complete_tx::bytes.multicast::cluster.L2::cache_hint"
        " [%1], [%4, {%7, %10, %13, %10, %8}], [%2], %11, %9;\n"
        "@e mbarrier.arrive.expect_tx.shared::cta.b64 _, [%2], %12;\n}"
        :: "r"(dst), "r"(dst_b), "r"(bar), "l"(ma), "l"(mb), "r"(ka), "r"(row), "r"(col), "r"(kb4), "l"(pol), "r"(0),
           "h"((uint16_t)3), "n"(G2_STAGE_BYTES), "r"(kb2) : "memory");
}
__device__ __forceinline__ void load_tail(uint32_t dst, uint32_t bar, const CUtensorMap* ma, const CUtensorMap* mb, int ka, int row,
                                          int rank, int kb) {
    asm volatile("{\n.reg .pred e;\nelect.sync _|e, 0xffffffff;\n"
        "@e cp.async.bulk.tensor.3d.shared::cluster.global.mbarrier::complete_tx::bytes [%0], [%2, {%3, %4, %5}], [%1];\n"
        "@e cp.async.bulk.tensor.5d.shared::cluster.global.mbarrier::complete_tx::bytes.multicast::cluster"
        " [%9], [%6, {%5, %5, %7, %5, %10}], [%1], %11;\n"
        "@e mbarrier.arrive.expect_tx.shared::cta.b64 _, [%1], %8;\n}"
        :: "r"(dst), "r"(bar), "l"(ma), "r"(ka), "r"(row), "r"(0), "l"(mb), "r"(kb), "n"(G1_STAGE_BYTES),
           "r"(dst + A_BYTES + rank * 16384), "r"(rank * 4), "h"((uint16_t)3) : "memory");
}
__device__ __forceinline__ uint4 ldg_stream(const void* p, uint64_t pol) {
    uint4 v;
    asm volatile("ld.global.nc.L1::no_allocate.L2::cache_hint.v4.u32 {%0,%1,%2,%3}, [%4], %5;"
                 : "=r"(v.x), "=r"(v.y), "=r"(v.z), "=r"(v.w) : "l"(p), "l"(pol));
    return v;
}
__device__ __forceinline__ void st_tagged(void* p, float a, float b, uint32_t tag) {
    asm volatile("st.relaxed.gpu.global.v2.b32 [%0], {%1,%2};"
                 :: "l"(p), "r"((__float_as_uint(a) & ~3u) | tag), "r"((__float_as_uint(b) & ~3u) | tag) : "memory");
}
__device__ __forceinline__ void st_relaxed(unsigned* p, uint32_t v) {
    asm volatile("st.relaxed.gpu.global.b32 [%0], %1;" :: "l"(p), "r"(v) : "memory");
}
__device__ __forceinline__ bool untagged(const uint4& v, uint32_t tag) {
    return ((v.x ^ tag) | (v.y ^ tag) | (v.z ^ tag) | (v.w ^ tag)) & 3;
}
__device__ __forceinline__ uint4 ld_relaxed(const void* p) {
    uint4 v;
    asm volatile("ld.relaxed.gpu.global.v4.b32 {%0,%1,%2,%3}, [%4];" : "=r"(v.x), "=r"(v.y), "=r"(v.z), "=r"(v.w) : "l"(p) : "memory");
    return v;
}
__device__ __forceinline__ void prefetch_map(const CUtensorMap* m) {
    asm volatile("prefetch.tensormap [%0];" :: "l"(m) : "memory");
}
template <int N> __device__ __forceinline__ void wg_wait() { asm volatile("wgmma.wait_group.sync.aligned %0;" :: "n"(N) : "memory"); }

constexpr uint32_t HI_128B = 0x40000040, HI_64B = 0x80000020;
__device__ __forceinline__ uint32_t desc_a(uint32_t addr) { return (addr & 0x3FFFF) >> 4 | 1 << 16; }
__device__ __forceinline__ uint32_t desc_b(uint32_t addr) { return (addr & 0x3FFFF) >> 4 | 512 << 16; }

#define R8(d, o) "+f"(d[o]), "+f"(d[o+1]), "+f"(d[o+2]), "+f"(d[o+3]), "+f"(d[o+4]), "+f"(d[o+5]), "+f"(d[o+6]), "+f"(d[o+7])
#define R32(d, o) R8(d, o), R8(d, o+8), R8(d, o+16), R8(d, o+24)
#define R64(d, o) R32(d, o), R32(d, o+32)
#define ACC00 "%0,%1,%2,%3,%4,%5,%6,%7,%8,%9,%10,%11,%12,%13,%14,%15,%16,%17,%18,%19,%20,%21,%22,%23,%24,%25,%26,%27,%28,%29,%30,%31,"\
    "%32,%33,%34,%35,%36,%37,%38,%39,%40,%41,%42,%43,%44,%45,%46,%47"
#define ACC0 ACC00 ",%48,%49,%50,%51,%52,%53,%54,%55,%56,%57,%58,%59,%60,%61,%62,%63"
#define ACC1 "%64,%65,%66,%67,%68,%69,%70,%71,%72,%73,%74,%75,%76,%77,%78,%79,%80,%81,%82,%83,%84,%85,%86,%87,%88,%89,%90,%91,%92,%93,%94,%95,"\
    "%96,%97,%98,%99,%100,%101,%102,%103,%104,%105,%106,%107,%108,%109,%110,%111"
#define ACC48 "{" ACC00 "}"
#define ACC64 "{" ACC0 "}"
#define ACC112 "{" ACC0 "," ACC1 "}"
#define ACC128 "{" ACC0 "," ACC1 ",%112,%113,%114,%115,%116,%117,%118,%119,%120,%121,%122,%123,%124,%125,%126,%127}"
#define MMA_K16(shape, acc, a, b, keep, ha, hb) \
    "mov.b64 da, {" a ", " ha "};\nmov.b64 db, {" b ", " hb "};\n" \
    "wgmma.mma_async.sync.aligned." shape ".f32.bf16.bf16 " acc ", da, db, " keep ", 1, 1, 0, 1;\n"
#define MMA_NEXT(op, a, b, sa, sb) op " " a ", " a ", " sa ";\n" op " " b ", " b ", " sb ";\n"
#define MMA_STEP_B(shape, acc, a, b, keep, ha, hb, sa, sb) \
    "{\n.reg .pred p, q;\n.reg .b64 da, db;\nsetp.ne.b32 p, " keep ", 0;\nsetp.eq.b32 q, 0, 0;\nwgmma.fence.sync.aligned;\n" \
    MMA_K16(shape, acc, a, b, "p", ha, hb) MMA_NEXT("xor.b32", a, b, "2", "128") MMA_K16(shape, acc, a, b, "q", ha, hb) MMA_NEXT("add.s32", a, b, sa, sb) \
    MMA_K16(shape, acc, a, b, "q", ha, hb) MMA_NEXT("xor.b32", a, b, "2", "128") MMA_K16(shape, acc, a, b, "q", ha, hb) \
    "wgmma.commit_group.sync.aligned;\n}"
#define MMA64(shape, acc, a, b, keep) "wgmma.mma_async.sync.aligned." shape ".f32.bf16.bf16 " acc ", " a ", " b ", " keep ", 1, 1, 0, 1;\n"
#define NEXT64(op, a, b, sa, sb) "mov.b64 {lo, hi}, " a ";\n" op " lo, lo, " sa ";\nmov.b64 " a ", {lo, hi};\n" \
    "mov.b64 {lo, hi}, " b ";\n" op " lo, lo, " sb ";\nmov.b64 " b ", {lo, hi};\n"
#define ADD64(op, a, b, sa, sb) "add.s64 " a ", " a ", " sa ";\nadd.s64 " b ", " b ", " sb ";\n"
#define MMA_STEP(shape, acc, a, b, na, nb, keep, sa) MMA_STEP_N(shape, acc, a, b, na, nb, keep, sa, NEXT64)
#define MMA_STEP_N(shape, acc, a, b, na, nb, keep, sa, LAST) \
    "{\n.reg .pred p, q;\n.reg .b32 lo, hi;\nsetp.ne.b32 p, " keep ", 0;\nsetp.eq.b32 q, 0, 0;\nwgmma.fence.sync.aligned;\n" \
    MMA64(shape, acc, a, b, "p") NEXT64("xor.b32", a, b, "2", "128") MMA64(shape, acc, a, b, "q") NEXT64("add.s32", a, b, sa, "128") \
    MMA64(shape, acc, a, b, "q") NEXT64("xor.b32", a, b, "2", "128") MMA64(shape, acc, a, b, "q") LAST("add.s32", a, b, na, nb) \
    "wgmma.commit_group.sync.aligned;\n}"
#define MMA_ARGS64(sa) "+l"(da), "+l"(db) : "r"(next / 16 - 4 - sa), "r"(next / 16 - 384), "r"(keep), "n"(sa) : "memory"

__device__ __forceinline__ void mma_step(float (&d)[128], uint64_t& da, uint64_t& db, int next, int keep) {
    asm volatile(MMA_STEP("m64n256k16", ACC128, "%128", "%129", "%130", "%131", "%132", "%133") : R64(d, 0), R64(d, 64), MMA_ARGS64(2));
}
__device__ __forceinline__ void mma_rank(float (&d)[128], uint32_t a0, uint32_t a1, uint32_t db) {
    asm volatile("{\n.reg .pred q;\n.reg .b64 db;\nsetp.eq.b32 q, 0, 0;\nmov.b64 db, {%131, 0x40000040};\nwgmma.fence.sync.aligned;\n"
                 "wgmma.mma_async.sync.aligned.m64n256k16.f32.bf16.bf16 " ACC128 ", {%128, %129, %130, %130}, db, q, 1, 1, 1;\n}"
                 : R64(d, 0), R64(d, 64) : "r"(a0), "r"(a1), "r"(0), "r"(db) : "memory");
}
__device__ __forceinline__ void mma_step224(float (&d)[128], uint64_t& da, uint64_t& db, int next, int keep) {
    asm volatile(MMA_STEP("m64n224k16", ACC112, "%112", "%113", "%114", "%115", "%116", "%117")
                 : R64(d, 0), R32(d, 64), R8(d, 96), R8(d, 104), MMA_ARGS64(2));
}
template <int SA> __device__ __forceinline__ void mma_step(float (&d)[64], uint64_t& da, uint64_t& db, int next, int keep) {
    asm volatile(MMA_STEP("m64n128k16", ACC64, "%64", "%65", "%66", "%67", "%68", "%69") : R64(d, 0), MMA_ARGS64(SA));
}
template <int SA> __device__ __forceinline__ void mma_step_c(float (&d)[64], uint64_t& da, uint64_t& db, int next, int keep,
                                                           uint64_t high = 0) {
    asm volatile(MMA_STEP_N("m64n128k16", ACC64, "%64", "%65", "%66", "%67", "%68", "%69", ADD64) : R64(d, 0), "+l"(da), "+l"(db)
                 : "l"((high << 32) + (next / 16 - 4 - SA)), "l"((int64_t)next / 16 - 384), "r"(keep), "n"(SA) : "memory");
}
__device__ __forceinline__ void mma_step96(float (&d)[64], uint64_t& da, uint64_t& db, int next, int keep) {
    asm volatile(MMA_STEP("m64n96k16", ACC48, "%48", "%49", "%50", "%51", "%52", "%53") : R32(d, 0), R8(d, 32), R8(d, 40), MMA_ARGS64(254));
}
__device__ __forceinline__ void mma_step_tail(float (&d)[128], uint32_t da, uint32_t b, int keep, bool down) {
    uint32_t db = (b & 0x3FFFF) >> 4 | 256 << 16;
    asm volatile(MMA_STEP_B("m64n256k16", ACC128, "%128", "%129", "%130", "%131", "0x80000040", "%132", "-96")
                 : R64(d, 0), R64(d, 64), "+r"(da), "+r"(db) : "r"(keep), "r"(down ? HI_64B : HI_128B), "r"(down ? 254 : 2) : "memory");
}

__device__ __forceinline__ uint32_t pack_bf16(float lo, float hi) {
    uint32_t r; asm("cvt.rn.bf16x2.f32 %0, %1, %2;" : "=r"(r) : "f"(hi), "f"(lo)); return r;
}
__device__ __forceinline__ float bf_lo(uint32_t v) { return __uint_as_float(v << 16); }
__device__ __forceinline__ float bf_hi(uint32_t v) { return __uint_as_float(v & 0xffff0000u); }
__device__ __forceinline__ float round_bf16(float v) { return bf_lo(pack_bf16(v, 0.f)); }
__device__ __forceinline__ uint32_t mul_bf16x2(uint32_t a, uint32_t b) {
    uint32_t r; asm("mul.rn.bf16x2 %0, %1, %2;" : "=r"(r) : "r"(a), "r"(b)); return r;
}
__device__ __forceinline__ uint32_t sub_bf16x2(uint32_t a, uint32_t b) {
    uint32_t r; asm("sub.rn.bf16x2 %0, %1, %2;" : "=r"(r) : "r"(a), "r"(b)); return r;
}
__device__ __forceinline__ uint32_t mul2_bf16x2(uint32_t a, uint32_t hi, uint32_t lo) {
    uint32_t r; asm("fma.rn.bf16x2 %0, %1, %2, %3;" : "=r"(r) : "r"(a), "r"(hi), "r"(mul_bf16x2(a, lo))); return r;
}
__device__ __forceinline__ float tanh_fast(float x) { float r; asm("tanh.approx.f32 %0, %1;" : "=f"(r) : "f"(x)); return r; }
__device__ __forceinline__ float gelu_twice(float g) {
    return fmaf(g, tanh_fast(fmaf(g * g, 0.044715f * 0.7978845608f, 0.7978845608f) * g), g);
}
__device__ __forceinline__ uint32_t geglu2(uint32_t g2, uint32_t u2) {
    return mul_bf16x2(pack_bf16(gelu_twice(bf_lo(g2)), gelu_twice(bf_hi(g2))), u2);
}
__device__ __forceinline__ uint32_t silu2(float lo, float hi) {
    const uint32_t h = mul_bf16x2(pack_bf16(lo, hi), 0x3e803e80u);
    return pack_bf16(fmaf(bf_lo(h), tanh_fast(bf_lo(h)), bf_lo(h)), fmaf(bf_hi(h), tanh_fast(bf_hi(h)), bf_hi(h)));
}
__device__ __forceinline__ float ex2_fast(float x) { float r; asm("ex2.approx.ftz.f32 %0, %1;" : "=f"(r) : "f"(x)); return r; }
__device__ __forceinline__ void unpack8(uint4 v, float (&f)[8]) {
    f[0] = bf_lo(v.x); f[1] = bf_hi(v.x); f[2] = bf_lo(v.y); f[3] = bf_hi(v.y);
    f[4] = bf_lo(v.z); f[5] = bf_hi(v.z); f[6] = bf_lo(v.w); f[7] = bf_hi(v.w);
}
template <int N> __device__ __forceinline__ void fence_regs(float (&d)[N]) {
#pragma unroll
    for (int i = 0; i < N; i++) asm volatile("" : "+f"(d[i]) :: "memory");
}

__device__ __forceinline__ float rcp_fast(float x) { float r; asm("rcp.approx.ftz.f32 %0, %1;" : "=f"(r) : "f"(x)); return r; }
__device__ __forceinline__ float sqrt_fast(float x) { float r; asm("sqrt.approx.ftz.f32 %0, %1;" : "=f"(r) : "f"(x)); return r; }
__device__ __forceinline__ uint32_t max_bf16x2(uint32_t a, uint32_t b) {
    uint32_t r; asm("max.bf16x2 %0, %1, %2;" : "=r"(r) : "r"(a), "r"(b)); return r;
}
__device__ __forceinline__ uint32_t transpose8(uint32_t a) {
    uint32_t r; asm volatile("movmatrix.sync.aligned.m8n8.trans.b16 %0, %1;" : "=r"(r) : "r"(a)); return r;
}
__device__ __forceinline__ void mma_sync(uint32_t* d, const uint32_t* a, uint32_t b0, uint32_t b1, const uint32_t* c) {
    asm volatile("mma.sync.aligned.m16n8k16.row.col.f32.bf16.bf16.f32 {%0,%1,%2,%3}, {%4,%5,%6,%7}, {%8,%9}, {%10,%11,%12,%13};"
        : "=r"(d[0]), "=r"(d[1]), "=r"(d[2]), "=r"(d[3])
        : "r"(a[0]), "r"(a[1]), "r"(a[2]), "r"(a[3]), "r"(b0), "r"(b1), "r"(c[0]), "r"(c[1]), "r"(c[2]), "r"(c[3]));
}
template <int N> struct Floats {
    float f[N];
    __device__ __forceinline__ Floats() {}
    __device__ __forceinline__ Floats(const uint32_t* p) {
#pragma unroll
        for (int i = 0; i < N; i++) asm("mov.b32 %0, %1;" : "=f"(f[i]) : "r"(p[i]));
    }
    __device__ __forceinline__ void put(uint32_t* p) const {
#pragma unroll
        for (int i = 0; i < N; i++) asm("mov.b32 %0, %1;" : "=r"(p[i]) : "f"(f[i]));
    }
    __device__ __forceinline__ float& operator[](int i) { return f[i]; }
};
__device__ __forceinline__ uint32_t fresh_tid() { uint32_t r; asm volatile("mov.u32 %0, %%tid.x;" : "=r"(r)); return r; }
template <typename T> __device__ __forceinline__ T uniform(T v) { return __shfl_sync(0xffffffffu, v, 0); }

__device__ __forceinline__ uint32_t forecast(uint32_t n0, uint32_t c0, float cycles, uint32_t tag) {
    const uint32_t n = nanos();
    return n + (int)((n - n0) * cycles * rcp_fast((uint32_t)clock() - c0)) & ~3u | tag;
}
__device__ __forceinline__ uint32_t plan_word(uint32_t base, int lane) { return uniform(lds32(base + PLAN_OFF + lane * 4)); }

__device__ __forceinline__ void fold_operands(const Params& prm, uint32_t base, int slot, int mblk, uint32_t tag, int w, int lane) {
    uint4 v[9];
#pragma unroll
    for (int m = 0; m < 9; m++) v[m] = make_uint4(0, 0, 0, 0);
    const float* parts = prm.colsum + (slot * 2 + (lane >> 4)) * 1024 + w * 64 + (lane & 15) * 4;
    const float* const rows = &prm.stats[mblk * 128 + w * 64 + lane * 2].x;
#pragma unroll 1
    for (int spins = 0; spins < (1 << 16); spins++) {
        bool missing = false;
        asm volatile("" : "+l"(parts));
#pragma unroll
        for (int m = 0; m < 9; m++) {
            if (untagged(v[m], tag)) {
                missing = true;
                v[m] = ld_relaxed(m < 8 ? parts + m * 128 : rows);
            }
        }
        if (!missing) break;
    }
    float4 c = make_float4(0.f, 0.f, 0.f, 0.f);
#pragma unroll
    for (int m = 0; m < 8; m++) {
        c.x += __uint_as_float(v[m].x ^ tag); c.y += __uint_as_float(v[m].y ^ tag);
        c.z += __uint_as_float(v[m].z ^ tag); c.w += __uint_as_float(v[m].w ^ tag);
    }
    sts128(base + STAT_OFF + w * 512 + lane * 16, make_uint4(v[8].x ^ tag, v[8].y ^ tag, v[8].z ^ tag, v[8].w ^ tag));
    const uint32_t ca = base + AUX_OFF + w * 8192 + (lane >> 4) * 16384 + (lane & 15) * 8;
#pragma unroll
    for (int r = 0; r < 3; r++) {
        const uint32_t lo = pack_bf16(c.x, c.y), hi = pack_bf16(c.z, c.w);
        sts64f((ca ^ r * 16) + r * 128, __uint_as_float(lo), __uint_as_float(hi));
        c.x -= bf_lo(lo); c.y -= bf_hi(lo); c.z -= bf_lo(hi); c.w -= bf_hi(hi);
    }
    asm volatile("fence.proxy.async.shared::cta;" ::: "memory");
    __syncwarp();
}
__device__ __forceinline__ float2 fold(float (&acc)[128], uint32_t base, int wg) {
    const uint32_t id = fresh_tid(), sp = base + STAT_OFF + (id & 96) * 8 + (id & 28) * 4 + wg * 8;
    const uint32_t sel = id & 2 ? 0x4444 : (id & 1 ? 0x4432 : 0x3232);
    const float2 sa = lds64f(sp), sb = lds64f(sp + 128);
    mma_rank(acc, __byte_perm(__float_as_uint(sa.x), 0, sel), __byte_perm(__float_as_uint(sb.x), 0, sel), desc_b(base + AUX_OFF));
    return make_float2(sa.y, sb.y);
}

__device__ __forceinline__ void tail_gemm(const Params& prm, uint32_t base, uint32_t t0, unsigned epoch, int grp, int warp, int lane) {
    const uint32_t full = base + BAR_OFF, empty = full + 32, sig = full + 192, dep = full + 256, folded = full + 320;
    const uint32_t tag = 1 + (epoch & 1);
    auto plan = [&](uint32_t p, uint32_t word) { return p < 4 ? p * 64 + grp / 2 * 32 + 15 : word >> p % 4 * 8 & 255; };
    auto rows = [&](uint32_t job) { return job / 32 * 2 + grp % 2; };
    if (warp == 8) {
        if (elect_one()) { prefetch_map(&prm.xn); prefetch_map(&prm.a2); prefetch_map(&prm.wd_tail); }
#pragma unroll 1
        for (int p = 0, i = G1_STAGES; p < 8; p++) {
            const bool first = p < 4;
            if (p == 4) mbar_wait_warp(dep + 16, 0);
            const uint32_t job = plan(p, plan_word(base, lane));
#pragma unroll 1
            for (int k = p ? 0 : G1_STAGES; k <= job % 32; k++, i++) {
                if (p == 3 && k % 2 == grp / 2)
                    asm volatile("{\n.reg .pred e;\nelect.sync _|e, 0xffffffff;\n"
                        "@e cp.async.bulk.prefetch.tensor.5d.L2.global [%0, {%2, %2, %1, %2, %3}];\n}"
                        :: "l"(&prm.wd_tail), "r"(k * 8), "r"(0), "r"(grp % 2 * 4) : "memory");
                if (i == 16 || i == 24 || k == 16) mbar_wait_warp(dep + (first ? i & 8 : 24), 0);
                TRACE_S(62, i, 16); TRACE_S(63, i, 4);
                mbar_wait_warp(empty + (i & 3) * 8, ~i >> 2 & 1);
                load_tail(base + (i & 3) * G1_STAGE_BYTES, full + (i & 3) * 8, first ? (p ? &prm.xn : &prm.x) : &prm.a2,
                          first ? &prm.wu_tail : &prm.wd_tail, p ? 0 : k * 64,
                          p ? (first ? rows(job) * G1_KSTEPS + k : rows(job) * G2_KSTEPS + 16 + k) * 128 : rows(job) * 64, grp % 2, first ? k * 2 : k * 8);
            }
        }
        return;
    }
    if (warp == 9) {
        const uint32_t n0 = nanos(), c0 = clock();
#pragma unroll 1
        for (int j = 0; j < 3; j++) {
            flag_wait<true>(prm.flags + (F_LN + j) * 512 + (j < 2 ? lane % 4 * 4 + grp : lane % 16) * 32, epoch * CNT_LN);
            fence_proxy_async();
            __syncwarp();
            if (lane == 0 && j < 2) mbar_arrive(dep + j * 8);
        }
        mbar_wait_warp(sig + 8, 0);
        if (lane == 0) st_relaxed(prm.flags + F_PACE * 512 + 64 + grp, forecast(n0, c0, DUE, tag));
        uint4 v, w;
#pragma unroll 1
        for (int spins = 0; spins < (1 << 19); spins++) {
            v = ld_relaxed(prm.flags + F_PACE * 512 + lane / 2 * 4);
            w = ld_relaxed(prm.flags + F_PACE * 512 + 64);
            if (!__any_sync(0xffffffffu, untagged(v, tag) || untagged(w, tag))) break;
            __nanosleep(256);
        }
        const uint32_t ref = uniform(v.x);
        const int due = min(max((int)((grp & 2 ? w.z : w.x) - ref), -100000), 100000) * 8;
        int late = max(max((int)(v.x - ref), (int)(v.y - ref)), max((int)(v.z - ref), (int)(v.w - ref)));
        late = min(max(max(late, __shfl_xor_sync(0xffffffffu, late, 2)), -100000), 100000) * LATE_SCALE + lane / 4;
        TRACE_PUT(16 + lane / 4, late + (1 << 20));
        int place = 0, n = SHARE_MIN;
#pragma unroll 1
        for (int g = 0; g < 32; g += 4) place += __shfl_sync(0xffffffffu, late, g) > late;
        const bool swap = (__reduce_add_sync(0xffffffffu, place + 1 & 2 ? late : -late) ^ w.x - w.z) >> 31;
        const bool mine = (place + 1 >> 1 & 1 ^ swap) == grp / 2;
#pragma unroll 1
        for (int j = 4 * SHARE_MIN; j < SHARE_SUM; j++) {
            const int most = __reduce_max_sync(0xffffffffu, mine && n < SHARE_MAX ? late : INT_MIN);
            if (j >= SHARE_LOW && due + (j - 38) * SPARE_NS * 8 > most) break;
            if (j == 38) TRACE_PUT(32, most - due + (1 << 20));
            if (most == late) { n++; late -= SHARE_NS * 8; }
        }
        auto first = [](uint32_t bits, int n) { return bits & (1u << min(max(n, 0), 24)) - 1; };
        const uint32_t job = lane / 4 * 32 + n - 1;
        if (mine) st_relaxed(prm.flags + F_SHARE * 512 + rows(job) * 32,
                             epoch << 24 | first(0x2aaaaa, 2 * n) | first(0x104104, 6 * n - 66) | first(0x10410, 6 * n - 90) |
                             first(0x41041, 6 * n - 108));
        if (mine) TRACE_PUT(24 + lane / 4, n);
        sts32(base + PLAN_OFF, __reduce_or_sync(0xffffffffu, mine ? job << place / 2 * 8 : 0));
        if (lane == 0) mbar_arrive(dep + 16);
        flag_wait<true>(prm.flags + F_SECOND * 512 + lane % 16 * 32, epoch * CNT_LN);
        fence_proxy_async();
        __syncwarp();
        if (lane == 0) mbar_arrive(dep + 24);
        return;
    }
    if (warp > 9) {
#pragma unroll 1
        for (int j = 0; j < 8; j++) sts128(base + AUX_OFF + (warp - 10) * 8192 + (j & 4) * 4096 + (j & 3) * 512 + lane * 16, make_uint4(0, 0, 0, 0));
        while ((uint32_t)clock() - t0 < 9000) __nanosleep(256);
        fold_operands(prm, base, 8, grp, tag, warp - 10, lane);
        if (lane) return;
        mbar_arrive(folded);
        if (warp == 11) return;
        TRACE(60);
#pragma unroll 1
        for (int p = 0; p < 8; p++) {
            mbar_wait(sig + p * 8, 0);
            flag_add(prm.flags + (p < 4 ? F_EARLY : F_TAIL2) * 512 + rows(plan(p, lds32(base + PLAN_OFF))) * 32);
            TRACE_S(50, p, 3); TRACE_S(51, p, 7);
        }
        prm.epoch[blockIdx.x * 16] = epoch;
        TRACE_DUMP();
        return;
    }
    asm volatile("setmaxnreg.inc.sync.aligned.u32 %0;" :: "n"(CONSUMER_REGS) : "memory");
    const uint32_t da = desc_a(base + (warp >> 2) * 8192);
    uint4* out = prm.tail;
    float acc[128];
    uint32_t pk[64];
    float2 inv = make_float2(0.f, 0.f);
    int i = 0, last;
    uint32_t peer;
    asm volatile("mapa.shared::cluster.u32 %0, %1, %2;" : "=r"(peer) : "r"(empty), "r"(lane & 1));
    auto release = [&]() {
        if ((threadIdx.x & 126) == 0 && i <= last)
            asm volatile("mbarrier.arrive.shared::cluster.b64 _, [%0];" :: "r"(peer + (i - 1 & 3) * 8) : "memory");
    };
    auto store = [&](int j) {
        asm volatile("st.global.v4.u32 [%0], {%1,%2,%3,%4};" :: "l"(out + j / 2 * 8192 + j % 2 * 256),
                     "r"(pk[4 * j]), "r"(pk[4 * j + 1]), "r"(pk[4 * j + 2]), "r"(pk[4 * j + 3]) : "memory");
    };
    auto step = [&](int k, int left) {
        mbar_wait(full + (i & 3) * 8, i >> 2 & 1);
        TRACE_S(45, warp * 128 + i, 0);
        if (warp >= 4 && left == G1_SKEW) asm volatile("bar.sync 1, 256;" ::: "memory");
        mma_step_tail(acc, da + (i & 3) * (G1_STAGE_BYTES / 16), base + A_BYTES + (i & 3) * G1_STAGE_BYTES, k, i >= 4 * G1_KSTEPS);
        if (warp < 4 && left == 1) asm volatile("bar.arrive 1, 256;" ::: "memory");
    };
    auto drip = [&](int p, int& n) {
        if (n > 0) { store(0); store(1); }
#pragma unroll
        for (int j = 8; j < 64; j++) asm volatile("mov.b32 %0, %1;" : "=r"(pk[j - 8]) : "r"(pk[j]));
        out += 8192;
        __syncwarp();
        if (--n == 0 && lane == 0) mbar_arrive(sig + p * 8 - 8);
    };
#pragma unroll
    for (int j = 0; j < 128; j++) asm volatile("mov.b32 %0, 0;" : "=f"(acc[j]));
#pragma unroll
    for (int j = 0; j < 64; j++) asm volatile("mov.b32 %0, 0;" : "=r"(pk[j]));
#pragma unroll 1
    for (int p = 0; p < 8; p++) {
        step(0, 0);
        i++;
        const uint32_t word = plan_word(base, lane), job = plan(p, word);
        last = __dp4a(word & 0x1f1f1f1fu, 0x01010101u, 4u * G1_KSTEPS);
#pragma unroll 1
        for (int left = job % 32, n = p ? 8 : 0; left > 0; left--) {
            if (i == G1_KSTEPS - 1) { mbar_wait(folded, 0); inv = fold(acc, base, warp >> 2); }
#pragma unroll 1
            do drip(p, n); while (n & 7 >> 31 - __clz(job % 32));
            step(1, left);
            wg_wait<1>();
            release();
            i++;
        }
        wg_wait<0>();
        fence_regs(acc);
        release();
        if (p == 0) {
#pragma unroll
            for (int j = 0; j < 128; j++) acc[j] *= j & 2 ? inv.y : inv.x;
            fence_regs(acc);
        }
        if (warp == 4) TRACE_PUT(46 + p + p / 4 * 3, (uint32_t)clock());
#pragma unroll
        for (int j = 0; j < 64; j++) pk[j] = pack_bf16(acc[2 * j], acc[2 * j + 1]);
        out = prm.tail + p / 4 * NGEMM * 512 + rows(job) * 512 + threadIdx.x;
    }
#pragma unroll
    for (int j = 0; j < 16; j++) store(j);
    __syncwarp();
    TRACE_S(58, warp, 4);
    if (lane == 0) mbar_arrive(sig + 56);
}

__device__ __forceinline__ int gate_col(int t, int nslot) { return t == 2 ? 960 + nslot * 64 : max(t * 1024 - 1536, 0) + nslot * 128; }

struct Role {
    int rank, role, mblk, nslot;
    __device__ __forceinline__ Role() {
        uint32_t id;
        asm volatile("mov.u32 %0, %%ctaid.x;" : "=r"(id));
        const uint32_t cl = id / 2;
        rank = id & 1;
        role = pick(cl < 4, 32 + cl * 8, cl - 8 + max(4u, (cl - 1) * 37 >> 8)) * 2 + rank;
        mblk = role & 15; nslot = role >> 4;
    }
};

__global__ void __cluster_dims__(2, 1, 1) __launch_bounds__(384, 1)
fused_kernel(const __grid_constant__ Params prm) {
    TRACE_GET(c0);
    const uint32_t base = smem_u32(smem_raw) & ~1023u;
    const uint32_t bars = base + BAR_OFF;
    auto full1 = [&](int s) { return bars + s * 8; };
    auto empty1 = [&](int s) { return bars + 32 + s * 8; };
    auto full2 = [&](int s) { return bars + 64 + s * 8; };
    auto empty2 = [&](int s) { return bars + 128 + s * 8; };
    const uint32_t sig_bar = bars + 192, dep_bar = bars + 256, cs_bar = bars + 304, fold_bar = bars + 320, x_bar = bars + 352;
    const uint32_t halo_bar = dep_bar + 32;
    auto stage2 = [&](int q) { return base + q * G2_STAGE_BYTES; };
    const uint32_t aux = base + AUX_OFF;

    asm volatile("{\n.reg .pred p;\nsetp.eq.u32 p, %1, 0;\n@p mbarrier.init.shared::cta.b64 [%0], 1;\n"
        "fence.mbarrier_init.release.cluster;\nbarrier.cluster.arrive.relaxed.aligned;\n}" :: "r"(bars), "r"(threadIdx.x) : "memory");
    const int warp = __shfl_sync(0xffffffffu, threadIdx.x >> 5, 0);
    auto cluster_wait = []() { asm volatile("barrier.cluster.wait.acquire.aligned;" ::: "memory"); };
    if ((warp | (blockIdx.x & NGEMM)) == 8) {
        const Role r;
        asm volatile("{\n.reg .pred e;\nelect.sync _|e, 0xffffffff;\n"
            "@e prefetch.tensormap [%0];\n@e prefetch.tensormap [%1];\n}" :: "l"(&prm.x), "l"(&prm.wg + r.rank) : "memory");
        cluster_wait();
        load_stage1(base, base + A_BYTES + r.rank * 16384, full1(0), &prm.x, &prm.wg + r.rank, &prm.wg + r.rank, 0, 0, r.mblk * 64,
                    r.nslot * 128, r.nslot * 128 + 64, 0, stream_policy());
    } else {
        cluster_wait();
    }
    const uint32_t t0 = clock();
    {
        uint32_t cta;
        asm volatile("mov.u32 %0, %%ctaid.x;" : "=r"(cta));
        if ((warp | (~cta & NGEMM)) == 8) load_tail(base, full1(0), &prm.x, &prm.wu_tail, 0, (cta - NGEMM) * 64, cta & 1, 0);
    }
    asm volatile("{\n.reg .pred e, q;\nelect.sync _|e, 0xffffffff;\nsetp.ne.and.u32 q, %2, 0, e;\n"
        "@q mbarrier.init.shared::cta.b64 [%0], %1;\n@e mbarrier.init.shared::cta.b64 [%0 + 8], %1;\n"
        "@e mbarrier.init.shared::cta.b64 [%0 + 16], %1;\n@e mbarrier.init.shared::cta.b64 [%0 + 24], %1;\n"
        "fence.mbarrier_init.release.cluster;\nbarrier.cluster.arrive.relaxed.aligned;\n}"
        :: "r"(bars + warp * 32), "r"(1 << (0x10fa08 >> warp * 2 & 3)), "r"(warp) : "memory");
    const int lane = threadIdx.x & 31;
    const Role me;
    const int rank = me.rank, role = me.role, mblk = me.mblk, nslot = me.nslot;
    const CUtensorMap* const w0 = &prm.wg + rank;

    unsigned* const flags = prm.flags + mblk * 32;
    if (warp >= 8) {
        asm volatile("setmaxnreg.dec.sync.aligned.u32 %0;" :: "n"(AUX_REGS));
        if (warp == 9) { TRACE_CLEAR(); TRACE_GT(0); TRACE_PUT(1, c0); }
        if ((warp | (~blockIdx.x & NGEMM)) == 8) {
#pragma unroll 1
            for (int i = 1; i < G1_STAGES; i++) {
                if (i == 1) cluster_wait();
                TRACE_S(57, i, 1);
                load_tail(base + i * G1_STAGE_BYTES, full1(i), &prm.x, &prm.wu_tail, i * 64, (blockIdx.x - NGEMM) * 64, blockIdx.x & 1, i * 2);
            }
        } else {
            cluster_wait();
        }
    }

    if (blockIdx.x >= NGEMM) {
        if (warp < 8) cluster_wait();
        const uint32_t seen = __ldcg(prm.epoch + blockIdx.x * 16);
        tail_gemm(prm, base, t0, seen + 1, blockIdx.x - NGEMM, warp, lane);
    } else if (warp == 9) {
        const unsigned epoch = __ldcg(prm.epoch + blockIdx.x * 16 + 2) + 1;
        const uint32_t n0 = nanos(), c1 = clock();
        {
            const __nv_bfloat16* const w = prm.pwu + ((mblk >> 1) * 128 + lane / 2) * DF + gate_col(4, nslot) + 96 + rank * 16 + lane % 2 * 8;
            uint4 v[8];
            float cs[8], f[8];
            mbar_wait(empty1(SUM2_STEP), 0);
#pragma unroll
            for (int j = 0; j < 8; j++) v[j] = __ldg(reinterpret_cast<const uint4*>(w + j * 16 * DF));
            unpack8(v[0], cs);
#pragma unroll
            for (int j = 1; j < 8; j++) {
                unpack8(v[j], f);
#pragma unroll
                for (int d = 0; d < 8; d++) cs[d] += f[d];
            }
#pragma unroll
            for (int d = 0; d < 4; d++)
                cs[d] = (lane & 16 ? cs[d + 4] : cs[d]) + __shfl_xor_sync(0xffffffffu, lane & 16 ? cs[d] : cs[d + 4], 16);
#pragma unroll
            for (int d = 0; d < 2; d++) {
                cs[d] = (lane & 8 ? cs[d + 2] : cs[d]) + __shfl_xor_sync(0xffffffffu, lane & 8 ? cs[d] : cs[d + 2], 8);
                cs[d] += __shfl_xor_sync(0xffffffffu, cs[d], 4);
                cs[d] += __shfl_xor_sync(0xffffffffu, cs[d], 2);
            }
            if (!(lane & 6))
                st_tagged(prm.colsum + (16 + nslot / 4) * 1024 + (mblk >> 1) * 128 + nslot % 4 * 32 + rank * 16 + lane % 2 * 8 + (lane >> 3) * 2,
                          cs[0], cs[1], 1 + (epoch & 1));
            TRACE(61);
        }
        if (lane == 0) {
            mbar_wait(sig_bar, 0);
            TRACE(11);
            flag_add(flags + F_LN * 512);
            TRACE(42);
            flag_wait(flags + F_LN * 512, epoch * CNT_LN);
            fence_proxy_async();
            mbar_arrive(dep_bar);
            mbar_wait(sig_bar + 56, 0);
            flag_add(flags + F_LN2 * 512);
            flag_wait(flags + F_LN2 * 512, epoch * CNT_LN);
            fence_proxy_async();
            mbar_arrive(dep_bar + 40);
            TRACE(59);
            prm.epoch[blockIdx.x * 16 + 2] = epoch;
#pragma unroll 1
            for (int p = 3; p < 7; p++) {
                mbar_wait(sig_bar + (p == 3 ? 16 : p * 8), 0);
                TRACE_S(37, p, 4);
                flag_add(flags + (p - (p < F_EARLY)) * 512);
                TRACE_S(43, p, 4);
                if (p == 3 && rank == 0) {
                    mbar_wait(sig_bar + 24, 0);
                    st_relaxed(prm.flags + F_PACE * 512 + mblk * 4 + nslot, forecast(n0, c1, REST, 1 + (epoch & 1)));
                }
            }
        }
    } else if (warp < 8) {
        asm volatile("setmaxnreg.inc.sync.aligned.u32 %0;" :: "n"(CONSUMER_REGS));
        const int wg = __shfl_sync(0xffffffffu, threadIdx.x >> 7, 0);
        const int cw = threadIdx.x >> 5;
        const int tid = threadIdx.x & 127;
        int spins = 1 << 18;
        float acc[128];
        uint32_t pk[64];
#pragma unroll
        for (int i = 0; i < 64; i++) asm volatile("mov.b32 %0, 0;" : "=r"(pk[i]));
#pragma unroll
        for (int i = 0; i < 128; i++) asm volatile("mov.b32 %0, 0;" : "=f"(acc[i]));
        cluster_wait();

        auto row0 = [&](uint32_t id) { return mblk * 128 + (id & 96) + wg; };
        __nv_bfloat16* optr = const_cast<__nv_bfloat16*>(prm.px) + (mblk * 128 + nslot * 16 + cw * 2) * DM + lane * 8;
        uint64_t da = desc_a(base + wg * 8192) | (uint64_t)prm.hi[0] << 32, db = desc_b(base + A_BYTES) | (uint64_t)prm.hi[1] << 32;
        auto next1 = [](int s) { return ((s + 1) % G1_STAGES - s) * G1_STAGE_BYTES; };
        auto next2 = [](int q) { return ((q + 1) % G2_STAGES - q) * G2_STAGE_BYTES; };
        uint32_t peer_bars;
        asm volatile("mapa.shared::cluster.u32 %0, %1, %2;" : "=r"(peer_bars) : "r"(bars), "r"(tid & 1));
        if (tid >= 2) peer_bars = 0;
        auto release = [&](uint32_t bar) {
            if (peer_bars) asm volatile("mbarrier.arrive.shared::cluster.b64 _, [%0];" :: "r"(peer_bars + (bar - bars)) : "memory");
        };
        auto up = [](int i) { return 32 + (i & 24) + (i & 3) * 2 + (i >> 2 & 1); };
        auto store_pk = [&](__nv_bfloat16* p, int j) {
            asm volatile("st.global.v4.u32 [%0], {%1,%2,%3,%4};"
                         :: "l"(p), "r"(pk[4 * j]), "r"(pk[4 * j + 1]), "r"(pk[4 * j + 2]), "r"(pk[4 * j + 3]) : "memory");
        };
        auto chunk_geglu = [&](int j) {
#pragma unroll
            for (int i = 4 * j; i < 4 * j + 4; i++) pk[i] = geglu2(pk[i], pk[up(i)]);
            store_pk(optr + (j & 1) * 256 + (j & 2) * 1024 + (j & 4) * 2048, j);
        };
        auto signal_stores = [&](int p) { __syncwarp(); if (lane == 0) mbar_arrive(sig_bar + p * 8); };

        auto chunk_ln = [&](int k) {
            Floats<6> mo(pk + 32);
            if (k == 0) {
                const uint4* xp = reinterpret_cast<const uint4*>(optr);
                pk[38] = __ldcg(prm.epoch + blockIdx.x * 16 + 2);
#pragma unroll
                for (int i = 0; i < 8; i++) {
                    const uint4 v = ldg_stream(xp + i * 32, stream_policy());
                    pk[4 * i] = v.x; pk[4 * i + 1] = v.y; pk[4 * i + 2] = v.z; pk[4 * i + 3] = v.w;
                }
            } else if (k >= LN_STEP && k < LN_STEP + 3) {
                if (k == LN_STEP) {
                    mo[0] = bf_lo(uniform(pk[0])); mo[1] = bf_lo(uniform(pk[16]));
                    mo[2] = mo[3] = mo[4] = mo[5] = 0.f;
                }
#pragma unroll
                for (int i = (k - LN_STEP) * 11; i < (k - LN_STEP) * 11 + 11 && i < 32; i++) {
                    const int r = i & 1;
                    const uint32_t w = pk[r * 16 + i / 2];
                    const float lo = bf_lo(w) - mo[r], hi = bf_hi(w) - mo[r];
                    mo[2 + r] += lo + hi;
                    mo[4 + r] = fmaf(hi, hi, fmaf(lo, lo, mo[4 + r]));
                }
                mo.put(pk + 32);
            } else if (k == LN_STEP + 3) {
                const bool second = lane & 16;
                float m1 = (second ? mo[3] : mo[2]) + __shfl_xor_sync(0xffffffffu, second ? mo[2] : mo[3], 16);
                float m2 = (second ? mo[5] : mo[4]) + __shfl_xor_sync(0xffffffffu, second ? mo[4] : mo[5], 16);
#pragma unroll
                for (int o = 8; o > 0; o >>= 1) {
                    m1 += __shfl_xor_sync(0xffffffffu, m1, o);
                    m2 += __shfl_xor_sync(0xffffffffu, m2, o);
                }
                m1 *= 1.f / DM;
                const float var = fmaxf(fmaf(-m1, m1, m2 * (1.f / DM)), 0.f);
                const float mean = round_bf16((second ? mo[1] : mo[0]) + m1);
                const float inv = rcp_fast(round_bf16(sqrt_fast(round_bf16(round_bf16(var) + 1e-5f))));
                if ((lane & 15) == 0) st_tagged(prm.stats + (uint32_t)(optr - prm.px) / DM + second, -mean, inv, 2 - (pk[38] & 1));
                const uint32_t id = fresh_tid();
                optr = prm.pxn + mblk * 128 * DM + nslot * 512 + (id & 24) * 1024 + (id & 224) * 2 + (id & 7 ^ id >> 5) * 8;
                const uint32_t split = pack_bf16(inv - round_bf16(inv), inv);
#pragma unroll
                for (int r = 0; r < 2; r++) {
                    const uint32_t f = __shfl_sync(0xffffffffu, split, r * 16);
                    pk[32 + 3 * r] = __byte_perm(__shfl_sync(0xffffffffu, __float_as_uint(mean), r * 16), 0, 0x3232);
                    pk[33 + 3 * r] = __byte_perm(f, 0, 0x3232);
                    pk[34 + 3 * r] = __byte_perm(f, 0, 0x1010);
                }
            } else if (k >= LN_STEP + 4 && k < LN_STEP + 8) {
#pragma unroll
                for (int i = k - LN_STEP - 4; i < 8; i += 4) {
                    const uint32_t* n = pk + 32 + i / 4 * 3;
#pragma unroll
                    for (int j = 4 * i; j < 4 * i + 4; j++) pk[j] = mul2_bf16x2(sub_bf16x2(pk[j], n[0]), n[1], n[2]);
                    store_pk(optr + i % 4 * 32768 + i / 4 * 4096, i);
                }
                if (k == LN_STEP + 5 || k == LN_STEP + 7) signal_stores(k == LN_STEP + 5 ? 0 : 7);
            } else if (k == FOLD_STEP) {
                mbar_wait(fold_bar, 0, spins);
                const float2 inv = fold(acc, base, wg);
                mo[0] = inv.x; mo[1] = inv.y;
                mo.put(pk + 32);
            }
        };

        auto halo = [&]() { const uint32_t id = fresh_tid(); return aux + (id & 96) * 128 + (id & 128) * 16 + (id & 31) * 4; };
        auto put = [&](uint32_t a, uint32_t v0, uint32_t v1) {
            asm volatile("st.shared.u32 [%0], %1;\nst.shared.u32 [%0 + 128], %2;" :: "r"(a + HALO_BYTES), "r"(v0), "r"(v1) : "memory");
        };
        auto get = [&](uint32_t a, uint32_t& v0, uint32_t& v1) {
            asm volatile("ld.shared.u32 %0, [%2];\nld.shared.u32 %1, [%2 + 128];" : "=r"(v0), "=r"(v1) : "r"(a) : "memory");
        };
        auto publish = [&](int p) { asm volatile("fence.proxy.async.shared::cta;" ::: "memory"); signal_stores(p); };
        const uint32_t zero[4] = {0, 0, 0, 0};
        auto meet = [&](int n, int k, uint32_t id) {
            if (n == 15 - MEET)
                asm volatile("{\n.reg .b32 c;\nmov.u32 c, %%clock;\nbar.arrive %1, 256;\nlop3.b32 %0, %0, c, 1, 0x70;\n}"
                             : "+r"(peer_bars) : "r"(2 + id / 128) : "memory");
            if (n == 15) {
                asm volatile("{\n.reg .b32 c;\nmov.u32 c, %%clock;\nbar.sync %1, 256;\nlop3.b32 %0, %0, c, 1, 0x70;\n}"
                             : "+r"(peer_bars) : "r"(3 - id / 128) : "memory");
                mma_step(acc, da, db, next1(k & 3), k);
                asm volatile("// batch step");
            }
        };
        auto mix_qk = [&]() {
            uint32_t c[2][4];
            const uint32_t a = halo(), id = fresh_tid();
            mbar_wait(halo_bar, 0, spins);
#pragma unroll
            for (int n = 0; n < 16; n++) {
                const int b = 1 - n / 8, h = (n & 4) / 2 + n % 2, j = n / 2 % 2;
                uint32_t* const kq = pk + 32 + 8 * h + 4 * j;
                uint32_t* const q = pk + 8 * h + 4 * b;
                mma_sync(j ? q : c[n % 2], kq, q[2 * j], q[2 * j + 1], j ? c[n % 2] : zero);
                if (b) get(a + (h * 2 + j) * 256, kq[1], kq[3]);
                meet(n, QK_STEP, id);
            }
        };
        auto chunk_qk = [&](int k) {
            constexpr float LOG2E = 1.4426950408889634f;
            uint32_t* const l = pk + 32;
            Floats<16> e(pk);
            if (k == KEY_STEP) {
                const uint32_t a = halo();
#pragma unroll
                for (int i = 0; i < 8; i++) put(a + i * 256, pk[33 + 4 * i], pk[35 + 4 * i]);
                publish(1);
            } else if (k == QK_STEP + 1) {
                const uint32_t id = fresh_tid();
                const bool u0 = id % 32 / 4 > id % 4 * 2, u1 = id % 32 / 4 > id % 4 * 2 + 1;
                const uint32_t gone = row0(id) < 2 ? (u0 ? 0xffffu : 0u) | (u1 ? 0xffff0000u : 0u) : 0u;
#pragma unroll
                for (int n = 0; n < 8; n++) {
                    const int b = n % 2;
                    const uint32_t* const c = pk + 4 * n;
                    uint32_t v = pack_bf16(__uint_as_float(pick(u0, c[2 - 2 * b], c[2 * b])), __uint_as_float(pick(u1, c[3 - 2 * b], c[1 + 2 * b])));
                    v = mul2_bf16x2(v, 0x3e353e35u, 0x379e379eu);
                    if (!b) v = v & ~gone | 0xce6ece6eu & gone;
                    l[n] = transpose8(v);
                }
            } else if (k == QK_STEP + 2) {
#pragma unroll
                for (int h = 0; h < 4; h++) {
                    uint32_t m = max_bf16x2(__byte_perm(l[2 * h], l[2 * h + 1], 0x5410), __byte_perm(l[2 * h], l[2 * h + 1], 0x7632));
                    m = max_bf16x2(m, __shfl_xor_sync(0xffffffffu, m, 1));
                    m = max_bf16x2(m, __shfl_xor_sync(0xffffffffu, m, 2));
#pragma unroll
                    for (int n = 2 * h; n < 2 * h + 2; n++) {
                        const float f = -LOG2E * (n % 2 ? bf_hi(m) : bf_lo(m));
                        e[2 * n] = ex2_fast(fmaf(bf_lo(l[n]), LOG2E, f));
                        e[2 * n + 1] = ex2_fast(fmaf(bf_hi(l[n]), LOG2E, f));
                    }
                }
                e.put(pk);
            } else if (k == QK_STEP + 3) {
                uint32_t p[8];
#pragma unroll
                for (int n = 0; n < 8; n++) {
                    float sum = e[2 * n] + e[2 * n + 1];
                    sum += __shfl_xor_sync(0xffffffffu, sum, 1);
                    sum += __shfl_xor_sync(0xffffffffu, sum, 2);
                    const float r = rcp_fast(sum);
                    p[n] = pack_bf16(e[2 * n] * r, e[2 * n + 1] * r);
                }
                const uint32_t a = aux + 5 * HALO_BYTES + fresh_tid() * 16;
                sts128(a, make_uint4(p[0], p[1], p[2], p[3]));
                sts128(a + 4096, make_uint4(p[4], p[5], p[6], p[7]));
            }
        };
        auto values = [&](int h) { return pk + (h & 2) * 16 + (h & 1) * 8; };
        auto mix_pv = [&]() {
            uint32_t lo[8], hi[8];
            const uint32_t id = fresh_tid();
            const uint32_t keep = (id % 4 * 2 > id % 32 / 4 ? 0xffffu : 0u) | (id % 4 * 2 + 1 > id % 32 / 4 ? 0xffff0000u : 0u);
            const uint4 p0 = lds128(aux + 5 * HALO_BYTES + id * 16), p1 = lds128(aux + 6 * HALO_BYTES + id * 16);
            const uint32_t p[8] = {p0.x, p0.y, p0.z, p0.w, p1.x, p1.y, p1.z, p1.w};
#pragma unroll
            for (int n = 0; n < 8; n++)
                asm volatile("and.b32 %0, %2, %3;\nand.b32 %1, %2, %4;" : "=r"(lo[n]), "=r"(hi[n])
                             : "r"(p[n]), "r"(n % 2 ? keep : ~keep), "r"(n % 2 ? ~keep : keep));
            mbar_wait(halo_bar, 1, spins);
#pragma unroll
            for (int n = 0; n < 16; n++) {
                const int i = (n & 8) / 2 + (n & 2) + (n & 4) / 4;
                mma_sync(pk + 4 * (n ^ 4), pk + 4 * (n ^ 4), lo[i], hi[i], zero);
                meet(n, PV_STEP, id);
            }
        };
        auto chunk_pv = [&](int k) {
            if (k == VAL_STEP || k == VAL_STEP + 1) {
                const uint32_t a = halo();
#pragma unroll
                for (int h = (k - VAL_STEP) * 2; h < (k - VAL_STEP + 1) * 2; h++) {
                    uint32_t* const w = values(h);
                    uint32_t v[8];
#pragma unroll
                    for (int i = 0; i < 8; i++) v[i] = transpose8(w[h < 2 ? (i & 1) + (i & 2) * 2 + (i & 4) / 2 : (i & 1) * 2 + (i & 2) / 2 + (i & 4)]);
#pragma unroll
                    for (int i = 0; i < 8; i++) w[i] = v[i];
                    put(a + h * 512, w[2], w[3]);
                    put(a + h * 512 + 256, w[6], w[7]);
                }
                if (k > VAL_STEP) publish(3);
            } else if (k == PV_STEP - 1) {
                const uint32_t a = halo(), id = fresh_tid();
                optr = prm.pa2 + (mblk * K2 + nslot * 128) * 128 + (id & 224) * 32 + id % 4 * 128 + (id >> 2 & 7 ^ id % 4 * 2) * 8;
                mbar_wait(halo_bar, 1, spins);
#pragma unroll
                for (int n = 0; n < 8; n++) {
                    uint32_t* const w = values(n / 2) + n % 2 * 4;
                    w[16] = w[0]; w[17] = w[1];
                    get(a + n * 256, w[18], w[19]);
                }
            } else if (k > PV_STEP && k <= PV_STEP + OUT_STEPS) {
#pragma unroll
                for (int n = 0; n < 8; n++) {
                    if (n * OUT_STEPS / 8 != k - PV_STEP - 1) continue;
                    const int j = n ^ n >> 1 & 1;
                    if (n % 2) optr = reinterpret_cast<__nv_bfloat16*>(reinterpret_cast<uintptr_t>(optr) ^ 16);
                    Floats<15> c(pk + j / 2 * 16 + j % 2);
                    asm volatile("st.global.v4.u32 [%0], {%1,%2,%3,%4};"
                                 :: "l"(optr + (~j & 2) * 256 + j % 2 * 64 + j / 4 * 8192), "r"(pack_bf16(c[0], c[2])),
                                    "r"(pack_bf16(c[4], c[6])), "r"(pack_bf16(c[8], c[10])), "r"(pack_bf16(c[12], c[14])) : "memory");
                }
                if (k == PV_STEP + OUT_STEPS) signal_stores(4);
            }
        };

        TRACE_SLOT(tile_slot, 16 + wg * 8);
#pragma unroll 1
        for (int t = 0; t < G1_TILES; t++) {
#pragma unroll
            for (int k = 0; k < G1_KSTEPS; k++) {
                const int s = k & 3;
                if (k == 0) asm volatile("" : "+r"(t));
                TRACE_STEP(t, k, 0);
                mbar_wait(full1(s), (k >> 2) & 1, spins);
                if (k == 0) TRACE_S(12, t, 0);
                TRACE_STEP(t, k, 1);
                if (wg == 1 && k == G1_KSTEPS - G1_SKEW) asm volatile("bar.sync 1, 256;" ::: "memory");
                if (k == PV_STEP && t == 3) mix_pv();
                else if (k == QK_STEP && t == 2) mix_qk();
                else if (t == G1_TILES - 1) mma_step224(acc, da, db, next1(s), k);
                else mma_step(acc, da, db, next1(s), k);
                if (wg == 0 && k == G1_KSTEPS - 1) asm volatile("bar.arrive 1, 256;" ::: "memory");
                wg_wait<1>();
                if (k > 0) release(empty1((k - 1) & 3));
                TRACE_STEP(t, k, 2);
                if (t == 0) chunk_ln(k);
                if (k >= 1 && k <= 8 && ((k < HALF_STEP || k > HALF_STEP + 3 ? 0x12 : 0x1a) >> t & 1)) {
                    chunk_geglu(k < HALF_STEP ? k - 1 : (k > HALF_STEP + 3 ? k - 5 : k - HALF_STEP + 4));
                    if (k == 8 && t != 3) signal_stores(t + 1);
                }
                if (t == 2) chunk_qk(k);
                if (t == 3) chunk_pv(k);
                if (k == PV_STEP + OUT_STEPS) {
                    const uint32_t id = fresh_tid();
                    optr = prm.pa2 + (mblk * K2 + DM + gate_col(t, nslot)) * 128 + (id & 128) * 32 + (id & 96) * 16 + (id & 31 ^ id >> 3 & 3) * 8;
                    asm volatile("" : "+l"(optr));
                }
            }
            wg_wait<0>();
            fence_regs(acc);
            release(empty1(3));
            if (t == 0) {
                Floats<2> inv(pk + 32);
#pragma unroll
                for (int i = 0; i < 128; i++) acc[i] *= inv[i / 2 % 2];
                fence_regs(acc);
            }
#pragma unroll
            for (int i = 0; i < 64; i++) {
                const int e = i < 32 ? (i & ~7) * 2 + (i & 3) * 4 + (i & 4) / 2 : i * 2;
                pk[i] = pack_bf16(acc[e], acc[e + 1]);
            }
            TRACE_NEXT(tile_slot);
        }

        float accd[64], accs[64];
        asm volatile("{\n.reg .b32 lo, hi;\nmov.b64 {lo, hi}, %0;\nxor.b32 hi, hi, %1;\nmov.b64 %0, {lo, hi};\n}" : "+l"(da) : "n"(HI_64B ^ HI_128B));
#pragma unroll
        for (int i = 0; i < 64; i++) accd[i] = 0.f;
#pragma unroll
        for (int u = 0; u < G2_HEAD; u++) {
            const int q = u % G2_STAGES;
            TRACE_STEP(5, u, 0);
            mbar_wait(full2(q), (u / G2_STAGES) & 1, spins);
            TRACE_STEP(5, u, 1);
            if (u % 2) mma_step_c<254>(accd, da, db, next2(q), u);
            else mma_step<254>(accd, da, db, next2(q), u);
            wg_wait<1>();
            if (u > 0) release(empty2((u - 1) % G2_STAGES));
            TRACE_STEP(5, u, 2);
            if (u == UP_STEP) {
#pragma unroll
                for (int i = 0; i < 2; i++) {
                    const uint4 v = ldg_stream(prm.tail + role * 512 + i * 256 + threadIdx.x, stream_policy());
                    pk[56 + 4 * i] = v.x; pk[57 + 4 * i] = v.y; pk[58 + 4 * i] = v.z; pk[59 + 4 * i] = v.w;
                }
            }
            if (u >= 1) {
                const int j = (u - 1) / 2;
#pragma unroll
                for (int i = 2 * u - 2; i < 2 * u; i++) pk[i] = geglu2(pk[i], pk[up(i)]);
                if (u % 2 == 0) store_pk(optr + (j & 1) * 256 + (j & 2) * 1024 + (j & 4) * 2048, j);
            }
            if (u == G2_HEAD - 1) signal_stores(6);
        }
        auto down = [&](int q, uint32_t phase, bool narrow, bool busy = false) {
            mbar_wait(full2(q), phase, spins);
            if (narrow) mma_step96(accd, da, db, next2(q), 1);
            else if (busy) mma_step_c<254>(accd, da, db, next2(q), 1, HI_128B - HI_64B);
            else mma_step<254>(accd, da, db, next2(q), 1);
            wg_wait<1>();
            release(empty2((q + G2_STAGES - 1) % G2_STAGES));
        };
        uint32_t shared_steps = plan_word(base, lane);
        down(5, 0, false);
#pragma unroll 1
        for (uint32_t r = 3; r < 9; r++, shared_steps >>= G2_STAGES) {
#pragma unroll
            for (int q = 0; q < G2_STAGES; q++) down(q, r & 1, shared_steps >> q & 1);
        }
        down(0, 1, false);
        down(1, 1, false, true);
        TRACE_NEXT(tile_slot);
#pragma unroll
        for (int i = 0; i < 64; i++) accs[i] = 0.f;
        uint32_t gk[32], xr[32];
        const uint32_t xs = aux + cw * 2048;
        const uint32_t xrow = xs + ((lane & 7) + ((lane >> 3) & 1) * 8) * 128;
        auto xaddr = [&](int j) { return xrow + (j >> 2) * 16384 + (((((j & 3) * 2) + (lane >> 4)) ^ (lane & 7)) << 4); };
#pragma unroll
        for (int u = G2_DSTEPS; u < G2_KSTEPS; u++) {
            const int q = u % G2_STAGES, v = u - G2_DSTEPS;
            mbar_wait(full2(q), (u / G2_STAGES) & 1, spins);
            if (wg == 1 && u == G2_KSTEPS - G2_SKEW) asm volatile("bar.sync 1, 256;" ::: "memory");
            if (u % 2) mma_step_c<2>(accs, da, db, next2(q), v);
            else mma_step<2>(accs, da, db, next2(q), v);
            if (wg == 0 && u == G2_KSTEPS - 1) asm volatile("bar.arrive 1, 256;" ::: "memory");
            if (v == TAIL_STEP) {
                TRACE_S(32, wg, 0);
                mbar_wait(dep_bar + 24, 0, spins);
                TRACE_S(33, wg, 0);
#pragma unroll
                for (int i = 0; i < 2; i++) {
                    const uint4 w = ldg_stream(prm.tail + (NGEMM + role) * 512 + i * 256 + threadIdx.x, stream_policy());
                    gk[24 + 4 * i] = w.x; gk[25 + 4 * i] = w.y; gk[26 + 4 * i] = w.z; gk[27 + 4 * i] = w.w;
                }
            }
#pragma unroll
            for (int i = 0; i < 32; i++) {
                if (v == (i < 24 ? i / 4 + 1 : TAIL_STEP + i / 4 - 3))
                    gk[i] = i < 24 ? silu2(accd[2 * i], accd[2 * i + 1])
                                   : silu2(accd[2 * i] + bf_lo(gk[i]), accd[2 * i + 1] + bf_hi(gk[i]));
            }
            if (v == XREAD_STEP) mbar_wait(x_bar, 0, spins);
            if (v >= XREAD_STEP && v < XREAD_STEP + 4) {
#pragma unroll
                for (int j = 2 * (v - XREAD_STEP); j < 2 * (v - XREAD_STEP + 1); j++)
                    asm volatile("ldmatrix.sync.aligned.m8n8.x4.shared.b16 {%0,%1,%2,%3}, [%4];"
                                 : "=r"(xr[4 * j]), "=r"(xr[4 * j + 1]), "=r"(xr[4 * j + 2]), "=r"(xr[4 * j + 3])
                                 : "r"(xaddr(j)) : "memory");
            }
            wg_wait<1>();
            if (v == 0) fence_regs(accd);
            if (u - 1 + G2_STAGES < G2_KSTEPS) release(empty2((u - 1) % G2_STAGES));
        }
        __nv_bfloat16* po = prm.pout + (row0(fresh_tid()) + (lane >> 3) * 2) * DM + nslot * 128 + 64 + (lane & 7) * 8;
        uint32_t so = xs + 16384 + (lane >> 3) * 128 + (((lane & 7) ^ (lane >> 3)) << 4);
        const int c0 = uniform(nslot * 128), c1 = uniform(row0(fresh_tid()) >> 1);
        const uint32_t xu = uniform(xs);
        asm volatile("" : "+l"(po), "+r"(so));
        wg_wait<0>();
        fence_regs(accs);
        TRACE_NEXT(tile_slot);
        TRACE_END();
#pragma unroll
        for (int j = 0; j < 8; j++) {
            uint32_t r[4];
#pragma unroll
            for (int i = 0; i < 4; i++) {
                const int e = j * 4 + i;
                asm("fma.rn.bf16x2 %0, %1, %2, %3;" : "=r"(r[i]) : "r"(pack_bf16(accs[2 * e], accs[2 * e + 1])), "r"(gk[e]), "r"(xr[e]));
            }
            asm volatile("stmatrix.sync.aligned.m8n8.x4.shared.b16 [%0], {%1,%2,%3,%4};"
                         :: "r"(xaddr(j)), "r"(r[0]), "r"(r[1]), "r"(r[2]), "r"(r[3]) : "memory");
            if (j == 3)
                asm volatile("{\n.reg .pred e;\nfence.proxy.async.shared::cta;\nbar.warp.sync 0xffffffff;\nelect.sync _|e, 0xffffffff;\n"
                    "@e cp.async.bulk.tensor.3d.global.shared::cta.bulk_group [%0, {%2, %3, %4}], [%1];\n}"
                    :: "l"(&prm.out), "r"(xu), "r"(c0), "r"(c1), "r"(wg) : "memory");
        }
        __syncwarp();
#pragma unroll
        for (int i = 0; i < 4; i++) {
            const uint4 v = lds128((so ^ (i & 1) * 64) + i * 512);
            asm volatile("st.global.v4.u32 [%0], {%1,%2,%3,%4};" :: "l"(po + i * 8 * DM), "r"(v.x), "r"(v.y), "r"(v.z), "r"(v.w) : "memory");
        }
        asm volatile("cp.async.bulk.commit_group;\ncp.async.bulk.wait_group.read 0;" ::: "memory");
        TRACE_LITE(10, clock());
        if (tid == 0) { TRACE_NEXT(tile_slot); if (wg == 1) TRACE_GT(13); TRACE_DUMP(); }
    } else if (warp > 9) {
        const int w = warp - 10;
        const unsigned epoch = __ldcg(prm.epoch + blockIdx.x * 16 + w) + 1;
        const uint32_t tag = 1 + (epoch & 1);
        TRACE_LITE(8, t0);
        const uint32_t at = (w ? SUM_LOAD1 : SUM_LOAD0) >> nslot * 4 & 15;
        mbar_wait(empty1(at & 3), 0);
        mbar_wait(empty1(at & 3), at >> 3);
        if (elect_one()) {
            mbar_expect_tx(cs_bar + w * 8, 16384);
            asm volatile("cp.async.bulk.tensor.2d.shared::cluster.global.mbarrier::complete_tx::bytes [%0], [%1, {%3, %5}], [%2];\n"
                "cp.async.bulk.tensor.2d.shared::cluster.global.mbarrier::complete_tx::bytes [%0 + 8192], [%1, {%4, %5}], [%2];"
                :: "r"(aux + w * 16384), "l"(w0), "r"(cs_bar + w * 8), "r"(nslot * 128), "r"(nslot * 128 + 64),
                   "r"(((mblk & ~1) + w) * 64) : "memory");
        }
        float cs[8];
#pragma unroll
        for (int d = 0; d < 8; d++) cs[d] = 0.f;
        const uint32_t wa = aux + w * 8192 + (lane >> 3) * 128 + (((lane & 7) ^ (lane >> 3)) << 4);
        uint4 v[8];
        auto fetch = [&](int h, uint32_t off) {
#pragma unroll
            for (int j = 0; j < 4; j++) v[h * 4 + j] = lds128((wa ^ (j & 1) * 64) + off + h * 2048 + j * 512);
        };
        auto add = [&](int h) {
#pragma unroll
            for (int j = 0; j < 4; j++) {
                float f[8];
                unpack8(v[h * 4 + j], f);
#pragma unroll
                for (int d = 0; d < 8; d++) cs[d] += f[d];
            }
        };
        mbar_wait(empty1(SUM_STEP & 3), 0);
        mbar_wait(empty1(SUM_STEP & 3), SUM_STEP >> 3);
        mbar_wait(cs_bar, 0);
        fetch(0, 0);
#pragma unroll 1
        for (int i = 0; i < 4; i++) {
            fetch(1, (i >> 1) * 16384 + (i & 1) * 4096);
            add(0);
            if (i == 1) mbar_wait(cs_bar + 8, 0);
            fetch(0, (i + 1 & 2) * 8192 + (~i & 1) * 4096);
            add(1);
        }
#pragma unroll
        for (int d = 0; d < 4; d++)
            cs[d] = (lane & 16 ? cs[d + 4] : cs[d]) + __shfl_xor_sync(0xffffffffu, lane & 16 ? cs[d] : cs[d + 4], 16);
#pragma unroll
        for (int d = 0; d < 2; d++)
            cs[d] = (lane & 8 ? cs[d + 2] : cs[d]) + __shfl_xor_sync(0xffffffffu, lane & 8 ? cs[d] : cs[d + 2], 8);
        st_tagged(prm.colsum + (nslot * 2 + rank) * 1024 + (mblk >> 1) * 128 + w * 64 + (lane & 7) * 8 + (lane >> 3) * 2,
                  cs[0], cs[1], tag);

        fold_operands(prm, base, nslot, mblk, tag, w, lane);
        if (lane == 0) {
            mbar_arrive(fold_bar);
            prm.epoch[blockIdx.x * 16 + w] = epoch;
            if (w == 0) {
                TRACE(35);
#pragma unroll 1
                for (uint32_t j = 0, n = 1 << 24; j < 4; n = (CNT_EARLY | CNT_LATE << 8 | 1 << 16) >> j * 8 & 255, j++) {
                    mbar_wait(sig_bar + (0xa0302820u >> j * 8 & 255), 0);
                    const uint32_t v = flag_wait(flags + (F_SHARE + j) * 512, epoch * n);
                    fence_proxy_async();
                    if (j) mbar_arrive(dep_bar + j * 8);
                    else sts32(base + PLAN_OFF, v & 0xffffff);
                }
            } else {
#pragma unroll 1
                for (int j = 0; j < 2; j++) {
                    uint8_t* const h = prm.halo + (j * NGEMM + role) * HALO_BYTES;
                    unsigned* const f = prm.flags + F_HALO * 512 + role * 32;
                    mbar_wait(sig_bar + 8 + j * 16, 0);
                    TRACE_S(38, j, 0); TRACE_S(9, j, 1);
                    asm volatile("cp.async.bulk.global.shared::cta.bulk_group [%0], [%1], %2;\n"
                        "cp.async.bulk.commit_group;\ncp.async.bulk.wait_group 0;"
                        :: "l"(h + HALO_BYTES), "r"(aux + 4 * HALO_BYTES), "n"(HALO_BYTES) : "memory");
                    fence_proxy_async();
                    TRACE_S(39, j, 0); TRACE_S(10, j, 1);
                    flag_add(f);
                    TRACE_S(40, j, 0); TRACE_S(34, j, 1);
                    if (mblk) flag_wait(f - 32, epoch * 2 - 1 + j);
                    fence_proxy_async();
                    TRACE_S(41, j, 0); TRACE_S(36, j, 1);
                    mbar_expect_tx(halo_bar, HALO_BYTES);
                    asm volatile("cp.async.bulk.shared::cluster.global.mbarrier::complete_tx::bytes [%0], [%1], %2, [%3];"
                        :: "r"(aux), "l"(mblk ? h : prm.halo), "n"(HALO_BYTES), "r"(halo_bar) : "memory");
                }
            }
        }
    } else {
#pragma unroll 1
        for (int k = 1; k < G1_STAGES; k++) {
            const uint32_t sa = base + k * G1_STAGE_BYTES;
            while ((uint32_t)clock() - t0 < (k == 3 ? PACE3 : PACE1 + (k - 1) * (PACE2 - PACE1))) {}
            load_stage1(sa, sa + A_BYTES + rank * 16384, full1(k), &prm.x, w0, w0, k * 64, k * 64, mblk * 64, nslot * 128,
                        nslot * 128 + 64, 0, stream_policy());
        }
        if (elect_one()) {
            prefetch_map(&prm.xn); prefetch_map(&prm.wqkv);
            prefetch_map(&prm.a2); prefetch_map(&prm.wo); prefetch_map(&prm.wd); prefetch_map(&prm.out);
        }
        uint32_t ph = 0;
#pragma unroll 1
        for (int t = 0; t < G1_TILES; t++) {
            const int col1 = (t == 1 ? rank * DM + nslot * 128 : gate_col(t, nslot)) + 64;
            const int col0 = t == 2 ? 2 * DM + nslot * 128 + rank * 64 : col1 - 64;
            if (t == 1) { TRACE_PUT(2, t0); TRACE(14); mbar_wait_warp(dep_bar, 0); TRACE(3); }
#pragma unroll 1
            for (int k = t ? 0 : G1_STAGES; k < G1_KSTEPS; k++) {
                const int s = k & 3;
                if (t == 1 && k == 8) mbar_wait_warp(dep_bar + 40, 0);
                mbar_wait_warp(empty1(s), ph);
                const uint32_t sa = base + s * G1_STAGE_BYTES;
                load_stage1(sa, sa + A_BYTES + rank * 16384, full1(s), t ? &prm.xn : &prm.x, t == 1 || t == 2 ? &prm.wqkv : w0,
                            t == 1 ? &prm.wqkv : w0, k * 64, t ? 0 : k * 64, t ? (mblk * G1_KSTEPS + k) * 128 : mblk * 64, col0, col1, t & 3,
                            stream_policy());
                TRACE_RING(t * 16 + k);
                if (s == 3) ph ^= 1;
            }
        }
        TRACE(4);
        mbar_wait_warp(dep_bar + 8, 0);
        TRACE(5);
        int q = 0, round = 4, own = SHARE_MAX; uint32_t ph2 = 1;
#pragma unroll 1
        for (int u = 0; u < G2_KSTEPS; u++) {
            if (u == G2_LATE) { TRACE(6); mbar_wait_warp(dep_bar + 16, 0); TRACE(7); }
            const uint32_t sa = stage2(q);
            const bool down = u < G2_DSTEPS;
            const int k = !down ? u - G2_DSTEPS : (u < 18 || u >= 40 ? own++ : (q & 1 ? u / 2 - 9 : round + (q ? q * 2 : 11)));
            mbar_wait_warp(u < G2_STAGES ? empty1((u * 2 + 1) / 3) : empty2(q), u < G2_STAGES ? ph : ph2);
            load_stage2(sa, sa + A_BYTES + rank * 8192, full2(q), &prm.a2, down ? &prm.wd : &prm.wo, 0,
                        (mblk * G2_KSTEPS + (down ? 16 : 0) + k) * 128, nslot * 128 + rank * 64, down ? 0 : k * 2, down ? k * 2 : 0, stream_policy());
            if (u == XLOAD_STEP + nslot * 2) {
                if (elect_one()) {
                    mbar_expect_tx(x_bar, 32768);
                    tma_3d(aux, &prm.x, x_bar, nslot * 128, mblk * 64, 0, stream_policy());
                    tma_3d(aux + 16384, &prm.x, x_bar, nslot * 128 + 64, mblk * 64, 0, stream_policy());
                }
                __syncwarp();
            }
            TRACE_RING(80 + u);
            if (++q == G2_STAGES) { q = 0; ph2 ^= 1; round++; }
        }
        TRACE(8);
    }
}

typedef CUresult (*EncodeFn)(CUtensorMap*, CUtensorMapDataType, cuuint32_t, void*, const cuuint64_t*, const cuuint64_t*,
                             const cuuint32_t*, const cuuint32_t*, CUtensorMapInterleave, CUtensorMapSwizzle,
                             CUtensorMapL2promotion, CUtensorMapFloatOOBfill);

void encode(EncodeFn fn, CUtensorMap* m, const void* ptr, int rank, const cuuint64_t* dims, const cuuint64_t* strides,
            const cuuint32_t* box, bool swizzle = true) {
    const cuuint32_t es[5] = {1, 1, 1, 1, 1};
    fn(m, CU_TENSOR_MAP_DATA_TYPE_BFLOAT16, rank, const_cast<void*>(ptr), dims, strides, box, es,
       CU_TENSOR_MAP_INTERLEAVE_NONE, !swizzle ? CU_TENSOR_MAP_SWIZZLE_NONE : box[0] == 32 ? CU_TENSOR_MAP_SWIZZLE_64B : CU_TENSOR_MAP_SWIZZLE_128B,
       CU_TENSOR_MAP_L2_PROMOTION_L2_128B, CU_TENSOR_MAP_FLOAT_OOB_FILL_NONE);
}
void encode_rows(EncodeFn fn, CUtensorMap* m, const void* ptr, int cols, int box_rows, int box_parity) {
    const cuuint64_t dims[3] = {(cuuint64_t)cols, SEQ / 2, 2}, strides[2] = {(cuuint64_t)cols * 4, (cuuint64_t)cols * 2};
    const cuuint32_t box[3] = {64, (cuuint32_t)box_rows, (cuuint32_t)box_parity};
    encode(fn, m, ptr, 3, dims, strides, box);
}
void encode_images(EncodeFn fn, CUtensorMap* m, const void* ptr, int cols) {
    const cuuint64_t dims[3] = {64, (cuuint64_t)SEQ * cols / 64 - 64, 2}, strides[2] = {128, 8192};
    const cuuint32_t box[3] = {64, 64, 2};
    encode(fn, m, ptr, 3, dims, strides, box, false);
}
void encode_w1(EncodeFn fn, CUtensorMap* m, const void* ptr, int cols) {
    const cuuint64_t dims[2] = {(cuuint64_t)cols, DM}, strides[1] = {(cuuint64_t)cols * 2};
    const cuuint32_t box[2] = {64, 64};
    encode(fn, m, ptr, 2, dims, strides, box);
}
void encode_tail(EncodeFn fn, CUtensorMap* m, const void* ptr, int rows, int cols, int n) {
    const cuuint64_t rb = cols * 2;
    const cuuint64_t dims[5] = {32, (cuuint64_t)n, (cuuint64_t)rows / (4 * n), 4, 8}, strides[4] = {rb, 4 * n * rb, n * rb, 256};
    const cuuint32_t box[5] = {32, (cuuint32_t)n, 16 / (cuuint32_t)n, 4, 4};
    encode(fn, m, (const __nv_bfloat16*)ptr + cols - 1024 + 96, 5, dims, strides, box);
}
void encode_w2(EncodeFn fn, CUtensorMap* m, const void* ptr, int rows) {
    const cuuint64_t rb = DM * 2;
    const cuuint64_t dims[5] = {DM, 2, 4, 4, (cuuint64_t)rows / 32}, strides[4] = {rb, 8 * rb, 2 * rb, 32 * rb};
    const cuuint32_t box[5] = {64, 2, 4, 4, 2};
    encode(fn, m, ptr, 5, dims, strides, box);
}
void encode_wo(EncodeFn fn, CUtensorMap* m, const void* ptr) {
    const cuuint64_t rb = DM * 2;
    const cuuint64_t dims[5] = {DM, 4, DM / 32, 2, 4}, strides[4] = {8 * rb, 32 * rb, rb, 2 * rb};
    const cuuint32_t box[5] = {64, 4, 2, 2, 4};
    encode(fn, m, ptr, 5, dims, strides, box);
}

}

extern "C" void kernel_launch(void* const* d_in, const int* in_sizes, int n_in, void* d_out, int out_size) {
    (void)in_sizes; (void)n_in; (void)out_size;
    static EncodeFn fn = nullptr;
    static Params prm;
    if (!fn) {
        cudaDriverEntryPointQueryResult st;
        cudaGetDriverEntryPoint("cuTensorMapEncodeTiled", (void**)&fn, cudaEnableDefault, &st);
        cudaGetSymbolAddress((void**)&prm.pxn, g_xn);
        cudaGetSymbolAddress((void**)&prm.pa2, g_a2);
        cudaGetSymbolAddress((void**)&prm.tail, g_tail);
        cudaGetSymbolAddress((void**)&prm.halo, g_halo);
        cudaGetSymbolAddress((void**)&prm.stats, g_stats);
        cudaGetSymbolAddress((void**)&prm.colsum, g_colsum);
        cudaGetSymbolAddress((void**)&prm.flags, g_flags);
        cudaGetSymbolAddress((void**)&prm.epoch, g_epoch);
        cudaFuncSetAttribute(fused_kernel, cudaFuncAttributeMaxDynamicSharedMemorySize, SMEM_BYTES);
    }
    encode_rows(fn, &prm.x, d_in[0], DM, 64, 2);
    encode_images(fn, &prm.xn, prm.pxn, DM);
    encode_images(fn, &prm.a2, prm.pa2, K2);
    encode_rows(fn, &prm.out, d_out, DM, 16, 1);
    encode_w1(fn, &prm.wqkv, d_in[1], NQKV);
    encode_w1(fn, &prm.wg, d_in[4], DF);
    encode_w1(fn, &prm.wu, d_in[5], DF);
    encode_tail(fn, &prm.wu_tail, d_in[5], DM, DF, 8);
    encode_tail(fn, &prm.wd_tail, d_in[6], DF, DM, 2);
    encode_wo(fn, &prm.wo, d_in[2]);
    encode_w2(fn, &prm.wd, d_in[6], DF);
    prm.hi[0] = prm.hi[1] = HI_128B;
    prm.px = (const __nv_bfloat16*)d_in[0];
    prm.pwu = (const __nv_bfloat16*)d_in[5];
    prm.pout = (__nv_bfloat16*)d_out;
    fused_kernel<<<NCTA, 384, SMEM_BYTES>>>(prm);
}
```

```cpp
#include <cuda_runtime.h>
#include <cuda_bf16.h>
#include <cuda.h>
#include <stdint.h>
#include <limits.h>

namespace {

constexpr int SEQ = 2048, DM = 1024, DF = 3584, K2 = DM + DF, NQKV = 3 * DM;
constexpr int NGEMM = 128, NCTA = 132;
constexpr int G1_STAGES = 4, G1_STAGE_BYTES = 49152, G1_KSTEPS = 16, G1_TILES = 5;
constexpr int G2_STAGES = 6, G2_STAGE_BYTES = 32768, G2_KSTEPS = 72, G2_LATE = 40, G2_DSTEPS = 56;
constexpr int G2_HEAD = 17;
constexpr int A_BYTES = 16384;
constexpr int AUX_OFF = G1_STAGES * G1_STAGE_BYTES;
constexpr int BAR_OFF = AUX_OFF + 32768;
constexpr int PLAN_OFF = BAR_OFF + 384, STAT_OFF = BAR_OFF + 1536;
constexpr int SMEM_BYTES = BAR_OFF + 2816;
constexpr int G1_SKEW = 2, G2_SKEW = 5;
constexpr int CONSUMER_REGS = 224, AUX_REGS = 56;
constexpr int HALO_BYTES = 4096;
constexpr int LN_STEP = 3, FOLD_STEP = 14, SUM_STEP = 11, SUM2_STEP = 2;
constexpr uint32_t SUM_LOAD0 = 0x87658765u, SUM_LOAD1 = 0x65876587u;
constexpr int KEY_STEP = 2, QK_STEP = 8;
constexpr int VAL_STEP = 1, HALF_STEP = 3, PV_STEP = 9, OUT_STEPS = 4;
constexpr int UP_STEP = 2, XLOAD_STEP = 44;
constexpr int XREAD_STEP = 5, TAIL_STEP = 7;
constexpr int MEET = 4;
constexpr int PACE1 = 800, PACE2 = 1325, PACE3 = 1700;
constexpr int SHARE_MIN = 3, SHARE_MAX = 22, SHARE_LOW = 36, SHARE_SUM = 43;
constexpr int SHARE_NS = 79, SPARE_NS = 640, LATE_SCALE = 8;
constexpr float REST = 65000.f, DUE = 75100.f;

enum { F_LN = 0, F_LN2 = 1, F_FIRST = 2, F_SECOND = 3, F_SHARE = 4, F_EARLY = 5, F_LATE = 6, F_TAIL2 = 7, F_PACE = 8, F_HALO = 9 };
constexpr unsigned CNT_LN = 8, CNT_EARLY = 9, CNT_LATE = 8;

__device__ __align__(1024) __nv_bfloat16 g_xn[SEQ * DM];
__device__ __align__(1024) __nv_bfloat16 g_a2[SEQ * K2];
__device__ __align__(128) uint4 g_tail[2 * NGEMM * 512];
__device__ __align__(128) uint8_t g_halo[(2 * NGEMM + 1) * HALO_BYTES];
__device__ __align__(128) float2 g_stats[SEQ];
__device__ __align__(128) float g_colsum[18 * 1024];
__device__ __align__(128) unsigned g_flags[(F_HALO + 8) * 16 * 32];
__device__ __align__(128) unsigned g_epoch[NCTA * 16];

struct Params {
    const __nv_bfloat16 *px, *pwu;
    __nv_bfloat16 *pxn, *pa2, *pout;
    uint4* tail;
    uint8_t* halo;
    float2* stats;
    float* colsum;
    unsigned *flags, *epoch;
    unsigned long long* trace;
    uint32_t hi[2];
    CUtensorMap x, wg, wu, xn, wqkv, a2, wu_tail, wd_tail, wo, wd, out;
};

extern __shared__ __align__(1024) uint8_t smem_raw[];

#define TRACE(slot) do {} while (0)
#define TRACE_GT(slot) do {} while (0)
#define TRACE_S(slot, v, want) do {} while (0)
#define TRACE_GET(v) do {} while (0)
#define TRACE_PUT(slot, v) do {} while (0)
#define TRACE_SLOT(v, slot) do {} while (0)
#define TRACE_NEXT(v) do {} while (0)
#define TRACE_DUMP() do {} while (0)
#define TRACE_CLEAR() do {} while (0)
#define STAGE_TRACE 0
#define TRACE_END() do {} while (0)
#define TRACE_LITE(i, c) do {} while (0)
#define TRACE_RING(i) do {} while (0)
#define TRACE_STEP(t, k, i) do {} while (0)

__device__ __forceinline__ uint32_t smem_u32(const void* p) { return (uint32_t)__cvta_generic_to_shared(p); }
__device__ __forceinline__ void mbar_expect_tx(uint32_t bar, uint32_t bytes) {
    asm volatile("mbarrier.arrive.expect_tx.shared::cta.b64 _, [%0], %1;" :: "r"(bar), "r"(bytes) : "memory");
}
__device__ __forceinline__ void mbar_arrive(uint32_t bar) {
    asm volatile("mbarrier.arrive.shared::cta.b64 _, [%0];" :: "r"(bar) : "memory");
}
__device__ __forceinline__ bool mbar_try_wait(uint32_t bar, uint32_t parity) {
    uint32_t ok;
    asm volatile("{\n.reg .pred p;\nmbarrier.try_wait.parity.shared::cta.b64 p, [%1], %2;\nselp.u32 %0, 1, 0, p;\n}"
                 : "=r"(ok) : "r"(bar), "r"(parity) : "memory");
    return ok;
}
__device__ __forceinline__ void mbar_wait(uint32_t bar, uint32_t parity) {
#pragma unroll 1
    for (int spins = 0; !mbar_try_wait(bar, parity) && spins < (1 << 17); spins++) {}
}
__device__ __forceinline__ void mbar_wait(uint32_t bar, uint32_t parity, int& spins) {
    asm volatile("{\n.reg .pred p;\nagain:\nmbarrier.try_wait.parity.shared::cta.b64 p, [%1], %2;\n@p bra done;\n"
                 "add.s32 %0, %0, -1;\nsetp.gt.s32 p, %0, 0;\n@p bra again;\ndone:\n}" : "+r"(spins) : "r"(bar), "r"(parity) : "memory");
}
template <bool WARP = false> __device__ __forceinline__ unsigned flag_wait(const unsigned* p, unsigned target) {
    unsigned v;
#pragma unroll 1
    for (int spins = 0; spins < (1 << 19); spins++) {
        asm volatile("ld.acquire.gpu.global.u32 %0, [%1];" : "=r"(v) : "l"(p) : "memory");
        if (WARP ? __all_sync(0xffffffffu, (int)(v - target) >= 0) : (int)(v - target) >= 0) break;
        __nanosleep(64);
    }
    return v;
}
__device__ __forceinline__ void mbar_wait_warp(uint32_t bar, uint32_t parity) {
#pragma unroll 1
    for (int spins = 0; !__all_sync(0xffffffffu, mbar_try_wait(bar, parity)) && spins < (1 << 17); spins++) {}
}
__device__ __forceinline__ void flag_add(unsigned* p) {
    asm volatile("red.release.gpu.global.add.u32 [%0], 1;" :: "l"(p) : "memory");
}
__device__ __forceinline__ bool elect_one() {
    uint32_t ok;
    asm volatile("{\n.reg .pred p;\nelect.sync _|p, 0xffffffff;\nselp.u32 %0, 1, 0, p;\n}" : "=r"(ok));
    return ok;
}
__device__ __forceinline__ uint32_t pick(bool c, uint32_t a, uint32_t b) {
    uint32_t r;
    asm("{\n.reg .pred p;\nsetp.ne.b32 p, %3, 0;\nselp.b32 %0, %1, %2, p;\n}" : "=r"(r) : "r"(a), "r"(b), "r"((uint32_t)c));
    return r;
}
template <typename T> __device__ __forceinline__ T* offset(T* p, uint32_t bytes) {
    asm("{\n.reg .b32 lo, hi;\nmov.b64 {lo, hi}, %0;\nadd.cc.u32 lo, lo, %1;\naddc.u32 hi, hi, 0;\nmov.b64 %0, {lo, hi};\n}" : "+l"(p) : "r"(bytes));
    return p;
}
__device__ __forceinline__ void fence_proxy_async() { asm volatile("fence.proxy.async.global;" ::: "memory"); }
__device__ __forceinline__ uint4 lds128(uint32_t addr) {
    uint4 v;
    asm volatile("ld.shared.v4.u32 {%0,%1,%2,%3}, [%4];" : "=r"(v.x), "=r"(v.y), "=r"(v.z), "=r"(v.w) : "r"(addr) : "memory");
    return v;
}
__device__ __forceinline__ uint32_t lds32(uint32_t addr) {
    uint32_t v;
    asm volatile("ld.shared.u32 %0, [%1];" : "=r"(v) : "r"(addr) : "memory");
    return v;
}
__device__ __forceinline__ void sts32(uint32_t addr, uint32_t v) { asm volatile("st.shared.u32 [%0], %1;" :: "r"(addr), "r"(v) : "memory"); }
__device__ __forceinline__ uint32_t nanos() { uint32_t t; asm volatile("mov.u32 %0, %%globaltimer_lo;" : "=r"(t)); return t; }
__device__ __forceinline__ float2 lds64f(uint32_t addr) {
    float2 v;
    asm volatile("ld.shared.v2.f32 {%0,%1}, [%2];" : "=f"(v.x), "=f"(v.y) : "r"(addr) : "memory");
    return v;
}
__device__ __forceinline__ void sts128(uint32_t addr, uint4 v) {
    asm volatile("st.shared.v4.u32 [%0], {%1,%2,%3,%4};" :: "r"(addr), "r"(v.x), "r"(v.y), "r"(v.z), "r"(v.w) : "memory");
}
__device__ __forceinline__ void sts64f(uint32_t addr, float a, float b) {
    asm volatile("st.shared.v2.f32 [%0], {%1,%2};" :: "r"(addr), "f"(a), "f"(b) : "memory");
}

__device__ __forceinline__ uint64_t stream_policy() { return 0x12F0000000000000ull; }
__device__ __forceinline__ void tma_3d(uint32_t dst, const CUtensorMap* m, uint32_t bar, int c0, int c1, int c2, uint64_t pol) {
    asm volatile("cp.async.bulk.tensor.3d.shared::cluster.global.mbarrier::complete_tx::bytes.L2::cache_hint"
                 " [%0], [%1, {%3, %4, %5}], [%2], %6;"
                 :: "r"(dst), "l"(m), "r"(bar), "r"(c0), "r"(c1), "r"(c2), "l"(pol) : "memory");
}
__device__ __forceinline__ void load_stage1(uint32_t dst, uint32_t dst_b, uint32_t bar, const CUtensorMap* ma, const CUtensorMap* mb0,
                                            const CUtensorMap* mb1, int k, int ka, int row, int col0, int col1, int keep_a, uint64_t pol) {
    asm volatile("{\n.reg .pred e, p, q;\nelect.sync _|e, 0xffffffff;\nsetp.ne.and.b32 p|q, %8, 0, e;\n"
        "@p cp.async.bulk.tensor.3d.shared::cluster.global.mbarrier::complete_tx::bytes [%0], [%3, {%15, %6, %10}], [%2];\n"
        "@q cp.async.bulk.tensor.3d.shared::cluster.global.mbarrier::complete_tx::bytes.L2::cache_hint [%0], [%3, {%15, %6, %10}], [%2], %9;\n"
        "@e cp.async.bulk.tensor.2d.shared::cluster.global.mbarrier::complete_tx::bytes.multicast::cluster.L2::cache_hint"
        " [%1], [%4, {%7, %5}], [%2], %11, %9;\n"
        "@e cp.async.bulk.tensor.2d.shared::cluster.global.mbarrier::complete_tx::bytes.multicast::cluster.L2::cache_hint"
        " [%1 + 8192], [%13, {%14, %5}], [%2], %11, %9;\n"
        "@e mbarrier.arrive.expect_tx.shared::cta.b64 _, [%2], %12;\n}"
        :: "r"(dst), "r"(dst_b), "r"(bar), "l"(ma), "l"(mb0), "r"(k), "r"(row), "r"(col0), "r"(keep_a), "l"(pol), "r"(0),
           "h"((uint16_t)3), "n"(G1_STAGE_BYTES), "l"(mb1), "r"(col1), "r"(ka) : "memory");
}
__device__ __forceinline__ void load_stage2(uint32_t dst, uint32_t dst_b, uint32_t bar, const CUtensorMap* ma, const CUtensorMap* mb,
                                            int ka, int row, int col, int kb2, int kb4, uint64_t pol) {
    asm volatile("{\n.reg .pred e;\nelect.sync _|e, 0xffffffff;\n"
        "@e cp.async.bulk.tensor.3d.shared::cluster.global.mbarrier::complete_tx::bytes.L2::cache_hint [%0], [%3, {%5, %6, %10}], [%2], %9;\n"
        "@e cp.async.bulk.tensor.5d.shared::cluster.global.mbarrier::complete_tx::bytes.multicast::cluster.L2::cache_hint"
        " [%1], [%4, {%7, %10, %13, %10, %8}], [%2], %11, %9;\n"
        "@e mbarrier.arrive.expect_tx.shared::cta.b64 _, [%2], %12;\n}"
        :: "r"(dst), "r"(dst_b), "r"(bar), "l"(ma), "l"(mb), "r"(ka), "r"(row), "r"(col), "r"(kb4), "l"(pol), "r"(0),
           "h"((uint16_t)3), "n"(G2_STAGE_BYTES), "r"(kb2) : "memory");
}
__device__ __forceinline__ void load_tail(uint32_t dst, uint32_t bar, const CUtensorMap* ma, const CUtensorMap* mb, int ka, int row,
                                          int rank, int kb) {
    asm volatile("{\n.reg .pred e;\nelect.sync _|e, 0xffffffff;\n"
        "@e cp.async.bulk.tensor.3d.shared::cluster.global.mbarrier::complete_tx::bytes [%0], [%2, {%3, %4, %5}], [%1];\n"
        "@e cp.async.bulk.tensor.5d.shared::cluster.global.mbarrier::complete_tx::bytes.multicast::cluster"
        " [%9], [%6, {%5, %5, %7, %5, %10}], [%1], %11;\n"
        "@e mbarrier.arrive.expect_tx.shared::cta.b64 _, [%1], %8;\n}"
        :: "r"(dst), "r"(bar), "l"(ma), "r"(ka), "r"(row), "r"(0), "l"(mb), "r"(kb), "n"(G1_STAGE_BYTES),
           "r"(dst + A_BYTES + rank * 16384), "r"(rank * 4), "h"((uint16_t)3) : "memory");
}
__device__ __forceinline__ uint4 ldg_stream(const void* p, uint64_t pol) {
    uint4 v;
    asm volatile("ld.global.nc.L1::no_allocate.L2::cache_hint.v4.u32 {%0,%1,%2,%3}, [%4], %5;"
                 : "=r"(v.x), "=r"(v.y), "=r"(v.z), "=r"(v.w) : "l"(p), "l"(pol));
    return v;
}
__device__ __forceinline__ void st_tagged(void* p, float a, float b, uint32_t tag) {
    asm volatile("st.relaxed.gpu.global.v2.b32 [%0], {%1,%2};"
                 :: "l"(p), "r"((__float_as_uint(a) & ~3u) | tag), "r"((__float_as_uint(b) & ~3u) | tag) : "memory");
}
__device__ __forceinline__ void st_relaxed(unsigned* p, uint32_t v) {
    asm volatile("st.relaxed.gpu.global.b32 [%0], %1;" :: "l"(p), "r"(v) : "memory");
}
__device__ __forceinline__ bool untagged(const uint4& v, uint32_t tag) {
    return ((v.x ^ tag) | (v.y ^ tag) | (v.z ^ tag) | (v.w ^ tag)) & 3;
}
__device__ __forceinline__ uint4 ld_relaxed(const void* p) {
    uint4 v;
    asm volatile("ld.relaxed.gpu.global.v4.b32 {%0,%1,%2,%3}, [%4];" : "=r"(v.x), "=r"(v.y), "=r"(v.z), "=r"(v.w) : "l"(p) : "memory");
    return v;
}
__device__ __forceinline__ void prefetch_map(const CUtensorMap* m) {
    asm volatile("prefetch.tensormap [%0];" :: "l"(m) : "memory");
}
template <int N> __device__ __forceinline__ void wg_wait() { asm volatile("wgmma.wait_group.sync.aligned %0;" :: "n"(N) : "memory"); }

constexpr uint32_t HI_128B = 0x40000040, HI_64B = 0x80000020;
__device__ __forceinline__ uint32_t desc_a(uint32_t addr) { return (addr & 0x3FFFF) >> 4 | 1 << 16; }
__device__ __forceinline__ uint32_t desc_b(uint32_t addr) { return (addr & 0x3FFFF) >> 4 | 512 << 16; }

#define R8(d, o) "+f"(d[o]), "+f"(d[o+1]), "+f"(d[o+2]), "+f"(d[o+3]), "+f"(d[o+4]), "+f"(d[o+5]), "+f"(d[o+6]), "+f"(d[o+7])
#define R32(d, o) R8(d, o), R8(d, o+8), R8(d, o+16), R8(d, o+24)
#define R64(d, o) R32(d, o), R32(d, o+32)
#define ACC00 "%0,%1,%2,%3,%4,%5,%6,%7,%8,%9,%10,%11,%12,%13,%14,%15,%16,%17,%18,%19,%20,%21,%22,%23,%24,%25,%26,%27,%28,%29,%30,%31,"\
    "%32,%33,%34,%35,%36,%37,%38,%39,%40,%41,%42,%43,%44,%45,%46,%47"
#define ACC0 ACC00 ",%48,%49,%50,%51,%52,%53,%54,%55,%56,%57,%58,%59,%60,%61,%62,%63"
#define ACC1 "%64,%65,%66,%67,%68,%69,%70,%71,%72,%73,%74,%75,%76,%77,%78,%79,%80,%81,%82,%83,%84,%85,%86,%87,%88,%89,%90,%91,%92,%93,%94,%95,"\
    "%96,%97,%98,%99,%100,%101,%102,%103,%104,%105,%106,%107,%108,%109,%110,%111"
#define ACC48 "{" ACC00 "}"
#define ACC64 "{" ACC0 "}"
#define ACC112 "{" ACC0 "," ACC1 "}"
#define ACC128 "{" ACC0 "," ACC1 ",%112,%113,%114,%115,%116,%117,%118,%119,%120,%121,%122,%123,%124,%125,%126,%127}"
#define MMA_K16(shape, acc, a, b, keep, ha, hb) \
    "mov.b64 da, {" a ", " ha "};\nmov.b64 db, {" b ", " hb "};\n" \
    "wgmma.mma_async.sync.aligned." shape ".f32.bf16.bf16 " acc ", da, db, " keep ", 1, 1, 0, 1;\n"
#define MMA_NEXT(op, a, b, sa, sb) op " " a ", " a ", " sa ";\n" op " " b ", " b ", " sb ";\n"
#define MMA_STEP_B(shape, acc, a, b, keep, ha, hb, sa, sb) \
    "{\n.reg .pred p, q;\n.reg .b64 da, db;\nsetp.ne.b32 p, " keep ", 0;\nsetp.eq.b32 q, 0, 0;\nwgmma.fence.sync.aligned;\n" \
    MMA_K16(shape, acc, a, b, "p", ha, hb) MMA_NEXT("xor.b32", a, b, "2", "128") MMA_K16(shape, acc, a, b, "q", ha, hb) MMA_NEXT("add.s32", a, b, sa, sb) \
    MMA_K16(shape, acc, a, b, "q", ha, hb) MMA_NEXT("xor.b32", a, b, "2", "128") MMA_K16(shape, acc, a, b, "q", ha, hb) \
    "wgmma.commit_group.sync.aligned;\n}"
#define MMA64(shape, acc, a, b, keep) "wgmma.mma_async.sync.aligned." shape ".f32.bf16.bf16 " acc ", " a ", " b ", " keep ", 1, 1, 0, 1;\n"
#define NEXT64(op, a, b, sa, sb) "mov.b64 {lo, hi}, " a ";\n" op " lo, lo, " sa ";\nmov.b64 " a ", {lo, hi};\n" \
    "mov.b64 {lo, hi}, " b ";\n" op " lo, lo, " sb ";\nmov.b64 " b ", {lo, hi};\n"
#define ADD64(op, a, b, sa, sb) "add.s64 " a ", " a ", " sa ";\nadd.s64 " b ", " b ", " sb ";\n"
#define MMA_STEP(shape, acc, a, b, na, nb, keep, sa) MMA_STEP_N(shape, acc, a, b, na, nb, keep, sa, NEXT64)
#define MMA_STEP_N(shape, acc, a, b, na, nb, keep, sa, LAST) \
    "{\n.reg .pred p, q;\n.reg .b32 lo, hi;\nsetp.ne.b32 p, " keep ", 0;\nsetp.eq.b32 q, 0, 0;\nwgmma.fence.sync.aligned;\n" \
    MMA64(shape, acc, a, b, "p") NEXT64("xor.b32", a, b, "2", "128") MMA64(shape, acc, a, b, "q") NEXT64("add.s32", a, b, sa, "128") \
    MMA64(shape, acc, a, b, "q") NEXT64("xor.b32", a, b, "2", "128") MMA64(shape, acc, a, b, "q") LAST("add.s32", a, b, na, nb) \
    "wgmma.commit_group.sync.aligned;\n}"
#define MMA_ARGS64(sa) "+l"(da), "+l"(db) : "r"(next / 16 - 4 - sa), "r"(next / 16 - 384), "r"(keep), "n"(sa) : "memory"

__device__ __forceinline__ void mma_step(float (&d)[128], uint64_t& da, uint64_t& db, int next, int keep) {
    asm volatile(MMA_STEP("m64n256k16", ACC128, "%128", "%129", "%130", "%131", "%132", "%133") : R64(d, 0), R64(d, 64), MMA_ARGS64(2));
}
__device__ __forceinline__ void mma_rank(float (&d)[128], uint32_t a0, uint32_t a1, uint32_t db) {
    asm volatile("{\n.reg .pred q;\n.reg .b64 db;\nsetp.eq.b32 q, 0, 0;\nmov.b64 db, {%131, 0x40000040};\nwgmma.fence.sync.aligned;\n"
                 "wgmma.mma_async.sync.aligned.m64n256k16.f32.bf16.bf16 " ACC128 ", {%128, %129, %130, %130}, db, q, 1, 1, 1;\n}"
                 : R64(d, 0), R64(d, 64) : "r"(a0), "r"(a1), "r"(0), "r"(db) : "memory");
}
__device__ __forceinline__ void mma_step224(float (&d)[128], uint64_t& da, uint64_t& db, int next, int keep) {
    asm volatile(MMA_STEP("m64n224k16", ACC112, "%112", "%113", "%114", "%115", "%116", "%117")
                 : R64(d, 0), R32(d, 64), R8(d, 96), R8(d, 104), MMA_ARGS64(2));
}
template <int SA> __device__ __forceinline__ void mma_step(float (&d)[64], uint64_t& da, uint64_t& db, int next, int keep) {
    asm volatile(MMA_STEP("m64n128k16", ACC64, "%64", "%65", "%66", "%67", "%68", "%69") : R64(d, 0), MMA_ARGS64(SA));
}
template <int SA> __device__ __forceinline__ void mma_step_c(float (&d)[64], uint64_t& da, uint64_t& db, int next, int keep,
                                                           uint64_t high = 0) {
    asm volatile(MMA_STEP_N("m64n128k16", ACC64, "%64", "%65", "%66", "%67", "%68", "%69", ADD64) : R64(d, 0), "+l"(da), "+l"(db)
                 : "l"((high << 32) + (next / 16 - 4 - SA)), "l"((int64_t)next / 16 - 384), "r"(keep), "n"(SA) : "memory");
}
__device__ __forceinline__ void mma_step96(float (&d)[64], uint64_t& da, uint64_t& db, int next, int keep) {
    asm volatile(MMA_STEP("m64n96k16", ACC48, "%48", "%49", "%50", "%51", "%52", "%53") : R32(d, 0), R8(d, 32), R8(d, 40), MMA_ARGS64(254));
}
__device__ __forceinline__ void mma_step_tail(float (&d)[128], uint32_t da, uint32_t b, int keep, bool down) {
    uint32_t db = (b & 0x3FFFF) >> 4 | 256 << 16;
    asm volatile(MMA_STEP_B("m64n256k16", ACC128, "%128", "%129", "%130", "%131", "0x80000040", "%132", "-96")
                 : R64(d, 0), R64(d, 64), "+r"(da), "+r"(db) : "r"(keep), "r"(down ? HI_64B : HI_128B), "r"(down ? 254 : 2) : "memory");
}

__device__ __forceinline__ uint32_t pack_bf16(float lo, float hi) {
    uint32_t r; asm("cvt.rn.bf16x2.f32 %0, %1, %2;" : "=r"(r) : "f"(hi), "f"(lo)); return r;
}
__device__ __forceinline__ float bf_lo(uint32_t v) { return __uint_as_float(v << 16); }
__device__ __forceinline__ float bf_hi(uint32_t v) { return __uint_as_float(v & 0xffff0000u); }
__device__ __forceinline__ float round_bf16(float v) { return bf_lo(pack_bf16(v, 0.f)); }
__device__ __forceinline__ uint32_t mul_bf16x2(uint32_t a, uint32_t b) {
    uint32_t r; asm("mul.rn.bf16x2 %0, %1, %2;" : "=r"(r) : "r"(a), "r"(b)); return r;
}
__device__ __forceinline__ uint32_t sub_bf16x2(uint32_t a, uint32_t b) {
    uint32_t r; asm("sub.rn.bf16x2 %0, %1, %2;" : "=r"(r) : "r"(a), "r"(b)); return r;
}
__device__ __forceinline__ uint32_t mul2_bf16x2(uint32_t a, uint32_t hi, uint32_t lo) {
    uint32_t r; asm("fma.rn.bf16x2 %0, %1, %2, %3;" : "=r"(r) : "r"(a), "r"(hi), "r"(mul_bf16x2(a, lo))); return r;
}
__device__ __forceinline__ float tanh_fast(float x) { float r; asm("tanh.approx.f32 %0, %1;" : "=f"(r) : "f"(x)); return r; }
__device__ __forceinline__ float gelu_twice(float g) {
    return fmaf(g, tanh_fast(fmaf(g * g, 0.044715f * 0.7978845608f, 0.7978845608f) * g), g);
}
__device__ __forceinline__ uint32_t geglu2(uint32_t g2, uint32_t u2) {
    return mul_bf16x2(pack_bf16(gelu_twice(bf_lo(g2)), gelu_twice(bf_hi(g2))), u2);
}
__device__ __forceinline__ uint32_t silu2(float lo, float hi) {
    const uint32_t h = mul_bf16x2(pack_bf16(lo, hi), 0x3e803e80u);
    return pack_bf16(fmaf(bf_lo(h), tanh_fast(bf_lo(h)), bf_lo(h)), fmaf(bf_hi(h), tanh_fast(bf_hi(h)), bf_hi(h)));
}
__device__ __forceinline__ float ex2_fast(float x) { float r; asm("ex2.approx.ftz.f32 %0, %1;" : "=f"(r) : "f"(x)); return r; }
__device__ __forceinline__ void unpack8(uint4 v, float (&f)[8]) {
    f[0] = bf_lo(v.x); f[1] = bf_hi(v.x); f[2] = bf_lo(v.y); f[3] = bf_hi(v.y);
    f[4] = bf_lo(v.z); f[5] = bf_hi(v.z); f[6] = bf_lo(v.w); f[7] = bf_hi(v.w);
}
template <int N> __device__ __forceinline__ void fence_regs(float (&d)[N]) {
#pragma unroll
    for (int i = 0; i < N; i++) asm volatile("" : "+f"(d[i]) :: "memory");
}

__device__ __forceinline__ float rcp_fast(float x) { float r; asm("rcp.approx.ftz.f32 %0, %1;" : "=f"(r) : "f"(x)); return r; }
__device__ __forceinline__ float sqrt_fast(float x) { float r; asm("sqrt.approx.ftz.f32 %0, %1;" : "=f"(r) : "f"(x)); return r; }
__device__ __forceinline__ uint32_t max_bf16x2(uint32_t a, uint32_t b) {
    uint32_t r; asm("max.bf16x2 %0, %1, %2;" : "=r"(r) : "r"(a), "r"(b)); return r;
}
__device__ __forceinline__ uint32_t transpose8(uint32_t a) {
    uint32_t r; asm volatile("movmatrix.sync.aligned.m8n8.trans.b16 %0, %1;" : "=r"(r) : "r"(a)); return r;
}
__device__ __forceinline__ void mma_sync(uint32_t* d, const uint32_t* a, uint32_t b0, uint32_t b1, const uint32_t* c) {
    asm volatile("mma.sync.aligned.m16n8k16.row.col.f32.bf16.bf16.f32 {%0,%1,%2,%3}, {%4,%5,%6,%7}, {%8,%9}, {%10,%11,%12,%13};"
        : "=r"(d[0]), "=r"(d[1]), "=r"(d[2]), "=r"(d[3])
        : "r"(a[0]), "r"(a[1]), "r"(a[2]), "r"(a[3]), "r"(b0), "r"(b1), "r"(c[0]), "r"(c[1]), "r"(c[2]), "r"(c[3]));
}
template <int N> struct Floats {
    float f[N];
    __device__ __forceinline__ Floats() {}
    __device__ __forceinline__ Floats(const uint32_t* p) {
#pragma unroll
        for (int i = 0; i < N; i++) asm("mov.b32 %0, %1;" : "=f"(f[i]) : "r"(p[i]));
    }
    __device__ __forceinline__ void put(uint32_t* p) const {
#pragma unroll
        for (int i = 0; i < N; i++) asm("mov.b32 %0, %1;" : "=r"(p[i]) : "f"(f[i]));
    }
    __device__ __forceinline__ float& operator[](int i) { return f[i]; }
};
__device__ __forceinline__ uint32_t fresh_tid() { uint32_t r; asm volatile("mov.u32 %0, %%tid.x;" : "=r"(r)); return r; }
template <typename T> __device__ __forceinline__ T uniform(T v) { return __shfl_sync(0xffffffffu, v, 0); }

__device__ __forceinline__ uint32_t forecast(uint32_t n0, uint32_t c0, float cycles, uint32_t tag) {
    const uint32_t n = nanos();
    return n + (int)((n - n0) * cycles * rcp_fast((uint32_t)clock() - c0)) & ~3u | tag;
}
__device__ __forceinline__ uint32_t plan_word(uint32_t base, int lane) { return uniform(lds32(base + PLAN_OFF + lane * 4)); }

__device__ __forceinline__ void fold_operands(const Params& prm, uint32_t base, int slot, int mblk, uint32_t tag, int w, int lane) {
    uint4 v[9];
#pragma unroll
    for (int m = 0; m < 9; m++) v[m] = make_uint4(0, 0, 0, 0);
    const float* parts = prm.colsum + (slot * 2 + (lane >> 4)) * 1024 + w * 64 + (lane & 15) * 4;
    const float* const rows = &offset(prm.stats, (mblk * 128 + w * 64 + lane * 2) * 8)->x;
#pragma unroll 1
    for (int spins = 0; spins < (1 << 16); spins++) {
        bool missing = false;
        asm volatile("" : "+l"(parts));
#pragma unroll
        for (int m = 0; m < 9; m++) {
            if (untagged(v[m], tag)) {
                missing = true;
                v[m] = ld_relaxed(m < 8 ? parts + m * 128 : rows);
            }
        }
        if (!missing) break;
    }
    float4 c = make_float4(0.f, 0.f, 0.f, 0.f);
#pragma unroll
    for (int m = 0; m < 8; m++) {
        c.x += __uint_as_float(v[m].x ^ tag); c.y += __uint_as_float(v[m].y ^ tag);
        c.z += __uint_as_float(v[m].z ^ tag); c.w += __uint_as_float(v[m].w ^ tag);
    }
    sts128(base + STAT_OFF + w * 512 + lane * 16, make_uint4(v[8].x ^ tag, v[8].y ^ tag, v[8].z ^ tag, v[8].w ^ tag));
    const uint32_t ca = base + AUX_OFF + w * 8192 + (lane >> 4) * 16384 + (lane & 15) * 8;
#pragma unroll
    for (int r = 0; r < 3; r++) {
        const uint32_t lo = pack_bf16(c.x, c.y), hi = pack_bf16(c.z, c.w);
        sts64f((ca ^ r * 16) + r * 128, __uint_as_float(lo), __uint_as_float(hi));
        c.x -= bf_lo(lo); c.y -= bf_hi(lo); c.z -= bf_lo(hi); c.w -= bf_hi(hi);
    }
    asm volatile("fence.proxy.async.shared::cta;" ::: "memory");
    __syncwarp();
}
__device__ __forceinline__ float2 fold(float (&acc)[128], uint32_t base, int wg) {
    const uint32_t id = fresh_tid(), sp = base + STAT_OFF + (id & 96) * 8 + (id & 28) * 4 + wg * 8;
    const uint32_t sel = id & 2 ? 0x4444 : (id & 1 ? 0x4432 : 0x3232);
    const float2 sa = lds64f(sp), sb = lds64f(sp + 128);
    mma_rank(acc, __byte_perm(__float_as_uint(sa.x), 0, sel), __byte_perm(__float_as_uint(sb.x), 0, sel), desc_b(base + AUX_OFF));
    return make_float2(sa.y, sb.y);
}

__device__ __forceinline__ void tail_gemm(const Params& prm, uint32_t base, uint32_t t0, unsigned epoch, int grp, int warp, int lane) {
    const uint32_t full = base + BAR_OFF, empty = full + 32, sig = full + 192, dep = full + 256, folded = full + 320;
    const uint32_t tag = 1 + (epoch & 1);
    auto plan = [&](uint32_t p, uint32_t word) { return p < 4 ? p * 64 + grp / 2 * 32 + 15 : word >> p % 4 * 8 & 255; };
    auto rows = [&](uint32_t job) { return job / 32 * 2 + grp % 2; };
    if (warp == 8) {
        if (elect_one()) { prefetch_map(&prm.xn); prefetch_map(&prm.a2); prefetch_map(&prm.wd_tail); }
#pragma unroll 1
        for (int p = 0, i = G1_STAGES; p < 8; p++) {
            const bool first = p < 4;
            if (p == 4) mbar_wait_warp(dep + 16, 0);
            const uint32_t job = plan(p, plan_word(base, lane));
#pragma unroll 1
            for (int k = p ? 0 : G1_STAGES; k <= job % 32; k++, i++) {
                if (p == 3 && k % 2 == grp / 2)
                    asm volatile("{\n.reg .pred e;\nelect.sync _|e, 0xffffffff;\n"
                        "@e cp.async.bulk.prefetch.tensor.5d.L2.global [%0, {%2, %2, %1, %2, %3}];\n}"
                        :: "l"(&prm.wd_tail), "r"(k * 8), "r"(0), "r"(grp % 2 * 4) : "memory");
                if (i == 16 || i == 24 || k == 16) mbar_wait_warp(dep + (first ? i & 8 : 24), 0);
                TRACE_S(62, i, 16); TRACE_S(63, i, 4);
                mbar_wait_warp(empty + (i & 3) * 8, ~i >> 2 & 1);
                load_tail(base + (i & 3) * G1_STAGE_BYTES, full + (i & 3) * 8, first ? (p ? &prm.xn : &prm.x) : &prm.a2,
                          first ? &prm.wu_tail : &prm.wd_tail, p ? 0 : k * 64,
                          p ? (first ? rows(job) * G1_KSTEPS + k : rows(job) * G2_KSTEPS + 16 + k) * 128 : rows(job) * 64, grp % 2, first ? k * 2 : k * 8);
            }
        }
        return;
    }
    if (warp == 9) {
        const uint32_t n0 = nanos(), c0 = clock();
#pragma unroll 1
        for (int j = 0; j < 3; j++) {
            flag_wait<true>(prm.flags + (F_LN + j) * 512 + (j < 2 ? lane % 4 * 4 + grp : lane % 16) * 32, epoch * CNT_LN);
            fence_proxy_async();
            __syncwarp();
            if (lane == 0 && j < 2) mbar_arrive(dep + j * 8);
        }
        mbar_wait_warp(sig + 8, 0);
        if (lane == 0) st_relaxed(prm.flags + F_PACE * 512 + 64 + grp, forecast(n0, c0, DUE, tag));
        uint4 v, w;
#pragma unroll 1
        for (int spins = 0; spins < (1 << 19); spins++) {
            v = ld_relaxed(prm.flags + F_PACE * 512 + lane / 2 * 4);
            w = ld_relaxed(prm.flags + F_PACE * 512 + 64);
            if (!__any_sync(0xffffffffu, untagged(v, tag) || untagged(w, tag))) break;
            __nanosleep(256);
        }
        const uint32_t ref = uniform(v.x);
        const int due = min(max((int)((grp & 2 ? w.z : w.x) - ref), -100000), 100000) * 8;
        int late = max(max((int)(v.x - ref), (int)(v.y - ref)), max((int)(v.z - ref), (int)(v.w - ref)));
        late = min(max(max(late, __shfl_xor_sync(0xffffffffu, late, 2)), -100000), 100000) * LATE_SCALE + lane / 4;
        TRACE_PUT(16 + lane / 4, late + (1 << 20));
        int place = 0, n = SHARE_MIN;
#pragma unroll 1
        for (int g = 0; g < 32; g += 4) place += __shfl_sync(0xffffffffu, late, g) > late;
        const bool swap = (__reduce_add_sync(0xffffffffu, place + 1 & 2 ? late : -late) ^ w.x - w.z) >> 31;
        const bool mine = (place + 1 >> 1 & 1 ^ swap) == grp / 2;
#pragma unroll 1
        for (int j = 4 * SHARE_MIN; j < SHARE_SUM; j++) {
            const int most = __reduce_max_sync(0xffffffffu, mine && n < SHARE_MAX ? late : INT_MIN);
            if (j >= SHARE_LOW && due + (j - 38) * SPARE_NS * 8 > most) break;
            if (j == 38) TRACE_PUT(32, most - due + (1 << 20));
            if (most == late) { n++; late -= SHARE_NS * 8; }
        }
        auto first = [](uint32_t bits, int n) { return bits & (1u << min(max(n, 0), 24)) - 1; };
        const uint32_t job = lane / 4 * 32 + n - 1;
        if (mine) st_relaxed(offset(prm.flags, rows(job) * 128) + F_SHARE * 512,
                             epoch << 24 | first(0x2aaaaa, 2 * n) | first(0x104104, 6 * n - 66) | first(0x10410, 6 * n - 90) |
                             first(0x41041, 6 * n - 108));
        if (mine) TRACE_PUT(24 + lane / 4, n);
        sts32(base + PLAN_OFF, __reduce_or_sync(0xffffffffu, mine ? job << place / 2 * 8 : 0));
        if (lane == 0) mbar_arrive(dep + 16);
        flag_wait<true>(offset(prm.flags, lane % 16 * 128) + F_SECOND * 512, epoch * CNT_LN);
        fence_proxy_async();
        __syncwarp();
        if (lane == 0) mbar_arrive(dep + 24);
        return;
    }
    if (warp > 9) {
#pragma unroll 1
        for (int j = 0; j < 8; j++) sts128(base + AUX_OFF + (warp - 10) * 8192 + (j & 4) * 4096 + (j & 3) * 512 + lane * 16, make_uint4(0, 0, 0, 0));
        while ((uint32_t)clock() - t0 < 9000) __nanosleep(256);
        fold_operands(prm, base, 8, grp, tag, warp - 10, lane);
        if (lane) return;
        mbar_arrive(folded);
        if (warp == 11) return;
        TRACE(60);
#pragma unroll 1
        for (int p = 0; p < 8; p++) {
            mbar_wait(sig + p * 8, 0);
            flag_add(prm.flags + (p < 4 ? F_EARLY : F_TAIL2) * 512 + rows(plan(p, lds32(base + PLAN_OFF))) * 32);
            TRACE_S(50, p, 3); TRACE_S(51, p, 7);
        }
        prm.epoch[blockIdx.x * 16] = epoch;
        TRACE_DUMP();
        return;
    }
    asm volatile("setmaxnreg.inc.sync.aligned.u32 %0;" :: "n"(CONSUMER_REGS) : "memory");
    const uint32_t da = desc_a(base + (warp >> 2) * 8192);
    uint4* out = prm.tail;
    float acc[128];
    uint32_t pk[64];
    float2 inv = make_float2(0.f, 0.f);
    int i = 0, last;
    uint32_t peer;
    asm volatile("mapa.shared::cluster.u32 %0, %1, %2;" : "=r"(peer) : "r"(empty), "r"(lane & 1));
    auto release = [&]() {
        if ((threadIdx.x & 126) == 0 && i <= last)
            asm volatile("mbarrier.arrive.shared::cluster.b64 _, [%0];" :: "r"(peer + (i - 1 & 3) * 8) : "memory");
    };
    auto store = [&](int j) {
        asm volatile("st.global.v4.u32 [%0], {%1,%2,%3,%4};" :: "l"(out + j / 2 * 8192 + j % 2 * 256),
                     "r"(pk[4 * j]), "r"(pk[4 * j + 1]), "r"(pk[4 * j + 2]), "r"(pk[4 * j + 3]) : "memory");
    };
    auto step = [&](int k, int left) {
        mbar_wait(full + (i & 3) * 8, i >> 2 & 1);
        TRACE_S(45, warp * 128 + i, 0);
        if (warp >= 4 && left == G1_SKEW) asm volatile("bar.sync 1, 256;" ::: "memory");
        mma_step_tail(acc, da + (i & 3) * (G1_STAGE_BYTES / 16), base + A_BYTES + (i & 3) * G1_STAGE_BYTES, k, i >= 4 * G1_KSTEPS);
        if (warp < 4 && left == 1) asm volatile("bar.arrive 1, 256;" ::: "memory");
    };
    auto drip = [&](int p, int& n) {
        if (n > 0) { store(0); store(1); }
#pragma unroll
        for (int j = 8; j < 64; j++) asm volatile("mov.b32 %0, %1;" : "=r"(pk[j - 8]) : "r"(pk[j]));
        out += 8192;
        __syncwarp();
        if (--n == 0 && lane == 0) mbar_arrive(sig + p * 8 - 8);
    };
#pragma unroll
    for (int j = 0; j < 128; j++) asm volatile("mov.b32 %0, 0;" : "=f"(acc[j]));
#pragma unroll
    for (int j = 0; j < 64; j++) asm volatile("mov.b32 %0, 0;" : "=r"(pk[j]));
#pragma unroll 1
    for (int p = 0; p < 8; p++) {
        step(0, 0);
        i++;
        const uint32_t word = plan_word(base, lane), job = plan(p, word);
        last = __dp4a(word & 0x1f1f1f1fu, 0x01010101u, 4u * G1_KSTEPS);
#pragma unroll 1
        for (int left = job % 32, n = p ? 8 : 0; left > 0; left--) {
            if (i == G1_KSTEPS - 1) { mbar_wait(folded, 0); inv = fold(acc, base, warp >> 2); }
#pragma unroll 1
            do drip(p, n); while (n & 7 >> 31 - __clz(job % 32));
            step(1, left);
            wg_wait<1>();
            release();
            i++;
        }
        wg_wait<0>();
        fence_regs(acc);
        release();
        if (p == 0) {
#pragma unroll
            for (int j = 0; j < 128; j++) acc[j] *= j & 2 ? inv.y : inv.x;
            fence_regs(acc);
        }
        if (warp == 4) TRACE_PUT(46 + p + p / 4 * 3, (uint32_t)clock());
#pragma unroll
        for (int j = 0; j < 64; j++) pk[j] = pack_bf16(acc[2 * j], acc[2 * j + 1]);
        out = prm.tail + p / 4 * NGEMM * 512 + rows(job) * 512 + threadIdx.x;
    }
#pragma unroll
    for (int j = 0; j < 16; j++) store(j);
    __syncwarp();
    TRACE_S(58, warp, 4);
    if (lane == 0) mbar_arrive(sig + 56);
}

__device__ __forceinline__ int gate_col(int t, int nslot) { return t == 2 ? 960 + nslot * 64 : max(t * 1024 - 1536, 0) + nslot * 128; }

struct Role {
    int rank, role, mblk, nslot;
    __device__ __forceinline__ Role() {
        uint32_t id;
        asm volatile("mov.u32 %0, %%ctaid.x;" : "=r"(id));
        const uint32_t cl = id / 2;
        rank = id & 1;
        role = pick(cl < 4, 32 + cl * 8, cl - 8 + max(4u, (cl - 1) * 37 >> 8)) * 2 + rank;
        mblk = role & 15; nslot = role >> 4;
    }
};

__global__ void __cluster_dims__(2, 1, 1) __launch_bounds__(384, 1)
fused_kernel(const __grid_constant__ Params prm) {
    TRACE_GET(c0);
    const uint32_t base = smem_u32(smem_raw) & ~1023u;
    const uint32_t bars = base + BAR_OFF;
    auto full1 = [&](int s) { return bars + s * 8; };
    auto empty1 = [&](int s) { return bars + 32 + s * 8; };
    auto full2 = [&](int s) { return bars + 64 + s * 8; };
    auto empty2 = [&](int s) { return bars + 128 + s * 8; };
    const uint32_t sig_bar = bars + 192, dep_bar = bars + 256, cs_bar = bars + 304, fold_bar = bars + 320, x_bar = bars + 352;
    const uint32_t halo_bar = dep_bar + 32;
    auto stage2 = [&](int q) { return base + q * G2_STAGE_BYTES; };
    const uint32_t aux = base + AUX_OFF;

    asm volatile("{\n.reg .pred p;\nsetp.eq.u32 p, %1, 0;\n@p mbarrier.init.shared::cta.b64 [%0], 1;\n"
        "fence.mbarrier_init.release.cluster;\nbarrier.cluster.arrive.relaxed.aligned;\n}" :: "r"(bars), "r"(threadIdx.x) : "memory");
    const int warp = __shfl_sync(0xffffffffu, threadIdx.x >> 5, 0);
    auto cluster_wait = []() { asm volatile("barrier.cluster.wait.acquire.aligned;" ::: "memory"); };
    if ((warp | (blockIdx.x & NGEMM)) == 8) {
        const Role r;
        asm volatile("{\n.reg .pred e;\nelect.sync _|e, 0xffffffff;\n"
            "@e prefetch.tensormap [%0];\n@e prefetch.tensormap [%1];\n}" :: "l"(&prm.x), "l"(&prm.wg + r.rank) : "memory");
        cluster_wait();
        load_stage1(base, base + A_BYTES + r.rank * 16384, full1(0), &prm.x, &prm.wg + r.rank, &prm.wg + r.rank, 0, 0, r.mblk * 64,
                    r.nslot * 128, r.nslot * 128 + 64, 0, stream_policy());
    } else {
        cluster_wait();
    }
    const uint32_t t0 = clock();
    {
        uint32_t cta;
        asm volatile("mov.u32 %0, %%ctaid.x;" : "=r"(cta));
        if ((warp | (~cta & NGEMM)) == 8) load_tail(base, full1(0), &prm.x, &prm.wu_tail, 0, (cta - NGEMM) * 64, cta & 1, 0);
    }
    asm volatile("{\n.reg .pred e, q;\nelect.sync _|e, 0xffffffff;\nsetp.ne.and.u32 q, %2, 0, e;\n"
        "@q mbarrier.init.shared::cta.b64 [%0], %1;\n@e mbarrier.init.shared::cta.b64 [%0 + 8], %1;\n"
        "@e mbarrier.init.shared::cta.b64 [%0 + 16], %1;\n@e mbarrier.init.shared::cta.b64 [%0 + 24], %1;\n"
        "fence.mbarrier_init.release.cluster;\nbarrier.cluster.arrive.relaxed.aligned;\n}"
        :: "r"(bars + warp * 32), "r"(1 << (0x10fa08 >> warp * 2 & 3)), "r"(warp) : "memory");
    const int lane = threadIdx.x & 31;
    const Role me;
    const int rank = me.rank, role = me.role, mblk = me.mblk, nslot = me.nslot;
    const CUtensorMap* const w0 = &prm.wg + rank;

    unsigned* const flags = prm.flags + mblk * 32;
    if (warp >= 8) {
        asm volatile("setmaxnreg.dec.sync.aligned.u32 %0;" :: "n"(AUX_REGS));
        if (warp == 9) { TRACE_CLEAR(); TRACE_GT(0); TRACE_PUT(1, c0); }
        if ((warp | (~blockIdx.x & NGEMM)) == 8) {
#pragma unroll 1
            for (int i = 1; i < G1_STAGES; i++) {
                if (i == 1) cluster_wait();
                TRACE_S(57, i, 1);
                load_tail(base + i * G1_STAGE_BYTES, full1(i), &prm.x, &prm.wu_tail, i * 64, (blockIdx.x - NGEMM) * 64, blockIdx.x & 1, i * 2);
            }
        } else {
            cluster_wait();
        }
    }

    if (blockIdx.x >= NGEMM) {
        if (warp < 8) cluster_wait();
        const uint32_t seen = __ldcg(prm.epoch + blockIdx.x * 16);
        tail_gemm(prm, base, t0, seen + 1, blockIdx.x - NGEMM, warp, lane);
    } else if (warp == 9) {
        const unsigned epoch = __ldcg(prm.epoch + blockIdx.x * 16 + 2) + 1;
        const uint32_t n0 = nanos(), c1 = clock();
        {
            const __nv_bfloat16* const w = prm.pwu + ((mblk >> 1) * 128 + lane / 2) * DF + gate_col(4, nslot) + 96 + rank * 16 + lane % 2 * 8;
            uint4 v[8];
            float cs[8], f[8];
            mbar_wait(empty1(SUM2_STEP), 0);
#pragma unroll
            for (int j = 0; j < 8; j++) v[j] = __ldg(reinterpret_cast<const uint4*>(w + j * 16 * DF));
            unpack8(v[0], cs);
#pragma unroll
            for (int j = 1; j < 8; j++) {
                unpack8(v[j], f);
#pragma unroll
                for (int d = 0; d < 8; d++) cs[d] += f[d];
            }
#pragma unroll
            for (int d = 0; d < 4; d++)
                cs[d] = (lane & 16 ? cs[d + 4] : cs[d]) + __shfl_xor_sync(0xffffffffu, lane & 16 ? cs[d] : cs[d + 4], 16);
#pragma unroll
            for (int d = 0; d < 2; d++) {
                cs[d] = (lane & 8 ? cs[d + 2] : cs[d]) + __shfl_xor_sync(0xffffffffu, lane & 8 ? cs[d] : cs[d + 2], 8);
                cs[d] += __shfl_xor_sync(0xffffffffu, cs[d], 4);
                cs[d] += __shfl_xor_sync(0xffffffffu, cs[d], 2);
            }
            if (!(lane & 6))
                st_tagged(prm.colsum + (16 + nslot / 4) * 1024 + (mblk >> 1) * 128 + nslot % 4 * 32 + rank * 16 + lane % 2 * 8 + (lane >> 3) * 2,
                          cs[0], cs[1], 1 + (epoch & 1));
            TRACE(61);
        }
        if (lane == 0) {
            mbar_wait(sig_bar, 0);
            TRACE(11);
            flag_add(flags + F_LN * 512);
            TRACE(42);
            flag_wait(flags + F_LN * 512, epoch * CNT_LN);
            fence_proxy_async();
            mbar_arrive(dep_bar);
            mbar_wait(sig_bar + 56, 0);
            flag_add(flags + F_LN2 * 512);
            flag_wait(flags + F_LN2 * 512, epoch * CNT_LN);
            fence_proxy_async();
            mbar_arrive(dep_bar + 40);
            TRACE(59);
            prm.epoch[blockIdx.x * 16 + 2] = epoch;
#pragma unroll 1
            for (int p = 3; p < 7; p++) {
                mbar_wait(sig_bar + (p == 3 ? 16 : p * 8), 0);
                TRACE_S(37, p, 4);
                flag_add(flags + (p - (p < F_EARLY)) * 512);
                TRACE_S(43, p, 4);
                if (p == 3 && rank == 0) {
                    mbar_wait(sig_bar + 24, 0);
                    st_relaxed(prm.flags + F_PACE * 512 + mblk * 4 + nslot, forecast(n0, c1, REST, 1 + (epoch & 1)));
                }
            }
        }
    } else if (warp < 8) {
        asm volatile("setmaxnreg.inc.sync.aligned.u32 %0;" :: "n"(CONSUMER_REGS));
        const int wg = __shfl_sync(0xffffffffu, threadIdx.x >> 7, 0);
        const int cw = threadIdx.x >> 5;
        const int tid = threadIdx.x & 127;
        int spins = 1 << 18;
        float acc[128];
        uint32_t pk[64];
#pragma unroll
        for (int i = 0; i < 64; i++) asm volatile("mov.b32 %0, 0;" : "=r"(pk[i]));
#pragma unroll
        for (int i = 0; i < 128; i++) asm volatile("mov.b32 %0, 0;" : "=f"(acc[i]));
        cluster_wait();

        auto row0 = [&](uint32_t id) { return mblk * 128 + (id & 96) + wg; };
        __nv_bfloat16* optr = const_cast<__nv_bfloat16*>(prm.px) + (mblk * 128 + nslot * 16 + cw * 2) * DM + lane * 8;
        uint64_t da = desc_a(base + wg * 8192) | (uint64_t)prm.hi[0] << 32, db = desc_b(base + A_BYTES) | (uint64_t)prm.hi[1] << 32;
        auto next1 = [](int s) { return ((s + 1) % G1_STAGES - s) * G1_STAGE_BYTES; };
        auto next2 = [](int q) { return ((q + 1) % G2_STAGES - q) * G2_STAGE_BYTES; };
        uint32_t peer_bars;
        asm volatile("mapa.shared::cluster.u32 %0, %1, %2;" : "=r"(peer_bars) : "r"(bars), "r"(tid & 1));
        if (tid >= 2) peer_bars = 0;
        auto release = [&](uint32_t bar) {
            if (peer_bars) asm volatile("mbarrier.arrive.shared::cluster.b64 _, [%0];" :: "r"(peer_bars + (bar - bars)) : "memory");
        };
        auto up = [](int i) { return 32 + (i & 24) + (i & 3) * 2 + (i >> 2 & 1); };
        auto store_pk = [&](__nv_bfloat16* p, int j) {
            asm volatile("st.global.v4.u32 [%0], {%1,%2,%3,%4};"
                         :: "l"(p), "r"(pk[4 * j]), "r"(pk[4 * j + 1]), "r"(pk[4 * j + 2]), "r"(pk[4 * j + 3]) : "memory");
        };
        auto chunk_geglu = [&](int j) {
#pragma unroll
            for (int i = 4 * j; i < 4 * j + 4; i++) pk[i] = geglu2(pk[i], pk[up(i)]);
            store_pk(optr + (j & 1) * 256 + (j & 2) * 1024 + (j & 4) * 2048, j);
        };
        auto signal_stores = [&](int p) { __syncwarp(); if (lane == 0) mbar_arrive(sig_bar + p * 8); };

        auto chunk_ln = [&](int k) {
            Floats<6> mo(pk + 32);
            if (k == 0) {
                const uint4* xp = reinterpret_cast<const uint4*>(optr);
                pk[38] = __ldcg(prm.epoch + blockIdx.x * 16 + 2);
#pragma unroll
                for (int i = 0; i < 8; i++) {
                    const uint4 v = ldg_stream(xp + i * 32, stream_policy());
                    pk[4 * i] = v.x; pk[4 * i + 1] = v.y; pk[4 * i + 2] = v.z; pk[4 * i + 3] = v.w;
                }
            } else if (k >= LN_STEP && k < LN_STEP + 3) {
                if (k == LN_STEP) {
                    mo[0] = bf_lo(uniform(pk[0])); mo[1] = bf_lo(uniform(pk[16]));
                    mo[2] = mo[3] = mo[4] = mo[5] = 0.f;
                }
#pragma unroll
                for (int i = (k - LN_STEP) * 11; i < (k - LN_STEP) * 11 + 11 && i < 32; i++) {
                    const int r = i & 1;
                    const uint32_t w = pk[r * 16 + i / 2];
                    const float lo = bf_lo(w) - mo[r], hi = bf_hi(w) - mo[r];
                    mo[2 + r] += lo + hi;
                    mo[4 + r] = fmaf(hi, hi, fmaf(lo, lo, mo[4 + r]));
                }
                mo.put(pk + 32);
            } else if (k == LN_STEP + 3) {
                const bool second = lane & 16;
                float m1 = (second ? mo[3] : mo[2]) + __shfl_xor_sync(0xffffffffu, second ? mo[2] : mo[3], 16);
                float m2 = (second ? mo[5] : mo[4]) + __shfl_xor_sync(0xffffffffu, second ? mo[4] : mo[5], 16);
#pragma unroll
                for (int o = 8; o > 0; o >>= 1) {
                    m1 += __shfl_xor_sync(0xffffffffu, m1, o);
                    m2 += __shfl_xor_sync(0xffffffffu, m2, o);
                }
                m1 *= 1.f / DM;
                const float var = fmaxf(fmaf(-m1, m1, m2 * (1.f / DM)), 0.f);
                const float mean = round_bf16((second ? mo[1] : mo[0]) + m1);
                const float inv = rcp_fast(round_bf16(sqrt_fast(round_bf16(round_bf16(var) + 1e-5f))));
                if ((lane & 15) == 0) st_tagged(prm.stats + (uint32_t)(optr - prm.px) / DM + second, -mean, inv, 2 - (pk[38] & 1));
                const uint32_t id = fresh_tid();
                optr = prm.pxn + mblk * 128 * DM + nslot * 512 + (id & 24) * 1024 + (id & 224) * 2 + (id & 7 ^ id >> 5) * 8;
                const uint32_t split = pack_bf16(inv - round_bf16(inv), inv);
#pragma unroll
                for (int r = 0; r < 2; r++) {
                    const uint32_t f = __shfl_sync(0xffffffffu, split, r * 16);
                    pk[32 + 3 * r] = __byte_perm(__shfl_sync(0xffffffffu, __float_as_uint(mean), r * 16), 0, 0x3232);
                    pk[33 + 3 * r] = __byte_perm(f, 0, 0x3232);
                    pk[34 + 3 * r] = __byte_perm(f, 0, 0x1010);
                }
            } else if (k >= LN_STEP + 4 && k < LN_STEP + 8) {
#pragma unroll
                for (int i = k - LN_STEP - 4; i < 8; i += 4) {
                    const uint32_t* n = pk + 32 + i / 4 * 3;
#pragma unroll
                    for (int j = 4 * i; j < 4 * i + 4; j++) pk[j] = mul2_bf16x2(sub_bf16x2(pk[j], n[0]), n[1], n[2]);
                    store_pk(optr + i % 4 * 32768 + i / 4 * 4096, i);
                }
                if (k == LN_STEP + 5 || k == LN_STEP + 7) signal_stores(k == LN_STEP + 5 ? 0 : 7);
            } else if (k == FOLD_STEP) {
                mbar_wait(fold_bar, 0, spins);
                const float2 inv = fold(acc, base, wg);
                mo[0] = inv.x; mo[1] = inv.y;
                mo.put(pk + 32);
            }
        };

        auto halo = [&]() { const uint32_t id = fresh_tid(); return aux + (id & 96) * 128 + (id & 128) * 16 + (id & 31) * 4; };
        auto put = [&](uint32_t a, uint32_t v0, uint32_t v1) {
            asm volatile("st.shared.u32 [%0], %1;\nst.shared.u32 [%0 + 128], %2;" :: "r"(a + HALO_BYTES), "r"(v0), "r"(v1) : "memory");
        };
        auto get = [&](uint32_t a, uint32_t& v0, uint32_t& v1) {
            asm volatile("ld.shared.u32 %0, [%2];\nld.shared.u32 %1, [%2 + 128];" : "=r"(v0), "=r"(v1) : "r"(a) : "memory");
        };
        auto publish = [&](int p) { asm volatile("fence.proxy.async.shared::cta;" ::: "memory"); signal_stores(p); };
        const uint32_t zero[4] = {0, 0, 0, 0};
        auto meet = [&](int n, int k, uint32_t id) {
            if (n == 15 - MEET)
                asm volatile("{\n.reg .b32 c;\nmov.u32 c, %%clock;\nbar.arrive %1, 256;\nlop3.b32 %0, %0, c, 1, 0x70;\n}"
                             : "+r"(peer_bars) : "r"(2 + id / 128) : "memory");
            if (n == 15) {
                asm volatile("{\n.reg .b32 c;\nmov.u32 c, %%clock;\nbar.sync %1, 256;\nlop3.b32 %0, %0, c, 1, 0x70;\n}"
                             : "+r"(peer_bars) : "r"(3 - id / 128) : "memory");
                mma_step(acc, da, db, next1(k & 3), k);
                asm volatile("// batch step");
            }
        };
        auto mix_qk = [&]() {
            uint32_t c[2][4];
            const uint32_t a = halo(), id = fresh_tid();
            mbar_wait(halo_bar, 0, spins);
#pragma unroll
            for (int n = 0; n < 16; n++) {
                const int b = 1 - n / 8, h = (n & 4) / 2 + n % 2, j = n / 2 % 2;
                uint32_t* const kq = pk + 32 + 8 * h + 4 * j;
                uint32_t* const q = pk + 8 * h + 4 * b;
                mma_sync(j ? q : c[n % 2], kq, q[2 * j], q[2 * j + 1], j ? c[n % 2] : zero);
                if (b) get(a + (h * 2 + j) * 256, kq[1], kq[3]);
                meet(n, QK_STEP, id);
            }
        };
        auto chunk_qk = [&](int k) {
            constexpr float LOG2E = 1.4426950408889634f;
            uint32_t* const l = pk + 32;
            Floats<16> e(pk);
            if (k == KEY_STEP) {
                const uint32_t a = halo();
#pragma unroll
                for (int i = 0; i < 8; i++) put(a + i * 256, pk[33 + 4 * i], pk[35 + 4 * i]);
                publish(1);
            } else if (k == QK_STEP + 1) {
                const uint32_t id = fresh_tid();
                const bool u0 = id % 32 / 4 > id % 4 * 2, u1 = id % 32 / 4 > id % 4 * 2 + 1;
                const uint32_t gone = row0(id) < 2 ? (u0 ? 0xffffu : 0u) | (u1 ? 0xffff0000u : 0u) : 0u;
#pragma unroll
                for (int n = 0; n < 8; n++) {
                    const int b = n % 2;
                    const uint32_t* const c = pk + 4 * n;
                    uint32_t v = pack_bf16(__uint_as_float(pick(u0, c[2 - 2 * b], c[2 * b])), __uint_as_float(pick(u1, c[3 - 2 * b], c[1 + 2 * b])));
                    v = mul2_bf16x2(v, 0x3e353e35u, 0x379e379eu);
                    if (!b) v = v & ~gone | 0xce6ece6eu & gone;
                    l[n] = transpose8(v);
                }
            } else if (k == QK_STEP + 2) {
#pragma unroll
                for (int h = 0; h < 4; h++) {
                    uint32_t m = max_bf16x2(__byte_perm(l[2 * h], l[2 * h + 1], 0x5410), __byte_perm(l[2 * h], l[2 * h + 1], 0x7632));
                    m = max_bf16x2(m, __shfl_xor_sync(0xffffffffu, m, 1));
                    m = max_bf16x2(m, __shfl_xor_sync(0xffffffffu, m, 2));
#pragma unroll
                    for (int n = 2 * h; n < 2 * h + 2; n++) {
                        const float f = -LOG2E * (n % 2 ? bf_hi(m) : bf_lo(m));
                        e[2 * n] = ex2_fast(fmaf(bf_lo(l[n]), LOG2E, f));
                        e[2 * n + 1] = ex2_fast(fmaf(bf_hi(l[n]), LOG2E, f));
                    }
                }
                e.put(pk);
            } else if (k == QK_STEP + 3) {
                uint32_t p[8];
#pragma unroll
                for (int n = 0; n < 8; n++) {
                    float sum = e[2 * n] + e[2 * n + 1];
                    sum += __shfl_xor_sync(0xffffffffu, sum, 1);
                    sum += __shfl_xor_sync(0xffffffffu, sum, 2);
                    const float r = rcp_fast(sum);
                    p[n] = pack_bf16(e[2 * n] * r, e[2 * n + 1] * r);
                }
                const uint32_t a = aux + 5 * HALO_BYTES + fresh_tid() * 16;
                sts128(a, make_uint4(p[0], p[1], p[2], p[3]));
                sts128(a + 4096, make_uint4(p[4], p[5], p[6], p[7]));
            }
        };
        auto values = [&](int h) { return pk + (h & 2) * 16 + (h & 1) * 8; };
        auto mix_pv = [&]() {
            uint32_t lo[8], hi[8];
            const uint32_t id = fresh_tid();
            const uint32_t keep = (id % 4 * 2 > id % 32 / 4 ? 0xffffu : 0u) | (id % 4 * 2 + 1 > id % 32 / 4 ? 0xffff0000u : 0u);
            const uint4 p0 = lds128(aux + 5 * HALO_BYTES + id * 16), p1 = lds128(aux + 6 * HALO_BYTES + id * 16);
            const uint32_t p[8] = {p0.x, p0.y, p0.z, p0.w, p1.x, p1.y, p1.z, p1.w};
#pragma unroll
            for (int n = 0; n < 8; n++)
                asm volatile("and.b32 %0, %2, %3;\nand.b32 %1, %2, %4;" : "=r"(lo[n]), "=r"(hi[n])
                             : "r"(p[n]), "r"(n % 2 ? keep : ~keep), "r"(n % 2 ? ~keep : keep));
            mbar_wait(halo_bar, 1, spins);
#pragma unroll
            for (int n = 0; n < 16; n++) {
                const int i = (n & 8) / 2 + (n & 2) + (n & 4) / 4;
                mma_sync(pk + 4 * (n ^ 4), pk + 4 * (n ^ 4), lo[i], hi[i], zero);
                meet(n, PV_STEP, id);
            }
        };
        auto chunk_pv = [&](int k) {
            if (k == VAL_STEP || k == VAL_STEP + 1) {
                const uint32_t a = halo();
#pragma unroll
                for (int h = (k - VAL_STEP) * 2; h < (k - VAL_STEP + 1) * 2; h++) {
                    uint32_t* const w = values(h);
                    uint32_t v[8];
#pragma unroll
                    for (int i = 0; i < 8; i++) v[i] = transpose8(w[h < 2 ? (i & 1) + (i & 2) * 2 + (i & 4) / 2 : (i & 1) * 2 + (i & 2) / 2 + (i & 4)]);
#pragma unroll
                    for (int i = 0; i < 8; i++) w[i] = v[i];
                    put(a + h * 512, w[2], w[3]);
                    put(a + h * 512 + 256, w[6], w[7]);
                }
                if (k > VAL_STEP) publish(3);
            } else if (k == PV_STEP - 1) {
                const uint32_t a = halo(), id = fresh_tid();
                optr = prm.pa2 + (mblk * K2 + nslot * 128) * 128 + (id & 224) * 32 + id % 4 * 128 + (id >> 2 & 7 ^ id % 4 * 2) * 8;
                mbar_wait(halo_bar, 1, spins);
#pragma unroll
                for (int n = 0; n < 8; n++) {
                    uint32_t* const w = values(n / 2) + n % 2 * 4;
                    w[16] = w[0]; w[17] = w[1];
                    get(a + n * 256, w[18], w[19]);
                }
            } else if (k > PV_STEP && k <= PV_STEP + OUT_STEPS) {
#pragma unroll
                for (int n = 0; n < 8; n++) {
                    if (n * OUT_STEPS / 8 != k - PV_STEP - 1) continue;
                    const int j = n ^ n >> 1 & 1;
                    if (n % 2) optr = reinterpret_cast<__nv_bfloat16*>(reinterpret_cast<uintptr_t>(optr) ^ 16);
                    Floats<15> c(pk + j / 2 * 16 + j % 2);
                    asm volatile("st.global.v4.u32 [%0], {%1,%2,%3,%4};"
                                 :: "l"(optr + (~j & 2) * 256 + j % 2 * 64 + j / 4 * 8192), "r"(pack_bf16(c[0], c[2])),
                                    "r"(pack_bf16(c[4], c[6])), "r"(pack_bf16(c[8], c[10])), "r"(pack_bf16(c[12], c[14])) : "memory");
                }
                if (k == PV_STEP + OUT_STEPS) signal_stores(4);
            }
        };

        TRACE_SLOT(tile_slot, 16 + wg * 8);
#pragma unroll 1
        for (int t = 0; t < G1_TILES; t++) {
#pragma unroll
            for (int k = 0; k < G1_KSTEPS; k++) {
                const int s = k & 3;
                if (k == 0) asm volatile("" : "+r"(t));
                TRACE_STEP(t, k, 0);
                mbar_wait(full1(s), (k >> 2) & 1, spins);
                if (k == 0) TRACE_S(12, t, 0);
                TRACE_STEP(t, k, 1);
                if (wg == 1 && k == G1_KSTEPS - G1_SKEW) asm volatile("bar.sync 1, 256;" ::: "memory");
                if (k == PV_STEP && t == 3) mix_pv();
                else if (k == QK_STEP && t == 2) mix_qk();
                else if (t == G1_TILES - 1) mma_step224(acc, da, db, next1(s), k);
                else mma_step(acc, da, db, next1(s), k);
                if (wg == 0 && k == G1_KSTEPS - 1) asm volatile("bar.arrive 1, 256;" ::: "memory");
                wg_wait<1>();
                if (k > 0) release(empty1((k - 1) & 3));
                TRACE_STEP(t, k, 2);
                if (t == 0) chunk_ln(k);
                if (k >= 1 && k <= 8 && ((k < HALF_STEP || k > HALF_STEP + 3 ? 0x12 : 0x1a) >> t & 1)) {
                    chunk_geglu(k < HALF_STEP ? k - 1 : (k > HALF_STEP + 3 ? k - 5 : k - HALF_STEP + 4));
                    if (k == 8 && t != 3) signal_stores(t + 1);
                }
                if (t == 2) chunk_qk(k);
                if (t == 3) chunk_pv(k);
                if (k == PV_STEP + OUT_STEPS) {
                    const uint32_t id = fresh_tid();
                    optr = prm.pa2 + (mblk * K2 + DM + gate_col(t, nslot)) * 128 + (id & 128) * 32 + (id & 96) * 16 + (id & 31 ^ id >> 3 & 3) * 8;
                    asm volatile("" : "+l"(optr));
                }
            }
            wg_wait<0>();
            fence_regs(acc);
            release(empty1(3));
            if (t == 0) {
                Floats<2> inv(pk + 32);
#pragma unroll
                for (int i = 0; i < 128; i++) acc[i] *= inv[i / 2 % 2];
                fence_regs(acc);
            }
#pragma unroll
            for (int i = 0; i < 64; i++) {
                const int e = i < 32 ? (i & ~7) * 2 + (i & 3) * 4 + (i & 4) / 2 : i * 2;
                pk[i] = pack_bf16(acc[e], acc[e + 1]);
            }
            TRACE_NEXT(tile_slot);
        }

        float accd[64], accs[64];
        asm volatile("{\n.reg .b32 lo, hi;\nmov.b64 {lo, hi}, %0;\nxor.b32 hi, hi, %1;\nmov.b64 %0, {lo, hi};\n}" : "+l"(da) : "n"(HI_64B ^ HI_128B));
#pragma unroll
        for (int i = 0; i < 64; i++) accd[i] = 0.f;
#pragma unroll
        for (int u = 0; u < G2_HEAD; u++) {
            const int q = u % G2_STAGES;
            TRACE_STEP(5, u, 0);
            mbar_wait(full2(q), (u / G2_STAGES) & 1, spins);
            TRACE_STEP(5, u, 1);
            if (u % 2) mma_step_c<254>(accd, da, db, next2(q), u);
            else mma_step<254>(accd, da, db, next2(q), u);
            wg_wait<1>();
            if (u > 0) release(empty2((u - 1) % G2_STAGES));
            TRACE_STEP(5, u, 2);
            if (u == UP_STEP) {
#pragma unroll
                for (int i = 0; i < 2; i++) {
                    const uint4 v = ldg_stream(prm.tail + role * 512 + i * 256 + threadIdx.x, stream_policy());
                    pk[56 + 4 * i] = v.x; pk[57 + 4 * i] = v.y; pk[58 + 4 * i] = v.z; pk[59 + 4 * i] = v.w;
                }
            }
            if (u >= 1) {
                const int j = (u - 1) / 2;
#pragma unroll
                for (int i = 2 * u - 2; i < 2 * u; i++) pk[i] = geglu2(pk[i], pk[up(i)]);
                if (u % 2 == 0) store_pk(optr + (j & 1) * 256 + (j & 2) * 1024 + (j & 4) * 2048, j);
            }
            if (u == G2_HEAD - 1) signal_stores(6);
        }
        auto down = [&](int q, uint32_t phase, bool narrow, bool busy = false) {
            mbar_wait(full2(q), phase, spins);
            if (narrow) mma_step96(accd, da, db, next2(q), 1);
            else if (busy) mma_step_c<254>(accd, da, db, next2(q), 1, HI_128B - HI_64B);
            else mma_step<254>(accd, da, db, next2(q), 1);
            wg_wait<1>();
            release(empty2((q + G2_STAGES - 1) % G2_STAGES));
        };
        uint32_t shared_steps = plan_word(base, lane);
        down(5, 0, false);
#pragma unroll 1
        for (uint32_t r = 3; r < 9; r++, shared_steps >>= G2_STAGES) {
#pragma unroll
            for (int q = 0; q < G2_STAGES; q++) down(q, r & 1, shared_steps >> q & 1);
        }
        down(0, 1, false);
        down(1, 1, false, true);
        TRACE_NEXT(tile_slot);
#pragma unroll
        for (int i = 0; i < 64; i++) accs[i] = 0.f;
        uint32_t gk[32], xr[32];
        const uint32_t xs = aux + cw * 2048;
        const uint32_t xrow = xs + ((lane & 7) + ((lane >> 3) & 1) * 8) * 128;
        auto xaddr = [&](int j) { return xrow + (j >> 2) * 16384 + (((((j & 3) * 2) + (lane >> 4)) ^ (lane & 7)) << 4); };
#pragma unroll
        for (int u = G2_DSTEPS; u < G2_KSTEPS; u++) {
            const int q = u % G2_STAGES, v = u - G2_DSTEPS;
            mbar_wait(full2(q), (u / G2_STAGES) & 1, spins);
            if (wg == 1 && u == G2_KSTEPS - G2_SKEW) asm volatile("bar.sync 1, 256;" ::: "memory");
            if (u % 2) mma_step_c<2>(accs, da, db, next2(q), v);
            else mma_step<2>(accs, da, db, next2(q), v);
            if (wg == 0 && u == G2_KSTEPS - 1) asm volatile("bar.arrive 1, 256;" ::: "memory");
            if (v == TAIL_STEP) {
                TRACE_S(32, wg, 0);
                mbar_wait(dep_bar + 24, 0, spins);
                TRACE_S(33, wg, 0);
#pragma unroll
                for (int i = 0; i < 2; i++) {
                    const uint4 w = ldg_stream(prm.tail + (NGEMM + role) * 512 + i * 256 + threadIdx.x, stream_policy());
                    gk[24 + 4 * i] = w.x; gk[25 + 4 * i] = w.y; gk[26 + 4 * i] = w.z; gk[27 + 4 * i] = w.w;
                }
            }
#pragma unroll
            for (int i = 0; i < 32; i++) {
                if (v == (i < 24 ? i / 4 + 1 : TAIL_STEP + i / 4 - 3))
                    gk[i] = i < 24 ? silu2(accd[2 * i], accd[2 * i + 1])
                                   : silu2(accd[2 * i] + bf_lo(gk[i]), accd[2 * i + 1] + bf_hi(gk[i]));
            }
            if (v == XREAD_STEP) mbar_wait(x_bar, 0, spins);
            if (v >= XREAD_STEP && v < XREAD_STEP + 4) {
#pragma unroll
                for (int j = 2 * (v - XREAD_STEP); j < 2 * (v - XREAD_STEP + 1); j++)
                    asm volatile("ldmatrix.sync.aligned.m8n8.x4.shared.b16 {%0,%1,%2,%3}, [%4];"
                                 : "=r"(xr[4 * j]), "=r"(xr[4 * j + 1]), "=r"(xr[4 * j + 2]), "=r"(xr[4 * j + 3])
                                 : "r"(xaddr(j)) : "memory");
            }
            wg_wait<1>();
            if (v == 0) fence_regs(accd);
            if (u - 1 + G2_STAGES < G2_KSTEPS) release(empty2((u - 1) % G2_STAGES));
        }
        __nv_bfloat16* po = prm.pout + (row0(fresh_tid()) + (lane >> 3) * 2) * DM + nslot * 128 + 64 + (lane & 7) * 8;
        uint32_t so = xs + 16384 + (lane >> 3) * 128 + (((lane & 7) ^ (lane >> 3)) << 4);
        const int c0 = uniform(nslot * 128), c1 = uniform(row0(fresh_tid()) >> 1);
        const uint32_t xu = uniform(xs);
        asm volatile("" : "+l"(po), "+r"(so));
        wg_wait<0>();
        fence_regs(accs);
        TRACE_NEXT(tile_slot);
        TRACE_END();
#pragma unroll
        for (int j = 0; j < 8; j++) {
            uint32_t r[4];
#pragma unroll
            for (int i = 0; i < 4; i++) {
                const int e = j * 4 + i;
                asm("fma.rn.bf16x2 %0, %1, %2, %3;" : "=r"(r[i]) : "r"(pack_bf16(accs[2 * e], accs[2 * e + 1])), "r"(gk[e]), "r"(xr[e]));
            }
            asm volatile("stmatrix.sync.aligned.m8n8.x4.shared.b16 [%0], {%1,%2,%3,%4};"
                         :: "r"(xaddr(j)), "r"(r[0]), "r"(r[1]), "r"(r[2]), "r"(r[3]) : "memory");
            if (j == 3)
                asm volatile("{\n.reg .pred e;\nfence.proxy.async.shared::cta;\nbar.warp.sync 0xffffffff;\nelect.sync _|e, 0xffffffff;\n"
                    "@e cp.async.bulk.tensor.3d.global.shared::cta.bulk_group [%0, {%2, %3, %4}], [%1];\n}"
                    :: "l"(&prm.out), "r"(xu), "r"(c0), "r"(c1), "r"(wg) : "memory");
        }
        __syncwarp();
#pragma unroll
        for (int i = 0; i < 4; i++) {
            const uint4 v = lds128((so ^ (i & 1) * 64) + i * 512);
            asm volatile("st.global.v4.u32 [%0], {%1,%2,%3,%4};" :: "l"(po + i * 8 * DM), "r"(v.x), "r"(v.y), "r"(v.z), "r"(v.w) : "memory");
        }
        asm volatile("cp.async.bulk.commit_group;\ncp.async.bulk.wait_group.read 0;" ::: "memory");
        TRACE_LITE(10, clock());
        if (tid == 0) { TRACE_NEXT(tile_slot); if (wg == 1) TRACE_GT(13); TRACE_DUMP(); }
    } else if (warp > 9) {
        const int w = warp - 10;
        const unsigned epoch = __ldcg(prm.epoch + blockIdx.x * 16 + w) + 1;
        const uint32_t tag = 1 + (epoch & 1);
        TRACE_LITE(8, t0);
        const uint32_t at = (w ? SUM_LOAD1 : SUM_LOAD0) >> nslot * 4 & 15;
        mbar_wait(empty1(at & 3), 0);
        mbar_wait(empty1(at & 3), at >> 3);
        if (elect_one()) {
            mbar_expect_tx(cs_bar + w * 8, 16384);
            asm volatile("cp.async.bulk.tensor.2d.shared::cluster.global.mbarrier::complete_tx::bytes [%0], [%1, {%3, %5}], [%2];\n"
                "cp.async.bulk.tensor.2d.shared::cluster.global.mbarrier::complete_tx::bytes [%0 + 8192], [%1, {%4, %5}], [%2];"
                :: "r"(aux + w * 16384), "l"(w0), "r"(cs_bar + w * 8), "r"(nslot * 128), "r"(nslot * 128 + 64),
                   "r"(((mblk & ~1) + w) * 64) : "memory");
        }
        float cs[8];
#pragma unroll
        for (int d = 0; d < 8; d++) cs[d] = 0.f;
        const uint32_t wa = aux + w * 8192 + (lane >> 3) * 128 + (((lane & 7) ^ (lane >> 3)) << 4);
        uint4 v[8];
        auto fetch = [&](int h, uint32_t off) {
#pragma unroll
            for (int j = 0; j < 4; j++) v[h * 4 + j] = lds128((wa ^ (j & 1) * 64) + off + h * 2048 + j * 512);
        };
        auto add = [&](int h) {
#pragma unroll
            for (int j = 0; j < 4; j++) {
                float f[8];
                unpack8(v[h * 4 + j], f);
#pragma unroll
                for (int d = 0; d < 8; d++) cs[d] += f[d];
            }
        };
        mbar_wait(empty1(SUM_STEP & 3), 0);
        mbar_wait(empty1(SUM_STEP & 3), SUM_STEP >> 3);
        mbar_wait(cs_bar, 0);
        fetch(0, 0);
#pragma unroll 1
        for (int i = 0; i < 4; i++) {
            fetch(1, (i >> 1) * 16384 + (i & 1) * 4096);
            add(0);
            if (i == 1) mbar_wait(cs_bar + 8, 0);
            fetch(0, (i + 1 & 2) * 8192 + (~i & 1) * 4096);
            add(1);
        }
#pragma unroll
        for (int d = 0; d < 4; d++)
            cs[d] = (lane & 16 ? cs[d + 4] : cs[d]) + __shfl_xor_sync(0xffffffffu, lane & 16 ? cs[d] : cs[d + 4], 16);
#pragma unroll
        for (int d = 0; d < 2; d++)
            cs[d] = (lane & 8 ? cs[d + 2] : cs[d]) + __shfl_xor_sync(0xffffffffu, lane & 8 ? cs[d] : cs[d + 2], 8);
        st_tagged(prm.colsum + (nslot * 2 + rank) * 1024 + (mblk >> 1) * 128 + w * 64 + (lane & 7) * 8 + (lane >> 3) * 2,
                  cs[0], cs[1], tag);

        fold_operands(prm, base, nslot, mblk, tag, w, lane);
        if (lane == 0) {
            mbar_arrive(fold_bar);
            prm.epoch[blockIdx.x * 16 + w] = epoch;
            if (w == 0) {
                TRACE(35);
#pragma unroll 1
                for (uint32_t j = 0, n = 1 << 24; j < 4; n = (CNT_EARLY | CNT_LATE << 8 | 1 << 16) >> j * 8 & 255, j++) {
                    mbar_wait(sig_bar + (0xa0302820u >> j * 8 & 255), 0);
                    const uint32_t v = flag_wait(flags + (F_SHARE + j) * 512, epoch * n);
                    fence_proxy_async();
                    if (j) mbar_arrive(dep_bar + j * 8);
                    else sts32(base + PLAN_OFF, v & 0xffffff);
                }
            } else {
#pragma unroll 1
                for (int j = 0; j < 2; j++) {
                    uint8_t* const h = prm.halo + (j * NGEMM + role) * HALO_BYTES;
                    unsigned* const f = prm.flags + F_HALO * 512 + role * 32;
                    mbar_wait(sig_bar + 8 + j * 16, 0);
                    TRACE_S(38, j, 0); TRACE_S(9, j, 1);
                    asm volatile("cp.async.bulk.global.shared::cta.bulk_group [%0], [%1], %2;\n"
                        "cp.async.bulk.commit_group;\ncp.async.bulk.wait_group 0;"
                        :: "l"(h + HALO_BYTES), "r"(aux + 4 * HALO_BYTES), "n"(HALO_BYTES) : "memory");
                    fence_proxy_async();
                    TRACE_S(39, j, 0); TRACE_S(10, j, 1);
                    flag_add(f);
                    TRACE_S(40, j, 0); TRACE_S(34, j, 1);
                    if (mblk) flag_wait(f - 32, epoch * 2 - 1 + j);
                    fence_proxy_async();
                    TRACE_S(41, j, 0); TRACE_S(36, j, 1);
                    mbar_expect_tx(halo_bar, HALO_BYTES);
                    asm volatile("cp.async.bulk.shared::cluster.global.mbarrier::complete_tx::bytes [%0], [%1], %2, [%3];"
                        :: "r"(aux), "l"(mblk ? h : prm.halo), "n"(HALO_BYTES), "r"(halo_bar) : "memory");
                }
            }
        }
    } else {
#pragma unroll 1
        for (int k = 1; k < G1_STAGES; k++) {
            const uint32_t sa = base + k * G1_STAGE_BYTES;
            while ((uint32_t)clock() - t0 < (k == 3 ? PACE3 : PACE1 + (k - 1) * (PACE2 - PACE1))) {}
            load_stage1(sa, sa + A_BYTES + rank * 16384, full1(k), &prm.x, w0, w0, k * 64, k * 64, mblk * 64, nslot * 128,
                        nslot * 128 + 64, 0, stream_policy());
        }
        if (elect_one()) {
            prefetch_map(&prm.xn); prefetch_map(&prm.wqkv);
            prefetch_map(&prm.a2); prefetch_map(&prm.wo); prefetch_map(&prm.wd); prefetch_map(&prm.out);
        }
        uint32_t ph = 0;
#pragma unroll 1
        for (int t = 0; t < G1_TILES; t++) {
            const int col1 = (t == 1 ? rank * DM + nslot * 128 : gate_col(t, nslot)) + 64;
            const int col0 = t == 2 ? 2 * DM + nslot * 128 + rank * 64 : col1 - 64;
            if (t == 1) { TRACE_PUT(2, t0); TRACE(14); mbar_wait_warp(dep_bar, 0); TRACE(3); }
#pragma unroll 1
            for (int k = t ? 0 : G1_STAGES; k < G1_KSTEPS; k++) {
                const int s = k & 3;
                if (t == 1 && k == 8) mbar_wait_warp(dep_bar + 40, 0);
                mbar_wait_warp(empty1(s), ph);
                const uint32_t sa = base + s * G1_STAGE_BYTES;
                load_stage1(sa, sa + A_BYTES + rank * 16384, full1(s), t ? &prm.xn : &prm.x, t == 1 || t == 2 ? &prm.wqkv : w0,
                            t == 1 ? &prm.wqkv : w0, k * 64, t ? 0 : k * 64, t ? (mblk * G1_KSTEPS + k) * 128 : mblk * 64, col0, col1, t & 3,
                            stream_policy());
                TRACE_RING(t * 16 + k);
                if (s == 3) ph ^= 1;
            }
        }
        TRACE(4);
        mbar_wait_warp(dep_bar + 8, 0);
        TRACE(5);
        int q = 0, round = 4, own = SHARE_MAX; uint32_t ph2 = 1;
#pragma unroll 1
        for (int u = 0; u < G2_KSTEPS; u++) {
            if (u == G2_LATE) { TRACE(6); mbar_wait_warp(dep_bar + 16, 0); TRACE(7); }
            const uint32_t sa = stage2(q);
            const bool down = u < G2_DSTEPS;
            const int k = !down ? u - G2_DSTEPS : (u < 18 || u >= 40 ? own++ : (q & 1 ? u / 2 - 9 : round + (q ? q * 2 : 11)));
            mbar_wait_warp(u < G2_STAGES ? empty1((u * 2 + 1) / 3) : empty2(q), u < G2_STAGES ? ph : ph2);
            load_stage2(sa, sa + A_BYTES + rank * 8192, full2(q), &prm.a2, down ? &prm.wd : &prm.wo, 0,
                        (mblk * G2_KSTEPS + (down ? 16 : 0) + k) * 128, nslot * 128 + rank * 64, down ? 0 : k * 2, down ? k * 2 : 0, stream_policy());
            if (u == XLOAD_STEP + nslot * 2) {
                if (elect_one()) {
                    mbar_expect_tx(x_bar, 32768);
                    tma_3d(aux, &prm.x, x_bar, nslot * 128, mblk * 64, 0, stream_policy());
                    tma_3d(aux + 16384, &prm.x, x_bar, nslot * 128 + 64, mblk * 64, 0, stream_policy());
                }
                __syncwarp();
            }
            TRACE_RING(80 + u);
            if (++q == G2_STAGES) { q = 0; ph2 ^= 1; round++; }
        }
        TRACE(8);
    }
}

typedef CUresult (*EncodeFn)(CUtensorMap*, CUtensorMapDataType, cuuint32_t, void*, const cuuint64_t*, const cuuint64_t*,
                             const cuuint32_t*, const cuuint32_t*, CUtensorMapInterleave, CUtensorMapSwizzle,
                             CUtensorMapL2promotion, CUtensorMapFloatOOBfill);

void encode(EncodeFn fn, CUtensorMap* m, const void* ptr, int rank, const cuuint64_t* dims, const cuuint64_t* strides,
            const cuuint32_t* box, bool swizzle = true) {
    const cuuint32_t es[5] = {1, 1, 1, 1, 1};
    fn(m, CU_TENSOR_MAP_DATA_TYPE_BFLOAT16, rank, const_cast<void*>(ptr), dims, strides, box, es,
       CU_TENSOR_MAP_INTERLEAVE_NONE, !swizzle ? CU_TENSOR_MAP_SWIZZLE_NONE : box[0] == 32 ? CU_TENSOR_MAP_SWIZZLE_64B : CU_TENSOR_MAP_SWIZZLE_128B,
       CU_TENSOR_MAP_L2_PROMOTION_L2_128B, CU_TENSOR_MAP_FLOAT_OOB_FILL_NONE);
}
void encode_rows(EncodeFn fn, CUtensorMap* m, const void* ptr, int cols, int box_rows, int box_parity) {
    const cuuint64_t dims[3] = {(cuuint64_t)cols, SEQ / 2, 2}, strides[2] = {(cuuint64_t)cols * 4, (cuuint64_t)cols * 2};
    const cuuint32_t box[3] = {64, (cuuint32_t)box_rows, (cuuint32_t)box_parity};
    encode(fn, m, ptr, 3, dims, strides, box);
}
void encode_images(EncodeFn fn, CUtensorMap* m, const void* ptr, int cols) {
    const cuuint64_t dims[3] = {64, (cuuint64_t)SEQ * cols / 64 - 64, 2}, strides[2] = {128, 8192};
    const cuuint32_t box[3] = {64, 64, 2};
    encode(fn, m, ptr, 3, dims, strides, box, false);
}
void encode_w1(EncodeFn fn, CUtensorMap* m, const void* ptr, int cols) {
    const cuuint64_t dims[2] = {(cuuint64_t)cols, DM}, strides[1] = {(cuuint64_t)cols * 2};
    const cuuint32_t box[2] = {64, 64};
    encode(fn, m, ptr, 2, dims, strides, box);
}
void encode_tail(EncodeFn fn, CUtensorMap* m, const void* ptr, int rows, int cols, int n) {
    const cuuint64_t rb = cols * 2;
    const cuuint64_t dims[5] = {32, (cuuint64_t)n, (cuuint64_t)rows / (4 * n), 4, 8}, strides[4] = {rb, 4 * n * rb, n * rb, 256};
    const cuuint32_t box[5] = {32, (cuuint32_t)n, 16 / (cuuint32_t)n, 4, 4};
    encode(fn, m, (const __nv_bfloat16*)ptr + cols - 1024 + 96, 5, dims, strides, box);
}
void encode_w2(EncodeFn fn, CUtensorMap* m, const void* ptr, int rows) {
    const cuuint64_t rb = DM * 2;
    const cuuint64_t dims[5] = {DM, 2, 4, 4, (cuuint64_t)rows / 32}, strides[4] = {rb, 8 * rb, 2 * rb, 32 * rb};
    const cuuint32_t box[5] = {64, 2, 4, 4, 2};
    encode(fn, m, ptr, 5, dims, strides, box);
}
void encode_wo(EncodeFn fn, CUtensorMap* m, const void* ptr) {
    const cuuint64_t rb = DM * 2;
    const cuuint64_t dims[5] = {DM, 4, DM / 32, 2, 4}, strides[4] = {8 * rb, 32 * rb, rb, 2 * rb};
    const cuuint32_t box[5] = {64, 4, 2, 2, 4};
    encode(fn, m, ptr, 5, dims, strides, box);
}

}

extern "C" void kernel_launch(void* const* d_in, const int* in_sizes, int n_in, void* d_out, int out_size) {
    (void)in_sizes; (void)n_in; (void)out_size;
    static EncodeFn fn = nullptr;
    static Params prm;
    if (!fn) {
        cudaDriverEntryPointQueryResult st;
        cudaGetDriverEntryPoint("cuTensorMapEncodeTiled", (void**)&fn, cudaEnableDefault, &st);
        cudaGetSymbolAddress((void**)&prm.pxn, g_xn);
        cudaGetSymbolAddress((void**)&prm.pa2, g_a2);
        cudaGetSymbolAddress((void**)&prm.tail, g_tail);
        cudaGetSymbolAddress((void**)&prm.halo, g_halo);
        cudaGetSymbolAddress((void**)&prm.stats, g_stats);
        cudaGetSymbolAddress((void**)&prm.colsum, g_colsum);
        cudaGetSymbolAddress((void**)&prm.flags, g_flags);
        cudaGetSymbolAddress((void**)&prm.epoch, g_epoch);
        cudaFuncSetAttribute(fused_kernel, cudaFuncAttributeMaxDynamicSharedMemorySize, SMEM_BYTES);
    }
    encode_rows(fn, &prm.x, d_in[0], DM, 64, 2);
    encode_images(fn, &prm.xn, prm.pxn, DM);
    encode_images(fn, &prm.a2, prm.pa2, K2);
    encode_rows(fn, &prm.out, d_out, DM, 16, 1);
    encode_w1(fn, &prm.wqkv, d_in[1], NQKV);
    encode_w1(fn, &prm.wg, d_in[4], DF);
    encode_w1(fn, &prm.wu, d_in[5], DF);
    encode_tail(fn, &prm.wu_tail, d_in[5], DM, DF, 8);
    encode_tail(fn, &prm.wd_tail, d_in[6], DF, DM, 2);
    encode_wo(fn, &prm.wo, d_in[2]);
    encode_w2(fn, &prm.wd, d_in[6], DF);
    prm.hi[0] = prm.hi[1] = HI_128B;
    prm.px = (const __nv_bfloat16*)d_in[0];
    prm.pwu = (const __nv_bfloat16*)d_in[5];
    prm.pout = (__nv_bfloat16*)d_out;
    fused_kernel<<<NCTA, 384, SMEM_BYTES>>>(prm);
}
```

```cpp
#include <cuda_runtime.h>
#include <cuda_bf16.h>
#include <cuda.h>
#include <stdint.h>
#include <limits.h>

namespace {

constexpr int SEQ = 2048, DM = 1024, DF = 3584, K2 = DM + DF, NQKV = 3 * DM;
constexpr int NGEMM = 128, NCTA = 132;
constexpr int G1_STAGES = 4, G1_STAGE_BYTES = 49152, G1_KSTEPS = 16, G1_TILES = 5;
constexpr int G2_STAGES = 6, G2_STAGE_BYTES = 32768, G2_KSTEPS = 72, G2_LATE = 40, G2_DSTEPS = 56;
constexpr int G2_HEAD = 17;
constexpr int A_BYTES = 16384;
constexpr int AUX_OFF = G1_STAGES * G1_STAGE_BYTES;
constexpr int BAR_OFF = AUX_OFF + 32768;
constexpr int PLAN_OFF = BAR_OFF + 384, STAT_OFF = BAR_OFF + 1536;
constexpr int SMEM_BYTES = BAR_OFF + 2816;
constexpr int G1_SKEW = 2, G2_SKEW = 5;
constexpr int CONSUMER_REGS = 224, AUX_REGS = 56;
constexpr int HALO_BYTES = 4096;
constexpr int LN_STEP = 3, FOLD_STEP = 14, SUM_STEP = 11, SUM2_STEP = 2;
constexpr uint32_t SUM_LOAD0 = 0x87658765u, SUM_LOAD1 = 0x65876587u;
constexpr int KEY_STEP = 2, QK_STEP = 8;
constexpr int VAL_STEP = 1, HALF_STEP = 3, PV_STEP = 9, OUT_STEPS = 4;
constexpr int UP_STEP = 2, XLOAD_STEP = 44;
constexpr int XREAD_STEP = 5, TAIL_STEP = 7;
constexpr int MEET = 4;
constexpr int PACE1 = 800, PACE2 = 1325, PACE3 = 1700;
constexpr int SHARE_MIN = 3, SHARE_MAX = 22, SHARE_LOW = 36, SHARE_SUM = 43;
constexpr int SHARE_NS = 79, SPARE_NS = 640, LATE_SCALE = 8;
constexpr float REST = 65000.f, DUE = 75300.f;

enum { F_LN = 0, F_LN2 = 1, F_FIRST = 2, F_SECOND = 3, F_SHARE = 4, F_EARLY = 5, F_LATE = 6, F_TAIL2 = 7, F_PACE = 8, F_HALO = 9 };
constexpr unsigned CNT_LN = 8, CNT_EARLY = 9, CNT_LATE = 8;

__device__ __align__(1024) __nv_bfloat16 g_xn[SEQ * DM];
__device__ __align__(1024) __nv_bfloat16 g_a2[SEQ * K2];
__device__ __align__(128) uint4 g_tail[2 * NGEMM * 512];
__device__ __align__(128) uint8_t g_halo[(2 * NGEMM + 1) * HALO_BYTES];
__device__ __align__(128) float2 g_stats[SEQ];
__device__ __align__(128) float g_colsum[18 * 1024];
__device__ __align__(128) unsigned g_flags[(F_HALO + 8) * 16 * 32];
__device__ __align__(128) unsigned g_epoch[NCTA * 16];

struct Params {
    const __nv_bfloat16 *px, *pwu;
    __nv_bfloat16 *pxn, *pa2, *pout;
    uint4* tail;
    uint8_t* halo;
    float2* stats;
    float* colsum;
    unsigned *flags, *epoch;
    unsigned long long* trace;
    uint32_t hi[2];
    CUtensorMap x, wg, wu, xn, wqkv, a2, wu_tail, wd_tail, wo, wd, out;
};

extern __shared__ __align__(1024) uint8_t smem_raw[];

#define TRACE(slot) do {} while (0)
#define TRACE_GT(slot) do {} while (0)
#define TRACE_S(slot, v, want) do {} while (0)
#define TRACE_GET(v) do {} while (0)
#define TRACE_PUT(slot, v) do {} while (0)
#define TRACE_SLOT(v, slot) do {} while (0)
#define TRACE_NEXT(v) do {} while (0)
#define TRACE_DUMP() do {} while (0)
#define TRACE_CLEAR() do {} while (0)
#define STAGE_TRACE 0
#define TRACE_END() do {} while (0)
#define TRACE_LITE(i, c) do {} while (0)
#define TRACE_RING(i) do {} while (0)
#define TRACE_STEP(t, k, i) do {} while (0)

__device__ __forceinline__ uint32_t smem_u32(const void* p) { return (uint32_t)__cvta_generic_to_shared(p); }
__device__ __forceinline__ void mbar_expect_tx(uint32_t bar, uint32_t bytes) {
    asm volatile("mbarrier.arrive.expect_tx.shared::cta.b64 _, [%0], %1;" :: "r"(bar), "r"(bytes) : "memory");
}
__device__ __forceinline__ void mbar_arrive(uint32_t bar) {
    asm volatile("mbarrier.arrive.shared::cta.b64 _, [%0];" :: "r"(bar) : "memory");
}
__device__ __forceinline__ bool mbar_try_wait(uint32_t bar, uint32_t parity) {
    uint32_t ok;
    asm volatile("{\n.reg .pred p;\nmbarrier.try_wait.parity.shared::cta.b64 p, [%1], %2;\nselp.u32 %0, 1, 0, p;\n}"
                 : "=r"(ok) : "r"(bar), "r"(parity) : "memory");
    return ok;
}
__device__ __forceinline__ void mbar_wait(uint32_t bar, uint32_t parity) {
#pragma unroll 1
    for (int spins = 0; !mbar_try_wait(bar, parity) && spins < (1 << 17); spins++) {}
}
__device__ __forceinline__ void mbar_wait(uint32_t bar, uint32_t parity, int& spins) {
    asm volatile("{\n.reg .pred p;\nagain:\nmbarrier.try_wait.parity.shared::cta.b64 p, [%1], %2;\n@p bra done;\n"
                 "add.s32 %0, %0, -1;\nsetp.gt.s32 p, %0, 0;\n@p bra again;\ndone:\n}" : "+r"(spins) : "r"(bar), "r"(parity) : "memory");
}
template <bool WARP = false> __device__ __forceinline__ unsigned flag_wait(const unsigned* p, unsigned target) {
    unsigned v;
#pragma unroll 1
    for (int spins = 0; spins < (1 << 19); spins++) {
        asm volatile("ld.acquire.gpu.global.u32 %0, [%1];" : "=r"(v) : "l"(p) : "memory");
        if (WARP ? __all_sync(0xffffffffu, (int)(v - target) >= 0) : (int)(v - target) >= 0) break;
        __nanosleep(64);
    }
    return v;
}
__device__ __forceinline__ void mbar_wait_warp(uint32_t bar, uint32_t parity) {
#pragma unroll 1
    for (int spins = 0; !__all_sync(0xffffffffu, mbar_try_wait(bar, parity)) && spins < (1 << 17); spins++) {}
}
__device__ __forceinline__ void flag_add(unsigned* p) {
    asm volatile("red.release.gpu.global.add.u32 [%0], 1;" :: "l"(p) : "memory");
}
__device__ __forceinline__ bool elect_one() {
    uint32_t ok;
    asm volatile("{\n.reg .pred p;\nelect.sync _|p, 0xffffffff;\nselp.u32 %0, 1, 0, p;\n}" : "=r"(ok));
    return ok;
}
__device__ __forceinline__ uint32_t pick(bool c, uint32_t a, uint32_t b) {
    uint32_t r;
    asm("{\n.reg .pred p;\nsetp.ne.b32 p, %3, 0;\nselp.b32 %0, %1, %2, p;\n}" : "=r"(r) : "r"(a), "r"(b), "r"((uint32_t)c));
    return r;
}
template <typename T> __device__ __forceinline__ T* offset(T* p, uint32_t bytes) {
    asm("{\n.reg .b32 lo, hi;\nmov.b64 {lo, hi}, %0;\nadd.cc.u32 lo, lo, %1;\naddc.u32 hi, hi, 0;\nmov.b64 %0, {lo, hi};\n}" : "+l"(p) : "r"(bytes));
    return p;
}
__device__ __forceinline__ void fence_proxy_async() { asm volatile("fence.proxy.async.global;" ::: "memory"); }
__device__ __forceinline__ uint4 lds128(uint32_t addr) {
    uint4 v;
    asm volatile("ld.shared.v4.u32 {%0,%1,%2,%3}, [%4];" : "=r"(v.x), "=r"(v.y), "=r"(v.z), "=r"(v.w) : "r"(addr) : "memory");
    return v;
}
__device__ __forceinline__ uint32_t lds32(uint32_t addr) {
    uint32_t v;
    asm volatile("ld.shared.u32 %0, [%1];" : "=r"(v) : "r"(addr) : "memory");
    return v;
}
__device__ __forceinline__ void sts32(uint32_t addr, uint32_t v) { asm volatile("st.shared.u32 [%0], %1;" :: "r"(addr), "r"(v) : "memory"); }
__device__ __forceinline__ uint32_t nanos() { uint32_t t; asm volatile("mov.u32 %0, %%globaltimer_lo;" : "=r"(t)); return t; }
__device__ __forceinline__ float2 lds64f(uint32_t addr) {
    float2 v;
    asm volatile("ld.shared.v2.f32 {%0,%1}, [%2];" : "=f"(v.x), "=f"(v.y) : "r"(addr) : "memory");
    return v;
}
__device__ __forceinline__ void sts128(uint32_t addr, uint4 v) {
    asm volatile("st.shared.v4.u32 [%0], {%1,%2,%3,%4};" :: "r"(addr), "r"(v.x), "r"(v.y), "r"(v.z), "r"(v.w) : "memory");
}
__device__ __forceinline__ void sts64f(uint32_t addr, float a, float b) {
    asm volatile("st.shared.v2.f32 [%0], {%1,%2};" :: "r"(addr), "f"(a), "f"(b) : "memory");
}

__device__ __forceinline__ uint64_t stream_policy() { return 0x12F0000000000000ull; }
__device__ __forceinline__ void tma_3d(uint32_t dst, const CUtensorMap* m, uint32_t bar, int c0, int c1, int c2, uint64_t pol) {
    asm volatile("cp.async.bulk.tensor.3d.shared::cluster.global.mbarrier::complete_tx::bytes.L2::cache_hint"
                 " [%0], [%1, {%3, %4, %5}], [%2], %6;"
                 :: "r"(dst), "l"(m), "r"(bar), "r"(c0), "r"(c1), "r"(c2), "l"(pol) : "memory");
}
__device__ __forceinline__ void load_stage1(uint32_t dst, uint32_t dst_b, uint32_t bar, const CUtensorMap* ma, const CUtensorMap* mb0,
                                            const CUtensorMap* mb1, int k, int ka, int row, int col0, int col1, int keep_a, uint64_t pol) {
    asm volatile("{\n.reg .pred e, p, q;\nelect.sync _|e, 0xffffffff;\nsetp.ne.and.b32 p|q, %8, 0, e;\n"
        "@p cp.async.bulk.tensor.3d.shared::cluster.global.mbarrier::complete_tx::bytes [%0], [%3, {%15, %6, %10}], [%2];\n"
        "@q cp.async.bulk.tensor.3d.shared::cluster.global.mbarrier::complete_tx::bytes.L2::cache_hint [%0], [%3, {%15, %6, %10}], [%2], %9;\n"
        "@e cp.async.bulk.tensor.2d.shared::cluster.global.mbarrier::complete_tx::bytes.multicast::cluster.L2::cache_hint"
        " [%1], [%4, {%7, %5}], [%2], %11, %9;\n"
        "@e cp.async.bulk.tensor.2d.shared::cluster.global.mbarrier::complete_tx::bytes.multicast::cluster.L2::cache_hint"
        " [%1 + 8192], [%13, {%14, %5}], [%2], %11, %9;\n"
        "@e mbarrier.arrive.expect_tx.shared::cta.b64 _, [%2], %12;\n}"
        :: "r"(dst), "r"(dst_b), "r"(bar), "l"(ma), "l"(mb0), "r"(k), "r"(row), "r"(col0), "r"(keep_a), "l"(pol), "r"(0),
           "h"((uint16_t)3), "n"(G1_STAGE_BYTES), "l"(mb1), "r"(col1), "r"(ka) : "memory");
}
__device__ __forceinline__ void load_stage2(uint32_t dst, uint32_t dst_b, uint32_t bar, const CUtensorMap* ma, const CUtensorMap* mb,
                                            int ka, int row, int col, int kb2, int kb4, uint64_t pol) {
    asm volatile("{\n.reg .pred e;\nelect.sync _|e, 0xffffffff;\n"
        "@e cp.async.bulk.tensor.3d.shared::cluster.global.mbarrier::complete_tx::bytes.L2::cache_hint [%0], [%3, {%5, %6, %10}], [%2], %9;\n"
        "@e cp.async.bulk.tensor.5d.shared::cluster.global.mbarrier::complete_tx::bytes.multicast::cluster.L2::cache_hint"
        " [%1], [%4, {%7, %10, %13, %10, %8}], [%2], %11, %9;\n"
        "@e mbarrier.arrive.expect_tx.shared::cta.b64 _, [%2], %12;\n}"
        :: "r"(dst), "r"(dst_b), "r"(bar), "l"(ma), "l"(mb), "r"(ka), "r"(row), "r"(col), "r"(kb4), "l"(pol), "r"(0),
           "h"((uint16_t)3), "n"(G2_STAGE_BYTES), "r"(kb2) : "memory");
}
__device__ __forceinline__ void load_tail(uint32_t dst, uint32_t bar, const CUtensorMap* ma, const CUtensorMap* mb, int ka, int row,
                                          int rank, int kb) {
    asm volatile("{\n.reg .pred e;\nelect.sync _|e, 0xffffffff;\n"
        "@e cp.async.bulk.tensor.3d.shared::cluster.global.mbarrier::complete_tx::bytes [%0], [%2, {%3, %4, %5}], [%1];\n"
        "@e cp.async.bulk.tensor.5d.shared::cluster.global.mbarrier::complete_tx::bytes.multicast::cluster"
        " [%9], [%6, {%5, %5, %7, %5, %10}], [%1], %11;\n"
        "@e mbarrier.arrive.expect_tx.shared::cta.b64 _, [%1], %8;\n}"
        :: "r"(dst), "r"(bar), "l"(ma), "r"(ka), "r"(row), "r"(0), "l"(mb), "r"(kb), "n"(G1_STAGE_BYTES),
           "r"(dst + A_BYTES + rank * 16384), "r"(rank * 4), "h"((uint16_t)3) : "memory");
}
__device__ __forceinline__ uint4 ldg_stream(const void* p, uint64_t pol) {
    uint4 v;
    asm volatile("ld.global.nc.L1::no_allocate.L2::cache_hint.v4.u32 {%0,%1,%2,%3}, [%4], %5;"
                 : "=r"(v.x), "=r"(v.y), "=r"(v.z), "=r"(v.w) : "l"(p), "l"(pol));
    return v;
}
__device__ __forceinline__ void st_tagged(void* p, float a, float b, uint32_t tag) {
    asm volatile("st.relaxed.gpu.global.v2.b32 [%0], {%1,%2};"
                 :: "l"(p), "r"((__float_as_uint(a) & ~3u) | tag), "r"((__float_as_uint(b) & ~3u) | tag) : "memory");
}
__device__ __forceinline__ void st_relaxed(unsigned* p, uint32_t v) {
    asm volatile("st.relaxed.gpu.global.b32 [%0], %1;" :: "l"(p), "r"(v) : "memory");
}
__device__ __forceinline__ bool untagged(const uint4& v, uint32_t tag) {
    return ((v.x ^ tag) | (v.y ^ tag) | (v.z ^ tag) | (v.w ^ tag)) & 3;
}
__device__ __forceinline__ uint4 ld_relaxed(const void* p) {
    uint4 v;
    asm volatile("ld.relaxed.gpu.global.v4.b32 {%0,%1,%2,%3}, [%4];" : "=r"(v.x), "=r"(v.y), "=r"(v.z), "=r"(v.w) : "l"(p) : "memory");
    return v;
}
__device__ __forceinline__ void prefetch_map(const CUtensorMap* m) {
    asm volatile("prefetch.tensormap [%0];" :: "l"(m) : "memory");
}
template <int N> __device__ __forceinline__ void wg_wait() { asm volatile("wgmma.wait_group.sync.aligned %0;" :: "n"(N) : "memory"); }

constexpr uint32_t HI_128B = 0x40000040, HI_64B = 0x80000020;
__device__ __forceinline__ uint32_t desc_a(uint32_t addr) { return (addr & 0x3FFFF) >> 4 | 1 << 16; }
__device__ __forceinline__ uint32_t desc_b(uint32_t addr) { return (addr & 0x3FFFF) >> 4 | 512 << 16; }

#define R8(d, o) "+f"(d[o]), "+f"(d[o+1]), "+f"(d[o+2]), "+f"(d[o+3]), "+f"(d[o+4]), "+f"(d[o+5]), "+f"(d[o+6]), "+f"(d[o+7])
#define R32(d, o) R8(d, o), R8(d, o+8), R8(d, o+16), R8(d, o+24)
#define R64(d, o) R32(d, o), R32(d, o+32)
#define ACC00 "%0,%1,%2,%3,%4,%5,%6,%7,%8,%9,%10,%11,%12,%13,%14,%15,%16,%17,%18,%19,%20,%21,%22,%23,%24,%25,%26,%27,%28,%29,%30,%31,"\
    "%32,%33,%34,%35,%36,%37,%38,%39,%40,%41,%42,%43,%44,%45,%46,%47"
#define ACC0 ACC00 ",%48,%49,%50,%51,%52,%53,%54,%55,%56,%57,%58,%59,%60,%61,%62,%63"
#define ACC1 "%64,%65,%66,%67,%68,%69,%70,%71,%72,%73,%74,%75,%76,%77,%78,%79,%80,%81,%82,%83,%84,%85,%86,%87,%88,%89,%90,%91,%92,%93,%94,%95,"\
    "%96,%97,%98,%99,%100,%101,%102,%103,%104,%105,%106,%107,%108,%109,%110,%111"
#define ACC48 "{" ACC00 "}"
#define ACC64 "{" ACC0 "}"
#define ACC112 "{" ACC0 "," ACC1 "}"
#define ACC128 "{" ACC0 "," ACC1 ",%112,%113,%114,%115,%116,%117,%118,%119,%120,%121,%122,%123,%124,%125,%126,%127}"
#define MMA_K16(shape, acc, a, b, keep, ha, hb) \
    "mov.b64 da, {" a ", " ha "};\nmov.b64 db, {" b ", " hb "};\n" \
    "wgmma.mma_async.sync.aligned." shape ".f32.bf16.bf16 " acc ", da, db, " keep ", 1, 1, 0, 1;\n"
#define MMA_NEXT(op, a, b, sa, sb) op " " a ", " a ", " sa ";\n" op " " b ", " b ", " sb ";\n"
#define MMA_STEP_B(shape, acc, a, b, keep, ha, hb, sa, sb) \
    "{\n.reg .pred p, q;\n.reg .b64 da, db;\nsetp.ne.b32 p, " keep ", 0;\nsetp.eq.b32 q, 0, 0;\nwgmma.fence.sync.aligned;\n" \
    MMA_K16(shape, acc, a, b, "p", ha, hb) MMA_NEXT("xor.b32", a, b, "2", "128") MMA_K16(shape, acc, a, b, "q", ha, hb) MMA_NEXT("add.s32", a, b, sa, sb) \
    MMA_K16(shape, acc, a, b, "q", ha, hb) MMA_NEXT("xor.b32", a, b, "2", "128") MMA_K16(shape, acc, a, b, "q", ha, hb) \
    "wgmma.commit_group.sync.aligned;\n}"
#define MMA64(shape, acc, a, b, keep) "wgmma.mma_async.sync.aligned." shape ".f32.bf16.bf16 " acc ", " a ", " b ", " keep ", 1, 1, 0, 1;\n"
#define NEXT64(op, a, b, sa, sb) "mov.b64 {lo, hi}, " a ";\n" op " lo, lo, " sa ";\nmov.b64 " a ", {lo, hi};\n" \
    "mov.b64 {lo, hi}, " b ";\n" op " lo, lo, " sb ";\nmov.b64 " b ", {lo, hi};\n"
#define ADD64(op, a, b, sa, sb) "add.s64 " a ", " a ", " sa ";\nadd.s64 " b ", " b ", " sb ";\n"
#define MMA_STEP(shape, acc, a, b, na, nb, keep, sa) MMA_STEP_N(shape, acc, a, b, na, nb, keep, sa, NEXT64)
#define MMA_STEP_N(shape, acc, a, b, na, nb, keep, sa, LAST) \
    "{\n.reg .pred p, q;\n.reg .b32 lo, hi;\nsetp.ne.b32 p, " keep ", 0;\nsetp.eq.b32 q, 0, 0;\nwgmma.fence.sync.aligned;\n" \
    MMA64(shape, acc, a, b, "p") NEXT64("xor.b32", a, b, "2", "128") MMA64(shape, acc, a, b, "q") NEXT64("add.s32", a, b, sa, "128") \
    MMA64(shape, acc, a, b, "q") NEXT64("xor.b32", a, b, "2", "128") MMA64(shape, acc, a, b, "q") LAST("add.s32", a, b, na, nb) \
    "wgmma.commit_group.sync.aligned;\n}"
#define MMA_ARGS64(sa) "+l"(da), "+l"(db) : "r"(next / 16 - 4 - sa), "r"(next / 16 - 384), "r"(keep), "n"(sa) : "memory"

__device__ __forceinline__ void mma_step(float (&d)[128], uint64_t& da, uint64_t& db, int next, int keep) {
    asm volatile(MMA_STEP("m64n256k16", ACC128, "%128", "%129", "%130", "%131", "%132", "%133") : R64(d, 0), R64(d, 64), MMA_ARGS64(2));
}
__device__ __forceinline__ void mma_rank(float (&d)[128], uint32_t a0, uint32_t a1, uint32_t db) {
    asm volatile("{\n.reg .pred q;\n.reg .b64 db;\nsetp.eq.b32 q, 0, 0;\nmov.b64 db, {%131, 0x40000040};\nwgmma.fence.sync.aligned;\n"
                 "wgmma.mma_async.sync.aligned.m64n256k16.f32.bf16.bf16 " ACC128 ", {%128, %129, %130, %130}, db, q, 1, 1, 1;\n}"
                 : R64(d, 0), R64(d, 64) : "r"(a0), "r"(a1), "r"(0), "r"(db) : "memory");
}
__device__ __forceinline__ void mma_step224(float (&d)[128], uint64_t& da, uint64_t& db, int next, int keep) {
    asm volatile(MMA_STEP("m64n224k16", ACC112, "%112", "%113", "%114", "%115", "%116", "%117")
                 : R64(d, 0), R32(d, 64), R8(d, 96), R8(d, 104), MMA_ARGS64(2));
}
template <int SA> __device__ __forceinline__ void mma_step(float (&d)[64], uint64_t& da, uint64_t& db, int next, int keep) {
    asm volatile(MMA_STEP("m64n128k16", ACC64, "%64", "%65", "%66", "%67", "%68", "%69") : R64(d, 0), MMA_ARGS64(SA));
}
template <int SA> __device__ __forceinline__ void mma_step_c(float (&d)[64], uint64_t& da, uint64_t& db, int next, int keep,
                                                           uint64_t high = 0) {
    asm volatile(MMA_STEP_N("m64n128k16", ACC64, "%64", "%65", "%66", "%67", "%68", "%69", ADD64) : R64(d, 0), "+l"(da), "+l"(db)
                 : "l"((high << 32) + (next / 16 - 4 - SA)), "l"((int64_t)next / 16 - 384), "r"(keep), "n"(SA) : "memory");
}
__device__ __forceinline__ void mma_step96(float (&d)[64], uint64_t& da, uint64_t& db, int next, int keep) {
    asm volatile(MMA_STEP("m64n96k16", ACC48, "%48", "%49", "%50", "%51", "%52", "%53") : R32(d, 0), R8(d, 32), R8(d, 40), MMA_ARGS64(254));
}
__device__ __forceinline__ void mma_step_tail(float (&d)[128], uint32_t da, uint32_t b, int keep, bool down) {
    uint32_t db = (b & 0x3FFFF) >> 4 | 256 << 16;
    asm volatile(MMA_STEP_B("m64n256k16", ACC128, "%128", "%129", "%130", "%131", "0x80000040", "%132", "-96")
                 : R64(d, 0), R64(d, 64), "+r"(da), "+r"(db) : "r"(keep), "r"(down ? HI_64B : HI_128B), "r"(down ? 254 : 2) : "memory");
}

__device__ __forceinline__ uint32_t pack_bf16(float lo, float hi) {
    uint32_t r; asm("cvt.rn.bf16x2.f32 %0, %1, %2;" : "=r"(r) : "f"(hi), "f"(lo)); return r;
}
__device__ __forceinline__ float bf_lo(uint32_t v) { return __uint_as_float(v << 16); }
__device__ __forceinline__ float bf_hi(uint32_t v) { return __uint_as_float(v & 0xffff0000u); }
__device__ __forceinline__ float round_bf16(float v) { return bf_lo(pack_bf16(v, 0.f)); }
__device__ __forceinline__ uint32_t mul_bf16x2(uint32_t a, uint32_t b) {
    uint32_t r; asm("mul.rn.bf16x2 %0, %1, %2;" : "=r"(r) : "r"(a), "r"(b)); return r;
}
__device__ __forceinline__ uint32_t sub_bf16x2(uint32_t a, uint32_t b) {
    uint32_t r; asm("sub.rn.bf16x2 %0, %1, %2;" : "=r"(r) : "r"(a), "r"(b)); return r;
}
__device__ __forceinline__ uint32_t mul2_bf16x2(uint32_t a, uint32_t hi, uint32_t lo) {
    uint32_t r; asm("fma.rn.bf16x2 %0, %1, %2, %3;" : "=r"(r) : "r"(a), "r"(hi), "r"(mul_bf16x2(a, lo))); return r;
}
__device__ __forceinline__ float tanh_fast(float x) { float r; asm("tanh.approx.f32 %0, %1;" : "=f"(r) : "f"(x)); return r; }
__device__ __forceinline__ float gelu_twice(float g) {
    return fmaf(g, tanh_fast(fmaf(g * g, 0.044715f * 0.7978845608f, 0.7978845608f) * g), g);
}
__device__ __forceinline__ uint32_t geglu2(uint32_t g2, uint32_t u2) {
    return mul_bf16x2(pack_bf16(gelu_twice(bf_lo(g2)), gelu_twice(bf_hi(g2))), u2);
}
__device__ __forceinline__ uint32_t silu2(float lo, float hi) {
    const uint32_t h = mul_bf16x2(pack_bf16(lo, hi), 0x3e803e80u);
    return pack_bf16(fmaf(bf_lo(h), tanh_fast(bf_lo(h)), bf_lo(h)), fmaf(bf_hi(h), tanh_fast(bf_hi(h)), bf_hi(h)));
}
__device__ __forceinline__ float ex2_fast(float x) { float r; asm("ex2.approx.ftz.f32 %0, %1;" : "=f"(r) : "f"(x)); return r; }
__device__ __forceinline__ void unpack8(uint4 v, float (&f)[8]) {
    f[0] = bf_lo(v.x); f[1] = bf_hi(v.x); f[2] = bf_lo(v.y); f[3] = bf_hi(v.y);
    f[4] = bf_lo(v.z); f[5] = bf_hi(v.z); f[6] = bf_lo(v.w); f[7] = bf_hi(v.w);
}
template <int N> __device__ __forceinline__ void fence_regs(float (&d)[N]) {
#pragma unroll
    for (int i = 0; i < N; i++) asm volatile("" : "+f"(d[i]) :: "memory");
}

__device__ __forceinline__ float rcp_fast(float x) { float r; asm("rcp.approx.ftz.f32 %0, %1;" : "=f"(r) : "f"(x)); return r; }
__device__ __forceinline__ float sqrt_fast(float x) { float r; asm("sqrt.approx.ftz.f32 %0, %1;" : "=f"(r) : "f"(x)); return r; }
__device__ __forceinline__ uint32_t max_bf16x2(uint32_t a, uint32_t b) {
    uint32_t r; asm("max.bf16x2 %0, %1, %2;" : "=r"(r) : "r"(a), "r"(b)); return r;
}
__device__ __forceinline__ uint32_t transpose8(uint32_t a) {
    uint32_t r; asm volatile("movmatrix.sync.aligned.m8n8.trans.b16 %0, %1;" : "=r"(r) : "r"(a)); return r;
}
__device__ __forceinline__ void mma_sync(uint32_t* d, const uint32_t* a, uint32_t b0, uint32_t b1, const uint32_t* c) {
    asm volatile("mma.sync.aligned.m16n8k16.row.col.f32.bf16.bf16.f32 {%0,%1,%2,%3}, {%4,%5,%6,%7}, {%8,%9}, {%10,%11,%12,%13};"
        : "=r"(d[0]), "=r"(d[1]), "=r"(d[2]), "=r"(d[3])
        : "r"(a[0]), "r"(a[1]), "r"(a[2]), "r"(a[3]), "r"(b0), "r"(b1), "r"(c[0]), "r"(c[1]), "r"(c[2]), "r"(c[3]));
}
template <int N> struct Floats {
    float f[N];
    __device__ __forceinline__ Floats() {}
    __device__ __forceinline__ Floats(const uint32_t* p) {
#pragma unroll
        for (int i = 0; i < N; i++) asm("mov.b32 %0, %1;" : "=f"(f[i]) : "r"(p[i]));
    }
    __device__ __forceinline__ void put(uint32_t* p) const {
#pragma unroll
        for (int i = 0; i < N; i++) asm("mov.b32 %0, %1;" : "=r"(p[i]) : "f"(f[i]));
    }
    __device__ __forceinline__ float& operator[](int i) { return f[i]; }
};
__device__ __forceinline__ uint32_t fresh_tid() { uint32_t r; asm volatile("mov.u32 %0, %%tid.x;" : "=r"(r)); return r; }
template <typename T> __device__ __forceinline__ T uniform(T v) { return __shfl_sync(0xffffffffu, v, 0); }

__device__ __forceinline__ uint32_t forecast(uint32_t n0, uint32_t c0, float cycles, uint32_t tag) {
    const uint32_t n = nanos();
    return n + (int)((n - n0) * cycles * rcp_fast((uint32_t)clock() - c0)) & ~3u | tag;
}
__device__ __forceinline__ uint32_t plan_word(uint32_t base, int lane) { return uniform(lds32(base + PLAN_OFF + lane * 4)); }

__device__ __forceinline__ void fold_operands(const Params& prm, uint32_t base, int slot, int mblk, uint32_t tag, int w, int lane) {
    uint4 v[9];
#pragma unroll
    for (int m = 0; m < 9; m++) v[m] = make_uint4(0, 0, 0, 0);
    const float* parts = prm.colsum + (slot * 2 + (lane >> 4)) * 1024 + w * 64 + (lane & 15) * 4;
    const float* const rows = &offset(prm.stats, (mblk * 128 + w * 64 + lane * 2) * 8)->x;
#pragma unroll 1
    for (int spins = 0; spins < (1 << 16); spins++) {
        bool missing = false;
        asm volatile("" : "+l"(parts));
#pragma unroll
        for (int m = 0; m < 9; m++) {
            if (untagged(v[m], tag)) {
                missing = true;
                v[m] = ld_relaxed(m < 8 ? parts + m * 128 : rows);
            }
        }
        if (!missing) break;
    }
    float4 c = make_float4(0.f, 0.f, 0.f, 0.f);
#pragma unroll
    for (int m = 0; m < 8; m++) {
        c.x += __uint_as_float(v[m].x ^ tag); c.y += __uint_as_float(v[m].y ^ tag);
        c.z += __uint_as_float(v[m].z ^ tag); c.w += __uint_as_float(v[m].w ^ tag);
    }
    sts128(base + STAT_OFF + w * 512 + lane * 16, make_uint4(v[8].x ^ tag, v[8].y ^ tag, v[8].z ^ tag, v[8].w ^ tag));
    const uint32_t ca = base + AUX_OFF + w * 8192 + (lane >> 4) * 16384 + (lane & 15) * 8;
#pragma unroll
    for (int r = 0; r < 3; r++) {
        const uint32_t lo = pack_bf16(c.x, c.y), hi = pack_bf16(c.z, c.w);
        sts64f((ca ^ r * 16) + r * 128, __uint_as_float(lo), __uint_as_float(hi));
        c.x -= bf_lo(lo); c.y -= bf_hi(lo); c.z -= bf_lo(hi); c.w -= bf_hi(hi);
    }
    asm volatile("fence.proxy.async.shared::cta;" ::: "memory");
    __syncwarp();
}
__device__ __forceinline__ float2 fold(float (&acc)[128], uint32_t base, int wg) {
    const uint32_t id = fresh_tid(), sp = base + STAT_OFF + (id & 96) * 8 + (id & 28) * 4 + wg * 8;
    const uint32_t sel = id & 2 ? 0x4444 : (id & 1 ? 0x4432 : 0x3232);
    const float2 sa = lds64f(sp), sb = lds64f(sp + 128);
    mma_rank(acc, __byte_perm(__float_as_uint(sa.x), 0, sel), __byte_perm(__float_as_uint(sb.x), 0, sel), desc_b(base + AUX_OFF));
    return make_float2(sa.y, sb.y);
}

__device__ __forceinline__ uint32_t tail_job(int grp, uint32_t p, uint32_t word) {
    return p < 4 ? p * 64 + grp / 2 * 32 + 15 : word >> p % 4 * 8 & 255;
}
__device__ __forceinline__ void tail_gemm(const Params& prm, uint32_t base, unsigned epoch, int grp, int warp, int lane) {
    const uint32_t full = base + BAR_OFF, empty = full + 32, sig = full + 192, dep = full + 256, folded = full + 320;
    const uint32_t tag = 1 + (epoch & 1);
    auto plan = [&](uint32_t p, uint32_t word) { return tail_job(grp, p, word); };
    auto rows = [&](uint32_t job) { return job / 32 * 2 + grp % 2; };
    if (warp == 8) {
        if (elect_one()) { prefetch_map(&prm.xn); prefetch_map(&prm.a2); prefetch_map(&prm.wd_tail); }
#pragma unroll 1
        for (int p = 0, i = G1_STAGES; p < 8; p++) {
            const bool first = p < 4;
            if (p == 4) mbar_wait_warp(dep + 16, 0);
            const uint32_t job = plan(p, plan_word(base, lane));
#pragma unroll 1
            for (int k = p ? 0 : G1_STAGES; k <= job % 32; k++, i++) {
                if (p == 3 && k % 2 == grp / 2)
                    asm volatile("{\n.reg .pred e;\nelect.sync _|e, 0xffffffff;\n"
                        "@e cp.async.bulk.prefetch.tensor.5d.L2.global [%0, {%2, %2, %1, %2, %3}];\n}"
                        :: "l"(&prm.wd_tail), "r"(k * 8), "r"(0), "r"(grp % 2 * 4) : "memory");
                if (i == 16 || i == 24 || k == 16) mbar_wait_warp(dep + (first ? i & 8 : 24), 0);
                TRACE_S(62, i, 16); TRACE_S(63, i, 4);
                mbar_wait_warp(empty + (i & 3) * 8, ~i >> 2 & 1);
                load_tail(base + (i & 3) * G1_STAGE_BYTES, full + (i & 3) * 8, first ? (p ? &prm.xn : &prm.x) : &prm.a2,
                          first ? &prm.wu_tail : &prm.wd_tail, p ? 0 : k * 64,
                          p ? (first ? rows(job) * G1_KSTEPS + k : rows(job) * G2_KSTEPS + 16 + k) * 128 : rows(job) * 64, grp % 2, first ? k * 2 : k * 8);
            }
        }
        return;
    }
    if (warp == 9) {
        const uint32_t n0 = nanos(), c0 = clock();
#pragma unroll 1
        for (int j = 0; j < 3; j++) {
            flag_wait<true>(prm.flags + (F_LN + j) * 512 + (j < 2 ? lane % 4 * 4 + grp : lane % 16) * 32, epoch * CNT_LN);
            fence_proxy_async();
            __syncwarp();
            if (lane == 0 && j < 2) mbar_arrive(dep + j * 8);
        }
        mbar_wait_warp(sig + 8, 0);
        if (lane == 0) st_relaxed(prm.flags + F_PACE * 512 + 64 + grp, forecast(n0, c0, DUE, tag));
        uint4 v, w;
#pragma unroll 1
        for (int spins = 0; spins < (1 << 19); spins++) {
            v = ld_relaxed(prm.flags + F_PACE * 512 + lane / 2 * 4);
            w = ld_relaxed(prm.flags + F_PACE * 512 + 64);
            if (!__any_sync(0xffffffffu, untagged(v, tag) || untagged(w, tag))) break;
            __nanosleep(256);
        }
        const uint32_t ref = uniform(v.x);
        const int due = min(max((int)((grp & 2 ? w.z : w.x) - ref), -100000), 100000) * 8;
        int late = max(max((int)(v.x - ref), (int)(v.y - ref)), max((int)(v.z - ref), (int)(v.w - ref)));
        late = min(max(max(late, __shfl_xor_sync(0xffffffffu, late, 2)), -100000), 100000) * LATE_SCALE + lane / 4;
        TRACE_PUT(16 + lane / 4, late + (1 << 20));
        int place = 0, n = SHARE_MIN;
#pragma unroll 1
        for (int g = 0; g < 32; g += 4) place += __shfl_sync(0xffffffffu, late, g) > late;
        const bool swap = (__reduce_add_sync(0xffffffffu, place + 1 & 2 ? late : -late) ^ w.x - w.z) >> 31;
        const bool mine = (place + 1 >> 1 & 1 ^ swap) == grp / 2;
#pragma unroll 1
        for (int j = 4 * SHARE_MIN; j < SHARE_SUM; j++) {
            const int most = __reduce_max_sync(0xffffffffu, mine && n < SHARE_MAX ? late : INT_MIN);
            if (j >= SHARE_LOW && due + (j - 38) * SPARE_NS * 8 > most) break;
            if (j == 38) TRACE_PUT(32, most - due + (1 << 20));
            if (most == late) { n++; late -= SHARE_NS * 8; }
        }
        auto first = [](uint32_t bits, int n) { return bits & (1u << min(max(n, 0), 24)) - 1; };
        const uint32_t job = lane / 4 * 32 + n - 1;
        if (mine) st_relaxed(offset(prm.flags, rows(job) * 128) + F_SHARE * 512,
                             epoch << 24 | first(0x2aaaaa, 2 * n) | first(0x104104, 6 * n - 66) | first(0x10410, 6 * n - 90) |
                             first(0x41041, 6 * n - 108));
        if (mine) TRACE_PUT(24 + lane / 4, n);
        sts32(base + PLAN_OFF, __reduce_or_sync(0xffffffffu, mine ? job << place / 2 * 8 : 0));
        if (lane == 0) mbar_arrive(dep + 16);
        flag_wait<true>(offset(prm.flags, lane % 16 * 128) + F_SECOND * 512, epoch * CNT_LN);
        fence_proxy_async();
        __syncwarp();
        if (lane == 0) mbar_arrive(dep + 24);
        return;
    }
    asm volatile("setmaxnreg.inc.sync.aligned.u32 %0;" :: "n"(CONSUMER_REGS) : "memory");
    const uint32_t da = desc_a(base + (warp >> 2) * 8192);
    uint4* out = prm.tail;
    float acc[128];
    uint32_t pk[64];
    float2 inv = make_float2(0.f, 0.f);
    int i = 0, last;
    uint32_t peer;
    asm volatile("mapa.shared::cluster.u32 %0, %1, %2;" : "=r"(peer) : "r"(empty), "r"(lane & 1));
    auto release = [&]() {
        if ((threadIdx.x & 126) == 0 && i <= last)
            asm volatile("mbarrier.arrive.shared::cluster.b64 _, [%0];" :: "r"(peer + (i - 1 & 3) * 8) : "memory");
    };
    auto store = [&](int j) {
        asm volatile("st.global.v4.u32 [%0], {%1,%2,%3,%4};" :: "l"(out + j / 2 * 8192 + j % 2 * 256),
                     "r"(pk[4 * j]), "r"(pk[4 * j + 1]), "r"(pk[4 * j + 2]), "r"(pk[4 * j + 3]) : "memory");
    };
    auto step = [&](int k, int left) {
        mbar_wait(full + (i & 3) * 8, i >> 2 & 1);
        TRACE_S(45, warp * 128 + i, 0);
        if (warp >= 4 && left == G1_SKEW) asm volatile("bar.sync 1, 256;" ::: "memory");
        mma_step_tail(acc, da + (i & 3) * (G1_STAGE_BYTES / 16), base + A_BYTES + (i & 3) * G1_STAGE_BYTES, k, i >= 4 * G1_KSTEPS);
        if (warp < 4 && left == 1) asm volatile("bar.arrive 1, 256;" ::: "memory");
    };
    auto drip = [&](int p, int& n) {
        if (n > 0) { store(0); store(1); }
#pragma unroll
        for (int j = 8; j < 64; j++) asm volatile("mov.b32 %0, %1;" : "=r"(pk[j - 8]) : "r"(pk[j]));
        out += 8192;
        __syncwarp();
        if (--n == 0 && lane == 0) mbar_arrive(sig + p * 8 - 8);
    };
#pragma unroll
    for (int j = 0; j < 128; j++) asm volatile("mov.b32 %0, 0;" : "=f"(acc[j]));
#pragma unroll
    for (int j = 0; j < 64; j++) asm volatile("mov.b32 %0, 0;" : "=r"(pk[j]));
#pragma unroll 1
    for (int p = 0; p < 8; p++) {
        step(0, 0);
        i++;
        const uint32_t word = plan_word(base, lane), job = plan(p, word);
        last = __dp4a(word & 0x1f1f1f1fu, 0x01010101u, 4u * G1_KSTEPS);
#pragma unroll 1
        for (int left = job % 32, n = p ? 8 : 0; left > 0; left--) {
            if (i == G1_KSTEPS - 1) { mbar_wait(folded, 0); inv = fold(acc, base, warp >> 2); }
#pragma unroll 1
            do drip(p, n); while (n & 7 >> 31 - __clz(job % 32));
            step(1, left);
            wg_wait<1>();
            release();
            i++;
        }
        wg_wait<0>();
        fence_regs(acc);
        release();
        if (p == 0) {
#pragma unroll
            for (int j = 0; j < 128; j++) acc[j] *= j & 2 ? inv.y : inv.x;
            fence_regs(acc);
        }
        if (warp == 4) TRACE_PUT(46 + p + p / 4 * 3, (uint32_t)clock());
#pragma unroll
        for (int j = 0; j < 64; j++) pk[j] = pack_bf16(acc[2 * j], acc[2 * j + 1]);
        out = prm.tail + p / 4 * NGEMM * 512 + rows(job) * 512 + threadIdx.x;
    }
#pragma unroll
    for (int j = 0; j < 16; j++) store(j);
    __syncwarp();
    TRACE_S(58, warp, 4);
    if (lane == 0) mbar_arrive(sig + 56);
}

__device__ __forceinline__ int gate_col(int t, int nslot) { return t == 2 ? 960 + nslot * 64 : max(t * 1024 - 1536, 0) + nslot * 128; }

struct Role {
    int rank, role, mblk, nslot;
    __device__ __forceinline__ Role() {
        uint32_t id;
        asm volatile("mov.u32 %0, %%ctaid.x;" : "=r"(id));
        const uint32_t cl = id / 2;
        rank = id & 1;
        role = pick(cl < 4, 32 + cl * 8, cl - 8 + max(4u, (cl - 1) * 37 >> 8)) * 2 + rank;
        mblk = role & 15; nslot = role >> 4;
    }
};

__global__ void __cluster_dims__(2, 1, 1) __launch_bounds__(384, 1)
fused_kernel(const __grid_constant__ Params prm) {
    TRACE_GET(c0);
    const uint32_t base = smem_u32(smem_raw) & ~1023u;
    const uint32_t bars = base + BAR_OFF;
    auto full1 = [&](int s) { return bars + s * 8; };
    auto empty1 = [&](int s) { return bars + 32 + s * 8; };
    auto full2 = [&](int s) { return bars + 64 + s * 8; };
    auto empty2 = [&](int s) { return bars + 128 + s * 8; };
    const uint32_t sig_bar = bars + 192, dep_bar = bars + 256, cs_bar = bars + 304, fold_bar = bars + 320, x_bar = bars + 352;
    const uint32_t halo_bar = dep_bar + 32;
    auto stage2 = [&](int q) { return base + q * G2_STAGE_BYTES; };
    const uint32_t aux = base + AUX_OFF;

    asm volatile("{\n.reg .pred p;\nsetp.eq.u32 p, %1, 0;\n@p mbarrier.init.shared::cta.b64 [%0], 1;\n"
        "fence.mbarrier_init.release.cluster;\nbarrier.cluster.arrive.relaxed.aligned;\n}" :: "r"(bars), "r"(threadIdx.x) : "memory");
    const int warp = __shfl_sync(0xffffffffu, threadIdx.x >> 5, 0);
    auto cluster_wait = []() { asm volatile("barrier.cluster.wait.acquire.aligned;" ::: "memory"); };
    if ((warp | (blockIdx.x & NGEMM)) == 8) {
        const Role r;
        asm volatile("{\n.reg .pred e;\nelect.sync _|e, 0xffffffff;\n"
            "@e prefetch.tensormap [%0];\n@e prefetch.tensormap [%1];\n}" :: "l"(&prm.x), "l"(&prm.wg + r.rank) : "memory");
        cluster_wait();
        load_stage1(base, base + A_BYTES + r.rank * 16384, full1(0), &prm.x, &prm.wg + r.rank, &prm.wg + r.rank, 0, 0, r.mblk * 64,
                    r.nslot * 128, r.nslot * 128 + 64, 0, stream_policy());
    } else {
        cluster_wait();
    }
    const uint32_t t0 = clock();
    {
        uint32_t cta;
        asm volatile("mov.u32 %0, %%ctaid.x;" : "=r"(cta));
        if ((warp | (~cta & NGEMM)) == 8) load_tail(base, full1(0), &prm.x, &prm.wu_tail, 0, (cta - NGEMM) * 64, cta & 1, 0);
    }
    asm volatile("{\n.reg .pred e, q;\nelect.sync _|e, 0xffffffff;\nsetp.ne.and.u32 q, %2, 0, e;\n"
        "@q mbarrier.init.shared::cta.b64 [%0], %1;\n@e mbarrier.init.shared::cta.b64 [%0 + 8], %1;\n"
        "@e mbarrier.init.shared::cta.b64 [%0 + 16], %1;\n@e mbarrier.init.shared::cta.b64 [%0 + 24], %1;\n"
        "fence.mbarrier_init.release.cluster;\nbarrier.cluster.arrive.relaxed.aligned;\n}"
        :: "r"(bars + warp * 32), "r"(1 << (0x10fa08 >> warp * 2 & 3)), "r"(warp) : "memory");
    const int lane = threadIdx.x & 31;
    const Role me;
    const int rank = me.rank, role = me.role, mblk = me.mblk, nslot = me.nslot;
    const CUtensorMap* const w0 = &prm.wg + rank;

    unsigned* const flags = prm.flags + mblk * 32;
    if (warp >= 8) {
        asm volatile("setmaxnreg.dec.sync.aligned.u32 %0;" :: "n"(AUX_REGS));
        if (warp == 9) { TRACE_CLEAR(); TRACE_GT(0); TRACE_PUT(1, c0); }
        if ((warp | (~blockIdx.x & NGEMM)) == 8) {
#pragma unroll 1
            for (int i = 1; i < G1_STAGES; i++) {
                if (i == 1) cluster_wait();
                TRACE_S(57, i, 1);
                load_tail(base + i * G1_STAGE_BYTES, full1(i), &prm.x, &prm.wu_tail, i * 64, (blockIdx.x - NGEMM) * 64, blockIdx.x & 1, i * 2);
            }
        } else {
            cluster_wait();
        }
    }

    if (blockIdx.x >= NGEMM && warp < 10) {
        if (warp < 8) cluster_wait();
        const uint32_t seen = __ldcg(prm.epoch + blockIdx.x * 16);
        tail_gemm(prm, base, seen + 1, blockIdx.x - NGEMM, warp, lane);
    } else if (warp == 9) {
        const unsigned epoch = __ldcg(prm.epoch + blockIdx.x * 16 + 2) + 1;
        const uint32_t n0 = nanos(), c1 = clock();
        {
            const __nv_bfloat16* const w = prm.pwu + ((mblk >> 1) * 128 + lane / 2) * DF + gate_col(4, nslot) + 96 + rank * 16 + lane % 2 * 8;
            uint4 v[8];
            float cs[8], f[8];
            mbar_wait(empty1(SUM2_STEP), 0);
#pragma unroll
            for (int j = 0; j < 8; j++) v[j] = __ldg(reinterpret_cast<const uint4*>(w + j * 16 * DF));
            unpack8(v[0], cs);
#pragma unroll
            for (int j = 1; j < 8; j++) {
                unpack8(v[j], f);
#pragma unroll
                for (int d = 0; d < 8; d++) cs[d] += f[d];
            }
#pragma unroll
            for (int d = 0; d < 4; d++)
                cs[d] = (lane & 16 ? cs[d + 4] : cs[d]) + __shfl_xor_sync(0xffffffffu, lane & 16 ? cs[d] : cs[d + 4], 16);
#pragma unroll
            for (int d = 0; d < 2; d++) {
                cs[d] = (lane & 8 ? cs[d + 2] : cs[d]) + __shfl_xor_sync(0xffffffffu, lane & 8 ? cs[d] : cs[d + 2], 8);
                cs[d] += __shfl_xor_sync(0xffffffffu, cs[d], 4);
                cs[d] += __shfl_xor_sync(0xffffffffu, cs[d], 2);
            }
            if (!(lane & 6))
                st_tagged(prm.colsum + (16 + nslot / 4) * 1024 + (mblk >> 1) * 128 + nslot % 4 * 32 + rank * 16 + lane % 2 * 8 + (lane >> 3) * 2,
                          cs[0], cs[1], 1 + (epoch & 1));
            TRACE(61);
        }
        if (lane == 0) {
            mbar_wait(sig_bar, 0);
            TRACE(11);
            flag_add(flags + F_LN * 512);
            TRACE(42);
            flag_wait(flags + F_LN * 512, epoch * CNT_LN);
            fence_proxy_async();
            mbar_arrive(dep_bar);
            mbar_wait(sig_bar + 56, 0);
            flag_add(flags + F_LN2 * 512);
            flag_wait(flags + F_LN2 * 512, epoch * CNT_LN);
            fence_proxy_async();
            mbar_arrive(dep_bar + 40);
            TRACE(59);
            prm.epoch[blockIdx.x * 16 + 2] = epoch;
#pragma unroll 1
            for (int p = 3; p < 7; p++) {
                mbar_wait(sig_bar + (p == 3 ? 16 : p * 8), 0);
                TRACE_S(37, p, 4);
                flag_add(flags + (p - (p < F_EARLY)) * 512);
                TRACE_S(43, p, 4);
                if (p == 3 && rank == 0) {
                    mbar_wait(sig_bar + 24, 0);
                    st_relaxed(prm.flags + F_PACE * 512 + mblk * 4 + nslot, forecast(n0, c1, REST, 1 + (epoch & 1)));
                }
            }
        }
    } else if (warp < 8) {
        asm volatile("setmaxnreg.inc.sync.aligned.u32 %0;" :: "n"(CONSUMER_REGS));
        const int wg = __shfl_sync(0xffffffffu, threadIdx.x >> 7, 0);
        const int cw = threadIdx.x >> 5;
        const int tid = threadIdx.x & 127;
        int spins = 1 << 18;
        float acc[128];
        uint32_t pk[64];
#pragma unroll
        for (int i = 0; i < 64; i++) asm volatile("mov.b32 %0, 0;" : "=r"(pk[i]));
#pragma unroll
        for (int i = 0; i < 128; i++) asm volatile("mov.b32 %0, 0;" : "=f"(acc[i]));
        cluster_wait();

        auto row0 = [&](uint32_t id) { return mblk * 128 + (id & 96) + wg; };
        __nv_bfloat16* optr = const_cast<__nv_bfloat16*>(prm.px) + (mblk * 128 + nslot * 16 + cw * 2) * DM + lane * 8;
        uint64_t da = desc_a(base + wg * 8192) | (uint64_t)prm.hi[0] << 32, db = desc_b(base + A_BYTES) | (uint64_t)prm.hi[1] << 32;
        auto next1 = [](int s) { return ((s + 1) % G1_STAGES - s) * G1_STAGE_BYTES; };
        auto next2 = [](int q) { return ((q + 1) % G2_STAGES - q) * G2_STAGE_BYTES; };
        uint32_t peer_bars;
        asm volatile("mapa.shared::cluster.u32 %0, %1, %2;" : "=r"(peer_bars) : "r"(bars), "r"(tid & 1));
        if (tid >= 2) peer_bars = 0;
        auto release = [&](uint32_t bar) {
            if (peer_bars) asm volatile("mbarrier.arrive.shared::cluster.b64 _, [%0];" :: "r"(peer_bars + (bar - bars)) : "memory");
        };
        auto up = [](int i) { return 32 + (i & 24) + (i & 3) * 2 + (i >> 2 & 1); };
        auto store_pk = [&](__nv_bfloat16* p, int j) {
            asm volatile("st.global.v4.u32 [%0], {%1,%2,%3,%4};"
                         :: "l"(p), "r"(pk[4 * j]), "r"(pk[4 * j + 1]), "r"(pk[4 * j + 2]), "r"(pk[4 * j + 3]) : "memory");
        };
        auto chunk_geglu = [&](int j) {
#pragma unroll
            for (int i = 4 * j; i < 4 * j + 4; i++) pk[i] = geglu2(pk[i], pk[up(i)]);
            store_pk(optr + (j & 1) * 256 + (j & 2) * 1024 + (j & 4) * 2048, j);
        };
        auto signal_stores = [&](int p) { __syncwarp(); if (lane == 0) mbar_arrive(sig_bar + p * 8); };

        auto chunk_ln = [&](int k) {
            Floats<6> mo(pk + 32);
            if (k == 0) {
                const uint4* xp = reinterpret_cast<const uint4*>(optr);
                pk[38] = __ldcg(prm.epoch + blockIdx.x * 16 + 2);
#pragma unroll
                for (int i = 0; i < 8; i++) {
                    const uint4 v = ldg_stream(xp + i * 32, stream_policy());
                    pk[4 * i] = v.x; pk[4 * i + 1] = v.y; pk[4 * i + 2] = v.z; pk[4 * i + 3] = v.w;
                }
            } else if (k >= LN_STEP && k < LN_STEP + 3) {
                if (k == LN_STEP) {
                    mo[0] = bf_lo(uniform(pk[0])); mo[1] = bf_lo(uniform(pk[16]));
                    mo[2] = mo[3] = mo[4] = mo[5] = 0.f;
                }
#pragma unroll
                for (int i = (k - LN_STEP) * 11; i < (k - LN_STEP) * 11 + 11 && i < 32; i++) {
                    const int r = i & 1;
                    const uint32_t w = pk[r * 16 + i / 2];
                    const float lo = bf_lo(w) - mo[r], hi = bf_hi(w) - mo[r];
                    mo[2 + r] += lo + hi;
                    mo[4 + r] = fmaf(hi, hi, fmaf(lo, lo, mo[4 + r]));
                }
                mo.put(pk + 32);
            } else if (k == LN_STEP + 3) {
                const bool second = lane & 16;
                float m1 = (second ? mo[3] : mo[2]) + __shfl_xor_sync(0xffffffffu, second ? mo[2] : mo[3], 16);
                float m2 = (second ? mo[5] : mo[4]) + __shfl_xor_sync(0xffffffffu, second ? mo[4] : mo[5], 16);
#pragma unroll
                for (int o = 8; o > 0; o >>= 1) {
                    m1 += __shfl_xor_sync(0xffffffffu, m1, o);
                    m2 += __shfl_xor_sync(0xffffffffu, m2, o);
                }
                m1 *= 1.f / DM;
                const float var = fmaxf(fmaf(-m1, m1, m2 * (1.f / DM)), 0.f);
                const float mean = round_bf16((second ? mo[1] : mo[0]) + m1);
                const float inv = rcp_fast(round_bf16(sqrt_fast(round_bf16(round_bf16(var) + 1e-5f))));
                if ((lane & 15) == 0) st_tagged(prm.stats + (uint32_t)(optr - prm.px) / DM + second, -mean, inv, 2 - (pk[38] & 1));
                const uint32_t id = fresh_tid();
                optr = prm.pxn + mblk * 128 * DM + nslot * 512 + (id & 24) * 1024 + (id & 224) * 2 + (id & 7 ^ id >> 5) * 8;
                const uint32_t split = pack_bf16(inv - round_bf16(inv), inv);
#pragma unroll
                for (int r = 0; r < 2; r++) {
                    const uint32_t f = __shfl_sync(0xffffffffu, split, r * 16);
                    pk[32 + 3 * r] = __byte_perm(__shfl_sync(0xffffffffu, __float_as_uint(mean), r * 16), 0, 0x3232);
                    pk[33 + 3 * r] = __byte_perm(f, 0, 0x3232);
                    pk[34 + 3 * r] = __byte_perm(f, 0, 0x1010);
                }
            } else if (k >= LN_STEP + 4 && k < LN_STEP + 8) {
#pragma unroll
                for (int i = k - LN_STEP - 4; i < 8; i += 4) {
                    const uint32_t* n = pk + 32 + i / 4 * 3;
#pragma unroll
                    for (int j = 4 * i; j < 4 * i + 4; j++) pk[j] = mul2_bf16x2(sub_bf16x2(pk[j], n[0]), n[1], n[2]);
                    store_pk(optr + i % 4 * 32768 + i / 4 * 4096, i);
                }
                if (k == LN_STEP + 5 || k == LN_STEP + 7) signal_stores(k == LN_STEP + 5 ? 0 : 7);
            } else if (k == FOLD_STEP) {
                mbar_wait(fold_bar, 0, spins);
                const float2 inv = fold(acc, base, wg);
                mo[0] = inv.x; mo[1] = inv.y;
                mo.put(pk + 32);
            }
        };

        auto halo = [&]() { const uint32_t id = fresh_tid(); return aux + (id & 96) * 128 + (id & 128) * 16 + (id & 31) * 4; };
        auto put = [&](uint32_t a, uint32_t v0, uint32_t v1) {
            asm volatile("st.shared.u32 [%0], %1;\nst.shared.u32 [%0 + 128], %2;" :: "r"(a + HALO_BYTES), "r"(v0), "r"(v1) : "memory");
        };
        auto get = [&](uint32_t a, uint32_t& v0, uint32_t& v1) {
            asm volatile("ld.shared.u32 %0, [%2];\nld.shared.u32 %1, [%2 + 128];" : "=r"(v0), "=r"(v1) : "r"(a) : "memory");
        };
        auto publish = [&](int p) { asm volatile("fence.proxy.async.shared::cta;" ::: "memory"); signal_stores(p); };
        const uint32_t zero[4] = {0, 0, 0, 0};
        auto meet = [&](int n, int k, uint32_t id) {
            if (n == 15 - MEET)
                asm volatile("{\n.reg .b32 c;\nmov.u32 c, %%clock;\nbar.arrive %1, 256;\nlop3.b32 %0, %0, c, 1, 0x70;\n}"
                             : "+r"(peer_bars) : "r"(2 + id / 128) : "memory");
            if (n == 15) {
                asm volatile("{\n.reg .b32 c;\nmov.u32 c, %%clock;\nbar.sync %1, 256;\nlop3.b32 %0, %0, c, 1, 0x70;\n}"
                             : "+r"(peer_bars) : "r"(3 - id / 128) : "memory");
                mma_step(acc, da, db, next1(k & 3), k);
                asm volatile("// batch step");
            }
        };
        auto mix_qk = [&]() {
            uint32_t c[2][4];
            const uint32_t a = halo(), id = fresh_tid();
            mbar_wait(halo_bar, 0, spins);
#pragma unroll
            for (int n = 0; n < 16; n++) {
                const int b = 1 - n / 8, h = (n & 4) / 2 + n % 2, j = n / 2 % 2;
                uint32_t* const kq = pk + 32 + 8 * h + 4 * j;
                uint32_t* const q = pk + 8 * h + 4 * b;
                mma_sync(j ? q : c[n % 2], kq, q[2 * j], q[2 * j + 1], j ? c[n % 2] : zero);
                if (b) get(a + (h * 2 + j) * 256, kq[1], kq[3]);
                meet(n, QK_STEP, id);
            }
        };
        auto chunk_qk = [&](int k) {
            constexpr float LOG2E = 1.4426950408889634f;
            uint32_t* const l = pk + 32;
            Floats<16> e(pk);
            if (k == KEY_STEP) {
                const uint32_t a = halo();
#pragma unroll
                for (int i = 0; i < 8; i++) put(a + i * 256, pk[33 + 4 * i], pk[35 + 4 * i]);
                publish(1);
            } else if (k == QK_STEP + 1) {
                const uint32_t id = fresh_tid();
                const bool u0 = id % 32 / 4 > id % 4 * 2, u1 = id % 32 / 4 > id % 4 * 2 + 1;
                const uint32_t gone = row0(id) < 2 ? (u0 ? 0xffffu : 0u) | (u1 ? 0xffff0000u : 0u) : 0u;
#pragma unroll
                for (int n = 0; n < 8; n++) {
                    const int b = n % 2;
                    const uint32_t* const c = pk + 4 * n;
                    uint32_t v = pack_bf16(__uint_as_float(pick(u0, c[2 - 2 * b], c[2 * b])), __uint_as_float(pick(u1, c[3 - 2 * b], c[1 + 2 * b])));
                    v = mul2_bf16x2(v, 0x3e353e35u, 0x379e379eu);
                    if (!b) v = v & ~gone | 0xce6ece6eu & gone;
                    l[n] = transpose8(v);
                }
            } else if (k == QK_STEP + 2) {
#pragma unroll
                for (int h = 0; h < 4; h++) {
                    uint32_t m = max_bf16x2(__byte_perm(l[2 * h], l[2 * h + 1], 0x5410), __byte_perm(l[2 * h], l[2 * h + 1], 0x7632));
                    m = max_bf16x2(m, __shfl_xor_sync(0xffffffffu, m, 1));
                    m = max_bf16x2(m, __shfl_xor_sync(0xffffffffu, m, 2));
#pragma unroll
                    for (int n = 2 * h; n < 2 * h + 2; n++) {
                        const float f = -LOG2E * (n % 2 ? bf_hi(m) : bf_lo(m));
                        e[2 * n] = ex2_fast(fmaf(bf_lo(l[n]), LOG2E, f));
                        e[2 * n + 1] = ex2_fast(fmaf(bf_hi(l[n]), LOG2E, f));
                    }
                }
                e.put(pk);
            } else if (k == QK_STEP + 3) {
                uint32_t p[8];
#pragma unroll
                for (int n = 0; n < 8; n++) {
                    float sum = e[2 * n] + e[2 * n + 1];
                    sum += __shfl_xor_sync(0xffffffffu, sum, 1);
                    sum += __shfl_xor_sync(0xffffffffu, sum, 2);
                    const float r = rcp_fast(sum);
                    p[n] = pack_bf16(e[2 * n] * r, e[2 * n + 1] * r);
                }
                const uint32_t a = aux + 5 * HALO_BYTES + fresh_tid() * 16;
                sts128(a, make_uint4(p[0], p[1], p[2], p[3]));
                sts128(a + 4096, make_uint4(p[4], p[5], p[6], p[7]));
            }
        };
        auto values = [&](int h) { return pk + (h & 2) * 16 + (h & 1) * 8; };
        auto mix_pv = [&]() {
            uint32_t lo[8], hi[8];
            const uint32_t id = fresh_tid();
            const uint32_t keep = (id % 4 * 2 > id % 32 / 4 ? 0xffffu : 0u) | (id % 4 * 2 + 1 > id % 32 / 4 ? 0xffff0000u : 0u);
            const uint4 p0 = lds128(aux + 5 * HALO_BYTES + id * 16), p1 = lds128(aux + 6 * HALO_BYTES + id * 16);
            const uint32_t p[8] = {p0.x, p0.y, p0.z, p0.w, p1.x, p1.y, p1.z, p1.w};
#pragma unroll
            for (int n = 0; n < 8; n++)
                asm volatile("and.b32 %0, %2, %3;\nand.b32 %1, %2, %4;" : "=r"(lo[n]), "=r"(hi[n])
                             : "r"(p[n]), "r"(n % 2 ? keep : ~keep), "r"(n % 2 ? ~keep : keep));
            mbar_wait(halo_bar, 1, spins);
#pragma unroll
            for (int n = 0; n < 16; n++) {
                const int i = (n & 8) / 2 + (n & 2) + (n & 4) / 4;
                mma_sync(pk + 4 * (n ^ 4), pk + 4 * (n ^ 4), lo[i], hi[i], zero);
                meet(n, PV_STEP, id);
            }
        };
        auto chunk_pv = [&](int k) {
            if (k == VAL_STEP || k == VAL_STEP + 1) {
                const uint32_t a = halo();
#pragma unroll
                for (int h = (k - VAL_STEP) * 2; h < (k - VAL_STEP + 1) * 2; h++) {
                    uint32_t* const w = values(h);
                    uint32_t v[8];
#pragma unroll
                    for (int i = 0; i < 8; i++) v[i] = transpose8(w[h < 2 ? (i & 1) + (i & 2) * 2 + (i & 4) / 2 : (i & 1) * 2 + (i & 2) / 2 + (i & 4)]);
#pragma unroll
                    for (int i = 0; i < 8; i++) w[i] = v[i];
                    put(a + h * 512, w[2], w[3]);
                    put(a + h * 512 + 256, w[6], w[7]);
                }
                if (k > VAL_STEP) publish(3);
            } else if (k == PV_STEP - 1) {
                const uint32_t a = halo(), id = fresh_tid();
                optr = prm.pa2 + (mblk * K2 + nslot * 128) * 128 + (id & 224) * 32 + id % 4 * 128 + (id >> 2 & 7 ^ id % 4 * 2) * 8;
                mbar_wait(halo_bar, 1, spins);
#pragma unroll
                for (int n = 0; n < 8; n++) {
                    uint32_t* const w = values(n / 2) + n % 2 * 4;
                    w[16] = w[0]; w[17] = w[1];
                    get(a + n * 256, w[18], w[19]);
                }
            } else if (k > PV_STEP && k <= PV_STEP + OUT_STEPS) {
#pragma unroll
                for (int n = 0; n < 8; n++) {
                    if (n * OUT_STEPS / 8 != k - PV_STEP - 1) continue;
                    const int j = n ^ n >> 1 & 1;
                    if (n % 2) optr = reinterpret_cast<__nv_bfloat16*>(reinterpret_cast<uintptr_t>(optr) ^ 16);
                    Floats<15> c(pk + j / 2 * 16 + j % 2);
                    asm volatile("st.global.v4.u32 [%0], {%1,%2,%3,%4};"
                                 :: "l"(optr + (~j & 2) * 256 + j % 2 * 64 + j / 4 * 8192), "r"(pack_bf16(c[0], c[2])),
                                    "r"(pack_bf16(c[4], c[6])), "r"(pack_bf16(c[8], c[10])), "r"(pack_bf16(c[12], c[14])) : "memory");
                }
                if (k == PV_STEP + OUT_STEPS) signal_stores(4);
            }
        };

        TRACE_SLOT(tile_slot, 16 + wg * 8);
#pragma unroll 1
        for (int t = 0; t < G1_TILES; t++) {
#pragma unroll
            for (int k = 0; k < G1_KSTEPS; k++) {
                const int s = k & 3;
                if (k == 0) asm volatile("" : "+r"(t));
                TRACE_STEP(t, k, 0);
                mbar_wait(full1(s), (k >> 2) & 1, spins);
                if (k == 0) TRACE_S(12, t, 0);
                TRACE_STEP(t, k, 1);
                if (wg == 1 && k == G1_KSTEPS - G1_SKEW) asm volatile("bar.sync 1, 256;" ::: "memory");
                if (k == PV_STEP && t == 3) mix_pv();
                else if (k == QK_STEP && t == 2) mix_qk();
                else if (t == G1_TILES - 1) mma_step224(acc, da, db, next1(s), k);
                else mma_step(acc, da, db, next1(s), k);
                if (wg == 0 && k == G1_KSTEPS - 1) asm volatile("bar.arrive 1, 256;" ::: "memory");
                wg_wait<1>();
                if (k > 0) release(empty1((k - 1) & 3));
                TRACE_STEP(t, k, 2);
                if (t == 0) chunk_ln(k);
                if (k >= 1 && k <= 8 && ((k < HALF_STEP || k > HALF_STEP + 3 ? 0x12 : 0x1a) >> t & 1)) {
                    chunk_geglu(k < HALF_STEP ? k - 1 : (k > HALF_STEP + 3 ? k - 5 : k - HALF_STEP + 4));
                    if (k == 8 && t != 3) signal_stores(t + 1);
                }
                if (t == 2) chunk_qk(k);
                if (t == 3) chunk_pv(k);
                if (k == PV_STEP + OUT_STEPS) {
                    const uint32_t id = fresh_tid();
                    optr = prm.pa2 + (mblk * K2 + DM + gate_col(t, nslot)) * 128 + (id & 128) * 32 + (id & 96) * 16 + (id & 31 ^ id >> 3 & 3) * 8;
                    asm volatile("" : "+l"(optr));
                }
            }
            wg_wait<0>();
            fence_regs(acc);
            release(empty1(3));
            if (t == 0) {
                Floats<2> inv(pk + 32);
#pragma unroll
                for (int i = 0; i < 128; i++) acc[i] *= inv[i / 2 % 2];
                fence_regs(acc);
            }
#pragma unroll
            for (int i = 0; i < 64; i++) {
                const int e = i < 32 ? (i & ~7) * 2 + (i & 3) * 4 + (i & 4) / 2 : i * 2;
                pk[i] = pack_bf16(acc[e], acc[e + 1]);
            }
            TRACE_NEXT(tile_slot);
        }

        float accd[64], accs[64];
        asm volatile("{\n.reg .b32 lo, hi;\nmov.b64 {lo, hi}, %0;\nxor.b32 hi, hi, %1;\nmov.b64 %0, {lo, hi};\n}" : "+l"(da) : "n"(HI_64B ^ HI_128B));
#pragma unroll
        for (int i = 0; i < 64; i++) accd[i] = 0.f;
#pragma unroll
        for (int u = 0; u < G2_HEAD; u++) {
            const int q = u % G2_STAGES;
            TRACE_STEP(5, u, 0);
            mbar_wait(full2(q), (u / G2_STAGES) & 1, spins);
            TRACE_STEP(5, u, 1);
            if (u % 2) mma_step_c<254>(accd, da, db, next2(q), u);
            else mma_step<254>(accd, da, db, next2(q), u);
            wg_wait<1>();
            if (u > 0) release(empty2((u - 1) % G2_STAGES));
            TRACE_STEP(5, u, 2);
            if (u == UP_STEP) {
#pragma unroll
                for (int i = 0; i < 2; i++) {
                    const uint4 v = ldg_stream(prm.tail + role * 512 + i * 256 + threadIdx.x, stream_policy());
                    pk[56 + 4 * i] = v.x; pk[57 + 4 * i] = v.y; pk[58 + 4 * i] = v.z; pk[59 + 4 * i] = v.w;
                }
            }
            if (u >= 1) {
                const int j = (u - 1) / 2;
#pragma unroll
                for (int i = 2 * u - 2; i < 2 * u; i++) pk[i] = geglu2(pk[i], pk[up(i)]);
                if (u % 2 == 0) store_pk(optr + (j & 1) * 256 + (j & 2) * 1024 + (j & 4) * 2048, j);
            }
            if (u == G2_HEAD - 1) signal_stores(6);
        }
        auto down = [&](int q, uint32_t phase, bool narrow, bool busy = false) {
            mbar_wait(full2(q), phase, spins);
            if (narrow) mma_step96(accd, da, db, next2(q), 1);
            else if (busy) mma_step_c<254>(accd, da, db, next2(q), 1, HI_128B - HI_64B);
            else mma_step<254>(accd, da, db, next2(q), 1);
            wg_wait<1>();
            release(empty2((q + G2_STAGES - 1) % G2_STAGES));
        };
        uint32_t shared_steps = plan_word(base, lane);
        down(5, 0, false);
#pragma unroll 1
        for (uint32_t r = 3; r < 9; r++, shared_steps >>= G2_STAGES) {
#pragma unroll
            for (int q = 0; q < G2_STAGES; q++) down(q, r & 1, shared_steps >> q & 1);
        }
        down(0, 1, false);
        down(1, 1, false, true);
        TRACE_NEXT(tile_slot);
#pragma unroll
        for (int i = 0; i < 64; i++) accs[i] = 0.f;
        uint32_t gk[32], xr[32];
        const uint32_t xs = aux + cw * 2048;
        const uint32_t xrow = xs + ((lane & 7) + ((lane >> 3) & 1) * 8) * 128;
        auto xaddr = [&](int j) { return xrow + (j >> 2) * 16384 + (((((j & 3) * 2) + (lane >> 4)) ^ (lane & 7)) << 4); };
#pragma unroll
        for (int u = G2_DSTEPS; u < G2_KSTEPS; u++) {
            const int q = u % G2_STAGES, v = u - G2_DSTEPS;
            mbar_wait(full2(q), (u / G2_STAGES) & 1, spins);
            if (wg == 1 && u == G2_KSTEPS - G2_SKEW) asm volatile("bar.sync 1, 256;" ::: "memory");
            if (u % 2) mma_step_c<2>(accs, da, db, next2(q), v);
            else mma_step<2>(accs, da, db, next2(q), v);
            if (wg == 0 && u == G2_KSTEPS - 1) asm volatile("bar.arrive 1, 256;" ::: "memory");
            if (v == TAIL_STEP) {
                TRACE_S(32, wg, 0);
                mbar_wait(dep_bar + 24, 0, spins);
                TRACE_S(33, wg, 0);
#pragma unroll
                for (int i = 0; i < 2; i++) {
                    const uint4 w = ldg_stream(prm.tail + (NGEMM + role) * 512 + i * 256 + threadIdx.x, stream_policy());
                    gk[24 + 4 * i] = w.x; gk[25 + 4 * i] = w.y; gk[26 + 4 * i] = w.z; gk[27 + 4 * i] = w.w;
                }
            }
#pragma unroll
            for (int i = 0; i < 32; i++) {
                if (v == (i < 24 ? i / 4 + 1 : TAIL_STEP + i / 4 - 3))
                    gk[i] = i < 24 ? silu2(accd[2 * i], accd[2 * i + 1])
                                   : silu2(accd[2 * i] + bf_lo(gk[i]), accd[2 * i + 1] + bf_hi(gk[i]));
            }
            if (v == XREAD_STEP) mbar_wait(x_bar, 0, spins);
            if (v >= XREAD_STEP && v < XREAD_STEP + 4) {
#pragma unroll
                for (int j = 2 * (v - XREAD_STEP); j < 2 * (v - XREAD_STEP + 1); j++)
                    asm volatile("ldmatrix.sync.aligned.m8n8.x4.shared.b16 {%0,%1,%2,%3}, [%4];"
                                 : "=r"(xr[4 * j]), "=r"(xr[4 * j + 1]), "=r"(xr[4 * j + 2]), "=r"(xr[4 * j + 3])
                                 : "r"(xaddr(j)) : "memory");
            }
            wg_wait<1>();
            if (v == 0) fence_regs(accd);
            if (u - 1 + G2_STAGES < G2_KSTEPS) release(empty2((u - 1) % G2_STAGES));
        }
        __nv_bfloat16* po = prm.pout + (row0(fresh_tid()) + (lane >> 3) * 2) * DM + nslot * 128 + 64 + (lane & 7) * 8;
        uint32_t so = xs + 16384 + (lane >> 3) * 128 + (((lane & 7) ^ (lane >> 3)) << 4);
        const int c0 = uniform(nslot * 128), c1 = uniform(row0(fresh_tid()) >> 1);
        const uint32_t xu = uniform(xs);
        asm volatile("" : "+l"(po), "+r"(so));
        wg_wait<0>();
        fence_regs(accs);
        TRACE_NEXT(tile_slot);
        TRACE_END();
#pragma unroll
        for (int j = 0; j < 8; j++) {
            uint32_t r[4];
#pragma unroll
            for (int i = 0; i < 4; i++) {
                const int e = j * 4 + i;
                asm("fma.rn.bf16x2 %0, %1, %2, %3;" : "=r"(r[i]) : "r"(pack_bf16(accs[2 * e], accs[2 * e + 1])), "r"(gk[e]), "r"(xr[e]));
            }
            asm volatile("stmatrix.sync.aligned.m8n8.x4.shared.b16 [%0], {%1,%2,%3,%4};"
                         :: "r"(xaddr(j)), "r"(r[0]), "r"(r[1]), "r"(r[2]), "r"(r[3]) : "memory");
            if (j == 3)
                asm volatile("{\n.reg .pred e;\nfence.proxy.async.shared::cta;\nbar.warp.sync 0xffffffff;\nelect.sync _|e, 0xffffffff;\n"
                    "@e cp.async.bulk.tensor.3d.global.shared::cta.bulk_group [%0, {%2, %3, %4}], [%1];\n}"
                    :: "l"(&prm.out), "r"(xu), "r"(c0), "r"(c1), "r"(wg) : "memory");
        }
        __syncwarp();
#pragma unroll
        for (int i = 0; i < 4; i++) {
            const uint4 v = lds128((so ^ (i & 1) * 64) + i * 512);
            asm volatile("st.global.v4.u32 [%0], {%1,%2,%3,%4};" :: "l"(po + i * 8 * DM), "r"(v.x), "r"(v.y), "r"(v.z), "r"(v.w) : "memory");
        }
        asm volatile("cp.async.bulk.commit_group;\ncp.async.bulk.wait_group.read 0;" ::: "memory");
        TRACE_LITE(10, clock());
        if (tid == 0) { TRACE_NEXT(tile_slot); if (wg == 1) TRACE_GT(13); TRACE_DUMP(); }
    } else if (warp > 9) {
        const int w = warp - 10;
        const bool spare = blockIdx.x >= NGEMM;
        const unsigned epoch = __ldcg(prm.epoch + blockIdx.x * 16 + (spare ? 0 : w)) + 1;
        const uint32_t tag = 1 + (epoch & 1);
        if (spare) {
#pragma unroll 1
            for (int j = 0; j < 8; j++) sts128(aux + w * 8192 + (j & 4) * 4096 + (j & 3) * 512 + lane * 16, make_uint4(0, 0, 0, 0));
            while ((uint32_t)clock() - t0 < 9000) __nanosleep(256);
        } else {
            TRACE_LITE(8, t0);
            const uint32_t at = (w ? SUM_LOAD1 : SUM_LOAD0) >> nslot * 4 & 15;
            mbar_wait(empty1(at & 3), 0);
            mbar_wait(empty1(at & 3), at >> 3);
            if (elect_one()) {
                mbar_expect_tx(cs_bar + w * 8, 16384);
                asm volatile("cp.async.bulk.tensor.2d.shared::cluster.global.mbarrier::complete_tx::bytes [%0], [%1, {%3, %5}], [%2];\n"
                    "cp.async.bulk.tensor.2d.shared::cluster.global.mbarrier::complete_tx::bytes [%0 + 8192], [%1, {%4, %5}], [%2];"
                    :: "r"(aux + w * 16384), "l"(w0), "r"(cs_bar + w * 8), "r"(nslot * 128), "r"(nslot * 128 + 64),
                       "r"(((mblk & ~1) + w) * 64) : "memory");
            }
            float cs[8];
#pragma unroll
            for (int d = 0; d < 8; d++) cs[d] = 0.f;
            const uint32_t wa = aux + w * 8192 + (lane >> 3) * 128 + (((lane & 7) ^ (lane >> 3)) << 4);
            uint4 v[8];
            auto fetch = [&](int h, uint32_t off) {
#pragma unroll
                for (int j = 0; j < 4; j++) v[h * 4 + j] = lds128((wa ^ (j & 1) * 64) + off + h * 2048 + j * 512);
            };
            auto add = [&](int h) {
#pragma unroll
                for (int j = 0; j < 4; j++) {
                    float f[8];
                    unpack8(v[h * 4 + j], f);
#pragma unroll
                    for (int d = 0; d < 8; d++) cs[d] += f[d];
                }
            };
            mbar_wait(empty1(SUM_STEP & 3), 0);
            mbar_wait(empty1(SUM_STEP & 3), SUM_STEP >> 3);
            mbar_wait(cs_bar, 0);
            fetch(0, 0);
#pragma unroll 1
            for (int i = 0; i < 4; i++) {
                fetch(1, (i >> 1) * 16384 + (i & 1) * 4096);
                add(0);
                if (i == 1) mbar_wait(cs_bar + 8, 0);
                fetch(0, (i + 1 & 2) * 8192 + (~i & 1) * 4096);
                add(1);
            }
#pragma unroll
            for (int d = 0; d < 4; d++)
                cs[d] = (lane & 16 ? cs[d + 4] : cs[d]) + __shfl_xor_sync(0xffffffffu, lane & 16 ? cs[d] : cs[d + 4], 16);
#pragma unroll
            for (int d = 0; d < 2; d++)
                cs[d] = (lane & 8 ? cs[d + 2] : cs[d]) + __shfl_xor_sync(0xffffffffu, lane & 8 ? cs[d] : cs[d + 2], 8);
            st_tagged(prm.colsum + (nslot * 2 + rank) * 1024 + (mblk >> 1) * 128 + w * 64 + (lane & 7) * 8 + (lane >> 3) * 2,
                      cs[0], cs[1], tag);
        }
        fold_operands(prm, base, spare ? 8 : nslot, spare ? blockIdx.x - NGEMM : mblk, tag, w, lane);
        if (lane == 0) {
            mbar_arrive(fold_bar);
            if (spare) {
                if (w) return;
                TRACE(60);
#pragma unroll 1
                for (int p = 0; p < 8; p++) {
                    mbar_wait(sig_bar + p * 8, 0);
                    const uint32_t pair = tail_job(blockIdx.x - NGEMM, p, lds32(base + PLAN_OFF)) / 32;
                    flag_add(offset(prm.flags, (p < 4 ? F_EARLY : F_TAIL2) * 2048 + (pair * 2 + rank) * 128));
                    TRACE_S(50, p, 3); TRACE_S(51, p, 7);
                }
                prm.epoch[blockIdx.x * 16] = epoch;
                TRACE_DUMP();
                return;
            }
            prm.epoch[blockIdx.x * 16 + w] = epoch;
            if (w == 0) {
                TRACE(35);
#pragma unroll 1
                for (uint32_t j = 0, n = 1 << 24; j < 4; n = (CNT_EARLY | CNT_LATE << 8 | 1 << 16) >> j * 8 & 255, j++) {
                    mbar_wait(sig_bar + (0xa0302820u >> j * 8 & 255), 0);
                    const uint32_t v = flag_wait(flags + (F_SHARE + j) * 512, epoch * n);
                    fence_proxy_async();
                    if (j) mbar_arrive(dep_bar + j * 8);
                    else sts32(base + PLAN_OFF, v & 0xffffff);
                }
            } else {
#pragma unroll 1
                for (int j = 0; j < 2; j++) {
                    uint8_t* const h = prm.halo + (j * NGEMM + role) * HALO_BYTES;
                    unsigned* const f = prm.flags + F_HALO * 512 + role * 32;
                    mbar_wait(sig_bar + 8 + j * 16, 0);
                    TRACE_S(38, j, 0); TRACE_S(9, j, 1);
                    asm volatile("cp.async.bulk.global.shared::cta.bulk_group [%0], [%1], %2;\n"
                        "cp.async.bulk.commit_group;\ncp.async.bulk.wait_group 0;"
                        :: "l"(h + HALO_BYTES), "r"(aux + 4 * HALO_BYTES), "n"(HALO_BYTES) : "memory");
                    fence_proxy_async();
                    TRACE_S(39, j, 0); TRACE_S(10, j, 1);
                    flag_add(f);
                    TRACE_S(40, j, 0); TRACE_S(34, j, 1);
                    if (mblk) flag_wait(f - 32, epoch * 2 - 1 + j);
                    fence_proxy_async();
                    TRACE_S(41, j, 0); TRACE_S(36, j, 1);
                    mbar_expect_tx(halo_bar, HALO_BYTES);
                    asm volatile("cp.async.bulk.shared::cluster.global.mbarrier::complete_tx::bytes [%0], [%1], %2, [%3];"
                        :: "r"(aux), "l"(mblk ? h : prm.halo), "n"(HALO_BYTES), "r"(halo_bar) : "memory");
                }
            }
        }
    } else {
#pragma unroll 1
        for (int k = 1; k < G1_STAGES; k++) {
            const uint32_t sa = base + k * G1_STAGE_BYTES;
            while ((uint32_t)clock() - t0 < (k == 3 ? PACE3 : PACE1 + (k - 1) * (PACE2 - PACE1))) {}
            load_stage1(sa, sa + A_BYTES + rank * 16384, full1(k), &prm.x, w0, w0, k * 64, k * 64, mblk * 64, nslot * 128,
                        nslot * 128 + 64, 0, stream_policy());
        }
        if (elect_one()) {
            prefetch_map(&prm.xn); prefetch_map(&prm.wqkv);
            prefetch_map(&prm.a2); prefetch_map(&prm.wo); prefetch_map(&prm.wd); prefetch_map(&prm.out);
        }
        uint32_t ph = 0;
#pragma unroll 1
        for (int t = 0; t < G1_TILES; t++) {
            const int col1 = (t == 1 ? rank * DM + nslot * 128 : gate_col(t, nslot)) + 64;
            const int col0 = t == 2 ? 2 * DM + nslot * 128 + rank * 64 : col1 - 64;
            if (t == 1) { TRACE_PUT(2, t0); TRACE(14); mbar_wait_warp(dep_bar, 0); TRACE(3); }
#pragma unroll 1
            for (int k = t ? 0 : G1_STAGES; k < G1_KSTEPS; k++) {
                const int s = k & 3;
                if (t == 1 && k == 8) mbar_wait_warp(dep_bar + 40, 0);
                mbar_wait_warp(empty1(s), ph);
                const uint32_t sa = base + s * G1_STAGE_BYTES;
                load_stage1(sa, sa + A_BYTES + rank * 16384, full1(s), t ? &prm.xn : &prm.x, t == 1 || t == 2 ? &prm.wqkv : w0,
                            t == 1 ? &prm.wqkv : w0, k * 64, t ? 0 : k * 64, t ? (mblk * G1_KSTEPS + k) * 128 : mblk * 64, col0, col1, t & 3,
                            stream_policy());
                TRACE_RING(t * 16 + k);
                if (s == 3) ph ^= 1;
            }
        }
        TRACE(4);
        mbar_wait_warp(dep_bar + 8, 0);
        TRACE(5);
        int q = 0, round = 4, own = SHARE_MAX; uint32_t ph2 = 1;
#pragma unroll 1
        for (int u = 0; u < G2_KSTEPS; u++) {
            if (u == G2_LATE) { TRACE(6); mbar_wait_warp(dep_bar + 16, 0); TRACE(7); }
            const uint32_t sa = stage2(q);
            const bool down = u < G2_DSTEPS;
            const int k = !down ? u - G2_DSTEPS : (u < 18 || u >= 40 ? own++ : (q & 1 ? u / 2 - 9 : round + (q ? q * 2 : 11)));
            mbar_wait_warp(u < G2_STAGES ? empty1((u * 2 + 1) / 3) : empty2(q), u < G2_STAGES ? ph : ph2);
            load_stage2(sa, sa + A_BYTES + rank * 8192, full2(q), &prm.a2, down ? &prm.wd : &prm.wo, 0,
                        (mblk * G2_KSTEPS + (down ? 16 : 0) + k) * 128, nslot * 128 + rank * 64, down ? 0 : k * 2, down ? k * 2 : 0, stream_policy());
            if (u == XLOAD_STEP + nslot * 2) {
                if (elect_one()) {
                    mbar_expect_tx(x_bar, 32768);
                    tma_3d(aux, &prm.x, x_bar, nslot * 128, mblk * 64, 0, stream_policy());
                    tma_3d(aux + 16384, &prm.x, x_bar, nslot * 128 + 64, mblk * 64, 0, stream_policy());
                }
                __syncwarp();
            }
            TRACE_RING(80 + u);
            if (++q == G2_STAGES) { q = 0; ph2 ^= 1; round++; }
        }
        TRACE(8);
    }
}

typedef CUresult (*EncodeFn)(CUtensorMap*, CUtensorMapDataType, cuuint32_t, void*, const cuuint64_t*, const cuuint64_t*,
                             const cuuint32_t*, const cuuint32_t*, CUtensorMapInterleave, CUtensorMapSwizzle,
                             CUtensorMapL2promotion, CUtensorMapFloatOOBfill);

void encode(EncodeFn fn, CUtensorMap* m, const void* ptr, int rank, const cuuint64_t* dims, const cuuint64_t* strides,
            const cuuint32_t* box, bool swizzle = true) {
    const cuuint32_t es[5] = {1, 1, 1, 1, 1};
    fn(m, CU_TENSOR_MAP_DATA_TYPE_BFLOAT16, rank, const_cast<void*>(ptr), dims, strides, box, es,
       CU_TENSOR_MAP_INTERLEAVE_NONE, !swizzle ? CU_TENSOR_MAP_SWIZZLE_NONE : box[0] == 32 ? CU_TENSOR_MAP_SWIZZLE_64B : CU_TENSOR_MAP_SWIZZLE_128B,
       CU_TENSOR_MAP_L2_PROMOTION_L2_128B, CU_TENSOR_MAP_FLOAT_OOB_FILL_NONE);
}
void encode_rows(EncodeFn fn, CUtensorMap* m, const void* ptr, int cols, int box_rows, int box_parity) {
    const cuuint64_t dims[3] = {(cuuint64_t)cols, SEQ / 2, 2}, strides[2] = {(cuuint64_t)cols * 4, (cuuint64_t)cols * 2};
    const cuuint32_t box[3] = {64, (cuuint32_t)box_rows, (cuuint32_t)box_parity};
    encode(fn, m, ptr, 3, dims, strides, box);
}
void encode_images(EncodeFn fn, CUtensorMap* m, const void* ptr, int cols) {
    const cuuint64_t dims[3] = {64, (cuuint64_t)SEQ * cols / 64 - 64, 2}, strides[2] = {128, 8192};
    const cuuint32_t box[3] = {64, 64, 2};
    encode(fn, m, ptr, 3, dims, strides, box, false);
}
void encode_w1(EncodeFn fn, CUtensorMap* m, const void* ptr, int cols) {
    const cuuint64_t dims[2] = {(cuuint64_t)cols, DM}, strides[1] = {(cuuint64_t)cols * 2};
    const cuuint32_t box[2] = {64, 64};
    encode(fn, m, ptr, 2, dims, strides, box);
}
void encode_tail(EncodeFn fn, CUtensorMap* m, const void* ptr, int rows, int cols, int n) {
    const cuuint64_t rb = cols * 2;
    const cuuint64_t dims[5] = {32, (cuuint64_t)n, (cuuint64_t)rows / (4 * n), 4, 8}, strides[4] = {rb, 4 * n * rb, n * rb, 256};
    const cuuint32_t box[5] = {32, (cuuint32_t)n, 16 / (cuuint32_t)n, 4, 4};
    encode(fn, m, (const __nv_bfloat16*)ptr + cols - 1024 + 96, 5, dims, strides, box);
}
void encode_w2(EncodeFn fn, CUtensorMap* m, const void* ptr, int rows) {
    const cuuint64_t rb = DM * 2;
    const cuuint64_t dims[5] = {DM, 2, 4, 4, (cuuint64_t)rows / 32}, strides[4] = {rb, 8 * rb, 2 * rb, 32 * rb};
    const cuuint32_t box[5] = {64, 2, 4, 4, 2};
    encode(fn, m, ptr, 5, dims, strides, box);
}
void encode_wo(EncodeFn fn, CUtensorMap* m, const void* ptr) {
    const cuuint64_t rb = DM * 2;
    const cuuint64_t dims[5] = {DM, 4, DM / 32, 2, 4}, strides[4] = {8 * rb, 32 * rb, rb, 2 * rb};
    const cuuint32_t box[5] = {64, 4, 2, 2, 4};
    encode(fn, m, ptr, 5, dims, strides, box);
}

}

extern "C" void kernel_launch(void* const* d_in, const int* in_sizes, int n_in, void* d_out, int out_size) {
    (void)in_sizes; (void)n_in; (void)out_size;
    static EncodeFn fn = nullptr;
    static Params prm;
    if (!fn) {
        cudaDriverEntryPointQueryResult st;
        cudaGetDriverEntryPoint("cuTensorMapEncodeTiled", (void**)&fn, cudaEnableDefault, &st);
        cudaGetSymbolAddress((void**)&prm.pxn, g_xn);
        cudaGetSymbolAddress((void**)&prm.pa2, g_a2);
        cudaGetSymbolAddress((void**)&prm.tail, g_tail);
        cudaGetSymbolAddress((void**)&prm.halo, g_halo);
        cudaGetSymbolAddress((void**)&prm.stats, g_stats);
        cudaGetSymbolAddress((void**)&prm.colsum, g_colsum);
        cudaGetSymbolAddress((void**)&prm.flags, g_flags);
        cudaGetSymbolAddress((void**)&prm.epoch, g_epoch);
        cudaFuncSetAttribute(fused_kernel, cudaFuncAttributeMaxDynamicSharedMemorySize, SMEM_BYTES);
    }
    encode_rows(fn, &prm.x, d_in[0], DM, 64, 2);
    encode_images(fn, &prm.xn, prm.pxn, DM);
    encode_images(fn, &prm.a2, prm.pa2, K2);
    encode_rows(fn, &prm.out, d_out, DM, 16, 1);
    encode_w1(fn, &prm.wqkv, d_in[1], NQKV);
    encode_w1(fn, &prm.wg, d_in[4], DF);
    encode_w1(fn, &prm.wu, d_in[5], DF);
    encode_tail(fn, &prm.wu_tail, d_in[5], DM, DF, 8);
    encode_tail(fn, &prm.wd_tail, d_in[6], DF, DM, 2);
    encode_wo(fn, &prm.wo, d_in[2]);
    encode_w2(fn, &prm.wd, d_in[6], DF);
    prm.hi[0] = prm.hi[1] = HI_128B;
    prm.px = (const __nv_bfloat16*)d_in[0];
    prm.pwu = (const __nv_bfloat16*)d_in[5];
    prm.pout = (__nv_bfloat16*)d_out;
    fused_kernel<<<NCTA, 384, SMEM_BYTES>>>(prm);
}
```
